```python
import torch

def _softmax(x, axis=-1):
    return torch.softmax(x, dim=axis)
def _gelu(x):
    return torch.nn.functional.gelu(x, approximate="tanh")
def _silu(x):
    return torch.nn.functional.silu(x)
def _sigmoid(x):
    return torch.sigmoid(x)
def _layernorm(x, axis=-1, eps=1e-5):
    m = x.mean(dim=axis, keepdim=True)
    v = x.var(dim=axis, keepdim=True, unbiased=False)
    return (x - m) / torch.sqrt(v + eps)
def _scatter_add(tgt, idx, src, axis=0):
    return tgt.clone().index_add_(axis, idx, src)
def _segment_sum(src, seg, n):
    out = torch.zeros((n,) + src.shape[1:], dtype=src.dtype)
    return out.index_add_(0, seg, src)
def _pad(x, pw):
    flat = tuple(v for pair in reversed(pw) for v in pair)
    return torch.nn.functional.pad(x, flat)

kernel_name = 'concat_heads__mha_block_cached__mha_block_cached__near_ridge'

def setup_inputs():

    _w = (lambda a: (lambda t: t.to(torch.bfloat16) if t.is_floating_point() else t)(torch.as_tensor(a)))
    def _A_setup():
        B, Sq, D = 16, 224, 640
        H, Sk, Dh = 32, 1024, 128
        return {
            "x": _w((lambda *s: torch.randn(*s, dtype=torch.bfloat16) * 0.8)(B, Sq, D)),
            "k_cache": _w((lambda *s: torch.randn(*s, dtype=torch.bfloat16) * 0.8)(B, H, Sk, Dh)),
            "v_cache": _w((lambda *s: torch.randn(*s, dtype=torch.bfloat16) * 0.05)(B, H, Sk, Dh)),
            "wq": _w((lambda *s: torch.randn(*s, dtype=torch.bfloat16) * 0.8)(D, H * Dh) * (D ** -0.5)),
            "wo": _w((lambda *s: torch.randn(*s, dtype=torch.bfloat16) * 0.05)(H * Dh, D) * ((H * Dh) ** -0.5)),
        }
    _A_in = _A_setup()

    def _B_setup():
        B, Sq, D = 16, 224, 640
        H, Sk, Dh = 32, 1024, 128
        return {
            "x": _w((lambda *s: torch.randn(*s, dtype=torch.bfloat16) * 0.8)(B, Sq, D)),
            "k_cache": _w((lambda *s: torch.randn(*s, dtype=torch.bfloat16) * 0.8)(B, H, Sk, Dh)),
            "v_cache": _w((lambda *s: torch.randn(*s, dtype=torch.bfloat16) * 0.05)(B, H, Sk, Dh)),
            "wq": _w((lambda *s: torch.randn(*s, dtype=torch.bfloat16) * 0.8)(D, H * Dh) * (D ** -0.5)),
            "wo": _w((lambda *s: torch.randn(*s, dtype=torch.bfloat16) * 0.05)(H * Dh, D) * ((H * Dh) ** -0.5)),
        }
    _B_in = _B_setup()

    return {
        "A_x": _A_in["x"],
        "A_k_cache": _A_in["k_cache"],
        "A_v_cache": _A_in["v_cache"],
        "A_wq": _A_in["wq"],
        "A_wo": _A_in["wo"],
        "B_x": _B_in["x"],
        "B_k_cache": _B_in["k_cache"],
        "B_v_cache": _B_in["v_cache"],
        "B_wq": _B_in["wq"],
        "B_wo": _B_in["wo"],
    }

def reference(A_x, A_k_cache, A_v_cache, A_wq, A_wo, B_x, B_k_cache, B_v_cache, B_wq, B_wo):
    def _A_ref(x, k_cache, v_cache, wq, wo):
        B, Sq, D = x.shape
        H, Dh = 32, 128
        q = (lambda x, *d: x.permute(*d))((x @ wq).reshape(B, Sq, H, Dh), 0, 2, 1, 3)
        scores = torch.einsum("bhqd,bhkd->bhqk", q, k_cache) * (Dh ** -0.5)
        p = _softmax(scores, axis=-1)
        o = torch.einsum("bhqk,bhkd->bhqd", p, v_cache)
        return (lambda x, *d: x.permute(*d))(o, 0, 2, 1, 3).reshape(B, Sq, H * Dh) @ wo

    def _B_ref(x, k_cache, v_cache, wq, wo):
        B, Sq, D = x.shape
        H, Dh = 32, 128
        q = (lambda x, *d: x.permute(*d))((x @ wq).reshape(B, Sq, H, Dh), 0, 2, 1, 3)
        scores = torch.einsum("bhqd,bhkd->bhqk", q, k_cache) * (Dh ** -0.5)
        p = _softmax(scores, axis=-1)
        o = torch.einsum("bhqk,bhkd->bhqd", p, v_cache)
        return (lambda x, *d: x.permute(*d))(o, 0, 2, 1, 3).reshape(B, Sq, H * Dh) @ wo

    a = _A_ref(A_x, A_k_cache, A_v_cache, A_wq, A_wo)
    b = _B_ref(B_x, B_k_cache, B_v_cache, B_wq, B_wo)
    return torch.concatenate([a, b], axis=-1)
```

```cpp
#include <cuda_runtime.h>
#include <cuda_bf16.h>
#include <cuda.h>
#include <stdint.h>

namespace {

__device__ __forceinline__ void wgmma_proj(float (&d)[64], uint64_t da, uint64_t db, int scaleD) {
  asm volatile("{\n.reg .pred p;\nsetp.ne.b32 p, %66, 0;\n"
      "wgmma.mma_async.sync.aligned.m64n128k16.f32.bf16.bf16 "
      "{%0, %1, %2, %3, %4, %5, %6, %7, %8, %9, %10, %11, %12, %13, %14, %15, %16, %17, %18, %19, %20, %21, %22, %23, %24, %25, %26, %27, %28, %29, %30, "
      "%31, %32, %33, %34, %35, %36, %37, %38, %39, %40, %41, %42, %43, %44, %45, %46, %47, %48, %49, %50, %51, %52, %53, %54, %55, %56, %57, %58, %59, %60, "
      "%61, %62, %63}, "
      "%64, %65, p, 1, 1, 1, 0;\n}\n"
      : "+f"(d[0]), "+f"(d[1]), "+f"(d[2]), "+f"(d[3]), "+f"(d[4]), "+f"(d[5]), "+f"(d[6]), "+f"(d[7]), "+f"(d[8]), "+f"(d[9]), "+f"(d[10]), "+f"(d[11]),
        "+f"(d[12]), "+f"(d[13]), "+f"(d[14]), "+f"(d[15]), "+f"(d[16]), "+f"(d[17]), "+f"(d[18]), "+f"(d[19]), "+f"(d[20]), "+f"(d[21]), "+f"(d[22]),
        "+f"(d[23]), "+f"(d[24]), "+f"(d[25]), "+f"(d[26]), "+f"(d[27]), "+f"(d[28]), "+f"(d[29]), "+f"(d[30]), "+f"(d[31]), "+f"(d[32]), "+f"(d[33]),
        "+f"(d[34]), "+f"(d[35]), "+f"(d[36]), "+f"(d[37]), "+f"(d[38]), "+f"(d[39]), "+f"(d[40]), "+f"(d[41]), "+f"(d[42]), "+f"(d[43]), "+f"(d[44]),
        "+f"(d[45]), "+f"(d[46]), "+f"(d[47]), "+f"(d[48]), "+f"(d[49]), "+f"(d[50]), "+f"(d[51]), "+f"(d[52]), "+f"(d[53]), "+f"(d[54]), "+f"(d[55]),
        "+f"(d[56]), "+f"(d[57]), "+f"(d[58]), "+f"(d[59]), "+f"(d[60]), "+f"(d[61]), "+f"(d[62]), "+f"(d[63])
      : "l"(da), "l"(db), "r"(scaleD));
}
__device__ __forceinline__ void wgmma_proj(float (&d)[48], uint64_t da, uint64_t db, int scaleD) {
  asm volatile("{\n.reg .pred p;\nsetp.ne.b32 p, %50, 0;\n"
      "wgmma.mma_async.sync.aligned.m64n96k16.f32.bf16.bf16 "
      "{%0, %1, %2, %3, %4, %5, %6, %7, %8, %9, %10, %11, %12, %13, %14, %15, %16, %17, %18, %19, %20, %21, %22, %23, %24, %25, %26, %27, %28, %29, %30, "
      "%31, %32, %33, %34, %35, %36, %37, %38, %39, %40, %41, %42, %43, %44, %45, %46, %47}, "
      "%48, %49, p, 1, 1, 1, 0;\n}\n"
      : "+f"(d[0]), "+f"(d[1]), "+f"(d[2]), "+f"(d[3]), "+f"(d[4]), "+f"(d[5]), "+f"(d[6]), "+f"(d[7]), "+f"(d[8]), "+f"(d[9]), "+f"(d[10]), "+f"(d[11]),
        "+f"(d[12]), "+f"(d[13]), "+f"(d[14]), "+f"(d[15]), "+f"(d[16]), "+f"(d[17]), "+f"(d[18]), "+f"(d[19]), "+f"(d[20]), "+f"(d[21]), "+f"(d[22]),
        "+f"(d[23]), "+f"(d[24]), "+f"(d[25]), "+f"(d[26]), "+f"(d[27]), "+f"(d[28]), "+f"(d[29]), "+f"(d[30]), "+f"(d[31]), "+f"(d[32]), "+f"(d[33]),
        "+f"(d[34]), "+f"(d[35]), "+f"(d[36]), "+f"(d[37]), "+f"(d[38]), "+f"(d[39]), "+f"(d[40]), "+f"(d[41]), "+f"(d[42]), "+f"(d[43]), "+f"(d[44]),
        "+f"(d[45]), "+f"(d[46]), "+f"(d[47])
      : "l"(da), "l"(db), "r"(scaleD));
}
__device__ __forceinline__ void wgmma_qk(float (&d)[32], uint64_t da, uint64_t db, int scaleD) {
  asm volatile("{\n.reg .pred p;\nsetp.ne.b32 p, %34, 0;\n"
      "wgmma.mma_async.sync.aligned.m64n64k16.f32.bf16.bf16 "
      "{%0, %1, %2, %3, %4, %5, %6, %7, %8, %9, %10, %11, %12, %13, %14, %15, %16, %17, %18, %19, %20, %21, %22, %23, %24, %25, %26, %27, %28, %29, %30, "
      "%31}, "
      "%32, %33, p, 1, 1, 0, 0;\n}\n"
      : "+f"(d[0]), "+f"(d[1]), "+f"(d[2]), "+f"(d[3]), "+f"(d[4]), "+f"(d[5]), "+f"(d[6]), "+f"(d[7]), "+f"(d[8]), "+f"(d[9]), "+f"(d[10]), "+f"(d[11]),
        "+f"(d[12]), "+f"(d[13]), "+f"(d[14]), "+f"(d[15]), "+f"(d[16]), "+f"(d[17]), "+f"(d[18]), "+f"(d[19]), "+f"(d[20]), "+f"(d[21]), "+f"(d[22]),
        "+f"(d[23]), "+f"(d[24]), "+f"(d[25]), "+f"(d[26]), "+f"(d[27]), "+f"(d[28]), "+f"(d[29]), "+f"(d[30]), "+f"(d[31])
      : "l"(da), "l"(db), "r"(scaleD));
}
__device__ __forceinline__ void wgmma_pv(float (&d)[64], uint32_t a0, uint32_t a1, uint32_t a2, uint32_t a3, uint64_t db, int scaleD) {
  asm volatile("{\n.reg .pred p;\nsetp.ne.b32 p, %69, 0;\n"
      "wgmma.mma_async.sync.aligned.m64n128k16.f32.bf16.bf16 "
      "{%0, %1, %2, %3, %4, %5, %6, %7, %8, %9, %10, %11, %12, %13, %14, %15, %16, %17, %18, %19, %20, %21, %22, %23, %24, %25, %26, %27, %28, %29, %30, "
      "%31, %32, %33, %34, %35, %36, %37, %38, %39, %40, %41, %42, %43, %44, %45, %46, %47, %48, %49, %50, %51, %52, %53, %54, %55, %56, %57, %58, %59, %60, "
      "%61, %62, %63}, "
      "{%64, %65, %66, %67}, %68, p, 1, 1, 1;\n}\n"
      : "+f"(d[0]), "+f"(d[1]), "+f"(d[2]), "+f"(d[3]), "+f"(d[4]), "+f"(d[5]), "+f"(d[6]), "+f"(d[7]), "+f"(d[8]), "+f"(d[9]), "+f"(d[10]), "+f"(d[11]),
        "+f"(d[12]), "+f"(d[13]), "+f"(d[14]), "+f"(d[15]), "+f"(d[16]), "+f"(d[17]), "+f"(d[18]), "+f"(d[19]), "+f"(d[20]), "+f"(d[21]), "+f"(d[22]),
        "+f"(d[23]), "+f"(d[24]), "+f"(d[25]), "+f"(d[26]), "+f"(d[27]), "+f"(d[28]), "+f"(d[29]), "+f"(d[30]), "+f"(d[31]), "+f"(d[32]), "+f"(d[33]),
        "+f"(d[34]), "+f"(d[35]), "+f"(d[36]), "+f"(d[37]), "+f"(d[38]), "+f"(d[39]), "+f"(d[40]), "+f"(d[41]), "+f"(d[42]), "+f"(d[43]), "+f"(d[44]),
        "+f"(d[45]), "+f"(d[46]), "+f"(d[47]), "+f"(d[48]), "+f"(d[49]), "+f"(d[50]), "+f"(d[51]), "+f"(d[52]), "+f"(d[53]), "+f"(d[54]), "+f"(d[55]),
        "+f"(d[56]), "+f"(d[57]), "+f"(d[58]), "+f"(d[59]), "+f"(d[60]), "+f"(d[61]), "+f"(d[62]), "+f"(d[63])
      : "r"(a0), "r"(a1), "r"(a2), "r"(a3), "l"(db), "r"(scaleD));
}
__device__ __forceinline__ void wgmma_qk_sp(float (&d)[32], uint32_t a0, uint32_t a1, uint32_t a2, uint32_t a3, uint64_t db, int scaleD, uint32_t meta) {
  asm volatile("{\n.reg .pred p;\nsetp.ne.b32 p, %37, 0;\n"
      "wgmma.mma_async.sp.sync.aligned.m64n64k32.f32.bf16.bf16 "
      "{%0, %1, %2, %3, %4, %5, %6, %7, %8, %9, %10, %11, %12, %13, %14, %15, %16, %17, %18, %19, %20, %21, %22, %23, %24, %25, %26, %27, %28, %29, %30, "
      "%31}, "
      "{%32, %33, %34, %35}, %36, %38, 0, p, 1, 1, 0;\n}\n"
      : "+f"(d[0]), "+f"(d[1]), "+f"(d[2]), "+f"(d[3]), "+f"(d[4]), "+f"(d[5]), "+f"(d[6]), "+f"(d[7]), "+f"(d[8]), "+f"(d[9]), "+f"(d[10]), "+f"(d[11]),
        "+f"(d[12]), "+f"(d[13]), "+f"(d[14]), "+f"(d[15]), "+f"(d[16]), "+f"(d[17]), "+f"(d[18]), "+f"(d[19]), "+f"(d[20]), "+f"(d[21]), "+f"(d[22]),
        "+f"(d[23]), "+f"(d[24]), "+f"(d[25]), "+f"(d[26]), "+f"(d[27]), "+f"(d[28]), "+f"(d[29]), "+f"(d[30]), "+f"(d[31])
      : "r"(a0), "r"(a1), "r"(a2), "r"(a3), "l"(db), "r"(scaleD), "r"(meta));
}
__device__ __forceinline__ void wgmma_pv_sp(float (&d)[64], uint32_t a0, uint32_t a1, uint32_t a2, uint32_t a3, uint64_t db, int scaleD, uint32_t meta) {
  asm volatile("{\n.reg .pred p;\nsetp.ne.b32 p, %69, 0;\n"
      "wgmma.mma_async.sp.sync.aligned.m64n128k32.f32.bf16.bf16 "
      "{%0, %1, %2, %3, %4, %5, %6, %7, %8, %9, %10, %11, %12, %13, %14, %15, %16, %17, %18, %19, %20, %21, %22, %23, %24, %25, %26, %27, %28, %29, %30, "
      "%31, %32, %33, %34, %35, %36, %37, %38, %39, %40, %41, %42, %43, %44, %45, %46, %47, %48, %49, %50, %51, %52, %53, %54, %55, %56, %57, %58, %59, %60, "
      "%61, %62, %63}, "
      "{%64, %65, %66, %67}, %68, %70, 0, p, 1, 1, 1;\n}\n"
      : "+f"(d[0]), "+f"(d[1]), "+f"(d[2]), "+f"(d[3]), "+f"(d[4]), "+f"(d[5]), "+f"(d[6]), "+f"(d[7]), "+f"(d[8]), "+f"(d[9]), "+f"(d[10]), "+f"(d[11]),
        "+f"(d[12]), "+f"(d[13]), "+f"(d[14]), "+f"(d[15]), "+f"(d[16]), "+f"(d[17]), "+f"(d[18]), "+f"(d[19]), "+f"(d[20]), "+f"(d[21]), "+f"(d[22]),
        "+f"(d[23]), "+f"(d[24]), "+f"(d[25]), "+f"(d[26]), "+f"(d[27]), "+f"(d[28]), "+f"(d[29]), "+f"(d[30]), "+f"(d[31]), "+f"(d[32]), "+f"(d[33]),
        "+f"(d[34]), "+f"(d[35]), "+f"(d[36]), "+f"(d[37]), "+f"(d[38]), "+f"(d[39]), "+f"(d[40]), "+f"(d[41]), "+f"(d[42]), "+f"(d[43]), "+f"(d[44]),
        "+f"(d[45]), "+f"(d[46]), "+f"(d[47]), "+f"(d[48]), "+f"(d[49]), "+f"(d[50]), "+f"(d[51]), "+f"(d[52]), "+f"(d[53]), "+f"(d[54]), "+f"(d[55]),
        "+f"(d[56]), "+f"(d[57]), "+f"(d[58]), "+f"(d[59]), "+f"(d[60]), "+f"(d[61]), "+f"(d[62]), "+f"(d[63])
      : "r"(a0), "r"(a1), "r"(a2), "r"(a3), "l"(db), "r"(scaleD), "r"(meta));
}
__device__ __forceinline__ void wgmma_proj_init(float (&d)[64], uint64_t da, uint64_t db, int scaleD) {
  asm volatile("{\n.reg .pred p;\nsetp.ne.b32 p, %66, 0;\n"
      "wgmma.mma_async.sync.aligned.m64n128k16.f32.bf16.bf16 "
      "{%0, %1, %2, %3, %4, %5, %6, %7, %8, %9, %10, %11, %12, %13, %14, %15, %16, %17, %18, %19, %20, %21, %22, %23, %24, %25, %26, %27, %28, %29, %30, "
      "%31, %32, %33, %34, %35, %36, %37, %38, %39, %40, %41, %42, %43, %44, %45, %46, %47, %48, %49, %50, %51, %52, %53, %54, %55, %56, %57, %58, %59, %60, "
      "%61, %62, %63}, "
      "%64, %65, p, 1, 1, 1, 0;\n}\n"
      : "=f"(d[0]), "=f"(d[1]), "=f"(d[2]), "=f"(d[3]), "=f"(d[4]), "=f"(d[5]), "=f"(d[6]), "=f"(d[7]), "=f"(d[8]), "=f"(d[9]), "=f"(d[10]), "=f"(d[11]),
        "=f"(d[12]), "=f"(d[13]), "=f"(d[14]), "=f"(d[15]), "=f"(d[16]), "=f"(d[17]), "=f"(d[18]), "=f"(d[19]), "=f"(d[20]), "=f"(d[21]), "=f"(d[22]),
        "=f"(d[23]), "=f"(d[24]), "=f"(d[25]), "=f"(d[26]), "=f"(d[27]), "=f"(d[28]), "=f"(d[29]), "=f"(d[30]), "=f"(d[31]), "=f"(d[32]), "=f"(d[33]),
        "=f"(d[34]), "=f"(d[35]), "=f"(d[36]), "=f"(d[37]), "=f"(d[38]), "=f"(d[39]), "=f"(d[40]), "=f"(d[41]), "=f"(d[42]), "=f"(d[43]), "=f"(d[44]),
        "=f"(d[45]), "=f"(d[46]), "=f"(d[47]), "=f"(d[48]), "=f"(d[49]), "=f"(d[50]), "=f"(d[51]), "=f"(d[52]), "=f"(d[53]), "=f"(d[54]), "=f"(d[55]),
        "=f"(d[56]), "=f"(d[57]), "=f"(d[58]), "=f"(d[59]), "=f"(d[60]), "=f"(d[61]), "=f"(d[62]), "=f"(d[63])
      : "l"(da), "l"(db), "r"(scaleD));
}
__device__ __forceinline__ void wgmma_proj_init(float (&d)[48], uint64_t da, uint64_t db, int scaleD) {
  asm volatile("{\n.reg .pred p;\nsetp.ne.b32 p, %50, 0;\n"
      "wgmma.mma_async.sync.aligned.m64n96k16.f32.bf16.bf16 "
      "{%0, %1, %2, %3, %4, %5, %6, %7, %8, %9, %10, %11, %12, %13, %14, %15, %16, %17, %18, %19, %20, %21, %22, %23, %24, %25, %26, %27, %28, %29, %30, "
      "%31, %32, %33, %34, %35, %36, %37, %38, %39, %40, %41, %42, %43, %44, %45, %46, %47}, "
      "%48, %49, p, 1, 1, 1, 0;\n}\n"
      : "=f"(d[0]), "=f"(d[1]), "=f"(d[2]), "=f"(d[3]), "=f"(d[4]), "=f"(d[5]), "=f"(d[6]), "=f"(d[7]), "=f"(d[8]), "=f"(d[9]), "=f"(d[10]), "=f"(d[11]),
        "=f"(d[12]), "=f"(d[13]), "=f"(d[14]), "=f"(d[15]), "=f"(d[16]), "=f"(d[17]), "=f"(d[18]), "=f"(d[19]), "=f"(d[20]), "=f"(d[21]), "=f"(d[22]),
        "=f"(d[23]), "=f"(d[24]), "=f"(d[25]), "=f"(d[26]), "=f"(d[27]), "=f"(d[28]), "=f"(d[29]), "=f"(d[30]), "=f"(d[31]), "=f"(d[32]), "=f"(d[33]),
        "=f"(d[34]), "=f"(d[35]), "=f"(d[36]), "=f"(d[37]), "=f"(d[38]), "=f"(d[39]), "=f"(d[40]), "=f"(d[41]), "=f"(d[42]), "=f"(d[43]), "=f"(d[44]),
        "=f"(d[45]), "=f"(d[46]), "=f"(d[47])
      : "l"(da), "l"(db), "r"(scaleD));
}
__device__ __forceinline__ void wgmma_qk_init(float (&d)[32], uint64_t da, uint64_t db, int scaleD) {
  asm volatile("{\n.reg .pred p;\nsetp.ne.b32 p, %34, 0;\n"
      "wgmma.mma_async.sync.aligned.m64n64k16.f32.bf16.bf16 "
      "{%0, %1, %2, %3, %4, %5, %6, %7, %8, %9, %10, %11, %12, %13, %14, %15, %16, %17, %18, %19, %20, %21, %22, %23, %24, %25, %26, %27, %28, %29, %30, "
      "%31}, "
      "%32, %33, p, 1, 1, 0, 0;\n}\n"
      : "=f"(d[0]), "=f"(d[1]), "=f"(d[2]), "=f"(d[3]), "=f"(d[4]), "=f"(d[5]), "=f"(d[6]), "=f"(d[7]), "=f"(d[8]), "=f"(d[9]), "=f"(d[10]), "=f"(d[11]),
        "=f"(d[12]), "=f"(d[13]), "=f"(d[14]), "=f"(d[15]), "=f"(d[16]), "=f"(d[17]), "=f"(d[18]), "=f"(d[19]), "=f"(d[20]), "=f"(d[21]), "=f"(d[22]),
        "=f"(d[23]), "=f"(d[24]), "=f"(d[25]), "=f"(d[26]), "=f"(d[27]), "=f"(d[28]), "=f"(d[29]), "=f"(d[30]), "=f"(d[31])
      : "l"(da), "l"(db), "r"(scaleD));
}
__device__ __forceinline__ void wgmma_pv_init(float (&d)[64], uint32_t a0, uint32_t a1, uint32_t a2, uint32_t a3, uint64_t db, int scaleD) {
  asm volatile("{\n.reg .pred p;\nsetp.ne.b32 p, %69, 0;\n"
      "wgmma.mma_async.sync.aligned.m64n128k16.f32.bf16.bf16 "
      "{%0, %1, %2, %3, %4, %5, %6, %7, %8, %9, %10, %11, %12, %13, %14, %15, %16, %17, %18, %19, %20, %21, %22, %23, %24, %25, %26, %27, %28, %29, %30, "
      "%31, %32, %33, %34, %35, %36, %37, %38, %39, %40, %41, %42, %43, %44, %45, %46, %47, %48, %49, %50, %51, %52, %53, %54, %55, %56, %57, %58, %59, %60, "
      "%61, %62, %63}, "
      "{%64, %65, %66, %67}, %68, p, 1, 1, 1;\n}\n"
      : "=f"(d[0]), "=f"(d[1]), "=f"(d[2]), "=f"(d[3]), "=f"(d[4]), "=f"(d[5]), "=f"(d[6]), "=f"(d[7]), "=f"(d[8]), "=f"(d[9]), "=f"(d[10]), "=f"(d[11]),
        "=f"(d[12]), "=f"(d[13]), "=f"(d[14]), "=f"(d[15]), "=f"(d[16]), "=f"(d[17]), "=f"(d[18]), "=f"(d[19]), "=f"(d[20]), "=f"(d[21]), "=f"(d[22]),
        "=f"(d[23]), "=f"(d[24]), "=f"(d[25]), "=f"(d[26]), "=f"(d[27]), "=f"(d[28]), "=f"(d[29]), "=f"(d[30]), "=f"(d[31]), "=f"(d[32]), "=f"(d[33]),
        "=f"(d[34]), "=f"(d[35]), "=f"(d[36]), "=f"(d[37]), "=f"(d[38]), "=f"(d[39]), "=f"(d[40]), "=f"(d[41]), "=f"(d[42]), "=f"(d[43]), "=f"(d[44]),
        "=f"(d[45]), "=f"(d[46]), "=f"(d[47]), "=f"(d[48]), "=f"(d[49]), "=f"(d[50]), "=f"(d[51]), "=f"(d[52]), "=f"(d[53]), "=f"(d[54]), "=f"(d[55]),
        "=f"(d[56]), "=f"(d[57]), "=f"(d[58]), "=f"(d[59]), "=f"(d[60]), "=f"(d[61]), "=f"(d[62]), "=f"(d[63])
      : "r"(a0), "r"(a1), "r"(a2), "r"(a3), "l"(db), "r"(scaleD));
}
__device__ __forceinline__ void wgmma_qk_sp_init(float (&d)[32], uint32_t a0, uint32_t a1, uint32_t a2, uint32_t a3, uint64_t db, int scaleD, uint32_t meta) {
  asm volatile("{\n.reg .pred p;\nsetp.ne.b32 p, %37, 0;\n"
      "wgmma.mma_async.sp.sync.aligned.m64n64k32.f32.bf16.bf16 "
      "{%0, %1, %2, %3, %4, %5, %6, %7, %8, %9, %10, %11, %12, %13, %14, %15, %16, %17, %18, %19, %20, %21, %22, %23, %24, %25, %26, %27, %28, %29, %30, "
      "%31}, "
      "{%32, %33, %34, %35}, %36, %38, 0, p, 1, 1, 0;\n}\n"
      : "=f"(d[0]), "=f"(d[1]), "=f"(d[2]), "=f"(d[3]), "=f"(d[4]), "=f"(d[5]), "=f"(d[6]), "=f"(d[7]), "=f"(d[8]), "=f"(d[9]), "=f"(d[10]), "=f"(d[11]),
        "=f"(d[12]), "=f"(d[13]), "=f"(d[14]), "=f"(d[15]), "=f"(d[16]), "=f"(d[17]), "=f"(d[18]), "=f"(d[19]), "=f"(d[20]), "=f"(d[21]), "=f"(d[22]),
        "=f"(d[23]), "=f"(d[24]), "=f"(d[25]), "=f"(d[26]), "=f"(d[27]), "=f"(d[28]), "=f"(d[29]), "=f"(d[30]), "=f"(d[31])
      : "r"(a0), "r"(a1), "r"(a2), "r"(a3), "l"(db), "r"(scaleD), "r"(meta));
}
__device__ __forceinline__ void wgmma_pv_sp_init(float (&d)[64], uint32_t a0, uint32_t a1, uint32_t a2, uint32_t a3, uint64_t db, int scaleD, uint32_t meta) {
  asm volatile("{\n.reg .pred p;\nsetp.ne.b32 p, %69, 0;\n"
      "wgmma.mma_async.sp.sync.aligned.m64n128k32.f32.bf16.bf16 "
      "{%0, %1, %2, %3, %4, %5, %6, %7, %8, %9, %10, %11, %12, %13, %14, %15, %16, %17, %18, %19, %20, %21, %22, %23, %24, %25, %26, %27, %28, %29, %30, "
      "%31, %32, %33, %34, %35, %36, %37, %38, %39, %40, %41, %42, %43, %44, %45, %46, %47, %48, %49, %50, %51, %52, %53, %54, %55, %56, %57, %58, %59, %60, "
      "%61, %62, %63}, "
      "{%64, %65, %66, %67}, %68, %70, 0, p, 1, 1, 1;\n}\n"
      : "=f"(d[0]), "=f"(d[1]), "=f"(d[2]), "=f"(d[3]), "=f"(d[4]), "=f"(d[5]), "=f"(d[6]), "=f"(d[7]), "=f"(d[8]), "=f"(d[9]), "=f"(d[10]), "=f"(d[11]),
        "=f"(d[12]), "=f"(d[13]), "=f"(d[14]), "=f"(d[15]), "=f"(d[16]), "=f"(d[17]), "=f"(d[18]), "=f"(d[19]), "=f"(d[20]), "=f"(d[21]), "=f"(d[22]),
        "=f"(d[23]), "=f"(d[24]), "=f"(d[25]), "=f"(d[26]), "=f"(d[27]), "=f"(d[28]), "=f"(d[29]), "=f"(d[30]), "=f"(d[31]), "=f"(d[32]), "=f"(d[33]),
        "=f"(d[34]), "=f"(d[35]), "=f"(d[36]), "=f"(d[37]), "=f"(d[38]), "=f"(d[39]), "=f"(d[40]), "=f"(d[41]), "=f"(d[42]), "=f"(d[43]), "=f"(d[44]),
        "=f"(d[45]), "=f"(d[46]), "=f"(d[47]), "=f"(d[48]), "=f"(d[49]), "=f"(d[50]), "=f"(d[51]), "=f"(d[52]), "=f"(d[53]), "=f"(d[54]), "=f"(d[55]),
        "=f"(d[56]), "=f"(d[57]), "=f"(d[58]), "=f"(d[59]), "=f"(d[60]), "=f"(d[61]), "=f"(d[62]), "=f"(d[63])
      : "r"(a0), "r"(a1), "r"(a2), "r"(a3), "l"(db), "r"(scaleD), "r"(meta));
}

constexpr int NB = 16, SQ = 224, DM = 640, NH = 32, SK = 1024, DH = 128;
constexpr int HD = NH * DH;
constexpr int NBETA = 2 * NB;
constexpr int NCTA = 132;
constexpr int NS = 10;
constexpr int SLOT = 16384;
constexpr int QBUF_OFF = NS * SLOT;
constexpr int QBUF_BYTES = 3 * 16384 + 8192;
constexpr int NSX = NS + 4;
constexpr int BAR_OFF = NSX * SLOT;
#define EXT_END_V 6
constexpr int EXT_BEG = 4, EXT_END = EXT_END_V;
constexpr int BAR_FULL = BAR_OFF;
constexpr int BAR_EMPTY = BAR_OFF + 8 * NSX;
constexpr int BAR_STG = BAR_OFF + 16 * NSX;
constexpr int BAR_FREE = BAR_STG + 32;
constexpr int BAR_DESC = BAR_FREE + 8;
constexpr int DESC_OFF = BAR_DESC + 8;
constexpr int TRACE_OFF = DESC_OFF + 16;
constexpr int SMEM_BYTES = TRACE_OFF;
constexpr float SM_C = 0.08838834764831845f * 1.4426950408889634f;
constexpr float SUM_LIMIT = 18446744073709551616.f;
constexpr uint32_t META_QK = 0xEEEE4444u;
constexpr uint32_t META_PV = 0x44EEEE44u;

#define QK_EARLY 7
#define QK_EARLY_MASK 3
#define SP_ORDER 1
#define SP_PRO0 0
#define KV_WIN_TILES 6
#define PR_KV 2
#define PR_X 2
#define PR_W 2
#define SHIFT_BLK 8
#define PROJ_V 0
#define Q_EXT_END 7
#define P_LAG 7
#define P_EARLY 13
#define RANGE_TABLE 0, 69, 139, 208, 277, 344, 410, 474, 536, 595, 653, 704, 760, 813, 862, 907, 945, 988, 1024, 1063, 1098, 1121, 1145, 1173, 1186, 1200, 1216

struct Params {
  CUtensorMap x[2][2], wq[2], kv[2][2], wo[2];
  CUtensorMap o_ld[2], o_st, o_st32, out_st, out_st32;
  const __nv_bfloat16* kp[2];
  const __nv_bfloat16* vp[2];
};

__device__ __nv_bfloat16 g_o[(size_t)NBETA * SQ * HD];
__device__ unsigned g_cnt[NBETA];
__device__ unsigned g_epoch, g_done, g_next;
__device__ __align__(128) uint8_t g_part[(size_t)NCTA * QBUF_BYTES];
__device__ unsigned g_flag[NCTA];

__device__ __forceinline__ uint32_t smem_u32(const void* p) { return (uint32_t)__cvta_generic_to_shared(p); }
__device__ __forceinline__ void mbar_init(uint32_t bar, int cnt) {
  asm volatile("mbarrier.init.shared::cta.b64 [%0], %1;" ::"r"(bar), "r"(cnt) : "memory");
}
__device__ __forceinline__ void mbar_expect_tx(uint32_t bar, int bytes) {
  asm volatile("mbarrier.arrive.expect_tx.shared::cta.b64 _, [%0], %1;" ::"r"(bar), "r"(bytes) : "memory");
}
__device__ __forceinline__ void mbar_arrive(uint32_t bar) {
  asm volatile("mbarrier.arrive.shared::cta.b64 _, [%0];" ::"r"(bar) : "memory");
}
__device__ __forceinline__ void mbar_arrive_warp(uint32_t bar) {
  asm volatile("{\n.reg .pred p;\nelect.sync _|p, 0xffffffff;\n@p mbarrier.arrive.shared::cta.b64 _, [%0];\n}" ::"r"(bar) : "memory");
}
__device__ __forceinline__ int lane_now() { int l; asm volatile("mov.u32 %0, %%laneid;" : "=r"(l)); return l; }
__device__ __forceinline__ bool mbar_try(uint32_t bar, uint32_t parity) {
  uint32_t ok;
  asm volatile("{\n.reg .pred p;\nmbarrier.try_wait.parity.shared::cta.b64 p, [%1], %2;\nselp.u32 %0, 1, 0, p;\n}"
               : "=r"(ok) : "r"(bar), "r"(parity) : "memory");
  return ok;
}
__device__ __forceinline__ void mbar_wait(uint32_t bar, uint32_t parity) {
  uint32_t n = 0;
  while (!mbar_try(bar, parity)) {
    if (++n > (1u << 22)) __trap();
  }
}
__device__ __forceinline__ void mbar_wait_w(uint32_t bar, uint32_t parity) {
  uint32_t n = 0;
  while (!__all_sync(0xffffffffu, mbar_try(bar, parity))) {
    if (++n > (1u << 22)) __trap();
  }
}
__device__ __forceinline__ void tma_ld2(uint32_t dst, const CUtensorMap* m, int c0, int c1, uint32_t bar) {
  asm volatile("cp.async.bulk.tensor.2d.shared::cluster.global.mbarrier::complete_tx::bytes [%0], [%1, {%3, %4}], [%2];"
               ::"r"(dst), "l"(m), "r"(bar), "r"(c0), "r"(c1) : "memory");
}
__device__ __forceinline__ void tma_ld2_hint(uint32_t dst, const CUtensorMap* m, int c0, int c1, uint32_t bar, uint64_t pol) {
  asm volatile("cp.async.bulk.tensor.2d.shared::cluster.global.mbarrier::complete_tx::bytes.L2::cache_hint [%0], [%1, {%3, %4}], [%2], %5;"
               ::"r"(dst), "l"(m), "r"(bar), "r"(c0), "r"(c1), "l"(pol) : "memory");
}
__device__ __forceinline__ void tma_ld3(uint32_t dst, const CUtensorMap* m, int c0, int c1, int c2, uint32_t bar) {
  asm volatile("cp.async.bulk.tensor.3d.shared::cluster.global.mbarrier::complete_tx::bytes [%0], [%1, {%3, %4, %5}], [%2];"
               ::"r"(dst), "l"(m), "r"(bar), "r"(c0), "r"(c1), "r"(c2) : "memory");
}
__device__ __forceinline__ void tma_ld3_hint(uint32_t dst, const CUtensorMap* m, int c0, int c1, int c2, uint32_t bar, uint64_t pol) {
  asm volatile("cp.async.bulk.tensor.3d.shared::cluster.global.mbarrier::complete_tx::bytes.L2::cache_hint"
               " [%0], [%1, {%3, %4, %5}], [%2], %6;"
               ::"r"(dst), "l"(m), "r"(bar), "r"(c0), "r"(c1), "r"(c2), "l"(pol) : "memory");
}
__device__ __forceinline__ void tma_st3(const CUtensorMap* m, uint32_t src, int c0, int c1, int c2) {
  asm volatile("cp.async.bulk.tensor.3d.global.shared::cta.bulk_group [%0, {%2, %3, %4}], [%1];"
               ::"l"(m), "r"(src), "r"(c0), "r"(c1), "r"(c2) : "memory");
}
__device__ __forceinline__ void tma_st3_hint(const CUtensorMap* m, uint32_t src, int c0, int c1, int c2, uint64_t pol) {
  asm volatile("cp.async.bulk.tensor.3d.global.shared::cta.bulk_group.L2::cache_hint [%0, {%2, %3, %4}], [%1], %5;"
               ::"l"(m), "r"(src), "r"(c0), "r"(c1), "r"(c2), "l"(pol) : "memory");
}
__device__ __forceinline__ void wg_fence() { asm volatile("wgmma.fence.sync.aligned;" ::: "memory"); }
__device__ __forceinline__ void wg_commit() { asm volatile("wgmma.commit_group.sync.aligned;" ::: "memory"); }
template <int N> __device__ __forceinline__ void wg_wait() { asm volatile("wgmma.wait_group.sync.aligned %0;" ::"n"(N) : "memory"); }
__device__ __forceinline__ void fence_async_smem() { asm volatile("fence.proxy.async.shared::cta;" ::: "memory"); }
__device__ __forceinline__ void bar_sync(int id, int n) { asm volatile("bar.sync %0, %1;" ::"r"(id), "r"(n) : "memory"); }
template <int N> __device__ __forceinline__ void reg_fence(float (&a)[N]) {
#pragma unroll
  for (int i = 0; i < N; i++) asm volatile("" : "+f"(a[i])::"memory");
}
template <int N> __device__ __forceinline__ void reg_fence(uint32_t (&a)[N]) {
#pragma unroll
  for (int i = 0; i < N; i++) asm volatile("" : "+r"(a[i])::"memory");
}
__device__ __forceinline__ float ex2(float x) { float y; asm("ex2.approx.ftz.f32 %0, %1;" : "=f"(y) : "f"(x)); return y; }
__device__ __forceinline__ uint32_t pack_bf16(float lo, float hi) {
  uint32_t r; asm("cvt.rn.bf16x2.f32 %0, %1, %2;" : "=r"(r) : "f"(hi), "f"(lo)); return r;
}
__device__ __forceinline__ void stsm4(uint32_t a, uint32_t r0, uint32_t r1, uint32_t r2, uint32_t r3) {
  asm volatile("stmatrix.sync.aligned.m8n8.x4.shared.b16 [%0], {%1, %2, %3, %4};" ::"r"(a), "r"(r0), "r"(r1), "r"(r2), "r"(r3) : "memory");
}
__device__ __forceinline__ void stsm4t(uint32_t a, uint32_t r0, uint32_t r1, uint32_t r2, uint32_t r3) {
  asm volatile("stmatrix.sync.aligned.m8n8.x4.trans.shared.b16 [%0], {%1, %2, %3, %4};" ::"r"(a), "r"(r0), "r"(r1), "r"(r2), "r"(r3) : "memory");
}
__device__ __forceinline__ void ldsm4(uint32_t a, uint32_t& r0, uint32_t& r1, uint32_t& r2, uint32_t& r3) {
  asm volatile("ldmatrix.sync.aligned.m8n8.x4.shared.b16 {%0, %1, %2, %3}, [%4];" : "=r"(r0), "=r"(r1), "=r"(r2), "=r"(r3) : "r"(a) : "memory");
}
__device__ __forceinline__ void sts16(uint32_t a, uint32_t v) { asm volatile("st.shared.u16 [%0], %1;" ::"r"(a), "h"((uint16_t)v) : "memory"); }
__device__ __forceinline__ void mma16816(float& c0, float& c1, float& c2, float& c3, uint32_t a0, uint32_t a1, uint32_t a2, uint32_t a3,
                                         uint32_t b0, uint32_t b1) {
  asm volatile("mma.sync.aligned.m16n8k16.row.col.f32.bf16.bf16.f32 {%0, %1, %2, %3}, {%4, %5, %6, %7}, {%8, %9}, {%0, %1, %2, %3};"
               : "+f"(c0), "+f"(c1), "+f"(c2), "+f"(c3) : "r"(a0), "r"(a1), "r"(a2), "r"(a3), "r"(b0), "r"(b1));
}
__device__ __forceinline__ uint32_t sdesc(uint32_t addr, uint32_t lbo) { return (addr >> 4) + ((lbo >> 4) << 16); }
__device__ __forceinline__ uint64_t desc64(uint32_t lo, uint32_t hi) { uint64_t d; asm("mov.b64 %0, {%1, %2};" : "=l"(d) : "r"(lo), "r"(hi)); return d; }
__device__ __forceinline__ void dadd(uint64_t& d, uint32_t inc) {
  asm("{\n.reg .b32 l, h;\nmov.b64 {l, h}, %0;\nadd.u32 l, l, %1;\nmov.b64 %0, {l, h};\n}" : "+l"(d) : "r"(inc));
}

struct Ring {
  uint32_t slot, phase, xmask;
  __device__ __forceinline__ void uniform() {
    slot = __shfl_sync(0xffffffffu, slot, 0); phase = __shfl_sync(0xffffffffu, phase, 0); xmask = __shfl_sync(0xffffffffu, xmask, 0);
  }
  __device__ __forceinline__ void next() { if (++slot == NS) { slot = 0; phase ^= 1; } }
  __device__ __forceinline__ void enter() {
    const uint32_t below = (1u << slot) - 1, low = (1u << NS) - 1;
    xmask = (xmask & ~low) | ((phase ? ~below : below) & low);
  }
  __device__ __forceinline__ void leave() { phase = (xmask >> slot) & 1; }
  __device__ __forceinline__ uint32_t parity_x() const { return xmask >> slot; }
  __device__ __forceinline__ void next_x(uint32_t lim) { xmask ^= 1u << slot; if (++slot >= lim) slot = 0; }
};

constexpr uint32_t Q_RANGES = NBETA * NH + P_EARLY * 5;
constexpr int TAIL_STEPS = (NBETA - P_EARLY) * 64, NRANGE = NCTA / 5;
struct Work { int kind, mode, k0, nsteps, range, beta, sub; };
__device__ __forceinline__ uint32_t queue_item(uint32_t q) {
  if (q < P_LAG * NH) return q;
  q -= P_LAG * NH;
  if (q < P_EARLY * (NH + 5)) {
    const uint32_t g = q / (NH + 5), u = q - g * (NH + 5);
    return u < NH ? (((P_LAG + g) << 5) | u) : ((1u << 30) | (63u << 16) | (g * 5 + u - NH));
  }
  return q - P_EARLY * (NH + 5) + (P_LAG + P_EARLY) * NH;
}
__constant__ short c_range[NRANGE + 1] = {RANGE_TABLE};
__device__ __forceinline__ int range_begin(int k) { return k >= NRANGE ? TAIL_STEPS : c_range[k]; }
__device__ __forceinline__ Work decode(uint32_t d) {
  Work w;
  w.kind = d >> 30; w.mode = (d >> 28) & 3; w.k0 = (d >> 22) & 63; w.range = (d >> 8) & 255;
  if (w.kind == 0) { w.beta = (d >> 5) & 31; w.sub = d & 31; w.nsteps = DM / 64; }
  else { const int t = d & 255; w.beta = t / 5; w.sub = t - w.beta * 5; w.nsteps = ((d >> 16) & 63) + 1; }
  return w;
}

__device__ __forceinline__ void wait_count(const unsigned* cnt, unsigned target) {
  unsigned v, n = 0;
  do {
    asm volatile("ld.acquire.gpu.global.u32 %0, [%1];" : "=r"(v) : "l"(cnt) : "memory");
    if (++n > (1u << 24)) __trap();
  } while ((int)(v - target) < 0);
}
__device__ __forceinline__ void wait_heads(int beta, unsigned target) { wait_count(&g_cnt[beta], target); }

#define TRACE(u, e)
#define TRACE_P(u, e)
#define TRACE_IN(u, e)

struct Ctx {
  uint32_t sb;
  int wg, warp;
  uint32_t mqk, mpv;
  bool lead;
  int src;
};
template <int N> __device__ __forceinline__ uint32_t dhi(uint32_t lo) { return 0x40000040u + (lo >> (26 + N)); }
template <int N> __device__ __forceinline__ uint64_t full_desc(uint32_t addr, uint32_t slot) { return desc64(addr >> 4, dhi<N>(slot)); }
__device__ __forceinline__ void release(const Ctx& c, uint32_t slot) {
  if (c.lead) mbar_arrive(c.sb + BAR_EMPTY + slot * 8);
}
__device__ __forceinline__ uint32_t acquire(const Ctx& c, Ring& r) {
  const uint32_t s = r.slot;
  mbar_wait_w(c.sb + BAR_FULL + s * 8, r.phase);
  r.next();
  return s;
}
__device__ __forceinline__ uint32_t acquire(const Ctx& c, Ring& r, uint32_t lim) {
  const uint32_t s = r.slot;
  mbar_wait_w(c.sb + BAR_FULL + s * 8, r.parity_x());
  r.next_x(lim);
  return s;
}

template <bool FIRST, int N>
__device__ __forceinline__ void proj_half(float (&acc)[N], uint64_t a, uint64_t b) {
  wg_fence();
  if (FIRST) wgmma_proj_init(acc, a, b, 0); else wgmma_proj(acc, a, b, 1);
#pragma unroll
  for (int k = 1; k < 4; k++) { dadd(a, 128); dadd(b, 2); wgmma_proj(acc, a, b, 1); }
  wg_commit();
}

__device__ __forceinline__ void proj_store16(uint32_t a, const float* f, float sc) {
  stsm4t(a, pack_bf16(f[0] * sc, f[1] * sc), pack_bf16(f[2] * sc, f[3] * sc), pack_bf16(f[4] * sc, f[5] * sc), pack_bf16(f[6] * sc, f[7] * sc));
}

__device__ __forceinline__ uint32_t stage_off(const Ctx& c) {
  const int lane = lane_now(), mi = lane >> 3, r8 = lane & 7;
  return ((mi >> 1) * 8 + r8) * 128 + (((2 * c.warp + (mi & 1)) ^ r8) << 4);
}
__device__ __forceinline__ void stage_lo(const Ctx& c, const float (&a0)[64], float sc) {
  const uint32_t lane_off = c.sb + QBUF_OFF + c.wg * 8192 + stage_off(c);
#pragma unroll
  for (int jj = 0; jj < 8; jj++) proj_store16(lane_off + (jj >> 2) * 16384 + (jj & 3) * 2048, &a0[jj * 8], sc);
}
__device__ __forceinline__ void stage_hi(const Ctx& c, const float (&a1)[48], float sc) {
  const uint32_t off = stage_off(c), lane_off = c.sb + QBUF_OFF + 2 * 16384 + c.wg * 8192 + off;
#pragma unroll
  for (int jj = 0; jj < 4; jj++) proj_store16(lane_off + jj * 2048, &a1[jj * 8], sc);
  const uint32_t t3 = c.sb + QBUF_OFF + 3 * 16384 + c.wg * 4096 + off;
  proj_store16(t3, &a1[32], sc);
  proj_store16(t3 + 2048, &a1[40], sc);
  fence_async_smem();
}

__device__ __forceinline__ void add16(uint32_t a, float* f) {
  uint32_t r[4];
  asm volatile("ldmatrix.sync.aligned.m8n8.x4.trans.shared.b16 {%0, %1, %2, %3}, [%4];"
               : "=r"(r[0]), "=r"(r[1]), "=r"(r[2]), "=r"(r[3]) : "r"(a) : "memory");
#pragma unroll
  for (int i = 0; i < 4; i++) { f[2 * i] += __uint_as_float(r[i] << 16); f[2 * i + 1] += __uint_as_float(r[i] & 0xffff0000u); }
}

__device__ __forceinline__ void projection(const Ctx& c, Ring& r, uint32_t sw, const Work& w, int unit) {
  float a0[64], a1[48];
  const int nsteps = w.nsteps;
  const int ext_end = w.kind == 0 ? Q_EXT_END : nsteps - EXT_END;
  uint32_t s0 = acquire(c, r);
  proj_half<true>(a0, full_desc<0>(c.sb + sw * SLOT + c.wg * 8192, s0), full_desc<1>(c.sb + s0 * SLOT, s0));
  uint32_t s1 = acquire(c, r);
  proj_half<true>(a1, full_desc<0>(c.sb + sw * SLOT + c.wg * 8192, s1), full_desc<1>(c.sb + s1 * SLOT, s1));
  wg_wait<1>();
  release(c, s0);
  r.enter();
#pragma unroll 1
  for (int ks = 1; ks < nsteps; ks++) {
    const uint32_t pw = sw, lim = (uint32_t)(ks - EXT_BEG) < (uint32_t)max(ext_end - EXT_BEG, 0) ? NSX : NS;
    sw = acquire(c, r, lim);
    uint64_t da = full_desc<0>(c.sb + sw * SLOT + c.wg * 8192, r.slot), db = full_desc<1>(c.sb + r.slot * SLOT, r.slot);
    if (PROJ_V & 1) asm volatile("" : "+l"(da), "+l"(db));
    s0 = acquire(c, r, lim);
    wg_wait<0>();
    if (!(PROJ_V & 2)) { release(c, pw); release(c, s1); }
    proj_half<false>(a0, da, db);
    if (PROJ_V & 2) { release(c, pw); release(c, s1); }
    da = full_desc<0>(c.sb + sw * SLOT + c.wg * 8192, r.slot); db = full_desc<1>(c.sb + r.slot * SLOT, r.slot);
    if (PROJ_V & 1) asm volatile("" : "+l"(da), "+l"(db));
    s1 = acquire(c, r, lim);
    wg_wait<0>();
    if (!(PROJ_V & 2)) release(c, s0);
    proj_half<false>(a1, da, db);
    if (PROJ_V & 2) release(c, s0);
  }
  r.leave();
  if (unit > 0) mbar_wait_w(c.sb + BAR_FREE, (unit - 1) & 1);
  if (w.kind == 0) {
#pragma unroll
    for (int x = NS; x < NSX; x++) mbar_wait_w(c.sb + BAR_EMPTY + x * 8, ((r.xmask >> x) & 1) ^ 1);
  }
  reg_fence(a0);
  TRACE(unit, 1);
  const float sc = w.kind == 0 ? SM_C : 1.f;
  if (w.mode != 2) stage_lo(c, a0, sc);
  if (w.kind == 0 && c.wg == 1) {
    fence_async_smem();
    asm volatile("bar.arrive 1, 256;" ::: "memory");
  }
  wg_wait<0>();
  reg_fence(a1);
  release(c, sw); release(c, s1);
  if (w.mode == 2) {
    const uint32_t off = c.sb + stage_off(c);
#pragma unroll 1
    for (int k = 0; k < w.k0; k++) {
#pragma unroll
      for (int t = 0; t < 4; t++) {
        const uint32_t sp = acquire(c, r), base = off + sp * SLOT + c.wg * (t == 3 ? 4096 : 8192);
#pragma unroll
        for (int jj = 0; jj < (t == 3 ? 2 : 4); jj++) add16(base + jj * 2048, t < 2 ? &a0[(t * 4 + jj) * 8] : &a1[((t - 2) * 4 + jj) * 8]);
        release(c, sp);
      }
    }
    stage_lo(c, a0, 1.f);
  }
  stage_hi(c, a1, sc);
}

struct RowStat { float m0, m1, l0, l1; };

__device__ __forceinline__ float quad_max(float x) {
  x = fmaxf(x, __shfl_xor_sync(0xffffffffu, x, 1));
  return fmaxf(x, __shfl_xor_sync(0xffffffffu, x, 2));
}
__device__ __forceinline__ float quad_sum(float x) {
  x += __shfl_xor_sync(0xffffffffu, x, 1);
  return x + __shfl_xor_sync(0xffffffffu, x, 2);
}
__device__ __forceinline__ void tile_exp(const float (&s)[32], uint32_t (&p)[16], float m0, float m1, float& t0, float& t1,
                                         float* late = nullptr) {
#pragma unroll
  for (int j = 0; j < 8; j++) {
    if (late && j == QK_EARLY) *late = t0 + t1;
    const float e0 = ex2(s[4 * j] - m0), e1 = ex2(s[4 * j + 1] - m0);
    const float e2 = ex2(s[4 * j + 2] - m1), e3 = ex2(s[4 * j + 3] - m1);
    if (j == 0) { t0 = e0 + e1; t1 = e2 + e3; } else { t0 += e0 + e1; t1 += e2 + e3; }
    p[2 * j] = pack_bf16(e0, e1);
    p[2 * j + 1] = pack_bf16(e2, e3);
  }
}
template <bool SP>
__device__ __forceinline__ void redo_tile(const Ctx& c, float (&o)[64], RowStat& st, uint32_t q_addr, const __nv_bfloat16* kp,
                                          const __nv_bfloat16* vp) {
  const int lane = lane_now(), g = lane >> 2, cc = lane & 3, mi = lane >> 3, r8 = lane & 7;
  const uint32_t qa = SP ? q_addr + (8 * c.warp + g) * 128 + cc * 4
                         : q_addr + (16 * c.warp + (mi & 1) * 8 + r8) * 128;
  const uint32_t* kq = reinterpret_cast<const uint32_t*>(kp + g * DH) + cc;
  const unsigned short* vq = reinterpret_cast<const unsigned short*>(vp + 2 * cc * DH) + g;
  float m0 = -INFINITY, m1 = -INFINITY, l0 = 0.f, l1 = 0.f;
#pragma unroll
  for (int i = 0; i < 64; i++) o[i] = 0.f;
#pragma unroll 1
  for (int kb = 0; kb < SK / 16; kb++) {
    float z[8] = {0.f, 0.f, 0.f, 0.f, 0.f, 0.f, 0.f, 0.f};
#pragma unroll 2
    for (int kk = 0; kk < 8; kk++) {
      uint32_t a0, a1 = 0, a2, a3 = 0;
      if (SP) {
        asm volatile("ld.shared.u32 %0, [%1];" : "=r"(a0) : "r"(qa + (kk >> 2) * 4096 + ((((kk & 3) * 2) ^ g) << 4)) : "memory");
        asm volatile("ld.shared.u32 %0, [%1];" : "=r"(a2) : "r"(qa + (kk >> 2) * 4096 + ((((kk & 3) * 2 + 1) ^ g) << 4)) : "memory");
      } else {
        ldsm4(qa + (kk >> 2) * 8192 + ((((kk & 3) * 2 + (mi >> 1)) ^ r8) << 4), a0, a1, a2, a3);
      }
      const uint32_t* kr = kq + kb * (16 * DH / 2) + kk * 8;
      mma16816(z[0], z[1], z[2], z[3], a0, a1, a2, a3, __ldg(kr), __ldg(kr + 4));
      mma16816(z[4], z[5], z[6], z[7], a0, a1, a2, a3, __ldg(kr + 8 * DH / 2), __ldg(kr + 8 * DH / 2 + 4));
    }
    const float n0 = fmaxf(m0, quad_max(fmaxf(fmaxf(z[0], z[1]), fmaxf(z[4], z[5]))));
    const float n1 = fmaxf(m1, quad_max(fmaxf(fmaxf(z[2], z[3]), fmaxf(z[6], z[7]))));
    const float al0 = ex2(m0 - n0), al1 = ex2(m1 - n1);
    m0 = n0; m1 = n1;
#pragma unroll
    for (int i = 0; i < 8; i++) z[i] = ex2(z[i] - ((i & 2) ? n1 : n0));
    l0 = l0 * al0 + (z[0] + z[1]) + (z[4] + z[5]);
    l1 = l1 * al1 + (z[2] + z[3]) + (z[6] + z[7]);
    const uint32_t a0 = pack_bf16(z[0], z[1]), a1 = SP ? 0u : pack_bf16(z[2], z[3]);
    const uint32_t a2 = pack_bf16(z[4], z[5]), a3 = SP ? 0u : pack_bf16(z[6], z[7]);
    const unsigned short* vr = vq + kb * (16 * DH);
#pragma unroll
    for (int nb = 0; nb < 16; nb++) {
      o[4 * nb] *= al0; o[4 * nb + 1] *= al0; o[4 * nb + 2] *= al1; o[4 * nb + 3] *= al1;
      const uint32_t b0 = __ldg(vr + nb * 8) | ((uint32_t)__ldg(vr + nb * 8 + DH) << 16);
      const uint32_t b1 = __ldg(vr + nb * 8 + 8 * DH) | ((uint32_t)__ldg(vr + nb * 8 + 9 * DH) << 16);
      mma16816(o[4 * nb], o[4 * nb + 1], o[4 * nb + 2], o[4 * nb + 3], a0, a1, a2, a3, b0, b1);
    }
  }
  st.l0 = l0; st.l1 = l1;
}
template <bool SP>
__device__ __forceinline__ void check_tile(const Ctx& c, float (&o)[64], RowStat& st, uint32_t q_addr, const __nv_bfloat16* kp,
                                           const __nv_bfloat16* vp) {
  const bool ok = st.l0 <= SUM_LIMIT && (SP || st.l1 <= SUM_LIMIT);
  if (__builtin_expect(__any_sync(0xffffffffu, !ok), 0)) redo_tile<SP>(c, o, st, q_addr, kp, vp);
}
__device__ __forceinline__ void sparse_exp(const Ctx& c, const float (&z)[16], uint32_t (&p)[8], float m, float& t) {
  uint32_t q[8];
#pragma unroll
  for (int j = 0; j < 8; j++) {
    const float e0 = ex2(z[2 * j] - m), e1 = ex2(z[2 * j + 1] - m);
    if (j == 0) t = e0 + e1; else t += e0 + e1;
    q[j] = pack_bf16(e0, e1);
  }
  const bool odd = c.src & 2;
  const int src = c.src;
#pragma unroll
  for (int g = 0; g < 4; g++) {
    p[2 * g] = __shfl_sync(0xffffffffu, odd ? q[2 * g + 1] : q[2 * g], src);
    p[2 * g + 1] = __shfl_sync(0xffffffffu, odd ? q[2 * g] : q[2 * g + 1], src ^ 1);
  }
}
template <bool SP>
__device__ __forceinline__ void first_max(const float (&s)[32], RowStat& st) {
  if constexpr (SP) {
    float x = fmaxf(s[0] + s[2], s[1] + s[3]);
#pragma unroll
    for (int j = 1; j < SHIFT_BLK; j++) x = fmaxf(x, fmaxf(s[4 * j] + s[4 * j + 2], s[4 * j + 1] + s[4 * j + 3]));
    st.m0 = quad_max(x);
  } else {
    float x0 = fmaxf(s[0], s[1]), x1 = fmaxf(s[2], s[3]);
#pragma unroll
    for (int j = 1; j < SHIFT_BLK; j++) {
      x0 = fmaxf(x0, fmaxf(s[4 * j], s[4 * j + 1]));
      x1 = fmaxf(x1, fmaxf(s[4 * j + 2], s[4 * j + 3]));
    }
    st.m0 = quad_max(x0); st.m1 = quad_max(x1);
  }
}
template <bool SP, bool FIRST>
__device__ __forceinline__ void exps(const Ctx& c, const float (&s)[32], uint32_t (&p)[SP ? 8 : 16], RowStat& st, float& late) {
  if constexpr (SP) {
    float z[16], t;
#pragma unroll
    for (int j = 0; j < 8; j++) { z[2 * j] = s[4 * j] + s[4 * j + 2]; z[2 * j + 1] = s[4 * j + 1] + s[4 * j + 3]; }
    sparse_exp(c, z, p, st.m0, t);
    late = t;
    st.l0 = FIRST ? t : st.l0 + t;
  } else {
    float t0, t1;
    tile_exp(s, p, st.m0, st.m1, t0, t1, &late);
    st.l0 = FIRST ? t0 : st.l0 + t0;
    st.l1 = FIRST ? t1 : st.l1 + t1;
  }
}
template <bool SP, bool INIT, int SITE, bool COMMIT = true>
__device__ __forceinline__ void issue_qk(const Ctx& c, float (&s)[32], const uint32_t (&qs)[16], uint32_t dq, uint32_t dk, uint32_t dep = 0,
                                         bool has_dep = false) {
  uint64_t a = desc64(dq, dhi<SITE & 1>(dk)), b = desc64(dk, dhi<1 - (SITE & 1)>(dk));
  const uint64_t a0 = has_dep ? desc64(dq + dep, 0x40000040u) : a;
  if (SP) {
    const uint64_t b0 = has_dep ? desc64(dk + dep, 0x40000040u) : b;
    if (INIT) wgmma_qk_sp_init(s, qs[0], qs[1], qs[2], qs[3], b0, 0, c.mqk); else wgmma_qk_sp(s, qs[0], qs[1], qs[2], qs[3], b0, 0, c.mqk);
#pragma unroll
    for (int k = 1; k < 4; k++) { dadd(b, k == 2 ? 508 : 4); wgmma_qk_sp(s, qs[4 * k], qs[4 * k + 1], qs[4 * k + 2], qs[4 * k + 3], b, 1, c.mqk); }
  } else {
    if (INIT) wgmma_qk_init(s, a0, b, 0); else wgmma_qk(s, a0, b, 0);
#pragma unroll
    for (int k = 1; k < 8; k++) { dadd(a, k == 4 ? 506 : 2); dadd(b, k == 4 ? 506 : 2); wgmma_qk(s, a, b, 1); }
  }
  if (COMMIT) wg_commit();
}
template <bool SP, bool ACC, int SITE, bool SPLIT = false>
__device__ __forceinline__ void issue_pv(const Ctx& c, float (&o)[64], const uint32_t (&p)[SP ? 8 : 16], uint32_t dv) {
  uint64_t b = desc64(dv, dhi<SITE & 1>(dv));
  if constexpr (SP) {
    if (ACC) wgmma_pv_sp(o, p[0], p[1], p[2], p[3], b, 1, c.mpv); else wgmma_pv_sp_init(o, p[0], p[1], p[2], p[3], b, 0, c.mpv);
    if (SPLIT) wg_commit();
    dadd(b, 256);
    wgmma_pv_sp(o, p[4], p[5], p[6], p[7], b, 1, c.mpv);
  } else {
    if (ACC) wgmma_pv(o, p[0], p[1], p[2], p[3], b, 1); else wgmma_pv_init(o, p[0], p[1], p[2], p[3], b, 0);
#pragma unroll
    for (int k = 1; k < 4; k++) { dadd(b, 128); wgmma_pv(o, p[4 * k], p[4 * k + 1], p[4 * k + 2], p[4 * k + 3], b, 1); }
  }
  wg_commit();
}
template <bool SP>
__device__ __forceinline__ void o_store(const Ctx& c, uint32_t tile_addr, const float (&o)[64], const RowStat& st) {
  const int lane = lane_now(), mi = lane >> 3, r8 = lane & 7;
  if (SP) {
    const float i0 = __fdividef(1.f, quad_sum(st.l0));
    const uint32_t row_addr = tile_addr + (8 * c.warp + r8) * 128;
#pragma unroll
    for (int jj = 0; jj < 4; jj++) {
      const int b = jj * 16;
      stsm4(row_addr + (jj >> 1) * 4096 + ((((jj & 1) * 4 + mi) ^ r8) << 4),
            pack_bf16((o[b] + o[b + 2]) * i0, (o[b + 1] + o[b + 3]) * i0), pack_bf16((o[b + 4] + o[b + 6]) * i0, (o[b + 5] + o[b + 7]) * i0),
            pack_bf16((o[b + 8] + o[b + 10]) * i0, (o[b + 9] + o[b + 11]) * i0),
            pack_bf16((o[b + 12] + o[b + 14]) * i0, (o[b + 13] + o[b + 15]) * i0));
    }
  } else {
    const float i0 = __fdividef(1.f, quad_sum(st.l0)), i1 = __fdividef(1.f, quad_sum(st.l1));
    const uint32_t row_addr = tile_addr + (16 * c.warp + (mi & 1) * 8 + r8) * 128;
#pragma unroll
    for (int jj = 0; jj < 8; jj++) {
      const int b = jj * 8;
      stsm4(row_addr + (jj >> 2) * 8192 + (((((2 * jj) & 7) + (mi >> 1)) ^ r8) << 4),
            pack_bf16(o[b] * i0, o[b + 1] * i0), pack_bf16(o[b + 2] * i1, o[b + 3] * i1),
            pack_bf16(o[b + 4] * i0, o[b + 5] * i0), pack_bf16(o[b + 6] * i1, o[b + 7] * i1));
    }
  }
}

template <bool SPA, bool SPB, int SITE, int ID>
__device__ __forceinline__ void batch(const Ctx& c, float (&s)[32], const uint32_t (&qs)[16], uint32_t dq, uint32_t dk, float (&ob)[64], uint32_t (&pb)[SPB ? 8 : 16],
                                      uint32_t dv, float late, uint32_t zero) {
  if constexpr (SPA && SP_ORDER) {
    reg_fence(pb);
    wg_fence();
    issue_pv<SPB, true, ID>(c, ob, pb, dv);
    issue_qk<SPA, false, ID>(c, s, qs, dq, dk);
  } else {
    constexpr bool EARLY = ((QK_EARLY_MASK >> (SITE + ((SPA || SPB) ? 2 : 0))) & 1) != 0;
    if (!EARLY) reg_fence(pb);
    wg_fence();
    issue_qk<SPA, false, ID, !(SPB && SP_ORDER)>(c, s, qs, dq, dk, __float_as_uint(late) & zero, EARLY);
    if (EARLY) { reg_fence(pb); wg_fence(); }
    issue_pv<SPB, true, ID, SPB && SP_ORDER>(c, ob, pb, dv);
  }
}

template <bool SP0, bool SP1>
__device__ __forceinline__ void attention(Ctx c, Ring& r, uint32_t sk, int t0, int t1, int unit, uint32_t zero,
                                          const __nv_bfloat16* const* kv, uint32_t d) {
  if (SP0 || SP1) { c.mqk = META_QK + zero; c.mpv = META_PV + zero; asm volatile("" : "+r"(c.mqk), "+r"(c.mpv)); }
  if (SP0 || SP1) { const int lane = lane_now(); c.src = (lane & 28) | ((lane & 1) << 1) | ((lane >> 1) & 1); }
  float o0[64], o1[64], s[32], late;
  uint32_t p0[SP0 ? 8 : 16], p1[SP1 ? 8 : 16];
  RowStat st0, st1;
  const uint32_t q0a = c.sb + QBUF_OFF + t0 * 16384, q1a = c.sb + QBUF_OFF + t1 * 16384;
  const uint32_t dq0 = sdesc(q0a, 0), dq1 = sdesc(q1a, 0);
  uint32_t sv, sn;
  uint32_t qs[16];
  if (SP0 || SP1) {
    const int lane = lane_now(), g = lane >> 2, cc = lane & 3;
    const uint32_t qa = (SP0 ? q0a : q1a) + (8 * c.warp + g) * 128 + (cc & 1) * 8;
#pragma unroll
    for (int k = 0; k < 8; k++)
      asm volatile("ld.shared.v2.u32 {%0, %1}, [%2];" : "=r"(qs[2 * k]), "=r"(qs[2 * k + 1])
                   : "r"(qa + (k >> 2) * 4096 + ((((k & 3) * 2 + (cc >> 1)) ^ g) << 4)) : "memory");
  }
  {
    float s1[32];
    wg_fence();
    issue_qk<SP0, true, 0>(c, s, qs, dq0, sdesc(c.sb + sk * SLOT, 0));
    issue_qk<SP1, true, 1>(c, s1, qs, dq1, sdesc(c.sb + sk * SLOT, 0));
    sv = acquire(c, r);
    sn = acquire(c, r);
    wg_wait<1>();
    reg_fence(s);
    first_max<SP0>(s, st0);
    exps<SP0, true>(c, s, p0, st0, late);
    reg_fence(p0);
    wg_fence();
    issue_qk<SP0, false, 2>(c, s, qs, dq0, sdesc(c.sb + sn * SLOT, 0));
    issue_pv<SP0, false, 0>(c, o0, p0, sdesc(c.sb + sv * SLOT, 8192));
    wg_wait<2>();
    reg_fence(s1);
    release(c, sk);
    sk = sn;
    first_max<SP1>(s1, st1);
    exps<SP1, true>(c, s1, p1, st1, late);
    reg_fence(p1);
    wg_fence();
    issue_pv<SP1, false, 1>(c, o1, p1, sdesc(c.sb + sv * SLOT, 8192));
    sn = acquire(c, r);
    if (SP0 && SP_ORDER && SP_PRO0) wg_wait<0>(); else wg_wait<1>();
    reg_fence(s);
  }
  TRACE_IN(unit, 4);
#pragma unroll 1
  for (int j = 1; j < 15; j++) {
    const uint32_t sv_prev = sv, sk_prev = sk;
    sv = sn;
    const uint32_t dv = sdesc(c.sb + sv * SLOT, 8192);
    reg_fence(p0);
    exps<SP0, false>(c, s, p0, st0, late);
    batch<SP1, SP0, 0, 3>(c, s, qs, dq1, sdesc(c.sb + sk * SLOT, 0), o0, p0, dv, late, zero);
    sk = acquire(c, r);
    wg_wait<1>();
    reg_fence(s); reg_fence(p1);
    release(c, sv_prev); release(c, sk_prev);
    exps<SP1, false>(c, s, p1, st1, late);
    batch<SP0, SP1, 1, 4>(c, s, qs, dq0, sdesc(c.sb + sk * SLOT, 0), o1, p1, dv, late, zero);
    sn = acquire(c, r);
    if (SP0 && SP_ORDER) wg_wait<0>(); else wg_wait<1>();
    reg_fence(s);
  }
  TRACE_IN(unit, 5);
  {
    const uint32_t sv_prev = sv;
    sv = sn;
    const uint32_t dv = sdesc(c.sb + sv * SLOT, 8192);
    reg_fence(p0);
    exps<SP0, false>(c, s, p0, st0, late);
    batch<SP1, SP0, 0, 5>(c, s, qs, dq1, sdesc(c.sb + sk * SLOT, 0), o0, p0, dv, late, zero);
    wg_wait<1>();
    reg_fence(s); reg_fence(p1);
    release(c, sv_prev); release(c, sk);
    exps<SP1, false>(c, s, p1, st1, late);
    reg_fence(p1);
    wg_fence();
    issue_pv<SP1, true, 2>(c, o1, p1, dv);
    const size_t hoff = (size_t)(d & 511) * (SK * DH);
    const int br = (d >> 9) & 1;
    wg_wait<1>();
    reg_fence(o0);
    check_tile<SP0>(c, o0, st0, q0a, kv[br] + hoff, kv[2 + br] + hoff);
    o_store<SP0>(c, q0a, o0, st0);
    wg_wait<0>();
    reg_fence(o1);
    release(c, sv);
    check_tile<SP1>(c, o1, st1, q1a, kv[br] + hoff, kv[2 + br] + hoff);
    o_store<SP1>(c, q1a, o1, st1);
    fence_async_smem();
  }
}

template <int WGSEL>
__device__ __forceinline__ void consumer(const Ctx& c, int cta, const __nv_bfloat16* const* kv) {
  Ring r{0, 0, 0};
  for (int i = 0;; i++) {
    TRACE(i, 0); TRACE(i, 6);
    r.uniform();
    const uint32_t sw = acquire(c, r);
    uint32_t d;
    asm volatile("ld.volatile.shared.u32 %0, [%1];" : "=r"(d) : "r"(c.sb + DESC_OFF + (i & 3) * 4) : "memory");
    d = __shfl_sync(0xffffffffu, d, 0);
    const Work w = decode(d);
    if (w.kind == 2) {
      if (c.wg == 0) {
        mbar_wait_w(c.sb + BAR_FREE, (i - 1) & 1);
        mbar_arrive_warp(c.sb + BAR_STG);
      }
      break;
    }
    projection(c, r, sw, w, i);
    if (w.kind == 0) {
      if (c.wg == 0) asm volatile("bar.arrive 6, 256;" ::: "memory");
      r.uniform();
      const uint32_t sk = acquire(c, r);
      bar_sync(c.wg == 0 ? 1 : 6, 256);
      TRACE(i, 2);
      if (WGSEL == 0) attention<false, false>(c, r, sk, 0, 1, i, w.mode, kv, d);
      else attention<true, false>(c, r, sk, 3, 2, i, w.mode, kv, d);
    } else {
      TRACE(i, 2);
    }
    __syncwarp();
    mbar_arrive_warp(c.sb + BAR_STG + c.wg * 8);
    TRACE(i, 3); TRACE(i, 7);
  }
}

template <bool SIMPLE>
__global__ void __launch_bounds__(384, 1) mha_fused_kernel(const __grid_constant__ Params P) {
  extern __shared__ __align__(1024) uint8_t smem_raw[];
  const uint32_t sbase = smem_u32(smem_raw);
  const int tid = threadIdx.x;
  const int wg = __shfl_sync(0xffffffffu, tid >> 7, 0);
  const int warp = __shfl_sync(0xffffffffu, (tid >> 5) & 3, 0);
  const int lane = tid & 31;
  const int cta = blockIdx.x;

  if (tid >= 256 && tid < 256 + 18) asm volatile("prefetch.tensormap [%0];" ::"l"(&P.x[0][0] + (tid - 256)) : "memory");
  if (tid == 0) {
    if ((sbase & 1023) || sbase + SMEM_BYTES > 0x40000) __trap();
    for (int i = 0; i < NSX; i++) { mbar_init(sbase + BAR_FULL + i * 8, 1); mbar_init(sbase + BAR_EMPTY + i * 8, 8); }
    for (int i = 0; i < 2; i++) mbar_init(sbase + BAR_STG + i * 8, 4);
    mbar_init(sbase + BAR_FREE, 1);
    mbar_init(sbase + BAR_DESC, 1);
    asm volatile("fence.mbarrier_init.release.cluster;" ::: "memory");
  }
  __syncthreads();

  if (wg == 2) {
    asm volatile("setmaxnreg.dec.sync.aligned.u32 24;");
    if (warp == 0 && lane == 0) {
      Ring r{0, 1, 0xffffffffu};
      uint32_t qi = cta;
      int pos = -1;
      for (int i = 0;; i++) {
        uint32_t d;
        if (qi < Q_RANGES) d = queue_item(qi);
        else if (SIMPLE) d = qi < NBETA * (NH + 5) ? (1u << 30) | (63u << 16) | (qi - NBETA * NH) : 2u << 30;
        else {
          const int e = qi - Q_RANGES, k = e / 5;
          if (pos < 0) pos = range_begin(k);
          const int end = range_begin(k + 1);
          if (pos >= end) d = 2u << 30;
          else {
            const int tile_end = (pos | 63) + 1, stop = min(end, tile_end), k0 = pos & 63;
            const int mode = k0 ? 1 : stop == tile_end ? 0 : 2;
            int f = k0;
            if (mode == 2) { f = 1; while (range_begin(k + 1 + f) < tile_end) f++; }
            d = (1u << 30) | (mode << 28) | (f << 22) | ((stop - pos - 1) << 16) | (e << 8) | ((P_EARLY + (pos >> 6) - k) * 5 + e);
            pos = stop;
          }
        }
        if ((d >> 30) == 1) wait_heads((d & 255) / 5, (*(volatile unsigned*)&g_epoch + 1) * NH);
        asm volatile("st.volatile.shared.u32 [%0], %1;" ::"r"(sbase + DESC_OFF + (i & 3) * 4), "r"(d) : "memory");
        mbar_arrive(sbase + BAR_DESC);
        const Work w = decode(d);
        if (w.kind == 2) {
          mbar_wait(sbase + BAR_EMPTY + r.slot * 8, r.phase);
          mbar_arrive(sbase + BAR_FULL + r.slot * 8);
          break;
        }
        const int ext_end = w.kind == 0 ? Q_EXT_END : w.nsteps - EXT_END;
        const CUtensorMap* m = w.kind == 0 ? &P.wq[w.beta >> 4] : &P.wo[w.beta >> 4];
        const int c1 = w.mode == 1 ? w.k0 * 64 : 0;
        r.enter();
        for (int ks = 0; ks < w.nsteps; ks++) {
          const uint32_t lim = (uint32_t)(ks - EXT_BEG) < (uint32_t)max(ext_end - EXT_BEG, 0) ? NSX : NS;
          if (ks == EXT_BEG && i > 0) mbar_wait(sbase + BAR_FREE, (i - 1) & 1);
          if (w.kind != 0 && pos < 0 && ks == w.nsteps - 2) qi = (SIMPLE ? gridDim.x : NCTA) + atomicAdd(&g_next, 1);
          const uint32_t bar = sbase + BAR_FULL + r.slot * 8;
          mbar_wait(sbase + BAR_EMPTY + r.slot * 8, r.parity_x());
          mbar_expect_tx(bar, 16384);
          tma_ld3(sbase + r.slot * SLOT, m, 0, c1 + ks * 64, w.sub * 2, bar);
          r.next_x(lim); r.next_x(lim); r.next_x(lim);
        }
        r.leave();
        if (w.kind == 0) {
          for (int j = 0; j < 3; j++) { mbar_wait(sbase + BAR_EMPTY + r.slot * 8, r.phase); r.phase ^= 1; }
          mbar_wait(sbase + BAR_EMPTY + r.slot * 8, r.phase);
          qi = (SIMPLE ? gridDim.x : NCTA) + atomicAdd(&g_next, 1);
          r.next(); r.next();
        } else if (w.mode == 2) {
          for (int k = 1; k <= w.k0; k++) {
            wait_count(&g_flag[w.range + 5 * k], *(volatile unsigned*)&g_epoch + 1);
            asm volatile("fence.proxy.async;" ::: "memory");
            for (int t = 0; t < 4; t++) {
              const uint32_t bar = sbase + BAR_FULL + r.slot * 8, bytes = t == 3 ? 8192 : 16384;
              mbar_wait(sbase + BAR_EMPTY + r.slot * 8, r.phase);
              mbar_expect_tx(bar, bytes);
              asm volatile("cp.async.bulk.shared::cluster.global.mbarrier::complete_tx::bytes [%0], [%1], %2, [%3];"
                           ::"r"(sbase + r.slot * SLOT), "l"(g_part + (size_t)(w.range + 5 * k) * QBUF_BYTES + t * 16384), "r"(bytes), "r"(bar)
                           : "memory");
              r.next();
            }
          }
        }
      }
    } else if (warp >= 2 && lane == 0) {
      const int hi = warp - 2;
      uint64_t pol_stream;
      asm volatile("createpolicy.fractional.L2::evict_first.b64 %0, 1.0;" : "=l"(pol_stream));
      Ring r{0, 1, 0xffffffffu};
      for (int i = 0;; i++) {
        uint32_t d;
        mbar_wait(sbase + BAR_DESC, i & 1);
        asm volatile("ld.volatile.shared.u32 %0, [%1];" : "=r"(d) : "r"(sbase + DESC_OFF + (i & 3) * 4) : "memory");
        const Work w = decode(d);
        if (w.kind == 2) break;
        const int ext_end = w.kind == 0 ? Q_EXT_END : w.nsteps - EXT_END;
        const CUtensorMap* m = w.kind == 0 ? &P.x[hi][w.beta >> 4] : &P.o_ld[hi];
        int c1 = (w.kind == 0 ? (w.beta & 15) : w.beta * 64 + (w.mode == 1 ? w.k0 : 0)) * SQ + hi * 128;
        if (w.kind != 0) asm volatile("fence.proxy.async;" ::: "memory");
        r.enter();
        for (int ks = 0; ks < w.nsteps; ks++) {
          const uint32_t lim = (uint32_t)(ks - EXT_BEG) < (uint32_t)max(ext_end - EXT_BEG, 0) ? NSX : NS;
          if (ks == EXT_BEG && i > 0) mbar_wait(sbase + BAR_FREE, (i - 1) & 1);
          r.next_x(lim);
          if (hi) r.next_x(lim);
          const uint32_t bar = sbase + BAR_FULL + r.slot * 8;
          mbar_wait(sbase + BAR_EMPTY + r.slot * 8, r.parity_x());
          mbar_expect_tx(bar, hi ? 96 * 128 : 128 * 128);
          if (w.kind == 0) tma_ld2(sbase + r.slot * SLOT, m, ks * 64, c1, bar);
          else { tma_ld2_hint(sbase + r.slot * SLOT, m, 0, c1, bar, pol_stream); c1 += SQ; }
          if (!hi) r.next_x(lim);
          r.next_x(lim);
        }
        r.leave();
        if (w.kind == 0) {
          m = &P.kv[hi][w.beta >> 4];
          c1 = (d & 511) * SK;
          for (int j = 0; j < 16; j++) {
            if (hi) r.next();
            const uint32_t bar = sbase + BAR_FULL + r.slot * 8;
            if (i == 0 && j < KV_WIN_TILES) {
              const int s2 = (int)r.slot - 2;
              mbar_wait(sbase + BAR_FULL + (s2 < 0 ? s2 + NS : s2) * 8, s2 < 0 ? r.phase : r.phase ^ 1);
            }
            mbar_wait(sbase + BAR_EMPTY + r.slot * 8, r.phase);
            mbar_expect_tx(bar, 16384);
            tma_ld3_hint(sbase + r.slot * SLOT, m, 0, c1, 0, bar, pol_stream);
            c1 += 64;
            r.next();
            if (!hi) r.next();
          }
        }
      }
    } else if (warp == 1 && lane == 0) {
      const uint32_t qb = sbase + QBUF_OFF;
      for (int i = 0;; i++) {
        mbar_wait(sbase + BAR_STG, i & 1);
        uint32_t d;
        asm volatile("ld.volatile.shared.u32 %0, [%1];" : "=r"(d) : "r"(sbase + DESC_OFF + (i & 3) * 4) : "memory");
        const Work w = decode(d);
        if (w.kind == 2) break;
#pragma unroll
        for (int h = 0; h < 2; h++) {
          if (h == 1) mbar_wait(sbase + BAR_STG + 8, i & 1);
          if (w.kind == 0) {
            const int cb = w.beta * 64 + w.sub * 2;
            tma_st3(&P.o_st, qb + h * 32768, 0, h * 128, cb);
            tma_st3(&P.o_st, qb + h * 32768 + 8192, 0, h * 128, cb + 1);
            tma_st3(h ? &P.o_st32 : &P.o_st, qb + h * 32768 + 16384, 0, h * 128 + 64, cb);
            tma_st3(h ? &P.o_st32 : &P.o_st, qb + h * 32768 + 16384 + (h ? 4096 : 8192), 0, h * 128 + 64, cb + 1);
          } else {
            if (w.mode == 1) {
#pragma unroll
              for (int t = 0; t < 4; t++) {
                const uint32_t o = t * 16384 + h * (t == 3 ? 4096 : 8192);
                asm volatile("cp.async.bulk.global.shared::cta.bulk_group [%0], [%1], %2;"
                             ::"l"(g_part + (size_t)w.range * QBUF_BYTES + o), "r"(qb + o), "r"(t == 3 ? 4096 : 8192) : "memory");
              }
              continue;
            }
            const int col = (w.beta >> 4) * DM + w.sub * 128 + h * 64;
            uint64_t pol;
            asm volatile("createpolicy.fractional.L2::evict_first.b64 %0, 1.0;" : "=l"(pol));
#pragma unroll
            for (int t = 0; t < 3; t++) tma_st3_hint(&P.out_st, qb + t * 16384 + h * 8192, col, t * 64, w.beta & 15, pol);
            tma_st3_hint(&P.out_st32, qb + 3 * 16384 + h * 4096, col, 192, w.beta & 15, pol);
          }
        }
        asm volatile("cp.async.bulk.commit_group;" ::: "memory");
        asm volatile("cp.async.bulk.wait_group.read 0;" ::: "memory");
        mbar_arrive(sbase + BAR_FREE);
        asm volatile("cp.async.bulk.wait_group 0;" ::: "memory");
        if (w.kind == 0) {
          asm volatile("fence.proxy.async;" ::: "memory");
          asm volatile("red.release.gpu.global.add.u32 [%0], 1;" ::"l"(&g_cnt[w.beta]) : "memory");
        } else if (w.mode == 1) {
          asm volatile("fence.proxy.async;" ::: "memory");
          asm volatile("st.release.gpu.global.u32 [%0], %1;" ::"l"(&g_flag[w.range]), "r"(*(volatile unsigned*)&g_epoch + 1) : "memory");
        }
      }
      __threadfence();
      if (atomicAdd(&g_done, 1) == gridDim.x - 1) { g_done = 0; g_next = 0; __threadfence(); atomicAdd(&g_epoch, 1); }
    }
  } else {
    asm volatile("setmaxnreg.inc.sync.aligned.u32 240;");
    Ctx c;
    c.sb = sbase; c.wg = wg; c.warp = warp; c.src = 0; c.mqk = 0; c.mpv = 0; c.lead = lane == 0;
    if (wg == 0) consumer<0>(c, cta, P.kp); else consumer<1>(c, cta, P.kp);
  }
}

typedef CUresult (*EncodeFn)(CUtensorMap*, CUtensorMapDataType, cuuint32_t, void*, const cuuint64_t*, const cuuint64_t*,
                             const cuuint32_t*, const cuuint32_t*, CUtensorMapInterleave, CUtensorMapSwizzle,
                             CUtensorMapL2promotion, CUtensorMapFloatOOBfill);

void make_map(EncodeFn enc, CUtensorMap* m, const void* ptr, int rank, const cuuint64_t* dims, const cuuint64_t* strides,
              const cuuint32_t* box, int promo = 2) {
  cuuint32_t es[5] = {1, 1, 1, 1, 1};
  enc(m, CU_TENSOR_MAP_DATA_TYPE_BFLOAT16, rank, const_cast<void*>(ptr), dims, strides, box, es,
      CU_TENSOR_MAP_INTERLEAVE_NONE, CU_TENSOR_MAP_SWIZZLE_128B, promo == 2 ? CU_TENSOR_MAP_L2_PROMOTION_L2_256B : promo == 1 ? CU_TENSOR_MAP_L2_PROMOTION_L2_128B : CU_TENSOR_MAP_L2_PROMOTION_NONE,
      CU_TENSOR_MAP_FLOAT_OOB_FILL_NONE);
}

}

extern "C" void kernel_launch(void* const* d_in, const int* in_sizes, int n_in, void* d_out, int out_size) {
  (void)in_sizes; (void)n_in; (void)out_size;
  static EncodeFn enc = nullptr;
  static void* o_ptr = nullptr;
  static int n_sm = 0;
  if (!enc) {
    void* fn = nullptr;
    cudaDriverEntryPointQueryResult qr;
    cudaGetDriverEntryPoint("cuTensorMapEncodeTiled", &fn, cudaEnableDefault, &qr);
    enc = (EncodeFn)fn;
    cudaGetSymbolAddress(&o_ptr, g_o);
    cudaFuncSetAttribute(mha_fused_kernel<false>, cudaFuncAttributeMaxDynamicSharedMemorySize, SMEM_BYTES);
    cudaFuncSetAttribute(mha_fused_kernel<true>, cudaFuncAttributeMaxDynamicSharedMemorySize, SMEM_BYTES);
    int dev = 0;
    cudaGetDevice(&dev);
    cudaDeviceGetAttribute(&n_sm, cudaDevAttrMultiProcessorCount, dev);
  }
  Params P;
  for (int br = 0; br < 2; br++) {
    const void* x = d_in[br * 5 + 0]; const void* kc = d_in[br * 5 + 1]; const void* vc = d_in[br * 5 + 2];
    const void* wq = d_in[br * 5 + 3]; const void* wo = d_in[br * 5 + 4];
    { cuuint64_t d[2] = {DM, (cuuint64_t)NB * SQ}, s[1] = {DM * 2}; cuuint32_t b[2] = {64, 128}, b2[2] = {64, 96};
      make_map(enc, &P.x[0][br], x, 2, d, s, b, PR_X); make_map(enc, &P.x[1][br], x, 2, d, s, b2, PR_X); }
    { cuuint64_t d[3] = {64, DM, HD / 64}, s[2] = {HD * 2, 128}; cuuint32_t b[3] = {64, 64, 2}; make_map(enc, &P.wq[br], wq, 3, d, s, b, PR_W); }
    { cuuint64_t d[3] = {64, HD, DM / 64}, s[2] = {DM * 2, 128}; cuuint32_t b[3] = {64, 64, 2}; make_map(enc, &P.wo[br], wo, 3, d, s, b, PR_W); }
    { cuuint64_t d[3] = {64, (cuuint64_t)NB * NH * SK, 2}, s[2] = {DH * 2, 128}; cuuint32_t b[3] = {64, 64, 2};
      make_map(enc, &P.kv[0][br], kc, 3, d, s, b, PR_KV); make_map(enc, &P.kv[1][br], vc, 3, d, s, b, PR_KV); }
    P.kp[br] = (const __nv_bfloat16*)kc; P.vp[br] = (const __nv_bfloat16*)vc;

  }
  { cuuint64_t d[2] = {64, (cuuint64_t)NBETA * 64 * SQ}, s[1] = {128}; cuuint32_t b[2] = {64, 128}, b2[2] = {64, 96};
    make_map(enc, &P.o_ld[0], o_ptr, 2, d, s, b); make_map(enc, &P.o_ld[1], o_ptr, 2, d, s, b2); }
  { cuuint64_t d[3] = {64, SQ, NBETA * 64}, s[2] = {128, SQ * 128}; cuuint32_t b[3] = {64, 64, 1}, b2[3] = {64, 32, 1};
    make_map(enc, &P.o_st, o_ptr, 3, d, s, b); make_map(enc, &P.o_st32, o_ptr, 3, d, s, b2); }
  { cuuint64_t d[3] = {2 * DM, SQ, NB}, s[2] = {2 * DM * 2, (cuuint64_t)SQ * 2 * DM * 2}; cuuint32_t b[3] = {64, 64, 1}, b2[3] = {64, 32, 1};
    make_map(enc, &P.out_st, d_out, 3, d, s, b); make_map(enc, &P.out_st32, d_out, 3, d, s, b2); }
  if (n_sm >= NCTA) mha_fused_kernel<false><<<NCTA, 384, SMEM_BYTES>>>(P);
  else mha_fused_kernel<true><<<n_sm, 384, SMEM_BYTES>>>(P);
}
```

```cpp
#include <cuda_runtime.h>
#include <cuda_bf16.h>
#include <cuda.h>
#include <stdint.h>

namespace {

__device__ __forceinline__ void wgmma_proj(float (&d)[64], uint64_t da, uint64_t db, int scaleD) {
  asm volatile("{\n.reg .pred p;\nsetp.ne.b32 p, %66, 0;\n"
      "wgmma.mma_async.sync.aligned.m64n128k16.f32.bf16.bf16 "
      "{%0, %1, %2, %3, %4, %5, %6, %7, %8, %9, %10, %11, %12, %13, %14, %15, %16, %17, %18, %19, %20, %21, %22, %23, %24, %25, %26, %27, %28, %29, %30, "
      "%31, %32, %33, %34, %35, %36, %37, %38, %39, %40, %41, %42, %43, %44, %45, %46, %47, %48, %49, %50, %51, %52, %53, %54, %55, %56, %57, %58, %59, %60, "
      "%61, %62, %63}, "
      "%64, %65, p, 1, 1, 1, 0;\n}\n"
      : "+f"(d[0]), "+f"(d[1]), "+f"(d[2]), "+f"(d[3]), "+f"(d[4]), "+f"(d[5]), "+f"(d[6]), "+f"(d[7]), "+f"(d[8]), "+f"(d[9]), "+f"(d[10]), "+f"(d[11]),
        "+f"(d[12]), "+f"(d[13]), "+f"(d[14]), "+f"(d[15]), "+f"(d[16]), "+f"(d[17]), "+f"(d[18]), "+f"(d[19]), "+f"(d[20]), "+f"(d[21]), "+f"(d[22]),
        "+f"(d[23]), "+f"(d[24]), "+f"(d[25]), "+f"(d[26]), "+f"(d[27]), "+f"(d[28]), "+f"(d[29]), "+f"(d[30]), "+f"(d[31]), "+f"(d[32]), "+f"(d[33]),
        "+f"(d[34]), "+f"(d[35]), "+f"(d[36]), "+f"(d[37]), "+f"(d[38]), "+f"(d[39]), "+f"(d[40]), "+f"(d[41]), "+f"(d[42]), "+f"(d[43]), "+f"(d[44]),
        "+f"(d[45]), "+f"(d[46]), "+f"(d[47]), "+f"(d[48]), "+f"(d[49]), "+f"(d[50]), "+f"(d[51]), "+f"(d[52]), "+f"(d[53]), "+f"(d[54]), "+f"(d[55]),
        "+f"(d[56]), "+f"(d[57]), "+f"(d[58]), "+f"(d[59]), "+f"(d[60]), "+f"(d[61]), "+f"(d[62]), "+f"(d[63])
      : "l"(da), "l"(db), "r"(scaleD));
}
__device__ __forceinline__ void wgmma_proj96(float (&d)[64], uint64_t da, uint64_t db, int scaleD) {
  asm volatile("{\n.reg .pred p;\nsetp.ne.b32 p, %50, 0;\n"
      "wgmma.mma_async.sync.aligned.m64n96k16.f32.bf16.bf16 "
      "{%0, %1, %2, %3, %4, %5, %6, %7, %8, %9, %10, %11, %12, %13, %14, %15, %16, %17, %18, %19, %20, %21, %22, %23, %24, %25, %26, %27, %28, %29, %30, "
      "%31, %32, %33, %34, %35, %36, %37, %38, %39, %40, %41, %42, %43, %44, %45, %46, %47}, "
      "%48, %49, p, 1, 1, 1, 0;\n}\n"
      : "+f"(d[0]), "+f"(d[1]), "+f"(d[2]), "+f"(d[3]), "+f"(d[4]), "+f"(d[5]), "+f"(d[6]), "+f"(d[7]), "+f"(d[8]), "+f"(d[9]), "+f"(d[10]), "+f"(d[11]),
        "+f"(d[12]), "+f"(d[13]), "+f"(d[14]), "+f"(d[15]), "+f"(d[16]), "+f"(d[17]), "+f"(d[18]), "+f"(d[19]), "+f"(d[20]), "+f"(d[21]), "+f"(d[22]),
        "+f"(d[23]), "+f"(d[24]), "+f"(d[25]), "+f"(d[26]), "+f"(d[27]), "+f"(d[28]), "+f"(d[29]), "+f"(d[30]), "+f"(d[31]), "+f"(d[32]), "+f"(d[33]),
        "+f"(d[34]), "+f"(d[35]), "+f"(d[36]), "+f"(d[37]), "+f"(d[38]), "+f"(d[39]), "+f"(d[40]), "+f"(d[41]), "+f"(d[42]), "+f"(d[43]), "+f"(d[44]),
        "+f"(d[45]), "+f"(d[46]), "+f"(d[47])
      : "l"(da), "l"(db), "r"(scaleD));
}
__device__ __forceinline__ void wgmma_qk(float (&d)[32], uint64_t da, uint64_t db, int scaleD) {
  asm volatile("{\n.reg .pred p;\nsetp.ne.b32 p, %34, 0;\n"
      "wgmma.mma_async.sync.aligned.m64n64k16.f32.bf16.bf16 "
      "{%0, %1, %2, %3, %4, %5, %6, %7, %8, %9, %10, %11, %12, %13, %14, %15, %16, %17, %18, %19, %20, %21, %22, %23, %24, %25, %26, %27, %28, %29, %30, "
      "%31}, "
      "%32, %33, p, 1, 1, 0, 0;\n}\n"
      : "+f"(d[0]), "+f"(d[1]), "+f"(d[2]), "+f"(d[3]), "+f"(d[4]), "+f"(d[5]), "+f"(d[6]), "+f"(d[7]), "+f"(d[8]), "+f"(d[9]), "+f"(d[10]), "+f"(d[11]),
        "+f"(d[12]), "+f"(d[13]), "+f"(d[14]), "+f"(d[15]), "+f"(d[16]), "+f"(d[17]), "+f"(d[18]), "+f"(d[19]), "+f"(d[20]), "+f"(d[21]), "+f"(d[22]),
        "+f"(d[23]), "+f"(d[24]), "+f"(d[25]), "+f"(d[26]), "+f"(d[27]), "+f"(d[28]), "+f"(d[29]), "+f"(d[30]), "+f"(d[31])
      : "l"(da), "l"(db), "r"(scaleD));
}
__device__ __forceinline__ void wgmma_pv(float (&d)[64], uint32_t a0, uint32_t a1, uint32_t a2, uint32_t a3, uint64_t db, int scaleD) {
  asm volatile("{\n.reg .pred p;\nsetp.ne.b32 p, %69, 0;\n"
      "wgmma.mma_async.sync.aligned.m64n128k16.f32.bf16.bf16 "
      "{%0, %1, %2, %3, %4, %5, %6, %7, %8, %9, %10, %11, %12, %13, %14, %15, %16, %17, %18, %19, %20, %21, %22, %23, %24, %25, %26, %27, %28, %29, %30, "
      "%31, %32, %33, %34, %35, %36, %37, %38, %39, %40, %41, %42, %43, %44, %45, %46, %47, %48, %49, %50, %51, %52, %53, %54, %55, %56, %57, %58, %59, %60, "
      "%61, %62, %63}, "
      "{%64, %65, %66, %67}, %68, p, 1, 1, 1;\n}\n"
      : "+f"(d[0]), "+f"(d[1]), "+f"(d[2]), "+f"(d[3]), "+f"(d[4]), "+f"(d[5]), "+f"(d[6]), "+f"(d[7]), "+f"(d[8]), "+f"(d[9]), "+f"(d[10]), "+f"(d[11]),
        "+f"(d[12]), "+f"(d[13]), "+f"(d[14]), "+f"(d[15]), "+f"(d[16]), "+f"(d[17]), "+f"(d[18]), "+f"(d[19]), "+f"(d[20]), "+f"(d[21]), "+f"(d[22]),
        "+f"(d[23]), "+f"(d[24]), "+f"(d[25]), "+f"(d[26]), "+f"(d[27]), "+f"(d[28]), "+f"(d[29]), "+f"(d[30]), "+f"(d[31]), "+f"(d[32]), "+f"(d[33]),
        "+f"(d[34]), "+f"(d[35]), "+f"(d[36]), "+f"(d[37]), "+f"(d[38]), "+f"(d[39]), "+f"(d[40]), "+f"(d[41]), "+f"(d[42]), "+f"(d[43]), "+f"(d[44]),
        "+f"(d[45]), "+f"(d[46]), "+f"(d[47]), "+f"(d[48]), "+f"(d[49]), "+f"(d[50]), "+f"(d[51]), "+f"(d[52]), "+f"(d[53]), "+f"(d[54]), "+f"(d[55]),
        "+f"(d[56]), "+f"(d[57]), "+f"(d[58]), "+f"(d[59]), "+f"(d[60]), "+f"(d[61]), "+f"(d[62]), "+f"(d[63])
      : "r"(a0), "r"(a1), "r"(a2), "r"(a3), "l"(db), "r"(scaleD));
}
__device__ __forceinline__ void wgmma_qk_sp(float (&d)[32], uint32_t a0, uint32_t a1, uint32_t a2, uint32_t a3, uint64_t db, int scaleD, uint32_t meta) {
  asm volatile("{\n.reg .pred p;\nsetp.ne.b32 p, %37, 0;\n"
      "wgmma.mma_async.sp.sync.aligned.m64n64k32.f32.bf16.bf16 "
      "{%0, %1, %2, %3, %4, %5, %6, %7, %8, %9, %10, %11, %12, %13, %14, %15, %16, %17, %18, %19, %20, %21, %22, %23, %24, %25, %26, %27, %28, %29, %30, "
      "%31}, "
      "{%32, %33, %34, %35}, %36, %38, 0, p, 1, 1, 0;\n}\n"
      : "+f"(d[0]), "+f"(d[1]), "+f"(d[2]), "+f"(d[3]), "+f"(d[4]), "+f"(d[5]), "+f"(d[6]), "+f"(d[7]), "+f"(d[8]), "+f"(d[9]), "+f"(d[10]), "+f"(d[11]),
        "+f"(d[12]), "+f"(d[13]), "+f"(d[14]), "+f"(d[15]), "+f"(d[16]), "+f"(d[17]), "+f"(d[18]), "+f"(d[19]), "+f"(d[20]), "+f"(d[21]), "+f"(d[22]),
        "+f"(d[23]), "+f"(d[24]), "+f"(d[25]), "+f"(d[26]), "+f"(d[27]), "+f"(d[28]), "+f"(d[29]), "+f"(d[30]), "+f"(d[31])
      : "r"(a0), "r"(a1), "r"(a2), "r"(a3), "l"(db), "r"(scaleD), "r"(meta));
}
__device__ __forceinline__ void wgmma_pv_sp(float (&d)[64], uint32_t a0, uint32_t a1, uint32_t a2, uint32_t a3, uint64_t db, int scaleD, uint32_t meta) {
  asm volatile("{\n.reg .pred p;\nsetp.ne.b32 p, %69, 0;\n"
      "wgmma.mma_async.sp.sync.aligned.m64n128k32.f32.bf16.bf16 "
      "{%0, %1, %2, %3, %4, %5, %6, %7, %8, %9, %10, %11, %12, %13, %14, %15, %16, %17, %18, %19, %20, %21, %22, %23, %24, %25, %26, %27, %28, %29, %30, "
      "%31, %32, %33, %34, %35, %36, %37, %38, %39, %40, %41, %42, %43, %44, %45, %46, %47, %48, %49, %50, %51, %52, %53, %54, %55, %56, %57, %58, %59, %60, "
      "%61, %62, %63}, "
      "{%64, %65, %66, %67}, %68, %70, 0, p, 1, 1, 1;\n}\n"
      : "+f"(d[0]), "+f"(d[1]), "+f"(d[2]), "+f"(d[3]), "+f"(d[4]), "+f"(d[5]), "+f"(d[6]), "+f"(d[7]), "+f"(d[8]), "+f"(d[9]), "+f"(d[10]), "+f"(d[11]),
        "+f"(d[12]), "+f"(d[13]), "+f"(d[14]), "+f"(d[15]), "+f"(d[16]), "+f"(d[17]), "+f"(d[18]), "+f"(d[19]), "+f"(d[20]), "+f"(d[21]), "+f"(d[22]),
        "+f"(d[23]), "+f"(d[24]), "+f"(d[25]), "+f"(d[26]), "+f"(d[27]), "+f"(d[28]), "+f"(d[29]), "+f"(d[30]), "+f"(d[31]), "+f"(d[32]), "+f"(d[33]),
        "+f"(d[34]), "+f"(d[35]), "+f"(d[36]), "+f"(d[37]), "+f"(d[38]), "+f"(d[39]), "+f"(d[40]), "+f"(d[41]), "+f"(d[42]), "+f"(d[43]), "+f"(d[44]),
        "+f"(d[45]), "+f"(d[46]), "+f"(d[47]), "+f"(d[48]), "+f"(d[49]), "+f"(d[50]), "+f"(d[51]), "+f"(d[52]), "+f"(d[53]), "+f"(d[54]), "+f"(d[55]),
        "+f"(d[56]), "+f"(d[57]), "+f"(d[58]), "+f"(d[59]), "+f"(d[60]), "+f"(d[61]), "+f"(d[62]), "+f"(d[63])
      : "r"(a0), "r"(a1), "r"(a2), "r"(a3), "l"(db), "r"(scaleD), "r"(meta));
}
__device__ __forceinline__ void wgmma_proj_init(float (&d)[64], uint64_t da, uint64_t db, int scaleD) {
  asm volatile("{\n.reg .pred p;\nsetp.ne.b32 p, %66, 0;\n"
      "wgmma.mma_async.sync.aligned.m64n128k16.f32.bf16.bf16 "
      "{%0, %1, %2, %3, %4, %5, %6, %7, %8, %9, %10, %11, %12, %13, %14, %15, %16, %17, %18, %19, %20, %21, %22, %23, %24, %25, %26, %27, %28, %29, %30, "
      "%31, %32, %33, %34, %35, %36, %37, %38, %39, %40, %41, %42, %43, %44, %45, %46, %47, %48, %49, %50, %51, %52, %53, %54, %55, %56, %57, %58, %59, %60, "
      "%61, %62, %63}, "
      "%64, %65, p, 1, 1, 1, 0;\n}\n"
      : "=f"(d[0]), "=f"(d[1]), "=f"(d[2]), "=f"(d[3]), "=f"(d[4]), "=f"(d[5]), "=f"(d[6]), "=f"(d[7]), "=f"(d[8]), "=f"(d[9]), "=f"(d[10]), "=f"(d[11]),
        "=f"(d[12]), "=f"(d[13]), "=f"(d[14]), "=f"(d[15]), "=f"(d[16]), "=f"(d[17]), "=f"(d[18]), "=f"(d[19]), "=f"(d[20]), "=f"(d[21]), "=f"(d[22]),
        "=f"(d[23]), "=f"(d[24]), "=f"(d[25]), "=f"(d[26]), "=f"(d[27]), "=f"(d[28]), "=f"(d[29]), "=f"(d[30]), "=f"(d[31]), "=f"(d[32]), "=f"(d[33]),
        "=f"(d[34]), "=f"(d[35]), "=f"(d[36]), "=f"(d[37]), "=f"(d[38]), "=f"(d[39]), "=f"(d[40]), "=f"(d[41]), "=f"(d[42]), "=f"(d[43]), "=f"(d[44]),
        "=f"(d[45]), "=f"(d[46]), "=f"(d[47]), "=f"(d[48]), "=f"(d[49]), "=f"(d[50]), "=f"(d[51]), "=f"(d[52]), "=f"(d[53]), "=f"(d[54]), "=f"(d[55]),
        "=f"(d[56]), "=f"(d[57]), "=f"(d[58]), "=f"(d[59]), "=f"(d[60]), "=f"(d[61]), "=f"(d[62]), "=f"(d[63])
      : "l"(da), "l"(db), "r"(scaleD));
}
__device__ __forceinline__ void wgmma_proj96_init(float (&d)[64], uint64_t da, uint64_t db, int scaleD) {
  asm volatile("{\n.reg .pred p;\nsetp.ne.b32 p, %50, 0;\n"
      "wgmma.mma_async.sync.aligned.m64n96k16.f32.bf16.bf16 "
      "{%0, %1, %2, %3, %4, %5, %6, %7, %8, %9, %10, %11, %12, %13, %14, %15, %16, %17, %18, %19, %20, %21, %22, %23, %24, %25, %26, %27, %28, %29, %30, "
      "%31, %32, %33, %34, %35, %36, %37, %38, %39, %40, %41, %42, %43, %44, %45, %46, %47}, "
      "%48, %49, p, 1, 1, 1, 0;\n}\n"
      : "=f"(d[0]), "=f"(d[1]), "=f"(d[2]), "=f"(d[3]), "=f"(d[4]), "=f"(d[5]), "=f"(d[6]), "=f"(d[7]), "=f"(d[8]), "=f"(d[9]), "=f"(d[10]), "=f"(d[11]),
        "=f"(d[12]), "=f"(d[13]), "=f"(d[14]), "=f"(d[15]), "=f"(d[16]), "=f"(d[17]), "=f"(d[18]), "=f"(d[19]), "=f"(d[20]), "=f"(d[21]), "=f"(d[22]),
        "=f"(d[23]), "=f"(d[24]), "=f"(d[25]), "=f"(d[26]), "=f"(d[27]), "=f"(d[28]), "=f"(d[29]), "=f"(d[30]), "=f"(d[31]), "=f"(d[32]), "=f"(d[33]),
        "=f"(d[34]), "=f"(d[35]), "=f"(d[36]), "=f"(d[37]), "=f"(d[38]), "=f"(d[39]), "=f"(d[40]), "=f"(d[41]), "=f"(d[42]), "=f"(d[43]), "=f"(d[44]),
        "=f"(d[45]), "=f"(d[46]), "=f"(d[47])
      : "l"(da), "l"(db), "r"(scaleD));
}
__device__ __forceinline__ void wgmma_qk_init(float (&d)[32], uint64_t da, uint64_t db, int scaleD) {
  asm volatile("{\n.reg .pred p;\nsetp.ne.b32 p, %34, 0;\n"
      "wgmma.mma_async.sync.aligned.m64n64k16.f32.bf16.bf16 "
      "{%0, %1, %2, %3, %4, %5, %6, %7, %8, %9, %10, %11, %12, %13, %14, %15, %16, %17, %18, %19, %20, %21, %22, %23, %24, %25, %26, %27, %28, %29, %30, "
      "%31}, "
      "%32, %33, p, 1, 1, 0, 0;\n}\n"
      : "=f"(d[0]), "=f"(d[1]), "=f"(d[2]), "=f"(d[3]), "=f"(d[4]), "=f"(d[5]), "=f"(d[6]), "=f"(d[7]), "=f"(d[8]), "=f"(d[9]), "=f"(d[10]), "=f"(d[11]),
        "=f"(d[12]), "=f"(d[13]), "=f"(d[14]), "=f"(d[15]), "=f"(d[16]), "=f"(d[17]), "=f"(d[18]), "=f"(d[19]), "=f"(d[20]), "=f"(d[21]), "=f"(d[22]),
        "=f"(d[23]), "=f"(d[24]), "=f"(d[25]), "=f"(d[26]), "=f"(d[27]), "=f"(d[28]), "=f"(d[29]), "=f"(d[30]), "=f"(d[31])
      : "l"(da), "l"(db), "r"(scaleD));
}
__device__ __forceinline__ void wgmma_pv_init(float (&d)[64], uint32_t a0, uint32_t a1, uint32_t a2, uint32_t a3, uint64_t db, int scaleD) {
  asm volatile("{\n.reg .pred p;\nsetp.ne.b32 p, %69, 0;\n"
      "wgmma.mma_async.sync.aligned.m64n128k16.f32.bf16.bf16 "
      "{%0, %1, %2, %3, %4, %5, %6, %7, %8, %9, %10, %11, %12, %13, %14, %15, %16, %17, %18, %19, %20, %21, %22, %23, %24, %25, %26, %27, %28, %29, %30, "
      "%31, %32, %33, %34, %35, %36, %37, %38, %39, %40, %41, %42, %43, %44, %45, %46, %47, %48, %49, %50, %51, %52, %53, %54, %55, %56, %57, %58, %59, %60, "
      "%61, %62, %63}, "
      "{%64, %65, %66, %67}, %68, p, 1, 1, 1;\n}\n"
      : "=f"(d[0]), "=f"(d[1]), "=f"(d[2]), "=f"(d[3]), "=f"(d[4]), "=f"(d[5]), "=f"(d[6]), "=f"(d[7]), "=f"(d[8]), "=f"(d[9]), "=f"(d[10]), "=f"(d[11]),
        "=f"(d[12]), "=f"(d[13]), "=f"(d[14]), "=f"(d[15]), "=f"(d[16]), "=f"(d[17]), "=f"(d[18]), "=f"(d[19]), "=f"(d[20]), "=f"(d[21]), "=f"(d[22]),
        "=f"(d[23]), "=f"(d[24]), "=f"(d[25]), "=f"(d[26]), "=f"(d[27]), "=f"(d[28]), "=f"(d[29]), "=f"(d[30]), "=f"(d[31]), "=f"(d[32]), "=f"(d[33]),
        "=f"(d[34]), "=f"(d[35]), "=f"(d[36]), "=f"(d[37]), "=f"(d[38]), "=f"(d[39]), "=f"(d[40]), "=f"(d[41]), "=f"(d[42]), "=f"(d[43]), "=f"(d[44]),
        "=f"(d[45]), "=f"(d[46]), "=f"(d[47]), "=f"(d[48]), "=f"(d[49]), "=f"(d[50]), "=f"(d[51]), "=f"(d[52]), "=f"(d[53]), "=f"(d[54]), "=f"(d[55]),
        "=f"(d[56]), "=f"(d[57]), "=f"(d[58]), "=f"(d[59]), "=f"(d[60]), "=f"(d[61]), "=f"(d[62]), "=f"(d[63])
      : "r"(a0), "r"(a1), "r"(a2), "r"(a3), "l"(db), "r"(scaleD));
}
__device__ __forceinline__ void wgmma_qk_sp_init(float (&d)[32], uint32_t a0, uint32_t a1, uint32_t a2, uint32_t a3, uint64_t db, int scaleD, uint32_t meta) {
  asm volatile("{\n.reg .pred p;\nsetp.ne.b32 p, %37, 0;\n"
      "wgmma.mma_async.sp.sync.aligned.m64n64k32.f32.bf16.bf16 "
      "{%0, %1, %2, %3, %4, %5, %6, %7, %8, %9, %10, %11, %12, %13, %14, %15, %16, %17, %18, %19, %20, %21, %22, %23, %24, %25, %26, %27, %28, %29, %30, "
      "%31}, "
      "{%32, %33, %34, %35}, %36, %38, 0, p, 1, 1, 0;\n}\n"
      : "=f"(d[0]), "=f"(d[1]), "=f"(d[2]), "=f"(d[3]), "=f"(d[4]), "=f"(d[5]), "=f"(d[6]), "=f"(d[7]), "=f"(d[8]), "=f"(d[9]), "=f"(d[10]), "=f"(d[11]),
        "=f"(d[12]), "=f"(d[13]), "=f"(d[14]), "=f"(d[15]), "=f"(d[16]), "=f"(d[17]), "=f"(d[18]), "=f"(d[19]), "=f"(d[20]), "=f"(d[21]), "=f"(d[22]),
        "=f"(d[23]), "=f"(d[24]), "=f"(d[25]), "=f"(d[26]), "=f"(d[27]), "=f"(d[28]), "=f"(d[29]), "=f"(d[30]), "=f"(d[31])
      : "r"(a0), "r"(a1), "r"(a2), "r"(a3), "l"(db), "r"(scaleD), "r"(meta));
}
__device__ __forceinline__ void wgmma_pv_sp_init(float (&d)[64], uint32_t a0, uint32_t a1, uint32_t a2, uint32_t a3, uint64_t db, int scaleD, uint32_t meta) {
  asm volatile("{\n.reg .pred p;\nsetp.ne.b32 p, %69, 0;\n"
      "wgmma.mma_async.sp.sync.aligned.m64n128k32.f32.bf16.bf16 "
      "{%0, %1, %2, %3, %4, %5, %6, %7, %8, %9, %10, %11, %12, %13, %14, %15, %16, %17, %18, %19, %20, %21, %22, %23, %24, %25, %26, %27, %28, %29, %30, "
      "%31, %32, %33, %34, %35, %36, %37, %38, %39, %40, %41, %42, %43, %44, %45, %46, %47, %48, %49, %50, %51, %52, %53, %54, %55, %56, %57, %58, %59, %60, "
      "%61, %62, %63}, "
      "{%64, %65, %66, %67}, %68, %70, 0, p, 1, 1, 1;\n}\n"
      : "=f"(d[0]), "=f"(d[1]), "=f"(d[2]), "=f"(d[3]), "=f"(d[4]), "=f"(d[5]), "=f"(d[6]), "=f"(d[7]), "=f"(d[8]), "=f"(d[9]), "=f"(d[10]), "=f"(d[11]),
        "=f"(d[12]), "=f"(d[13]), "=f"(d[14]), "=f"(d[15]), "=f"(d[16]), "=f"(d[17]), "=f"(d[18]), "=f"(d[19]), "=f"(d[20]), "=f"(d[21]), "=f"(d[22]),
        "=f"(d[23]), "=f"(d[24]), "=f"(d[25]), "=f"(d[26]), "=f"(d[27]), "=f"(d[28]), "=f"(d[29]), "=f"(d[30]), "=f"(d[31]), "=f"(d[32]), "=f"(d[33]),
        "=f"(d[34]), "=f"(d[35]), "=f"(d[36]), "=f"(d[37]), "=f"(d[38]), "=f"(d[39]), "=f"(d[40]), "=f"(d[41]), "=f"(d[42]), "=f"(d[43]), "=f"(d[44]),
        "=f"(d[45]), "=f"(d[46]), "=f"(d[47]), "=f"(d[48]), "=f"(d[49]), "=f"(d[50]), "=f"(d[51]), "=f"(d[52]), "=f"(d[53]), "=f"(d[54]), "=f"(d[55]),
        "=f"(d[56]), "=f"(d[57]), "=f"(d[58]), "=f"(d[59]), "=f"(d[60]), "=f"(d[61]), "=f"(d[62]), "=f"(d[63])
      : "r"(a0), "r"(a1), "r"(a2), "r"(a3), "l"(db), "r"(scaleD), "r"(meta));
}

constexpr int NB = 16, SQ = 224, DM = 640, NH = 32, SK = 1024, DH = 128;
constexpr int HD = NH * DH;
constexpr int NBETA = 2 * NB;
constexpr int NCTA = 132;
constexpr int NS = 10;
constexpr int SLOT = 16384;
constexpr int QBUF_OFF = NS * SLOT;
constexpr int QBUF_BYTES = 3 * 16384 + 8192;
constexpr int NSX = NS + 4;
constexpr int BAR_OFF = NSX * SLOT;
constexpr int BAR_FULL = BAR_OFF;
constexpr int BAR_EMPTY = BAR_OFF + 8 * NSX;
constexpr int BAR_STG = BAR_OFF + 16 * NSX;
constexpr int BAR_DESC = BAR_STG + 32;
constexpr int BAR_GO = BAR_DESC + 8;
constexpr int DESC_OFF = BAR_GO + 8;
constexpr int EPOCH_OFF = DESC_OFF + 16;
constexpr int TRACE_OFF = EPOCH_OFF + 8;
constexpr int SMEM_BYTES = TRACE_OFF;
constexpr float SM_C = 0.08838834764831845f * 1.4426950408889634f;
constexpr float SUM_HI = 1099511627776.f, SUM_LO = 1.f / 1099511627776.f;
constexpr uint32_t META_QK = 0xEEEE4444u;
constexpr uint32_t META_PV = 0x44EEEE44u;

#define QK_EARLY_MASK 3
#define QD_FIRST 0
#define QSTART 0
#define EARLY_BEG 1
#define KV_WIN_TILES 6
#define PR_KV 2
#define PR_X 2
#define PR_W 2
#define REG_C 232
#define REG_P 40
#define GO_P 4
#define P_POS 256
#define P_STRIDE 32
#define B_LATE 13
#define H_LATE 25
#define RANGE_ORDER 0, 1, 2, 3, 4, 5, 6, 7, 8, 9, 10, 11, 12, 13, 14, 15, 16, 17, 18, 19, 20, 21, 22, 23, 24, 25
#define P_EARLY 13
#define RANGE_TABLE 0, 69, 139, 208, 277, 344, 410, 474, 536, 595, 653, 704, 760, 813, 862, 907, 945, 988, 1024, 1063, 1098, 1121, 1145, 1173, 1186, 1200, 1216

struct Params {
  CUtensorMap x[2][2], wq[2], kv[2][2], wo[2];
  CUtensorMap o_ld[2], o_st[2], out_st[2];
  const __nv_bfloat16* kp[2];
  const __nv_bfloat16* vp[2];
};

__device__ __nv_bfloat16 g_o[(size_t)NBETA * SQ * HD];
__device__ unsigned g_cnt[2][NBETA];
__device__ unsigned g_epoch, g_next;
__device__ __align__(128) uint8_t g_part[(size_t)NCTA * QBUF_BYTES];
__device__ unsigned g_flag[NCTA];

__device__ __forceinline__ uint32_t smem_u32(const void* p) { return (uint32_t)__cvta_generic_to_shared(p); }
__device__ __forceinline__ void mbar_init(uint32_t bar, int cnt) {
  asm volatile("mbarrier.init.shared::cta.b64 [%0], %1;" ::"r"(bar), "r"(cnt) : "memory");
}
__device__ __forceinline__ void mbar_expect_tx(uint32_t bar, int bytes) {
  asm volatile("mbarrier.arrive.expect_tx.shared::cta.b64 _, [%0], %1;" ::"r"(bar), "r"(bytes) : "memory");
}
__device__ __forceinline__ void mbar_arrive(uint32_t bar) {
  asm volatile("mbarrier.arrive.shared::cta.b64 _, [%0];" ::"r"(bar) : "memory");
}
__device__ __forceinline__ void mbar_arrive_warp(uint32_t bar) {
  asm volatile("{\n.reg .pred p;\nelect.sync _|p, 0xffffffff;\n@p mbarrier.arrive.shared::cta.b64 _, [%0];\n}" ::"r"(bar) : "memory");
}
__device__ __forceinline__ int lane_now() { int l; asm volatile("mov.u32 %0, %%laneid;" : "=r"(l)); return l; }
__device__ __forceinline__ bool mbar_try(uint32_t bar, uint32_t parity) {
  uint32_t ok;
  asm volatile("{\n.reg .pred p;\nmbarrier.try_wait.parity.shared::cta.b64 p, [%1], %2;\nselp.u32 %0, 1, 0, p;\n}"
               : "=r"(ok) : "r"(bar), "r"(parity) : "memory");
  return ok;
}
__device__ __forceinline__ bool mbar_test(uint32_t bar, uint32_t parity) {
  uint32_t ok;
  asm volatile("{\n.reg .pred p;\nmbarrier.test_wait.parity.shared::cta.b64 p, [%1], %2;\nselp.u32 %0, 1, 0, p;\n}"
               : "=r"(ok) : "r"(bar), "r"(parity) : "memory");
  return ok;
}
__device__ __forceinline__ void mbar_wait(uint32_t bar, uint32_t parity) {
  uint32_t n = 0;
  while (!mbar_try(bar, parity)) {
    if (++n > (1u << 22)) __trap();
  }
}
__device__ __forceinline__ void mbar_wait_w(uint32_t bar, uint32_t parity) {
  uint32_t n = 0;
  while (!__all_sync(0xffffffffu, mbar_try(bar, parity))) {
    if (++n > (1u << 22)) __trap();
  }
}
__device__ __forceinline__ void tma_ld2(uint32_t dst, const CUtensorMap* m, int c0, int c1, uint32_t bar) {
  asm volatile("cp.async.bulk.tensor.2d.shared::cluster.global.mbarrier::complete_tx::bytes [%0], [%1, {%3, %4}], [%2];"
               ::"r"(dst), "l"(m), "r"(bar), "r"(c0), "r"(c1) : "memory");
}
__device__ __forceinline__ void tma_ld2_hint(uint32_t dst, const CUtensorMap* m, int c0, int c1, uint32_t bar, uint64_t pol) {
  asm volatile("cp.async.bulk.tensor.2d.shared::cluster.global.mbarrier::complete_tx::bytes.L2::cache_hint [%0], [%1, {%3, %4}], [%2], %5;"
               ::"r"(dst), "l"(m), "r"(bar), "r"(c0), "r"(c1), "l"(pol) : "memory");
}
__device__ __forceinline__ void tma_ld3(uint32_t dst, const CUtensorMap* m, int c0, int c1, int c2, uint32_t bar) {
  asm volatile("cp.async.bulk.tensor.3d.shared::cluster.global.mbarrier::complete_tx::bytes [%0], [%1, {%3, %4, %5}], [%2];"
               ::"r"(dst), "l"(m), "r"(bar), "r"(c0), "r"(c1), "r"(c2) : "memory");
}
__device__ __forceinline__ void tma_ld3_hint(uint32_t dst, const CUtensorMap* m, int c0, int c1, int c2, uint32_t bar, uint64_t pol) {
  asm volatile("cp.async.bulk.tensor.3d.shared::cluster.global.mbarrier::complete_tx::bytes.L2::cache_hint"
               " [%0], [%1, {%3, %4, %5}], [%2], %6;"
               ::"r"(dst), "l"(m), "r"(bar), "r"(c0), "r"(c1), "r"(c2), "l"(pol) : "memory");
}
__device__ __forceinline__ void tma_st3(const CUtensorMap* m, uint32_t src, int c0, int c1, int c2) {
  asm volatile("cp.async.bulk.tensor.3d.global.shared::cta.bulk_group [%0, {%2, %3, %4}], [%1];"
               ::"l"(m), "r"(src), "r"(c0), "r"(c1), "r"(c2) : "memory");
}
__device__ __forceinline__ void tma_st3_hint(const CUtensorMap* m, uint32_t src, int c0, int c1, int c2, uint64_t pol) {
  asm volatile("cp.async.bulk.tensor.3d.global.shared::cta.bulk_group.L2::cache_hint [%0, {%2, %3, %4}], [%1], %5;"
               ::"l"(m), "r"(src), "r"(c0), "r"(c1), "r"(c2), "l"(pol) : "memory");
}
#define ELECT "{\n.reg .pred p;\nelect.sync _|p, 0xffffffff;\n@p "
__device__ __forceinline__ void tma_st3_w(const CUtensorMap* m, uint32_t src, int c0, int c1, int c2) {
  asm volatile(ELECT "cp.async.bulk.tensor.3d.global.shared::cta.bulk_group [%0, {%2, %3, %4}], [%1];\n}"
               ::"l"(m), "r"(src), "r"(c0), "r"(c1), "r"(c2) : "memory");
}
__device__ __forceinline__ void tma_st3_hint_w(const CUtensorMap* m, uint32_t src, int c0, int c1, int c2, uint64_t pol) {
  asm volatile(ELECT "cp.async.bulk.tensor.3d.global.shared::cta.bulk_group.L2::cache_hint [%0, {%2, %3, %4}], [%1], %5;\n}"
               ::"l"(m), "r"(src), "r"(c0), "r"(c1), "r"(c2), "l"(pol) : "memory");
}
__device__ __forceinline__ void mbar_arrive8_w(uint32_t bar) {
  asm volatile(ELECT "mbarrier.arrive.shared::cta.b64 _, [%0], 8;\n}" ::"r"(bar) : "memory");
}
__device__ __forceinline__ void bulk_commit() { asm volatile("cp.async.bulk.commit_group;" ::: "memory"); }
template <int N> __device__ __forceinline__ void bulk_wait_read() { asm volatile("cp.async.bulk.wait_group.read %0;" ::"n"(N) : "memory"); }
__device__ __forceinline__ void wg_fence() { asm volatile("wgmma.fence.sync.aligned;" ::: "memory"); }
__device__ __forceinline__ void wg_commit() { asm volatile("wgmma.commit_group.sync.aligned;" ::: "memory"); }
template <int N> __device__ __forceinline__ void wg_wait() { asm volatile("wgmma.wait_group.sync.aligned %0;" ::"n"(N) : "memory"); }
__device__ __forceinline__ void fence_async_smem() { asm volatile("fence.proxy.async.shared::cta;" ::: "memory"); }
__device__ __forceinline__ void bar_sync(int id, int n) { asm volatile("bar.sync %0, %1;" ::"r"(id), "r"(n) : "memory"); }
template <int N> __device__ __forceinline__ void reg_fence(float (&a)[N]) {
#pragma unroll
  for (int i = 0; i < N; i++) asm volatile("" : "+f"(a[i])::"memory");
}
template <int N> __device__ __forceinline__ void reg_fence(uint32_t (&a)[N]) {
#pragma unroll
  for (int i = 0; i < N; i++) asm volatile("" : "+r"(a[i])::"memory");
}
__device__ __forceinline__ float ex2(float x) { float y; asm("ex2.approx.ftz.f32 %0, %1;" : "=f"(y) : "f"(x)); return y; }
__device__ __forceinline__ uint32_t pack_bf16(float lo, float hi) {
  uint32_t r; asm("cvt.rn.bf16x2.f32 %0, %1, %2;" : "=r"(r) : "f"(hi), "f"(lo)); return r;
}
__device__ __forceinline__ void stsm4(uint32_t a, uint32_t r0, uint32_t r1, uint32_t r2, uint32_t r3) {
  asm volatile("stmatrix.sync.aligned.m8n8.x4.shared.b16 [%0], {%1, %2, %3, %4};" ::"r"(a), "r"(r0), "r"(r1), "r"(r2), "r"(r3) : "memory");
}
__device__ __forceinline__ void stsm4t(uint32_t a, uint32_t r0, uint32_t r1, uint32_t r2, uint32_t r3) {
  asm volatile("stmatrix.sync.aligned.m8n8.x4.trans.shared.b16 [%0], {%1, %2, %3, %4};" ::"r"(a), "r"(r0), "r"(r1), "r"(r2), "r"(r3) : "memory");
}
__device__ __forceinline__ void ldsm4(uint32_t a, uint32_t& r0, uint32_t& r1, uint32_t& r2, uint32_t& r3) {
  asm volatile("ldmatrix.sync.aligned.m8n8.x4.shared.b16 {%0, %1, %2, %3}, [%4];" : "=r"(r0), "=r"(r1), "=r"(r2), "=r"(r3) : "r"(a) : "memory");
}
__device__ __forceinline__ void sts16(uint32_t a, uint32_t v) { asm volatile("st.shared.u16 [%0], %1;" ::"r"(a), "h"((uint16_t)v) : "memory"); }
__device__ __forceinline__ void mma16816(float& c0, float& c1, float& c2, float& c3, uint32_t a0, uint32_t a1, uint32_t a2, uint32_t a3,
                                         uint32_t b0, uint32_t b1) {
  asm volatile("mma.sync.aligned.m16n8k16.row.col.f32.bf16.bf16.f32 {%0, %1, %2, %3}, {%4, %5, %6, %7}, {%8, %9}, {%0, %1, %2, %3};"
               : "+f"(c0), "+f"(c1), "+f"(c2), "+f"(c3) : "r"(a0), "r"(a1), "r"(a2), "r"(a3), "r"(b0), "r"(b1));
}
__device__ __forceinline__ uint32_t sdesc(uint32_t addr, uint32_t lbo) { return (addr >> 4) + ((lbo >> 4) << 16); }
__device__ __forceinline__ uint64_t desc64(uint32_t lo, uint32_t hi) { uint64_t d; asm("mov.b64 %0, {%1, %2};" : "=l"(d) : "r"(lo), "r"(hi)); return d; }
__device__ __forceinline__ void dadd(uint64_t& d, uint32_t inc) {
  asm("{\n.reg .b32 l, h;\nmov.b64 {l, h}, %0;\nadd.u32 l, l, %1;\nmov.b64 %0, {l, h};\n}" : "+l"(d) : "r"(inc));
}

struct Ring {
  uint32_t slot, phase, xp;
  __device__ __forceinline__ void uniform() {
    slot = __shfl_sync(0xffffffffu, slot, 0); phase = __shfl_sync(0xffffffffu, phase, 0); xp = __shfl_sync(0xffffffffu, xp, 0);
  }
  __device__ __forceinline__ void next() { if (++slot == NS) { slot = 0; phase ^= 1; } }
  __device__ __forceinline__ void next_if(bool p) { slot += p; if (slot == NS) { slot = 0; phase ^= 1; } }
};
__device__ __forceinline__ uint32_t borrow(int ks, int n) { const int k = ks + 1; return k >= 4 && (k | 3) - 1 <= n ? k & 3 : 3; }

constexpr uint32_t Q_RANGES = NBETA * NH + P_EARLY * 5;
constexpr int TAIL_STEPS = (NBETA - P_EARLY) * 64, NRANGE = NCTA / 5;
struct Work { int kind, mode, k0, nsteps, range, beta, sub; };
struct Sched { uint16_t queue[Q_RANGES]; uint32_t piece[NRANGE + 1][4]; };
constexpr Sched make_sched() {
  Sched s{};
  int q = 0, a = 0;
  for (int pass = 0; pass < 2; pass++)
    for (int b = pass ? B_LATE : 0; b < NBETA; b++)
      for (int h = pass ? H_LATE : 0; h < (pass || b < B_LATE ? NH : H_LATE); h++) {
        if (a >= P_POS && (a - P_POS) % P_STRIDE == 0 && (a - P_POS) / P_STRIDE < P_EARLY)
          for (int col = 0; col < 5; col++) s.queue[q++] = 0x8000 | col << 8 | (a - P_POS) / P_STRIDE;
        s.queue[q++] = b << 5 | h;
        a++;
      }
  constexpr int B[NRANGE + 1] = {RANGE_TABLE};
  constexpr int ORD[NRANGE] = {RANGE_ORDER};
  for (int g = 0; g <= NRANGE; g++) {
    int n = 0;
    if (g < NRANGE) {
      const int r = ORD[g];
      for (int pos = B[r]; pos < B[r + 1];) {
        const int te = (pos | 63) + 1, stop = B[r + 1] < te ? B[r + 1] : te, mode = pos & 63 ? 1 : stop == te ? 0 : 2;
        int f = 0;
        if (mode == 2) { f = 1; while (B[r + 1 + f] < te) f++; }
        s.piece[g][n++] = 1u << 30 | mode << 28 | (te - stop) << 22 | (stop - pos - 1) << 16 | r << 11 | f << 5 | (P_EARLY + (pos >> 6));
        pos = stop;
      }
    }
    for (; n < 4; n++) s.piece[g][n] = 2u << 30;
  }
  return s;
}
__constant__ Sched c_sched = make_sched();
__device__ __forceinline__ Work decode(uint32_t d) {
  Work w;
  w.kind = d >> 30; if (w.kind == 3) w.kind = 1;
  w.mode = (d >> 28) & 3; w.k0 = (d >> 22) & 63;
  if (w.kind == 0) { w.beta = (d >> 5) & 31; w.sub = d & 31; w.nsteps = DM / 64; }
  else { w.beta = d & 31; w.sub = (d >> 8) & 7; w.nsteps = ((d >> 16) & 63) + 1; }
  w.range = ((d >> 11) & 31) * 5 + w.sub;
  return w;
}

__device__ __forceinline__ bool reached(const unsigned* cnt, unsigned target) {
  unsigned v;
  asm volatile("ld.acquire.gpu.global.u32 %0, [%1];" : "=r"(v) : "l"(cnt) : "memory");
  return (int)(v - target) >= 0;
}
__device__ __forceinline__ void wait_count(const unsigned* cnt, unsigned target) {
  unsigned n = 0;
  while (!reached(cnt, target)) { if (++n > (1u << 24)) __trap(); }
}
__device__ __forceinline__ uint32_t lds(uint32_t a) { uint32_t v; asm volatile("ld.volatile.shared.u32 %0, [%1];" : "=r"(v) : "r"(a) : "memory"); return v; }

#define TRACE(u, e)
#define T3(u, e)
#define T2C(u, e)
#define T2P(u, r, e)
#define TRACE_P(u, e)
#define TRACE_IN(u, e)

struct Ctx {
  uint32_t sb;
  int wg, warp;
  uint32_t mqk, mpv;
  bool lead;
  int src;
};
template <int N> __device__ __forceinline__ uint32_t dhi(uint32_t lo) { return 0x40000040u + (lo >> (26 + N)); }
template <int N> __device__ __forceinline__ uint64_t full_desc(uint32_t addr, uint32_t slot) { return desc64(addr >> 4, dhi<N>(slot)); }
__device__ __forceinline__ void release(const Ctx& c, uint32_t slot) {
  if (c.lead) mbar_arrive(c.sb + BAR_EMPTY + slot * 8);
}
__device__ __forceinline__ uint32_t acquire(const Ctx& c, Ring& r) {
  const uint32_t s = r.slot;
  mbar_wait_w(c.sb + BAR_FULL + s * 8, r.phase);
  r.next();
  return s;
}
__device__ __forceinline__ void mbar_wait2_w(uint32_t b0, uint32_t p0, uint32_t b1, uint32_t p1) {
  uint32_t n = 0;
  while (!__all_sync(0xffffffffu, mbar_try(b0, p0) & mbar_try(b1, p1))) {
    if (++n > (1u << 22)) __trap();
  }
}
__device__ __forceinline__ void acquire2(const Ctx& c, Ring& r, uint32_t& s0, uint32_t& s1, bool wait = true) {
  const uint32_t p0 = r.phase;
  s0 = r.slot; r.next(); s1 = r.slot;
  if (wait) mbar_wait2_w(c.sb + BAR_FULL + s0 * 8, p0, c.sb + BAR_FULL + s1 * 8, r.phase);
  r.next();
}
__device__ __forceinline__ void staged(const Ctx& c, int part) {
  fence_async_smem();
  __syncwarp();
  mbar_arrive_warp(c.sb + BAR_STG + c.wg * 16 + part * 8);
}

template <bool FIRST, bool HI>
__device__ __forceinline__ void proj_half(const Ctx& c, float (&acc)[64], uint32_t w, uint32_t x) {
  uint64_t a = full_desc<0>(c.sb + w * SLOT + c.wg * 8192, x), b = full_desc<1>(c.sb + x * SLOT, x);
  wg_fence();
  if (HI) { if (FIRST) wgmma_proj96_init(acc, a, b, 0); else wgmma_proj96(acc, a, b, 1); }
  else { if (FIRST) wgmma_proj_init(acc, a, b, 0); else wgmma_proj(acc, a, b, 1); }
#pragma unroll
  for (int k = 1; k < 4; k++) { dadd(a, 128); dadd(b, 2); if (HI) wgmma_proj96(acc, a, b, 1); else wgmma_proj(acc, a, b, 1); }
  wg_commit();
}

__device__ __forceinline__ void proj_store16(uint32_t a, const float* f, float sc) {
  stsm4t(a, pack_bf16(f[0] * sc, f[1] * sc), pack_bf16(f[2] * sc, f[3] * sc), pack_bf16(f[4] * sc, f[5] * sc), pack_bf16(f[6] * sc, f[7] * sc));
}

__device__ __forceinline__ uint32_t stage_off(const Ctx& c) {
  const int lane = lane_now(), mi = lane >> 3, r8 = lane & 7;
  return ((mi >> 1) * 8 + r8) * 128 + (((2 * c.warp + (mi & 1)) ^ r8) << 4);
}
__device__ __forceinline__ void stage_lo(const Ctx& c, const float (&a0)[64], float sc) {
  const uint32_t lane_off = c.sb + QBUF_OFF + c.wg * 8192 + stage_off(c);
#pragma unroll
  for (int jj = 0; jj < 8; jj++) proj_store16(lane_off + (jj >> 2) * 16384 + (jj & 3) * 2048, &a0[jj * 8], sc);
}
__device__ __forceinline__ uint32_t q3_swz(uint32_t r8) { return ((r8 & 3) << 1) | (r8 >> 2); }
template <bool IS_Q>
__device__ __forceinline__ void stage_hi(const Ctx& c, const float (&a1)[64], float sc) {
  const uint32_t off = stage_off(c), lane_off = c.sb + QBUF_OFF + 2 * 16384 + c.wg * 8192 + off;
#pragma unroll
  for (int jj = 0; jj < 4; jj++) proj_store16(lane_off + jj * 2048, &a1[jj * 8], sc);
  const uint32_t r8 = (off >> 7) & 7;
  const uint32_t t3 = c.sb + QBUF_OFF + 3 * 16384 + c.wg * 4096 + (IS_Q ? off ^ ((r8 ^ q3_swz(r8)) << 4) : off);
  proj_store16(t3, &a1[32], sc);
  proj_store16(t3 + 2048, &a1[40], sc);
}

__device__ __forceinline__ void add16(uint32_t a, float* f) {
  uint32_t r[4];
  asm volatile("ldmatrix.sync.aligned.m8n8.x4.trans.shared.b16 {%0, %1, %2, %3}, [%4];"
               : "=r"(r[0]), "=r"(r[1]), "=r"(r[2]), "=r"(r[3]) : "r"(a) : "memory");
#pragma unroll
  for (int i = 0; i < 4; i++) { f[2 * i] += __uint_as_float(r[i] << 16); f[2 * i + 1] += __uint_as_float(r[i] & 0xffff0000u); }
}

__device__ __forceinline__ void trace_dump(const Ctx& c) {
}
struct Slots { uint32_t w, x; };
__device__ __forceinline__ void proj_begin(const Ctx& c, Ring& r, float (&a0)[64], Slots& h, bool wait) {
  acquire2(c, r, h.w, h.x, wait);
  proj_half<true, false>(c, a0, h.w, h.x);
}
__device__ __forceinline__ void proj_main(const Ctx& c, Ring& r, float (&a0)[64], float (&a1)[64], Slots& h, int kind, int n, int unit) {
  T2C(unit, 1);
  uint32_t y = acquire(c, r), w = h.w, x, py;
  T2C(unit, 2);
  wg_wait<0>();
  T2C(unit, 3);
  release(c, h.x);
  proj_half<true, true>(c, a1, w, y);
  int ks = 1;
#pragma unroll 1
  while (true) {
    const uint32_t b = borrow(ks, n), pw = w, p0 = r.phase;
    w = r.slot; r.next();
    const uint32_t p1 = b != 3 ? r.xp : r.phase;
    x = b != 3 ? NS + b : r.slot; r.next_if(b == 3);
    mbar_wait2_w(c.sb + BAR_FULL + w * 8, p0, c.sb + BAR_FULL + x * 8, p1);
    if (ks < 10) T2C(unit, ks * 4);
    wg_wait<0>();
    if (ks < 10) T2C(unit, ks * 4 + 1);
    release(c, pw); release(c, y);
    proj_half<false, false>(c, a0, w, x);
    py = b == 0 ? r.xp : r.phase;
    y = b == 0 ? NS + 3 : r.slot; r.next_if(b != 0);
    r.xp ^= b == 2;
    if (++ks == n) break;
    mbar_wait_w(c.sb + BAR_FULL + y * 8, py);
    if (ks < 11) T2C(unit, ks * 4 - 2);
    wg_wait<0>();
    if (ks < 11) T2C(unit, ks * 4 - 1);
    release(c, x);
    proj_half<false, true>(c, a1, w, y);
  }
  {
    const uint32_t pe = r.xp ^ (unit & 1) ^ 1, k0 = kind == 0 ? r.slot : y, pk = kind == 0 ? r.phase : py;
    uint32_t cnt = 0;
    while (true) {
      bool ok = mbar_try(c.sb + BAR_FULL + y * 8, py) & mbar_try(c.sb + BAR_FULL + k0 * 8, pk);
#pragma unroll
      for (int t = 0; t < 2; t++) ok &= mbar_try(c.sb + BAR_EMPTY + (NS + t) * 8, pe);
      if (__all_sync(0xffffffffu, ok)) break;
      if (++cnt > (1u << 22)) __trap();
    }
  }
  T2C(unit, 38);
  wg_wait<0>();
  T2C(unit, 39);
  release(c, x);
  proj_half<false, true>(c, a1, w, y);
  h.w = w; h.x = y;
  reg_fence(a0);
}
__device__ __forceinline__ void wait_hi_free(const Ctx& c, const Ring& r, int unit) {
  const uint32_t pe = r.xp ^ (unit & 1) ^ 1;
  mbar_wait2_w(c.sb + BAR_EMPTY + (NS + 2) * 8, pe, c.sb + BAR_EMPTY + (NS + 3) * 8, pe);
}
__device__ __forceinline__ void proj_end(const Ctx& c, float (&a1)[64], const Slots& h) {
  wg_wait<0>();
#pragma unroll
  for (int i = 0; i < 48; i++) asm volatile("" : "+f"(a1[i])::"memory");
  release(c, h.w); release(c, h.x);
}
__device__ __forceinline__ uint32_t get_desc(const Ctx& c, int i) {
  uint32_t d;
  mbar_wait_w(c.sb + BAR_DESC, (i - 1) & 1);
  asm volatile("ld.volatile.shared.u32 %0, [%1];" : "=r"(d) : "r"(c.sb + DESC_OFF + (i & 3) * 4) : "memory");
  return __shfl_sync(0xffffffffu, d, 0);
}

struct RowSum { float l0, l1; };

__device__ __forceinline__ float quad_max(float x) {
  x = fmaxf(x, __shfl_xor_sync(0xffffffffu, x, 1));
  return fmaxf(x, __shfl_xor_sync(0xffffffffu, x, 2));
}
__device__ __forceinline__ float quad_sum(float x) {
  x += __shfl_xor_sync(0xffffffffu, x, 1);
  return x + __shfl_xor_sync(0xffffffffu, x, 2);
}
template <bool SP, bool FIRST>
__device__ __forceinline__ void exps(const Ctx& c, const float (&s)[32], uint32_t (&p)[SP ? 8 : 16], RowSum& st) {
  if constexpr (SP) {
    uint32_t q[8];
    float t;
#pragma unroll
    for (int j = 0; j < 8; j++) {
      const float e0 = ex2(s[4 * j] + s[4 * j + 2]), e1 = ex2(s[4 * j + 1] + s[4 * j + 3]);
      if (j == 0) t = e0 + e1; else t += e0 + e1;
      q[j] = pack_bf16(e0, e1);
    }
    const bool odd = c.src & 2;
#pragma unroll
    for (int g = 0; g < 4; g++) {
      p[2 * g] = __shfl_sync(0xffffffffu, odd ? q[2 * g + 1] : q[2 * g], c.src);
      p[2 * g + 1] = __shfl_sync(0xffffffffu, odd ? q[2 * g] : q[2 * g + 1], c.src ^ 1);
    }
    st.l0 = FIRST ? t : st.l0 + t;
  } else {
    float t0, t1;
#pragma unroll
    for (int j = 0; j < 8; j++) {
      const float e0 = ex2(s[4 * j]), e1 = ex2(s[4 * j + 1]), e2 = ex2(s[4 * j + 2]), e3 = ex2(s[4 * j + 3]);
      if (j == 0) { t0 = e0 + e1; t1 = e2 + e3; } else { t0 += e0 + e1; t1 += e2 + e3; }
      p[2 * j] = pack_bf16(e0, e1);
      p[2 * j + 1] = pack_bf16(e2, e3);
    }
    st.l0 = FIRST ? t0 : st.l0 + t0;
    st.l1 = FIRST ? t1 : st.l1 + t1;
  }
}
template <bool SP>
__device__ __forceinline__ bool finish_sums(RowSum& st) {
  const float a = quad_sum(st.l0), b = SP ? a : quad_sum(st.l1);
  st.l0 = __fdividef(1.f, a); st.l1 = __fdividef(1.f, b);
  return !(a >= SUM_LO && a <= SUM_HI && b >= SUM_LO && b <= SUM_HI);
}
template <bool SP, bool INIT, int SITE, bool COMMIT = true>
__device__ __forceinline__ void issue_qk(const Ctx& c, float (&s)[32], const uint32_t (&qs)[16], uint32_t dq, uint32_t dk) {
  uint64_t a = desc64(dq, dhi<SITE & 1>(dk)), b = desc64(dk, dhi<1 - (SITE & 1)>(dk));
  if (SP) {
    if (INIT) wgmma_qk_sp_init(s, qs[0], qs[1], qs[2], qs[3], b, 0, c.mqk); else wgmma_qk_sp(s, qs[0], qs[1], qs[2], qs[3], b, 0, c.mqk);
#pragma unroll
    for (int k = 1; k < 4; k++) { dadd(b, k == 2 ? 508 : 4); wgmma_qk_sp(s, qs[4 * k], qs[4 * k + 1], qs[4 * k + 2], qs[4 * k + 3], b, 1, c.mqk); }
  } else {
    if (INIT) wgmma_qk_init(s, a, b, 0); else wgmma_qk(s, a, b, 0);
#pragma unroll
    for (int k = 1; k < 8; k++) { dadd(a, k == 4 ? 506 : 2); dadd(b, k == 4 ? 506 : 2); wgmma_qk(s, a, b, 1); }
  }
  if (COMMIT) wg_commit();
}
template <bool SP, bool ACC, int SITE, bool SPLIT = false>
__device__ __forceinline__ void issue_pv(const Ctx& c, float (&o)[64], const uint32_t (&p)[SP ? 8 : 16], uint32_t dv) {
  uint64_t b = desc64(dv, dhi<SITE & 1>(dv));
  if constexpr (SP) {
    if (ACC) wgmma_pv_sp(o, p[0], p[1], p[2], p[3], b, 1, c.mpv); else wgmma_pv_sp_init(o, p[0], p[1], p[2], p[3], b, 0, c.mpv);
    if (SPLIT) wg_commit();
    dadd(b, 256);
    wgmma_pv_sp(o, p[4], p[5], p[6], p[7], b, 1, c.mpv);
  } else {
    if (ACC) wgmma_pv(o, p[0], p[1], p[2], p[3], b, 1); else wgmma_pv_init(o, p[0], p[1], p[2], p[3], b, 0);
#pragma unroll
    for (int k = 1; k < 4; k++) { dadd(b, 128); wgmma_pv(o, p[4 * k], p[4 * k + 1], p[4 * k + 2], p[4 * k + 3], b, 1); }
  }
  wg_commit();
}
template <bool SP>
__device__ __forceinline__ void o_store(const Ctx& c, uint32_t tile_addr, const float (&o)[64], const RowSum& inv, uint32_t half = 8192) {
  const int lane = lane_now(), mi = lane >> 3, r8 = lane & 7;
  if (SP) {
    const float i0 = inv.l0;
    const uint32_t row_addr = tile_addr + (8 * c.warp + r8) * 128;
#pragma unroll
    for (int jj = 0; jj < 4; jj++) {
      const int b = jj * 16;
      stsm4(row_addr + (jj >> 1) * 4096 + ((((jj & 1) * 4 + mi) ^ r8) << 4),
            pack_bf16((o[b] + o[b + 2]) * i0, (o[b + 1] + o[b + 3]) * i0), pack_bf16((o[b + 4] + o[b + 6]) * i0, (o[b + 5] + o[b + 7]) * i0),
            pack_bf16((o[b + 8] + o[b + 10]) * i0, (o[b + 9] + o[b + 11]) * i0),
            pack_bf16((o[b + 12] + o[b + 14]) * i0, (o[b + 13] + o[b + 15]) * i0));
    }
  } else {
    const float i0 = inv.l0, i1 = inv.l1;
    const uint32_t row_addr = tile_addr + (16 * c.warp + (mi & 1) * 8 + r8) * 128;
#pragma unroll
    for (int jj = 0; jj < 8; jj++) {
      const int b = jj * 8;
      stsm4(row_addr + (jj >> 2) * half + (((((2 * jj) & 7) + (mi >> 1)) ^ r8) << 4),
            pack_bf16(o[b] * i0, o[b + 1] * i0), pack_bf16(o[b + 2] * i1, o[b + 3] * i1),
            pack_bf16(o[b + 4] * i0, o[b + 5] * i0), pack_bf16(o[b + 6] * i1, o[b + 7] * i1));
    }
  }
}

__device__ __forceinline__ void redo_tile(const Ctx& c, uint32_t q_addr, uint32_t half, const __nv_bfloat16* kp, const __nv_bfloat16* vp) {
  float o[64];
  const int lane = lane_now(), g = lane >> 2, cc = lane & 3, mi = lane >> 3, r8 = lane & 7;
  const uint32_t qa = q_addr + (16 * c.warp + (mi & 1) * 8 + r8) * 128, swz = half == 4096 ? q3_swz(r8) : r8;
  const uint32_t* kq = reinterpret_cast<const uint32_t*>(kp + g * DH) + cc;
  const unsigned short* vq = reinterpret_cast<const unsigned short*>(vp + 2 * cc * DH) + g;
  float m0 = -INFINITY, m1 = -INFINITY, l0 = 0.f, l1 = 0.f;
#pragma unroll
  for (int i = 0; i < 64; i++) o[i] = 0.f;
#pragma unroll 1
  for (int kb = 0; kb < SK / 16; kb++) {
    float z[8] = {0.f, 0.f, 0.f, 0.f, 0.f, 0.f, 0.f, 0.f};
#pragma unroll 2
    for (int kk = 0; kk < 8; kk++) {
      uint32_t a0, a1, a2, a3;
      ldsm4(qa + (kk >> 2) * half + ((((kk & 3) * 2 + (mi >> 1)) ^ swz) << 4), a0, a1, a2, a3);
      const uint32_t* kr = kq + kb * (16 * DH / 2) + kk * 8;
      mma16816(z[0], z[1], z[2], z[3], a0, a1, a2, a3, __ldg(kr), __ldg(kr + 4));
      mma16816(z[4], z[5], z[6], z[7], a0, a1, a2, a3, __ldg(kr + 8 * DH / 2), __ldg(kr + 8 * DH / 2 + 4));
    }
    const float n0 = fmaxf(m0, quad_max(fmaxf(fmaxf(z[0], z[1]), fmaxf(z[4], z[5]))));
    const float n1 = fmaxf(m1, quad_max(fmaxf(fmaxf(z[2], z[3]), fmaxf(z[6], z[7]))));
    const float al0 = ex2(m0 - n0), al1 = ex2(m1 - n1);
    m0 = n0; m1 = n1;
#pragma unroll
    for (int i = 0; i < 8; i++) z[i] = ex2(z[i] - ((i & 2) ? n1 : n0));
    l0 = l0 * al0 + (z[0] + z[1]) + (z[4] + z[5]);
    l1 = l1 * al1 + (z[2] + z[3]) + (z[6] + z[7]);
    const uint32_t a0 = pack_bf16(z[0], z[1]), a1 = pack_bf16(z[2], z[3]), a2 = pack_bf16(z[4], z[5]), a3 = pack_bf16(z[6], z[7]);
    const unsigned short* vr = vq + kb * (16 * DH);
#pragma unroll
    for (int nb = 0; nb < 16; nb++) {
      o[4 * nb] *= al0; o[4 * nb + 1] *= al0; o[4 * nb + 2] *= al1; o[4 * nb + 3] *= al1;
      const uint32_t b0 = __ldg(vr + nb * 8) | ((uint32_t)__ldg(vr + nb * 8 + DH) << 16);
      const uint32_t b1 = __ldg(vr + nb * 8 + 8 * DH) | ((uint32_t)__ldg(vr + nb * 8 + 9 * DH) << 16);
      mma16816(o[4 * nb], o[4 * nb + 1], o[4 * nb + 2], o[4 * nb + 3], a0, a1, a2, a3, b0, b1);
    }
  }
  __syncwarp();
  o_store<false>(c, q_addr, o, RowSum{__fdividef(1.f, quad_sum(l0)), __fdividef(1.f, quad_sum(l1))}, half);
}

template <bool SPA, bool SPB, int SITE, int ID>
__device__ __forceinline__ void batch(const Ctx& c, float (&s)[32], const uint32_t (&qs)[16], uint32_t dq, uint32_t dk, float (&ob)[64],
                                      uint32_t (&pb)[SPB ? 8 : 16], uint32_t dv) {
  if constexpr (SPA) {
    reg_fence(pb);
    wg_fence();
    issue_pv<SPB, true, ID>(c, ob, pb, dv);
    issue_qk<SPA, false, ID>(c, s, qs, dq, dk);
  } else {
    constexpr bool EARLY = ((QK_EARLY_MASK >> (SITE + (SPB ? 2 : 0))) & 1) != 0;
    if (!EARLY) reg_fence(pb);
    wg_fence();
    issue_qk<SPA, false, ID, !SPB>(c, s, qs, dq, dk);
    if (EARLY) { reg_fence(pb); wg_fence(); }
    issue_pv<SPB, true, ID, SPB>(c, ob, pb, dv);
  }
}

template <bool SP0>
__device__ __forceinline__ bool attention(Ctx c, Ring& r, int unit, uint32_t& d, float (&o1)[64], RowSum& st1, const Slots& h) {
  constexpr bool SP1 = false;
  c.wg = SP0;
  if (SP0) { c.mqk = META_QK + (d >> 28); c.mpv = META_PV + (d >> 28); asm volatile("" : "+r"(c.mqk), "+r"(c.mpv)); }
  if (SP0) { const int lane = lane_now(); c.src = (lane & 28) | ((lane & 1) << 1) | ((lane >> 1) & 1); }
  float o0[64], s[32];
  uint32_t p0[SP0 ? 8 : 16], p1[16];
  RowSum st0;
  const uint32_t q0a = c.sb + QBUF_OFF + (SP0 ? 3 : 0) * 16384, q1a = c.sb + QBUF_OFF + (SP0 ? 2 : 1) * 16384;
  const uint32_t dq0 = sdesc(q0a, 0), dq1 = sdesc(q1a, 0);
  uint32_t sk = r.slot, sv, sn;
  r.next();
  uint32_t qs[16];
  if (SP0) {
    asm volatile("bar.arrive 1, 256;" ::: "memory");
    proj_end(c, o1, h);
    wait_hi_free(c, r, unit);
    T2C(unit, 42);
    stage_hi<true>(c, o1, SM_C);
    fence_async_smem();
    T2C(unit, 43);
    bar_sync(6, 256);
    const int lane = lane_now(), g = lane >> 2, cc = lane & 3;
    const uint32_t qa = q0a + (8 * c.warp + g) * 128 + (cc & 1) * 8;
#pragma unroll
    for (int k = 0; k < 8; k++)
      asm volatile("ld.shared.v2.u32 {%0, %1}, [%2];" : "=r"(qs[2 * k]), "=r"(qs[2 * k + 1])
                   : "r"(qa + (k >> 2) * 4096 + ((((k & 3) * 2 + (cc >> 1)) ^ q3_swz(g)) << 4)) : "memory");
  } else {
    proj_end(c, o1, h);
    if (QSTART == 1) {
      wait_hi_free(c, r, unit);
      T2C(unit, 42);
      stage_hi<true>(c, o1, SM_C);
      fence_async_smem();
      asm volatile("bar.arrive 6, 256;" ::: "memory");
    }
    T2C(unit, 43);
    bar_sync(1, 256);
  }
  TRACE(unit, 2);
  T2C(unit, 44);
  if (SP0 && QD_FIRST) {
    float s1[32];
    wg_fence();
    issue_qk<SP1, true, 1>(c, s1, qs, dq1, sdesc(c.sb + sk * SLOT, 0));
    reg_fence(qs);
    wg_fence();
    issue_qk<SP0, true, 0>(c, s, qs, dq0, sdesc(c.sb + sk * SLOT, 0));
    T2C(unit, 45);
    acquire2(c, r, sv, sn);
    wg_wait<1>();
    reg_fence(s1);
    T2C(unit, 47);
    exps<SP1, true>(c, s1, p1, st1);
    reg_fence(p1);
    wg_fence();
    issue_pv<SP1, false, 1>(c, o1, p1, sdesc(c.sb + sv * SLOT, 8192));
    wg_wait<1>();
    reg_fence(s);
    T2C(unit, 48);
    release(c, sk);
    sk = sn;
    exps<SP0, true>(c, s, p0, st0);
    reg_fence(p0);
    wg_fence();
    issue_pv<SP0, false, 0>(c, o0, p0, sdesc(c.sb + sv * SLOT, 8192));
    issue_qk<SP0, false, 2>(c, s, qs, dq0, sdesc(c.sb + sk * SLOT, 0));
    T2C(unit, 49);
    sn = acquire(c, r);
    T2C(unit, 50);
    wg_wait<0>();
    reg_fence(s);
  } else
  {
    float s1[32];
    wg_fence();
    issue_qk<SP0, true, 0>(c, s, qs, dq0, sdesc(c.sb + sk * SLOT, 0));
    issue_qk<SP1, true, 1>(c, s1, qs, dq1, sdesc(c.sb + sk * SLOT, 0));
    T2C(unit, 45);
    if (!SP0 && QSTART == 0) {
      wait_hi_free(c, r, unit);
#pragma unroll
      for (int i = 0; i < 48; i++) asm volatile("" : "+f"(o1[i])::"memory");
      stage_hi<true>(c, o1, SM_C);
      fence_async_smem();
      asm volatile("bar.arrive 6, 256;" ::: "memory");
    }
    T2C(unit, 46);
    acquire2(c, r, sv, sn);
    wg_wait<1>();
    reg_fence(s);
    T2C(unit, 47);
    exps<SP0, true>(c, s, p0, st0);
    reg_fence(p0);
    wg_fence();
    issue_qk<SP0, false, 2>(c, s, qs, dq0, sdesc(c.sb + sn * SLOT, 0));
    issue_pv<SP0, false, 0>(c, o0, p0, sdesc(c.sb + sv * SLOT, 8192));
    wg_wait<2>();
    reg_fence(s1);
    T2C(unit, 48);
    release(c, sk);
    sk = sn;
    exps<SP1, true>(c, s1, p1, st1);
    reg_fence(p1);
    wg_fence();
    issue_pv<SP1, false, 1>(c, o1, p1, sdesc(c.sb + sv * SLOT, 8192));
    T2C(unit, 49);
    sn = acquire(c, r);
    T2C(unit, 50);
    wg_wait<1>();
    reg_fence(s);
  }
  TRACE_IN(unit, 4);
  T2C(unit, 51);
#pragma unroll 1
  for (int j = 1; j < 15; j++) {
    const uint32_t sv_prev = sv, sk_prev = sk;
    sv = sn;
    const uint32_t dv = sdesc(c.sb + sv * SLOT, 8192);
    reg_fence(p0);
    exps<SP0, false>(c, s, p0, st0);
    batch<SP1, SP0, 0, 3>(c, s, qs, dq1, sdesc(c.sb + sk * SLOT, 0), o0, p0, dv);
    sk = acquire(c, r);
    wg_wait<1>();
    reg_fence(s); reg_fence(p1);
    release(c, sv_prev); release(c, sk_prev);
    exps<SP1, false>(c, s, p1, st1);
    batch<SP0, SP1, 1, 4>(c, s, qs, dq0, sdesc(c.sb + sk * SLOT, 0), o1, p1, dv);
    sn = acquire(c, r);
    if (SP0) wg_wait<0>(); else wg_wait<1>();
    reg_fence(s);
  }
  TRACE_IN(unit, 5);
  T2C(unit + 1, 52);
  const uint32_t sv_prev = sv;
  sv = sn;
  const uint32_t dv = sdesc(c.sb + sv * SLOT, 8192);
  reg_fence(p0);
  exps<SP0, false>(c, s, p0, st0);
  batch<SP1, SP0, 0, 5>(c, s, qs, dq1, sdesc(c.sb + sk * SLOT, 0), o0, p0, dv);
  asm volatile("ld.volatile.shared.u32 %0, [%1];" : "=r"(d) : "r"(c.sb + DESC_OFF + ((unit + 1) & 3) * 4) : "memory");
  wg_wait<1>();
  reg_fence(s); reg_fence(p1);
  T2C(unit + 1, 53);
  release(c, sv_prev); release(c, sk);
  d = __shfl_sync(0xffffffffu, d, 0);
  bool bad = finish_sums<SP0>(st0);
  exps<SP1, false>(c, s, p1, st1);
  reg_fence(p1);
  wg_fence();
  issue_pv<SP1, true, 2>(c, o1, p1, dv);
  T2C(unit + 1, 54);
  Ring t = r;
  t.next();
  const bool have = EARLY_BEG && (mbar_test(c.sb + BAR_FULL + r.slot * 8, r.phase) & mbar_test(c.sb + BAR_FULL + t.slot * 8, t.phase));
  bad |= finish_sums<SP1>(st1);
  uint32_t any;
  asm volatile("{\n.reg .pred p, q;\nsetp.ne.u32 p, %1, 0;\nbar.red.or.pred q, %2, 128, p;\nselp.u32 %0, 1, 0, q;\n}"
               : "=r"(any) : "r"((uint32_t)bad), "n"(2 + SP0) : "memory");
  bad = __any_sync(0xffffffffu, any);
  if (EARLY_BEG && d < (2u << 30) && !__all_sync(0xffffffffu, have)) { uint32_t a, b; t = r; acquire2(c, t, a, b); }
  wg_wait<1>();
  reg_fence(o0);
  T2C(unit + 1, 55);
  if (__builtin_expect(!bad, 1)) {
    o_store<SP0>(c, q0a, o0, st0);
    staged(c, 0);
  }
  T2C(unit + 1, 56);
  wg_wait<0>();
  reg_fence(o1);
  T2C(unit + 1, 57);
  release(c, sv);
  return bad;
}

__device__ __forceinline__ void consumer(const Ctx& c, const __nv_bfloat16* const* kv) {
  Ring r{0, 0, 0};
  float a0[64], a1[64];
  Slots h;
  RowSum inv;
  uint32_t d = blockIdx.x, dc;
  int i = 0;
begin:
  proj_begin(c, r, a0, h, true);
  while (true) {
    TRACE(i, 0); TRACE(i, 6);
    dc = d;
    proj_main(c, r, a0, a1, h, d >> 30, d >> 30 ? ((d >> 16) & 63) + 1 : DM / 64, i);
    TRACE(i, 1);
    if (d >> 30) goto out_tile;
    T2C(i, 40);
    stage_lo(c, a0, SM_C);
    fence_async_smem();
    T2C(i, 41);
    if (c.wg == 0 ? attention<false>(c, r, i, d, a1, inv, h) : attention<true>(c, r, i, d, a1, inv, h)) goto redo;
    if (!EARLY_BEG || d >= (2u << 30)) break;
    proj_begin(c, r, a0, h, false);
    T2C(i + 1, 58);
    reg_fence(a1);
    o_store<false>(c, c.sb + QBUF_OFF + (c.wg + 1) * 16384, a1, inv);
    staged(c, 1);
    TRACE(i, 3); TRACE(i, 7);
    i++;
  }
  o_store<false>(c, c.sb + QBUF_OFF + (c.wg + 1) * 16384, a1, inv);
  staged(c, 1);
  T2C(i + 1, 58);
next:
  TRACE(i, 3); TRACE(i, 7);
  if ((d >> 30) != 2) {
    i++;
    r.uniform();
    goto begin;
  }
  trace_dump(c);
  return;
out_tile:
  proj_end(c, a1, h);
  if (((d >> 28) & 3) == 2) {
    const uint32_t off = c.sb + stage_off(c);
#pragma unroll 1
    for (int k = (d >> 5) & 3; k > 0; k--) {
#pragma unroll
      for (int t = 0; t < 4; t++) {
        const uint32_t sp = acquire(c, r), base = off + sp * SLOT + c.wg * (t == 3 ? 4096 : 8192);
#pragma unroll
        for (int jj = 0; jj < (t == 3 ? 2 : 4); jj++) add16(base + jj * 2048, t < 2 ? &a0[(t * 4 + jj) * 8] : &a1[((t - 2) * 4 + jj) * 8]);
        release(c, sp);
      }
    }
  }
  stage_lo(c, a0, 1.f);
  staged(c, 0);
  d = get_desc(c, i + 1);
  wait_hi_free(c, r, i);
  stage_hi<false>(c, a1, 1.f);
  staged(c, 1);
  TRACE(i, 2);
  goto next;
redo:
  {
    const size_t hoff = (size_t)(dc & 511) * (SK * DH);
    const int br = (dc >> 9) & 1;
#pragma unroll 1
    for (int part = 0; part < 2; part++) {
      const int t = c.wg ? 3 - part : part;
      if (t < 3 || c.warp < 2) redo_tile(c, c.sb + QBUF_OFF + t * 16384, t == 3 ? 4096 : 8192, kv[br] + hoff, kv[2 + br] + hoff);
      staged(c, part);
    }
  }
  goto next;
}

template <bool SIMPLE>
__global__ void __launch_bounds__(384, 1) mha_fused_kernel(const __grid_constant__ Params P) {
  extern __shared__ __align__(1024) uint8_t smem_raw[];
  const uint32_t sbase = smem_u32(smem_raw);
  const int tid = threadIdx.x;
  const int wg = __shfl_sync(0xffffffffu, tid >> 7, 0);
  const int warp = __shfl_sync(0xffffffffu, (tid >> 5) & 3, 0);
  const int lane = tid & 31;
  const int cta = blockIdx.x;

  if (tid == 0) T3(15, 0);
  if (tid >= 256 && tid < 256 + 18) asm volatile("prefetch.tensormap [%0];" ::"l"(&P.x[0][0] + (tid - 256)) : "memory");
  if (tid == 0) {
    if ((sbase & 1023) || sbase + SMEM_BYTES > 0x40000) __trap();
    for (int i = 0; i < NSX; i++) { mbar_init(sbase + BAR_FULL + i * 8, 1); mbar_init(sbase + BAR_EMPTY + i * 8, 8); }
    for (int i = 0; i < 4; i++) mbar_init(sbase + BAR_STG + i * 8, 4);
    mbar_init(sbase + BAR_DESC, 1);
    mbar_init(sbase + BAR_GO, 1);
    asm volatile("fence.mbarrier_init.release.cluster;" ::: "memory");
  }
  __syncthreads();

  if (wg == 2) {
    asm volatile("setmaxnreg.dec.sync.aligned.u32 %0;" ::"n"(REG_P));
    if (warp == 1) {
      const uint32_t qb = sbase + QBUF_OFF;
      const uint32_t ep = __shfl_sync(0xffffffffu, *(volatile unsigned*)&g_epoch + 1, 0);
      asm volatile("st.volatile.shared.u32 [%0], %1;" ::"r"(sbase + EPOCH_OFF), "r"(ep) : "memory");
      uint32_t dc = cta, qi = 0, piece = 0;
      for (int i = 0; (dc >> 30) != 2; i++) {
        mbar_wait_w(sbase + BAR_GO, i & 1);
        if (piece == 0) {
          if (lane == 0) {
            qi = atomicAdd(&g_next, 1);
            if (qi == (SIMPLE ? NBETA * (NH + 5) : Q_RANGES) - 1) { g_next = 0; g_epoch = ep; }
          }
          qi = __shfl_sync(0xffffffffu, qi, 0) + (SIMPLE ? gridDim.x : NCTA);
        }
        uint32_t d;
        if (qi < Q_RANGES) { d = c_sched.queue[qi]; if (d & 0x8000) d ^= (1u << 30) | (63u << 16) | 0x8000; }
        else if (SIMPLE) { const uint32_t t = qi - NBETA * NH; d = t < NBETA * 5 ? (1u << 30) | (63u << 16) | (t % 5) << 8 | t / 5 : 2u << 30; }
        else { const uint32_t e = qi - Q_RANGES, g = e / 5; d = c_sched.piece[g][piece++] | (e - g * 5) << 8; }
        if ((d >> 30) == 1) {
          const uint32_t ok = __ballot_sync(0xffffffffu, reached(&g_cnt[lane & 1][d & 31], ep * (lane & 1 ? NH - H_LATE : H_LATE)));
          if (!(ok & 2)) d |= ((d >> 22) & 63) >= 2 * H_LATE ? (2u << 30) | 128 : 128;
          if (!(ok & 1)) d |= 2u << 30;
        }
        asm volatile("st.volatile.shared.u32 [%0], %1;" ::"r"(sbase + DESC_OFF + ((i + 1) & 3) * 4), "r"(d) : "memory");
        __syncwarp();
        mbar_arrive_warp(sbase + BAR_DESC);
        const Work w = decode(dc);
        dc = d;
        if (w.kind == 0) {
#pragma unroll
          for (int e = 0; e < 4; e++) {
            const int t = (0x2130 >> (4 * e)) & 3;
            mbar_wait_w(sbase + BAR_STG + (e & 1) * 16 + (e >> 1) * 8, i & 1);
            tma_st3_w(&P.o_st[t == 3], qb + t * 16384, 0, t * 64, w.beta * 64 + w.sub * 2);
            bulk_commit();
            T2P(i + 1, 5, 2 * e);
            if (e) {
              bulk_wait_read<1>();
              mbar_arrive8_w(sbase + BAR_EMPTY + (NS + ((0x1300 >> (4 * e)) & 3)) * 8);
              T2P(i + 1, 5, 2 * e - 1);
            }
          }
          bulk_wait_read<0>();
          mbar_arrive8_w(sbase + BAR_EMPTY + (NS + 2) * 8);
          T2P(i + 1, 5, 7);
        } else {
          uint64_t pol;
          asm volatile("createpolicy.fractional.L2::evict_first.b64 %0, 1.0;" : "=l"(pol));
#pragma unroll
          for (int e = 0; e < 4; e++) {
            const int h = e & 1;
            mbar_wait_w(sbase + BAR_STG + h * 16 + (e >> 1) * 8, i & 1);
#pragma unroll
            for (int t = e & 2; t < (e & 2) + 2; t++) {
              const uint32_t half = t == 3 ? 4096 : 8192, o = t * 16384 + h * half;
              if (w.mode == 1)
                asm volatile(ELECT "cp.async.bulk.global.shared::cta.bulk_group [%0], [%1], %2;\n}"
                             ::"l"(g_part + (size_t)w.range * QBUF_BYTES + o), "r"(qb + o), "r"(half) : "memory");
              else tma_st3_hint_w(&P.out_st[t == 3], qb + o, (w.beta >> 4) * DM + w.sub * 128 + h * 64, t * 64, w.beta & 15, pol);
            }
            if (h) bulk_commit();
          }
          bulk_wait_read<1>();
          mbar_arrive8_w(sbase + BAR_EMPTY + NS * 8);
          mbar_arrive8_w(sbase + BAR_EMPTY + (NS + 1) * 8);
          bulk_wait_read<0>();
          mbar_arrive8_w(sbase + BAR_EMPTY + (NS + 2) * 8);
          mbar_arrive8_w(sbase + BAR_EMPTY + (NS + 3) * 8);
        }
        T3(i, 0);
        asm volatile("cp.async.bulk.wait_group 0;" ::: "memory");
        T3(i, 1);
        if (w.kind == 0) asm volatile(ELECT "red.release.gpu.global.add.u32 [%0], 1;\n}" ::"l"(&g_cnt[w.sub >= H_LATE][w.beta]) : "memory");
        else if (w.mode == 1) asm volatile(ELECT "st.release.gpu.global.u32 [%0], %1;\n}" ::"l"(&g_flag[w.range]), "r"(ep) : "memory");
        T3(i, 2);
      }
      T3(15, 1);
    } else
    if (warp == 0 && lane == 0) {
      Ring r{0, 1, 1};
      uint32_t d = cta;
      for (int i = 0;; i++) {
        const Work w = decode(d);
        if (w.kind == 2) break;
        const CUtensorMap* m = w.kind == 0 ? &P.wq[w.beta >> 4] : &P.wo[w.beta >> 4];
        const int c1 = w.k0 * 64;
        for (int ks = 0; ks < w.nsteps; ks++) {
          const uint32_t b = borrow(ks, w.nsteps), bar = sbase + BAR_FULL + r.slot * 8;
          mbar_wait(bar + (BAR_EMPTY - BAR_FULL), r.phase);
          mbar_expect_tx(bar, 16384);
          tma_ld3(sbase + r.slot * SLOT, m, 0, c1 + ks * 64, w.sub * 2, bar);
          if (ks < 10) T2P(i, 2, ks);
          if (w.kind != 0 && ks == max(w.nsteps - GO_P, 4)) mbar_arrive(sbase + BAR_GO);
          r.next(); r.next_if(b == 3); r.next_if(b != 0);
        }
        if (w.kind == 0) {
          r.phase ^= 1; r.next(); r.next();
        } else if (w.mode == 2) {
          for (int k = 1; k <= ((d >> 5) & 3); k++) {
            wait_count(&g_flag[w.range + 5 * k], lds(sbase + EPOCH_OFF));
            asm volatile("fence.proxy.async.global;" ::: "memory");
            for (int t = 0; t < 4; t++) {
              const uint32_t bar = sbase + BAR_FULL + r.slot * 8, bytes = t == 3 ? 8192 : 16384;
              mbar_wait(sbase + BAR_EMPTY + r.slot * 8, r.phase);
              mbar_expect_tx(bar, bytes);
              asm volatile("cp.async.bulk.shared::cluster.global.mbarrier::complete_tx::bytes [%0], [%1], %2, [%3];"
                           ::"r"(sbase + r.slot * SLOT), "l"(g_part + (size_t)(w.range + 5 * k) * QBUF_BYTES + t * 16384), "r"(bytes), "r"(bar)
                           : "memory");
              r.next();
            }
          }
        }
        mbar_wait(sbase + BAR_DESC, i & 1);
        d = lds(sbase + DESC_OFF + ((i + 1) & 3) * 4);
      }
    } else if (warp >= 2 && lane == 0) {
      const int hi = warp - 2;
      uint64_t pol_stream;
      asm volatile("createpolicy.fractional.L2::evict_first.b64 %0, 1.0;" : "=l"(pol_stream));
      Ring r{0, 1, 1};
      uint32_t d = cta;
      for (int i = 0;; i++) {
        const Work w = decode(d);
        if (w.kind == 2) break;
        const CUtensorMap* m = w.kind == 0 ? &P.x[hi][w.beta >> 4] : &P.o_ld[hi];
        int c1 = (w.kind == 0 ? (w.beta & 15) : w.beta * 64 + w.k0) * SQ + hi * 128;
        int k_late = -1;
        if (w.kind != 0) {
          if (!hi) T3(i, 3);
          if (d >= (3u << 30)) wait_count(&g_cnt[0][w.beta], lds(sbase + EPOCH_OFF) * H_LATE);
          if (d & 128) k_late = max(2 * H_LATE - w.k0, 0);
          if (!hi) T3(i, 4);
          asm volatile("fence.proxy.async.global;" ::: "memory");
          if (!hi) T3(i, 5);
        }
        for (int ks = 0; ks < w.nsteps; ks++) {
          if (ks == k_late) {
            if (!hi) T3(i, 6);
            wait_count(&g_cnt[1][d & 31], lds(sbase + EPOCH_OFF) * (NH - H_LATE));
            asm volatile("fence.proxy.async.global;" ::: "memory");
            if (!hi) T3(i, 7);
          }
          const uint32_t b = borrow(ks, w.nsteps);
          const bool bo = hi ? b == 0 : b != 3;
          r.next(); r.next_if(hi && b == 3);
          const uint32_t sl = bo ? NS + b + 3 * hi : r.slot, bar = sbase + BAR_FULL + sl * 8;
          mbar_wait(bar + (BAR_EMPTY - BAR_FULL), bo ? r.xp : r.phase);
          mbar_expect_tx(bar, hi ? 96 * 128 : 128 * 128);
          if (w.kind == 0) tma_ld2(sbase + sl * SLOT, m, ks * 64, c1, bar);
          else { tma_ld2_hint(sbase + sl * SLOT, m, 0, c1, bar, pol_stream); c1 += SQ; }
          if (ks < 10) T2P(i, 3 + hi, ks);
          r.next_if(!bo); r.next_if(!hi && b != 0);
          r.xp ^= b == 2;
        }
        r.xp ^= 1;
        if (w.kind == 0) {
          m = &P.kv[hi][w.beta >> 4];
          c1 = (d & 511) * SK;
          for (int j = 0; j < 16; j++) {
            if (hi) r.next();
            const uint32_t bar = sbase + BAR_FULL + r.slot * 8;
            if (i == 0 && j < KV_WIN_TILES) {
              const int s2 = (int)r.slot - 2;
              mbar_wait(sbase + BAR_FULL + (s2 < 0 ? s2 + NS : s2) * 8, s2 < 0 ? r.phase : r.phase ^ 1);
            }
            if (j == 15 && hi) mbar_wait(sbase + BAR_DESC, i & 1);
            mbar_wait(sbase + BAR_EMPTY + r.slot * 8, r.phase);
            mbar_expect_tx(bar, 16384);
            tma_ld3_hint(sbase + r.slot * SLOT, m, 0, c1, 0, bar, pol_stream);
            T2P(i, 3 + hi, 16 + j);
            if (j == 14 && !hi) mbar_arrive(sbase + BAR_GO);
            c1 += 64;
            r.next();
            if (!hi) r.next();
          }
        }
        mbar_wait(sbase + BAR_DESC, i & 1);
        d = lds(sbase + DESC_OFF + ((i + 1) & 3) * 4);
      }
    }
  } else {
    asm volatile("setmaxnreg.inc.sync.aligned.u32 %0;" ::"n"(REG_C));
    Ctx c;
    c.sb = sbase; c.wg = wg; c.warp = warp; c.src = 0; c.mqk = 0; c.mpv = 0; c.lead = lane == 0;
    consumer(c, P.kp);
  }
}

typedef CUresult (*EncodeFn)(CUtensorMap*, CUtensorMapDataType, cuuint32_t, void*, const cuuint64_t*, const cuuint64_t*,
                             const cuuint32_t*, const cuuint32_t*, CUtensorMapInterleave, CUtensorMapSwizzle,
                             CUtensorMapL2promotion, CUtensorMapFloatOOBfill);

void make_map(EncodeFn enc, CUtensorMap* m, const void* ptr, int rank, const cuuint64_t* dims, const cuuint64_t* strides,
              const cuuint32_t* box, int promo = 2) {
  cuuint32_t es[5] = {1, 1, 1, 1, 1};
  enc(m, CU_TENSOR_MAP_DATA_TYPE_BFLOAT16, rank, const_cast<void*>(ptr), dims, strides, box, es,
      CU_TENSOR_MAP_INTERLEAVE_NONE, CU_TENSOR_MAP_SWIZZLE_128B, promo == 2 ? CU_TENSOR_MAP_L2_PROMOTION_L2_256B : promo == 1 ? CU_TENSOR_MAP_L2_PROMOTION_L2_128B : CU_TENSOR_MAP_L2_PROMOTION_NONE,
      CU_TENSOR_MAP_FLOAT_OOB_FILL_NONE);
}

}

extern "C" void kernel_launch(void* const* d_in, const int* in_sizes, int n_in, void* d_out, int out_size) {
  (void)in_sizes; (void)n_in; (void)out_size;
  static EncodeFn enc = nullptr;
  static void* o_ptr = nullptr;
  static int n_sm = 0;
  if (!enc) {
    void* fn = nullptr;
    cudaDriverEntryPointQueryResult qr;
    cudaGetDriverEntryPoint("cuTensorMapEncodeTiled", &fn, cudaEnableDefault, &qr);
    enc = (EncodeFn)fn;
    cudaGetSymbolAddress(&o_ptr, g_o);
    cudaFuncSetAttribute(mha_fused_kernel<false>, cudaFuncAttributeMaxDynamicSharedMemorySize, SMEM_BYTES);
    cudaFuncSetAttribute(mha_fused_kernel<true>, cudaFuncAttributeMaxDynamicSharedMemorySize, SMEM_BYTES);
    int dev = 0;
    cudaGetDevice(&dev);
    cudaDeviceGetAttribute(&n_sm, cudaDevAttrMultiProcessorCount, dev);
  }
  Params P;
  for (int br = 0; br < 2; br++) {
    const void* x = d_in[br * 5 + 0]; const void* kc = d_in[br * 5 + 1]; const void* vc = d_in[br * 5 + 2];
    const void* wq = d_in[br * 5 + 3]; const void* wo = d_in[br * 5 + 4];
    { cuuint64_t d[2] = {DM, (cuuint64_t)NB * SQ}, s[1] = {DM * 2}; cuuint32_t b[2] = {64, 128}, b2[2] = {64, 96};
      make_map(enc, &P.x[0][br], x, 2, d, s, b, PR_X); make_map(enc, &P.x[1][br], x, 2, d, s, b2, PR_X); }
    { cuuint64_t d[3] = {64, DM, HD / 64}, s[2] = {HD * 2, 128}; cuuint32_t b[3] = {64, 64, 2}; make_map(enc, &P.wq[br], wq, 3, d, s, b, PR_W); }
    { cuuint64_t d[3] = {64, HD, DM / 64}, s[2] = {DM * 2, 128}; cuuint32_t b[3] = {64, 64, 2}; make_map(enc, &P.wo[br], wo, 3, d, s, b, PR_W); }
    { cuuint64_t d[3] = {64, (cuuint64_t)NB * NH * SK, 2}, s[2] = {DH * 2, 128}; cuuint32_t b[3] = {64, 64, 2};
      make_map(enc, &P.kv[0][br], kc, 3, d, s, b, PR_KV); make_map(enc, &P.kv[1][br], vc, 3, d, s, b, PR_KV); }
    P.kp[br] = (const __nv_bfloat16*)kc; P.vp[br] = (const __nv_bfloat16*)vc;

  }
  { cuuint64_t d[2] = {64, (cuuint64_t)NBETA * 64 * SQ}, s[1] = {128}; cuuint32_t b[2] = {64, 128}, b2[2] = {64, 96};
    make_map(enc, &P.o_ld[0], o_ptr, 2, d, s, b); make_map(enc, &P.o_ld[1], o_ptr, 2, d, s, b2); }
  { cuuint64_t d[3] = {64, SQ, NBETA * 64}, s[2] = {128, SQ * 128}; cuuint32_t b[3] = {64, 64, 2}, b2[3] = {64, 32, 2};
    make_map(enc, &P.o_st[0], o_ptr, 3, d, s, b); make_map(enc, &P.o_st[1], o_ptr, 3, d, s, b2); }
  { cuuint64_t d[3] = {2 * DM, SQ, NB}, s[2] = {2 * DM * 2, (cuuint64_t)SQ * 2 * DM * 2}; cuuint32_t b[3] = {64, 64, 1}, b2[3] = {64, 32, 1};
    make_map(enc, &P.out_st[0], d_out, 3, d, s, b); make_map(enc, &P.out_st[1], d_out, 3, d, s, b2); }
  if (n_sm >= NCTA) mha_fused_kernel<false><<<NCTA, 384, SMEM_BYTES>>>(P);
  else mha_fused_kernel<true><<<n_sm, 384, SMEM_BYTES>>>(P);
}
```

```cpp
#include <cuda_runtime.h>
#include <cuda_bf16.h>
#include <cuda.h>
#include <stdint.h>

namespace {

__device__ __forceinline__ void wgmma_proj(float (&d)[64], uint64_t da, uint64_t db, int scaleD) {
  asm volatile("{\n.reg .pred p;\nsetp.ne.b32 p, %66, 0;\n"
      "wgmma.mma_async.sync.aligned.m64n128k16.f32.bf16.bf16 "
      "{%0, %1, %2, %3, %4, %5, %6, %7, %8, %9, %10, %11, %12, %13, %14, %15, %16, %17, %18, %19, %20, %21, %22, %23, %24, %25, %26, %27, %28, %29, %30, "
      "%31, %32, %33, %34, %35, %36, %37, %38, %39, %40, %41, %42, %43, %44, %45, %46, %47, %48, %49, %50, %51, %52, %53, %54, %55, %56, %57, %58, %59, %60, "
      "%61, %62, %63}, "
      "%64, %65, p, 1, 1, 1, 0;\n}\n"
      : "+f"(d[0]), "+f"(d[1]), "+f"(d[2]), "+f"(d[3]), "+f"(d[4]), "+f"(d[5]), "+f"(d[6]), "+f"(d[7]), "+f"(d[8]), "+f"(d[9]), "+f"(d[10]), "+f"(d[11]),
        "+f"(d[12]), "+f"(d[13]), "+f"(d[14]), "+f"(d[15]), "+f"(d[16]), "+f"(d[17]), "+f"(d[18]), "+f"(d[19]), "+f"(d[20]), "+f"(d[21]), "+f"(d[22]),
        "+f"(d[23]), "+f"(d[24]), "+f"(d[25]), "+f"(d[26]), "+f"(d[27]), "+f"(d[28]), "+f"(d[29]), "+f"(d[30]), "+f"(d[31]), "+f"(d[32]), "+f"(d[33]),
        "+f"(d[34]), "+f"(d[35]), "+f"(d[36]), "+f"(d[37]), "+f"(d[38]), "+f"(d[39]), "+f"(d[40]), "+f"(d[41]), "+f"(d[42]), "+f"(d[43]), "+f"(d[44]),
        "+f"(d[45]), "+f"(d[46]), "+f"(d[47]), "+f"(d[48]), "+f"(d[49]), "+f"(d[50]), "+f"(d[51]), "+f"(d[52]), "+f"(d[53]), "+f"(d[54]), "+f"(d[55]),
        "+f"(d[56]), "+f"(d[57]), "+f"(d[58]), "+f"(d[59]), "+f"(d[60]), "+f"(d[61]), "+f"(d[62]), "+f"(d[63])
      : "l"(da), "l"(db), "r"(scaleD));
}
__device__ __forceinline__ void wgmma_proj96(float (&d)[64], uint64_t da, uint64_t db, int scaleD) {
  asm volatile("{\n.reg .pred p;\nsetp.ne.b32 p, %50, 0;\n"
      "wgmma.mma_async.sync.aligned.m64n96k16.f32.bf16.bf16 "
      "{%0, %1, %2, %3, %4, %5, %6, %7, %8, %9, %10, %11, %12, %13, %14, %15, %16, %17, %18, %19, %20, %21, %22, %23, %24, %25, %26, %27, %28, %29, %30, "
      "%31, %32, %33, %34, %35, %36, %37, %38, %39, %40, %41, %42, %43, %44, %45, %46, %47}, "
      "%48, %49, p, 1, 1, 1, 0;\n}\n"
      : "+f"(d[0]), "+f"(d[1]), "+f"(d[2]), "+f"(d[3]), "+f"(d[4]), "+f"(d[5]), "+f"(d[6]), "+f"(d[7]), "+f"(d[8]), "+f"(d[9]), "+f"(d[10]), "+f"(d[11]),
        "+f"(d[12]), "+f"(d[13]), "+f"(d[14]), "+f"(d[15]), "+f"(d[16]), "+f"(d[17]), "+f"(d[18]), "+f"(d[19]), "+f"(d[20]), "+f"(d[21]), "+f"(d[22]),
        "+f"(d[23]), "+f"(d[24]), "+f"(d[25]), "+f"(d[26]), "+f"(d[27]), "+f"(d[28]), "+f"(d[29]), "+f"(d[30]), "+f"(d[31]), "+f"(d[32]), "+f"(d[33]),
        "+f"(d[34]), "+f"(d[35]), "+f"(d[36]), "+f"(d[37]), "+f"(d[38]), "+f"(d[39]), "+f"(d[40]), "+f"(d[41]), "+f"(d[42]), "+f"(d[43]), "+f"(d[44]),
        "+f"(d[45]), "+f"(d[46]), "+f"(d[47])
      : "l"(da), "l"(db), "r"(scaleD));
}
__device__ __forceinline__ void wgmma_qk(float (&d)[32], uint64_t da, uint64_t db, int scaleD) {
  asm volatile("{\n.reg .pred p;\nsetp.ne.b32 p, %34, 0;\n"
      "wgmma.mma_async.sync.aligned.m64n64k16.f32.bf16.bf16 "
      "{%0, %1, %2, %3, %4, %5, %6, %7, %8, %9, %10, %11, %12, %13, %14, %15, %16, %17, %18, %19, %20, %21, %22, %23, %24, %25, %26, %27, %28, %29, %30, "
      "%31}, "
      "%32, %33, p, 1, 1, 0, 0;\n}\n"
      : "+f"(d[0]), "+f"(d[1]), "+f"(d[2]), "+f"(d[3]), "+f"(d[4]), "+f"(d[5]), "+f"(d[6]), "+f"(d[7]), "+f"(d[8]), "+f"(d[9]), "+f"(d[10]), "+f"(d[11]),
        "+f"(d[12]), "+f"(d[13]), "+f"(d[14]), "+f"(d[15]), "+f"(d[16]), "+f"(d[17]), "+f"(d[18]), "+f"(d[19]), "+f"(d[20]), "+f"(d[21]), "+f"(d[22]),
        "+f"(d[23]), "+f"(d[24]), "+f"(d[25]), "+f"(d[26]), "+f"(d[27]), "+f"(d[28]), "+f"(d[29]), "+f"(d[30]), "+f"(d[31])
      : "l"(da), "l"(db), "r"(scaleD));
}
__device__ __forceinline__ void wgmma_pv(float (&d)[64], uint32_t a0, uint32_t a1, uint32_t a2, uint32_t a3, uint64_t db, int scaleD) {
  asm volatile("{\n.reg .pred p;\nsetp.ne.b32 p, %69, 0;\n"
      "wgmma.mma_async.sync.aligned.m64n128k16.f32.bf16.bf16 "
      "{%0, %1, %2, %3, %4, %5, %6, %7, %8, %9, %10, %11, %12, %13, %14, %15, %16, %17, %18, %19, %20, %21, %22, %23, %24, %25, %26, %27, %28, %29, %30, "
      "%31, %32, %33, %34, %35, %36, %37, %38, %39, %40, %41, %42, %43, %44, %45, %46, %47, %48, %49, %50, %51, %52, %53, %54, %55, %56, %57, %58, %59, %60, "
      "%61, %62, %63}, "
      "{%64, %65, %66, %67}, %68, p, 1, 1, 1;\n}\n"
      : "+f"(d[0]), "+f"(d[1]), "+f"(d[2]), "+f"(d[3]), "+f"(d[4]), "+f"(d[5]), "+f"(d[6]), "+f"(d[7]), "+f"(d[8]), "+f"(d[9]), "+f"(d[10]), "+f"(d[11]),
        "+f"(d[12]), "+f"(d[13]), "+f"(d[14]), "+f"(d[15]), "+f"(d[16]), "+f"(d[17]), "+f"(d[18]), "+f"(d[19]), "+f"(d[20]), "+f"(d[21]), "+f"(d[22]),
        "+f"(d[23]), "+f"(d[24]), "+f"(d[25]), "+f"(d[26]), "+f"(d[27]), "+f"(d[28]), "+f"(d[29]), "+f"(d[30]), "+f"(d[31]), "+f"(d[32]), "+f"(d[33]),
        "+f"(d[34]), "+f"(d[35]), "+f"(d[36]), "+f"(d[37]), "+f"(d[38]), "+f"(d[39]), "+f"(d[40]), "+f"(d[41]), "+f"(d[42]), "+f"(d[43]), "+f"(d[44]),
        "+f"(d[45]), "+f"(d[46]), "+f"(d[47]), "+f"(d[48]), "+f"(d[49]), "+f"(d[50]), "+f"(d[51]), "+f"(d[52]), "+f"(d[53]), "+f"(d[54]), "+f"(d[55]),
        "+f"(d[56]), "+f"(d[57]), "+f"(d[58]), "+f"(d[59]), "+f"(d[60]), "+f"(d[61]), "+f"(d[62]), "+f"(d[63])
      : "r"(a0), "r"(a1), "r"(a2), "r"(a3), "l"(db), "r"(scaleD));
}
__device__ __forceinline__ void wgmma_qk_sp(float (&d)[32], uint32_t a0, uint32_t a1, uint32_t a2, uint32_t a3, uint64_t db, int scaleD, uint32_t meta) {
  asm volatile("{\n.reg .pred p;\nsetp.ne.b32 p, %37, 0;\n"
      "wgmma.mma_async.sp.sync.aligned.m64n64k32.f32.bf16.bf16 "
      "{%0, %1, %2, %3, %4, %5, %6, %7, %8, %9, %10, %11, %12, %13, %14, %15, %16, %17, %18, %19, %20, %21, %22, %23, %24, %25, %26, %27, %28, %29, %30, "
      "%31}, "
      "{%32, %33, %34, %35}, %36, %38, 0, p, 1, 1, 0;\n}\n"
      : "+f"(d[0]), "+f"(d[1]), "+f"(d[2]), "+f"(d[3]), "+f"(d[4]), "+f"(d[5]), "+f"(d[6]), "+f"(d[7]), "+f"(d[8]), "+f"(d[9]), "+f"(d[10]), "+f"(d[11]),
        "+f"(d[12]), "+f"(d[13]), "+f"(d[14]), "+f"(d[15]), "+f"(d[16]), "+f"(d[17]), "+f"(d[18]), "+f"(d[19]), "+f"(d[20]), "+f"(d[21]), "+f"(d[22]),
        "+f"(d[23]), "+f"(d[24]), "+f"(d[25]), "+f"(d[26]), "+f"(d[27]), "+f"(d[28]), "+f"(d[29]), "+f"(d[30]), "+f"(d[31])
      : "r"(a0), "r"(a1), "r"(a2), "r"(a3), "l"(db), "r"(scaleD), "r"(meta));
}
__device__ __forceinline__ void wgmma_pv_sp(float (&d)[64], uint32_t a0, uint32_t a1, uint32_t a2, uint32_t a3, uint64_t db, int scaleD, uint32_t meta) {
  asm volatile("{\n.reg .pred p;\nsetp.ne.b32 p, %69, 0;\n"
      "wgmma.mma_async.sp.sync.aligned.m64n128k32.f32.bf16.bf16 "
      "{%0, %1, %2, %3, %4, %5, %6, %7, %8, %9, %10, %11, %12, %13, %14, %15, %16, %17, %18, %19, %20, %21, %22, %23, %24, %25, %26, %27, %28, %29, %30, "
      "%31, %32, %33, %34, %35, %36, %37, %38, %39, %40, %41, %42, %43, %44, %45, %46, %47, %48, %49, %50, %51, %52, %53, %54, %55, %56, %57, %58, %59, %60, "
      "%61, %62, %63}, "
      "{%64, %65, %66, %67}, %68, %70, 0, p, 1, 1, 1;\n}\n"
      : "+f"(d[0]), "+f"(d[1]), "+f"(d[2]), "+f"(d[3]), "+f"(d[4]), "+f"(d[5]), "+f"(d[6]), "+f"(d[7]), "+f"(d[8]), "+f"(d[9]), "+f"(d[10]), "+f"(d[11]),
        "+f"(d[12]), "+f"(d[13]), "+f"(d[14]), "+f"(d[15]), "+f"(d[16]), "+f"(d[17]), "+f"(d[18]), "+f"(d[19]), "+f"(d[20]), "+f"(d[21]), "+f"(d[22]),
        "+f"(d[23]), "+f"(d[24]), "+f"(d[25]), "+f"(d[26]), "+f"(d[27]), "+f"(d[28]), "+f"(d[29]), "+f"(d[30]), "+f"(d[31]), "+f"(d[32]), "+f"(d[33]),
        "+f"(d[34]), "+f"(d[35]), "+f"(d[36]), "+f"(d[37]), "+f"(d[38]), "+f"(d[39]), "+f"(d[40]), "+f"(d[41]), "+f"(d[42]), "+f"(d[43]), "+f"(d[44]),
        "+f"(d[45]), "+f"(d[46]), "+f"(d[47]), "+f"(d[48]), "+f"(d[49]), "+f"(d[50]), "+f"(d[51]), "+f"(d[52]), "+f"(d[53]), "+f"(d[54]), "+f"(d[55]),
        "+f"(d[56]), "+f"(d[57]), "+f"(d[58]), "+f"(d[59]), "+f"(d[60]), "+f"(d[61]), "+f"(d[62]), "+f"(d[63])
      : "r"(a0), "r"(a1), "r"(a2), "r"(a3), "l"(db), "r"(scaleD), "r"(meta));
}
__device__ __forceinline__ void wgmma_proj_init(float (&d)[64], uint64_t da, uint64_t db, int scaleD) {
  asm volatile("{\n.reg .pred p;\nsetp.ne.b32 p, %66, 0;\n"
      "wgmma.mma_async.sync.aligned.m64n128k16.f32.bf16.bf16 "
      "{%0, %1, %2, %3, %4, %5, %6, %7, %8, %9, %10, %11, %12, %13, %14, %15, %16, %17, %18, %19, %20, %21, %22, %23, %24, %25, %26, %27, %28, %29, %30, "
      "%31, %32, %33, %34, %35, %36, %37, %38, %39, %40, %41, %42, %43, %44, %45, %46, %47, %48, %49, %50, %51, %52, %53, %54, %55, %56, %57, %58, %59, %60, "
      "%61, %62, %63}, "
      "%64, %65, p, 1, 1, 1, 0;\n}\n"
      : "=f"(d[0]), "=f"(d[1]), "=f"(d[2]), "=f"(d[3]), "=f"(d[4]), "=f"(d[5]), "=f"(d[6]), "=f"(d[7]), "=f"(d[8]), "=f"(d[9]), "=f"(d[10]), "=f"(d[11]),
        "=f"(d[12]), "=f"(d[13]), "=f"(d[14]), "=f"(d[15]), "=f"(d[16]), "=f"(d[17]), "=f"(d[18]), "=f"(d[19]), "=f"(d[20]), "=f"(d[21]), "=f"(d[22]),
        "=f"(d[23]), "=f"(d[24]), "=f"(d[25]), "=f"(d[26]), "=f"(d[27]), "=f"(d[28]), "=f"(d[29]), "=f"(d[30]), "=f"(d[31]), "=f"(d[32]), "=f"(d[33]),
        "=f"(d[34]), "=f"(d[35]), "=f"(d[36]), "=f"(d[37]), "=f"(d[38]), "=f"(d[39]), "=f"(d[40]), "=f"(d[41]), "=f"(d[42]), "=f"(d[43]), "=f"(d[44]),
        "=f"(d[45]), "=f"(d[46]), "=f"(d[47]), "=f"(d[48]), "=f"(d[49]), "=f"(d[50]), "=f"(d[51]), "=f"(d[52]), "=f"(d[53]), "=f"(d[54]), "=f"(d[55]),
        "=f"(d[56]), "=f"(d[57]), "=f"(d[58]), "=f"(d[59]), "=f"(d[60]), "=f"(d[61]), "=f"(d[62]), "=f"(d[63])
      : "l"(da), "l"(db), "r"(scaleD));
}
__device__ __forceinline__ void wgmma_proj96_init(float (&d)[64], uint64_t da, uint64_t db, int scaleD) {
  asm volatile("{\n.reg .pred p;\nsetp.ne.b32 p, %50, 0;\n"
      "wgmma.mma_async.sync.aligned.m64n96k16.f32.bf16.bf16 "
      "{%0, %1, %2, %3, %4, %5, %6, %7, %8, %9, %10, %11, %12, %13, %14, %15, %16, %17, %18, %19, %20, %21, %22, %23, %24, %25, %26, %27, %28, %29, %30, "
      "%31, %32, %33, %34, %35, %36, %37, %38, %39, %40, %41, %42, %43, %44, %45, %46, %47}, "
      "%48, %49, p, 1, 1, 1, 0;\n}\n"
      : "=f"(d[0]), "=f"(d[1]), "=f"(d[2]), "=f"(d[3]), "=f"(d[4]), "=f"(d[5]), "=f"(d[6]), "=f"(d[7]), "=f"(d[8]), "=f"(d[9]), "=f"(d[10]), "=f"(d[11]),
        "=f"(d[12]), "=f"(d[13]), "=f"(d[14]), "=f"(d[15]), "=f"(d[16]), "=f"(d[17]), "=f"(d[18]), "=f"(d[19]), "=f"(d[20]), "=f"(d[21]), "=f"(d[22]),
        "=f"(d[23]), "=f"(d[24]), "=f"(d[25]), "=f"(d[26]), "=f"(d[27]), "=f"(d[28]), "=f"(d[29]), "=f"(d[30]), "=f"(d[31]), "=f"(d[32]), "=f"(d[33]),
        "=f"(d[34]), "=f"(d[35]), "=f"(d[36]), "=f"(d[37]), "=f"(d[38]), "=f"(d[39]), "=f"(d[40]), "=f"(d[41]), "=f"(d[42]), "=f"(d[43]), "=f"(d[44]),
        "=f"(d[45]), "=f"(d[46]), "=f"(d[47])
      : "l"(da), "l"(db), "r"(scaleD));
}
__device__ __forceinline__ void wgmma_qk_init(float (&d)[32], uint64_t da, uint64_t db, int scaleD) {
  asm volatile("{\n.reg .pred p;\nsetp.ne.b32 p, %34, 0;\n"
      "wgmma.mma_async.sync.aligned.m64n64k16.f32.bf16.bf16 "
      "{%0, %1, %2, %3, %4, %5, %6, %7, %8, %9, %10, %11, %12, %13, %14, %15, %16, %17, %18, %19, %20, %21, %22, %23, %24, %25, %26, %27, %28, %29, %30, "
      "%31}, "
      "%32, %33, p, 1, 1, 0, 0;\n}\n"
      : "=f"(d[0]), "=f"(d[1]), "=f"(d[2]), "=f"(d[3]), "=f"(d[4]), "=f"(d[5]), "=f"(d[6]), "=f"(d[7]), "=f"(d[8]), "=f"(d[9]), "=f"(d[10]), "=f"(d[11]),
        "=f"(d[12]), "=f"(d[13]), "=f"(d[14]), "=f"(d[15]), "=f"(d[16]), "=f"(d[17]), "=f"(d[18]), "=f"(d[19]), "=f"(d[20]), "=f"(d[21]), "=f"(d[22]),
        "=f"(d[23]), "=f"(d[24]), "=f"(d[25]), "=f"(d[26]), "=f"(d[27]), "=f"(d[28]), "=f"(d[29]), "=f"(d[30]), "=f"(d[31])
      : "l"(da), "l"(db), "r"(scaleD));
}
__device__ __forceinline__ void wgmma_pv_init(float (&d)[64], uint32_t a0, uint32_t a1, uint32_t a2, uint32_t a3, uint64_t db, int scaleD) {
  asm volatile("{\n.reg .pred p;\nsetp.ne.b32 p, %69, 0;\n"
      "wgmma.mma_async.sync.aligned.m64n128k16.f32.bf16.bf16 "
      "{%0, %1, %2, %3, %4, %5, %6, %7, %8, %9, %10, %11, %12, %13, %14, %15, %16, %17, %18, %19, %20, %21, %22, %23, %24, %25, %26, %27, %28, %29, %30, "
      "%31, %32, %33, %34, %35, %36, %37, %38, %39, %40, %41, %42, %43, %44, %45, %46, %47, %48, %49, %50, %51, %52, %53, %54, %55, %56, %57, %58, %59, %60, "
      "%61, %62, %63}, "
      "{%64, %65, %66, %67}, %68, p, 1, 1, 1;\n}\n"
      : "=f"(d[0]), "=f"(d[1]), "=f"(d[2]), "=f"(d[3]), "=f"(d[4]), "=f"(d[5]), "=f"(d[6]), "=f"(d[7]), "=f"(d[8]), "=f"(d[9]), "=f"(d[10]), "=f"(d[11]),
        "=f"(d[12]), "=f"(d[13]), "=f"(d[14]), "=f"(d[15]), "=f"(d[16]), "=f"(d[17]), "=f"(d[18]), "=f"(d[19]), "=f"(d[20]), "=f"(d[21]), "=f"(d[22]),
        "=f"(d[23]), "=f"(d[24]), "=f"(d[25]), "=f"(d[26]), "=f"(d[27]), "=f"(d[28]), "=f"(d[29]), "=f"(d[30]), "=f"(d[31]), "=f"(d[32]), "=f"(d[33]),
        "=f"(d[34]), "=f"(d[35]), "=f"(d[36]), "=f"(d[37]), "=f"(d[38]), "=f"(d[39]), "=f"(d[40]), "=f"(d[41]), "=f"(d[42]), "=f"(d[43]), "=f"(d[44]),
        "=f"(d[45]), "=f"(d[46]), "=f"(d[47]), "=f"(d[48]), "=f"(d[49]), "=f"(d[50]), "=f"(d[51]), "=f"(d[52]), "=f"(d[53]), "=f"(d[54]), "=f"(d[55]),
        "=f"(d[56]), "=f"(d[57]), "=f"(d[58]), "=f"(d[59]), "=f"(d[60]), "=f"(d[61]), "=f"(d[62]), "=f"(d[63])
      : "r"(a0), "r"(a1), "r"(a2), "r"(a3), "l"(db), "r"(scaleD));
}
__device__ __forceinline__ void wgmma_qk_sp_init(float (&d)[32], uint32_t a0, uint32_t a1, uint32_t a2, uint32_t a3, uint64_t db, int scaleD, uint32_t meta) {
  asm volatile("{\n.reg .pred p;\nsetp.ne.b32 p, %37, 0;\n"
      "wgmma.mma_async.sp.sync.aligned.m64n64k32.f32.bf16.bf16 "
      "{%0, %1, %2, %3, %4, %5, %6, %7, %8, %9, %10, %11, %12, %13, %14, %15, %16, %17, %18, %19, %20, %21, %22, %23, %24, %25, %26, %27, %28, %29, %30, "
      "%31}, "
      "{%32, %33, %34, %35}, %36, %38, 0, p, 1, 1, 0;\n}\n"
      : "=f"(d[0]), "=f"(d[1]), "=f"(d[2]), "=f"(d[3]), "=f"(d[4]), "=f"(d[5]), "=f"(d[6]), "=f"(d[7]), "=f"(d[8]), "=f"(d[9]), "=f"(d[10]), "=f"(d[11]),
        "=f"(d[12]), "=f"(d[13]), "=f"(d[14]), "=f"(d[15]), "=f"(d[16]), "=f"(d[17]), "=f"(d[18]), "=f"(d[19]), "=f"(d[20]), "=f"(d[21]), "=f"(d[22]),
        "=f"(d[23]), "=f"(d[24]), "=f"(d[25]), "=f"(d[26]), "=f"(d[27]), "=f"(d[28]), "=f"(d[29]), "=f"(d[30]), "=f"(d[31])
      : "r"(a0), "r"(a1), "r"(a2), "r"(a3), "l"(db), "r"(scaleD), "r"(meta));
}
__device__ __forceinline__ void wgmma_pv_sp_init(float (&d)[64], uint32_t a0, uint32_t a1, uint32_t a2, uint32_t a3, uint64_t db, int scaleD, uint32_t meta) {
  asm volatile("{\n.reg .pred p;\nsetp.ne.b32 p, %69, 0;\n"
      "wgmma.mma_async.sp.sync.aligned.m64n128k32.f32.bf16.bf16 "
      "{%0, %1, %2, %3, %4, %5, %6, %7, %8, %9, %10, %11, %12, %13, %14, %15, %16, %17, %18, %19, %20, %21, %22, %23, %24, %25, %26, %27, %28, %29, %30, "
      "%31, %32, %33, %34, %35, %36, %37, %38, %39, %40, %41, %42, %43, %44, %45, %46, %47, %48, %49, %50, %51, %52, %53, %54, %55, %56, %57, %58, %59, %60, "
      "%61, %62, %63}, "
      "{%64, %65, %66, %67}, %68, %70, 0, p, 1, 1, 1;\n}\n"
      : "=f"(d[0]), "=f"(d[1]), "=f"(d[2]), "=f"(d[3]), "=f"(d[4]), "=f"(d[5]), "=f"(d[6]), "=f"(d[7]), "=f"(d[8]), "=f"(d[9]), "=f"(d[10]), "=f"(d[11]),
        "=f"(d[12]), "=f"(d[13]), "=f"(d[14]), "=f"(d[15]), "=f"(d[16]), "=f"(d[17]), "=f"(d[18]), "=f"(d[19]), "=f"(d[20]), "=f"(d[21]), "=f"(d[22]),
        "=f"(d[23]), "=f"(d[24]), "=f"(d[25]), "=f"(d[26]), "=f"(d[27]), "=f"(d[28]), "=f"(d[29]), "=f"(d[30]), "=f"(d[31]), "=f"(d[32]), "=f"(d[33]),
        "=f"(d[34]), "=f"(d[35]), "=f"(d[36]), "=f"(d[37]), "=f"(d[38]), "=f"(d[39]), "=f"(d[40]), "=f"(d[41]), "=f"(d[42]), "=f"(d[43]), "=f"(d[44]),
        "=f"(d[45]), "=f"(d[46]), "=f"(d[47]), "=f"(d[48]), "=f"(d[49]), "=f"(d[50]), "=f"(d[51]), "=f"(d[52]), "=f"(d[53]), "=f"(d[54]), "=f"(d[55]),
        "=f"(d[56]), "=f"(d[57]), "=f"(d[58]), "=f"(d[59]), "=f"(d[60]), "=f"(d[61]), "=f"(d[62]), "=f"(d[63])
      : "r"(a0), "r"(a1), "r"(a2), "r"(a3), "l"(db), "r"(scaleD), "r"(meta));
}

constexpr int NB = 16, SQ = 224, DM = 640, NH = 32, SK = 1024, DH = 128;
constexpr int HD = NH * DH;
constexpr int NBETA = 2 * NB;
constexpr int NCTA = 132;
constexpr int NS = 10;
constexpr int SLOT = 16384;
constexpr int QBUF_OFF = NS * SLOT;
constexpr int QBUF_BYTES = 3 * 16384 + 8192;
constexpr int NSX = NS + 4;
constexpr int BAR_OFF = NSX * SLOT;
constexpr int BAR_FULL = BAR_OFF;
constexpr int BAR_EMPTY = BAR_OFF + 8 * NSX;
constexpr int BAR_STG = BAR_OFF + 16 * NSX;
constexpr int BAR_DESC = BAR_STG + 32;
constexpr int BAR_GO = BAR_DESC + 8;
constexpr int DESC_OFF = BAR_GO + 8;
constexpr int EPOCH_OFF = DESC_OFF + 16;
constexpr int TRACE_OFF = EPOCH_OFF + 8;
constexpr int SMEM_BYTES = TRACE_OFF;
constexpr float SM_C = 0.08838834764831845f * 1.4426950408889634f;
constexpr float SUM_HI = 1099511627776.f, SUM_LO = 1.f / 1099511627776.f;
constexpr uint32_t META_QK = 0xEEEE4444u;
constexpr uint32_t META_PV = 0x44EEEE44u;

#define QK_EARLY_MASK 3
#define QD_FIRST 0
#define QSTART 0
#define EARLY_BEG 1
#define KV_WIN_TILES 6
#define PR_KV 2
#define PR_X 2
#define PR_W 2
#define REG_C 232
#define REG_P 40
#define GO_P 4
#define P_POS 256
#define P_STRIDE 32
#define B_LATE 32
#define H_LATE 25
#define RANGE_ORDER 0, 1, 2, 3, 4, 5, 6, 7, 8, 9, 10, 11, 12, 13, 14, 15, 16, 17, 18, 19, 20, 21, 22, 23, 24, 25
#define P_EARLY 13
#define RANGE_TABLE 0, 69, 139, 208, 277, 344, 410, 474, 536, 595, 653, 704, 760, 813, 862, 907, 945, 988, 1024, 1063, 1098, 1121, 1145, 1173, 1186, 1200, 1216

struct Params {
  CUtensorMap x[2][2], wq[2], kv[2][2], wo[2];
  CUtensorMap o_ld[2], o_st[2], out_st[2];
  const __nv_bfloat16* kp[2];
  const __nv_bfloat16* vp[2];
};

__device__ __nv_bfloat16 g_o[(size_t)NBETA * SQ * HD];
__device__ unsigned g_cnt[2][NBETA];
__device__ unsigned g_epoch, g_next;
__device__ __align__(128) uint8_t g_part[(size_t)NCTA * QBUF_BYTES];
__device__ unsigned g_flag[NCTA];

__device__ __forceinline__ uint32_t smem_u32(const void* p) { return (uint32_t)__cvta_generic_to_shared(p); }
__device__ __forceinline__ void mbar_init(uint32_t bar, int cnt) {
  asm volatile("mbarrier.init.shared::cta.b64 [%0], %1;" ::"r"(bar), "r"(cnt) : "memory");
}
__device__ __forceinline__ void mbar_arrive(uint32_t bar) {
  asm volatile("mbarrier.arrive.shared::cta.b64 _, [%0];" ::"r"(bar) : "memory");
}
__device__ __forceinline__ void mbar_arrive_warp(uint32_t bar) {
  asm volatile("{\n.reg .pred p;\nelect.sync _|p, 0xffffffff;\n@p mbarrier.arrive.shared::cta.b64 _, [%0];\n}" ::"r"(bar) : "memory");
}
__device__ __forceinline__ int lane_now() { int l; asm volatile("mov.u32 %0, %%laneid;" : "=r"(l)); return l; }
__device__ __forceinline__ bool mbar_try(uint32_t bar, uint32_t parity) {
  uint32_t ok;
  asm volatile("{\n.reg .pred p;\nmbarrier.try_wait.parity.shared::cta.b64 p, [%1], %2;\nselp.u32 %0, 1, 0, p;\n}"
               : "=r"(ok) : "r"(bar), "r"(parity) : "memory");
  return ok;
}
__device__ __forceinline__ bool mbar_test(uint32_t bar, uint32_t parity) {
  uint32_t ok;
  asm volatile("{\n.reg .pred p;\nmbarrier.test_wait.parity.shared::cta.b64 p, [%1], %2;\nselp.u32 %0, 1, 0, p;\n}"
               : "=r"(ok) : "r"(bar), "r"(parity) : "memory");
  return ok;
}
__device__ __forceinline__ void mbar_wait_w(uint32_t bar, uint32_t parity) {
  uint32_t n = 0;
  while (!__all_sync(0xffffffffu, mbar_try(bar, parity))) {
    if (++n > (1u << 22)) __trap();
  }
}
#define ELECT "{\n.reg .pred p;\nelect.sync _|p, 0xffffffff;\n@p "
__device__ __forceinline__ void tma_st3_w(const CUtensorMap* m, uint32_t src, int c0, int c1, int c2) {
  asm volatile(ELECT "cp.async.bulk.tensor.3d.global.shared::cta.bulk_group [%0, {%2, %3, %4}], [%1];\n}"
               ::"l"(m), "r"(src), "r"(c0), "r"(c1), "r"(c2) : "memory");
}
__device__ __forceinline__ void tma_st3_hint_w(const CUtensorMap* m, uint32_t src, int c0, int c1, int c2, uint64_t pol) {
  asm volatile(ELECT "cp.async.bulk.tensor.3d.global.shared::cta.bulk_group.L2::cache_hint [%0, {%2, %3, %4}], [%1], %5;\n}"
               ::"l"(m), "r"(src), "r"(c0), "r"(c1), "r"(c2), "l"(pol) : "memory");
}
#define EXPECT(bar, bytes) "mbarrier.arrive.expect_tx.shared::cta.b64 _, [" bar "], " bytes ";\n@p "
__device__ __forceinline__ void tma_ld2_w(uint32_t dst, const CUtensorMap* m, int c0, int c1, uint32_t bar, uint32_t bytes) {
  asm volatile(ELECT EXPECT("%2", "%5") "cp.async.bulk.tensor.2d.shared::cluster.global.mbarrier::complete_tx::bytes [%0], [%1, {%3, %4}], [%2];\n}"
               ::"r"(dst), "l"(m), "r"(bar), "r"(c0), "r"(c1), "r"(bytes) : "memory");
}
__device__ __forceinline__ void tma_ld2_hint_w(uint32_t dst, const CUtensorMap* m, int c0, int c1, uint32_t bar, uint32_t bytes, uint64_t pol) {
  asm volatile(ELECT EXPECT("%2", "%6") "cp.async.bulk.tensor.2d.shared::cluster.global.mbarrier::complete_tx::bytes.L2::cache_hint"
               " [%0], [%1, {%3, %4}], [%2], %5;\n}"
               ::"r"(dst), "l"(m), "r"(bar), "r"(c0), "r"(c1), "l"(pol), "r"(bytes) : "memory");
}
__device__ __forceinline__ void tma_ld3_w(uint32_t dst, const CUtensorMap* m, int c0, int c1, int c2, uint32_t bar) {
  asm volatile(ELECT EXPECT("%2", "16384") "cp.async.bulk.tensor.3d.shared::cluster.global.mbarrier::complete_tx::bytes [%0], [%1, {%3, %4, %5}], [%2];\n}"
               ::"r"(dst), "l"(m), "r"(bar), "r"(c0), "r"(c1), "r"(c2) : "memory");
}
__device__ __forceinline__ void tma_ld3_hint_w(uint32_t dst, const CUtensorMap* m, int c0, int c1, int c2, uint32_t bar, uint64_t pol) {
  asm volatile(ELECT EXPECT("%2", "16384") "cp.async.bulk.tensor.3d.shared::cluster.global.mbarrier::complete_tx::bytes.L2::cache_hint"
               " [%0], [%1, {%3, %4, %5}], [%2], %6;\n}"
               ::"r"(dst), "l"(m), "r"(bar), "r"(c0), "r"(c1), "r"(c2), "l"(pol) : "memory");
}
__device__ __forceinline__ void mbar_arrive8_w(uint32_t bar) {
  asm volatile(ELECT "mbarrier.arrive.shared::cta.b64 _, [%0], 8;\n}" ::"r"(bar) : "memory");
}
__device__ __forceinline__ void bulk_commit() { asm volatile("cp.async.bulk.commit_group;" ::: "memory"); }
template <int N> __device__ __forceinline__ void bulk_wait_read() { asm volatile("cp.async.bulk.wait_group.read %0;" ::"n"(N) : "memory"); }
__device__ __forceinline__ void wg_fence() { asm volatile("wgmma.fence.sync.aligned;" ::: "memory"); }
__device__ __forceinline__ void wg_commit() { asm volatile("wgmma.commit_group.sync.aligned;" ::: "memory"); }
template <int N> __device__ __forceinline__ void wg_wait() { asm volatile("wgmma.wait_group.sync.aligned %0;" ::"n"(N) : "memory"); }
__device__ __forceinline__ void fence_async_smem() { asm volatile("fence.proxy.async.shared::cta;" ::: "memory"); }
__device__ __forceinline__ void bar_sync(int id, int n) { asm volatile("bar.sync %0, %1;" ::"r"(id), "r"(n) : "memory"); }
template <int N> __device__ __forceinline__ void reg_fence(float (&a)[N]) {
#pragma unroll
  for (int i = 0; i < N; i++) asm volatile("" : "+f"(a[i])::"memory");
}
template <int N> __device__ __forceinline__ void reg_fence(uint32_t (&a)[N]) {
#pragma unroll
  for (int i = 0; i < N; i++) asm volatile("" : "+r"(a[i])::"memory");
}
__device__ __forceinline__ float ex2(float x) { float y; asm("ex2.approx.ftz.f32 %0, %1;" : "=f"(y) : "f"(x)); return y; }
__device__ __forceinline__ uint32_t pack_bf16(float lo, float hi) {
  uint32_t r; asm("cvt.rn.bf16x2.f32 %0, %1, %2;" : "=r"(r) : "f"(hi), "f"(lo)); return r;
}
__device__ __forceinline__ void stsm4(uint32_t a, uint32_t r0, uint32_t r1, uint32_t r2, uint32_t r3) {
  asm volatile("stmatrix.sync.aligned.m8n8.x4.shared.b16 [%0], {%1, %2, %3, %4};" ::"r"(a), "r"(r0), "r"(r1), "r"(r2), "r"(r3) : "memory");
}
__device__ __forceinline__ void stsm4t(uint32_t a, uint32_t r0, uint32_t r1, uint32_t r2, uint32_t r3) {
  asm volatile("stmatrix.sync.aligned.m8n8.x4.trans.shared.b16 [%0], {%1, %2, %3, %4};" ::"r"(a), "r"(r0), "r"(r1), "r"(r2), "r"(r3) : "memory");
}
__device__ __forceinline__ void ldsm4(uint32_t a, uint32_t& r0, uint32_t& r1, uint32_t& r2, uint32_t& r3) {
  asm volatile("ldmatrix.sync.aligned.m8n8.x4.shared.b16 {%0, %1, %2, %3}, [%4];" : "=r"(r0), "=r"(r1), "=r"(r2), "=r"(r3) : "r"(a) : "memory");
}
__device__ __forceinline__ void sts16(uint32_t a, uint32_t v) { asm volatile("st.shared.u16 [%0], %1;" ::"r"(a), "h"((uint16_t)v) : "memory"); }
__device__ __forceinline__ void mma16816(float& c0, float& c1, float& c2, float& c3, uint32_t a0, uint32_t a1, uint32_t a2, uint32_t a3,
                                         uint32_t b0, uint32_t b1) {
  asm volatile("mma.sync.aligned.m16n8k16.row.col.f32.bf16.bf16.f32 {%0, %1, %2, %3}, {%4, %5, %6, %7}, {%8, %9}, {%0, %1, %2, %3};"
               : "+f"(c0), "+f"(c1), "+f"(c2), "+f"(c3) : "r"(a0), "r"(a1), "r"(a2), "r"(a3), "r"(b0), "r"(b1));
}
__device__ __forceinline__ uint32_t sdesc(uint32_t addr, uint32_t lbo) { return (addr >> 4) + ((lbo >> 4) << 16); }
__device__ __forceinline__ uint64_t desc64(uint32_t lo, uint32_t hi) { uint64_t d; asm("mov.b64 %0, {%1, %2};" : "=l"(d) : "r"(lo), "r"(hi)); return d; }
__device__ __forceinline__ void dadd(uint64_t& d, uint32_t inc) {
  asm("{\n.reg .b32 l, h;\nmov.b64 {l, h}, %0;\nadd.u32 l, l, %1;\nmov.b64 %0, {l, h};\n}" : "+l"(d) : "r"(inc));
}

struct Ring {
  uint32_t slot, phase, xp;
  __device__ __forceinline__ void uniform() {
    slot = __shfl_sync(0xffffffffu, slot, 0); phase = __shfl_sync(0xffffffffu, phase, 0); xp = __shfl_sync(0xffffffffu, xp, 0);
  }
  __device__ __forceinline__ void next() { if (++slot == NS) { slot = 0; phase ^= 1; } }
  __device__ __forceinline__ void next_if(bool p) { slot += p; if (slot == NS) { slot = 0; phase ^= 1; } }
};
__device__ __forceinline__ uint32_t borrow(int ks, int n) { const int k = ks + 1; return k >= 4 && (k | 3) - 1 <= n ? k & 3 : 3; }

constexpr uint32_t Q_RANGES = NBETA * NH + P_EARLY * 5;
constexpr int TAIL_STEPS = (NBETA - P_EARLY) * 64, NRANGE = NCTA / 5;
struct Work { int kind, mode, k0, nsteps, range, beta, sub; };
struct Sched { uint16_t queue[Q_RANGES]; uint32_t piece[NRANGE + 1][4]; };
constexpr Sched make_sched() {
  Sched s{};
  int q = 0, a = 0;
  for (int pass = 0; pass < 2; pass++)
    for (int b = pass ? B_LATE : 0; b < NBETA; b++)
      for (int h = pass ? H_LATE : 0; h < (pass || b < B_LATE ? NH : H_LATE); h++) {
        if (a >= P_POS && (a - P_POS) % P_STRIDE == 0 && (a - P_POS) / P_STRIDE < P_EARLY)
          for (int col = 0; col < 5; col++) s.queue[q++] = 0x8000 | col << 8 | (a - P_POS) / P_STRIDE;
        s.queue[q++] = b << 5 | h;
        a++;
      }
  constexpr int B[NRANGE + 1] = {RANGE_TABLE};
  constexpr int ORD[NRANGE] = {RANGE_ORDER};
  for (int g = 0; g <= NRANGE; g++) {
    int n = 0;
    if (g < NRANGE) {
      const int r = ORD[g];
      for (int pos = B[r]; pos < B[r + 1];) {
        const int te = (pos | 63) + 1, stop = B[r + 1] < te ? B[r + 1] : te, mode = pos & 63 ? 1 : stop == te ? 0 : 2;
        int f = 0;
        if (mode == 2) { f = 1; while (B[r + 1 + f] < te) f++; }
        s.piece[g][n++] = 1u << 30 | mode << 28 | (te - stop) << 22 | (stop - pos - 1) << 16 | r << 11 | f << 5 | (P_EARLY + (pos >> 6));
        pos = stop;
      }
    }
    for (; n < 4; n++) s.piece[g][n] = 2u << 30;
  }
  return s;
}
__constant__ Sched c_sched = make_sched();
__device__ __forceinline__ Work decode(uint32_t d) {
  Work w;
  w.kind = d >> 30; if (w.kind == 3) w.kind = 1;
  w.mode = (d >> 28) & 3; w.k0 = (d >> 22) & 63;
  if (w.kind == 0) { w.beta = (d >> 5) & 31; w.sub = d & 31; w.nsteps = DM / 64; }
  else { w.beta = d & 31; w.sub = (d >> 8) & 7; w.nsteps = ((d >> 16) & 63) + 1; }
  w.range = ((d >> 11) & 31) * 5 + w.sub;
  return w;
}

__device__ __forceinline__ bool reached(const unsigned* cnt, unsigned target) {
  unsigned v;
  asm volatile("ld.acquire.gpu.global.u32 %0, [%1];" : "=r"(v) : "l"(cnt) : "memory");
  return (int)(v - target) >= 0;
}
__device__ __forceinline__ void wait_count(const unsigned* cnt, unsigned target) {
  unsigned n = 0;
  while (!__all_sync(0xffffffffu, reached(cnt, target))) { if (++n > (1u << 24)) __trap(); }
}
__device__ __forceinline__ uint32_t lds(uint32_t a) { uint32_t v; asm volatile("ld.volatile.shared.u32 %0, [%1];" : "=r"(v) : "r"(a) : "memory"); return v; }

#define TRACE(u, e)
#define T3(u, e)
#define T2C(u, e)
#define T2P(u, r, e)
#define TRACE_P(u, e)
#define TRACE_IN(u, e)

struct Ctx {
  uint32_t sb;
  int wg, warp;
  uint32_t mqk, mpv;
  bool lead;
  int src;
};
template <int N> __device__ __forceinline__ uint32_t dhi(uint32_t lo) { return 0x40000040u + (lo >> (26 + N)); }
template <int N> __device__ __forceinline__ uint64_t full_desc(uint32_t addr, uint32_t slot) { return desc64(addr >> 4, dhi<N>(slot)); }
__device__ __forceinline__ void release(const Ctx& c, uint32_t slot) {
  if (c.lead) mbar_arrive(c.sb + BAR_EMPTY + slot * 8);
}
__device__ __forceinline__ uint32_t acquire(const Ctx& c, Ring& r) {
  const uint32_t s = r.slot;
  mbar_wait_w(c.sb + BAR_FULL + s * 8, r.phase);
  r.next();
  return s;
}
__device__ __forceinline__ void mbar_wait2_w(uint32_t b0, uint32_t p0, uint32_t b1, uint32_t p1) {
  uint32_t n = 0;
  while (!__all_sync(0xffffffffu, mbar_try(b0, p0) & mbar_try(b1, p1))) {
    if (++n > (1u << 22)) __trap();
  }
}
__device__ __forceinline__ void acquire2(const Ctx& c, Ring& r, uint32_t& s0, uint32_t& s1, bool wait = true) {
  const uint32_t p0 = r.phase;
  s0 = r.slot; r.next(); s1 = r.slot;
  if (wait) mbar_wait2_w(c.sb + BAR_FULL + s0 * 8, p0, c.sb + BAR_FULL + s1 * 8, r.phase);
  r.next();
}
__device__ __forceinline__ void staged(const Ctx& c, int part) {
  fence_async_smem();
  __syncwarp();
  mbar_arrive_warp(c.sb + BAR_STG + c.wg * 16 + part * 8);
}

template <bool FIRST, bool HI>
__device__ __forceinline__ void proj_half(const Ctx& c, float (&acc)[64], uint32_t w, uint32_t x) {
  uint64_t a = full_desc<0>(c.sb + w * SLOT + c.wg * 8192, x), b = full_desc<1>(c.sb + x * SLOT, x);
  wg_fence();
  if (HI) { if (FIRST) wgmma_proj96_init(acc, a, b, 0); else wgmma_proj96(acc, a, b, 1); }
  else { if (FIRST) wgmma_proj_init(acc, a, b, 0); else wgmma_proj(acc, a, b, 1); }
#pragma unroll
  for (int k = 1; k < 4; k++) { dadd(a, 128); dadd(b, 2); if (HI) wgmma_proj96(acc, a, b, 1); else wgmma_proj(acc, a, b, 1); }
  wg_commit();
}

__device__ __forceinline__ void proj_store16(uint32_t a, const float* f, float sc) {
  stsm4t(a, pack_bf16(f[0] * sc, f[1] * sc), pack_bf16(f[2] * sc, f[3] * sc), pack_bf16(f[4] * sc, f[5] * sc), pack_bf16(f[6] * sc, f[7] * sc));
}

__device__ __forceinline__ uint32_t stage_off(const Ctx& c) {
  const int lane = lane_now(), mi = lane >> 3, r8 = lane & 7;
  return ((mi >> 1) * 8 + r8) * 128 + (((2 * c.warp + (mi & 1)) ^ r8) << 4);
}
__device__ __forceinline__ void stage_lo(const Ctx& c, const float (&a0)[64], float sc) {
  const uint32_t lane_off = c.sb + QBUF_OFF + c.wg * 8192 + stage_off(c);
#pragma unroll
  for (int jj = 0; jj < 8; jj++) proj_store16(lane_off + (jj >> 2) * 16384 + (jj & 3) * 2048, &a0[jj * 8], sc);
}
__device__ __forceinline__ uint32_t q3_swz(uint32_t r8) { return ((r8 & 3) << 1) | (r8 >> 2); }
template <bool IS_Q>
__device__ __forceinline__ void stage_hi(const Ctx& c, const float (&a1)[64], float sc) {
  const uint32_t off = stage_off(c), lane_off = c.sb + QBUF_OFF + 2 * 16384 + c.wg * 8192 + off;
#pragma unroll
  for (int jj = 0; jj < 4; jj++) proj_store16(lane_off + jj * 2048, &a1[jj * 8], sc);
  const uint32_t r8 = (off >> 7) & 7;
  const uint32_t t3 = c.sb + QBUF_OFF + 3 * 16384 + c.wg * 4096 + (IS_Q ? off ^ ((r8 ^ q3_swz(r8)) << 4) : off);
  proj_store16(t3, &a1[32], sc);
  proj_store16(t3 + 2048, &a1[40], sc);
}

__device__ __forceinline__ void add16(uint32_t a, float* f) {
  uint32_t r[4];
  asm volatile("ldmatrix.sync.aligned.m8n8.x4.trans.shared.b16 {%0, %1, %2, %3}, [%4];"
               : "=r"(r[0]), "=r"(r[1]), "=r"(r[2]), "=r"(r[3]) : "r"(a) : "memory");
#pragma unroll
  for (int i = 0; i < 4; i++) { f[2 * i] += __uint_as_float(r[i] << 16); f[2 * i + 1] += __uint_as_float(r[i] & 0xffff0000u); }
}

__device__ __forceinline__ void trace_dump(const Ctx& c) {
}
struct Slots { uint32_t w, x; };
__device__ __forceinline__ void proj_begin(const Ctx& c, Ring& r, float (&a0)[64], Slots& h, bool wait) {
  acquire2(c, r, h.w, h.x, wait);
  proj_half<true, false>(c, a0, h.w, h.x);
}
__device__ __forceinline__ void proj_main(const Ctx& c, Ring& r, float (&a0)[64], float (&a1)[64], Slots& h, int kind, int n, int unit) {
  T2C(unit, 1);
  uint32_t y = acquire(c, r), w = h.w, x, py;
  T2C(unit, 2);
  wg_wait<0>();
  T2C(unit, 3);
  release(c, h.x);
  proj_half<true, true>(c, a1, w, y);
  int ks = 1;
#pragma unroll 1
  while (true) {
    const uint32_t b = borrow(ks, n), pw = w, p0 = r.phase;
    w = r.slot; r.next();
    const uint32_t p1 = b != 3 ? r.xp : r.phase;
    x = b != 3 ? NS + b : r.slot; r.next_if(b == 3);
    mbar_wait2_w(c.sb + BAR_FULL + w * 8, p0, c.sb + BAR_FULL + x * 8, p1);
    if (ks < 10) T2C(unit, ks * 4);
    wg_wait<0>();
    if (ks < 10) T2C(unit, ks * 4 + 1);
    release(c, pw); release(c, y);
    proj_half<false, false>(c, a0, w, x);
    py = b == 0 ? r.xp : r.phase;
    y = b == 0 ? NS + 3 : r.slot; r.next_if(b != 0);
    r.xp ^= b == 2;
    if (++ks == n) break;
    mbar_wait_w(c.sb + BAR_FULL + y * 8, py);
    if (ks < 11) T2C(unit, ks * 4 - 2);
    wg_wait<0>();
    if (ks < 11) T2C(unit, ks * 4 - 1);
    release(c, x);
    proj_half<false, true>(c, a1, w, y);
  }
  {
    const uint32_t pe = r.xp ^ (unit & 1) ^ 1, k0 = kind == 0 ? r.slot : y, pk = kind == 0 ? r.phase : py;
    uint32_t cnt = 0;
    while (true) {
      bool ok = mbar_try(c.sb + BAR_FULL + y * 8, py) & mbar_try(c.sb + BAR_FULL + k0 * 8, pk);
#pragma unroll
      for (int t = 0; t < 2; t++) ok &= mbar_try(c.sb + BAR_EMPTY + (NS + t) * 8, pe);
      if (__all_sync(0xffffffffu, ok)) break;
      if (++cnt > (1u << 22)) __trap();
    }
  }
  T2C(unit, 38);
  wg_wait<0>();
  T2C(unit, 39);
  release(c, x);
  proj_half<false, true>(c, a1, w, y);
  h.w = w; h.x = y;
  reg_fence(a0);
}
__device__ __forceinline__ void wait_hi_free(const Ctx& c, const Ring& r, int unit) {
  const uint32_t pe = r.xp ^ (unit & 1) ^ 1;
  mbar_wait2_w(c.sb + BAR_EMPTY + (NS + 2) * 8, pe, c.sb + BAR_EMPTY + (NS + 3) * 8, pe);
}
__device__ __forceinline__ void proj_end(const Ctx& c, float (&a1)[64], const Slots& h) {
  wg_wait<0>();
#pragma unroll
  for (int i = 0; i < 48; i++) asm volatile("" : "+f"(a1[i])::"memory");
  release(c, h.w); release(c, h.x);
}
__device__ __forceinline__ uint32_t get_desc(const Ctx& c, int i) {
  uint32_t d;
  mbar_wait_w(c.sb + BAR_DESC, (i - 1) & 1);
  asm volatile("ld.volatile.shared.u32 %0, [%1];" : "=r"(d) : "r"(c.sb + DESC_OFF + (i & 3) * 4) : "memory");
  return __shfl_sync(0xffffffffu, d, 0);
}

struct RowSum { float l0, l1; };

__device__ __forceinline__ float quad_max(float x) {
  x = fmaxf(x, __shfl_xor_sync(0xffffffffu, x, 1));
  return fmaxf(x, __shfl_xor_sync(0xffffffffu, x, 2));
}
__device__ __forceinline__ float quad_sum(float x) {
  x += __shfl_xor_sync(0xffffffffu, x, 1);
  return x + __shfl_xor_sync(0xffffffffu, x, 2);
}
template <bool SP, bool FIRST>
__device__ __forceinline__ void exps(const Ctx& c, const float (&s)[32], uint32_t (&p)[SP ? 8 : 16], RowSum& st) {
  if constexpr (SP) {
    uint32_t q[8];
    float t;
#pragma unroll
    for (int j = 0; j < 8; j++) {
      const float e0 = ex2(s[4 * j] + s[4 * j + 2]), e1 = ex2(s[4 * j + 1] + s[4 * j + 3]);
      if (j == 0) t = e0 + e1; else t += e0 + e1;
      q[j] = pack_bf16(e0, e1);
    }
    const bool odd = c.src & 2;
#pragma unroll
    for (int g = 0; g < 4; g++) {
      p[2 * g] = __shfl_sync(0xffffffffu, odd ? q[2 * g + 1] : q[2 * g], c.src);
      p[2 * g + 1] = __shfl_sync(0xffffffffu, odd ? q[2 * g] : q[2 * g + 1], c.src ^ 1);
    }
    st.l0 = FIRST ? t : st.l0 + t;
  } else {
    float t0, t1;
#pragma unroll
    for (int j = 0; j < 8; j++) {
      const float e0 = ex2(s[4 * j]), e1 = ex2(s[4 * j + 1]), e2 = ex2(s[4 * j + 2]), e3 = ex2(s[4 * j + 3]);
      if (j == 0) { t0 = e0 + e1; t1 = e2 + e3; } else { t0 += e0 + e1; t1 += e2 + e3; }
      p[2 * j] = pack_bf16(e0, e1);
      p[2 * j + 1] = pack_bf16(e2, e3);
    }
    st.l0 = FIRST ? t0 : st.l0 + t0;
    st.l1 = FIRST ? t1 : st.l1 + t1;
  }
}
template <bool SP>
__device__ __forceinline__ bool finish_sums(RowSum& st) {
  const float a = quad_sum(st.l0), b = SP ? a : quad_sum(st.l1);
  st.l0 = __fdividef(1.f, a); st.l1 = __fdividef(1.f, b);
  return !(a >= SUM_LO && a <= SUM_HI && b >= SUM_LO && b <= SUM_HI);
}
template <bool SP, bool INIT, int SITE, bool COMMIT = true>
__device__ __forceinline__ void issue_qk(const Ctx& c, float (&s)[32], const uint32_t (&qs)[16], uint32_t dq, uint32_t dk) {
  uint64_t a = desc64(dq, dhi<SITE & 1>(dk)), b = desc64(dk, dhi<1 - (SITE & 1)>(dk));
  if (SP) {
    if (INIT) wgmma_qk_sp_init(s, qs[0], qs[1], qs[2], qs[3], b, 0, c.mqk); else wgmma_qk_sp(s, qs[0], qs[1], qs[2], qs[3], b, 0, c.mqk);
#pragma unroll
    for (int k = 1; k < 4; k++) { dadd(b, k == 2 ? 508 : 4); wgmma_qk_sp(s, qs[4 * k], qs[4 * k + 1], qs[4 * k + 2], qs[4 * k + 3], b, 1, c.mqk); }
  } else {
    if (INIT) wgmma_qk_init(s, a, b, 0); else wgmma_qk(s, a, b, 0);
#pragma unroll
    for (int k = 1; k < 8; k++) { dadd(a, k == 4 ? 506 : 2); dadd(b, k == 4 ? 506 : 2); wgmma_qk(s, a, b, 1); }
  }
  if (COMMIT) wg_commit();
}
template <bool SP, bool ACC, int SITE, bool SPLIT = false>
__device__ __forceinline__ void issue_pv(const Ctx& c, float (&o)[64], const uint32_t (&p)[SP ? 8 : 16], uint32_t dv) {
  uint64_t b = desc64(dv, dhi<SITE & 1>(dv));
  if constexpr (SP) {
    if (ACC) wgmma_pv_sp(o, p[0], p[1], p[2], p[3], b, 1, c.mpv); else wgmma_pv_sp_init(o, p[0], p[1], p[2], p[3], b, 0, c.mpv);
    if (SPLIT) wg_commit();
    dadd(b, 256);
    wgmma_pv_sp(o, p[4], p[5], p[6], p[7], b, 1, c.mpv);
  } else {
    if (ACC) wgmma_pv(o, p[0], p[1], p[2], p[3], b, 1); else wgmma_pv_init(o, p[0], p[1], p[2], p[3], b, 0);
#pragma unroll
    for (int k = 1; k < 4; k++) { dadd(b, 128); wgmma_pv(o, p[4 * k], p[4 * k + 1], p[4 * k + 2], p[4 * k + 3], b, 1); }
  }
  wg_commit();
}
template <bool SP>
__device__ __forceinline__ void o_store(const Ctx& c, uint32_t tile_addr, const float (&o)[64], const RowSum& inv, uint32_t half = 8192) {
  const int lane = lane_now(), mi = lane >> 3, r8 = lane & 7;
  if (SP) {
    const float i0 = inv.l0;
    const uint32_t row_addr = tile_addr + (8 * c.warp + r8) * 128;
#pragma unroll
    for (int jj = 0; jj < 4; jj++) {
      const int b = jj * 16;
      stsm4(row_addr + (jj >> 1) * 4096 + ((((jj & 1) * 4 + mi) ^ r8) << 4),
            pack_bf16((o[b] + o[b + 2]) * i0, (o[b + 1] + o[b + 3]) * i0), pack_bf16((o[b + 4] + o[b + 6]) * i0, (o[b + 5] + o[b + 7]) * i0),
            pack_bf16((o[b + 8] + o[b + 10]) * i0, (o[b + 9] + o[b + 11]) * i0),
            pack_bf16((o[b + 12] + o[b + 14]) * i0, (o[b + 13] + o[b + 15]) * i0));
    }
  } else {
    const float i0 = inv.l0, i1 = inv.l1;
    const uint32_t row_addr = tile_addr + (16 * c.warp + (mi & 1) * 8 + r8) * 128;
#pragma unroll
    for (int jj = 0; jj < 8; jj++) {
      const int b = jj * 8;
      stsm4(row_addr + (jj >> 2) * half + (((((2 * jj) & 7) + (mi >> 1)) ^ r8) << 4),
            pack_bf16(o[b] * i0, o[b + 1] * i0), pack_bf16(o[b + 2] * i1, o[b + 3] * i1),
            pack_bf16(o[b + 4] * i0, o[b + 5] * i0), pack_bf16(o[b + 6] * i1, o[b + 7] * i1));
    }
  }
}

__device__ __forceinline__ void redo_tile(const Ctx& c, uint32_t q_addr, uint32_t half, const __nv_bfloat16* kp, const __nv_bfloat16* vp) {
  float o[64];
  const int lane = lane_now(), g = lane >> 2, cc = lane & 3, mi = lane >> 3, r8 = lane & 7;
  const uint32_t qa = q_addr + (16 * c.warp + (mi & 1) * 8 + r8) * 128, swz = half == 4096 ? q3_swz(r8) : r8;
  const uint32_t* kq = reinterpret_cast<const uint32_t*>(kp + g * DH) + cc;
  const unsigned short* vq = reinterpret_cast<const unsigned short*>(vp + 2 * cc * DH) + g;
  float m0 = -INFINITY, m1 = -INFINITY, l0 = 0.f, l1 = 0.f;
#pragma unroll
  for (int i = 0; i < 64; i++) o[i] = 0.f;
#pragma unroll 1
  for (int kb = 0; kb < SK / 16; kb++) {
    float z[8] = {0.f, 0.f, 0.f, 0.f, 0.f, 0.f, 0.f, 0.f};
#pragma unroll 2
    for (int kk = 0; kk < 8; kk++) {
      uint32_t a0, a1, a2, a3;
      ldsm4(qa + (kk >> 2) * half + ((((kk & 3) * 2 + (mi >> 1)) ^ swz) << 4), a0, a1, a2, a3);
      const uint32_t* kr = kq + kb * (16 * DH / 2) + kk * 8;
      mma16816(z[0], z[1], z[2], z[3], a0, a1, a2, a3, __ldg(kr), __ldg(kr + 4));
      mma16816(z[4], z[5], z[6], z[7], a0, a1, a2, a3, __ldg(kr + 8 * DH / 2), __ldg(kr + 8 * DH / 2 + 4));
    }
    const float n0 = fmaxf(m0, quad_max(fmaxf(fmaxf(z[0], z[1]), fmaxf(z[4], z[5]))));
    const float n1 = fmaxf(m1, quad_max(fmaxf(fmaxf(z[2], z[3]), fmaxf(z[6], z[7]))));
    const float al0 = ex2(m0 - n0), al1 = ex2(m1 - n1);
    m0 = n0; m1 = n1;
#pragma unroll
    for (int i = 0; i < 8; i++) z[i] = ex2(z[i] - ((i & 2) ? n1 : n0));
    l0 = l0 * al0 + (z[0] + z[1]) + (z[4] + z[5]);
    l1 = l1 * al1 + (z[2] + z[3]) + (z[6] + z[7]);
    const uint32_t a0 = pack_bf16(z[0], z[1]), a1 = pack_bf16(z[2], z[3]), a2 = pack_bf16(z[4], z[5]), a3 = pack_bf16(z[6], z[7]);
    const unsigned short* vr = vq + kb * (16 * DH);
#pragma unroll
    for (int nb = 0; nb < 16; nb++) {
      o[4 * nb] *= al0; o[4 * nb + 1] *= al0; o[4 * nb + 2] *= al1; o[4 * nb + 3] *= al1;
      const uint32_t b0 = __ldg(vr + nb * 8) | ((uint32_t)__ldg(vr + nb * 8 + DH) << 16);
      const uint32_t b1 = __ldg(vr + nb * 8 + 8 * DH) | ((uint32_t)__ldg(vr + nb * 8 + 9 * DH) << 16);
      mma16816(o[4 * nb], o[4 * nb + 1], o[4 * nb + 2], o[4 * nb + 3], a0, a1, a2, a3, b0, b1);
    }
  }
  __syncwarp();
  o_store<false>(c, q_addr, o, RowSum{__fdividef(1.f, quad_sum(l0)), __fdividef(1.f, quad_sum(l1))}, half);
}

template <bool SPA, bool SPB, int SITE, int ID>
__device__ __forceinline__ void batch(const Ctx& c, float (&s)[32], const uint32_t (&qs)[16], uint32_t dq, uint32_t dk, float (&ob)[64],
                                      uint32_t (&pb)[SPB ? 8 : 16], uint32_t dv) {
  if constexpr (SPA) {
    reg_fence(pb);
    wg_fence();
    issue_pv<SPB, true, ID>(c, ob, pb, dv);
    issue_qk<SPA, false, ID>(c, s, qs, dq, dk);
  } else {
    constexpr bool EARLY = ((QK_EARLY_MASK >> (SITE + (SPB ? 2 : 0))) & 1) != 0;
    if (!EARLY) reg_fence(pb);
    wg_fence();
    issue_qk<SPA, false, ID, !SPB>(c, s, qs, dq, dk);
    if (EARLY) { reg_fence(pb); wg_fence(); }
    issue_pv<SPB, true, ID, SPB>(c, ob, pb, dv);
  }
}

template <bool SP0>
__device__ __forceinline__ bool attention(Ctx c, Ring& r, int unit, uint32_t& d, float (&o1)[64], RowSum& st1, const Slots& h) {
  constexpr bool SP1 = false;
  c.wg = SP0;
  if (SP0) { c.mqk = META_QK + (d >> 28); c.mpv = META_PV + (d >> 28); asm volatile("" : "+r"(c.mqk), "+r"(c.mpv)); }
  if (SP0) { const int lane = lane_now(); c.src = (lane & 28) | ((lane & 1) << 1) | ((lane >> 1) & 1); }
  float o0[64], s[32];
  uint32_t p0[SP0 ? 8 : 16], p1[16];
  RowSum st0;
  const uint32_t q0a = c.sb + QBUF_OFF + (SP0 ? 3 : 0) * 16384, q1a = c.sb + QBUF_OFF + (SP0 ? 2 : 1) * 16384;
  const uint32_t dq0 = sdesc(q0a, 0), dq1 = sdesc(q1a, 0);
  uint32_t sk = r.slot, sv, sn;
  r.next();
  uint32_t qs[16];
  if (SP0) {
    asm volatile("bar.arrive 1, 256;" ::: "memory");
    proj_end(c, o1, h);
    wait_hi_free(c, r, unit);
    T2C(unit, 42);
    stage_hi<true>(c, o1, SM_C);
    fence_async_smem();
    T2C(unit, 43);
    bar_sync(6, 256);
    const int lane = lane_now(), g = lane >> 2, cc = lane & 3;
    const uint32_t qa = q0a + (8 * c.warp + g) * 128 + (cc & 1) * 8;
#pragma unroll
    for (int k = 0; k < 8; k++)
      asm volatile("ld.shared.v2.u32 {%0, %1}, [%2];" : "=r"(qs[2 * k]), "=r"(qs[2 * k + 1])
                   : "r"(qa + (k >> 2) * 4096 + ((((k & 3) * 2 + (cc >> 1)) ^ q3_swz(g)) << 4)) : "memory");
  } else {
    proj_end(c, o1, h);
    if (QSTART == 1) {
      wait_hi_free(c, r, unit);
      T2C(unit, 42);
      stage_hi<true>(c, o1, SM_C);
      fence_async_smem();
      asm volatile("bar.arrive 6, 256;" ::: "memory");
    }
    T2C(unit, 43);
    bar_sync(1, 256);
  }
  TRACE(unit, 2);
  T2C(unit, 44);
  if (SP0 && QD_FIRST) {
    float s1[32];
    wg_fence();
    issue_qk<SP1, true, 1>(c, s1, qs, dq1, sdesc(c.sb + sk * SLOT, 0));
    reg_fence(qs);
    wg_fence();
    issue_qk<SP0, true, 0>(c, s, qs, dq0, sdesc(c.sb + sk * SLOT, 0));
    T2C(unit, 45);
    acquire2(c, r, sv, sn);
    wg_wait<1>();
    reg_fence(s1);
    T2C(unit, 47);
    exps<SP1, true>(c, s1, p1, st1);
    reg_fence(p1);
    wg_fence();
    issue_pv<SP1, false, 1>(c, o1, p1, sdesc(c.sb + sv * SLOT, 8192));
    wg_wait<1>();
    reg_fence(s);
    T2C(unit, 48);
    release(c, sk);
    sk = sn;
    exps<SP0, true>(c, s, p0, st0);
    reg_fence(p0);
    wg_fence();
    issue_pv<SP0, false, 0>(c, o0, p0, sdesc(c.sb + sv * SLOT, 8192));
    issue_qk<SP0, false, 2>(c, s, qs, dq0, sdesc(c.sb + sk * SLOT, 0));
    T2C(unit, 49);
    sn = acquire(c, r);
    T2C(unit, 50);
    wg_wait<0>();
    reg_fence(s);
  } else
  {
    float s1[32];
    wg_fence();
    issue_qk<SP0, true, 0>(c, s, qs, dq0, sdesc(c.sb + sk * SLOT, 0));
    issue_qk<SP1, true, 1>(c, s1, qs, dq1, sdesc(c.sb + sk * SLOT, 0));
    T2C(unit, 45);
    if (!SP0 && QSTART == 0) {
      wait_hi_free(c, r, unit);
#pragma unroll
      for (int i = 0; i < 48; i++) asm volatile("" : "+f"(o1[i])::"memory");
      stage_hi<true>(c, o1, SM_C);
      fence_async_smem();
      asm volatile("bar.arrive 6, 256;" ::: "memory");
    }
    T2C(unit, 46);
    acquire2(c, r, sv, sn);
    wg_wait<1>();
    reg_fence(s);
    T2C(unit, 47);
    exps<SP0, true>(c, s, p0, st0);
    reg_fence(p0);
    wg_fence();
    issue_qk<SP0, false, 2>(c, s, qs, dq0, sdesc(c.sb + sn * SLOT, 0));
    issue_pv<SP0, false, 0>(c, o0, p0, sdesc(c.sb + sv * SLOT, 8192));
    wg_wait<2>();
    reg_fence(s1);
    T2C(unit, 48);
    release(c, sk);
    sk = sn;
    exps<SP1, true>(c, s1, p1, st1);
    reg_fence(p1);
    wg_fence();
    issue_pv<SP1, false, 1>(c, o1, p1, sdesc(c.sb + sv * SLOT, 8192));
    T2C(unit, 49);
    sn = acquire(c, r);
    T2C(unit, 50);
    wg_wait<1>();
    reg_fence(s);
  }
  TRACE_IN(unit, 4);
  T2C(unit, 51);
#pragma unroll 1
  for (int j = 1; j < 15; j++) {
    const uint32_t sv_prev = sv, sk_prev = sk;
    sv = sn;
    const uint32_t dv = sdesc(c.sb + sv * SLOT, 8192);
    reg_fence(p0);
    exps<SP0, false>(c, s, p0, st0);
    batch<SP1, SP0, 0, 3>(c, s, qs, dq1, sdesc(c.sb + sk * SLOT, 0), o0, p0, dv);
    sk = acquire(c, r);
    wg_wait<1>();
    reg_fence(s); reg_fence(p1);
    release(c, sv_prev); release(c, sk_prev);
    exps<SP1, false>(c, s, p1, st1);
    batch<SP0, SP1, 1, 4>(c, s, qs, dq0, sdesc(c.sb + sk * SLOT, 0), o1, p1, dv);
    sn = acquire(c, r);
    if (SP0) wg_wait<0>(); else wg_wait<1>();
    reg_fence(s);
  }
  TRACE_IN(unit, 5);
  T2C(unit + 1, 52);
  const uint32_t sv_prev = sv;
  sv = sn;
  const uint32_t dv = sdesc(c.sb + sv * SLOT, 8192);
  reg_fence(p0);
  exps<SP0, false>(c, s, p0, st0);
  batch<SP1, SP0, 0, 5>(c, s, qs, dq1, sdesc(c.sb + sk * SLOT, 0), o0, p0, dv);
  asm volatile("ld.volatile.shared.u32 %0, [%1];" : "=r"(d) : "r"(c.sb + DESC_OFF + ((unit + 1) & 3) * 4) : "memory");
  wg_wait<1>();
  reg_fence(s); reg_fence(p1);
  T2C(unit + 1, 53);
  release(c, sv_prev); release(c, sk);
  d = __shfl_sync(0xffffffffu, d, 0);
  bool bad = finish_sums<SP0>(st0);
  exps<SP1, false>(c, s, p1, st1);
  reg_fence(p1);
  wg_fence();
  issue_pv<SP1, true, 2>(c, o1, p1, dv);
  T2C(unit + 1, 54);
  Ring t = r;
  t.next();
  const bool have = EARLY_BEG && (mbar_test(c.sb + BAR_FULL + r.slot * 8, r.phase) & mbar_test(c.sb + BAR_FULL + t.slot * 8, t.phase));
  bad |= finish_sums<SP1>(st1);
  uint32_t any;
  asm volatile("{\n.reg .pred p, q;\nsetp.ne.u32 p, %1, 0;\nbar.red.or.pred q, %2, 128, p;\nselp.u32 %0, 1, 0, q;\n}"
               : "=r"(any) : "r"((uint32_t)bad), "n"(2 + SP0) : "memory");
  bad = __any_sync(0xffffffffu, any);
  if (EARLY_BEG && d < (2u << 30) && !__all_sync(0xffffffffu, have)) { uint32_t a, b; t = r; acquire2(c, t, a, b); }
  wg_wait<1>();
  reg_fence(o0);
  T2C(unit + 1, 55);
  if (__builtin_expect(!bad, 1)) {
    o_store<SP0>(c, q0a, o0, st0);
    staged(c, 0);
  }
  T2C(unit + 1, 56);
  wg_wait<0>();
  reg_fence(o1);
  T2C(unit + 1, 57);
  release(c, sv);
  return bad;
}

__device__ __forceinline__ void consumer(const Ctx& c, const __nv_bfloat16* const* kv) {
  Ring r{0, 0, 0};
  float a0[64], a1[64];
  Slots h;
  RowSum inv;
  uint32_t d = blockIdx.x, dc;
  int i = 0;
begin:
  proj_begin(c, r, a0, h, true);
  while (true) {
    TRACE(i, 0); TRACE(i, 6);
    dc = d;
    proj_main(c, r, a0, a1, h, d >> 30, d >> 30 ? ((d >> 16) & 63) + 1 : DM / 64, i);
    TRACE(i, 1);
    if (d >> 30) goto out_tile;
    T2C(i, 40);
    stage_lo(c, a0, SM_C);
    fence_async_smem();
    T2C(i, 41);
    if (c.wg == 0 ? attention<false>(c, r, i, d, a1, inv, h) : attention<true>(c, r, i, d, a1, inv, h)) goto redo;
    if (!EARLY_BEG || d >= (2u << 30)) break;
    proj_begin(c, r, a0, h, false);
    T2C(i + 1, 58);
    reg_fence(a1);
    o_store<false>(c, c.sb + QBUF_OFF + (c.wg + 1) * 16384, a1, inv);
    staged(c, 1);
    TRACE(i, 3); TRACE(i, 7);
    i++;
  }
  o_store<false>(c, c.sb + QBUF_OFF + (c.wg + 1) * 16384, a1, inv);
  staged(c, 1);
  T2C(i + 1, 58);
next:
  TRACE(i, 3); TRACE(i, 7);
  if ((d >> 30) != 2) {
    i++;
    r.uniform();
    goto begin;
  }
  trace_dump(c);
  return;
out_tile:
  proj_end(c, a1, h);
  if (((d >> 28) & 3) == 2) {
    const uint32_t off = c.sb + stage_off(c);
#pragma unroll 1
    for (int k = (d >> 5) & 3; k > 0; k--) {
#pragma unroll
      for (int t = 0; t < 4; t++) {
        const uint32_t sp = acquire(c, r), base = off + sp * SLOT + c.wg * (t == 3 ? 4096 : 8192);
#pragma unroll
        for (int jj = 0; jj < (t == 3 ? 2 : 4); jj++) add16(base + jj * 2048, t < 2 ? &a0[(t * 4 + jj) * 8] : &a1[((t - 2) * 4 + jj) * 8]);
        release(c, sp);
      }
    }
  }
  stage_lo(c, a0, 1.f);
  staged(c, 0);
  d = get_desc(c, i + 1);
  wait_hi_free(c, r, i);
  stage_hi<false>(c, a1, 1.f);
  staged(c, 1);
  TRACE(i, 2);
  goto next;
redo:
  {
    const size_t hoff = (size_t)(dc & 511) * (SK * DH);
    const int br = (dc >> 9) & 1;
#pragma unroll 1
    for (int part = 0; part < 2; part++) {
      const int t = c.wg ? 3 - part : part;
      if (t < 3 || c.warp < 2) redo_tile(c, c.sb + QBUF_OFF + t * 16384, t == 3 ? 4096 : 8192, kv[br] + hoff, kv[2 + br] + hoff);
      staged(c, part);
    }
  }
  goto next;
}

template <bool SIMPLE>
__global__ void __launch_bounds__(384, 1) mha_fused_kernel(const __grid_constant__ Params P) {
  extern __shared__ __align__(1024) uint8_t smem_raw[];
  const uint32_t sbase = smem_u32(smem_raw);
  const int tid = threadIdx.x;
  const int wg = __shfl_sync(0xffffffffu, tid >> 7, 0);
  const int warp = __shfl_sync(0xffffffffu, (tid >> 5) & 3, 0);
  const int lane = tid & 31;
  const int cta = blockIdx.x;

  if (tid == 0) T3(15, 0);
  if (tid >= 256 && tid < 256 + 18) asm volatile("prefetch.tensormap [%0];" ::"l"(&P.x[0][0] + (tid - 256)) : "memory");
  if (tid == 0) {
    if ((sbase & 1023) || sbase + SMEM_BYTES > 0x40000) __trap();
    for (int i = 0; i < NSX; i++) { mbar_init(sbase + BAR_FULL + i * 8, 1); mbar_init(sbase + BAR_EMPTY + i * 8, 8); }
    for (int i = 0; i < 4; i++) mbar_init(sbase + BAR_STG + i * 8, 4);
    mbar_init(sbase + BAR_DESC, 1);
    mbar_init(sbase + BAR_GO, 1);
    asm volatile("fence.mbarrier_init.release.cluster;" ::: "memory");
  }
  __syncthreads();

  if (wg == 2) {
    asm volatile("setmaxnreg.dec.sync.aligned.u32 %0;" ::"n"(REG_P));
    if (warp == 1) {
      const uint32_t qb = sbase + QBUF_OFF;
      const uint32_t ep = __shfl_sync(0xffffffffu, *(volatile unsigned*)&g_epoch + 1, 0);
      asm volatile("st.volatile.shared.u32 [%0], %1;" ::"r"(sbase + EPOCH_OFF), "r"(ep) : "memory");
      uint32_t dc = cta, qi = 0, piece = 0;
      for (int i = 0; (dc >> 30) != 2; i++) {
        mbar_wait_w(sbase + BAR_GO, i & 1);
        if (piece == 0) {
          if (lane == 0) {
            qi = atomicAdd(&g_next, 1);
            if (qi == (SIMPLE ? NBETA * (NH + 5) : Q_RANGES) - 1) { g_next = 0; g_epoch = ep; }
          }
          qi = __shfl_sync(0xffffffffu, qi, 0) + (SIMPLE ? gridDim.x : NCTA);
        }
        uint32_t d;
        if (qi < Q_RANGES) { d = c_sched.queue[qi]; if (d & 0x8000) d ^= (1u << 30) | (63u << 16) | 0x8000; }
        else if (SIMPLE) { const uint32_t t = qi - NBETA * NH; d = t < NBETA * 5 ? (1u << 30) | (63u << 16) | (t % 5) << 8 | t / 5 : 2u << 30; }
        else { const uint32_t e = qi - Q_RANGES, g = e / 5; d = c_sched.piece[g][piece++] | (e - g * 5) << 8; }
        if ((d >> 30) == 1) {
          const uint32_t ok = __ballot_sync(0xffffffffu, reached(&g_cnt[lane & 1][d & 31], ep * (lane & 1 ? NH - H_LATE : H_LATE)));
          if (!(ok & 2)) d |= ((d >> 22) & 63) >= 2 * H_LATE ? (2u << 30) | 128 : 128;
          if (!(ok & 1)) d |= 2u << 30;
        }
        asm volatile("st.volatile.shared.u32 [%0], %1;" ::"r"(sbase + DESC_OFF + ((i + 1) & 3) * 4), "r"(d) : "memory");
        __syncwarp();
        mbar_arrive_warp(sbase + BAR_DESC);
        const Work w = decode(dc);
        dc = d;
        if (w.kind == 0) {
#pragma unroll
          for (int e = 0; e < 4; e++) {
            const int t = (0x2130 >> (4 * e)) & 3;
            mbar_wait_w(sbase + BAR_STG + (e & 1) * 16 + (e >> 1) * 8, i & 1);
            tma_st3_w(&P.o_st[t == 3], qb + t * 16384, 0, t * 64, w.beta * 64 + w.sub * 2);
            bulk_commit();
            T2P(i + 1, 5, 2 * e);
            if (e) {
              bulk_wait_read<1>();
              mbar_arrive8_w(sbase + BAR_EMPTY + (NS + ((0x1300 >> (4 * e)) & 3)) * 8);
              T2P(i + 1, 5, 2 * e - 1);
            }
          }
          bulk_wait_read<0>();
          mbar_arrive8_w(sbase + BAR_EMPTY + (NS + 2) * 8);
          T2P(i + 1, 5, 7);
        } else {
          uint64_t pol;
          asm volatile("createpolicy.fractional.L2::evict_first.b64 %0, 1.0;" : "=l"(pol));
#pragma unroll
          for (int e = 0; e < 4; e++) {
            const int h = e & 1;
            mbar_wait_w(sbase + BAR_STG + h * 16 + (e >> 1) * 8, i & 1);
#pragma unroll
            for (int t = e & 2; t < (e & 2) + 2; t++) {
              const uint32_t half = t == 3 ? 4096 : 8192, o = t * 16384 + h * half;
              if (w.mode == 1)
                asm volatile(ELECT "cp.async.bulk.global.shared::cta.bulk_group [%0], [%1], %2;\n}"
                             ::"l"(g_part + (size_t)w.range * QBUF_BYTES + o), "r"(qb + o), "r"(half) : "memory");
              else tma_st3_hint_w(&P.out_st[t == 3], qb + o, (w.beta >> 4) * DM + w.sub * 128 + h * 64, t * 64, w.beta & 15, pol);
            }
            if (h) bulk_commit();
          }
          bulk_wait_read<1>();
          mbar_arrive8_w(sbase + BAR_EMPTY + NS * 8);
          mbar_arrive8_w(sbase + BAR_EMPTY + (NS + 1) * 8);
          bulk_wait_read<0>();
          mbar_arrive8_w(sbase + BAR_EMPTY + (NS + 2) * 8);
          mbar_arrive8_w(sbase + BAR_EMPTY + (NS + 3) * 8);
        }
        T3(i, 0);
        asm volatile("cp.async.bulk.wait_group 0;" ::: "memory");
        T3(i, 1);
        if (w.kind == 0) asm volatile(ELECT "red.release.gpu.global.add.u32 [%0], 1;\n}" ::"l"(&g_cnt[w.sub >= H_LATE][w.beta]) : "memory");
        else if (w.mode == 1) asm volatile(ELECT "st.release.gpu.global.u32 [%0], %1;\n}" ::"l"(&g_flag[w.range]), "r"(ep) : "memory");
        T3(i, 2);
      }
      T3(15, 1);
    } else
    if (warp == 0) {
      Ring r{0, 1, 1};
      uint32_t d = cta;
      for (int i = 0;; i++) {
        const Work w = decode(d);
        if (w.kind == 2) break;
        const CUtensorMap* m = w.kind == 0 ? &P.wq[w.beta >> 4] : &P.wo[w.beta >> 4];
        const int c1 = w.k0 * 64;
        for (int ks = 0; ks < w.nsteps; ks++) {
          const uint32_t b = borrow(ks, w.nsteps), bar = sbase + BAR_FULL + r.slot * 8;
          mbar_wait_w(bar + (BAR_EMPTY - BAR_FULL), r.phase);
          tma_ld3_w(sbase + r.slot * SLOT, m, 0, c1 + ks * 64, w.sub * 2, bar);
          if (ks < 10) T2P(i, 2, ks);
          if (w.kind != 0 && ks == max(w.nsteps - GO_P, 4)) mbar_arrive_warp(sbase + BAR_GO);
          r.next(); r.next_if(b == 3); r.next_if(b != 0);
        }
        if (w.kind == 0) {
          r.phase ^= 1; r.next(); r.next();
        } else if (w.mode == 2) {
          for (int k = 1; k <= ((d >> 5) & 3); k++) {
            wait_count(&g_flag[w.range + 5 * k], lds(sbase + EPOCH_OFF));
            asm volatile("fence.proxy.async.global;" ::: "memory");
            for (int t = 0; t < 4; t++) {
              const uint32_t bar = sbase + BAR_FULL + r.slot * 8, bytes = t == 3 ? 8192 : 16384;
              mbar_wait_w(sbase + BAR_EMPTY + r.slot * 8, r.phase);
              asm volatile(ELECT EXPECT("%3", "%2") "cp.async.bulk.shared::cluster.global.mbarrier::complete_tx::bytes [%0], [%1], %2, [%3];\n}"
                           ::"r"(sbase + r.slot * SLOT), "l"(g_part + (size_t)(w.range + 5 * k) * QBUF_BYTES + t * 16384), "r"(bytes), "r"(bar)
                           : "memory");
              r.next();
            }
          }
        }
        mbar_wait_w(sbase + BAR_DESC, i & 1);
        d = __shfl_sync(0xffffffffu, lds(sbase + DESC_OFF + ((i + 1) & 3) * 4), 0);
      }
    } else {
      const int hi = warp - 2;
      uint64_t pol_stream;
      asm volatile("createpolicy.fractional.L2::evict_first.b64 %0, 1.0;" : "=l"(pol_stream));
      Ring r{0, 1, 1};
      uint32_t d = cta;
      for (int i = 0;; i++) {
        const Work w = decode(d);
        if (w.kind == 2) break;
        const CUtensorMap* m = w.kind == 0 ? &P.x[hi][w.beta >> 4] : &P.o_ld[hi];
        int c1 = (w.kind == 0 ? (w.beta & 15) : w.beta * 64 + w.k0) * SQ + hi * 128;
        int k_late = -1;
        if (w.kind != 0) {
          if (!hi) T3(i, 3);
          if (d >= (3u << 30)) wait_count(&g_cnt[0][w.beta], lds(sbase + EPOCH_OFF) * H_LATE);
          if (d & 128) k_late = max(2 * H_LATE - w.k0, 0);
          if (!hi) T3(i, 4);
          asm volatile("fence.proxy.async.global;" ::: "memory");
          if (!hi) T3(i, 5);
        }
        for (int ks = 0; ks < w.nsteps; ks++) {
          if (ks == k_late) {
            if (!hi) T3(i, 6);
            wait_count(&g_cnt[1][d & 31], lds(sbase + EPOCH_OFF) * (NH - H_LATE));
            asm volatile("fence.proxy.async.global;" ::: "memory");
            if (!hi) T3(i, 7);
          }
          const uint32_t b = borrow(ks, w.nsteps);
          const bool bo = hi ? b == 0 : b != 3;
          r.next(); r.next_if(hi && b == 3);
          const uint32_t sl = bo ? NS + b + 3 * hi : r.slot, bar = sbase + BAR_FULL + sl * 8;
          mbar_wait_w(bar + (BAR_EMPTY - BAR_FULL), bo ? r.xp : r.phase);
          if (w.kind == 0) tma_ld2_w(sbase + sl * SLOT, m, ks * 64, c1, bar, hi ? 96 * 128 : 128 * 128);
          else { tma_ld2_hint_w(sbase + sl * SLOT, m, 0, c1, bar, hi ? 96 * 128 : 128 * 128, pol_stream); c1 += SQ; }
          if (ks < 10) T2P(i, 3 + hi, ks);
          r.next_if(!bo); r.next_if(!hi && b != 0);
          r.xp ^= b == 2;
        }
        r.xp ^= 1;
        if (w.kind == 0) {
          m = &P.kv[hi][w.beta >> 4];
          c1 = (d & 511) * SK;
          for (int j = 0; j < 16; j++) {
            if (hi) r.next();
            const uint32_t bar = sbase + BAR_FULL + r.slot * 8;
            if (i == 0 && j < KV_WIN_TILES) {
              const int s2 = (int)r.slot - 2;
              mbar_wait_w(sbase + BAR_FULL + (s2 < 0 ? s2 + NS : s2) * 8, s2 < 0 ? r.phase : r.phase ^ 1);
            }
            if (j == 15 && hi) mbar_wait_w(sbase + BAR_DESC, i & 1);
            mbar_wait_w(sbase + BAR_EMPTY + r.slot * 8, r.phase);
            tma_ld3_hint_w(sbase + r.slot * SLOT, m, 0, c1, 0, bar, pol_stream);
            T2P(i, 3 + hi, 16 + j);
            if (j == 14 && !hi) mbar_arrive_warp(sbase + BAR_GO);
            c1 += 64;
            r.next();
            if (!hi) r.next();
          }
        }
        mbar_wait_w(sbase + BAR_DESC, i & 1);
        d = __shfl_sync(0xffffffffu, lds(sbase + DESC_OFF + ((i + 1) & 3) * 4), 0);
      }
    }
  } else {
    asm volatile("setmaxnreg.inc.sync.aligned.u32 %0;" ::"n"(REG_C));
    Ctx c;
    c.sb = sbase; c.wg = wg; c.warp = warp; c.src = 0; c.mqk = 0; c.mpv = 0; c.lead = lane == 0;
    consumer(c, P.kp);
  }
}

typedef CUresult (*EncodeFn)(CUtensorMap*, CUtensorMapDataType, cuuint32_t, void*, const cuuint64_t*, const cuuint64_t*,
                             const cuuint32_t*, const cuuint32_t*, CUtensorMapInterleave, CUtensorMapSwizzle,
                             CUtensorMapL2promotion, CUtensorMapFloatOOBfill);

void make_map(EncodeFn enc, CUtensorMap* m, const void* ptr, int rank, const cuuint64_t* dims, const cuuint64_t* strides,
              const cuuint32_t* box, int promo = 2) {
  cuuint32_t es[5] = {1, 1, 1, 1, 1};
  enc(m, CU_TENSOR_MAP_DATA_TYPE_BFLOAT16, rank, const_cast<void*>(ptr), dims, strides, box, es,
      CU_TENSOR_MAP_INTERLEAVE_NONE, CU_TENSOR_MAP_SWIZZLE_128B, promo == 2 ? CU_TENSOR_MAP_L2_PROMOTION_L2_256B : promo == 1 ? CU_TENSOR_MAP_L2_PROMOTION_L2_128B : CU_TENSOR_MAP_L2_PROMOTION_NONE,
      CU_TENSOR_MAP_FLOAT_OOB_FILL_NONE);
}

}

extern "C" void kernel_launch(void* const* d_in, const int* in_sizes, int n_in, void* d_out, int out_size) {
  (void)in_sizes; (void)n_in; (void)out_size;
  static EncodeFn enc = nullptr;
  static void* o_ptr = nullptr;
  static int n_sm = 0;
  if (!enc) {
    void* fn = nullptr;
    cudaDriverEntryPointQueryResult qr;
    cudaGetDriverEntryPoint("cuTensorMapEncodeTiled", &fn, cudaEnableDefault, &qr);
    enc = (EncodeFn)fn;
    cudaGetSymbolAddress(&o_ptr, g_o);
    cudaFuncSetAttribute(mha_fused_kernel<false>, cudaFuncAttributeMaxDynamicSharedMemorySize, SMEM_BYTES);
    cudaFuncSetAttribute(mha_fused_kernel<true>, cudaFuncAttributeMaxDynamicSharedMemorySize, SMEM_BYTES);
    int dev = 0;
    cudaGetDevice(&dev);
    cudaDeviceGetAttribute(&n_sm, cudaDevAttrMultiProcessorCount, dev);
  }
  Params P;
  for (int br = 0; br < 2; br++) {
    const void* x = d_in[br * 5 + 0]; const void* kc = d_in[br * 5 + 1]; const void* vc = d_in[br * 5 + 2];
    const void* wq = d_in[br * 5 + 3]; const void* wo = d_in[br * 5 + 4];
    { cuuint64_t d[2] = {DM, (cuuint64_t)NB * SQ}, s[1] = {DM * 2}; cuuint32_t b[2] = {64, 128}, b2[2] = {64, 96};
      make_map(enc, &P.x[0][br], x, 2, d, s, b, PR_X); make_map(enc, &P.x[1][br], x, 2, d, s, b2, PR_X); }
    { cuuint64_t d[3] = {64, DM, HD / 64}, s[2] = {HD * 2, 128}; cuuint32_t b[3] = {64, 64, 2}; make_map(enc, &P.wq[br], wq, 3, d, s, b, PR_W); }
    { cuuint64_t d[3] = {64, HD, DM / 64}, s[2] = {DM * 2, 128}; cuuint32_t b[3] = {64, 64, 2}; make_map(enc, &P.wo[br], wo, 3, d, s, b, PR_W); }
    { cuuint64_t d[3] = {64, (cuuint64_t)NB * NH * SK, 2}, s[2] = {DH * 2, 128}; cuuint32_t b[3] = {64, 64, 2};
      make_map(enc, &P.kv[0][br], kc, 3, d, s, b, PR_KV); make_map(enc, &P.kv[1][br], vc, 3, d, s, b, PR_KV); }
    P.kp[br] = (const __nv_bfloat16*)kc; P.vp[br] = (const __nv_bfloat16*)vc;

  }
  { cuuint64_t d[2] = {64, (cuuint64_t)NBETA * 64 * SQ}, s[1] = {128}; cuuint32_t b[2] = {64, 128}, b2[2] = {64, 96};
    make_map(enc, &P.o_ld[0], o_ptr, 2, d, s, b); make_map(enc, &P.o_ld[1], o_ptr, 2, d, s, b2); }
  { cuuint64_t d[3] = {64, SQ, NBETA * 64}, s[2] = {128, SQ * 128}; cuuint32_t b[3] = {64, 64, 2}, b2[3] = {64, 32, 2};
    make_map(enc, &P.o_st[0], o_ptr, 3, d, s, b); make_map(enc, &P.o_st[1], o_ptr, 3, d, s, b2); }
  { cuuint64_t d[3] = {2 * DM, SQ, NB}, s[2] = {2 * DM * 2, (cuuint64_t)SQ * 2 * DM * 2}; cuuint32_t b[3] = {64, 64, 1}, b2[3] = {64, 32, 1};
    make_map(enc, &P.out_st[0], d_out, 3, d, s, b); make_map(enc, &P.out_st[1], d_out, 3, d, s, b2); }
  if (n_sm >= NCTA) mha_fused_kernel<false><<<NCTA, 384, SMEM_BYTES>>>(P);
  else mha_fused_kernel<true><<<n_sm, 384, SMEM_BYTES>>>(P);
}
```

```cpp
#include <cuda_runtime.h>
#include <cuda_bf16.h>
#include <cuda.h>
#include <stdint.h>

namespace {

__device__ __forceinline__ void wgmma_proj(float (&d)[64], uint64_t da, uint64_t db, int scaleD) {
  asm volatile("{\n.reg .pred p;\nsetp.ne.b32 p, %66, 0;\n"
      "wgmma.mma_async.sync.aligned.m64n128k16.f32.bf16.bf16 "
      "{%0, %1, %2, %3, %4, %5, %6, %7, %8, %9, %10, %11, %12, %13, %14, %15, %16, %17, %18, %19, %20, %21, %22, %23, %24, %25, %26, %27, %28, %29, %30, "
      "%31, %32, %33, %34, %35, %36, %37, %38, %39, %40, %41, %42, %43, %44, %45, %46, %47, %48, %49, %50, %51, %52, %53, %54, %55, %56, %57, %58, %59, %60, "
      "%61, %62, %63}, "
      "%64, %65, p, 1, 1, 1, 0;\n}\n"
      : "+f"(d[0]), "+f"(d[1]), "+f"(d[2]), "+f"(d[3]), "+f"(d[4]), "+f"(d[5]), "+f"(d[6]), "+f"(d[7]), "+f"(d[8]), "+f"(d[9]), "+f"(d[10]), "+f"(d[11]),
        "+f"(d[12]), "+f"(d[13]), "+f"(d[14]), "+f"(d[15]), "+f"(d[16]), "+f"(d[17]), "+f"(d[18]), "+f"(d[19]), "+f"(d[20]), "+f"(d[21]), "+f"(d[22]),
        "+f"(d[23]), "+f"(d[24]), "+f"(d[25]), "+f"(d[26]), "+f"(d[27]), "+f"(d[28]), "+f"(d[29]), "+f"(d[30]), "+f"(d[31]), "+f"(d[32]), "+f"(d[33]),
        "+f"(d[34]), "+f"(d[35]), "+f"(d[36]), "+f"(d[37]), "+f"(d[38]), "+f"(d[39]), "+f"(d[40]), "+f"(d[41]), "+f"(d[42]), "+f"(d[43]), "+f"(d[44]),
        "+f"(d[45]), "+f"(d[46]), "+f"(d[47]), "+f"(d[48]), "+f"(d[49]), "+f"(d[50]), "+f"(d[51]), "+f"(d[52]), "+f"(d[53]), "+f"(d[54]), "+f"(d[55]),
        "+f"(d[56]), "+f"(d[57]), "+f"(d[58]), "+f"(d[59]), "+f"(d[60]), "+f"(d[61]), "+f"(d[62]), "+f"(d[63])
      : "l"(da), "l"(db), "r"(scaleD));
}
__device__ __forceinline__ void wgmma_proj96(float (&d)[64], uint64_t da, uint64_t db, int scaleD) {
  asm volatile("{\n.reg .pred p;\nsetp.ne.b32 p, %50, 0;\n"
      "wgmma.mma_async.sync.aligned.m64n96k16.f32.bf16.bf16 "
      "{%0, %1, %2, %3, %4, %5, %6, %7, %8, %9, %10, %11, %12, %13, %14, %15, %16, %17, %18, %19, %20, %21, %22, %23, %24, %25, %26, %27, %28, %29, %30, "
      "%31, %32, %33, %34, %35, %36, %37, %38, %39, %40, %41, %42, %43, %44, %45, %46, %47}, "
      "%48, %49, p, 1, 1, 1, 0;\n}\n"
      : "+f"(d[0]), "+f"(d[1]), "+f"(d[2]), "+f"(d[3]), "+f"(d[4]), "+f"(d[5]), "+f"(d[6]), "+f"(d[7]), "+f"(d[8]), "+f"(d[9]), "+f"(d[10]), "+f"(d[11]),
        "+f"(d[12]), "+f"(d[13]), "+f"(d[14]), "+f"(d[15]), "+f"(d[16]), "+f"(d[17]), "+f"(d[18]), "+f"(d[19]), "+f"(d[20]), "+f"(d[21]), "+f"(d[22]),
        "+f"(d[23]), "+f"(d[24]), "+f"(d[25]), "+f"(d[26]), "+f"(d[27]), "+f"(d[28]), "+f"(d[29]), "+f"(d[30]), "+f"(d[31]), "+f"(d[32]), "+f"(d[33]),
        "+f"(d[34]), "+f"(d[35]), "+f"(d[36]), "+f"(d[37]), "+f"(d[38]), "+f"(d[39]), "+f"(d[40]), "+f"(d[41]), "+f"(d[42]), "+f"(d[43]), "+f"(d[44]),
        "+f"(d[45]), "+f"(d[46]), "+f"(d[47])
      : "l"(da), "l"(db), "r"(scaleD));
}
__device__ __forceinline__ void wgmma_qk(float (&d)[32], uint64_t da, uint64_t db, int scaleD) {
  asm volatile("{\n.reg .pred p;\nsetp.ne.b32 p, %34, 0;\n"
      "wgmma.mma_async.sync.aligned.m64n64k16.f32.bf16.bf16 "
      "{%0, %1, %2, %3, %4, %5, %6, %7, %8, %9, %10, %11, %12, %13, %14, %15, %16, %17, %18, %19, %20, %21, %22, %23, %24, %25, %26, %27, %28, %29, %30, "
      "%31}, "
      "%32, %33, p, 1, 1, 0, 0;\n}\n"
      : "+f"(d[0]), "+f"(d[1]), "+f"(d[2]), "+f"(d[3]), "+f"(d[4]), "+f"(d[5]), "+f"(d[6]), "+f"(d[7]), "+f"(d[8]), "+f"(d[9]), "+f"(d[10]), "+f"(d[11]),
        "+f"(d[12]), "+f"(d[13]), "+f"(d[14]), "+f"(d[15]), "+f"(d[16]), "+f"(d[17]), "+f"(d[18]), "+f"(d[19]), "+f"(d[20]), "+f"(d[21]), "+f"(d[22]),
        "+f"(d[23]), "+f"(d[24]), "+f"(d[25]), "+f"(d[26]), "+f"(d[27]), "+f"(d[28]), "+f"(d[29]), "+f"(d[30]), "+f"(d[31])
      : "l"(da), "l"(db), "r"(scaleD));
}
__device__ __forceinline__ void wgmma_pv(float (&d)[64], uint32_t a0, uint32_t a1, uint32_t a2, uint32_t a3, uint64_t db, int scaleD) {
  asm volatile("{\n.reg .pred p;\nsetp.ne.b32 p, %69, 0;\n"
      "wgmma.mma_async.sync.aligned.m64n128k16.f32.bf16.bf16 "
      "{%0, %1, %2, %3, %4, %5, %6, %7, %8, %9, %10, %11, %12, %13, %14, %15, %16, %17, %18, %19, %20, %21, %22, %23, %24, %25, %26, %27, %28, %29, %30, "
      "%31, %32, %33, %34, %35, %36, %37, %38, %39, %40, %41, %42, %43, %44, %45, %46, %47, %48, %49, %50, %51, %52, %53, %54, %55, %56, %57, %58, %59, %60, "
      "%61, %62, %63}, "
      "{%64, %65, %66, %67}, %68, p, 1, 1, 1;\n}\n"
      : "+f"(d[0]), "+f"(d[1]), "+f"(d[2]), "+f"(d[3]), "+f"(d[4]), "+f"(d[5]), "+f"(d[6]), "+f"(d[7]), "+f"(d[8]), "+f"(d[9]), "+f"(d[10]), "+f"(d[11]),
        "+f"(d[12]), "+f"(d[13]), "+f"(d[14]), "+f"(d[15]), "+f"(d[16]), "+f"(d[17]), "+f"(d[18]), "+f"(d[19]), "+f"(d[20]), "+f"(d[21]), "+f"(d[22]),
        "+f"(d[23]), "+f"(d[24]), "+f"(d[25]), "+f"(d[26]), "+f"(d[27]), "+f"(d[28]), "+f"(d[29]), "+f"(d[30]), "+f"(d[31]), "+f"(d[32]), "+f"(d[33]),
        "+f"(d[34]), "+f"(d[35]), "+f"(d[36]), "+f"(d[37]), "+f"(d[38]), "+f"(d[39]), "+f"(d[40]), "+f"(d[41]), "+f"(d[42]), "+f"(d[43]), "+f"(d[44]),
        "+f"(d[45]), "+f"(d[46]), "+f"(d[47]), "+f"(d[48]), "+f"(d[49]), "+f"(d[50]), "+f"(d[51]), "+f"(d[52]), "+f"(d[53]), "+f"(d[54]), "+f"(d[55]),
        "+f"(d[56]), "+f"(d[57]), "+f"(d[58]), "+f"(d[59]), "+f"(d[60]), "+f"(d[61]), "+f"(d[62]), "+f"(d[63])
      : "r"(a0), "r"(a1), "r"(a2), "r"(a3), "l"(db), "r"(scaleD));
}
__device__ __forceinline__ void wgmma_qk_sp(float (&d)[32], uint32_t a0, uint32_t a1, uint32_t a2, uint32_t a3, uint64_t db, int scaleD, uint32_t meta) {
  asm volatile("{\n.reg .pred p;\nsetp.ne.b32 p, %37, 0;\n"
      "wgmma.mma_async.sp.sync.aligned.m64n64k32.f32.bf16.bf16 "
      "{%0, %1, %2, %3, %4, %5, %6, %7, %8, %9, %10, %11, %12, %13, %14, %15, %16, %17, %18, %19, %20, %21, %22, %23, %24, %25, %26, %27, %28, %29, %30, "
      "%31}, "
      "{%32, %33, %34, %35}, %36, %38, 0, p, 1, 1, 0;\n}\n"
      : "+f"(d[0]), "+f"(d[1]), "+f"(d[2]), "+f"(d[3]), "+f"(d[4]), "+f"(d[5]), "+f"(d[6]), "+f"(d[7]), "+f"(d[8]), "+f"(d[9]), "+f"(d[10]), "+f"(d[11]),
        "+f"(d[12]), "+f"(d[13]), "+f"(d[14]), "+f"(d[15]), "+f"(d[16]), "+f"(d[17]), "+f"(d[18]), "+f"(d[19]), "+f"(d[20]), "+f"(d[21]), "+f"(d[22]),
        "+f"(d[23]), "+f"(d[24]), "+f"(d[25]), "+f"(d[26]), "+f"(d[27]), "+f"(d[28]), "+f"(d[29]), "+f"(d[30]), "+f"(d[31])
      : "r"(a0), "r"(a1), "r"(a2), "r"(a3), "l"(db), "r"(scaleD), "r"(meta));
}
__device__ __forceinline__ void wgmma_pv_sp(float (&d)[64], uint32_t a0, uint32_t a1, uint32_t a2, uint32_t a3, uint64_t db, int scaleD, uint32_t meta) {
  asm volatile("{\n.reg .pred p;\nsetp.ne.b32 p, %69, 0;\n"
      "wgmma.mma_async.sp.sync.aligned.m64n128k32.f32.bf16.bf16 "
      "{%0, %1, %2, %3, %4, %5, %6, %7, %8, %9, %10, %11, %12, %13, %14, %15, %16, %17, %18, %19, %20, %21, %22, %23, %24, %25, %26, %27, %28, %29, %30, "
      "%31, %32, %33, %34, %35, %36, %37, %38, %39, %40, %41, %42, %43, %44, %45, %46, %47, %48, %49, %50, %51, %52, %53, %54, %55, %56, %57, %58, %59, %60, "
      "%61, %62, %63}, "
      "{%64, %65, %66, %67}, %68, %70, 0, p, 1, 1, 1;\n}\n"
      : "+f"(d[0]), "+f"(d[1]), "+f"(d[2]), "+f"(d[3]), "+f"(d[4]), "+f"(d[5]), "+f"(d[6]), "+f"(d[7]), "+f"(d[8]), "+f"(d[9]), "+f"(d[10]), "+f"(d[11]),
        "+f"(d[12]), "+f"(d[13]), "+f"(d[14]), "+f"(d[15]), "+f"(d[16]), "+f"(d[17]), "+f"(d[18]), "+f"(d[19]), "+f"(d[20]), "+f"(d[21]), "+f"(d[22]),
        "+f"(d[23]), "+f"(d[24]), "+f"(d[25]), "+f"(d[26]), "+f"(d[27]), "+f"(d[28]), "+f"(d[29]), "+f"(d[30]), "+f"(d[31]), "+f"(d[32]), "+f"(d[33]),
        "+f"(d[34]), "+f"(d[35]), "+f"(d[36]), "+f"(d[37]), "+f"(d[38]), "+f"(d[39]), "+f"(d[40]), "+f"(d[41]), "+f"(d[42]), "+f"(d[43]), "+f"(d[44]),
        "+f"(d[45]), "+f"(d[46]), "+f"(d[47]), "+f"(d[48]), "+f"(d[49]), "+f"(d[50]), "+f"(d[51]), "+f"(d[52]), "+f"(d[53]), "+f"(d[54]), "+f"(d[55]),
        "+f"(d[56]), "+f"(d[57]), "+f"(d[58]), "+f"(d[59]), "+f"(d[60]), "+f"(d[61]), "+f"(d[62]), "+f"(d[63])
      : "r"(a0), "r"(a1), "r"(a2), "r"(a3), "l"(db), "r"(scaleD), "r"(meta));
}
__device__ __forceinline__ void wgmma_proj_init(float (&d)[64], uint64_t da, uint64_t db, int scaleD) {
  asm volatile("{\n.reg .pred p;\nsetp.ne.b32 p, %66, 0;\n"
      "wgmma.mma_async.sync.aligned.m64n128k16.f32.bf16.bf16 "
      "{%0, %1, %2, %3, %4, %5, %6, %7, %8, %9, %10, %11, %12, %13, %14, %15, %16, %17, %18, %19, %20, %21, %22, %23, %24, %25, %26, %27, %28, %29, %30, "
      "%31, %32, %33, %34, %35, %36, %37, %38, %39, %40, %41, %42, %43, %44, %45, %46, %47, %48, %49, %50, %51, %52, %53, %54, %55, %56, %57, %58, %59, %60, "
      "%61, %62, %63}, "
      "%64, %65, p, 1, 1, 1, 0;\n}\n"
      : "=f"(d[0]), "=f"(d[1]), "=f"(d[2]), "=f"(d[3]), "=f"(d[4]), "=f"(d[5]), "=f"(d[6]), "=f"(d[7]), "=f"(d[8]), "=f"(d[9]), "=f"(d[10]), "=f"(d[11]),
        "=f"(d[12]), "=f"(d[13]), "=f"(d[14]), "=f"(d[15]), "=f"(d[16]), "=f"(d[17]), "=f"(d[18]), "=f"(d[19]), "=f"(d[20]), "=f"(d[21]), "=f"(d[22]),
        "=f"(d[23]), "=f"(d[24]), "=f"(d[25]), "=f"(d[26]), "=f"(d[27]), "=f"(d[28]), "=f"(d[29]), "=f"(d[30]), "=f"(d[31]), "=f"(d[32]), "=f"(d[33]),
        "=f"(d[34]), "=f"(d[35]), "=f"(d[36]), "=f"(d[37]), "=f"(d[38]), "=f"(d[39]), "=f"(d[40]), "=f"(d[41]), "=f"(d[42]), "=f"(d[43]), "=f"(d[44]),
        "=f"(d[45]), "=f"(d[46]), "=f"(d[47]), "=f"(d[48]), "=f"(d[49]), "=f"(d[50]), "=f"(d[51]), "=f"(d[52]), "=f"(d[53]), "=f"(d[54]), "=f"(d[55]),
        "=f"(d[56]), "=f"(d[57]), "=f"(d[58]), "=f"(d[59]), "=f"(d[60]), "=f"(d[61]), "=f"(d[62]), "=f"(d[63])
      : "l"(da), "l"(db), "r"(scaleD));
}
__device__ __forceinline__ void wgmma_proj96_init(float (&d)[64], uint64_t da, uint64_t db, int scaleD) {
  asm volatile("{\n.reg .pred p;\nsetp.ne.b32 p, %50, 0;\n"
      "wgmma.mma_async.sync.aligned.m64n96k16.f32.bf16.bf16 "
      "{%0, %1, %2, %3, %4, %5, %6, %7, %8, %9, %10, %11, %12, %13, %14, %15, %16, %17, %18, %19, %20, %21, %22, %23, %24, %25, %26, %27, %28, %29, %30, "
      "%31, %32, %33, %34, %35, %36, %37, %38, %39, %40, %41, %42, %43, %44, %45, %46, %47}, "
      "%48, %49, p, 1, 1, 1, 0;\n}\n"
      : "=f"(d[0]), "=f"(d[1]), "=f"(d[2]), "=f"(d[3]), "=f"(d[4]), "=f"(d[5]), "=f"(d[6]), "=f"(d[7]), "=f"(d[8]), "=f"(d[9]), "=f"(d[10]), "=f"(d[11]),
        "=f"(d[12]), "=f"(d[13]), "=f"(d[14]), "=f"(d[15]), "=f"(d[16]), "=f"(d[17]), "=f"(d[18]), "=f"(d[19]), "=f"(d[20]), "=f"(d[21]), "=f"(d[22]),
        "=f"(d[23]), "=f"(d[24]), "=f"(d[25]), "=f"(d[26]), "=f"(d[27]), "=f"(d[28]), "=f"(d[29]), "=f"(d[30]), "=f"(d[31]), "=f"(d[32]), "=f"(d[33]),
        "=f"(d[34]), "=f"(d[35]), "=f"(d[36]), "=f"(d[37]), "=f"(d[38]), "=f"(d[39]), "=f"(d[40]), "=f"(d[41]), "=f"(d[42]), "=f"(d[43]), "=f"(d[44]),
        "=f"(d[45]), "=f"(d[46]), "=f"(d[47])
      : "l"(da), "l"(db), "r"(scaleD));
}
__device__ __forceinline__ void wgmma_qk_init(float (&d)[32], uint64_t da, uint64_t db, int scaleD) {
  asm volatile("{\n.reg .pred p;\nsetp.ne.b32 p, %34, 0;\n"
      "wgmma.mma_async.sync.aligned.m64n64k16.f32.bf16.bf16 "
      "{%0, %1, %2, %3, %4, %5, %6, %7, %8, %9, %10, %11, %12, %13, %14, %15, %16, %17, %18, %19, %20, %21, %22, %23, %24, %25, %26, %27, %28, %29, %30, "
      "%31}, "
      "%32, %33, p, 1, 1, 0, 0;\n}\n"
      : "=f"(d[0]), "=f"(d[1]), "=f"(d[2]), "=f"(d[3]), "=f"(d[4]), "=f"(d[5]), "=f"(d[6]), "=f"(d[7]), "=f"(d[8]), "=f"(d[9]), "=f"(d[10]), "=f"(d[11]),
        "=f"(d[12]), "=f"(d[13]), "=f"(d[14]), "=f"(d[15]), "=f"(d[16]), "=f"(d[17]), "=f"(d[18]), "=f"(d[19]), "=f"(d[20]), "=f"(d[21]), "=f"(d[22]),
        "=f"(d[23]), "=f"(d[24]), "=f"(d[25]), "=f"(d[26]), "=f"(d[27]), "=f"(d[28]), "=f"(d[29]), "=f"(d[30]), "=f"(d[31])
      : "l"(da), "l"(db), "r"(scaleD));
}
__device__ __forceinline__ void wgmma_pv_init(float (&d)[64], uint32_t a0, uint32_t a1, uint32_t a2, uint32_t a3, uint64_t db, int scaleD) {
  asm volatile("{\n.reg .pred p;\nsetp.ne.b32 p, %69, 0;\n"
      "wgmma.mma_async.sync.aligned.m64n128k16.f32.bf16.bf16 "
      "{%0, %1, %2, %3, %4, %5, %6, %7, %8, %9, %10, %11, %12, %13, %14, %15, %16, %17, %18, %19, %20, %21, %22, %23, %24, %25, %26, %27, %28, %29, %30, "
      "%31, %32, %33, %34, %35, %36, %37, %38, %39, %40, %41, %42, %43, %44, %45, %46, %47, %48, %49, %50, %51, %52, %53, %54, %55, %56, %57, %58, %59, %60, "
      "%61, %62, %63}, "
      "{%64, %65, %66, %67}, %68, p, 1, 1, 1;\n}\n"
      : "=f"(d[0]), "=f"(d[1]), "=f"(d[2]), "=f"(d[3]), "=f"(d[4]), "=f"(d[5]), "=f"(d[6]), "=f"(d[7]), "=f"(d[8]), "=f"(d[9]), "=f"(d[10]), "=f"(d[11]),
        "=f"(d[12]), "=f"(d[13]), "=f"(d[14]), "=f"(d[15]), "=f"(d[16]), "=f"(d[17]), "=f"(d[18]), "=f"(d[19]), "=f"(d[20]), "=f"(d[21]), "=f"(d[22]),
        "=f"(d[23]), "=f"(d[24]), "=f"(d[25]), "=f"(d[26]), "=f"(d[27]), "=f"(d[28]), "=f"(d[29]), "=f"(d[30]), "=f"(d[31]), "=f"(d[32]), "=f"(d[33]),
        "=f"(d[34]), "=f"(d[35]), "=f"(d[36]), "=f"(d[37]), "=f"(d[38]), "=f"(d[39]), "=f"(d[40]), "=f"(d[41]), "=f"(d[42]), "=f"(d[43]), "=f"(d[44]),
        "=f"(d[45]), "=f"(d[46]), "=f"(d[47]), "=f"(d[48]), "=f"(d[49]), "=f"(d[50]), "=f"(d[51]), "=f"(d[52]), "=f"(d[53]), "=f"(d[54]), "=f"(d[55]),
        "=f"(d[56]), "=f"(d[57]), "=f"(d[58]), "=f"(d[59]), "=f"(d[60]), "=f"(d[61]), "=f"(d[62]), "=f"(d[63])
      : "r"(a0), "r"(a1), "r"(a2), "r"(a3), "l"(db), "r"(scaleD));
}
__device__ __forceinline__ void wgmma_qk_sp_init(float (&d)[32], uint32_t a0, uint32_t a1, uint32_t a2, uint32_t a3, uint64_t db, int scaleD, uint32_t meta) {
  asm volatile("{\n.reg .pred p;\nsetp.ne.b32 p, %37, 0;\n"
      "wgmma.mma_async.sp.sync.aligned.m64n64k32.f32.bf16.bf16 "
      "{%0, %1, %2, %3, %4, %5, %6, %7, %8, %9, %10, %11, %12, %13, %14, %15, %16, %17, %18, %19, %20, %21, %22, %23, %24, %25, %26, %27, %28, %29, %30, "
      "%31}, "
      "{%32, %33, %34, %35}, %36, %38, 0, p, 1, 1, 0;\n}\n"
      : "=f"(d[0]), "=f"(d[1]), "=f"(d[2]), "=f"(d[3]), "=f"(d[4]), "=f"(d[5]), "=f"(d[6]), "=f"(d[7]), "=f"(d[8]), "=f"(d[9]), "=f"(d[10]), "=f"(d[11]),
        "=f"(d[12]), "=f"(d[13]), "=f"(d[14]), "=f"(d[15]), "=f"(d[16]), "=f"(d[17]), "=f"(d[18]), "=f"(d[19]), "=f"(d[20]), "=f"(d[21]), "=f"(d[22]),
        "=f"(d[23]), "=f"(d[24]), "=f"(d[25]), "=f"(d[26]), "=f"(d[27]), "=f"(d[28]), "=f"(d[29]), "=f"(d[30]), "=f"(d[31])
      : "r"(a0), "r"(a1), "r"(a2), "r"(a3), "l"(db), "r"(scaleD), "r"(meta));
}
__device__ __forceinline__ void wgmma_pv_sp_init(float (&d)[64], uint32_t a0, uint32_t a1, uint32_t a2, uint32_t a3, uint64_t db, int scaleD, uint32_t meta) {
  asm volatile("{\n.reg .pred p;\nsetp.ne.b32 p, %69, 0;\n"
      "wgmma.mma_async.sp.sync.aligned.m64n128k32.f32.bf16.bf16 "
      "{%0, %1, %2, %3, %4, %5, %6, %7, %8, %9, %10, %11, %12, %13, %14, %15, %16, %17, %18, %19, %20, %21, %22, %23, %24, %25, %26, %27, %28, %29, %30, "
      "%31, %32, %33, %34, %35, %36, %37, %38, %39, %40, %41, %42, %43, %44, %45, %46, %47, %48, %49, %50, %51, %52, %53, %54, %55, %56, %57, %58, %59, %60, "
      "%61, %62, %63}, "
      "{%64, %65, %66, %67}, %68, %70, 0, p, 1, 1, 1;\n}\n"
      : "=f"(d[0]), "=f"(d[1]), "=f"(d[2]), "=f"(d[3]), "=f"(d[4]), "=f"(d[5]), "=f"(d[6]), "=f"(d[7]), "=f"(d[8]), "=f"(d[9]), "=f"(d[10]), "=f"(d[11]),
        "=f"(d[12]), "=f"(d[13]), "=f"(d[14]), "=f"(d[15]), "=f"(d[16]), "=f"(d[17]), "=f"(d[18]), "=f"(d[19]), "=f"(d[20]), "=f"(d[21]), "=f"(d[22]),
        "=f"(d[23]), "=f"(d[24]), "=f"(d[25]), "=f"(d[26]), "=f"(d[27]), "=f"(d[28]), "=f"(d[29]), "=f"(d[30]), "=f"(d[31]), "=f"(d[32]), "=f"(d[33]),
        "=f"(d[34]), "=f"(d[35]), "=f"(d[36]), "=f"(d[37]), "=f"(d[38]), "=f"(d[39]), "=f"(d[40]), "=f"(d[41]), "=f"(d[42]), "=f"(d[43]), "=f"(d[44]),
        "=f"(d[45]), "=f"(d[46]), "=f"(d[47]), "=f"(d[48]), "=f"(d[49]), "=f"(d[50]), "=f"(d[51]), "=f"(d[52]), "=f"(d[53]), "=f"(d[54]), "=f"(d[55]),
        "=f"(d[56]), "=f"(d[57]), "=f"(d[58]), "=f"(d[59]), "=f"(d[60]), "=f"(d[61]), "=f"(d[62]), "=f"(d[63])
      : "r"(a0), "r"(a1), "r"(a2), "r"(a3), "l"(db), "r"(scaleD), "r"(meta));
}

constexpr int NB = 16, SQ = 224, DM = 640, NH = 32, SK = 1024, DH = 128;
constexpr int HD = NH * DH;
constexpr int NBETA = 2 * NB;
constexpr int NCTA = 132;
constexpr int NS = 10;
constexpr int SLOT = 16384;
constexpr int QBUF_OFF = NS * SLOT;
constexpr int QBUF_BYTES = 3 * 16384 + 8192;
constexpr int NSX = NS + 4;
constexpr int BAR_OFF = NSX * SLOT;
constexpr int BAR_FULL = BAR_OFF;
constexpr int BAR_EMPTY = BAR_OFF + 8 * NSX;
constexpr int BAR_STG = BAR_OFF + 16 * NSX;
constexpr int BAR_DESC = BAR_STG + 32;
constexpr int BAR_GO = BAR_DESC + 8;
constexpr int DESC_OFF = BAR_GO + 8;
constexpr int EPOCH_OFF = DESC_OFF + 16;
constexpr int TRACE_OFF = EPOCH_OFF + 8;
constexpr int SMEM_BYTES = TRACE_OFF;
constexpr float SM_C = 0.08838834764831845f * 1.4426950408889634f;
constexpr float SUM_HI = 1099511627776.f, SUM_LO = 1.f / 1099511627776.f;
constexpr uint32_t META_QK = 0xEEEE4444u;
constexpr uint32_t META_PV = 0x44EEEE44u;

#define QK_EARLY_MASK 3
#define QD_FIRST 1
#define SKEW_BEG 0
#define QSTART 0
#define EARLY_BEG 1
#define KV_WIN_TILES 6
#define PR_KV 2
#define PR_X 2
#define PR_W 2
#define REG_C 232
#define REG_P 40
#define GO_P 4
#define P_POS 256
#define P_STRIDE 32
#define B_LATE 32
#define H_LATE 25
#define RANGE_ORDER 0, 1, 2, 3, 4, 5, 6, 7, 8, 9, 10, 11, 12, 13, 14, 15, 16, 17, 18, 19, 20, 21, 22, 23, 24, 25
#define P_EARLY 13
#define RANGE_TABLE 0, 69, 139, 208, 277, 344, 410, 474, 536, 595, 653, 704, 760, 813, 862, 907, 945, 988, 1024, 1063, 1098, 1121, 1145, 1173, 1186, 1200, 1216

struct Params {
  CUtensorMap x[2][2], wq[2], kv[2][2], wo[2];
  CUtensorMap o_ld[2], o_st[2], out_st[2];
  const __nv_bfloat16* kp[2];
  const __nv_bfloat16* vp[2];
};

__device__ __nv_bfloat16 g_o[(size_t)NBETA * SQ * HD];
__device__ unsigned g_cnt[2][NBETA];
__device__ unsigned g_epoch, g_next;
__device__ __align__(128) uint8_t g_part[(size_t)NCTA * QBUF_BYTES];
__device__ unsigned g_flag[NCTA];

__device__ __forceinline__ uint32_t smem_u32(const void* p) { return (uint32_t)__cvta_generic_to_shared(p); }
__device__ __forceinline__ void mbar_init(uint32_t bar, int cnt) {
  asm volatile("mbarrier.init.shared::cta.b64 [%0], %1;" ::"r"(bar), "r"(cnt) : "memory");
}
__device__ __forceinline__ void mbar_arrive(uint32_t bar) {
  asm volatile("mbarrier.arrive.shared::cta.b64 _, [%0];" ::"r"(bar) : "memory");
}
__device__ __forceinline__ void mbar_arrive_warp(uint32_t bar) {
  asm volatile("{\n.reg .pred p;\nelect.sync _|p, 0xffffffff;\n@p mbarrier.arrive.shared::cta.b64 _, [%0];\n}" ::"r"(bar) : "memory");
}
__device__ __forceinline__ int lane_now() { int l; asm volatile("mov.u32 %0, %%laneid;" : "=r"(l)); return l; }
__device__ __forceinline__ bool mbar_try(uint32_t bar, uint32_t parity) {
  uint32_t ok;
  asm volatile("{\n.reg .pred p;\nmbarrier.try_wait.parity.shared::cta.b64 p, [%1], %2;\nselp.u32 %0, 1, 0, p;\n}"
               : "=r"(ok) : "r"(bar), "r"(parity) : "memory");
  return ok;
}
__device__ __forceinline__ bool mbar_test(uint32_t bar, uint32_t parity) {
  uint32_t ok;
  asm volatile("{\n.reg .pred p;\nmbarrier.test_wait.parity.shared::cta.b64 p, [%1], %2;\nselp.u32 %0, 1, 0, p;\n}"
               : "=r"(ok) : "r"(bar), "r"(parity) : "memory");
  return ok;
}
__device__ __forceinline__ void mbar_wait_w(uint32_t bar, uint32_t parity) {
  uint32_t n = 0;
  while (!__all_sync(0xffffffffu, mbar_try(bar, parity))) {
    if (++n > (1u << 22)) __trap();
  }
}
#define ELECT "{\n.reg .pred p;\nelect.sync _|p, 0xffffffff;\n@p "
__device__ __forceinline__ void tma_st3_w(const CUtensorMap* m, uint32_t src, int c0, int c1, int c2) {
  asm volatile(ELECT "cp.async.bulk.tensor.3d.global.shared::cta.bulk_group [%0, {%2, %3, %4}], [%1];\n}"
               ::"l"(m), "r"(src), "r"(c0), "r"(c1), "r"(c2) : "memory");
}
__device__ __forceinline__ void tma_st3_hint_w(const CUtensorMap* m, uint32_t src, int c0, int c1, int c2, uint64_t pol) {
  asm volatile(ELECT "cp.async.bulk.tensor.3d.global.shared::cta.bulk_group.L2::cache_hint [%0, {%2, %3, %4}], [%1], %5;\n}"
               ::"l"(m), "r"(src), "r"(c0), "r"(c1), "r"(c2), "l"(pol) : "memory");
}
#define EXPECT(bar, bytes) "mbarrier.arrive.expect_tx.shared::cta.b64 _, [" bar "], " bytes ";\n@p "
__device__ __forceinline__ void tma_ld2_w(uint32_t dst, const CUtensorMap* m, int c0, int c1, uint32_t bar, uint32_t bytes) {
  asm volatile(ELECT EXPECT("%2", "%5") "cp.async.bulk.tensor.2d.shared::cluster.global.mbarrier::complete_tx::bytes [%0], [%1, {%3, %4}], [%2];\n}"
               ::"r"(dst), "l"(m), "r"(bar), "r"(c0), "r"(c1), "r"(bytes) : "memory");
}
__device__ __forceinline__ void tma_ld2_hint_w(uint32_t dst, const CUtensorMap* m, int c0, int c1, uint32_t bar, uint32_t bytes, uint64_t pol) {
  asm volatile(ELECT EXPECT("%2", "%6") "cp.async.bulk.tensor.2d.shared::cluster.global.mbarrier::complete_tx::bytes.L2::cache_hint"
               " [%0], [%1, {%3, %4}], [%2], %5;\n}"
               ::"r"(dst), "l"(m), "r"(bar), "r"(c0), "r"(c1), "l"(pol), "r"(bytes) : "memory");
}
__device__ __forceinline__ void tma_ld3_w(uint32_t dst, const CUtensorMap* m, int c0, int c1, int c2, uint32_t bar) {
  asm volatile(ELECT EXPECT("%2", "16384") "cp.async.bulk.tensor.3d.shared::cluster.global.mbarrier::complete_tx::bytes [%0], [%1, {%3, %4, %5}], [%2];\n}"
               ::"r"(dst), "l"(m), "r"(bar), "r"(c0), "r"(c1), "r"(c2) : "memory");
}
__device__ __forceinline__ void tma_ld3_hint_w(uint32_t dst, const CUtensorMap* m, int c0, int c1, int c2, uint32_t bar, uint64_t pol) {
  asm volatile(ELECT EXPECT("%2", "16384") "cp.async.bulk.tensor.3d.shared::cluster.global.mbarrier::complete_tx::bytes.L2::cache_hint"
               " [%0], [%1, {%3, %4, %5}], [%2], %6;\n}"
               ::"r"(dst), "l"(m), "r"(bar), "r"(c0), "r"(c1), "r"(c2), "l"(pol) : "memory");
}
__device__ __forceinline__ void mbar_arrive8_w(uint32_t bar) {
  asm volatile(ELECT "mbarrier.arrive.shared::cta.b64 _, [%0], 8;\n}" ::"r"(bar) : "memory");
}
__device__ __forceinline__ void bulk_commit() { asm volatile("cp.async.bulk.commit_group;" ::: "memory"); }
template <int N> __device__ __forceinline__ void bulk_wait_read() { asm volatile("cp.async.bulk.wait_group.read %0;" ::"n"(N) : "memory"); }
__device__ __forceinline__ void wg_fence() { asm volatile("wgmma.fence.sync.aligned;" ::: "memory"); }
__device__ __forceinline__ void wg_commit() { asm volatile("wgmma.commit_group.sync.aligned;" ::: "memory"); }
template <int N> __device__ __forceinline__ void wg_wait() { asm volatile("wgmma.wait_group.sync.aligned %0;" ::"n"(N) : "memory"); }
__device__ __forceinline__ void fence_async_smem() { asm volatile("fence.proxy.async.shared::cta;" ::: "memory"); }
__device__ __forceinline__ void bar_sync(int id, int n) { asm volatile("bar.sync %0, %1;" ::"r"(id), "r"(n) : "memory"); }
template <int N> __device__ __forceinline__ void reg_fence(float (&a)[N]) {
#pragma unroll
  for (int i = 0; i < N; i++) asm volatile("" : "+f"(a[i])::"memory");
}
template <int N> __device__ __forceinline__ void reg_fence(uint32_t (&a)[N]) {
#pragma unroll
  for (int i = 0; i < N; i++) asm volatile("" : "+r"(a[i])::"memory");
}
__device__ __forceinline__ float ex2(float x) { float y; asm("ex2.approx.ftz.f32 %0, %1;" : "=f"(y) : "f"(x)); return y; }
__device__ __forceinline__ uint32_t pack_bf16(float lo, float hi) {
  uint32_t r; asm("cvt.rn.bf16x2.f32 %0, %1, %2;" : "=r"(r) : "f"(hi), "f"(lo)); return r;
}
__device__ __forceinline__ void stsm4(uint32_t a, uint32_t r0, uint32_t r1, uint32_t r2, uint32_t r3) {
  asm volatile("stmatrix.sync.aligned.m8n8.x4.shared.b16 [%0], {%1, %2, %3, %4};" ::"r"(a), "r"(r0), "r"(r1), "r"(r2), "r"(r3) : "memory");
}
__device__ __forceinline__ void stsm4t(uint32_t a, uint32_t r0, uint32_t r1, uint32_t r2, uint32_t r3) {
  asm volatile("stmatrix.sync.aligned.m8n8.x4.trans.shared.b16 [%0], {%1, %2, %3, %4};" ::"r"(a), "r"(r0), "r"(r1), "r"(r2), "r"(r3) : "memory");
}
__device__ __forceinline__ void ldsm4(uint32_t a, uint32_t& r0, uint32_t& r1, uint32_t& r2, uint32_t& r3) {
  asm volatile("ldmatrix.sync.aligned.m8n8.x4.shared.b16 {%0, %1, %2, %3}, [%4];" : "=r"(r0), "=r"(r1), "=r"(r2), "=r"(r3) : "r"(a) : "memory");
}
__device__ __forceinline__ void sts16(uint32_t a, uint32_t v) { asm volatile("st.shared.u16 [%0], %1;" ::"r"(a), "h"((uint16_t)v) : "memory"); }
__device__ __forceinline__ void mma16816(float& c0, float& c1, float& c2, float& c3, uint32_t a0, uint32_t a1, uint32_t a2, uint32_t a3,
                                         uint32_t b0, uint32_t b1) {
  asm volatile("mma.sync.aligned.m16n8k16.row.col.f32.bf16.bf16.f32 {%0, %1, %2, %3}, {%4, %5, %6, %7}, {%8, %9}, {%0, %1, %2, %3};"
               : "+f"(c0), "+f"(c1), "+f"(c2), "+f"(c3) : "r"(a0), "r"(a1), "r"(a2), "r"(a3), "r"(b0), "r"(b1));
}
__device__ __forceinline__ uint32_t sdesc(uint32_t addr, uint32_t lbo) { return (addr >> 4) + ((lbo >> 4) << 16); }
__device__ __forceinline__ uint64_t desc64(uint32_t lo, uint32_t hi) { uint64_t d; asm("mov.b64 %0, {%1, %2};" : "=l"(d) : "r"(lo), "r"(hi)); return d; }
__device__ __forceinline__ void dadd(uint64_t& d, uint32_t inc) {
  asm("{\n.reg .b32 l, h;\nmov.b64 {l, h}, %0;\nadd.u32 l, l, %1;\nmov.b64 %0, {l, h};\n}" : "+l"(d) : "r"(inc));
}

struct Ring {
  uint32_t slot, phase, xp;
  __device__ __forceinline__ void uniform() {
    slot = __shfl_sync(0xffffffffu, slot, 0); phase = __shfl_sync(0xffffffffu, phase, 0); xp = __shfl_sync(0xffffffffu, xp, 0);
  }
  __device__ __forceinline__ void next() { if (++slot == NS) { slot = 0; phase ^= 1; } }
  __device__ __forceinline__ void next_if(bool p) { slot += p; if (slot == NS) { slot = 0; phase ^= 1; } }
};
__device__ __forceinline__ uint32_t borrow(int ks, int n) { const int k = ks + 1; return k >= 4 && (k | 3) - 1 <= n ? k & 3 : 3; }

constexpr uint32_t Q_RANGES = NBETA * NH + P_EARLY * 5;
constexpr int TAIL_STEPS = (NBETA - P_EARLY) * 64, NRANGE = NCTA / 5;
struct Work { int kind, mode, k0, nsteps, range, beta, sub; };
struct Sched { uint16_t queue[Q_RANGES]; uint32_t piece[NRANGE + 1][4]; };
constexpr Sched make_sched() {
  Sched s{};
  int q = 0, a = 0;
  for (int pass = 0; pass < 2; pass++)
    for (int b = pass ? B_LATE : 0; b < NBETA; b++)
      for (int h = pass ? H_LATE : 0; h < (pass || b < B_LATE ? NH : H_LATE); h++) {
        if (a >= P_POS && (a - P_POS) % P_STRIDE == 0 && (a - P_POS) / P_STRIDE < P_EARLY)
          for (int col = 0; col < 5; col++) s.queue[q++] = 0x8000 | col << 8 | (a - P_POS) / P_STRIDE;
        s.queue[q++] = b << 5 | h;
        a++;
      }
  constexpr int B[NRANGE + 1] = {RANGE_TABLE};
  constexpr int ORD[NRANGE] = {RANGE_ORDER};
  for (int g = 0; g <= NRANGE; g++) {
    int n = 0;
    if (g < NRANGE) {
      const int r = ORD[g];
      for (int pos = B[r]; pos < B[r + 1];) {
        const int te = (pos | 63) + 1, stop = B[r + 1] < te ? B[r + 1] : te, mode = pos & 63 ? 1 : stop == te ? 0 : 2;
        int f = 0;
        if (mode == 2) { f = 1; while (B[r + 1 + f] < te) f++; }
        s.piece[g][n++] = 1u << 30 | mode << 28 | (te - stop) << 22 | (stop - pos - 1) << 16 | r << 11 | f << 5 | (P_EARLY + (pos >> 6));
        pos = stop;
      }
    }
    for (; n < 4; n++) s.piece[g][n] = 2u << 30;
  }
  return s;
}
__constant__ Sched c_sched = make_sched();
__device__ __forceinline__ Work decode(uint32_t d) {
  Work w;
  w.kind = d >> 30; if (w.kind == 3) w.kind = 1;
  w.mode = (d >> 28) & 3; w.k0 = (d >> 22) & 63;
  if (w.kind == 0) { w.beta = (d >> 5) & 31; w.sub = d & 31; w.nsteps = DM / 64; }
  else { w.beta = d & 31; w.sub = (d >> 8) & 7; w.nsteps = ((d >> 16) & 63) + 1; }
  w.range = ((d >> 11) & 31) * 5 + w.sub;
  return w;
}

__device__ __forceinline__ bool reached(const unsigned* cnt, unsigned target) {
  unsigned v;
  asm volatile("ld.acquire.gpu.global.u32 %0, [%1];" : "=r"(v) : "l"(cnt) : "memory");
  return (int)(v - target) >= 0;
}
__device__ __forceinline__ void wait_count(const unsigned* cnt, unsigned target) {
  unsigned n = 0;
  while (!__all_sync(0xffffffffu, reached(cnt, target))) { if (++n > (1u << 24)) __trap(); }
}
__device__ __forceinline__ uint32_t lds(uint32_t a) { uint32_t v; asm volatile("ld.volatile.shared.u32 %0, [%1];" : "=r"(v) : "r"(a) : "memory"); return v; }

#define TRACE(u, e)
#define T3(u, e)
#define T2C(u, e)
#define T2P(u, r, e)
#define TRACE_P(u, e)
#define TRACE_IN(u, e)

struct Ctx {
  uint32_t sb;
  int wg, warp;
  uint32_t mqk, mpv;
  bool lead;
  int src;
};
template <int N> __device__ __forceinline__ uint32_t dhi(uint32_t lo) { return 0x40000040u + (lo >> (26 + N)); }
template <int N> __device__ __forceinline__ uint64_t full_desc(uint32_t addr, uint32_t slot) { return desc64(addr >> 4, dhi<N>(slot)); }
__device__ __forceinline__ void release(const Ctx& c, uint32_t slot) {
  if (c.lead) mbar_arrive(c.sb + BAR_EMPTY + slot * 8);
}
__device__ __forceinline__ uint32_t acquire(const Ctx& c, Ring& r) {
  const uint32_t s = r.slot;
  mbar_wait_w(c.sb + BAR_FULL + s * 8, r.phase);
  r.next();
  return s;
}
__device__ __forceinline__ void mbar_wait2_w(uint32_t b0, uint32_t p0, uint32_t b1, uint32_t p1) {
  uint32_t n = 0;
  while (!__all_sync(0xffffffffu, mbar_try(b0, p0) & mbar_try(b1, p1))) {
    if (++n > (1u << 22)) __trap();
  }
}
__device__ __forceinline__ void acquire2(const Ctx& c, Ring& r, uint32_t& s0, uint32_t& s1, bool wait = true) {
  const uint32_t p0 = r.phase;
  s0 = r.slot; r.next(); s1 = r.slot;
  if (wait) mbar_wait2_w(c.sb + BAR_FULL + s0 * 8, p0, c.sb + BAR_FULL + s1 * 8, r.phase);
  r.next();
}
__device__ __forceinline__ void staged(const Ctx& c, int part) {
  fence_async_smem();
  __syncwarp();
  mbar_arrive_warp(c.sb + BAR_STG + c.wg * 16 + part * 8);
}

template <bool FIRST, bool HI>
__device__ __forceinline__ void proj_half(const Ctx& c, float (&acc)[64], uint32_t w, uint32_t x) {
  uint64_t a = full_desc<0>(c.sb + w * SLOT + c.wg * 8192, x), b = full_desc<1>(c.sb + x * SLOT, x);
  wg_fence();
  if (HI) { if (FIRST) wgmma_proj96_init(acc, a, b, 0); else wgmma_proj96(acc, a, b, 1); }
  else { if (FIRST) wgmma_proj_init(acc, a, b, 0); else wgmma_proj(acc, a, b, 1); }
#pragma unroll
  for (int k = 1; k < 4; k++) { dadd(a, 128); dadd(b, 2); if (HI) wgmma_proj96(acc, a, b, 1); else wgmma_proj(acc, a, b, 1); }
  wg_commit();
}

__device__ __forceinline__ void proj_store16(uint32_t a, const float* f, float sc) {
  stsm4t(a, pack_bf16(f[0] * sc, f[1] * sc), pack_bf16(f[2] * sc, f[3] * sc), pack_bf16(f[4] * sc, f[5] * sc), pack_bf16(f[6] * sc, f[7] * sc));
}

__device__ __forceinline__ uint32_t stage_off(const Ctx& c) {
  const int lane = lane_now(), mi = lane >> 3, r8 = lane & 7;
  return ((mi >> 1) * 8 + r8) * 128 + (((2 * c.warp + (mi & 1)) ^ r8) << 4);
}
__device__ __forceinline__ void stage_lo(const Ctx& c, const float (&a0)[64], float sc) {
  const uint32_t lane_off = c.sb + QBUF_OFF + c.wg * 8192 + stage_off(c);
#pragma unroll
  for (int jj = 0; jj < 8; jj++) proj_store16(lane_off + (jj >> 2) * 16384 + (jj & 3) * 2048, &a0[jj * 8], sc);
}
__device__ __forceinline__ uint32_t q3_swz(uint32_t r8) { return ((r8 & 3) << 1) | (r8 >> 2); }
template <bool IS_Q>
__device__ __forceinline__ void stage_hi(const Ctx& c, const float (&a1)[64], float sc) {
  const uint32_t off = stage_off(c), lane_off = c.sb + QBUF_OFF + 2 * 16384 + c.wg * 8192 + off;
#pragma unroll
  for (int jj = 0; jj < 4; jj++) proj_store16(lane_off + jj * 2048, &a1[jj * 8], sc);
  const uint32_t r8 = (off >> 7) & 7;
  const uint32_t t3 = c.sb + QBUF_OFF + 3 * 16384 + c.wg * 4096 + (IS_Q ? off ^ ((r8 ^ q3_swz(r8)) << 4) : off);
  proj_store16(t3, &a1[32], sc);
  proj_store16(t3 + 2048, &a1[40], sc);
}

__device__ __forceinline__ void add16(uint32_t a, float* f) {
  uint32_t r[4];
  asm volatile("ldmatrix.sync.aligned.m8n8.x4.trans.shared.b16 {%0, %1, %2, %3}, [%4];"
               : "=r"(r[0]), "=r"(r[1]), "=r"(r[2]), "=r"(r[3]) : "r"(a) : "memory");
#pragma unroll
  for (int i = 0; i < 4; i++) { f[2 * i] += __uint_as_float(r[i] << 16); f[2 * i + 1] += __uint_as_float(r[i] & 0xffff0000u); }
}

__device__ __forceinline__ void trace_dump(const Ctx& c) {
}
struct Slots { uint32_t w, x, y, py, w2, x2; };
__device__ __forceinline__ void begin_acquire(const Ctx& c, Ring& r, Slots& h, bool wait) {
  acquire2(c, r, h.w, h.x, wait);
  if (SKEW_BEG) { h.y = r.slot; h.py = r.phase; r.next(); acquire2(c, r, h.w2, h.x2, wait); }
}
__device__ __forceinline__ void proj_begin(const Ctx& c, Ring& r, float (&a0)[64], Slots& h, bool wait) {
  begin_acquire(c, r, h, wait);
  proj_half<true, false>(c, a0, h.w, h.x);
  if (SKEW_BEG) proj_half<false, false>(c, a0, h.w2, h.x2);
}
__device__ __forceinline__ void proj_main(const Ctx& c, Ring& r, float (&a0)[64], float (&a1)[64], Slots& h, int kind, int n, int unit) {
  T2C(unit, 1);
  uint32_t y, w, x, py;
  if (SKEW_BEG) {
    y = r.slot; w = h.w2;
    mbar_wait2_w(c.sb + BAR_FULL + h.y * 8, h.py, c.sb + BAR_FULL + y * 8, r.phase);
    r.next();
    T2C(unit, 2);
    wg_wait<0>();
    T2C(unit, 3);
    release(c, h.x); release(c, h.x2);
    proj_half<true, true>(c, a1, h.w, h.y);
    proj_half<false, true>(c, a1, w, y);
    wg_wait<1>();
    release(c, h.w); release(c, h.y);
  } else {
    y = acquire(c, r); w = h.w;
    T2C(unit, 2);
    wg_wait<0>();
    T2C(unit, 3);
    release(c, h.x);
    proj_half<true, true>(c, a1, w, y);
  }
  int ks = 1 + SKEW_BEG;
#pragma unroll 1
  while (true) {
    const uint32_t b = borrow(ks, n), pw = w, p0 = r.phase;
    w = r.slot; r.next();
    const uint32_t p1 = b != 3 ? r.xp : r.phase;
    x = b != 3 ? NS + b : r.slot; r.next_if(b == 3);
    mbar_wait2_w(c.sb + BAR_FULL + w * 8, p0, c.sb + BAR_FULL + x * 8, p1);
    if (ks < 10) T2C(unit, ks * 4);
    wg_wait<0>();
    if (ks < 10) T2C(unit, ks * 4 + 1);
    release(c, pw); release(c, y);
    proj_half<false, false>(c, a0, w, x);
    py = b == 0 ? r.xp : r.phase;
    y = b == 0 ? NS + 3 : r.slot; r.next_if(b != 0);
    r.xp ^= b == 2;
    if (++ks == n) break;
    mbar_wait_w(c.sb + BAR_FULL + y * 8, py);
    if (ks < 11) T2C(unit, ks * 4 - 2);
    wg_wait<0>();
    if (ks < 11) T2C(unit, ks * 4 - 1);
    release(c, x);
    proj_half<false, true>(c, a1, w, y);
  }
  {
    const uint32_t pe = r.xp ^ (unit & 1) ^ 1, k0 = kind == 0 ? r.slot : y, pk = kind == 0 ? r.phase : py;
    uint32_t cnt = 0;
    while (true) {
      bool ok = mbar_try(c.sb + BAR_FULL + y * 8, py) & mbar_try(c.sb + BAR_FULL + k0 * 8, pk);
#pragma unroll
      for (int t = 0; t < 2; t++) ok &= mbar_try(c.sb + BAR_EMPTY + (NS + t) * 8, pe);
      if (__all_sync(0xffffffffu, ok)) break;
      if (++cnt > (1u << 22)) __trap();
    }
  }
  T2C(unit, 38);
  wg_wait<0>();
  T2C(unit, 39);
  release(c, x);
  proj_half<false, true>(c, a1, w, y);
  h.w = w; h.x = y;
  reg_fence(a0);
}
__device__ __forceinline__ void wait_hi_free(const Ctx& c, const Ring& r, int unit) {
  const uint32_t pe = r.xp ^ (unit & 1) ^ 1;
  mbar_wait2_w(c.sb + BAR_EMPTY + (NS + 2) * 8, pe, c.sb + BAR_EMPTY + (NS + 3) * 8, pe);
}
__device__ __forceinline__ void proj_end(const Ctx& c, float (&a1)[64], const Slots& h) {
  wg_wait<0>();
#pragma unroll
  for (int i = 0; i < 48; i++) asm volatile("" : "+f"(a1[i])::"memory");
  release(c, h.w); release(c, h.x);
}
__device__ __forceinline__ uint32_t get_desc(const Ctx& c, int i) {
  uint32_t d;
  mbar_wait_w(c.sb + BAR_DESC, (i - 1) & 1);
  asm volatile("ld.volatile.shared.u32 %0, [%1];" : "=r"(d) : "r"(c.sb + DESC_OFF + (i & 3) * 4) : "memory");
  return __shfl_sync(0xffffffffu, d, 0);
}

struct RowSum { float l0, l1; };

__device__ __forceinline__ float quad_max(float x) {
  x = fmaxf(x, __shfl_xor_sync(0xffffffffu, x, 1));
  return fmaxf(x, __shfl_xor_sync(0xffffffffu, x, 2));
}
__device__ __forceinline__ float quad_sum(float x) {
  x += __shfl_xor_sync(0xffffffffu, x, 1);
  return x + __shfl_xor_sync(0xffffffffu, x, 2);
}
template <bool SP, bool FIRST>
__device__ __forceinline__ void exps(const Ctx& c, const float (&s)[32], uint32_t (&p)[SP ? 8 : 16], RowSum& st) {
  if constexpr (SP) {
    uint32_t q[8];
    float t;
#pragma unroll
    for (int j = 0; j < 8; j++) {
      const float e0 = ex2(s[4 * j] + s[4 * j + 2]), e1 = ex2(s[4 * j + 1] + s[4 * j + 3]);
      if (j == 0) t = e0 + e1; else t += e0 + e1;
      q[j] = pack_bf16(e0, e1);
    }
    const bool odd = c.src & 2;
#pragma unroll
    for (int g = 0; g < 4; g++) {
      p[2 * g] = __shfl_sync(0xffffffffu, odd ? q[2 * g + 1] : q[2 * g], c.src);
      p[2 * g + 1] = __shfl_sync(0xffffffffu, odd ? q[2 * g] : q[2 * g + 1], c.src ^ 1);
    }
    st.l0 = FIRST ? t : st.l0 + t;
  } else {
    float t0, t1;
#pragma unroll
    for (int j = 0; j < 8; j++) {
      const float e0 = ex2(s[4 * j]), e1 = ex2(s[4 * j + 1]), e2 = ex2(s[4 * j + 2]), e3 = ex2(s[4 * j + 3]);
      if (j == 0) { t0 = e0 + e1; t1 = e2 + e3; } else { t0 += e0 + e1; t1 += e2 + e3; }
      p[2 * j] = pack_bf16(e0, e1);
      p[2 * j + 1] = pack_bf16(e2, e3);
    }
    st.l0 = FIRST ? t0 : st.l0 + t0;
    st.l1 = FIRST ? t1 : st.l1 + t1;
  }
}
template <bool SP>
__device__ __forceinline__ bool finish_sums(RowSum& st) {
  const float a = quad_sum(st.l0), b = SP ? a : quad_sum(st.l1);
  st.l0 = __fdividef(1.f, a); st.l1 = __fdividef(1.f, b);
  return !(a >= SUM_LO && a <= SUM_HI && b >= SUM_LO && b <= SUM_HI);
}
template <bool SP, bool INIT, int SITE, bool COMMIT = true>
__device__ __forceinline__ void issue_qk(const Ctx& c, float (&s)[32], const uint32_t (&qs)[16], uint32_t dq, uint32_t dk) {
  uint64_t a = desc64(dq, dhi<SITE & 1>(dk)), b = desc64(dk, dhi<1 - (SITE & 1)>(dk));
  if (SP) {
    if (INIT) wgmma_qk_sp_init(s, qs[0], qs[1], qs[2], qs[3], b, 0, c.mqk); else wgmma_qk_sp(s, qs[0], qs[1], qs[2], qs[3], b, 0, c.mqk);
#pragma unroll
    for (int k = 1; k < 4; k++) { dadd(b, k == 2 ? 508 : 4); wgmma_qk_sp(s, qs[4 * k], qs[4 * k + 1], qs[4 * k + 2], qs[4 * k + 3], b, 1, c.mqk); }
  } else {
    if (INIT) wgmma_qk_init(s, a, b, 0); else wgmma_qk(s, a, b, 0);
#pragma unroll
    for (int k = 1; k < 8; k++) { dadd(a, k == 4 ? 506 : 2); dadd(b, k == 4 ? 506 : 2); wgmma_qk(s, a, b, 1); }
  }
  if (COMMIT) wg_commit();
}
template <bool SP, bool ACC, int SITE, bool SPLIT = false>
__device__ __forceinline__ void issue_pv(const Ctx& c, float (&o)[64], const uint32_t (&p)[SP ? 8 : 16], uint32_t dv) {
  uint64_t b = desc64(dv, dhi<SITE & 1>(dv));
  if constexpr (SP) {
    if (ACC) wgmma_pv_sp(o, p[0], p[1], p[2], p[3], b, 1, c.mpv); else wgmma_pv_sp_init(o, p[0], p[1], p[2], p[3], b, 0, c.mpv);
    if (SPLIT) wg_commit();
    dadd(b, 256);
    wgmma_pv_sp(o, p[4], p[5], p[6], p[7], b, 1, c.mpv);
  } else {
    if (ACC) wgmma_pv(o, p[0], p[1], p[2], p[3], b, 1); else wgmma_pv_init(o, p[0], p[1], p[2], p[3], b, 0);
#pragma unroll
    for (int k = 1; k < 4; k++) { dadd(b, 128); wgmma_pv(o, p[4 * k], p[4 * k + 1], p[4 * k + 2], p[4 * k + 3], b, 1); }
  }
  wg_commit();
}
template <bool SP>
__device__ __forceinline__ void o_store(const Ctx& c, uint32_t tile_addr, const float (&o)[64], const RowSum& inv, uint32_t half = 8192) {
  const int lane = lane_now(), mi = lane >> 3, r8 = lane & 7;
  if (SP) {
    const float i0 = inv.l0;
    const uint32_t row_addr = tile_addr + (8 * c.warp + r8) * 128;
#pragma unroll
    for (int jj = 0; jj < 4; jj++) {
      const int b = jj * 16;
      stsm4(row_addr + (jj >> 1) * 4096 + ((((jj & 1) * 4 + mi) ^ r8) << 4),
            pack_bf16((o[b] + o[b + 2]) * i0, (o[b + 1] + o[b + 3]) * i0), pack_bf16((o[b + 4] + o[b + 6]) * i0, (o[b + 5] + o[b + 7]) * i0),
            pack_bf16((o[b + 8] + o[b + 10]) * i0, (o[b + 9] + o[b + 11]) * i0),
            pack_bf16((o[b + 12] + o[b + 14]) * i0, (o[b + 13] + o[b + 15]) * i0));
    }
  } else {
    const float i0 = inv.l0, i1 = inv.l1;
    const uint32_t row_addr = tile_addr + (half == 4096 ? 8 * c.warp + r8 : 16 * c.warp + (mi & 1) * 8 + r8) * 128;
#pragma unroll
    for (int jj = 0; jj < 8; jj++) {
      const int b = jj * 8;
      stsm4(row_addr + (jj >> 2) * half + (((((2 * jj) & 7) + (mi >> 1)) ^ r8) << 4),
            pack_bf16(o[b] * i0, o[b + 1] * i0), pack_bf16(o[b + 2] * i1, o[b + 3] * i1),
            pack_bf16(o[b + 4] * i0, o[b + 5] * i0), pack_bf16(o[b + 6] * i1, o[b + 7] * i1));
    }
  }
}

__device__ __forceinline__ void redo_tile(const Ctx& c, uint32_t q_addr, uint32_t half, const __nv_bfloat16* kp, const __nv_bfloat16* vp) {
  float o[64];
  const int lane = lane_now(), g = lane >> 2, cc = lane & 3, mi = lane >> 3, r8 = lane & 7;
  const uint32_t qa = q_addr + (half == 4096 ? 8 * c.warp + r8 : 16 * c.warp + (mi & 1) * 8 + r8) * 128, swz = half == 4096 ? q3_swz(r8) : r8;
  const uint32_t* kq = reinterpret_cast<const uint32_t*>(kp + g * DH) + cc;
  const unsigned short* vq = reinterpret_cast<const unsigned short*>(vp + 2 * cc * DH) + g;
  float m0 = -INFINITY, m1 = -INFINITY, l0 = 0.f, l1 = 0.f;
#pragma unroll
  for (int i = 0; i < 64; i++) o[i] = 0.f;
#pragma unroll 1
  for (int kb = 0; kb < SK / 16; kb++) {
    float z[8] = {0.f, 0.f, 0.f, 0.f, 0.f, 0.f, 0.f, 0.f};
#pragma unroll 2
    for (int kk = 0; kk < 8; kk++) {
      uint32_t a0, a1, a2, a3;
      ldsm4(qa + (kk >> 2) * half + ((((kk & 3) * 2 + (mi >> 1)) ^ swz) << 4), a0, a1, a2, a3);
      const uint32_t* kr = kq + kb * (16 * DH / 2) + kk * 8;
      mma16816(z[0], z[1], z[2], z[3], a0, a1, a2, a3, __ldg(kr), __ldg(kr + 4));
      mma16816(z[4], z[5], z[6], z[7], a0, a1, a2, a3, __ldg(kr + 8 * DH / 2), __ldg(kr + 8 * DH / 2 + 4));
    }
    const float n0 = fmaxf(m0, quad_max(fmaxf(fmaxf(z[0], z[1]), fmaxf(z[4], z[5]))));
    const float n1 = fmaxf(m1, quad_max(fmaxf(fmaxf(z[2], z[3]), fmaxf(z[6], z[7]))));
    const float al0 = ex2(m0 - n0), al1 = ex2(m1 - n1);
    m0 = n0; m1 = n1;
#pragma unroll
    for (int i = 0; i < 8; i++) z[i] = ex2(z[i] - ((i & 2) ? n1 : n0));
    l0 = l0 * al0 + (z[0] + z[1]) + (z[4] + z[5]);
    l1 = l1 * al1 + (z[2] + z[3]) + (z[6] + z[7]);
    const uint32_t a0 = pack_bf16(z[0], z[1]), a1 = pack_bf16(z[2], z[3]), a2 = pack_bf16(z[4], z[5]), a3 = pack_bf16(z[6], z[7]);
    const unsigned short* vr = vq + kb * (16 * DH);
#pragma unroll
    for (int nb = 0; nb < 16; nb++) {
      o[4 * nb] *= al0; o[4 * nb + 1] *= al0; o[4 * nb + 2] *= al1; o[4 * nb + 3] *= al1;
      const uint32_t b0 = __ldg(vr + nb * 8) | ((uint32_t)__ldg(vr + nb * 8 + DH) << 16);
      const uint32_t b1 = __ldg(vr + nb * 8 + 8 * DH) | ((uint32_t)__ldg(vr + nb * 8 + 9 * DH) << 16);
      mma16816(o[4 * nb], o[4 * nb + 1], o[4 * nb + 2], o[4 * nb + 3], a0, a1, a2, a3, b0, b1);
    }
  }
  __syncwarp();
  o_store<false>(c, q_addr, o, RowSum{__fdividef(1.f, quad_sum(l0)), __fdividef(1.f, quad_sum(l1))}, half);
}

template <bool SPA, bool SPB, int SITE, int ID>
__device__ __forceinline__ void batch(const Ctx& c, float (&s)[32], const uint32_t (&qs)[16], uint32_t dq, uint32_t dk, float (&ob)[64],
                                      uint32_t (&pb)[SPB ? 8 : 16], uint32_t dv) {
  if constexpr (SPA) {
    reg_fence(pb);
    wg_fence();
    issue_pv<SPB, true, ID>(c, ob, pb, dv);
    issue_qk<SPA, false, ID>(c, s, qs, dq, dk);
  } else {
    constexpr bool EARLY = ((QK_EARLY_MASK >> (SITE + (SPB ? 2 : 0))) & 1) != 0;
    if (!EARLY) reg_fence(pb);
    wg_fence();
    issue_qk<SPA, false, ID, !SPB>(c, s, qs, dq, dk);
    if (EARLY) { reg_fence(pb); wg_fence(); }
    issue_pv<SPB, true, ID, SPB>(c, ob, pb, dv);
  }
}

template <bool SP0>
__device__ __forceinline__ int attention(Ctx c, Ring& r, int unit, uint32_t& d, float (&o1)[64], RowSum& st1, const Slots& h) {
  constexpr bool SP1 = false;
  c.wg = SP0;
  if (SP0) { c.mqk = META_QK + (d >> 28); c.mpv = META_PV + (d >> 28); asm volatile("" : "+r"(c.mqk), "+r"(c.mpv)); }
  if (SP0) { const int lane = lane_now(); c.src = (lane & 28) | ((lane & 1) << 1) | ((lane >> 1) & 1); }
  float o0[64], s[32];
  uint32_t p0[SP0 ? 8 : 16], p1[16];
  RowSum st0;
  const uint32_t q0a = c.sb + QBUF_OFF + (SP0 ? 3 : 0) * 16384, q1a = c.sb + QBUF_OFF + (SP0 ? 2 : 1) * 16384;
  const uint32_t dq0 = sdesc(q0a, 0), dq1 = sdesc(q1a, 0);
  uint32_t sk = r.slot, sv, sn;
  r.next();
  uint32_t qs[16];
  if (SP0) {
    asm volatile("bar.arrive 1, 256;" ::: "memory");
    proj_end(c, o1, h);
    wait_hi_free(c, r, unit);
    T2C(unit, 42);
    stage_hi<true>(c, o1, SM_C);
    fence_async_smem();
    T2C(unit, 43);
    bar_sync(6, 256);
    const int lane = lane_now(), g = lane >> 2, cc = lane & 3;
    const uint32_t qa = q0a + (8 * c.warp + g) * 128 + (cc & 1) * 8;
#pragma unroll
    for (int k = 0; k < 8; k++)
      asm volatile("ld.shared.v2.u32 {%0, %1}, [%2];" : "=r"(qs[2 * k]), "=r"(qs[2 * k + 1])
                   : "r"(qa + (k >> 2) * 4096 + ((((k & 3) * 2 + (cc >> 1)) ^ q3_swz(g)) << 4)) : "memory");
  } else {
    proj_end(c, o1, h);
    if (QSTART == 1) {
      wait_hi_free(c, r, unit);
      T2C(unit, 42);
      stage_hi<true>(c, o1, SM_C);
      fence_async_smem();
      asm volatile("bar.arrive 6, 256;" ::: "memory");
    }
    T2C(unit, 43);
    bar_sync(1, 256);
  }
  TRACE(unit, 2);
  T2C(unit, 44);
  if (SP0 && QD_FIRST) {
    float s1[32];
    wg_fence();
    issue_qk<SP1, true, 1>(c, s1, qs, dq1, sdesc(c.sb + sk * SLOT, 0));
    reg_fence(qs);
    wg_fence();
    issue_qk<SP0, true, 0>(c, s, qs, dq0, sdesc(c.sb + sk * SLOT, 0));
    T2C(unit, 45);
    acquire2(c, r, sv, sn);
    wg_wait<1>();
    reg_fence(s1);
    T2C(unit, 47);
    exps<SP1, true>(c, s1, p1, st1);
    reg_fence(p1);
    wg_fence();
    issue_pv<SP1, false, 1>(c, o1, p1, sdesc(c.sb + sv * SLOT, 8192));
    wg_wait<1>();
    reg_fence(s);
    T2C(unit, 48);
    release(c, sk);
    sk = sn;
    exps<SP0, true>(c, s, p0, st0);
    reg_fence(p0);
    wg_fence();
    issue_pv<SP0, false, 0>(c, o0, p0, sdesc(c.sb + sv * SLOT, 8192));
    issue_qk<SP0, false, 2>(c, s, qs, dq0, sdesc(c.sb + sk * SLOT, 0));
    T2C(unit, 49);
    sn = acquire(c, r);
    T2C(unit, 50);
    wg_wait<0>();
    reg_fence(s);
  } else
  {
    float s1[32];
    wg_fence();
    issue_qk<SP0, true, 0>(c, s, qs, dq0, sdesc(c.sb + sk * SLOT, 0));
    issue_qk<SP1, true, 1>(c, s1, qs, dq1, sdesc(c.sb + sk * SLOT, 0));
    T2C(unit, 45);
    if (!SP0 && QSTART == 0) {
      wait_hi_free(c, r, unit);
#pragma unroll
      for (int i = 0; i < 48; i++) asm volatile("" : "+f"(o1[i])::"memory");
      stage_hi<true>(c, o1, SM_C);
      fence_async_smem();
      asm volatile("bar.arrive 6, 256;" ::: "memory");
    }
    T2C(unit, 46);
    acquire2(c, r, sv, sn);
    wg_wait<1>();
    reg_fence(s);
    T2C(unit, 47);
    exps<SP0, true>(c, s, p0, st0);
    reg_fence(p0);
    wg_fence();
    issue_qk<SP0, false, 2>(c, s, qs, dq0, sdesc(c.sb + sn * SLOT, 0));
    issue_pv<SP0, false, 0>(c, o0, p0, sdesc(c.sb + sv * SLOT, 8192));
    wg_wait<2>();
    reg_fence(s1);
    T2C(unit, 48);
    release(c, sk);
    sk = sn;
    exps<SP1, true>(c, s1, p1, st1);
    reg_fence(p1);
    wg_fence();
    issue_pv<SP1, false, 1>(c, o1, p1, sdesc(c.sb + sv * SLOT, 8192));
    T2C(unit, 49);
    sn = acquire(c, r);
    T2C(unit, 50);
    wg_wait<1>();
    reg_fence(s);
  }
  TRACE_IN(unit, 4);
  T2C(unit, 51);
#pragma unroll 1
  for (int j = 1; j < 15; j++) {
    const uint32_t sv_prev = sv, sk_prev = sk;
    sv = sn;
    const uint32_t dv = sdesc(c.sb + sv * SLOT, 8192);
    reg_fence(p0);
    exps<SP0, false>(c, s, p0, st0);
    batch<SP1, SP0, 0, 3>(c, s, qs, dq1, sdesc(c.sb + sk * SLOT, 0), o0, p0, dv);
    sk = acquire(c, r);
    wg_wait<1>();
    reg_fence(s); reg_fence(p1);
    release(c, sv_prev); release(c, sk_prev);
    exps<SP1, false>(c, s, p1, st1);
    batch<SP0, SP1, 1, 4>(c, s, qs, dq0, sdesc(c.sb + sk * SLOT, 0), o1, p1, dv);
    sn = acquire(c, r);
    if (SP0) wg_wait<0>(); else wg_wait<1>();
    reg_fence(s);
  }
  TRACE_IN(unit, 5);
  T2C(unit + 1, 52);
  const uint32_t sv_prev = sv;
  sv = sn;
  const uint32_t dv = sdesc(c.sb + sv * SLOT, 8192);
  reg_fence(p0);
  exps<SP0, false>(c, s, p0, st0);
  batch<SP1, SP0, 0, 5>(c, s, qs, dq1, sdesc(c.sb + sk * SLOT, 0), o0, p0, dv);
  asm volatile("ld.volatile.shared.u32 %0, [%1];" : "=r"(d) : "r"(c.sb + DESC_OFF + ((unit + 1) & 3) * 4) : "memory");
  wg_wait<1>();
  reg_fence(s); reg_fence(p1);
  T2C(unit + 1, 53);
  release(c, sv_prev); release(c, sk);
  d = __shfl_sync(0xffffffffu, d, 0);
  const bool bad0 = __any_sync(0xffffffffu, finish_sums<SP0>(st0));
  exps<SP1, false>(c, s, p1, st1);
  reg_fence(p1);
  wg_fence();
  issue_pv<SP1, true, 2>(c, o1, p1, dv);
  T2C(unit + 1, 54);
  bool have = EARLY_BEG;
  if (EARLY_BEG) {
    Ring t = r;
#pragma unroll
    for (int k = 0; k < (SKEW_BEG ? 5 : 2); k++) { if (k != 2) have &= mbar_test(c.sb + BAR_FULL + t.slot * 8, t.phase); t.next(); }
  }
  const bool bad = finish_sums<SP1>(st1) | bad0;
  wg_wait<1>();
  reg_fence(o0);
  T2C(unit + 1, 55);
  if (__builtin_expect(!bad0, 1)) {
    o_store<SP0>(c, q0a, o0, st0);
    staged(c, 0);
  }
  uint32_t any;
  asm volatile("{\n.reg .pred p, q;\nsetp.ne.u32 p, %1, 0;\nbar.red.or.pred q, %2, 128, p;\nselp.u32 %0, 1, 0, q;\n}"
               : "=r"(any) : "r"((uint32_t)bad), "n"(2 + SP0) : "memory");
  if (EARLY_BEG && d < (2u << 30) && !__all_sync(0xffffffffu, have)) { Ring t = r; Slots u; begin_acquire(c, t, u, true); }
  T2C(unit + 1, 56);
  wg_wait<0>();
  reg_fence(o1);
  T2C(unit + 1, 57);
  release(c, sv);
  return __any_sync(0xffffffffu, any) ? 2 - bad0 : 0;
}

__device__ __forceinline__ void consumer(const Ctx& c, const __nv_bfloat16* const* kv) {
  Ring r{0, 0, 0};
  float a0[64], a1[64];
  Slots h;
  RowSum inv;
  uint32_t d = blockIdx.x, dc;
  int i = 0, part;
begin:
  proj_begin(c, r, a0, h, true);
  while (true) {
    TRACE(i, 0); TRACE(i, 6);
    dc = d;
    proj_main(c, r, a0, a1, h, d >> 30, d >> 30 ? ((d >> 16) & 63) + 1 : DM / 64, i);
    TRACE(i, 1);
    if (d >> 30) goto out_tile;
    T2C(i, 40);
    stage_lo(c, a0, SM_C);
    fence_async_smem();
    T2C(i, 41);
    part = c.wg == 0 ? attention<false>(c, r, i, d, a1, inv, h) : attention<true>(c, r, i, d, a1, inv, h);
    if (part) goto redo;
    if (!EARLY_BEG || d >= (2u << 30)) break;
    proj_begin(c, r, a0, h, false);
    T2C(i + 1, 58);
    reg_fence(a1);
    o_store<false>(c, c.sb + QBUF_OFF + (c.wg + 1) * 16384, a1, inv);
    staged(c, 1);
    TRACE(i, 3); TRACE(i, 7);
    i++;
  }
  o_store<false>(c, c.sb + QBUF_OFF + (c.wg + 1) * 16384, a1, inv);
  staged(c, 1);
  T2C(i + 1, 58);
next:
  TRACE(i, 3); TRACE(i, 7);
  if ((d >> 30) != 2) {
    i++;
    r.uniform();
    goto begin;
  }
  trace_dump(c);
  return;
out_tile:
  proj_end(c, a1, h);
  if (((d >> 28) & 3) == 2) {
    const uint32_t off = c.sb + stage_off(c);
#pragma unroll 1
    for (int k = (d >> 5) & 3; k > 0; k--) {
#pragma unroll
      for (int t = 0; t < 4; t++) {
        const uint32_t sp = acquire(c, r), base = off + sp * SLOT + c.wg * (t == 3 ? 4096 : 8192);
#pragma unroll
        for (int jj = 0; jj < (t == 3 ? 2 : 4); jj++) add16(base + jj * 2048, t < 2 ? &a0[(t * 4 + jj) * 8] : &a1[((t - 2) * 4 + jj) * 8]);
        release(c, sp);
      }
    }
  }
  stage_lo(c, a0, 1.f);
  staged(c, 0);
  d = get_desc(c, i + 1);
  wait_hi_free(c, r, i);
  stage_hi<false>(c, a1, 1.f);
  staged(c, 1);
  TRACE(i, 2);
  goto next;
redo:
  {
    const size_t hoff = (size_t)(dc & 511) * (SK * DH);
    const int br = (dc >> 9) & 1;
#pragma unroll 1
    for (part--; part < 2; part++) {
      const int t = c.wg ? 3 - part : part;
      redo_tile(c, c.sb + QBUF_OFF + t * 16384, t == 3 ? 4096 : 8192, kv[br] + hoff, kv[2 + br] + hoff);
      staged(c, part);
    }
  }
  goto next;
}

template <bool SIMPLE>
__global__ void __launch_bounds__(384, 1) mha_fused_kernel(const __grid_constant__ Params P) {
  extern __shared__ __align__(1024) uint8_t smem_raw[];
  const uint32_t sbase = smem_u32(smem_raw);
  const int tid = threadIdx.x;
  const int wg = __shfl_sync(0xffffffffu, tid >> 7, 0);
  const int warp = __shfl_sync(0xffffffffu, (tid >> 5) & 3, 0);
  const int lane = tid & 31;
  const int cta = blockIdx.x;

  if (tid == 0) T3(15, 0);
  if (tid >= 256 && tid < 256 + 18) asm volatile("prefetch.tensormap [%0];" ::"l"(&P.x[0][0] + (tid - 256)) : "memory");
  if (tid == 0) {
    if ((sbase & 1023) || sbase + SMEM_BYTES > 0x40000) __trap();
    for (int i = 0; i < NSX; i++) { mbar_init(sbase + BAR_FULL + i * 8, 1); mbar_init(sbase + BAR_EMPTY + i * 8, 8); }
    for (int i = 0; i < 4; i++) mbar_init(sbase + BAR_STG + i * 8, 4);
    mbar_init(sbase + BAR_DESC, 1);
    mbar_init(sbase + BAR_GO, 1);
    asm volatile("fence.mbarrier_init.release.cluster;" ::: "memory");
  }
  __syncthreads();

  if (wg == 2) {
    asm volatile("setmaxnreg.dec.sync.aligned.u32 %0;" ::"n"(REG_P));
    if (warp == 1) {
      const uint32_t qb = sbase + QBUF_OFF;
      const uint32_t ep = __shfl_sync(0xffffffffu, *(volatile unsigned*)&g_epoch + 1, 0);
      asm volatile("st.volatile.shared.u32 [%0], %1;" ::"r"(sbase + EPOCH_OFF), "r"(ep) : "memory");
      uint32_t dc = cta, qi = 0, piece = 0;
      for (int i = 0; (dc >> 30) != 2; i++) {
        mbar_wait_w(sbase + BAR_GO, i & 1);
        if (piece == 0) {
          if (lane == 0) {
            qi = atomicAdd(&g_next, 1);
            if (qi == (SIMPLE ? NBETA * (NH + 5) : Q_RANGES) - 1) { g_next = 0; g_epoch = ep; }
          }
          qi = __shfl_sync(0xffffffffu, qi, 0) + (SIMPLE ? gridDim.x : NCTA);
        }
        uint32_t d;
        if (qi < Q_RANGES) { d = c_sched.queue[qi]; if (d & 0x8000) d ^= (1u << 30) | (63u << 16) | 0x8000; }
        else if (SIMPLE) { const uint32_t t = qi - NBETA * NH; d = t < NBETA * 5 ? (1u << 30) | (63u << 16) | (t % 5) << 8 | t / 5 : 2u << 30; }
        else { const uint32_t e = qi - Q_RANGES, g = e / 5; d = c_sched.piece[g][piece++] | (e - g * 5) << 8; }
        if ((d >> 30) == 1) {
          const uint32_t ok = __ballot_sync(0xffffffffu, reached(&g_cnt[lane & 1][d & 31], ep * (lane & 1 ? NH - H_LATE : H_LATE)));
          if (!(ok & 2)) d |= ((d >> 22) & 63) >= 2 * H_LATE ? (2u << 30) | 128 : 128;
          if (!(ok & 1)) d |= 2u << 30;
        }
        asm volatile("st.volatile.shared.u32 [%0], %1;" ::"r"(sbase + DESC_OFF + ((i + 1) & 3) * 4), "r"(d) : "memory");
        __syncwarp();
        mbar_arrive_warp(sbase + BAR_DESC);
        const Work w = decode(dc);
        dc = d;
        if (w.kind == 0) {
#pragma unroll
          for (int e = 0; e < 4; e++) {
            const int t = (0x2130 >> (4 * e)) & 3;
            mbar_wait_w(sbase + BAR_STG + (e & 1) * 16 + (e >> 1) * 8, i & 1);
            tma_st3_w(&P.o_st[t == 3], qb + t * 16384, 0, t * 64, w.beta * 64 + w.sub * 2);
            bulk_commit();
            T2P(i + 1, 5, 2 * e);
            if (e) {
              bulk_wait_read<1>();
              mbar_arrive8_w(sbase + BAR_EMPTY + (NS + ((0x1300 >> (4 * e)) & 3)) * 8);
              T2P(i + 1, 5, 2 * e - 1);
            }
          }
          bulk_wait_read<0>();
          mbar_arrive8_w(sbase + BAR_EMPTY + (NS + 2) * 8);
          T2P(i + 1, 5, 7);
        } else {
          uint64_t pol;
          asm volatile("createpolicy.fractional.L2::evict_first.b64 %0, 1.0;" : "=l"(pol));
#pragma unroll
          for (int e = 0; e < 4; e++) {
            const int h = e & 1;
            mbar_wait_w(sbase + BAR_STG + h * 16 + (e >> 1) * 8, i & 1);
#pragma unroll
            for (int t = e & 2; t < (e & 2) + 2; t++) {
              const uint32_t half = t == 3 ? 4096 : 8192, o = t * 16384 + h * half;
              if (w.mode == 1)
                asm volatile(ELECT "cp.async.bulk.global.shared::cta.bulk_group [%0], [%1], %2;\n}"
                             ::"l"(g_part + (size_t)w.range * QBUF_BYTES + o), "r"(qb + o), "r"(half) : "memory");
              else tma_st3_hint_w(&P.out_st[t == 3], qb + o, (w.beta >> 4) * DM + w.sub * 128 + h * 64, t * 64, w.beta & 15, pol);
            }
            if (h) bulk_commit();
          }
          bulk_wait_read<1>();
          mbar_arrive8_w(sbase + BAR_EMPTY + NS * 8);
          mbar_arrive8_w(sbase + BAR_EMPTY + (NS + 1) * 8);
          bulk_wait_read<0>();
          mbar_arrive8_w(sbase + BAR_EMPTY + (NS + 2) * 8);
          mbar_arrive8_w(sbase + BAR_EMPTY + (NS + 3) * 8);
        }
        T3(i, 0);
        asm volatile("cp.async.bulk.wait_group 0;" ::: "memory");
        T3(i, 1);
        if (w.kind == 0) asm volatile(ELECT "red.release.gpu.global.add.u32 [%0], 1;\n}" ::"l"(&g_cnt[w.sub >= H_LATE][w.beta]) : "memory");
        else if (w.mode == 1) asm volatile(ELECT "st.release.gpu.global.u32 [%0], %1;\n}" ::"l"(&g_flag[w.range]), "r"(ep) : "memory");
        T3(i, 2);
      }
      T3(15, 1);
    } else
    if (warp == 0) {
      Ring r{0, 1, 1};
      uint32_t d = cta;
      for (int i = 0;; i++) {
        const Work w = decode(d);
        if (w.kind == 2) break;
        const CUtensorMap* m = w.kind == 0 ? &P.wq[w.beta >> 4] : &P.wo[w.beta >> 4];
        const int c1 = w.k0 * 64;
        for (int ks = 0; ks < w.nsteps; ks++) {
          const uint32_t b = borrow(ks, w.nsteps), bar = sbase + BAR_FULL + r.slot * 8;
          mbar_wait_w(bar + (BAR_EMPTY - BAR_FULL), r.phase);
          tma_ld3_w(sbase + r.slot * SLOT, m, 0, c1 + ks * 64, w.sub * 2, bar);
          if (ks < 10) T2P(i, 2, ks);
          if (w.kind != 0 && ks == max(w.nsteps - GO_P, 4)) mbar_arrive_warp(sbase + BAR_GO);
          r.next(); r.next_if(b == 3); r.next_if(b != 0);
        }
        if (w.kind == 0) {
          r.phase ^= 1; r.next(); r.next();
        } else if (w.mode == 2) {
          for (int k = 1; k <= ((d >> 5) & 3); k++) {
            wait_count(&g_flag[w.range + 5 * k], lds(sbase + EPOCH_OFF));
            asm volatile("fence.proxy.async.global;" ::: "memory");
            for (int t = 0; t < 4; t++) {
              const uint32_t bar = sbase + BAR_FULL + r.slot * 8, bytes = t == 3 ? 8192 : 16384;
              mbar_wait_w(sbase + BAR_EMPTY + r.slot * 8, r.phase);
              asm volatile(ELECT EXPECT("%3", "%2") "cp.async.bulk.shared::cluster.global.mbarrier::complete_tx::bytes [%0], [%1], %2, [%3];\n}"
                           ::"r"(sbase + r.slot * SLOT), "l"(g_part + (size_t)(w.range + 5 * k) * QBUF_BYTES + t * 16384), "r"(bytes), "r"(bar)
                           : "memory");
              r.next();
            }
          }
        }
        mbar_wait_w(sbase + BAR_DESC, i & 1);
        d = __shfl_sync(0xffffffffu, lds(sbase + DESC_OFF + ((i + 1) & 3) * 4), 0);
      }
    } else {
      const int hi = warp - 2;
      uint64_t pol_stream;
      asm volatile("createpolicy.fractional.L2::evict_first.b64 %0, 1.0;" : "=l"(pol_stream));
      Ring r{0, 1, 1};
      uint32_t d = cta;
      for (int i = 0;; i++) {
        const Work w = decode(d);
        if (w.kind == 2) break;
        const CUtensorMap* m = w.kind == 0 ? &P.x[hi][w.beta >> 4] : &P.o_ld[hi];
        int c1 = (w.kind == 0 ? (w.beta & 15) : w.beta * 64 + w.k0) * SQ + hi * 128;
        int k_late = -1;
        if (w.kind != 0) {
          if (!hi) T3(i, 3);
          if (d >= (3u << 30)) wait_count(&g_cnt[0][w.beta], lds(sbase + EPOCH_OFF) * H_LATE);
          if (d & 128) k_late = max(2 * H_LATE - w.k0, 0);
          if (!hi) T3(i, 4);
          asm volatile("fence.proxy.async.global;" ::: "memory");
          if (!hi) T3(i, 5);
        }
        for (int ks = 0; ks < w.nsteps; ks++) {
          if (ks == k_late) {
            if (!hi) T3(i, 6);
            wait_count(&g_cnt[1][d & 31], lds(sbase + EPOCH_OFF) * (NH - H_LATE));
            asm volatile("fence.proxy.async.global;" ::: "memory");
            if (!hi) T3(i, 7);
          }
          const uint32_t b = borrow(ks, w.nsteps);
          const bool bo = hi ? b == 0 : b != 3;
          r.next(); r.next_if(hi && b == 3);
          const uint32_t sl = bo ? NS + b + 3 * hi : r.slot, bar = sbase + BAR_FULL + sl * 8;
          mbar_wait_w(bar + (BAR_EMPTY - BAR_FULL), bo ? r.xp : r.phase);
          if (w.kind == 0) tma_ld2_w(sbase + sl * SLOT, m, ks * 64, c1, bar, hi ? 96 * 128 : 128 * 128);
          else { tma_ld2_hint_w(sbase + sl * SLOT, m, 0, c1, bar, hi ? 96 * 128 : 128 * 128, pol_stream); c1 += SQ; }
          if (ks < 10) T2P(i, 3 + hi, ks);
          r.next_if(!bo); r.next_if(!hi && b != 0);
          r.xp ^= b == 2;
        }
        r.xp ^= 1;
        if (w.kind == 0) {
          m = &P.kv[hi][w.beta >> 4];
          c1 = (d & 511) * SK;
          for (int j = 0; j < 16; j++) {
            if (hi) r.next();
            const uint32_t bar = sbase + BAR_FULL + r.slot * 8;
            if (i == 0 && j < KV_WIN_TILES) {
              const int s2 = (int)r.slot - 2;
              mbar_wait_w(sbase + BAR_FULL + (s2 < 0 ? s2 + NS : s2) * 8, s2 < 0 ? r.phase : r.phase ^ 1);
            }
            if (j == 15 && hi) mbar_wait_w(sbase + BAR_DESC, i & 1);
            mbar_wait_w(sbase + BAR_EMPTY + r.slot * 8, r.phase);
            tma_ld3_hint_w(sbase + r.slot * SLOT, m, 0, c1, 0, bar, pol_stream);
            T2P(i, 3 + hi, 16 + j);
            if (j == 14 && !hi) mbar_arrive_warp(sbase + BAR_GO);
            c1 += 64;
            r.next();
            if (!hi) r.next();
          }
        }
        mbar_wait_w(sbase + BAR_DESC, i & 1);
        d = __shfl_sync(0xffffffffu, lds(sbase + DESC_OFF + ((i + 1) & 3) * 4), 0);
      }
    }
  } else {
    asm volatile("setmaxnreg.inc.sync.aligned.u32 %0;" ::"n"(REG_C));
    Ctx c;
    c.sb = sbase; c.wg = wg; c.warp = warp; c.src = 0; c.mqk = 0; c.mpv = 0; c.lead = lane == 0;
    consumer(c, P.kp);
  }
}

typedef CUresult (*EncodeFn)(CUtensorMap*, CUtensorMapDataType, cuuint32_t, void*, const cuuint64_t*, const cuuint64_t*,
                             const cuuint32_t*, const cuuint32_t*, CUtensorMapInterleave, CUtensorMapSwizzle,
                             CUtensorMapL2promotion, CUtensorMapFloatOOBfill);

void make_map(EncodeFn enc, CUtensorMap* m, const void* ptr, int rank, const cuuint64_t* dims, const cuuint64_t* strides,
              const cuuint32_t* box, int promo = 2) {
  cuuint32_t es[5] = {1, 1, 1, 1, 1};
  enc(m, CU_TENSOR_MAP_DATA_TYPE_BFLOAT16, rank, const_cast<void*>(ptr), dims, strides, box, es,
      CU_TENSOR_MAP_INTERLEAVE_NONE, CU_TENSOR_MAP_SWIZZLE_128B, promo == 2 ? CU_TENSOR_MAP_L2_PROMOTION_L2_256B : promo == 1 ? CU_TENSOR_MAP_L2_PROMOTION_L2_128B : CU_TENSOR_MAP_L2_PROMOTION_NONE,
      CU_TENSOR_MAP_FLOAT_OOB_FILL_NONE);
}

}

extern "C" void kernel_launch(void* const* d_in, const int* in_sizes, int n_in, void* d_out, int out_size) {
  (void)in_sizes; (void)n_in; (void)out_size;
  static EncodeFn enc = nullptr;
  static void* o_ptr = nullptr;
  static int n_sm = 0;
  if (!enc) {
    void* fn = nullptr;
    cudaDriverEntryPointQueryResult qr;
    cudaGetDriverEntryPoint("cuTensorMapEncodeTiled", &fn, cudaEnableDefault, &qr);
    enc = (EncodeFn)fn;
    cudaGetSymbolAddress(&o_ptr, g_o);
    cudaFuncSetAttribute(mha_fused_kernel<false>, cudaFuncAttributeMaxDynamicSharedMemorySize, SMEM_BYTES);
    cudaFuncSetAttribute(mha_fused_kernel<true>, cudaFuncAttributeMaxDynamicSharedMemorySize, SMEM_BYTES);
    int dev = 0;
    cudaGetDevice(&dev);
    cudaDeviceGetAttribute(&n_sm, cudaDevAttrMultiProcessorCount, dev);
  }
  Params P;
  for (int br = 0; br < 2; br++) {
    const void* x = d_in[br * 5 + 0]; const void* kc = d_in[br * 5 + 1]; const void* vc = d_in[br * 5 + 2];
    const void* wq = d_in[br * 5 + 3]; const void* wo = d_in[br * 5 + 4];
    { cuuint64_t d[2] = {DM, (cuuint64_t)NB * SQ}, s[1] = {DM * 2}; cuuint32_t b[2] = {64, 128}, b2[2] = {64, 96};
      make_map(enc, &P.x[0][br], x, 2, d, s, b, PR_X); make_map(enc, &P.x[1][br], x, 2, d, s, b2, PR_X); }
    { cuuint64_t d[3] = {64, DM, HD / 64}, s[2] = {HD * 2, 128}; cuuint32_t b[3] = {64, 64, 2}; make_map(enc, &P.wq[br], wq, 3, d, s, b, PR_W); }
    { cuuint64_t d[3] = {64, HD, DM / 64}, s[2] = {DM * 2, 128}; cuuint32_t b[3] = {64, 64, 2}; make_map(enc, &P.wo[br], wo, 3, d, s, b, PR_W); }
    { cuuint64_t d[3] = {64, (cuuint64_t)NB * NH * SK, 2}, s[2] = {DH * 2, 128}; cuuint32_t b[3] = {64, 64, 2};
      make_map(enc, &P.kv[0][br], kc, 3, d, s, b, PR_KV); make_map(enc, &P.kv[1][br], vc, 3, d, s, b, PR_KV); }
    P.kp[br] = (const __nv_bfloat16*)kc; P.vp[br] = (const __nv_bfloat16*)vc;

  }
  { cuuint64_t d[2] = {64, (cuuint64_t)NBETA * 64 * SQ}, s[1] = {128}; cuuint32_t b[2] = {64, 128}, b2[2] = {64, 96};
    make_map(enc, &P.o_ld[0], o_ptr, 2, d, s, b); make_map(enc, &P.o_ld[1], o_ptr, 2, d, s, b2); }
  { cuuint64_t d[3] = {64, SQ, NBETA * 64}, s[2] = {128, SQ * 128}; cuuint32_t b[3] = {64, 64, 2}, b2[3] = {64, 32, 2};
    make_map(enc, &P.o_st[0], o_ptr, 3, d, s, b); make_map(enc, &P.o_st[1], o_ptr, 3, d, s, b2); }
  { cuuint64_t d[3] = {2 * DM, SQ, NB}, s[2] = {2 * DM * 2, (cuuint64_t)SQ * 2 * DM * 2}; cuuint32_t b[3] = {64, 64, 1}, b2[3] = {64, 32, 1};
    make_map(enc, &P.out_st[0], d_out, 3, d, s, b); make_map(enc, &P.out_st[1], d_out, 3, d, s, b2); }
  if (n_sm >= NCTA) mha_fused_kernel<false><<<NCTA, 384, SMEM_BYTES>>>(P);
  else mha_fused_kernel<true><<<n_sm, 384, SMEM_BYTES>>>(P);
}
```

```cpp
#include <cuda_runtime.h>
#include <cuda_bf16.h>
#include <cuda.h>
#include <stdint.h>

namespace {

__device__ __forceinline__ void wgmma_proj(float (&d)[64], uint64_t da, uint64_t db, int scaleD) {
  asm volatile("{\n.reg .pred p;\nsetp.ne.b32 p, %66, 0;\n"
      "wgmma.mma_async.sync.aligned.m64n128k16.f32.bf16.bf16 "
      "{%0, %1, %2, %3, %4, %5, %6, %7, %8, %9, %10, %11, %12, %13, %14, %15, %16, %17, %18, %19, %20, %21, %22, %23, %24, %25, %26, %27, %28, %29, %30, "
      "%31, %32, %33, %34, %35, %36, %37, %38, %39, %40, %41, %42, %43, %44, %45, %46, %47, %48, %49, %50, %51, %52, %53, %54, %55, %56, %57, %58, %59, %60, "
      "%61, %62, %63}, "
      "%64, %65, p, 1, 1, 0, 1;\n}\n"
      : "+f"(d[0]), "+f"(d[1]), "+f"(d[2]), "+f"(d[3]), "+f"(d[4]), "+f"(d[5]), "+f"(d[6]), "+f"(d[7]), "+f"(d[8]), "+f"(d[9]), "+f"(d[10]), "+f"(d[11]),
        "+f"(d[12]), "+f"(d[13]), "+f"(d[14]), "+f"(d[15]), "+f"(d[16]), "+f"(d[17]), "+f"(d[18]), "+f"(d[19]), "+f"(d[20]), "+f"(d[21]), "+f"(d[22]),
        "+f"(d[23]), "+f"(d[24]), "+f"(d[25]), "+f"(d[26]), "+f"(d[27]), "+f"(d[28]), "+f"(d[29]), "+f"(d[30]), "+f"(d[31]), "+f"(d[32]), "+f"(d[33]),
        "+f"(d[34]), "+f"(d[35]), "+f"(d[36]), "+f"(d[37]), "+f"(d[38]), "+f"(d[39]), "+f"(d[40]), "+f"(d[41]), "+f"(d[42]), "+f"(d[43]), "+f"(d[44]),
        "+f"(d[45]), "+f"(d[46]), "+f"(d[47]), "+f"(d[48]), "+f"(d[49]), "+f"(d[50]), "+f"(d[51]), "+f"(d[52]), "+f"(d[53]), "+f"(d[54]), "+f"(d[55]),
        "+f"(d[56]), "+f"(d[57]), "+f"(d[58]), "+f"(d[59]), "+f"(d[60]), "+f"(d[61]), "+f"(d[62]), "+f"(d[63])
      : "l"(da), "l"(db), "r"(scaleD));
}
__device__ __forceinline__ void wgmma_proj96(float (&d)[64], uint64_t da, uint64_t db, int scaleD) {
  asm volatile("{\n.reg .pred p;\nsetp.ne.b32 p, %50, 0;\n"
      "wgmma.mma_async.sync.aligned.m64n96k16.f32.bf16.bf16 "
      "{%0, %1, %2, %3, %4, %5, %6, %7, %8, %9, %10, %11, %12, %13, %14, %15, %16, %17, %18, %19, %20, %21, %22, %23, %24, %25, %26, %27, %28, %29, %30, "
      "%31, %32, %33, %34, %35, %36, %37, %38, %39, %40, %41, %42, %43, %44, %45, %46, %47}, "
      "%48, %49, p, 1, 1, 1, 0;\n}\n"
      : "+f"(d[0]), "+f"(d[1]), "+f"(d[2]), "+f"(d[3]), "+f"(d[4]), "+f"(d[5]), "+f"(d[6]), "+f"(d[7]), "+f"(d[8]), "+f"(d[9]), "+f"(d[10]), "+f"(d[11]),
        "+f"(d[12]), "+f"(d[13]), "+f"(d[14]), "+f"(d[15]), "+f"(d[16]), "+f"(d[17]), "+f"(d[18]), "+f"(d[19]), "+f"(d[20]), "+f"(d[21]), "+f"(d[22]),
        "+f"(d[23]), "+f"(d[24]), "+f"(d[25]), "+f"(d[26]), "+f"(d[27]), "+f"(d[28]), "+f"(d[29]), "+f"(d[30]), "+f"(d[31]), "+f"(d[32]), "+f"(d[33]),
        "+f"(d[34]), "+f"(d[35]), "+f"(d[36]), "+f"(d[37]), "+f"(d[38]), "+f"(d[39]), "+f"(d[40]), "+f"(d[41]), "+f"(d[42]), "+f"(d[43]), "+f"(d[44]),
        "+f"(d[45]), "+f"(d[46]), "+f"(d[47])
      : "l"(da), "l"(db), "r"(scaleD));
}
__device__ __forceinline__ void wgmma_qk(float (&d)[32], uint64_t da, uint64_t db, int scaleD) {
  asm volatile("{\n.reg .pred p;\nsetp.ne.b32 p, %34, 0;\n"
      "wgmma.mma_async.sync.aligned.m64n64k16.f32.bf16.bf16 "
      "{%0, %1, %2, %3, %4, %5, %6, %7, %8, %9, %10, %11, %12, %13, %14, %15, %16, %17, %18, %19, %20, %21, %22, %23, %24, %25, %26, %27, %28, %29, %30, "
      "%31}, "
      "%32, %33, p, 1, 1, 0, 0;\n}\n"
      : "+f"(d[0]), "+f"(d[1]), "+f"(d[2]), "+f"(d[3]), "+f"(d[4]), "+f"(d[5]), "+f"(d[6]), "+f"(d[7]), "+f"(d[8]), "+f"(d[9]), "+f"(d[10]), "+f"(d[11]),
        "+f"(d[12]), "+f"(d[13]), "+f"(d[14]), "+f"(d[15]), "+f"(d[16]), "+f"(d[17]), "+f"(d[18]), "+f"(d[19]), "+f"(d[20]), "+f"(d[21]), "+f"(d[22]),
        "+f"(d[23]), "+f"(d[24]), "+f"(d[25]), "+f"(d[26]), "+f"(d[27]), "+f"(d[28]), "+f"(d[29]), "+f"(d[30]), "+f"(d[31])
      : "l"(da), "l"(db), "r"(scaleD));
}
__device__ __forceinline__ void wgmma_pv(float (&d)[64], uint32_t a0, uint32_t a1, uint32_t a2, uint32_t a3, uint64_t db, int scaleD) {
  asm volatile("{\n.reg .pred p;\nsetp.ne.b32 p, %69, 0;\n"
      "wgmma.mma_async.sync.aligned.m64n128k16.f32.bf16.bf16 "
      "{%0, %1, %2, %3, %4, %5, %6, %7, %8, %9, %10, %11, %12, %13, %14, %15, %16, %17, %18, %19, %20, %21, %22, %23, %24, %25, %26, %27, %28, %29, %30, "
      "%31, %32, %33, %34, %35, %36, %37, %38, %39, %40, %41, %42, %43, %44, %45, %46, %47, %48, %49, %50, %51, %52, %53, %54, %55, %56, %57, %58, %59, %60, "
      "%61, %62, %63}, "
      "{%64, %65, %66, %67}, %68, p, 1, 1, 1;\n}\n"
      : "+f"(d[0]), "+f"(d[1]), "+f"(d[2]), "+f"(d[3]), "+f"(d[4]), "+f"(d[5]), "+f"(d[6]), "+f"(d[7]), "+f"(d[8]), "+f"(d[9]), "+f"(d[10]), "+f"(d[11]),
        "+f"(d[12]), "+f"(d[13]), "+f"(d[14]), "+f"(d[15]), "+f"(d[16]), "+f"(d[17]), "+f"(d[18]), "+f"(d[19]), "+f"(d[20]), "+f"(d[21]), "+f"(d[22]),
        "+f"(d[23]), "+f"(d[24]), "+f"(d[25]), "+f"(d[26]), "+f"(d[27]), "+f"(d[28]), "+f"(d[29]), "+f"(d[30]), "+f"(d[31]), "+f"(d[32]), "+f"(d[33]),
        "+f"(d[34]), "+f"(d[35]), "+f"(d[36]), "+f"(d[37]), "+f"(d[38]), "+f"(d[39]), "+f"(d[40]), "+f"(d[41]), "+f"(d[42]), "+f"(d[43]), "+f"(d[44]),
        "+f"(d[45]), "+f"(d[46]), "+f"(d[47]), "+f"(d[48]), "+f"(d[49]), "+f"(d[50]), "+f"(d[51]), "+f"(d[52]), "+f"(d[53]), "+f"(d[54]), "+f"(d[55]),
        "+f"(d[56]), "+f"(d[57]), "+f"(d[58]), "+f"(d[59]), "+f"(d[60]), "+f"(d[61]), "+f"(d[62]), "+f"(d[63])
      : "r"(a0), "r"(a1), "r"(a2), "r"(a3), "l"(db), "r"(scaleD));
}
__device__ __forceinline__ void wgmma_qk_sp(float (&d)[32], uint32_t a0, uint32_t a1, uint32_t a2, uint32_t a3, uint64_t db, int scaleD, uint32_t meta) {
  asm volatile("{\n.reg .pred p;\nsetp.ne.b32 p, %37, 0;\n"
      "wgmma.mma_async.sp.sync.aligned.m64n64k32.f32.bf16.bf16 "
      "{%0, %1, %2, %3, %4, %5, %6, %7, %8, %9, %10, %11, %12, %13, %14, %15, %16, %17, %18, %19, %20, %21, %22, %23, %24, %25, %26, %27, %28, %29, %30, "
      "%31}, "
      "{%32, %33, %34, %35}, %36, %38, 0, p, 1, 1, 0;\n}\n"
      : "+f"(d[0]), "+f"(d[1]), "+f"(d[2]), "+f"(d[3]), "+f"(d[4]), "+f"(d[5]), "+f"(d[6]), "+f"(d[7]), "+f"(d[8]), "+f"(d[9]), "+f"(d[10]), "+f"(d[11]),
        "+f"(d[12]), "+f"(d[13]), "+f"(d[14]), "+f"(d[15]), "+f"(d[16]), "+f"(d[17]), "+f"(d[18]), "+f"(d[19]), "+f"(d[20]), "+f"(d[21]), "+f"(d[22]),
        "+f"(d[23]), "+f"(d[24]), "+f"(d[25]), "+f"(d[26]), "+f"(d[27]), "+f"(d[28]), "+f"(d[29]), "+f"(d[30]), "+f"(d[31])
      : "r"(a0), "r"(a1), "r"(a2), "r"(a3), "l"(db), "r"(scaleD), "r"(meta));
}
__device__ __forceinline__ void wgmma_pv_sp(float (&d)[64], uint32_t a0, uint32_t a1, uint32_t a2, uint32_t a3, uint64_t db, int scaleD, uint32_t meta) {
  asm volatile("{\n.reg .pred p;\nsetp.ne.b32 p, %69, 0;\n"
      "wgmma.mma_async.sp.sync.aligned.m64n128k32.f32.bf16.bf16 "
      "{%0, %1, %2, %3, %4, %5, %6, %7, %8, %9, %10, %11, %12, %13, %14, %15, %16, %17, %18, %19, %20, %21, %22, %23, %24, %25, %26, %27, %28, %29, %30, "
      "%31, %32, %33, %34, %35, %36, %37, %38, %39, %40, %41, %42, %43, %44, %45, %46, %47, %48, %49, %50, %51, %52, %53, %54, %55, %56, %57, %58, %59, %60, "
      "%61, %62, %63}, "
      "{%64, %65, %66, %67}, %68, %70, 0, p, 1, 1, 1;\n}\n"
      : "+f"(d[0]), "+f"(d[1]), "+f"(d[2]), "+f"(d[3]), "+f"(d[4]), "+f"(d[5]), "+f"(d[6]), "+f"(d[7]), "+f"(d[8]), "+f"(d[9]), "+f"(d[10]), "+f"(d[11]),
        "+f"(d[12]), "+f"(d[13]), "+f"(d[14]), "+f"(d[15]), "+f"(d[16]), "+f"(d[17]), "+f"(d[18]), "+f"(d[19]), "+f"(d[20]), "+f"(d[21]), "+f"(d[22]),
        "+f"(d[23]), "+f"(d[24]), "+f"(d[25]), "+f"(d[26]), "+f"(d[27]), "+f"(d[28]), "+f"(d[29]), "+f"(d[30]), "+f"(d[31]), "+f"(d[32]), "+f"(d[33]),
        "+f"(d[34]), "+f"(d[35]), "+f"(d[36]), "+f"(d[37]), "+f"(d[38]), "+f"(d[39]), "+f"(d[40]), "+f"(d[41]), "+f"(d[42]), "+f"(d[43]), "+f"(d[44]),
        "+f"(d[45]), "+f"(d[46]), "+f"(d[47]), "+f"(d[48]), "+f"(d[49]), "+f"(d[50]), "+f"(d[51]), "+f"(d[52]), "+f"(d[53]), "+f"(d[54]), "+f"(d[55]),
        "+f"(d[56]), "+f"(d[57]), "+f"(d[58]), "+f"(d[59]), "+f"(d[60]), "+f"(d[61]), "+f"(d[62]), "+f"(d[63])
      : "r"(a0), "r"(a1), "r"(a2), "r"(a3), "l"(db), "r"(scaleD), "r"(meta));
}
__device__ __forceinline__ void wgmma_proj_init(float (&d)[64], uint64_t da, uint64_t db, int scaleD) {
  asm volatile("{\n.reg .pred p;\nsetp.ne.b32 p, %66, 0;\n"
      "wgmma.mma_async.sync.aligned.m64n128k16.f32.bf16.bf16 "
      "{%0, %1, %2, %3, %4, %5, %6, %7, %8, %9, %10, %11, %12, %13, %14, %15, %16, %17, %18, %19, %20, %21, %22, %23, %24, %25, %26, %27, %28, %29, %30, "
      "%31, %32, %33, %34, %35, %36, %37, %38, %39, %40, %41, %42, %43, %44, %45, %46, %47, %48, %49, %50, %51, %52, %53, %54, %55, %56, %57, %58, %59, %60, "
      "%61, %62, %63}, "
      "%64, %65, p, 1, 1, 0, 1;\n}\n"
      : "=f"(d[0]), "=f"(d[1]), "=f"(d[2]), "=f"(d[3]), "=f"(d[4]), "=f"(d[5]), "=f"(d[6]), "=f"(d[7]), "=f"(d[8]), "=f"(d[9]), "=f"(d[10]), "=f"(d[11]),
        "=f"(d[12]), "=f"(d[13]), "=f"(d[14]), "=f"(d[15]), "=f"(d[16]), "=f"(d[17]), "=f"(d[18]), "=f"(d[19]), "=f"(d[20]), "=f"(d[21]), "=f"(d[22]),
        "=f"(d[23]), "=f"(d[24]), "=f"(d[25]), "=f"(d[26]), "=f"(d[27]), "=f"(d[28]), "=f"(d[29]), "=f"(d[30]), "=f"(d[31]), "=f"(d[32]), "=f"(d[33]),
        "=f"(d[34]), "=f"(d[35]), "=f"(d[36]), "=f"(d[37]), "=f"(d[38]), "=f"(d[39]), "=f"(d[40]), "=f"(d[41]), "=f"(d[42]), "=f"(d[43]), "=f"(d[44]),
        "=f"(d[45]), "=f"(d[46]), "=f"(d[47]), "=f"(d[48]), "=f"(d[49]), "=f"(d[50]), "=f"(d[51]), "=f"(d[52]), "=f"(d[53]), "=f"(d[54]), "=f"(d[55]),
        "=f"(d[56]), "=f"(d[57]), "=f"(d[58]), "=f"(d[59]), "=f"(d[60]), "=f"(d[61]), "=f"(d[62]), "=f"(d[63])
      : "l"(da), "l"(db), "r"(scaleD));
}
__device__ __forceinline__ void wgmma_proj96_init(float (&d)[64], uint64_t da, uint64_t db, int scaleD) {
  asm volatile("{\n.reg .pred p;\nsetp.ne.b32 p, %50, 0;\n"
      "wgmma.mma_async.sync.aligned.m64n96k16.f32.bf16.bf16 "
      "{%0, %1, %2, %3, %4, %5, %6, %7, %8, %9, %10, %11, %12, %13, %14, %15, %16, %17, %18, %19, %20, %21, %22, %23, %24, %25, %26, %27, %28, %29, %30, "
      "%31, %32, %33, %34, %35, %36, %37, %38, %39, %40, %41, %42, %43, %44, %45, %46, %47}, "
      "%48, %49, p, 1, 1, 1, 0;\n}\n"
      : "=f"(d[0]), "=f"(d[1]), "=f"(d[2]), "=f"(d[3]), "=f"(d[4]), "=f"(d[5]), "=f"(d[6]), "=f"(d[7]), "=f"(d[8]), "=f"(d[9]), "=f"(d[10]), "=f"(d[11]),
        "=f"(d[12]), "=f"(d[13]), "=f"(d[14]), "=f"(d[15]), "=f"(d[16]), "=f"(d[17]), "=f"(d[18]), "=f"(d[19]), "=f"(d[20]), "=f"(d[21]), "=f"(d[22]),
        "=f"(d[23]), "=f"(d[24]), "=f"(d[25]), "=f"(d[26]), "=f"(d[27]), "=f"(d[28]), "=f"(d[29]), "=f"(d[30]), "=f"(d[31]), "=f"(d[32]), "=f"(d[33]),
        "=f"(d[34]), "=f"(d[35]), "=f"(d[36]), "=f"(d[37]), "=f"(d[38]), "=f"(d[39]), "=f"(d[40]), "=f"(d[41]), "=f"(d[42]), "=f"(d[43]), "=f"(d[44]),
        "=f"(d[45]), "=f"(d[46]), "=f"(d[47])
      : "l"(da), "l"(db), "r"(scaleD));
}
__device__ __forceinline__ void wgmma_qk_init(float (&d)[32], uint64_t da, uint64_t db, int scaleD) {
  asm volatile("{\n.reg .pred p;\nsetp.ne.b32 p, %34, 0;\n"
      "wgmma.mma_async.sync.aligned.m64n64k16.f32.bf16.bf16 "
      "{%0, %1, %2, %3, %4, %5, %6, %7, %8, %9, %10, %11, %12, %13, %14, %15, %16, %17, %18, %19, %20, %21, %22, %23, %24, %25, %26, %27, %28, %29, %30, "
      "%31}, "
      "%32, %33, p, 1, 1, 0, 0;\n}\n"
      : "=f"(d[0]), "=f"(d[1]), "=f"(d[2]), "=f"(d[3]), "=f"(d[4]), "=f"(d[5]), "=f"(d[6]), "=f"(d[7]), "=f"(d[8]), "=f"(d[9]), "=f"(d[10]), "=f"(d[11]),
        "=f"(d[12]), "=f"(d[13]), "=f"(d[14]), "=f"(d[15]), "=f"(d[16]), "=f"(d[17]), "=f"(d[18]), "=f"(d[19]), "=f"(d[20]), "=f"(d[21]), "=f"(d[22]),
        "=f"(d[23]), "=f"(d[24]), "=f"(d[25]), "=f"(d[26]), "=f"(d[27]), "=f"(d[28]), "=f"(d[29]), "=f"(d[30]), "=f"(d[31])
      : "l"(da), "l"(db), "r"(scaleD));
}
__device__ __forceinline__ void wgmma_pv_init(float (&d)[64], uint32_t a0, uint32_t a1, uint32_t a2, uint32_t a3, uint64_t db, int scaleD) {
  asm volatile("{\n.reg .pred p;\nsetp.ne.b32 p, %69, 0;\n"
      "wgmma.mma_async.sync.aligned.m64n128k16.f32.bf16.bf16 "
      "{%0, %1, %2, %3, %4, %5, %6, %7, %8, %9, %10, %11, %12, %13, %14, %15, %16, %17, %18, %19, %20, %21, %22, %23, %24, %25, %26, %27, %28, %29, %30, "
      "%31, %32, %33, %34, %35, %36, %37, %38, %39, %40, %41, %42, %43, %44, %45, %46, %47, %48, %49, %50, %51, %52, %53, %54, %55, %56, %57, %58, %59, %60, "
      "%61, %62, %63}, "
      "{%64, %65, %66, %67}, %68, p, 1, 1, 1;\n}\n"
      : "=f"(d[0]), "=f"(d[1]), "=f"(d[2]), "=f"(d[3]), "=f"(d[4]), "=f"(d[5]), "=f"(d[6]), "=f"(d[7]), "=f"(d[8]), "=f"(d[9]), "=f"(d[10]), "=f"(d[11]),
        "=f"(d[12]), "=f"(d[13]), "=f"(d[14]), "=f"(d[15]), "=f"(d[16]), "=f"(d[17]), "=f"(d[18]), "=f"(d[19]), "=f"(d[20]), "=f"(d[21]), "=f"(d[22]),
        "=f"(d[23]), "=f"(d[24]), "=f"(d[25]), "=f"(d[26]), "=f"(d[27]), "=f"(d[28]), "=f"(d[29]), "=f"(d[30]), "=f"(d[31]), "=f"(d[32]), "=f"(d[33]),
        "=f"(d[34]), "=f"(d[35]), "=f"(d[36]), "=f"(d[37]), "=f"(d[38]), "=f"(d[39]), "=f"(d[40]), "=f"(d[41]), "=f"(d[42]), "=f"(d[43]), "=f"(d[44]),
        "=f"(d[45]), "=f"(d[46]), "=f"(d[47]), "=f"(d[48]), "=f"(d[49]), "=f"(d[50]), "=f"(d[51]), "=f"(d[52]), "=f"(d[53]), "=f"(d[54]), "=f"(d[55]),
        "=f"(d[56]), "=f"(d[57]), "=f"(d[58]), "=f"(d[59]), "=f"(d[60]), "=f"(d[61]), "=f"(d[62]), "=f"(d[63])
      : "r"(a0), "r"(a1), "r"(a2), "r"(a3), "l"(db), "r"(scaleD));
}
__device__ __forceinline__ void wgmma_qk_sp_init(float (&d)[32], uint32_t a0, uint32_t a1, uint32_t a2, uint32_t a3, uint64_t db, int scaleD, uint32_t meta) {
  asm volatile("{\n.reg .pred p;\nsetp.ne.b32 p, %37, 0;\n"
      "wgmma.mma_async.sp.sync.aligned.m64n64k32.f32.bf16.bf16 "
      "{%0, %1, %2, %3, %4, %5, %6, %7, %8, %9, %10, %11, %12, %13, %14, %15, %16, %17, %18, %19, %20, %21, %22, %23, %24, %25, %26, %27, %28, %29, %30, "
      "%31}, "
      "{%32, %33, %34, %35}, %36, %38, 0, p, 1, 1, 0;\n}\n"
      : "=f"(d[0]), "=f"(d[1]), "=f"(d[2]), "=f"(d[3]), "=f"(d[4]), "=f"(d[5]), "=f"(d[6]), "=f"(d[7]), "=f"(d[8]), "=f"(d[9]), "=f"(d[10]), "=f"(d[11]),
        "=f"(d[12]), "=f"(d[13]), "=f"(d[14]), "=f"(d[15]), "=f"(d[16]), "=f"(d[17]), "=f"(d[18]), "=f"(d[19]), "=f"(d[20]), "=f"(d[21]), "=f"(d[22]),
        "=f"(d[23]), "=f"(d[24]), "=f"(d[25]), "=f"(d[26]), "=f"(d[27]), "=f"(d[28]), "=f"(d[29]), "=f"(d[30]), "=f"(d[31])
      : "r"(a0), "r"(a1), "r"(a2), "r"(a3), "l"(db), "r"(scaleD), "r"(meta));
}
__device__ __forceinline__ void wgmma_pv_sp_init(float (&d)[64], uint32_t a0, uint32_t a1, uint32_t a2, uint32_t a3, uint64_t db, int scaleD, uint32_t meta) {
  asm volatile("{\n.reg .pred p;\nsetp.ne.b32 p, %69, 0;\n"
      "wgmma.mma_async.sp.sync.aligned.m64n128k32.f32.bf16.bf16 "
      "{%0, %1, %2, %3, %4, %5, %6, %7, %8, %9, %10, %11, %12, %13, %14, %15, %16, %17, %18, %19, %20, %21, %22, %23, %24, %25, %26, %27, %28, %29, %30, "
      "%31, %32, %33, %34, %35, %36, %37, %38, %39, %40, %41, %42, %43, %44, %45, %46, %47, %48, %49, %50, %51, %52, %53, %54, %55, %56, %57, %58, %59, %60, "
      "%61, %62, %63}, "
      "{%64, %65, %66, %67}, %68, %70, 0, p, 1, 1, 1;\n}\n"
      : "=f"(d[0]), "=f"(d[1]), "=f"(d[2]), "=f"(d[3]), "=f"(d[4]), "=f"(d[5]), "=f"(d[6]), "=f"(d[7]), "=f"(d[8]), "=f"(d[9]), "=f"(d[10]), "=f"(d[11]),
        "=f"(d[12]), "=f"(d[13]), "=f"(d[14]), "=f"(d[15]), "=f"(d[16]), "=f"(d[17]), "=f"(d[18]), "=f"(d[19]), "=f"(d[20]), "=f"(d[21]), "=f"(d[22]),
        "=f"(d[23]), "=f"(d[24]), "=f"(d[25]), "=f"(d[26]), "=f"(d[27]), "=f"(d[28]), "=f"(d[29]), "=f"(d[30]), "=f"(d[31]), "=f"(d[32]), "=f"(d[33]),
        "=f"(d[34]), "=f"(d[35]), "=f"(d[36]), "=f"(d[37]), "=f"(d[38]), "=f"(d[39]), "=f"(d[40]), "=f"(d[41]), "=f"(d[42]), "=f"(d[43]), "=f"(d[44]),
        "=f"(d[45]), "=f"(d[46]), "=f"(d[47]), "=f"(d[48]), "=f"(d[49]), "=f"(d[50]), "=f"(d[51]), "=f"(d[52]), "=f"(d[53]), "=f"(d[54]), "=f"(d[55]),
        "=f"(d[56]), "=f"(d[57]), "=f"(d[58]), "=f"(d[59]), "=f"(d[60]), "=f"(d[61]), "=f"(d[62]), "=f"(d[63])
      : "r"(a0), "r"(a1), "r"(a2), "r"(a3), "l"(db), "r"(scaleD), "r"(meta));
}

constexpr int NB = 16, SQ = 224, DM = 640, NH = 32, SK = 1024, DH = 128;
constexpr int HD = NH * DH;
constexpr int NBETA = 2 * NB;
constexpr int NCTA = 132;
constexpr int NS = 10;
constexpr int SLOT = 16384;
constexpr int QBUF_OFF = NS * SLOT;
constexpr int NSX = NS + 4;
constexpr int BAR_OFF = NSX * SLOT;
constexpr int BAR_FULL = BAR_OFF;
constexpr int BAR_EMPTY = BAR_OFF + 8 * NSX;
constexpr int BAR_STG = BAR_OFF + 16 * NSX;
constexpr int BAR_OUT = BAR_STG + 32;
constexpr int BAR_DESC = BAR_OUT + 8;
constexpr int BAR_GO = BAR_DESC + 8;
constexpr int DESC_OFF = BAR_GO + 8;
constexpr int EPOCH_OFF = DESC_OFF + 16;
constexpr int TRACE_OFF = EPOCH_OFF + 8;
constexpr int SMEM_BYTES = TRACE_OFF;
constexpr float SM_C = 0.08838834764831845f * 1.4426950408889634f;
constexpr float SUM_HI = 1099511627776.f, SUM_LO = 1.f / 1099511627776.f;
constexpr uint32_t META_QK = 0xEEEE4444u;
constexpr uint32_t META_PV = 0x44EEEE44u;

#define QK_EARLY_MASK 3
#define ST_ORDER 0x2130
#define LAG_BAR 5
#define ST_NOW 9
#define PF_UNITS 0
#define PF_MASK 0x2a8
#define PF_MASK0 PF_MASK
#define PF_X 0
#define PF_XJ 2
#define PF_W 0
#define KV_WIN_UNITS 2
#define KV_WIN_D 4
#define KV_WIN_T2 16
#define O_LD_POL 1
#define PACK_EARLY 0x00
#define O_STEPS 4
#define TLB_WARM 0
#define DEV_HALF 0
#define DEV_IDLE 0
#define KV_WIN_RAMP 4
#define KV_WIN_N 132
#define BORROW_ALT 0
#define PF_J0 0
#define PDEPTH 0
#define EARLY_BEG 1
#define KV_WIN_TILES -2
#define PR_KV 2
#define PR_X 2
#define PR_W 2
#define REG_C 232
#define REG_P 40
#define GO_P 4
#define P_POS 224
#define P_STRIDE 32
#define B_LATE 32
#define H_LATE 25
#define RANGE_ORDER 0, 1, 2, 3, 4, 5, 6, 7, 8, 9, 10, 11, 12, 13, 14, 15, 16, 17, 18, 19, 20, 21, 22, 23, 24, 25
#define P_EARLY 13
#define RANGE_TABLE 0, 69, 139, 208, 277, 344, 410, 474, 536, 595, 653, 704, 760, 813, 862, 907, 945, 988, 1024, 1063, 1098, 1121, 1145, 1173, 1186, 1200, 1216

struct Params {
  CUtensorMap x[2][2], wq[2], kv[2][2], wo[2];
  CUtensorMap o_ld[2], o_st[2], out_st[2];
  const __nv_bfloat16* kp[2];
  const __nv_bfloat16* vp[2];
};

constexpr int O_BLOCKS = NBETA * 64 + 2 * NCTA;
__device__ __align__(128) __nv_bfloat16 g_o[(size_t)O_BLOCKS * SQ * 64];
__device__ unsigned g_cnt[2][NBETA];
__device__ unsigned g_epoch, g_next;
__device__ unsigned g_flag[NCTA];

__device__ __forceinline__ uint32_t smem_u32(const void* p) { return (uint32_t)__cvta_generic_to_shared(p); }
__device__ __forceinline__ void mbar_init(uint32_t bar, int cnt) {
  asm volatile("mbarrier.init.shared::cta.b64 [%0], %1;" ::"r"(bar), "r"(cnt) : "memory");
}
__device__ __forceinline__ void mbar_arrive(uint32_t bar) {
  asm volatile("mbarrier.arrive.shared::cta.b64 _, [%0];" ::"r"(bar) : "memory");
}
__device__ __forceinline__ void mbar_arrive_warp(uint32_t bar) {
  asm volatile("{\n.reg .pred p;\nelect.sync _|p, 0xffffffff;\n@p mbarrier.arrive.shared::cta.b64 _, [%0];\n}" ::"r"(bar) : "memory");
}
__device__ __forceinline__ int lane_now() { int l; asm volatile("mov.u32 %0, %%laneid;" : "=r"(l)); return l; }
__device__ __forceinline__ bool mbar_try(uint32_t bar, uint32_t parity) {
  uint32_t ok;
  asm volatile("{\n.reg .pred p;\nmbarrier.try_wait.parity.shared::cta.b64 p, [%1], %2;\nselp.u32 %0, 1, 0, p;\n}"
               : "=r"(ok) : "r"(bar), "r"(parity) : "memory");
  return ok;
}
__device__ __forceinline__ bool mbar_test(uint32_t bar, uint32_t parity) {
  uint32_t ok;
  asm volatile("{\n.reg .pred p;\nmbarrier.test_wait.parity.shared::cta.b64 p, [%1], %2;\nselp.u32 %0, 1, 0, p;\n}"
               : "=r"(ok) : "r"(bar), "r"(parity) : "memory");
  return ok;
}
__device__ __forceinline__ void mbar_wait_w(uint32_t bar, uint32_t parity) {
  uint32_t n = 0;
  while (!__all_sync(0xffffffffu, mbar_try(bar, parity))) {
    if (++n > (1u << 22)) __trap();
  }
}
#define ELECT "{\n.reg .pred p;\nelect.sync _|p, 0xffffffff;\n@p "
__device__ __forceinline__ void tma_st3_hint_w(const CUtensorMap* m, uint32_t src, int c0, int c1, int c2, uint64_t pol) {
  asm volatile(ELECT "cp.async.bulk.tensor.3d.global.shared::cta.bulk_group.L2::cache_hint [%0, {%2, %3, %4}], [%1], %5;\n}"
               ::"l"(m), "r"(src), "r"(c0), "r"(c1), "r"(c2), "l"(pol) : "memory");
}
#define EXPECT(bar, bytes) "mbarrier.arrive.expect_tx.shared::cta.b64 _, [" bar "], " bytes ";\n@p "
__device__ __forceinline__ void tma_ld2_w(uint32_t dst, const CUtensorMap* m, int c0, int c1, uint32_t bar, uint32_t bytes) {
  asm volatile(ELECT EXPECT("%2", "%5") "cp.async.bulk.tensor.2d.shared::cluster.global.mbarrier::complete_tx::bytes [%0], [%1, {%3, %4}], [%2];\n}"
               ::"r"(dst), "l"(m), "r"(bar), "r"(c0), "r"(c1), "r"(bytes) : "memory");
}
__device__ __forceinline__ void tma_ld2_hint_w(uint32_t dst, const CUtensorMap* m, int c0, int c1, uint32_t bar, uint32_t bytes, uint64_t pol) {
  asm volatile(ELECT EXPECT("%2", "%6") "cp.async.bulk.tensor.2d.shared::cluster.global.mbarrier::complete_tx::bytes.L2::cache_hint"
               " [%0], [%1, {%3, %4}], [%2], %5;\n}"
               ::"r"(dst), "l"(m), "r"(bar), "r"(c0), "r"(c1), "l"(pol), "r"(bytes) : "memory");
}
__device__ __forceinline__ void tma_ld3_w(uint32_t dst, const CUtensorMap* m, int c0, int c1, int c2, uint32_t bar, uint32_t bytes) {
  asm volatile(ELECT EXPECT("%2", "%6") "cp.async.bulk.tensor.3d.shared::cluster.global.mbarrier::complete_tx::bytes [%0], [%1, {%3, %4, %5}], [%2];\n}"
               ::"r"(dst), "l"(m), "r"(bar), "r"(c0), "r"(c1), "r"(c2), "r"(bytes) : "memory");
}
__device__ __forceinline__ void tma_ld3_hint_w(uint32_t dst, const CUtensorMap* m, int c0, int c1, int c2, uint32_t bar, uint64_t pol) {
  asm volatile(ELECT EXPECT("%2", "16384") "cp.async.bulk.tensor.3d.shared::cluster.global.mbarrier::complete_tx::bytes.L2::cache_hint"
               " [%0], [%1, {%3, %4, %5}], [%2], %6;\n}"
               ::"r"(dst), "l"(m), "r"(bar), "r"(c0), "r"(c1), "r"(c2), "l"(pol) : "memory");
}
__device__ __forceinline__ void tma_ld_wo_w(uint32_t dst, const CUtensorMap* m, int col, int grp, uint32_t bar) {
  asm volatile(ELECT EXPECT("%2", "16384") "cp.async.bulk.tensor.5d.shared::cluster.global.mbarrier::complete_tx::bytes [%0], [%1, {%3, 0, 0, 0, %4}], [%2];\n"
               "@p cp.async.bulk.tensor.5d.shared::cluster.global.mbarrier::complete_tx::bytes [%5], [%1, {%6, 0, 0, 0, %4}], [%2];\n}"
               ::"r"(dst), "l"(m), "r"(bar), "r"(col), "r"(grp), "r"(dst + 8192), "r"(col + 64) : "memory");
}
__device__ __forceinline__ void mbar_arrive8_w(uint32_t bar) {
  asm volatile(ELECT "mbarrier.arrive.shared::cta.b64 _, [%0], 8;\n}" ::"r"(bar) : "memory");
}
__device__ __forceinline__ void bulk_commit() { asm volatile("cp.async.bulk.commit_group;" ::: "memory"); }
template <int N> __device__ __forceinline__ void bulk_wait_read() { asm volatile("cp.async.bulk.wait_group.read %0;" ::"n"(N) : "memory"); }
__device__ __forceinline__ void wg_fence() { asm volatile("wgmma.fence.sync.aligned;" ::: "memory"); }
__device__ __forceinline__ void wg_commit() { asm volatile("wgmma.commit_group.sync.aligned;" ::: "memory"); }
template <int N> __device__ __forceinline__ void wg_wait() { asm volatile("wgmma.wait_group.sync.aligned %0;" ::"n"(N) : "memory"); }
__device__ __forceinline__ void fence_async_smem() { asm volatile("fence.proxy.async.shared::cta;" ::: "memory"); }
__device__ __forceinline__ void bar_sync(int id, int n) { asm volatile("bar.sync %0, %1;" ::"r"(id), "r"(n) : "memory"); }
template <int N> __device__ __forceinline__ void reg_fence(float (&a)[N]) {
#pragma unroll
  for (int i = 0; i < N; i++) asm volatile("" : "+f"(a[i])::"memory");
}
template <int N> __device__ __forceinline__ void reg_fence(uint32_t (&a)[N]) {
#pragma unroll
  for (int i = 0; i < N; i++) asm volatile("" : "+r"(a[i])::"memory");
}
__device__ __forceinline__ float ex2(float x) { float y; asm("ex2.approx.ftz.f32 %0, %1;" : "=f"(y) : "f"(x)); return y; }
__device__ __forceinline__ uint32_t pack_bf16(float lo, float hi) {
  uint32_t r; asm("cvt.rn.bf16x2.f32 %0, %1, %2;" : "=r"(r) : "f"(hi), "f"(lo)); return r;
}
__device__ __forceinline__ void stsm4(uint32_t a, uint32_t r0, uint32_t r1, uint32_t r2, uint32_t r3) {
  asm volatile("stmatrix.sync.aligned.m8n8.x4.shared.b16 [%0], {%1, %2, %3, %4};" ::"r"(a), "r"(r0), "r"(r1), "r"(r2), "r"(r3) : "memory");
}
__device__ __forceinline__ void stsm4t(uint32_t a, uint32_t r0, uint32_t r1, uint32_t r2, uint32_t r3) {
  asm volatile("stmatrix.sync.aligned.m8n8.x4.trans.shared.b16 [%0], {%1, %2, %3, %4};" ::"r"(a), "r"(r0), "r"(r1), "r"(r2), "r"(r3) : "memory");
}
__device__ __forceinline__ void ldsm4(uint32_t a, uint32_t& r0, uint32_t& r1, uint32_t& r2, uint32_t& r3) {
  asm volatile("ldmatrix.sync.aligned.m8n8.x4.shared.b16 {%0, %1, %2, %3}, [%4];" : "=r"(r0), "=r"(r1), "=r"(r2), "=r"(r3) : "r"(a) : "memory");
}
__device__ __forceinline__ void sts16(uint32_t a, uint32_t v) { asm volatile("st.shared.u16 [%0], %1;" ::"r"(a), "h"((uint16_t)v) : "memory"); }
__device__ __forceinline__ void mma16816(float& c0, float& c1, float& c2, float& c3, uint32_t a0, uint32_t a1, uint32_t a2, uint32_t a3,
                                         uint32_t b0, uint32_t b1) {
  asm volatile("mma.sync.aligned.m16n8k16.row.col.f32.bf16.bf16.f32 {%0, %1, %2, %3}, {%4, %5, %6, %7}, {%8, %9}, {%0, %1, %2, %3};"
               : "+f"(c0), "+f"(c1), "+f"(c2), "+f"(c3) : "r"(a0), "r"(a1), "r"(a2), "r"(a3), "r"(b0), "r"(b1));
}
__device__ __forceinline__ uint32_t sdesc(uint32_t addr, uint32_t lbo) { return (addr >> 4) + ((lbo >> 4) << 16); }
__device__ __forceinline__ uint64_t desc64(uint32_t lo, uint32_t hi) { uint64_t d; asm("mov.b64 %0, {%1, %2};" : "=l"(d) : "r"(lo), "r"(hi)); return d; }
__device__ __forceinline__ void dadd(uint64_t& d, uint32_t inc) {
  asm("{\n.reg .b32 l, h;\nmov.b64 {l, h}, %0;\nadd.u32 l, l, %1;\nmov.b64 %0, {l, h};\n}" : "+l"(d) : "r"(inc));
}

struct Ring {
  uint32_t slot, phase, xp;
  __device__ __forceinline__ void uniform() {
    slot = __shfl_sync(0xffffffffu, slot, 0); phase = __shfl_sync(0xffffffffu, phase, 0); xp = __shfl_sync(0xffffffffu, xp, 0);
  }
  __device__ __forceinline__ void next() { if (++slot == NS) { slot = 0; phase ^= 1; } }
  __device__ __forceinline__ void next_if(bool p) { slot += p; if (slot == NS) { slot = 0; phase ^= 1; } }
};
__device__ __forceinline__ uint32_t borrow(int ks, int n) {
  if (BORROW_ALT) return (ks & 1) && ks >= 3 && ks + 1 < n ? (~ks >> 1) & 1 : 2;
  const int k = ks + 1;
  return k >= 4 && !(k & 2) && k < n ? k & 1 : 2;
}

constexpr uint32_t Q_RANGES = NBETA * NH + P_EARLY * 5;
constexpr int TAIL_STEPS = (NBETA - P_EARLY) * 64, NRANGE = NCTA / 5;
struct Work { int kind, mode, k0, nsteps, range, beta, sub; };
struct Sched { uint16_t queue[Q_RANGES]; uint32_t piece[NRANGE + 1][4]; };
constexpr Sched make_sched() {
  Sched s{};
  int q = 0, a = 0;
  for (int pass = 0; pass < 2; pass++)
    for (int b = pass ? B_LATE : 0; b < NBETA; b++)
      for (int h = pass ? H_LATE : 0; h < (pass || b < B_LATE ? NH : H_LATE); h++) {
        if (a >= P_POS && (a - P_POS) % P_STRIDE == 0 && (a - P_POS) / P_STRIDE < P_EARLY)
          for (int col = 0; col < 5; col++) s.queue[q++] = 0x8000 | col << 8 | (a - P_POS) / P_STRIDE;
        s.queue[q++] = b << 5 | h;
        a++;
      }
  constexpr int B[NRANGE + 1] = {RANGE_TABLE};
  constexpr int ORD[NRANGE] = {RANGE_ORDER};
  for (int g = 0; g <= NRANGE; g++) {
    int n = 0;
    if (g < NRANGE) {
      const int r = ORD[g];
      for (int pos = B[r]; pos < B[r + 1];) {
        const int te = (pos | 63) + 1, stop = B[r + 1] < te ? B[r + 1] : te, mode = pos & 63 ? 1 : stop == te ? 0 : 2;
        int f = 0;
        if (mode == 2) { f = 1; while (B[r + 1 + f] < te) f++; }
        s.piece[g][n++] = 1u << 30 | mode << 28 | (te - stop) << 22 | (stop - pos - 1) << 16 | r << 11 | f << 5 | (P_EARLY + (pos >> 6));
        pos = stop;
      }
    }
    for (; n < 4; n++) s.piece[g][n] = 2u << 30;
  }
  return s;
}
__constant__ Sched c_sched = make_sched();
__device__ __forceinline__ Work decode(uint32_t d) {
  Work w;
  w.kind = d >> 30; if (w.kind == 3) w.kind = 1;
  w.mode = (d >> 28) & 3; w.k0 = (d >> 22) & 63;
  if (w.kind == 0) { w.beta = (d >> 5) & 31; w.sub = d & 31; w.nsteps = DM / 64; }
  else { w.beta = d & 31; w.sub = (d >> 8) & 7; w.nsteps = ((d >> 16) & 63) + 1; }
  w.range = ((d >> 11) & 31) * 5 + w.sub;
  return w;
}

__device__ __forceinline__ bool reached(const unsigned* cnt, unsigned target) {
  unsigned v;
  asm volatile("ld.acquire.gpu.global.u32 %0, [%1];" : "=r"(v) : "l"(cnt) : "memory");
  return (int)(v - target) >= 0;
}
__device__ __forceinline__ void wait_count(const unsigned* cnt, unsigned target) {
  unsigned n = 0;
  while (!__all_sync(0xffffffffu, reached(cnt, target))) { if (++n > (1u << 24)) __trap(); }
}
__device__ __forceinline__ uint32_t lds(uint32_t a) { uint32_t v; asm volatile("ld.volatile.shared.u32 %0, [%1];" : "=r"(v) : "r"(a) : "memory"); return v; }

#define TRACE(u, e)
#define T3(u, e)
#define T2C(u, e)
#define T2P(u, r, e)
#define TCLK(k)
#define TRACE_P(u, e)
#define TRACE_IN(u, e)

struct Ctx {
  uint32_t sb;
  int wg, warp;
  uint32_t mqk, mpv;
  bool lead;
  int src;
};
template <int N> __device__ __forceinline__ uint32_t dhi(uint32_t lo) { return 0x40000040u + (lo >> (26 + N)); }
template <int N> __device__ __forceinline__ uint64_t full_desc(uint32_t addr, uint32_t slot) { return desc64(addr >> 4, dhi<N>(slot)); }
__device__ __forceinline__ void release(const Ctx& c, uint32_t slot) {
  if (c.lead) mbar_arrive(c.sb + BAR_EMPTY + slot * 8);
}
__device__ __forceinline__ uint32_t acquire(const Ctx& c, Ring& r) {
  const uint32_t s = r.slot;
  mbar_wait_w(c.sb + BAR_FULL + s * 8, r.phase);
  r.next();
  return s;
}
__device__ __forceinline__ void mbar_wait2_w(uint32_t b0, uint32_t p0, uint32_t b1, uint32_t p1) {
  uint32_t n = 0;
  while (!__all_sync(0xffffffffu, mbar_try(b0, p0) & mbar_try(b1, p1))) {
    if (++n > (1u << 22)) __trap();
  }
}
__device__ __forceinline__ void mbar_wait3_w(uint32_t b0, uint32_t p0, uint32_t b1, uint32_t p1, uint32_t b2, uint32_t p2) {
  uint32_t n = 0;
  while (!__all_sync(0xffffffffu, mbar_try(b0, p0) & mbar_try(b1, p1) & mbar_try(b2, p2))) {
    if (++n > (1u << 22)) __trap();
  }
}
__device__ __forceinline__ void acquire2(const Ctx& c, Ring& r, uint32_t& s0, uint32_t& s1) {
  const uint32_t p0 = r.phase;
  s0 = r.slot; r.next(); s1 = r.slot;
  mbar_wait2_w(c.sb + BAR_FULL + s0 * 8, p0, c.sb + BAR_FULL + s1 * 8, r.phase);
  r.next();
}
__device__ __forceinline__ void staged(const Ctx& c, int part) {
  fence_async_smem();
  __syncwarp();
  mbar_arrive_warp(c.sb + BAR_STG + c.wg * 16 + part * 8);
}

template <int WG, bool FIRST, int H>
__device__ __forceinline__ void proj_half(const Ctx& c, float (&acc)[64], uint32_t w, uint32_t x) {
  uint64_t a = full_desc<0>(c.sb + (WG ? w : x) * SLOT + H * 8192, x);
  uint64_t b = WG ? full_desc<1>(c.sb + x * SLOT, x) : desc64(sdesc(c.sb + w * SLOT, 8192), dhi<1>(x));
  wg_fence();
  if (WG) { if (FIRST) wgmma_proj96_init(acc, a, b, 0); else wgmma_proj96(acc, a, b, 1); }
  else { if (FIRST) wgmma_proj_init(acc, a, b, 0); else wgmma_proj(acc, a, b, 1); }
#pragma unroll
  for (int k = 1; k < 4; k++) { dadd(a, WG ? 128 : 2); dadd(b, WG ? 2 : 128); if (WG) wgmma_proj96(acc, a, b, 1); else wgmma_proj(acc, a, b, 1); }
  wg_commit();
}

__device__ __forceinline__ void proj_store16(uint32_t a, const float* f, float sc) {
  stsm4t(a, pack_bf16(f[0] * sc, f[1] * sc), pack_bf16(f[2] * sc, f[3] * sc), pack_bf16(f[4] * sc, f[5] * sc), pack_bf16(f[6] * sc, f[7] * sc));
}

__device__ __forceinline__ uint32_t stage_off(const Ctx& c) {
  const int lane = lane_now(), mi = lane >> 3, r8 = lane & 7;
  return ((mi >> 1) * 8 + r8) * 128 + (((2 * c.warp + (mi & 1)) ^ r8) << 4);
}
__device__ __forceinline__ uint32_t q3_swz(uint32_t r8) { return ((r8 & 3) << 1) | (r8 >> 2); }
template <int H>
__device__ __forceinline__ void stage_t2(const Ctx& c, const float (&a)[64], float sc) {
  const uint32_t base = c.sb + QBUF_OFF + 2 * 16384 + H * 8192 + stage_off(c);
#pragma unroll
  for (int jj = 0; jj < 4; jj++) proj_store16(base + jj * 2048, &a[jj * 8], sc);
}
template <int H, bool IS_Q>
__device__ __forceinline__ void stage_t3(const Ctx& c, const float (&a)[64], float sc) {
  const uint32_t off = stage_off(c), r8 = (off >> 7) & 7;
  const uint32_t t3 = c.sb + QBUF_OFF + 3 * 16384 + H * 4096 + (IS_Q ? off ^ ((r8 ^ q3_swz(r8)) << 4) : off);
  proj_store16(t3, &a[32], sc);
  proj_store16(t3 + 2048, &a[40], sc);
}

template <bool TRANS>
__device__ __forceinline__ void add16(uint32_t a, float* f) {
  uint32_t r[4];
  if (TRANS) asm volatile("ldmatrix.sync.aligned.m8n8.x4.trans.shared.b16 {%0, %1, %2, %3}, [%4];"
                          : "=r"(r[0]), "=r"(r[1]), "=r"(r[2]), "=r"(r[3]) : "r"(a) : "memory");
  else ldsm4(a, r[0], r[1], r[2], r[3]);
#pragma unroll
  for (int i = 0; i < 4; i++) { f[2 * i] += __uint_as_float(r[i] << 16); f[2 * i + 1] += __uint_as_float(r[i] & 0xffff0000u); }
}

__device__ __forceinline__ void trace_dump(const Ctx& c) {
}
struct RowSum { float l0, l1; };
__device__ __forceinline__ const char* o_addr(uint32_t item, int row) {
  const int lane = lane_now();
  return reinterpret_cast<const char*>(g_o) + ((item * (2 * SQ) + row) * 128 + (lane >> 2) * 128 + (lane & 3) * 16);
}
template <int MODE, int I0 = 0, int NI = 4>
__device__ __forceinline__ void o_emit(const char* p, const float (&o)[64], float inv) {
#pragma unroll
  for (int i = I0; i < I0 + NI; i++) {
    uint32_t q[4];
#pragma unroll
    for (int j = 0; j < 4; j++) {
      const float* f = &o[16 * i + 4 * j];
      q[j] = MODE == 2 ? pack_bf16((f[0] + f[2]) * inv, (f[1] + f[3]) * inv) : pack_bf16(f[2 * MODE] * inv, f[2 * MODE + 1] * inv);
    }
    asm volatile("st.global.v4.b32 [%0], {%1, %2, %3, %4};"
                 ::"l"(p + (i >> 1) * (SQ * 128) + (i & 1) * 64), "r"(q[0]), "r"(q[1]), "r"(q[2]), "r"(q[3]) : "memory");
  }
}
__device__ __forceinline__ void o_done(const Ctx& c) {
  __syncwarp();
  mbar_arrive_warp(c.sb + BAR_OUT);
  __syncwarp();
}
template <int WG, int PART>
__device__ __forceinline__ void o_first(const Ctx& c, uint32_t item, const float (&o)[64], const RowSum& inv) {
  constexpr int N = (PACK_EARLY >> (4 * WG)) & 15, B = PART ? N : 0, E = PART ? 8 : N;
  const char* p = o_addr(item, WG ? 192 + 8 * c.warp : 16 * c.warp);
  if constexpr (B < 4) o_emit<WG ? 2 : 0, B, (E < 4 ? E : 4) - B>(p, o, inv.l0);
  if constexpr (!WG && E > 4) o_emit<1, (B > 4 ? B : 4) - 4, E - (B > 4 ? B : 4)>(p + 1024, o, inv.l1);
}
template <int K0, int K1>
__device__ __forceinline__ void o_piece(const Ctx& c, const char* p, int k, const float (&o)[64], const RowSum& inv) {
  constexpr int NI = 8 / O_STEPS, M = K0 * NI / 4;
  if constexpr (K1 - K0 == 1) {
    o_emit<M, K0 * NI % 4, NI>(p + M * 1024, o, M ? inv.l1 : inv.l0);
    if (K1 == O_STEPS) o_done(c);
  } else {
    if (k <= (K0 + K1) / 2) o_piece<K0, (K0 + K1) / 2>(c, p, k, o, inv); else o_piece<(K0 + K1) / 2, K1>(c, p, k, o, inv);
  }
}
template <int WG>
__device__ __forceinline__ void o_second(const Ctx& c, uint32_t item, int k, float (&o)[64], const RowSum& inv) {
  reg_fence(o);
  o_piece<0, O_STEPS>(c, o_addr(item, 64 + 64 * WG + 16 * c.warp), k, o, inv);
}
template <int WG>
__device__ __forceinline__ void release_q(const Ctx& c) {
#pragma unroll
  for (int t = 0; t < 2; t++)
    if (c.lead) asm volatile("mbarrier.arrive.shared::cta.b64 _, [%0], 2;" ::"r"(c.sb + BAR_EMPTY + (NS + 2 * WG + t) * 8) : "memory");
  __syncwarp();
}
struct Slots { uint32_t w, x, o, po; };
template <int WG>
__device__ __forceinline__ void acc_fence(float (&a)[64]) {
#pragma unroll
  for (int i = 0; i < (WG ? 48 : 64); i++) asm volatile("" : "+f"(a[i])::"memory");
}
template <int WG>
__device__ __forceinline__ void begin_acquire(const Ctx& c, Ring& r, Slots& h, bool wait) {
  const uint32_t s0 = r.slot, p0 = r.phase, f = c.sb + BAR_FULL;
  r.next();
  const uint32_t p1 = r.phase;
  h.w = r.slot; r.next();
  h.x = WG ? r.slot : s0; h.o = WG ? s0 : r.slot; h.po = r.phase;
  if (wait) { if (WG) mbar_wait3_w(f + s0 * 8, p0, f + h.w * 8, p1, f + h.x * 8, r.phase); else mbar_wait2_w(f + s0 * 8, p0, f + h.w * 8, p1); }
  r.next();
}
template <int WG>
__device__ __forceinline__ void proj_begin(const Ctx& c, Ring& r, float (&a0)[64], Slots& h, bool wait) {
  begin_acquire<WG>(c, r, h, wait);
  proj_half<WG, true, 0>(c, a0, h.w, h.x);
  if (WG) release(c, h.o);
}
template <int WG>
__device__ __forceinline__ void proj_main(const Ctx& c, Ring& r, float (&a0)[64], float (&a1)[64], Slots& h, int n, int unit,
                                          uint32_t item, int nq, float (&o1)[64], const RowSum& inv) {
  constexpr bool DEEP = (PDEPTH >> WG) & 1;
  T2C(unit, 3);
  int ks = 1;
#pragma unroll 1
  do {
    const Slots p = h;
    const uint32_t b = borrow(ks, n), tile = NS + (WG ? 3 - b : b), f = c.sb + BAR_FULL;
    const uint32_t s0 = b != 2 ? tile : r.slot, p0 = b != 2 ? (r.xp >> b) & 1 : r.phase;
    r.next_if(b == 2);
    const uint32_t p1 = r.phase;
    h.w = r.slot; r.next();
    const uint32_t s2 = b != 2 ? tile : r.slot;
    h.po = b != 2 ? p0 : r.phase;
    r.next_if(b == 2);
    r.xp ^= 1 << b;
    h.x = WG ? s2 : s0; h.o = WG ? s0 : s2;
    mbar_wait3_w(f + s0 * 8, p0, f + h.w * 8, p1, f + (WG ? s2 : p.o) * 8, WG ? h.po : p.po);
    if (ks < 10) T2C(unit, ks * 4);
    if (DEEP) {
      proj_half<WG, false, 0>(c, a0, h.w, h.x);
      release(c, WG ? h.o : p.o);
      if (ks < 10) T2C(unit, ks * 4 + 1);
      wg_wait<1>();
      if (ks < 10) T2C(unit, ks * 4 + 2);
      release(c, p.x); release(c, p.w);
    } else {
      release(c, WG ? h.o : p.o);
      wg_wait<0>();
      release(c, p.x); release(c, p.w);
      if (ks < 10) T2C(unit, ks * 4 + 1);
      proj_half<WG, false, 0>(c, a0, h.w, h.x);
      if (ks < 10) T2C(unit, ks * 4 + 2);
    }
    proj_half<WG, false, 1>(c, a1, h.w, h.x);
    if (ks < 10) T2C(unit, ks * 4 + 3);
    if (ks <= nq) o_second<WG>(c, item, ks, o1, inv);
  } while (++ks != n);
  {
    const uint32_t e0 = c.sb + BAR_EMPTY + (NS + 3 * WG) * 8, e1 = c.sb + BAR_EMPTY + (NS + 1 + WG) * 8;
    const uint32_t p0 = (r.xp ^ unit ^ 1) & 1, p1 = ((r.xp >> 1) ^ unit ^ 1) & 1;
    if (WG) mbar_wait2_w(e0, p0, e1, p1); else mbar_wait3_w(e0, p0, e1, p1, c.sb + BAR_FULL + h.o * 8, h.po);
  }
  if (!WG) release(c, h.o);
  wg_wait<1>();
  acc_fence<WG>(a0);
}
template <int WG>
__device__ __forceinline__ void proj_end(const Ctx& c, float (&a1)[64], const Slots& h) {
  wg_wait<0>();
  acc_fence<WG>(a1);
  release(c, h.x); release(c, h.w);
}
__device__ __forceinline__ uint32_t get_desc(const Ctx& c, int i) {
  uint32_t d;
  mbar_wait_w(c.sb + BAR_DESC, (i - 1) & 1);
  asm volatile("ld.volatile.shared.u32 %0, [%1];" : "=r"(d) : "r"(c.sb + DESC_OFF + (i & 3) * 4) : "memory");
  return __shfl_sync(0xffffffffu, d, 0);
}

__device__ __forceinline__ float quad_max(float x) {
  x = fmaxf(x, __shfl_xor_sync(0xffffffffu, x, 1));
  return fmaxf(x, __shfl_xor_sync(0xffffffffu, x, 2));
}
__device__ __forceinline__ float quad_sum(float x) {
  x += __shfl_xor_sync(0xffffffffu, x, 1);
  return x + __shfl_xor_sync(0xffffffffu, x, 2);
}
template <bool SP, bool FIRST>
__device__ __forceinline__ void exps(const Ctx& c, const float (&s)[32], uint32_t (&p)[SP ? 8 : 16], RowSum& st) {
  if constexpr (SP) {
    uint32_t q[8];
    float t;
#pragma unroll
    for (int j = 0; j < 8; j++) {
      const float e0 = ex2(s[4 * j] + s[4 * j + 2]), e1 = ex2(s[4 * j + 1] + s[4 * j + 3]);
      if (j == 0) t = e0 + e1; else t += e0 + e1;
      q[j] = pack_bf16(e0, e1);
    }
    const bool odd = c.src & 2;
#pragma unroll
    for (int g = 0; g < 4; g++) {
      p[2 * g] = __shfl_sync(0xffffffffu, odd ? q[2 * g + 1] : q[2 * g], c.src);
      p[2 * g + 1] = __shfl_sync(0xffffffffu, odd ? q[2 * g] : q[2 * g + 1], c.src ^ 1);
    }
    st.l0 = FIRST ? t : st.l0 + t;
  } else {
    float t0, t1;
#pragma unroll
    for (int j = 0; j < 8; j++) {
      const float e0 = ex2(s[4 * j]), e1 = ex2(s[4 * j + 1]), e2 = ex2(s[4 * j + 2]), e3 = ex2(s[4 * j + 3]);
      if (j == 0) { t0 = e0 + e1; t1 = e2 + e3; } else { t0 += e0 + e1; t1 += e2 + e3; }
      p[2 * j] = pack_bf16(e0, e1);
      p[2 * j + 1] = pack_bf16(e2, e3);
    }
    st.l0 = FIRST ? t0 : st.l0 + t0;
    st.l1 = FIRST ? t1 : st.l1 + t1;
  }
}
template <bool SP>
__device__ __forceinline__ bool finish_sums(RowSum& st) {
  const float a = quad_sum(st.l0), b = SP ? a : quad_sum(st.l1);
  st.l0 = __fdividef(1.f, a); st.l1 = __fdividef(1.f, b);
  return !DEV_HALF && !(a >= SUM_LO && a <= SUM_HI && b >= SUM_LO && b <= SUM_HI);
}
template <bool SP, bool INIT, int SITE, bool COMMIT = true>
__device__ __forceinline__ void issue_qk(const Ctx& c, float (&s)[32], const uint32_t (&qs)[16], uint32_t dq, uint32_t dk) {
  uint64_t a = desc64(dq, dhi<SITE & 1>(dk)), b = desc64(dk, dhi<1 - (SITE & 1)>(dk));
  if (SP) {
    if (INIT) wgmma_qk_sp_init(s, qs[0], qs[1], qs[2], qs[3], b, 0, c.mqk); else wgmma_qk_sp(s, qs[0], qs[1], qs[2], qs[3], b, 0, c.mqk);
#pragma unroll
    for (int k = 1; k < 4; k++) { dadd(b, k == 2 ? 508 : 4); wgmma_qk_sp(s, qs[4 * k], qs[4 * k + 1], qs[4 * k + 2], qs[4 * k + 3], b, 1, c.mqk); }
  } else {
    if (INIT) wgmma_qk_init(s, a, b, 0); else wgmma_qk(s, a, b, 0);
#pragma unroll
    for (int k = 1; k < 8; k++) { dadd(a, k == 4 ? 506 : 2); dadd(b, k == 4 ? 506 : 2); wgmma_qk(s, a, b, 1); }
  }
  if (COMMIT) wg_commit();
}
template <bool SP, bool ACC, int SITE, bool SPLIT = false>
__device__ __forceinline__ void issue_pv(const Ctx& c, float (&o)[64], const uint32_t (&p)[SP ? 8 : 16], uint32_t dv) {
  uint64_t b = desc64(dv, dhi<SITE & 1>(dv));
  if constexpr (SP) {
    if (ACC) wgmma_pv_sp(o, p[0], p[1], p[2], p[3], b, 1, c.mpv); else wgmma_pv_sp_init(o, p[0], p[1], p[2], p[3], b, 0, c.mpv);
    if (SPLIT) wg_commit();
    dadd(b, 256);
    wgmma_pv_sp(o, p[4], p[5], p[6], p[7], b, 1, c.mpv);
  } else {
    if (ACC) wgmma_pv(o, p[0], p[1], p[2], p[3], b, 1); else wgmma_pv_init(o, p[0], p[1], p[2], p[3], b, 0);
#pragma unroll
    for (int k = 1; k < 4; k++) { dadd(b, 128); wgmma_pv(o, p[4 * k], p[4 * k + 1], p[4 * k + 2], p[4 * k + 3], b, 1); }
  }
  wg_commit();
}
__device__ __forceinline__ void stage_rows(const Ctx& c, uint32_t tile_addr, const float (&o)[64], float sc) {
  const int lane = lane_now(), mi = lane >> 3, r8 = lane & 7;
  const uint32_t row_addr = tile_addr + (16 * c.warp + (mi & 1) * 8 + r8) * 128;
#pragma unroll
  for (int jj = 0; jj < 8; jj++) {
    const int b = jj * 8;
    stsm4(row_addr + (jj >> 2) * 8192 + (((((2 * jj) & 7) + (mi >> 1)) ^ r8) << 4),
          pack_bf16(o[b] * sc, o[b + 1] * sc), pack_bf16(o[b + 2] * sc, o[b + 3] * sc),
          pack_bf16(o[b + 4] * sc, o[b + 5] * sc), pack_bf16(o[b + 6] * sc, o[b + 7] * sc));
  }
}

__device__ __forceinline__ void redo_tile(const Ctx& c, uint32_t q_addr, uint32_t half, const __nv_bfloat16* kp, const __nv_bfloat16* vp,
                                          uint32_t item, int row) {
  float o[64];
  const int lane = lane_now(), g = lane >> 2, cc = lane & 3, mi = lane >> 3, r8 = lane & 7;
  const uint32_t qa = q_addr + (half == 4096 ? 8 * c.warp + r8 : 16 * c.warp + (mi & 1) * 8 + r8) * 128, swz = half == 4096 ? q3_swz(r8) : r8;
  const uint32_t* kq = reinterpret_cast<const uint32_t*>(kp + g * DH) + cc;
  const unsigned short* vq = reinterpret_cast<const unsigned short*>(vp + 2 * cc * DH) + g;
  float m0 = -INFINITY, m1 = -INFINITY, l0 = 0.f, l1 = 0.f;
#pragma unroll
  for (int i = 0; i < 64; i++) o[i] = 0.f;
#pragma unroll 1
  for (int kb = 0; kb < SK / 16; kb++) {
    float z[8] = {0.f, 0.f, 0.f, 0.f, 0.f, 0.f, 0.f, 0.f};
#pragma unroll 2
    for (int kk = 0; kk < 8; kk++) {
      uint32_t a0, a1, a2, a3;
      ldsm4(qa + (kk >> 2) * half + ((((kk & 3) * 2 + (mi >> 1)) ^ swz) << 4), a0, a1, a2, a3);
      const uint32_t* kr = kq + kb * (16 * DH / 2) + kk * 8;
      mma16816(z[0], z[1], z[2], z[3], a0, a1, a2, a3, __ldg(kr), __ldg(kr + 4));
      mma16816(z[4], z[5], z[6], z[7], a0, a1, a2, a3, __ldg(kr + 8 * DH / 2), __ldg(kr + 8 * DH / 2 + 4));
    }
    const float n0 = fmaxf(m0, quad_max(fmaxf(fmaxf(z[0], z[1]), fmaxf(z[4], z[5]))));
    const float n1 = fmaxf(m1, quad_max(fmaxf(fmaxf(z[2], z[3]), fmaxf(z[6], z[7]))));
    const float al0 = ex2(m0 - n0), al1 = ex2(m1 - n1);
    m0 = n0; m1 = n1;
#pragma unroll
    for (int i = 0; i < 8; i++) z[i] = ex2(z[i] - ((i & 2) ? n1 : n0));
    l0 = l0 * al0 + (z[0] + z[1]) + (z[4] + z[5]);
    l1 = l1 * al1 + (z[2] + z[3]) + (z[6] + z[7]);
    const uint32_t a0 = pack_bf16(z[0], z[1]), a1 = pack_bf16(z[2], z[3]), a2 = pack_bf16(z[4], z[5]), a3 = pack_bf16(z[6], z[7]);
    const unsigned short* vr = vq + kb * (16 * DH);
#pragma unroll
    for (int nb = 0; nb < 16; nb++) {
      o[4 * nb] *= al0; o[4 * nb + 1] *= al0; o[4 * nb + 2] *= al1; o[4 * nb + 3] *= al1;
      const uint32_t b0 = __ldg(vr + nb * 8) | ((uint32_t)__ldg(vr + nb * 8 + DH) << 16);
      const uint32_t b1 = __ldg(vr + nb * 8 + 8 * DH) | ((uint32_t)__ldg(vr + nb * 8 + 9 * DH) << 16);
      mma16816(o[4 * nb], o[4 * nb + 1], o[4 * nb + 2], o[4 * nb + 3], a0, a1, a2, a3, b0, b1);
    }
  }
  const char* p = o_addr(item, row);
  o_emit<0>(p, o, __fdividef(1.f, quad_sum(l0)));
  o_emit<1>(half == 4096 ? p : p + 1024, o, __fdividef(1.f, quad_sum(l1)));
}

template <bool SPA, bool SPB, int SITE, int ID>
__device__ __forceinline__ void batch(const Ctx& c, float (&s)[32], const uint32_t (&qs)[16], uint32_t dq, uint32_t dk, float (&ob)[64],
                                      uint32_t (&pb)[SPB ? 8 : 16], uint32_t dv) {
  if constexpr (SPA) {
    reg_fence(pb);
    wg_fence();
    issue_pv<SPB, true, ID>(c, ob, pb, dv);
    issue_qk<SPA, false, ID>(c, s, qs, dq, dk);
  } else {
    constexpr bool EARLY = ((QK_EARLY_MASK >> (SITE + (SPB ? 2 : 0))) & 1) != 0;
    if (!EARLY) reg_fence(pb);
    wg_fence();
    issue_qk<SPA, false, ID, !SPB>(c, s, qs, dq, dk);
    if (EARLY) { reg_fence(pb); wg_fence(); }
    issue_pv<SPB, true, ID, SPB>(c, ob, pb, dv);
  }
}

template <bool SP0>
__device__ __forceinline__ bool attention(Ctx c, Ring& r, int unit, uint32_t& d, const float (&a0)[64], float (&o0)[64], float (&o1)[64],
                                          RowSum& st0, RowSum& st1, const Slots& h, uint32_t item) {
  constexpr bool SP1 = false;
  if (SP0) { c.mqk = META_QK + (d >> 28); c.mpv = META_PV + (d >> 28); asm volatile("" : "+r"(c.mqk), "+r"(c.mpv)); }
  if (SP0) { const int lane = lane_now(); c.src = (lane & 28) | ((lane & 1) << 1) | ((lane >> 1) & 1); }
  float s[32];
  uint32_t p0[SP0 ? 8 : 16], p1[16];
  const uint32_t q0a = c.sb + QBUF_OFF + (SP0 ? 3 : 0) * 16384, q1a = c.sb + QBUF_OFF + (SP0 ? 2 : 1) * 16384;
  const uint32_t dq0 = sdesc(q0a, 0), dq1 = sdesc(q1a, 0);
  uint32_t sk, sv, sn;
  uint32_t qs[16];
  T2C(unit, 40);
  if (SP0) {
    stage_t3<0, true>(c, a0, SM_C);
    stage_t2<0>(c, a0, SM_C);
    T2C(unit, 41);
    proj_end<1>(c, o0, h);
    T2C(unit, 42);
    stage_t3<1, true>(c, o0, SM_C);
    stage_t2<1>(c, o0, SM_C);
    sk = acquire(c, r);
    fence_async_smem();
    T2C(unit, 43);
    bar_sync(1, LAG_BAR & 14 ? 256 : 128);
    const int lane = lane_now(), g = lane >> 2, cc = lane & 3;
    const uint32_t qa = q0a + (8 * c.warp + g) * 128 + (cc & 1) * 8;
#pragma unroll
    for (int k = 0; k < 8; k++)
      asm volatile("ld.shared.v2.u32 {%0, %1}, [%2];" : "=r"(qs[2 * k]), "=r"(qs[2 * k + 1])
                   : "r"(qa + (k >> 2) * 4096 + ((((k & 3) * 2 + (cc >> 1)) ^ q3_swz(g)) << 4)) : "memory");
    TRACE(unit, 2);
    T2C(unit, 44);
    float s1[32];
    wg_fence();
    issue_qk<SP1, true, 1>(c, s1, qs, dq1, sdesc(c.sb + sk * SLOT, 0));
    reg_fence(qs);
    wg_fence();
    issue_qk<SP0, true, 0>(c, s, qs, dq0, sdesc(c.sb + sk * SLOT, 0));
    T2C(unit, 45);
    acquire2(c, r, sv, sn);
    wg_wait<1>();
    reg_fence(s1);
    T2C(unit, 47);
    exps<SP1, true>(c, s1, p1, st1);
    reg_fence(p1);
    wg_fence();
    issue_pv<SP1, false, 1>(c, o1, p1, sdesc(c.sb + sv * SLOT, 8192));
    if (LAG_BAR & 1) asm volatile("bar.arrive 4, 256;" ::: "memory");
    wg_wait<1>();
    reg_fence(s);
    T2C(unit, 48);
    release(c, sk);
    sk = sn;
    exps<SP0, true>(c, s, p0, st0);
    reg_fence(p0);
    wg_fence();
    issue_pv<SP0, false, 0>(c, o0, p0, sdesc(c.sb + sv * SLOT, 8192));
    issue_qk<SP0, false, 2>(c, s, qs, dq0, sdesc(c.sb + sk * SLOT, 0));
    T2C(unit, 49);
    sn = acquire(c, r);
    T2C(unit, 50);
    wg_wait<0>();
    reg_fence(s);
  } else {
    float s1[32];
    stage_rows(c, q0a, a0, SM_C);
    sk = acquire(c, r);
    fence_async_smem();
    T2C(unit, 41);
    proj_end<0>(c, o0, h);
    TRACE(unit, 2);
    T2C(unit, 42);
    __syncwarp();
    wg_fence();
    issue_qk<SP0, true, 0>(c, s, qs, dq0, sdesc(c.sb + sk * SLOT, 0));
    if (LAG_BAR & 8) asm volatile("bar.arrive 1, 256;" ::: "memory");
    T2C(unit, 43);
    reg_fence(o0);
    stage_rows(c, q1a, o0, SM_C);
    fence_async_smem();
    __syncwarp();
    T2C(unit, 44);
    if (LAG_BAR & 4) asm volatile("bar.arrive 1, 256;" ::: "memory");
    wg_fence();
    issue_qk<SP1, true, 1>(c, s1, qs, dq1, sdesc(c.sb + sk * SLOT, 0));
    if (LAG_BAR & 2) asm volatile("bar.arrive 1, 256;" ::: "memory");
    T2C(unit, 45);
    acquire2(c, r, sv, sn);
    wg_wait<1>();
    reg_fence(s);
    T2C(unit, 47);
    exps<SP0, true>(c, s, p0, st0);
    reg_fence(p0);
    wg_fence();
    issue_qk<SP0, false, 2>(c, s, qs, dq0, sdesc(c.sb + sn * SLOT, 0));
    issue_pv<SP0, false, 0>(c, o0, p0, sdesc(c.sb + sv * SLOT, 8192));
    wg_wait<2>();
    reg_fence(s1);
    T2C(unit, 48);
    release(c, sk);
    sk = sn;
    exps<SP1, true>(c, s1, p1, st1);
    reg_fence(p1);
    wg_fence();
    issue_pv<SP1, false, 1>(c, o1, p1, sdesc(c.sb + sv * SLOT, 8192));
    T2C(unit, 49);
    sn = acquire(c, r);
    if (LAG_BAR & 1) bar_sync(4, 256);
    T2C(unit, 50);
    wg_wait<1>();
    reg_fence(s);
  }
  TRACE_IN(unit, 4);
  T2C(unit, 51);
#pragma unroll 1
  for (int j = 1; j < 15; j++) {
    const uint32_t sv_prev = sv, sk_prev = sk;
    sv = sn;
    const uint32_t dv = sdesc(c.sb + sv * SLOT, 8192);
    reg_fence(p0);
    exps<SP0, false>(c, s, p0, st0);
    batch<SP1, SP0, 0, 3>(c, s, qs, dq1, sdesc(c.sb + sk * SLOT, 0), o0, p0, dv);
    sk = acquire(c, r);
    wg_wait<1>();
    reg_fence(s); reg_fence(p1);
    release(c, sv_prev); release(c, sk_prev);
    exps<SP1, false>(c, s, p1, st1);
    batch<SP0, SP1, 1, 4>(c, s, qs, dq0, sdesc(c.sb + sk * SLOT, 0), o1, p1, dv);
    sn = acquire(c, r);
    if (SP0) wg_wait<0>(); else wg_wait<1>();
    reg_fence(s);
  }
  TRACE_IN(unit, 5);
  T2C(unit + 1, 52);
  const uint32_t sv_prev = sv;
  sv = sn;
  const uint32_t dv = sdesc(c.sb + sv * SLOT, 8192);
  reg_fence(p0);
  exps<SP0, false>(c, s, p0, st0);
  batch<SP1, SP0, 0, 5>(c, s, qs, dq1, sdesc(c.sb + sk * SLOT, 0), o0, p0, dv);
  asm volatile("ld.volatile.shared.u32 %0, [%1];" : "=r"(d) : "r"(c.sb + DESC_OFF + ((unit + 1) & 3) * 4) : "memory");
  wg_wait<1>();
  reg_fence(s); reg_fence(p1);
  T2C(unit + 1, 53);
  release(c, sv_prev); release(c, sk);
  d = __shfl_sync(0xffffffffu, d, 0);
  const bool bad0 = finish_sums<SP0>(st0);
  exps<SP1, false>(c, s, p1, st1);
  reg_fence(p1);
  wg_fence();
  issue_pv<SP1, true, 2>(c, o1, p1, dv);
  T2C(unit + 1, 54);
  bool have = EARLY_BEG;
  if (EARLY_BEG) {
    Ring t = r;
#pragma unroll
    for (int k = 0; k < 2 + SP0; k++) { have &= mbar_test(c.sb + BAR_FULL + t.slot * 8, t.phase); t.next(); }
  }
  const bool bad = finish_sums<SP1>(st1) | bad0;
  if ((PACK_EARLY >> (4 * SP0)) & 15) {
    wg_wait<1>();
    reg_fence(o0);
    o_first<SP0, 0>(c, item, o0, st0);
  }
  T2C(unit + 1, 55);
  if (EARLY_BEG && d < (2u << 30) && !__all_sync(0xffffffffu, have)) { Ring t = r; Slots u; begin_acquire<SP0>(c, t, u, true); }
  T2C(unit + 1, 56);
  wg_wait<0>();
  reg_fence(o0); reg_fence(o1);
  T2C(unit + 1, 57);
  release(c, sv);
  return bad;
}
template <int WG>
__device__ __forceinline__ bool wg_any(bool p) {
  uint32_t any;
  asm volatile("{\n.reg .pred p, q;\nsetp.ne.u32 p, %1, 0;\nbar.red.or.pred q, %2, 128, p;\nselp.u32 %0, 1, 0, q;\n}"
               : "=r"(any) : "r"((uint32_t)p), "n"(2 + WG) : "memory");
  return __any_sync(0xffffffffu, any);
}

template <int WG>
__device__ __forceinline__ void consumer(Ctx c, const __nv_bfloat16* const* kv) {
  c.wg = WG;
  Ring r{0, 0, 0};
  bool bad;
  float a0[64], a1[64], o1[64];
  Slots h;
  RowSum inv0, inv1;
  uint32_t d = blockIdx.x, dc = 0;
  int i = 0, nq;
begin:
  proj_begin<WG>(c, r, a0, h, true);
  proj_half<WG, true, 1>(c, a1, h.w, h.x);
  nq = 0;
#pragma unroll
  for (int k = 0; k < 64; k++) asm volatile("" : "=f"(o1[k]));
  asm volatile("" : "=f"(inv1.l0), "=f"(inv1.l1));
  while (true) {
    TRACE(i, 0); TRACE(i, 6);
    proj_main<WG>(c, r, a0, a1, h, d >> 30 ? ((d >> 16) & 63) + 1 : DM / 64, i, dc, nq, o1, inv1);
    dc = d;
    TRACE(i, 1);
    if (d >> 30) goto out_tile;
    bad = attention<WG>(c, r, i, d, a0, a1, o1, inv0, inv1, h, dc);
    if (!EARLY_BEG || d >= (2u << 30)) break;
    Ring t = r;
    begin_acquire<WG>(c, t, h, false);
    proj_half<WG, true, 0>(c, a0, h.w, h.x);
    T2C(i + 1, 58);
    reg_fence(a1);
    o_first<WG, 1>(c, dc, a1, inv0);
    if (__builtin_expect(wg_any<WG>(bad), 0)) {
      wg_wait<0>();
      acc_fence<WG>(a0);
      goto redo;
    }
    r = t;
    T2C(i + 1, 1);
    proj_half<WG, true, 1>(c, a1, h.w, h.x);
    if (WG) release(c, h.o);
    release_q<WG>(c);
    T2C(i + 1, 2);
    nq = O_STEPS;
    TRACE(i, 3); TRACE(i, 7);
    i++;
  }
  if (wg_any<WG>(bad)) goto redo;
  release_q<WG>(c);
  o_first<WG, 1>(c, dc, a1, inv0);
#pragma unroll
  for (int k = 1; k <= O_STEPS; k++) o_second<WG>(c, dc, k, o1, inv1);
  T2C(i + 1, 58);
next:
  TRACE(i, 3); TRACE(i, 7);
  if ((d >> 30) != 2) {
    i++;
    r.uniform();
    goto begin;
  }
  trace_dump(c);
  return;
out_tile:
  proj_end<WG>(c, a1, h);
  if (((d >> 28) & 3) == 2) {
    const int lane = lane_now(), mi = lane >> 3, r8 = lane & 7;
    const uint32_t off = c.sb + (WG ? stage_off(c) : (16 * c.warp + (mi & 1) * 8 + r8) * 128);
#pragma unroll 1
    for (int k = (d >> 5) & 3; k > 0; k--) {
      uint32_t s0, s1;
      if (WG) { acquire2(c, r, s0, s1); release(c, s0); release(c, s1); }
#pragma unroll
      for (int t = 0; t < 2; t++) {
        const uint32_t sp = acquire(c, r), base = off + sp * SLOT;
        if (WG) {
#pragma unroll
          for (int jj = 0; jj < (t ? 2 : 4); jj++) {
            add16<true>(base + jj * 2048, &a0[(t * 4 + jj) * 8]);
            add16<true>(base + jj * 2048 + (t ? 4096 : 8192), &a1[(t * 4 + jj) * 8]);
          }
        } else {
#pragma unroll
          for (int jj = 0; jj < 8; jj++) add16<false>(base + (jj >> 2) * 8192 + (((((2 * jj) & 7) + (mi >> 1)) ^ r8) << 4), t ? &a1[jj * 8] : &a0[jj * 8]);
        }
        release(c, sp);
      }
      if (!WG) { acquire2(c, r, s0, s1); release(c, s0); release(c, s1); }
    }
  }
  if (WG) { stage_t3<0, false>(c, a0, 1.f); stage_t3<1, false>(c, a1, 1.f); }
  else stage_rows(c, c.sb + QBUF_OFF, a0, 1.f);
  staged(c, 0);
  if (WG) { stage_t2<0>(c, a0, 1.f); stage_t2<1>(c, a1, 1.f); }
  else stage_rows(c, c.sb + QBUF_OFF + 16384, a1, 1.f);
  staged(c, 1);
  d = get_desc(c, i + 1);
  TRACE(i, 2);
  goto next;
redo:
  {
    const size_t hoff = (size_t)(dc & 511) * (SK * DH);
    const int br = (dc >> 9) & 1;
#pragma unroll 1
    for (int part = 0; part < 2; part++) {
      const int t = WG ? 3 - part : part;
      redo_tile(c, c.sb + QBUF_OFF + t * 16384, t == 3 ? 4096 : 8192, kv[br] + hoff, kv[2 + br] + hoff, dc,
                t * 64 + (t == 3 ? 8 : 16) * c.warp);
    }
    o_done(c);
    release_q<WG>(c);
  }
  goto next;
}

template <bool SIMPLE>
__global__ void __launch_bounds__(384, 1) mha_fused_kernel(const __grid_constant__ Params P) {
  extern __shared__ __align__(1024) uint8_t smem_raw[];
  const uint32_t sbase = smem_u32(smem_raw);
  const int tid = threadIdx.x;
  const int wg = __shfl_sync(0xffffffffu, tid >> 7, 0);
  const int warp = __shfl_sync(0xffffffffu, (tid >> 5) & 3, 0);
  const int lane = tid & 31;
  const int cta = blockIdx.x;

  if (tid == 0) T3(15, 0);
  if (tid >= 256 && tid < 256 + 18) asm volatile("prefetch.tensormap [%0];" ::"l"(&P.x[0][0] + (tid - 256)) : "memory");
  if (tid == 0) {
    if ((sbase & 1023) || sbase + SMEM_BYTES > 0x40000) __trap();
    for (int i = 0; i < NSX; i++) { mbar_init(sbase + BAR_FULL + i * 8, 1); mbar_init(sbase + BAR_EMPTY + i * 8, 8); }
    for (int i = 0; i < 4; i++) mbar_init(sbase + BAR_STG + i * 8, 4);
    mbar_init(sbase + BAR_OUT, 8);
    mbar_init(sbase + BAR_DESC, 1);
    mbar_init(sbase + BAR_GO, 1);
    asm volatile("fence.mbarrier_init.release.cluster;" ::: "memory");
  }
  __syncthreads();

  if (wg == 2) {
    asm volatile("setmaxnreg.dec.sync.aligned.u32 %0;" ::"n"(REG_P));
    if (warp == 1) {
      const uint32_t qb = sbase + QBUF_OFF;
      const uint32_t ep = __shfl_sync(0xffffffffu, *(volatile unsigned*)&g_epoch + 1, 0);
      asm volatile("st.volatile.shared.u32 [%0], %1;" ::"r"(sbase + EPOCH_OFF), "r"(ep) : "memory");
      uint32_t dc = cta, qi = 0, piece = 0, na = 0;
      for (int i = 0; (dc >> 30) != 2; i++) {
        mbar_wait_w(sbase + BAR_GO, i & 1);
        if (TLB_WARM && (dc >> 30) == 0) asm volatile(ELECT "st.global.u32 [%0], 0;\n}" ::"l"(g_o + dc * (2 * SQ * 64)) : "memory");
        if (piece == 0) {
          if (lane == 0) {
            qi = atomicAdd(&g_next, 1);
            if (qi == (SIMPLE ? NBETA * (NH + 5) : Q_RANGES) - 1) { g_next = 0; g_epoch = ep; }
          }
          qi = __shfl_sync(0xffffffffu, qi, 0) + (SIMPLE ? gridDim.x : NCTA);
        }
        uint32_t d;
        if (qi < Q_RANGES) { d = c_sched.queue[qi]; if (d & 0x8000) d ^= (1u << 30) | (63u << 16) | 0x8000; }
        else if (SIMPLE) { const uint32_t t = qi - NBETA * NH; d = t < NBETA * 5 ? (1u << 30) | (63u << 16) | (t % 5) << 8 | t / 5 : 2u << 30; }
        else { const uint32_t e = qi - Q_RANGES, g = e / 5; d = c_sched.piece[g][piece++] | (e - g * 5) << 8; }
        if ((d >> 30) == 1) {
          const uint32_t ok = __ballot_sync(0xffffffffu, reached(&g_cnt[lane & 1][d & 31], ep * (lane & 1 ? NH - H_LATE : H_LATE)));
          if (!(ok & 2)) d |= ((d >> 22) & 63) >= 2 * H_LATE - O_STEPS ? (2u << 30) | 128 : 128;
          if (!(ok & 1) || (O_STEPS > 4 && ((d >> 16) & 63) < O_STEPS)) d |= 2u << 30;
        }
        asm volatile("st.volatile.shared.u32 [%0], %1;" ::"r"(sbase + DESC_OFF + ((i + 1) & 3) * 4), "r"(d) : "memory");
        __syncwarp();
        mbar_arrive_warp(sbase + BAR_DESC);
        const Work w = decode(dc);
        dc = d;
        if (w.kind == 0) {
          mbar_wait_w(sbase + BAR_OUT, na++ & 1);
          T3(i, 0); T3(i, 1);
          asm volatile(ELECT "red.release.gpu.global.add.u32 [%0], 1;\n}" ::"l"(&g_cnt[w.sub >= H_LATE][w.beta]) : "memory");
          T3(i, 2);
          continue;
        }
        const bool fin = w.mode != 1;
        uint64_t pol, pol2;
        asm volatile("createpolicy.fractional.L2::evict_first.b64 %0, 1.0;" : "=l"(pol));
        asm volatile("createpolicy.fractional.L2::evict_normal.b64 %0, 1.0;" : "=l"(pol2));
        if (!fin) pol = pol2;
        const CUtensorMap* m = fin ? P.out_st : P.o_st;
        const int c1 = fin ? (w.beta & 15) * SQ : 0;
        const int c2 = fin ? (w.beta >> 4) * (DM / 64) + w.sub * 2 : NBETA * 64 + w.range * 2;
        uint32_t pend = 0;
#pragma unroll 1
        for (int e = 0; e < 4; e++) {
          const int t = (ST_ORDER >> (4 * e)) & 3;
          mbar_wait_w(sbase + BAR_STG + (t ^ (t >> 1)) * 8, (i - na) & 1);
          tma_st3_hint_w(m + (t == 3), qb + t * 16384, 0, c1 + t * 64, c2, pol);
          bulk_commit();
          T2P(i + 1, 5, 2 * e);
          if (pend) {
            bulk_wait_read<1>();
            mbar_arrive8_w(pend);
            T2P(i + 1, 5, 2 * e - 1);
          }
          pend = sbase + BAR_EMPTY + (NS + t) * 8;
          if ((ST_NOW >> e) & 1) {
            bulk_wait_read<0>();
            mbar_arrive8_w(pend);
            pend = 0;
            T2P(i + 1, 5, 2 * e + 1);
          }
        }
        T3(i, 0);
        asm volatile("cp.async.bulk.wait_group 0;" ::: "memory");
        T3(i, 1);
        if (w.mode == 1) asm volatile(ELECT "st.release.gpu.global.u32 [%0], %1;\n}" ::"l"(&g_flag[w.range]), "r"(ep) : "memory");
        T3(i, 2);
      }
      T3(15, 1);
    } else
    if (warp == 0) {
      Ring r{0, 1, 3};
      uint32_t d = cta;
      for (int i = 0;; i++) {
        const Work w = decode(d);
        if (w.kind == 2) break;
        const CUtensorMap* m = w.kind == 0 ? &P.wq[w.beta >> 4] : &P.wo[w.beta >> 4];
        for (int ks = 0; ks < w.nsteps; ks++) {
          const uint32_t b = borrow(ks, w.nsteps);
          r.next_if(b == 2);
          const uint32_t bar = sbase + BAR_FULL + r.slot * 8;
          mbar_wait_w(bar + (BAR_EMPTY - BAR_FULL), r.phase);
          if (w.kind == 0) tma_ld3_w(sbase + r.slot * SLOT, m, 0, ks * 64, w.sub * 2, bar, 16384);
          else tma_ld_wo_w(sbase + r.slot * SLOT, m, w.sub * 128, (w.k0 + ks) * 2, bar);
          if (ks < 10) T2P(i, 2, ks);
          if (w.kind != 0 && ks == max(w.nsteps - GO_P, 4)) mbar_arrive_warp(sbase + BAR_GO);
          r.next(); r.next_if(b == 2);
        }
        if (w.kind == 0) {
          r.phase ^= 1; r.next(); r.next();
        } else if (w.mode == 2) {
          for (int k = 1; k <= ((d >> 5) & 3); k++) {
            wait_count(&g_flag[w.range + 5 * k], lds(sbase + EPOCH_OFF));
            asm volatile("fence.proxy.async.global;" ::: "memory");
#pragma unroll 1
            for (int t = 0; t < 4; t++) {
              mbar_wait_w(sbase + BAR_EMPTY + r.slot * 8, r.phase);
              tma_ld3_w(sbase + r.slot * SLOT, &P.o_st[t == 3], 0, t * 64, NBETA * 64 + (w.range + 5 * k) * 2, sbase + BAR_FULL + r.slot * 8,
                        t == 3 ? 8192 : 16384);
              r.next();
            }
          }
        }
        mbar_wait_w(sbase + BAR_DESC, i & 1);
        d = __shfl_sync(0xffffffffu, lds(sbase + DESC_OFF + ((i + 1) & 3) * 4), 0);
      }
    } else {
      const int hi = warp - 2;
      uint64_t pol_stream;
      asm volatile("createpolicy.fractional.L2::evict_first.b64 %0, 1.0;" : "=l"(pol_stream));
      Ring r{0, 1, 3};
      uint32_t d = cta;
      for (int i = 0;; i++) {
        const Work w = decode(d);
        if (w.kind == 2) break;
        const CUtensorMap* m = w.kind == 0 ? &P.x[hi][w.beta >> 4] : &P.o_ld[hi];
        int c1 = (w.kind == 0 ? (w.beta & 15) : w.beta * 64 + w.k0) * SQ + hi * 128;
        int k_late = -1;
        if (w.kind != 0) {
          if (!hi) T3(i, 3);
          if (d >= (3u << 30)) wait_count(&g_cnt[0][w.beta], lds(sbase + EPOCH_OFF) * H_LATE);
          if (d & 128) k_late = max(2 * H_LATE - w.k0, 0);
          if (!hi) T3(i, 4);
          asm volatile("fence.proxy.async.global;" ::: "memory");
          if (!hi) T3(i, 5);
        }
        for (int ks = 0; ks < w.nsteps; ks++) {
          if (ks == k_late) {
            if (!hi) T3(i, 6);
            wait_count(&g_cnt[1][d & 31], lds(sbase + EPOCH_OFF) * (NH - H_LATE));
            asm volatile("fence.proxy.async.global;" ::: "memory");
            if (!hi) T3(i, 7);
          }
          const uint32_t b = borrow(ks, w.nsteps);
          const bool bo = b != 2;
          r.next_if(hi && !bo); r.next_if(hi && !bo);
          const uint32_t sl = bo ? NS + (b ^ (3 * hi)) : r.slot, bar = sbase + BAR_FULL + sl * 8;
          mbar_wait_w(bar + (BAR_EMPTY - BAR_FULL), bo ? (r.xp >> b) & 1 : r.phase);
          if (w.kind == 0) tma_ld2_w(sbase + sl * SLOT, m, ks * 64, c1, bar, (hi ? 96 * 128 : 128 * 128) >> (DEV_HALF & 1));
          else if (O_LD_POL) { tma_ld2_hint_w(sbase + sl * SLOT, m, 0, c1, bar, (hi ? 96 * 128 : 128 * 128) >> (DEV_HALF >> 1), pol_stream); c1 += SQ; }
          else { tma_ld2_w(sbase + sl * SLOT, m, 0, c1, bar, hi ? 96 * 128 : 128 * 128); c1 += SQ; }
          if (PF_UNITS && w.kind == 0 && i < PF_UNITS && (((i ? PF_MASK : PF_MASK0) >> ks) & 1))
            asm volatile(ELECT "cp.async.bulk.prefetch.tensor.3d.L2.global.L2::cache_hint [%0, {0, %1, 0}], %2;\n}"
                         ::"l"(&P.kv[hi][w.beta >> 4]), "r"((d & 511) * SK + 64 * (PF_J0 + __popc((i ? PF_MASK : PF_MASK0) & ((1 << ks) - 1)))), "l"(pol_stream) : "memory");
          if (ks < 10) T2P(i, 3 + hi, ks);
          if (!hi && w.kind != 0 && !(ks & 3)) TCLK(i * 16 + (ks >> 2));
          r.next(); r.next_if(!hi && !bo); r.next_if(!hi && !bo);
          r.xp ^= 1 << b;
        }
        r.xp ^= 3;
        if (w.kind == 0) {
          m = &P.kv[hi][w.beta >> 4];
          c1 = (d & 511) * SK;
          for (int j = 0; j < 16; j++) {
            if (hi) r.next();
            const uint32_t bar = sbase + BAR_FULL + r.slot * 8;
            const bool tight = i < KV_WIN_UNITS && j < KV_WIN_TILES + ((KV_WIN_RAMP * ((int)d - KV_WIN_N * i)) >> 5);
            if (tight || (KV_WIN_D && j < KV_WIN_T2)) {
              const int s2 = (int)r.slot - (tight ? 2 : KV_WIN_D);
              mbar_wait_w(sbase + BAR_FULL + (s2 < 0 ? s2 + NS : s2) * 8, s2 < 0 ? r.phase : r.phase ^ 1);
            }
            if (j == 15 && hi) mbar_wait_w(sbase + BAR_DESC, i & 1);
            mbar_wait_w(sbase + BAR_EMPTY + r.slot * 8, r.phase);
            tma_ld3_hint_w(sbase + r.slot * SLOT, m, 0, c1, 0, bar, pol_stream);
            T2P(i, 3 + hi, 16 + j);
            if (!hi) TCLK(i * 16 + j);
            if (j == 14 && !hi) mbar_arrive_warp(sbase + BAR_GO);
            if (PF_X && j == PF_XJ && (d & 31) < 10 && d + PF_X * 32 < 1024)
              asm volatile(ELECT "cp.async.bulk.prefetch.tensor.2d.L2.global [%0, {%1, %2}];\n}"
                           ::"l"(&P.x[hi][(d + PF_X * 32) >> 9]), "r"((d & 31) * 64), "r"((((d >> 5) + PF_X) & 15) * SQ + hi * 128) : "memory");
            if (PF_W && j < 5 && (d >> 5) == PF_W)
              asm volatile(ELECT "cp.async.bulk.prefetch.tensor.3d.L2.global [%0, {0, %1, %2}];\n}"
                           ::"l"(&P.wq[1]), "r"((j * 2 + hi) * 64), "r"((d & 31) * 2) : "memory");
            c1 += 64;
            r.next();
            if (!hi) r.next();
          }
        }
        mbar_wait_w(sbase + BAR_DESC, i & 1);
        d = __shfl_sync(0xffffffffu, lds(sbase + DESC_OFF + ((i + 1) & 3) * 4), 0);
      }
    }
  } else {
    asm volatile("setmaxnreg.inc.sync.aligned.u32 %0;" ::"n"(REG_C));
    Ctx c;
    c.sb = sbase; c.wg = wg; c.warp = warp; c.src = 0; c.mqk = 0; c.mpv = 0; c.lead = lane == 0;
    if (wg == 0) consumer<0>(c, P.kp); else consumer<1>(c, P.kp);
  }
}

typedef CUresult (*EncodeFn)(CUtensorMap*, CUtensorMapDataType, cuuint32_t, void*, const cuuint64_t*, const cuuint64_t*,
                             const cuuint32_t*, const cuuint32_t*, CUtensorMapInterleave, CUtensorMapSwizzle,
                             CUtensorMapL2promotion, CUtensorMapFloatOOBfill);

void make_map(EncodeFn enc, CUtensorMap* m, const void* ptr, int rank, const cuuint64_t* dims, const cuuint64_t* strides,
              const cuuint32_t* box, int promo = 2) {
  cuuint32_t es[5] = {1, 1, 1, 1, 1};
  enc(m, CU_TENSOR_MAP_DATA_TYPE_BFLOAT16, rank, const_cast<void*>(ptr), dims, strides, box, es,
      CU_TENSOR_MAP_INTERLEAVE_NONE, CU_TENSOR_MAP_SWIZZLE_128B, promo == 2 ? CU_TENSOR_MAP_L2_PROMOTION_L2_256B : promo == 1 ? CU_TENSOR_MAP_L2_PROMOTION_L2_128B : CU_TENSOR_MAP_L2_PROMOTION_NONE,
      CU_TENSOR_MAP_FLOAT_OOB_FILL_NONE);
}

}

extern "C" void kernel_launch(void* const* d_in, const int* in_sizes, int n_in, void* d_out, int out_size) {
  (void)in_sizes; (void)n_in; (void)out_size;
  static EncodeFn enc = nullptr;
  static void* o_ptr = nullptr;
  static int n_sm = 0;
  if (!enc) {
    void* fn = nullptr;
    cudaDriverEntryPointQueryResult qr;
    cudaGetDriverEntryPoint("cuTensorMapEncodeTiled", &fn, cudaEnableDefault, &qr);
    enc = (EncodeFn)fn;
    cudaGetSymbolAddress(&o_ptr, g_o);
    cudaFuncSetAttribute(mha_fused_kernel<false>, cudaFuncAttributeMaxDynamicSharedMemorySize, SMEM_BYTES);
    cudaFuncSetAttribute(mha_fused_kernel<true>, cudaFuncAttributeMaxDynamicSharedMemorySize, SMEM_BYTES);
    int dev = 0;
    cudaGetDevice(&dev);
    cudaDeviceGetAttribute(&n_sm, cudaDevAttrMultiProcessorCount, dev);
  }
  Params P;
  for (int br = 0; br < 2; br++) {
    const void* x = d_in[br * 5 + 0]; const void* kc = d_in[br * 5 + 1]; const void* vc = d_in[br * 5 + 2];
    const void* wq = d_in[br * 5 + 3]; const void* wo = d_in[br * 5 + 4];
    { cuuint64_t d[2] = {DM, (cuuint64_t)NB * SQ}, s[1] = {DM * 2}; cuuint32_t b[2] = {64, 128 >> (DEV_HALF & 1)}, b2[2] = {64, 96 >> (DEV_HALF & 1)};
      make_map(enc, &P.x[0][br], x, 2, d, s, b, PR_X); make_map(enc, &P.x[1][br], x, 2, d, s, b2, PR_X); }
    { cuuint64_t d[3] = {64, DM, HD / 64}, s[2] = {HD * 2, 128}; cuuint32_t b[3] = {64, 64, 2}; make_map(enc, &P.wq[br], wq, 3, d, s, b, PR_W); }
    { cuuint64_t d[5] = {DM, 2, 4, 4, HD / 32}, s[4] = {DM * 2, 8 * DM * 2, 2 * DM * 2, 32 * DM * 2}; cuuint32_t b[5] = {64, 2, 4, 4, 2};
      make_map(enc, &P.wo[br], wo, 5, d, s, b, PR_W); }
    { cuuint64_t d[3] = {64, (cuuint64_t)NB * NH * SK, 2}, s[2] = {DH * 2, 128}; cuuint32_t b[3] = {64, 64, 2};
      make_map(enc, &P.kv[0][br], kc, 3, d, s, b, PR_KV); make_map(enc, &P.kv[1][br], vc, 3, d, s, b, PR_KV); }
    P.kp[br] = (const __nv_bfloat16*)kc; P.vp[br] = (const __nv_bfloat16*)vc;

  }
  { cuuint64_t d[2] = {64, (cuuint64_t)NBETA * 64 * SQ}, s[1] = {128}; cuuint32_t b[2] = {64, 128 >> (DEV_HALF >> 1)}, b2[2] = {64, 96 >> (DEV_HALF >> 1)};
    make_map(enc, &P.o_ld[0], o_ptr, 2, d, s, b); make_map(enc, &P.o_ld[1], o_ptr, 2, d, s, b2); }
  { cuuint64_t d[3] = {64, SQ, O_BLOCKS}, s[2] = {128, SQ * 128}; cuuint32_t b[3] = {64, 64, 2}, b2[3] = {64, 32, 2};
    make_map(enc, &P.o_st[0], o_ptr, 3, d, s, b); make_map(enc, &P.o_st[1], o_ptr, 3, d, s, b2); }
  { cuuint64_t d[3] = {64, (cuuint64_t)NB * SQ, 2 * DM / 64}, s[2] = {2 * DM * 2, 128}; cuuint32_t b[3] = {64, 64, 2}, b2[3] = {64, 32, 2};
    make_map(enc, &P.out_st[0], d_out, 3, d, s, b); make_map(enc, &P.out_st[1], d_out, 3, d, s, b2); }
  if (n_sm >= NCTA) mha_fused_kernel<false><<<NCTA, 384, SMEM_BYTES>>>(P);
  else mha_fused_kernel<true><<<n_sm, 384, SMEM_BYTES>>>(P);
}
```

```cpp
#include <cuda_runtime.h>
#include <cuda_bf16.h>
#include <cuda.h>
#include <stdint.h>
#include <stdlib.h>

namespace {

__device__ __forceinline__ void wgmma_proj(float (&d)[64], uint64_t da, uint64_t db, int scaleD) {
  asm volatile("{\n.reg .pred p;\nsetp.ne.b32 p, %66, 0;\n"
      "wgmma.mma_async.sync.aligned.m64n128k16.f32.bf16.bf16 "
      "{%0, %1, %2, %3, %4, %5, %6, %7, %8, %9, %10, %11, %12, %13, %14, %15, %16, %17, %18, %19, %20, %21, %22, %23, %24, %25, %26, %27, %28, %29, %30, "
      "%31, %32, %33, %34, %35, %36, %37, %38, %39, %40, %41, %42, %43, %44, %45, %46, %47, %48, %49, %50, %51, %52, %53, %54, %55, %56, %57, %58, %59, %60, "
      "%61, %62, %63}, "
      "%64, %65, p, 1, 1, 0, 1;\n}\n"
      : "+f"(d[0]), "+f"(d[1]), "+f"(d[2]), "+f"(d[3]), "+f"(d[4]), "+f"(d[5]), "+f"(d[6]), "+f"(d[7]), "+f"(d[8]), "+f"(d[9]), "+f"(d[10]), "+f"(d[11]),
        "+f"(d[12]), "+f"(d[13]), "+f"(d[14]), "+f"(d[15]), "+f"(d[16]), "+f"(d[17]), "+f"(d[18]), "+f"(d[19]), "+f"(d[20]), "+f"(d[21]), "+f"(d[22]),
        "+f"(d[23]), "+f"(d[24]), "+f"(d[25]), "+f"(d[26]), "+f"(d[27]), "+f"(d[28]), "+f"(d[29]), "+f"(d[30]), "+f"(d[31]), "+f"(d[32]), "+f"(d[33]),
        "+f"(d[34]), "+f"(d[35]), "+f"(d[36]), "+f"(d[37]), "+f"(d[38]), "+f"(d[39]), "+f"(d[40]), "+f"(d[41]), "+f"(d[42]), "+f"(d[43]), "+f"(d[44]),
        "+f"(d[45]), "+f"(d[46]), "+f"(d[47]), "+f"(d[48]), "+f"(d[49]), "+f"(d[50]), "+f"(d[51]), "+f"(d[52]), "+f"(d[53]), "+f"(d[54]), "+f"(d[55]),
        "+f"(d[56]), "+f"(d[57]), "+f"(d[58]), "+f"(d[59]), "+f"(d[60]), "+f"(d[61]), "+f"(d[62]), "+f"(d[63])
      : "l"(da), "l"(db), "r"(scaleD));
}
__device__ __forceinline__ void wgmma_proj96(float (&d)[64], uint64_t da, uint64_t db, int scaleD) {
  asm volatile("{\n.reg .pred p;\nsetp.ne.b32 p, %50, 0;\n"
      "wgmma.mma_async.sync.aligned.m64n96k16.f32.bf16.bf16 "
      "{%0, %1, %2, %3, %4, %5, %6, %7, %8, %9, %10, %11, %12, %13, %14, %15, %16, %17, %18, %19, %20, %21, %22, %23, %24, %25, %26, %27, %28, %29, %30, "
      "%31, %32, %33, %34, %35, %36, %37, %38, %39, %40, %41, %42, %43, %44, %45, %46, %47}, "
      "%48, %49, p, 1, 1, 1, 0;\n}\n"
      : "+f"(d[0]), "+f"(d[1]), "+f"(d[2]), "+f"(d[3]), "+f"(d[4]), "+f"(d[5]), "+f"(d[6]), "+f"(d[7]), "+f"(d[8]), "+f"(d[9]), "+f"(d[10]), "+f"(d[11]),
        "+f"(d[12]), "+f"(d[13]), "+f"(d[14]), "+f"(d[15]), "+f"(d[16]), "+f"(d[17]), "+f"(d[18]), "+f"(d[19]), "+f"(d[20]), "+f"(d[21]), "+f"(d[22]),
        "+f"(d[23]), "+f"(d[24]), "+f"(d[25]), "+f"(d[26]), "+f"(d[27]), "+f"(d[28]), "+f"(d[29]), "+f"(d[30]), "+f"(d[31]), "+f"(d[32]), "+f"(d[33]),
        "+f"(d[34]), "+f"(d[35]), "+f"(d[36]), "+f"(d[37]), "+f"(d[38]), "+f"(d[39]), "+f"(d[40]), "+f"(d[41]), "+f"(d[42]), "+f"(d[43]), "+f"(d[44]),
        "+f"(d[45]), "+f"(d[46]), "+f"(d[47])
      : "l"(da), "l"(db), "r"(scaleD));
}
__device__ __forceinline__ void wgmma_qk(float (&d)[32], uint64_t da, uint64_t db, int scaleD) {
  asm volatile("{\n.reg .pred p;\nsetp.ne.b32 p, %34, 0;\n"
      "wgmma.mma_async.sync.aligned.m64n64k16.f32.bf16.bf16 "
      "{%0, %1, %2, %3, %4, %5, %6, %7, %8, %9, %10, %11, %12, %13, %14, %15, %16, %17, %18, %19, %20, %21, %22, %23, %24, %25, %26, %27, %28, %29, %30, "
      "%31}, "
      "%32, %33, p, 1, 1, 0, 0;\n}\n"
      : "+f"(d[0]), "+f"(d[1]), "+f"(d[2]), "+f"(d[3]), "+f"(d[4]), "+f"(d[5]), "+f"(d[6]), "+f"(d[7]), "+f"(d[8]), "+f"(d[9]), "+f"(d[10]), "+f"(d[11]),
        "+f"(d[12]), "+f"(d[13]), "+f"(d[14]), "+f"(d[15]), "+f"(d[16]), "+f"(d[17]), "+f"(d[18]), "+f"(d[19]), "+f"(d[20]), "+f"(d[21]), "+f"(d[22]),
        "+f"(d[23]), "+f"(d[24]), "+f"(d[25]), "+f"(d[26]), "+f"(d[27]), "+f"(d[28]), "+f"(d[29]), "+f"(d[30]), "+f"(d[31])
      : "l"(da), "l"(db), "r"(scaleD));
}
__device__ __forceinline__ void wgmma_pv(float (&d)[64], uint32_t a0, uint32_t a1, uint32_t a2, uint32_t a3, uint64_t db, int scaleD) {
  asm volatile("{\n.reg .pred p;\nsetp.ne.b32 p, %69, 0;\n"
      "wgmma.mma_async.sync.aligned.m64n128k16.f32.bf16.bf16 "
      "{%0, %1, %2, %3, %4, %5, %6, %7, %8, %9, %10, %11, %12, %13, %14, %15, %16, %17, %18, %19, %20, %21, %22, %23, %24, %25, %26, %27, %28, %29, %30, "
      "%31, %32, %33, %34, %35, %36, %37, %38, %39, %40, %41, %42, %43, %44, %45, %46, %47, %48, %49, %50, %51, %52, %53, %54, %55, %56, %57, %58, %59, %60, "
      "%61, %62, %63}, "
      "{%64, %65, %66, %67}, %68, p, 1, 1, 1;\n}\n"
      : "+f"(d[0]), "+f"(d[1]), "+f"(d[2]), "+f"(d[3]), "+f"(d[4]), "+f"(d[5]), "+f"(d[6]), "+f"(d[7]), "+f"(d[8]), "+f"(d[9]), "+f"(d[10]), "+f"(d[11]),
        "+f"(d[12]), "+f"(d[13]), "+f"(d[14]), "+f"(d[15]), "+f"(d[16]), "+f"(d[17]), "+f"(d[18]), "+f"(d[19]), "+f"(d[20]), "+f"(d[21]), "+f"(d[22]),
        "+f"(d[23]), "+f"(d[24]), "+f"(d[25]), "+f"(d[26]), "+f"(d[27]), "+f"(d[28]), "+f"(d[29]), "+f"(d[30]), "+f"(d[31]), "+f"(d[32]), "+f"(d[33]),
        "+f"(d[34]), "+f"(d[35]), "+f"(d[36]), "+f"(d[37]), "+f"(d[38]), "+f"(d[39]), "+f"(d[40]), "+f"(d[41]), "+f"(d[42]), "+f"(d[43]), "+f"(d[44]),
        "+f"(d[45]), "+f"(d[46]), "+f"(d[47]), "+f"(d[48]), "+f"(d[49]), "+f"(d[50]), "+f"(d[51]), "+f"(d[52]), "+f"(d[53]), "+f"(d[54]), "+f"(d[55]),
        "+f"(d[56]), "+f"(d[57]), "+f"(d[58]), "+f"(d[59]), "+f"(d[60]), "+f"(d[61]), "+f"(d[62]), "+f"(d[63])
      : "r"(a0), "r"(a1), "r"(a2), "r"(a3), "l"(db), "r"(scaleD));
}
__device__ __forceinline__ void wgmma_qk_sp(float (&d)[32], uint32_t a0, uint32_t a1, uint32_t a2, uint32_t a3, uint64_t db, int scaleD, uint32_t meta) {
  asm volatile("{\n.reg .pred p;\nsetp.ne.b32 p, %37, 0;\n"
      "wgmma.mma_async.sp.sync.aligned.m64n64k32.f32.bf16.bf16 "
      "{%0, %1, %2, %3, %4, %5, %6, %7, %8, %9, %10, %11, %12, %13, %14, %15, %16, %17, %18, %19, %20, %21, %22, %23, %24, %25, %26, %27, %28, %29, %30, "
      "%31}, "
      "{%32, %33, %34, %35}, %36, %38, 0, p, 1, 1, 0;\n}\n"
      : "+f"(d[0]), "+f"(d[1]), "+f"(d[2]), "+f"(d[3]), "+f"(d[4]), "+f"(d[5]), "+f"(d[6]), "+f"(d[7]), "+f"(d[8]), "+f"(d[9]), "+f"(d[10]), "+f"(d[11]),
        "+f"(d[12]), "+f"(d[13]), "+f"(d[14]), "+f"(d[15]), "+f"(d[16]), "+f"(d[17]), "+f"(d[18]), "+f"(d[19]), "+f"(d[20]), "+f"(d[21]), "+f"(d[22]),
        "+f"(d[23]), "+f"(d[24]), "+f"(d[25]), "+f"(d[26]), "+f"(d[27]), "+f"(d[28]), "+f"(d[29]), "+f"(d[30]), "+f"(d[31])
      : "r"(a0), "r"(a1), "r"(a2), "r"(a3), "l"(db), "r"(scaleD), "r"(meta));
}
__device__ __forceinline__ void wgmma_pv_sp(float (&d)[64], uint32_t a0, uint32_t a1, uint32_t a2, uint32_t a3, uint64_t db, int scaleD, uint32_t meta) {
  asm volatile("{\n.reg .pred p;\nsetp.ne.b32 p, %69, 0;\n"
      "wgmma.mma_async.sp.sync.aligned.m64n128k32.f32.bf16.bf16 "
      "{%0, %1, %2, %3, %4, %5, %6, %7, %8, %9, %10, %11, %12, %13, %14, %15, %16, %17, %18, %19, %20, %21, %22, %23, %24, %25, %26, %27, %28, %29, %30, "
      "%31, %32, %33, %34, %35, %36, %37, %38, %39, %40, %41, %42, %43, %44, %45, %46, %47, %48, %49, %50, %51, %52, %53, %54, %55, %56, %57, %58, %59, %60, "
      "%61, %62, %63}, "
      "{%64, %65, %66, %67}, %68, %70, 0, p, 1, 1, 1;\n}\n"
      : "+f"(d[0]), "+f"(d[1]), "+f"(d[2]), "+f"(d[3]), "+f"(d[4]), "+f"(d[5]), "+f"(d[6]), "+f"(d[7]), "+f"(d[8]), "+f"(d[9]), "+f"(d[10]), "+f"(d[11]),
        "+f"(d[12]), "+f"(d[13]), "+f"(d[14]), "+f"(d[15]), "+f"(d[16]), "+f"(d[17]), "+f"(d[18]), "+f"(d[19]), "+f"(d[20]), "+f"(d[21]), "+f"(d[22]),
        "+f"(d[23]), "+f"(d[24]), "+f"(d[25]), "+f"(d[26]), "+f"(d[27]), "+f"(d[28]), "+f"(d[29]), "+f"(d[30]), "+f"(d[31]), "+f"(d[32]), "+f"(d[33]),
        "+f"(d[34]), "+f"(d[35]), "+f"(d[36]), "+f"(d[37]), "+f"(d[38]), "+f"(d[39]), "+f"(d[40]), "+f"(d[41]), "+f"(d[42]), "+f"(d[43]), "+f"(d[44]),
        "+f"(d[45]), "+f"(d[46]), "+f"(d[47]), "+f"(d[48]), "+f"(d[49]), "+f"(d[50]), "+f"(d[51]), "+f"(d[52]), "+f"(d[53]), "+f"(d[54]), "+f"(d[55]),
        "+f"(d[56]), "+f"(d[57]), "+f"(d[58]), "+f"(d[59]), "+f"(d[60]), "+f"(d[61]), "+f"(d[62]), "+f"(d[63])
      : "r"(a0), "r"(a1), "r"(a2), "r"(a3), "l"(db), "r"(scaleD), "r"(meta));
}
__device__ __forceinline__ void wgmma_proj_init(float (&d)[64], uint64_t da, uint64_t db, int scaleD) {
  asm volatile("{\n.reg .pred p;\nsetp.ne.b32 p, %66, 0;\n"
      "wgmma.mma_async.sync.aligned.m64n128k16.f32.bf16.bf16 "
      "{%0, %1, %2, %3, %4, %5, %6, %7, %8, %9, %10, %11, %12, %13, %14, %15, %16, %17, %18, %19, %20, %21, %22, %23, %24, %25, %26, %27, %28, %29, %30, "
      "%31, %32, %33, %34, %35, %36, %37, %38, %39, %40, %41, %42, %43, %44, %45, %46, %47, %48, %49, %50, %51, %52, %53, %54, %55, %56, %57, %58, %59, %60, "
      "%61, %62, %63}, "
      "%64, %65, p, 1, 1, 0, 1;\n}\n"
      : "=f"(d[0]), "=f"(d[1]), "=f"(d[2]), "=f"(d[3]), "=f"(d[4]), "=f"(d[5]), "=f"(d[6]), "=f"(d[7]), "=f"(d[8]), "=f"(d[9]), "=f"(d[10]), "=f"(d[11]),
        "=f"(d[12]), "=f"(d[13]), "=f"(d[14]), "=f"(d[15]), "=f"(d[16]), "=f"(d[17]), "=f"(d[18]), "=f"(d[19]), "=f"(d[20]), "=f"(d[21]), "=f"(d[22]),
        "=f"(d[23]), "=f"(d[24]), "=f"(d[25]), "=f"(d[26]), "=f"(d[27]), "=f"(d[28]), "=f"(d[29]), "=f"(d[30]), "=f"(d[31]), "=f"(d[32]), "=f"(d[33]),
        "=f"(d[34]), "=f"(d[35]), "=f"(d[36]), "=f"(d[37]), "=f"(d[38]), "=f"(d[39]), "=f"(d[40]), "=f"(d[41]), "=f"(d[42]), "=f"(d[43]), "=f"(d[44]),
        "=f"(d[45]), "=f"(d[46]), "=f"(d[47]), "=f"(d[48]), "=f"(d[49]), "=f"(d[50]), "=f"(d[51]), "=f"(d[52]), "=f"(d[53]), "=f"(d[54]), "=f"(d[55]),
        "=f"(d[56]), "=f"(d[57]), "=f"(d[58]), "=f"(d[59]), "=f"(d[60]), "=f"(d[61]), "=f"(d[62]), "=f"(d[63])
      : "l"(da), "l"(db), "r"(scaleD));
}
__device__ __forceinline__ void wgmma_proj96_init(float (&d)[64], uint64_t da, uint64_t db, int scaleD) {
  asm volatile("{\n.reg .pred p;\nsetp.ne.b32 p, %50, 0;\n"
      "wgmma.mma_async.sync.aligned.m64n96k16.f32.bf16.bf16 "
      "{%0, %1, %2, %3, %4, %5, %6, %7, %8, %9, %10, %11, %12, %13, %14, %15, %16, %17, %18, %19, %20, %21, %22, %23, %24, %25, %26, %27, %28, %29, %30, "
      "%31, %32, %33, %34, %35, %36, %37, %38, %39, %40, %41, %42, %43, %44, %45, %46, %47}, "
      "%48, %49, p, 1, 1, 1, 0;\n}\n"
      : "=f"(d[0]), "=f"(d[1]), "=f"(d[2]), "=f"(d[3]), "=f"(d[4]), "=f"(d[5]), "=f"(d[6]), "=f"(d[7]), "=f"(d[8]), "=f"(d[9]), "=f"(d[10]), "=f"(d[11]),
        "=f"(d[12]), "=f"(d[13]), "=f"(d[14]), "=f"(d[15]), "=f"(d[16]), "=f"(d[17]), "=f"(d[18]), "=f"(d[19]), "=f"(d[20]), "=f"(d[21]), "=f"(d[22]),
        "=f"(d[23]), "=f"(d[24]), "=f"(d[25]), "=f"(d[26]), "=f"(d[27]), "=f"(d[28]), "=f"(d[29]), "=f"(d[30]), "=f"(d[31]), "=f"(d[32]), "=f"(d[33]),
        "=f"(d[34]), "=f"(d[35]), "=f"(d[36]), "=f"(d[37]), "=f"(d[38]), "=f"(d[39]), "=f"(d[40]), "=f"(d[41]), "=f"(d[42]), "=f"(d[43]), "=f"(d[44]),
        "=f"(d[45]), "=f"(d[46]), "=f"(d[47])
      : "l"(da), "l"(db), "r"(scaleD));
}
__device__ __forceinline__ void wgmma_qk_init(float (&d)[32], uint64_t da, uint64_t db, int scaleD) {
  asm volatile("{\n.reg .pred p;\nsetp.ne.b32 p, %34, 0;\n"
      "wgmma.mma_async.sync.aligned.m64n64k16.f32.bf16.bf16 "
      "{%0, %1, %2, %3, %4, %5, %6, %7, %8, %9, %10, %11, %12, %13, %14, %15, %16, %17, %18, %19, %20, %21, %22, %23, %24, %25, %26, %27, %28, %29, %30, "
      "%31}, "
      "%32, %33, p, 1, 1, 0, 0;\n}\n"
      : "=f"(d[0]), "=f"(d[1]), "=f"(d[2]), "=f"(d[3]), "=f"(d[4]), "=f"(d[5]), "=f"(d[6]), "=f"(d[7]), "=f"(d[8]), "=f"(d[9]), "=f"(d[10]), "=f"(d[11]),
        "=f"(d[12]), "=f"(d[13]), "=f"(d[14]), "=f"(d[15]), "=f"(d[16]), "=f"(d[17]), "=f"(d[18]), "=f"(d[19]), "=f"(d[20]), "=f"(d[21]), "=f"(d[22]),
        "=f"(d[23]), "=f"(d[24]), "=f"(d[25]), "=f"(d[26]), "=f"(d[27]), "=f"(d[28]), "=f"(d[29]), "=f"(d[30]), "=f"(d[31])
      : "l"(da), "l"(db), "r"(scaleD));
}
__device__ __forceinline__ void wgmma_pv_init(float (&d)[64], uint32_t a0, uint32_t a1, uint32_t a2, uint32_t a3, uint64_t db, int scaleD) {
  asm volatile("{\n.reg .pred p;\nsetp.ne.b32 p, %69, 0;\n"
      "wgmma.mma_async.sync.aligned.m64n128k16.f32.bf16.bf16 "
      "{%0, %1, %2, %3, %4, %5, %6, %7, %8, %9, %10, %11, %12, %13, %14, %15, %16, %17, %18, %19, %20, %21, %22, %23, %24, %25, %26, %27, %28, %29, %30, "
      "%31, %32, %33, %34, %35, %36, %37, %38, %39, %40, %41, %42, %43, %44, %45, %46, %47, %48, %49, %50, %51, %52, %53, %54, %55, %56, %57, %58, %59, %60, "
      "%61, %62, %63}, "
      "{%64, %65, %66, %67}, %68, p, 1, 1, 1;\n}\n"
      : "=f"(d[0]), "=f"(d[1]), "=f"(d[2]), "=f"(d[3]), "=f"(d[4]), "=f"(d[5]), "=f"(d[6]), "=f"(d[7]), "=f"(d[8]), "=f"(d[9]), "=f"(d[10]), "=f"(d[11]),
        "=f"(d[12]), "=f"(d[13]), "=f"(d[14]), "=f"(d[15]), "=f"(d[16]), "=f"(d[17]), "=f"(d[18]), "=f"(d[19]), "=f"(d[20]), "=f"(d[21]), "=f"(d[22]),
        "=f"(d[23]), "=f"(d[24]), "=f"(d[25]), "=f"(d[26]), "=f"(d[27]), "=f"(d[28]), "=f"(d[29]), "=f"(d[30]), "=f"(d[31]), "=f"(d[32]), "=f"(d[33]),
        "=f"(d[34]), "=f"(d[35]), "=f"(d[36]), "=f"(d[37]), "=f"(d[38]), "=f"(d[39]), "=f"(d[40]), "=f"(d[41]), "=f"(d[42]), "=f"(d[43]), "=f"(d[44]),
        "=f"(d[45]), "=f"(d[46]), "=f"(d[47]), "=f"(d[48]), "=f"(d[49]), "=f"(d[50]), "=f"(d[51]), "=f"(d[52]), "=f"(d[53]), "=f"(d[54]), "=f"(d[55]),
        "=f"(d[56]), "=f"(d[57]), "=f"(d[58]), "=f"(d[59]), "=f"(d[60]), "=f"(d[61]), "=f"(d[62]), "=f"(d[63])
      : "r"(a0), "r"(a1), "r"(a2), "r"(a3), "l"(db), "r"(scaleD));
}
__device__ __forceinline__ void wgmma_qk_sp_init(float (&d)[32], uint32_t a0, uint32_t a1, uint32_t a2, uint32_t a3, uint64_t db, int scaleD, uint32_t meta) {
  asm volatile("{\n.reg .pred p;\nsetp.ne.b32 p, %37, 0;\n"
      "wgmma.mma_async.sp.sync.aligned.m64n64k32.f32.bf16.bf16 "
      "{%0, %1, %2, %3, %4, %5, %6, %7, %8, %9, %10, %11, %12, %13, %14, %15, %16, %17, %18, %19, %20, %21, %22, %23, %24, %25, %26, %27, %28, %29, %30, "
      "%31}, "
      "{%32, %33, %34, %35}, %36, %38, 0, p, 1, 1, 0;\n}\n"
      : "=f"(d[0]), "=f"(d[1]), "=f"(d[2]), "=f"(d[3]), "=f"(d[4]), "=f"(d[5]), "=f"(d[6]), "=f"(d[7]), "=f"(d[8]), "=f"(d[9]), "=f"(d[10]), "=f"(d[11]),
        "=f"(d[12]), "=f"(d[13]), "=f"(d[14]), "=f"(d[15]), "=f"(d[16]), "=f"(d[17]), "=f"(d[18]), "=f"(d[19]), "=f"(d[20]), "=f"(d[21]), "=f"(d[22]),
        "=f"(d[23]), "=f"(d[24]), "=f"(d[25]), "=f"(d[26]), "=f"(d[27]), "=f"(d[28]), "=f"(d[29]), "=f"(d[30]), "=f"(d[31])
      : "r"(a0), "r"(a1), "r"(a2), "r"(a3), "l"(db), "r"(scaleD), "r"(meta));
}
__device__ __forceinline__ void wgmma_pv_sp_init(float (&d)[64], uint32_t a0, uint32_t a1, uint32_t a2, uint32_t a3, uint64_t db, int scaleD, uint32_t meta) {
  asm volatile("{\n.reg .pred p;\nsetp.ne.b32 p, %69, 0;\n"
      "wgmma.mma_async.sp.sync.aligned.m64n128k32.f32.bf16.bf16 "
      "{%0, %1, %2, %3, %4, %5, %6, %7, %8, %9, %10, %11, %12, %13, %14, %15, %16, %17, %18, %19, %20, %21, %22, %23, %24, %25, %26, %27, %28, %29, %30, "
      "%31, %32, %33, %34, %35, %36, %37, %38, %39, %40, %41, %42, %43, %44, %45, %46, %47, %48, %49, %50, %51, %52, %53, %54, %55, %56, %57, %58, %59, %60, "
      "%61, %62, %63}, "
      "{%64, %65, %66, %67}, %68, %70, 0, p, 1, 1, 1;\n}\n"
      : "=f"(d[0]), "=f"(d[1]), "=f"(d[2]), "=f"(d[3]), "=f"(d[4]), "=f"(d[5]), "=f"(d[6]), "=f"(d[7]), "=f"(d[8]), "=f"(d[9]), "=f"(d[10]), "=f"(d[11]),
        "=f"(d[12]), "=f"(d[13]), "=f"(d[14]), "=f"(d[15]), "=f"(d[16]), "=f"(d[17]), "=f"(d[18]), "=f"(d[19]), "=f"(d[20]), "=f"(d[21]), "=f"(d[22]),
        "=f"(d[23]), "=f"(d[24]), "=f"(d[25]), "=f"(d[26]), "=f"(d[27]), "=f"(d[28]), "=f"(d[29]), "=f"(d[30]), "=f"(d[31]), "=f"(d[32]), "=f"(d[33]),
        "=f"(d[34]), "=f"(d[35]), "=f"(d[36]), "=f"(d[37]), "=f"(d[38]), "=f"(d[39]), "=f"(d[40]), "=f"(d[41]), "=f"(d[42]), "=f"(d[43]), "=f"(d[44]),
        "=f"(d[45]), "=f"(d[46]), "=f"(d[47]), "=f"(d[48]), "=f"(d[49]), "=f"(d[50]), "=f"(d[51]), "=f"(d[52]), "=f"(d[53]), "=f"(d[54]), "=f"(d[55]),
        "=f"(d[56]), "=f"(d[57]), "=f"(d[58]), "=f"(d[59]), "=f"(d[60]), "=f"(d[61]), "=f"(d[62]), "=f"(d[63])
      : "r"(a0), "r"(a1), "r"(a2), "r"(a3), "l"(db), "r"(scaleD), "r"(meta));
}

constexpr int NB = 16, SQ = 224, DM = 640, NH = 32, SK = 1024, DH = 128;
constexpr int HD = NH * DH;
constexpr int NBETA = 2 * NB;
constexpr int NCTA = 132;
constexpr int NS = 10;
constexpr int SLOT = 16384;
constexpr int QBUF_OFF = NS * SLOT;
constexpr int NSX = NS + 4;
constexpr int BAR_OFF = NSX * SLOT;
constexpr int BAR_FULL = BAR_OFF;
constexpr int BAR_EMPTY = BAR_OFF + 8 * NSX;
constexpr int BAR_STG = BAR_OFF + 16 * NSX;
constexpr int BAR_OUT = BAR_STG + 32;
constexpr int BAR_DESC = BAR_OUT + 8;
constexpr int BAR_GO = BAR_DESC + 8;
constexpr int DESC_OFF = BAR_GO + 8;
constexpr int EPOCH_OFF = DESC_OFF + 16;
constexpr int TRACE_OFF = EPOCH_OFF + 8;
constexpr int SMEM_BYTES = TRACE_OFF;
constexpr float SM_C = 0.08838834764831845f * 1.4426950408889634f;
constexpr float SUM_HI = 1099511627776.f, SUM_LO = 1.f / 1099511627776.f;
constexpr uint32_t META_QK = 0xEEEE4444u;
constexpr uint32_t META_PV = 0x44EEEE44u;

#define QK_EARLY_MASK 3
#define ST_ORDER 0x2130
#define LAG_BAR 5
#define ST_NOW 9
#define PF_UNITS 0
#define PF_MASK 0x2a8
#define PF_MASK0 PF_MASK
#define PF_X 0
#define PF_XJ 2
#define PF_W 0
#define KV_WIN_UNITS 2
#define KV_WIN_D 4
#define KV_WIN_T2 16
#define O_LD_POL 1
#define PACK_EARLY 0x00
#define O_STEPS 4
#define TLB_WARM 0
#define DEV_HALF 0
#define DEV_IDLE 0
#define KV_WIN_RAMP 4
#define KV_WIN_N 132
#define BORROW_ALT 0
#define PF_J0 0
#define PDEPTH 0
#define EARLY_BEG 1
#define KV_WIN_TILES -2
#define PR_KV 2
#define PR_X 2
#define PR_W 2
#define REG_C 232
#define REG_P 40
#define GO_P 4
#define P_POS 224
#define P_STRIDE 32
#define B_LATE 28
#define H_LATE 24
#define P_EARLY 13
#define PIECE_TABLE 0x5026401a,0x68dc4034,0x50275816,0x695a5837,0x50295015,0x6a175036,0x501e080d,0x681f083c,0x50253812,0x69d8383a,0x403f980e,0x80000000,0x5036180f,0x80000000,0x50203011,0x69993032,0x50367019,0x80000000,0x50224814,0x6a954835,0x50246017,0x6b526038,0x502c6818,0x6dc86839,0x5017b813,0x69d8b85f,0x50102810,0x685e2831,0x646e2030,0x80000000,0x501f101c,0x6dc8102f,0x5017801b,0x6c8d805e,0x6627783b,0x80000000,0x6627b033,0x80000000,0x501a901e,0x80000000,0x56d6881e,0x80000000,0x501ca81d,0x80000000,0x6762a03d,0x80000000,0x67e0002d,0x80000000,0x5512c01f,0x80000000,0x5013c81f,0x80000000

struct Params {
  CUtensorMap x[2][2], wq[2], kv[2][2], wo[2];
  CUtensorMap o_ld[2], o_st[2], out_st[2];
  const __nv_bfloat16* kp[2];
  const __nv_bfloat16* vp[2];
};

constexpr int NPART = 32 * 5, O_BLOCKS = NBETA * 64 + 2 * NPART;
__device__ __align__(128) __nv_bfloat16 g_o[(size_t)O_BLOCKS * SQ * 64];
__device__ unsigned g_cnt[2][NBETA];
__device__ unsigned g_epoch, g_next;
__device__ unsigned g_flag[NPART];

__device__ __forceinline__ uint32_t smem_u32(const void* p) { return (uint32_t)__cvta_generic_to_shared(p); }
__device__ __forceinline__ void mbar_init(uint32_t bar, int cnt) {
  asm volatile("mbarrier.init.shared::cta.b64 [%0], %1;" ::"r"(bar), "r"(cnt) : "memory");
}
__device__ __forceinline__ void mbar_arrive(uint32_t bar) {
  asm volatile("mbarrier.arrive.shared::cta.b64 _, [%0];" ::"r"(bar) : "memory");
}
__device__ __forceinline__ void mbar_arrive_warp(uint32_t bar) {
  asm volatile("{\n.reg .pred p;\nelect.sync _|p, 0xffffffff;\n@p mbarrier.arrive.shared::cta.b64 _, [%0];\n}" ::"r"(bar) : "memory");
}
__device__ __forceinline__ int lane_now() { int l; asm volatile("mov.u32 %0, %%laneid;" : "=r"(l)); return l; }
__device__ __forceinline__ bool mbar_try(uint32_t bar, uint32_t parity) {
  uint32_t ok;
  asm volatile("{\n.reg .pred p;\nmbarrier.try_wait.parity.shared::cta.b64 p, [%1], %2;\nselp.u32 %0, 1, 0, p;\n}"
               : "=r"(ok) : "r"(bar), "r"(parity) : "memory");
  return ok;
}
__device__ __forceinline__ bool mbar_test(uint32_t bar, uint32_t parity) {
  uint32_t ok;
  asm volatile("{\n.reg .pred p;\nmbarrier.test_wait.parity.shared::cta.b64 p, [%1], %2;\nselp.u32 %0, 1, 0, p;\n}"
               : "=r"(ok) : "r"(bar), "r"(parity) : "memory");
  return ok;
}
__device__ __forceinline__ void mbar_wait_w(uint32_t bar, uint32_t parity) {
  uint32_t n = 0;
  while (!__all_sync(0xffffffffu, mbar_try(bar, parity))) {
    if (++n > (1u << 22)) __trap();
  }
}
#define ELECT "{\n.reg .pred p;\nelect.sync _|p, 0xffffffff;\n@p "
__device__ __forceinline__ void tma_st3_hint_w(const CUtensorMap* m, uint32_t src, int c0, int c1, int c2, uint64_t pol) {
  asm volatile(ELECT "cp.async.bulk.tensor.3d.global.shared::cta.bulk_group.L2::cache_hint [%0, {%2, %3, %4}], [%1], %5;\n}"
               ::"l"(m), "r"(src), "r"(c0), "r"(c1), "r"(c2), "l"(pol) : "memory");
}
#define EXPECT(bar, bytes) "mbarrier.arrive.expect_tx.shared::cta.b64 _, [" bar "], " bytes ";\n@p "
__device__ __forceinline__ void tma_ld2_w(uint32_t dst, const CUtensorMap* m, int c0, int c1, uint32_t bar, uint32_t bytes) {
  asm volatile(ELECT EXPECT("%2", "%5") "cp.async.bulk.tensor.2d.shared::cluster.global.mbarrier::complete_tx::bytes [%0], [%1, {%3, %4}], [%2];\n}"
               ::"r"(dst), "l"(m), "r"(bar), "r"(c0), "r"(c1), "r"(bytes) : "memory");
}
__device__ __forceinline__ void tma_ld2_hint_w(uint32_t dst, const CUtensorMap* m, int c0, int c1, uint32_t bar, uint32_t bytes, uint64_t pol) {
  asm volatile(ELECT EXPECT("%2", "%6") "cp.async.bulk.tensor.2d.shared::cluster.global.mbarrier::complete_tx::bytes.L2::cache_hint"
               " [%0], [%1, {%3, %4}], [%2], %5;\n}"
               ::"r"(dst), "l"(m), "r"(bar), "r"(c0), "r"(c1), "l"(pol), "r"(bytes) : "memory");
}
__device__ __forceinline__ void tma_ld3_w(uint32_t dst, const CUtensorMap* m, int c0, int c1, int c2, uint32_t bar, uint32_t bytes) {
  asm volatile(ELECT EXPECT("%2", "%6") "cp.async.bulk.tensor.3d.shared::cluster.global.mbarrier::complete_tx::bytes [%0], [%1, {%3, %4, %5}], [%2];\n}"
               ::"r"(dst), "l"(m), "r"(bar), "r"(c0), "r"(c1), "r"(c2), "r"(bytes) : "memory");
}
__device__ __forceinline__ void tma_ld3_hint_w(uint32_t dst, const CUtensorMap* m, int c0, int c1, int c2, uint32_t bar, uint64_t pol) {
  asm volatile(ELECT EXPECT("%2", "16384") "cp.async.bulk.tensor.3d.shared::cluster.global.mbarrier::complete_tx::bytes.L2::cache_hint"
               " [%0], [%1, {%3, %4, %5}], [%2], %6;\n}"
               ::"r"(dst), "l"(m), "r"(bar), "r"(c0), "r"(c1), "r"(c2), "l"(pol) : "memory");
}
__device__ __forceinline__ void tma_ld_wo_w(uint32_t dst, const CUtensorMap* m, int col, int grp, uint32_t bar) {
  asm volatile(ELECT EXPECT("%2", "16384") "cp.async.bulk.tensor.5d.shared::cluster.global.mbarrier::complete_tx::bytes [%0], [%1, {%3, 0, 0, 0, %4}], [%2];\n"
               "@p cp.async.bulk.tensor.5d.shared::cluster.global.mbarrier::complete_tx::bytes [%5], [%1, {%6, 0, 0, 0, %4}], [%2];\n}"
               ::"r"(dst), "l"(m), "r"(bar), "r"(col), "r"(grp), "r"(dst + 8192), "r"(col + 64) : "memory");
}
__device__ __forceinline__ void mbar_arrive8_w(uint32_t bar) {
  asm volatile(ELECT "mbarrier.arrive.shared::cta.b64 _, [%0], 8;\n}" ::"r"(bar) : "memory");
}
__device__ __forceinline__ void bulk_commit() { asm volatile("cp.async.bulk.commit_group;" ::: "memory"); }
template <int N> __device__ __forceinline__ void bulk_wait_read() { asm volatile("cp.async.bulk.wait_group.read %0;" ::"n"(N) : "memory"); }
__device__ __forceinline__ void wg_fence() { asm volatile("wgmma.fence.sync.aligned;" ::: "memory"); }
__device__ __forceinline__ void wg_commit() { asm volatile("wgmma.commit_group.sync.aligned;" ::: "memory"); }
template <int N> __device__ __forceinline__ void wg_wait() { asm volatile("wgmma.wait_group.sync.aligned %0;" ::"n"(N) : "memory"); }
__device__ __forceinline__ void fence_async_smem() { asm volatile("fence.proxy.async.shared::cta;" ::: "memory"); }
__device__ __forceinline__ void bar_sync(int id, int n) { asm volatile("bar.sync %0, %1;" ::"r"(id), "r"(n) : "memory"); }
template <int N> __device__ __forceinline__ void reg_fence(float (&a)[N]) {
#pragma unroll
  for (int i = 0; i < N; i++) asm volatile("" : "+f"(a[i])::"memory");
}
template <int N> __device__ __forceinline__ void reg_fence(uint32_t (&a)[N]) {
#pragma unroll
  for (int i = 0; i < N; i++) asm volatile("" : "+r"(a[i])::"memory");
}
__device__ __forceinline__ float ex2(float x) { float y; asm("ex2.approx.ftz.f32 %0, %1;" : "=f"(y) : "f"(x)); return y; }
__device__ __forceinline__ uint32_t pack_bf16(float lo, float hi) {
  uint32_t r; asm("cvt.rn.bf16x2.f32 %0, %1, %2;" : "=r"(r) : "f"(hi), "f"(lo)); return r;
}
__device__ __forceinline__ void stsm4(uint32_t a, uint32_t r0, uint32_t r1, uint32_t r2, uint32_t r3) {
  asm volatile("stmatrix.sync.aligned.m8n8.x4.shared.b16 [%0], {%1, %2, %3, %4};" ::"r"(a), "r"(r0), "r"(r1), "r"(r2), "r"(r3) : "memory");
}
__device__ __forceinline__ void stsm4t(uint32_t a, uint32_t r0, uint32_t r1, uint32_t r2, uint32_t r3) {
  asm volatile("stmatrix.sync.aligned.m8n8.x4.trans.shared.b16 [%0], {%1, %2, %3, %4};" ::"r"(a), "r"(r0), "r"(r1), "r"(r2), "r"(r3) : "memory");
}
__device__ __forceinline__ void ldsm4(uint32_t a, uint32_t& r0, uint32_t& r1, uint32_t& r2, uint32_t& r3) {
  asm volatile("ldmatrix.sync.aligned.m8n8.x4.shared.b16 {%0, %1, %2, %3}, [%4];" : "=r"(r0), "=r"(r1), "=r"(r2), "=r"(r3) : "r"(a) : "memory");
}
__device__ __forceinline__ void sts16(uint32_t a, uint32_t v) { asm volatile("st.shared.u16 [%0], %1;" ::"r"(a), "h"((uint16_t)v) : "memory"); }
__device__ __forceinline__ void mma16816(float& c0, float& c1, float& c2, float& c3, uint32_t a0, uint32_t a1, uint32_t a2, uint32_t a3,
                                         uint32_t b0, uint32_t b1) {
  asm volatile("mma.sync.aligned.m16n8k16.row.col.f32.bf16.bf16.f32 {%0, %1, %2, %3}, {%4, %5, %6, %7}, {%8, %9}, {%0, %1, %2, %3};"
               : "+f"(c0), "+f"(c1), "+f"(c2), "+f"(c3) : "r"(a0), "r"(a1), "r"(a2), "r"(a3), "r"(b0), "r"(b1));
}
__device__ __forceinline__ uint32_t sdesc(uint32_t addr, uint32_t lbo) { return (addr >> 4) + ((lbo >> 4) << 16); }
__device__ __forceinline__ uint64_t desc64(uint32_t lo, uint32_t hi) { uint64_t d; asm("mov.b64 %0, {%1, %2};" : "=l"(d) : "r"(lo), "r"(hi)); return d; }
__device__ __forceinline__ void dadd(uint64_t& d, uint32_t inc) {
  asm("{\n.reg .b32 l, h;\nmov.b64 {l, h}, %0;\nadd.u32 l, l, %1;\nmov.b64 %0, {l, h};\n}" : "+l"(d) : "r"(inc));
}

struct Ring {
  uint32_t slot, phase, xp;
  __device__ __forceinline__ void uniform() {
    slot = __shfl_sync(0xffffffffu, slot, 0); phase = __shfl_sync(0xffffffffu, phase, 0); xp = __shfl_sync(0xffffffffu, xp, 0);
  }
  __device__ __forceinline__ void next() { if (++slot == NS) { slot = 0; phase ^= 1; } }
  __device__ __forceinline__ void next_if(bool p) { slot += p; if (slot == NS) { slot = 0; phase ^= 1; } }
};
__device__ __forceinline__ uint32_t borrow(int ks, int n) {
  if (BORROW_ALT) return (ks & 1) && ks >= 3 && ks + 1 < n ? (~ks >> 1) & 1 : 2;
  const int k = ks + 1;
  return k >= 4 && !(k & 2) && k < n ? k & 1 : 2;
}

constexpr uint32_t Q_RANGES = NBETA * NH + P_EARLY * 5;
constexpr int TAIL_STEPS = (NBETA - P_EARLY) * 64, NRANGE = NCTA / 5;
struct Work { int kind, mode, k0, nsteps, range, beta, sub; };
struct Sched { uint16_t queue[Q_RANGES]; uint32_t piece[NRANGE + 1][4]; };
constexpr Sched make_sched() {
  Sched s{};
  int q = 0, a = 0;
  for (int pass = 0; pass < 2; pass++)
    for (int b = pass ? B_LATE : 0; b < NBETA; b++)
      for (int h = pass ? H_LATE : 0; h < (pass || b < B_LATE ? NH : H_LATE); h++) {
        if (a >= P_POS && (a - P_POS) % P_STRIDE == 0 && (a - P_POS) / P_STRIDE < P_EARLY)
          for (int col = 0; col < 5; col++) s.queue[q++] = 0x8000 | col << 8 | (a - P_POS) / P_STRIDE;
        s.queue[q++] = b << 5 | h;
        a++;
      }
  constexpr uint32_t T[NRANGE * 2] = {PIECE_TABLE};
  for (int g = 0; g <= NRANGE; g++)
    for (int n = 0; n < 4; n++) s.piece[g][n] = g < NRANGE && n < 2 ? T[2 * g + n] : 2u << 30;
  return s;
}
__constant__ Sched c_sched = make_sched();
__device__ __forceinline__ Work decode(uint32_t d) {
  Work w;
  w.kind = d >> 30; if (w.kind == 3) w.kind = 1;
  w.mode = (d >> 28) & 3; w.k0 = (d >> 22) & 63;
  if (w.kind == 0) { w.beta = (d >> 5) & 31; w.sub = d & 31; w.nsteps = DM / 64; }
  else { w.beta = d & 31; w.sub = (d >> 8) & 7; w.nsteps = ((d >> 16) & 63) + 1; }
  w.range = ((d >> 11) & 31) * 5 + w.sub;
  return w;
}

__device__ __forceinline__ bool reached(const unsigned* cnt, unsigned target) {
  unsigned v;
  asm volatile("ld.acquire.gpu.global.u32 %0, [%1];" : "=r"(v) : "l"(cnt) : "memory");
  return (int)(v - target) >= 0;
}
__device__ __forceinline__ void wait_count(const unsigned* cnt, unsigned target) {
  unsigned n = 0;
  while (!__all_sync(0xffffffffu, reached(cnt, target))) { if (++n > (1u << 24)) __trap(); }
}
__device__ __forceinline__ uint32_t lds(uint32_t a) { uint32_t v; asm volatile("ld.volatile.shared.u32 %0, [%1];" : "=r"(v) : "r"(a) : "memory"); return v; }

#define TRACE(u, e)
#define T3(u, e)
#define T2C(u, e)
#define T2P(u, r, e)
#define TTAIL(k)
#define TCLK(k)
#define TRACE_P(u, e)
#define TRACE_IN(u, e)

struct Ctx {
  uint32_t sb;
  int wg, warp;
  uint32_t mqk, mpv;
  bool lead;
  int src;
};
template <int N> __device__ __forceinline__ uint32_t dhi(uint32_t lo) { return 0x40000040u + (lo >> (26 + N)); }
template <int N> __device__ __forceinline__ uint64_t full_desc(uint32_t addr, uint32_t slot) { return desc64(addr >> 4, dhi<N>(slot)); }
__device__ __forceinline__ void release(const Ctx& c, uint32_t slot) {
  if (c.lead) mbar_arrive(c.sb + BAR_EMPTY + slot * 8);
}
__device__ __forceinline__ uint32_t acquire(const Ctx& c, Ring& r) {
  const uint32_t s = r.slot;
  mbar_wait_w(c.sb + BAR_FULL + s * 8, r.phase);
  r.next();
  return s;
}
__device__ __forceinline__ void mbar_wait2_w(uint32_t b0, uint32_t p0, uint32_t b1, uint32_t p1) {
  uint32_t n = 0;
  while (!__all_sync(0xffffffffu, mbar_try(b0, p0) & mbar_try(b1, p1))) {
    if (++n > (1u << 22)) __trap();
  }
}
__device__ __forceinline__ void mbar_wait3_w(uint32_t b0, uint32_t p0, uint32_t b1, uint32_t p1, uint32_t b2, uint32_t p2) {
  uint32_t n = 0;
  while (!__all_sync(0xffffffffu, mbar_try(b0, p0) & mbar_try(b1, p1) & mbar_try(b2, p2))) {
    if (++n > (1u << 22)) __trap();
  }
}
__device__ __forceinline__ void acquire2(const Ctx& c, Ring& r, uint32_t& s0, uint32_t& s1) {
  const uint32_t p0 = r.phase;
  s0 = r.slot; r.next(); s1 = r.slot;
  mbar_wait2_w(c.sb + BAR_FULL + s0 * 8, p0, c.sb + BAR_FULL + s1 * 8, r.phase);
  r.next();
}
__device__ __forceinline__ void staged(const Ctx& c, int part) {
  fence_async_smem();
  __syncwarp();
  mbar_arrive_warp(c.sb + BAR_STG + c.wg * 16 + part * 8);
}

template <int WG, bool FIRST, int H>
__device__ __forceinline__ void proj_half(const Ctx& c, float (&acc)[64], uint32_t w, uint32_t x) {
  uint64_t a = full_desc<0>(c.sb + (WG ? w : x) * SLOT + H * 8192, x);
  uint64_t b = WG ? full_desc<1>(c.sb + x * SLOT, x) : desc64(sdesc(c.sb + w * SLOT, 8192), dhi<1>(x));
  wg_fence();
  if (WG) { if (FIRST) wgmma_proj96_init(acc, a, b, 0); else wgmma_proj96(acc, a, b, 1); }
  else { if (FIRST) wgmma_proj_init(acc, a, b, 0); else wgmma_proj(acc, a, b, 1); }
#pragma unroll
  for (int k = 1; k < 4; k++) { dadd(a, WG ? 128 : 2); dadd(b, WG ? 2 : 128); if (WG) wgmma_proj96(acc, a, b, 1); else wgmma_proj(acc, a, b, 1); }
  wg_commit();
}

__device__ __forceinline__ void proj_store16(uint32_t a, const float* f, float sc) {
  stsm4t(a, pack_bf16(f[0] * sc, f[1] * sc), pack_bf16(f[2] * sc, f[3] * sc), pack_bf16(f[4] * sc, f[5] * sc), pack_bf16(f[6] * sc, f[7] * sc));
}

__device__ __forceinline__ uint32_t stage_off(const Ctx& c) {
  const int lane = lane_now(), mi = lane >> 3, r8 = lane & 7;
  return ((mi >> 1) * 8 + r8) * 128 + (((2 * c.warp + (mi & 1)) ^ r8) << 4);
}
__device__ __forceinline__ uint32_t q3_swz(uint32_t r8) { return ((r8 & 3) << 1) | (r8 >> 2); }
template <int H>
__device__ __forceinline__ void stage_t2(const Ctx& c, const float (&a)[64], float sc) {
  const uint32_t base = c.sb + QBUF_OFF + 2 * 16384 + H * 8192 + stage_off(c);
#pragma unroll
  for (int jj = 0; jj < 4; jj++) proj_store16(base + jj * 2048, &a[jj * 8], sc);
}
template <int H, bool IS_Q>
__device__ __forceinline__ void stage_t3(const Ctx& c, const float (&a)[64], float sc) {
  const uint32_t off = stage_off(c), r8 = (off >> 7) & 7;
  const uint32_t t3 = c.sb + QBUF_OFF + 3 * 16384 + H * 4096 + (IS_Q ? off ^ ((r8 ^ q3_swz(r8)) << 4) : off);
  proj_store16(t3, &a[32], sc);
  proj_store16(t3 + 2048, &a[40], sc);
}

template <bool TRANS>
__device__ __forceinline__ void add16(uint32_t a, float* f) {
  uint32_t r[4];
  if (TRANS) asm volatile("ldmatrix.sync.aligned.m8n8.x4.trans.shared.b16 {%0, %1, %2, %3}, [%4];"
                          : "=r"(r[0]), "=r"(r[1]), "=r"(r[2]), "=r"(r[3]) : "r"(a) : "memory");
  else ldsm4(a, r[0], r[1], r[2], r[3]);
#pragma unroll
  for (int i = 0; i < 4; i++) { f[2 * i] += __uint_as_float(r[i] << 16); f[2 * i + 1] += __uint_as_float(r[i] & 0xffff0000u); }
}

__device__ __forceinline__ void trace_dump(const Ctx& c) {
}
struct RowSum { float l0, l1; };
__device__ __forceinline__ const char* o_addr(uint32_t item, int row) {
  const int lane = lane_now();
  return reinterpret_cast<const char*>(g_o) + ((item * (2 * SQ) + row) * 128 + (lane >> 2) * 128 + (lane & 3) * 16);
}
template <int MODE, int I0 = 0, int NI = 4>
__device__ __forceinline__ void o_emit(const char* p, const float (&o)[64], float inv) {
#pragma unroll
  for (int i = I0; i < I0 + NI; i++) {
    uint32_t q[4];
#pragma unroll
    for (int j = 0; j < 4; j++) {
      const float* f = &o[16 * i + 4 * j];
      q[j] = MODE == 2 ? pack_bf16((f[0] + f[2]) * inv, (f[1] + f[3]) * inv) : pack_bf16(f[2 * MODE] * inv, f[2 * MODE + 1] * inv);
    }
    asm volatile("st.global.v4.b32 [%0], {%1, %2, %3, %4};"
                 ::"l"(p + (i >> 1) * (SQ * 128) + (i & 1) * 64), "r"(q[0]), "r"(q[1]), "r"(q[2]), "r"(q[3]) : "memory");
  }
}
__device__ __forceinline__ void o_done(const Ctx& c) {
  __syncwarp();
  mbar_arrive_warp(c.sb + BAR_OUT);
  __syncwarp();
}
template <int WG, int PART>
__device__ __forceinline__ void o_first(const Ctx& c, uint32_t item, const float (&o)[64], const RowSum& inv) {
  constexpr int N = (PACK_EARLY >> (4 * WG)) & 15, B = PART ? N : 0, E = PART ? 8 : N;
  const char* p = o_addr(item, WG ? 192 + 8 * c.warp : 16 * c.warp);
  if constexpr (B < 4) o_emit<WG ? 2 : 0, B, (E < 4 ? E : 4) - B>(p, o, inv.l0);
  if constexpr (!WG && E > 4) o_emit<1, (B > 4 ? B : 4) - 4, E - (B > 4 ? B : 4)>(p + 1024, o, inv.l1);
}
template <int K0, int K1>
__device__ __forceinline__ void o_piece(const Ctx& c, const char* p, int k, const float (&o)[64], const RowSum& inv) {
  constexpr int NI = 8 / O_STEPS, M = K0 * NI / 4;
  if constexpr (K1 - K0 == 1) {
    o_emit<M, K0 * NI % 4, NI>(p + M * 1024, o, M ? inv.l1 : inv.l0);
    if (K1 == O_STEPS) o_done(c);
  } else {
    if (k <= (K0 + K1) / 2) o_piece<K0, (K0 + K1) / 2>(c, p, k, o, inv); else o_piece<(K0 + K1) / 2, K1>(c, p, k, o, inv);
  }
}
template <int WG>
__device__ __forceinline__ void o_second(const Ctx& c, uint32_t item, int k, float (&o)[64], const RowSum& inv) {
  reg_fence(o);
  o_piece<0, O_STEPS>(c, o_addr(item, 64 + 64 * WG + 16 * c.warp), k, o, inv);
}
template <int WG>
__device__ __forceinline__ void release_q(const Ctx& c) {
#pragma unroll
  for (int t = 0; t < 2; t++)
    if (c.lead) asm volatile("mbarrier.arrive.shared::cta.b64 _, [%0], 2;" ::"r"(c.sb + BAR_EMPTY + (NS + 2 * WG + t) * 8) : "memory");
  __syncwarp();
}
struct Slots { uint32_t w, x, o, po; };
template <int WG>
__device__ __forceinline__ void acc_fence(float (&a)[64]) {
#pragma unroll
  for (int i = 0; i < (WG ? 48 : 64); i++) asm volatile("" : "+f"(a[i])::"memory");
}
template <int WG>
__device__ __forceinline__ void begin_acquire(const Ctx& c, Ring& r, Slots& h, bool wait) {
  const uint32_t s0 = r.slot, p0 = r.phase, f = c.sb + BAR_FULL;
  r.next();
  const uint32_t p1 = r.phase;
  h.w = r.slot; r.next();
  h.x = WG ? r.slot : s0; h.o = WG ? s0 : r.slot; h.po = r.phase;
  if (wait) { if (WG) mbar_wait3_w(f + s0 * 8, p0, f + h.w * 8, p1, f + h.x * 8, r.phase); else mbar_wait2_w(f + s0 * 8, p0, f + h.w * 8, p1); }
  r.next();
}
template <int WG>
__device__ __forceinline__ void proj_begin(const Ctx& c, Ring& r, float (&a0)[64], Slots& h, bool wait) {
  begin_acquire<WG>(c, r, h, wait);
  proj_half<WG, true, 0>(c, a0, h.w, h.x);
  if (WG) release(c, h.o);
}
template <int WG>
__device__ __forceinline__ void proj_main(const Ctx& c, Ring& r, float (&a0)[64], float (&a1)[64], Slots& h, int n, int unit,
                                          uint32_t item, int nq, float (&o1)[64], const RowSum& inv) {
  constexpr bool DEEP = (PDEPTH >> WG) & 1;
  T2C(unit, 3);
  int ks = 1;
#pragma unroll 1
  do {
    const Slots p = h;
    const uint32_t b = borrow(ks, n), tile = NS + (WG ? 3 - b : b), f = c.sb + BAR_FULL;
    const uint32_t s0 = b != 2 ? tile : r.slot, p0 = b != 2 ? (r.xp >> b) & 1 : r.phase;
    r.next_if(b == 2);
    const uint32_t p1 = r.phase;
    h.w = r.slot; r.next();
    const uint32_t s2 = b != 2 ? tile : r.slot;
    h.po = b != 2 ? p0 : r.phase;
    r.next_if(b == 2);
    r.xp ^= 1 << b;
    h.x = WG ? s2 : s0; h.o = WG ? s0 : s2;
    mbar_wait3_w(f + s0 * 8, p0, f + h.w * 8, p1, f + (WG ? s2 : p.o) * 8, WG ? h.po : p.po);
    if (ks < 10) T2C(unit, ks * 4);
    if (DEEP) {
      proj_half<WG, false, 0>(c, a0, h.w, h.x);
      release(c, WG ? h.o : p.o);
      if (ks < 10) T2C(unit, ks * 4 + 1);
      wg_wait<1>();
      if (ks < 10) T2C(unit, ks * 4 + 2);
      release(c, p.x); release(c, p.w);
    } else {
      release(c, WG ? h.o : p.o);
      wg_wait<0>();
      release(c, p.x); release(c, p.w);
      if (ks < 10) T2C(unit, ks * 4 + 1);
      proj_half<WG, false, 0>(c, a0, h.w, h.x);
      if (ks < 10) T2C(unit, ks * 4 + 2);
    }
    proj_half<WG, false, 1>(c, a1, h.w, h.x);
    if (ks < 10) T2C(unit, ks * 4 + 3);
    if (ks <= nq) o_second<WG>(c, item, ks, o1, inv);
  } while (++ks != n);
  {
    const uint32_t e0 = c.sb + BAR_EMPTY + (NS + 3 * WG) * 8, e1 = c.sb + BAR_EMPTY + (NS + 1 + WG) * 8;
    const uint32_t p0 = (r.xp ^ unit ^ 1) & 1, p1 = ((r.xp >> 1) ^ unit ^ 1) & 1;
    if (WG) mbar_wait2_w(e0, p0, e1, p1); else mbar_wait3_w(e0, p0, e1, p1, c.sb + BAR_FULL + h.o * 8, h.po);
  }
  if (!WG) release(c, h.o);
  wg_wait<1>();
  acc_fence<WG>(a0);
}
template <int WG>
__device__ __forceinline__ void proj_end(const Ctx& c, float (&a1)[64], const Slots& h) {
  wg_wait<0>();
  acc_fence<WG>(a1);
  release(c, h.x); release(c, h.w);
}
__device__ __forceinline__ uint32_t get_desc(const Ctx& c, int i) {
  uint32_t d;
  mbar_wait_w(c.sb + BAR_DESC, (i - 1) & 1);
  asm volatile("ld.volatile.shared.u32 %0, [%1];" : "=r"(d) : "r"(c.sb + DESC_OFF + (i & 3) * 4) : "memory");
  return __shfl_sync(0xffffffffu, d, 0);
}

__device__ __forceinline__ float quad_max(float x) {
  x = fmaxf(x, __shfl_xor_sync(0xffffffffu, x, 1));
  return fmaxf(x, __shfl_xor_sync(0xffffffffu, x, 2));
}
__device__ __forceinline__ float quad_sum(float x) {
  x += __shfl_xor_sync(0xffffffffu, x, 1);
  return x + __shfl_xor_sync(0xffffffffu, x, 2);
}
template <bool SP, bool FIRST>
__device__ __forceinline__ void exps(const Ctx& c, const float (&s)[32], uint32_t (&p)[SP ? 8 : 16], RowSum& st) {
  if constexpr (SP) {
    uint32_t q[8];
    float t;
#pragma unroll
    for (int j = 0; j < 8; j++) {
      const float e0 = ex2(s[4 * j] + s[4 * j + 2]), e1 = ex2(s[4 * j + 1] + s[4 * j + 3]);
      if (j == 0) t = e0 + e1; else t += e0 + e1;
      q[j] = pack_bf16(e0, e1);
    }
    const bool odd = c.src & 2;
#pragma unroll
    for (int g = 0; g < 4; g++) {
      p[2 * g] = __shfl_sync(0xffffffffu, odd ? q[2 * g + 1] : q[2 * g], c.src);
      p[2 * g + 1] = __shfl_sync(0xffffffffu, odd ? q[2 * g] : q[2 * g + 1], c.src ^ 1);
    }
    st.l0 = FIRST ? t : st.l0 + t;
  } else {
    float t0, t1;
#pragma unroll
    for (int j = 0; j < 8; j++) {
      const float e0 = ex2(s[4 * j]), e1 = ex2(s[4 * j + 1]), e2 = ex2(s[4 * j + 2]), e3 = ex2(s[4 * j + 3]);
      if (j == 0) { t0 = e0 + e1; t1 = e2 + e3; } else { t0 += e0 + e1; t1 += e2 + e3; }
      p[2 * j] = pack_bf16(e0, e1);
      p[2 * j + 1] = pack_bf16(e2, e3);
    }
    st.l0 = FIRST ? t0 : st.l0 + t0;
    st.l1 = FIRST ? t1 : st.l1 + t1;
  }
}
template <bool SP>
__device__ __forceinline__ bool finish_sums(RowSum& st) {
  const float a = quad_sum(st.l0), b = SP ? a : quad_sum(st.l1);
  st.l0 = __fdividef(1.f, a); st.l1 = __fdividef(1.f, b);
  return !DEV_HALF && !(a >= SUM_LO && a <= SUM_HI && b >= SUM_LO && b <= SUM_HI);
}
template <bool SP, bool INIT, int SITE, bool COMMIT = true>
__device__ __forceinline__ void issue_qk(const Ctx& c, float (&s)[32], const uint32_t (&qs)[16], uint32_t dq, uint32_t dk) {
  uint64_t a = desc64(dq, dhi<SITE & 1>(dk)), b = desc64(dk, dhi<1 - (SITE & 1)>(dk));
  if (SP) {
    if (INIT) wgmma_qk_sp_init(s, qs[0], qs[1], qs[2], qs[3], b, 0, c.mqk); else wgmma_qk_sp(s, qs[0], qs[1], qs[2], qs[3], b, 0, c.mqk);
#pragma unroll
    for (int k = 1; k < 4; k++) { dadd(b, k == 2 ? 508 : 4); wgmma_qk_sp(s, qs[4 * k], qs[4 * k + 1], qs[4 * k + 2], qs[4 * k + 3], b, 1, c.mqk); }
  } else {
    if (INIT) wgmma_qk_init(s, a, b, 0); else wgmma_qk(s, a, b, 0);
#pragma unroll
    for (int k = 1; k < 8; k++) { dadd(a, k == 4 ? 506 : 2); dadd(b, k == 4 ? 506 : 2); wgmma_qk(s, a, b, 1); }
  }
  if (COMMIT) wg_commit();
}
template <bool SP, bool ACC, int SITE, bool SPLIT = false>
__device__ __forceinline__ void issue_pv(const Ctx& c, float (&o)[64], const uint32_t (&p)[SP ? 8 : 16], uint32_t dv) {
  uint64_t b = desc64(dv, dhi<SITE & 1>(dv));
  if constexpr (SP) {
    if (ACC) wgmma_pv_sp(o, p[0], p[1], p[2], p[3], b, 1, c.mpv); else wgmma_pv_sp_init(o, p[0], p[1], p[2], p[3], b, 0, c.mpv);
    if (SPLIT) wg_commit();
    dadd(b, 256);
    wgmma_pv_sp(o, p[4], p[5], p[6], p[7], b, 1, c.mpv);
  } else {
    if (ACC) wgmma_pv(o, p[0], p[1], p[2], p[3], b, 1); else wgmma_pv_init(o, p[0], p[1], p[2], p[3], b, 0);
#pragma unroll
    for (int k = 1; k < 4; k++) { dadd(b, 128); wgmma_pv(o, p[4 * k], p[4 * k + 1], p[4 * k + 2], p[4 * k + 3], b, 1); }
  }
  wg_commit();
}
__device__ __forceinline__ void stage_rows(const Ctx& c, uint32_t tile_addr, const float (&o)[64], float sc) {
  const int lane = lane_now(), mi = lane >> 3, r8 = lane & 7;
  const uint32_t row_addr = tile_addr + (16 * c.warp + (mi & 1) * 8 + r8) * 128;
#pragma unroll
  for (int jj = 0; jj < 8; jj++) {
    const int b = jj * 8;
    stsm4(row_addr + (jj >> 2) * 8192 + (((((2 * jj) & 7) + (mi >> 1)) ^ r8) << 4),
          pack_bf16(o[b] * sc, o[b + 1] * sc), pack_bf16(o[b + 2] * sc, o[b + 3] * sc),
          pack_bf16(o[b + 4] * sc, o[b + 5] * sc), pack_bf16(o[b + 6] * sc, o[b + 7] * sc));
  }
}

__device__ __forceinline__ void redo_tile(const Ctx& c, uint32_t q_addr, uint32_t half, const __nv_bfloat16* kp, const __nv_bfloat16* vp,
                                          uint32_t item, int row) {
  float o[64];
  const int lane = lane_now(), g = lane >> 2, cc = lane & 3, mi = lane >> 3, r8 = lane & 7;
  const uint32_t qa = q_addr + (half == 4096 ? 8 * c.warp + r8 : 16 * c.warp + (mi & 1) * 8 + r8) * 128, swz = half == 4096 ? q3_swz(r8) : r8;
  const uint32_t* kq = reinterpret_cast<const uint32_t*>(kp + g * DH) + cc;
  const unsigned short* vq = reinterpret_cast<const unsigned short*>(vp + 2 * cc * DH) + g;
  float m0 = -INFINITY, m1 = -INFINITY, l0 = 0.f, l1 = 0.f;
#pragma unroll
  for (int i = 0; i < 64; i++) o[i] = 0.f;
#pragma unroll 1
  for (int kb = 0; kb < SK / 16; kb++) {
    float z[8] = {0.f, 0.f, 0.f, 0.f, 0.f, 0.f, 0.f, 0.f};
#pragma unroll 2
    for (int kk = 0; kk < 8; kk++) {
      uint32_t a0, a1, a2, a3;
      ldsm4(qa + (kk >> 2) * half + ((((kk & 3) * 2 + (mi >> 1)) ^ swz) << 4), a0, a1, a2, a3);
      const uint32_t* kr = kq + kb * (16 * DH / 2) + kk * 8;
      mma16816(z[0], z[1], z[2], z[3], a0, a1, a2, a3, __ldg(kr), __ldg(kr + 4));
      mma16816(z[4], z[5], z[6], z[7], a0, a1, a2, a3, __ldg(kr + 8 * DH / 2), __ldg(kr + 8 * DH / 2 + 4));
    }
    const float n0 = fmaxf(m0, quad_max(fmaxf(fmaxf(z[0], z[1]), fmaxf(z[4], z[5]))));
    const float n1 = fmaxf(m1, quad_max(fmaxf(fmaxf(z[2], z[3]), fmaxf(z[6], z[7]))));
    const float al0 = ex2(m0 - n0), al1 = ex2(m1 - n1);
    m0 = n0; m1 = n1;
#pragma unroll
    for (int i = 0; i < 8; i++) z[i] = ex2(z[i] - ((i & 2) ? n1 : n0));
    l0 = l0 * al0 + (z[0] + z[1]) + (z[4] + z[5]);
    l1 = l1 * al1 + (z[2] + z[3]) + (z[6] + z[7]);
    const uint32_t a0 = pack_bf16(z[0], z[1]), a1 = pack_bf16(z[2], z[3]), a2 = pack_bf16(z[4], z[5]), a3 = pack_bf16(z[6], z[7]);
    const unsigned short* vr = vq + kb * (16 * DH);
#pragma unroll
    for (int nb = 0; nb < 16; nb++) {
      o[4 * nb] *= al0; o[4 * nb + 1] *= al0; o[4 * nb + 2] *= al1; o[4 * nb + 3] *= al1;
      const uint32_t b0 = __ldg(vr + nb * 8) | ((uint32_t)__ldg(vr + nb * 8 + DH) << 16);
      const uint32_t b1 = __ldg(vr + nb * 8 + 8 * DH) | ((uint32_t)__ldg(vr + nb * 8 + 9 * DH) << 16);
      mma16816(o[4 * nb], o[4 * nb + 1], o[4 * nb + 2], o[4 * nb + 3], a0, a1, a2, a3, b0, b1);
    }
  }
  const char* p = o_addr(item, row);
  o_emit<0>(p, o, __fdividef(1.f, quad_sum(l0)));
  o_emit<1>(half == 4096 ? p : p + 1024, o, __fdividef(1.f, quad_sum(l1)));
}

template <bool SPA, bool SPB, int SITE, int ID>
__device__ __forceinline__ void batch(const Ctx& c, float (&s)[32], const uint32_t (&qs)[16], uint32_t dq, uint32_t dk, float (&ob)[64],
                                      uint32_t (&pb)[SPB ? 8 : 16], uint32_t dv) {
  if constexpr (SPA) {
    reg_fence(pb);
    wg_fence();
    issue_pv<SPB, true, ID>(c, ob, pb, dv);
    issue_qk<SPA, false, ID>(c, s, qs, dq, dk);
  } else {
    constexpr bool EARLY = ((QK_EARLY_MASK >> (SITE + (SPB ? 2 : 0))) & 1) != 0;
    if (!EARLY) reg_fence(pb);
    wg_fence();
    issue_qk<SPA, false, ID, !SPB>(c, s, qs, dq, dk);
    if (EARLY) { reg_fence(pb); wg_fence(); }
    issue_pv<SPB, true, ID, SPB>(c, ob, pb, dv);
  }
}

template <bool SP0>
__device__ __forceinline__ bool attention(Ctx c, Ring& r, int unit, uint32_t& d, const float (&a0)[64], float (&o0)[64], float (&o1)[64],
                                          RowSum& st0, RowSum& st1, const Slots& h, uint32_t item) {
  constexpr bool SP1 = false;
  if (SP0) { c.mqk = META_QK + (d >> 28); c.mpv = META_PV + (d >> 28); asm volatile("" : "+r"(c.mqk), "+r"(c.mpv)); }
  if (SP0) { const int lane = lane_now(); c.src = (lane & 28) | ((lane & 1) << 1) | ((lane >> 1) & 1); }
  float s[32];
  uint32_t p0[SP0 ? 8 : 16], p1[16];
  const uint32_t q0a = c.sb + QBUF_OFF + (SP0 ? 3 : 0) * 16384, q1a = c.sb + QBUF_OFF + (SP0 ? 2 : 1) * 16384;
  const uint32_t dq0 = sdesc(q0a, 0), dq1 = sdesc(q1a, 0);
  uint32_t sk, sv, sn;
  uint32_t qs[16];
  T2C(unit, 40);
  if (SP0) {
    stage_t3<0, true>(c, a0, SM_C);
    stage_t2<0>(c, a0, SM_C);
    T2C(unit, 41);
    proj_end<1>(c, o0, h);
    T2C(unit, 42);
    stage_t3<1, true>(c, o0, SM_C);
    stage_t2<1>(c, o0, SM_C);
    sk = acquire(c, r);
    fence_async_smem();
    T2C(unit, 43);
    bar_sync(1, LAG_BAR & 14 ? 256 : 128);
    const int lane = lane_now(), g = lane >> 2, cc = lane & 3;
    const uint32_t qa = q0a + (8 * c.warp + g) * 128 + (cc & 1) * 8;
#pragma unroll
    for (int k = 0; k < 8; k++)
      asm volatile("ld.shared.v2.u32 {%0, %1}, [%2];" : "=r"(qs[2 * k]), "=r"(qs[2 * k + 1])
                   : "r"(qa + (k >> 2) * 4096 + ((((k & 3) * 2 + (cc >> 1)) ^ q3_swz(g)) << 4)) : "memory");
    TRACE(unit, 2);
    T2C(unit, 44);
    float s1[32];
    wg_fence();
    issue_qk<SP1, true, 1>(c, s1, qs, dq1, sdesc(c.sb + sk * SLOT, 0));
    reg_fence(qs);
    wg_fence();
    issue_qk<SP0, true, 0>(c, s, qs, dq0, sdesc(c.sb + sk * SLOT, 0));
    T2C(unit, 45);
    acquire2(c, r, sv, sn);
    wg_wait<1>();
    reg_fence(s1);
    T2C(unit, 47);
    exps<SP1, true>(c, s1, p1, st1);
    reg_fence(p1);
    wg_fence();
    issue_pv<SP1, false, 1>(c, o1, p1, sdesc(c.sb + sv * SLOT, 8192));
    if (LAG_BAR & 1) asm volatile("bar.arrive 4, 256;" ::: "memory");
    wg_wait<1>();
    reg_fence(s);
    T2C(unit, 48);
    release(c, sk);
    sk = sn;
    exps<SP0, true>(c, s, p0, st0);
    reg_fence(p0);
    wg_fence();
    issue_pv<SP0, false, 0>(c, o0, p0, sdesc(c.sb + sv * SLOT, 8192));
    issue_qk<SP0, false, 2>(c, s, qs, dq0, sdesc(c.sb + sk * SLOT, 0));
    T2C(unit, 49);
    sn = acquire(c, r);
    T2C(unit, 50);
    wg_wait<0>();
    reg_fence(s);
  } else {
    float s1[32];
    stage_rows(c, q0a, a0, SM_C);
    sk = acquire(c, r);
    fence_async_smem();
    T2C(unit, 41);
    proj_end<0>(c, o0, h);
    TRACE(unit, 2);
    T2C(unit, 42);
    __syncwarp();
    wg_fence();
    issue_qk<SP0, true, 0>(c, s, qs, dq0, sdesc(c.sb + sk * SLOT, 0));
    if (LAG_BAR & 8) asm volatile("bar.arrive 1, 256;" ::: "memory");
    T2C(unit, 43);
    reg_fence(o0);
    stage_rows(c, q1a, o0, SM_C);
    fence_async_smem();
    __syncwarp();
    T2C(unit, 44);
    if (LAG_BAR & 4) asm volatile("bar.arrive 1, 256;" ::: "memory");
    wg_fence();
    issue_qk<SP1, true, 1>(c, s1, qs, dq1, sdesc(c.sb + sk * SLOT, 0));
    if (LAG_BAR & 2) asm volatile("bar.arrive 1, 256;" ::: "memory");
    T2C(unit, 45);
    acquire2(c, r, sv, sn);
    wg_wait<1>();
    reg_fence(s);
    T2C(unit, 47);
    exps<SP0, true>(c, s, p0, st0);
    reg_fence(p0);
    wg_fence();
    issue_qk<SP0, false, 2>(c, s, qs, dq0, sdesc(c.sb + sn * SLOT, 0));
    issue_pv<SP0, false, 0>(c, o0, p0, sdesc(c.sb + sv * SLOT, 8192));
    wg_wait<2>();
    reg_fence(s1);
    T2C(unit, 48);
    release(c, sk);
    sk = sn;
    exps<SP1, true>(c, s1, p1, st1);
    reg_fence(p1);
    wg_fence();
    issue_pv<SP1, false, 1>(c, o1, p1, sdesc(c.sb + sv * SLOT, 8192));
    T2C(unit, 49);
    sn = acquire(c, r);
    if (LAG_BAR & 1) bar_sync(4, 256);
    T2C(unit, 50);
    wg_wait<1>();
    reg_fence(s);
  }
  TRACE_IN(unit, 4);
  T2C(unit, 51);
#pragma unroll 1
  for (int j = 1; j < 15; j++) {
    const uint32_t sv_prev = sv, sk_prev = sk;
    sv = sn;
    const uint32_t dv = sdesc(c.sb + sv * SLOT, 8192);
    reg_fence(p0);
    exps<SP0, false>(c, s, p0, st0);
    batch<SP1, SP0, 0, 3>(c, s, qs, dq1, sdesc(c.sb + sk * SLOT, 0), o0, p0, dv);
    sk = acquire(c, r);
    wg_wait<1>();
    reg_fence(s); reg_fence(p1);
    release(c, sv_prev); release(c, sk_prev);
    exps<SP1, false>(c, s, p1, st1);
    batch<SP0, SP1, 1, 4>(c, s, qs, dq0, sdesc(c.sb + sk * SLOT, 0), o1, p1, dv);
    sn = acquire(c, r);
    if (SP0) wg_wait<0>(); else wg_wait<1>();
    reg_fence(s);
  }
  TRACE_IN(unit, 5);
  T2C(unit + 1, 52);
  const uint32_t sv_prev = sv;
  sv = sn;
  const uint32_t dv = sdesc(c.sb + sv * SLOT, 8192);
  reg_fence(p0);
  exps<SP0, false>(c, s, p0, st0);
  batch<SP1, SP0, 0, 5>(c, s, qs, dq1, sdesc(c.sb + sk * SLOT, 0), o0, p0, dv);
  asm volatile("ld.volatile.shared.u32 %0, [%1];" : "=r"(d) : "r"(c.sb + DESC_OFF + ((unit + 1) & 3) * 4) : "memory");
  wg_wait<1>();
  reg_fence(s); reg_fence(p1);
  T2C(unit + 1, 53);
  release(c, sv_prev); release(c, sk);
  d = __shfl_sync(0xffffffffu, d, 0);
  const bool bad0 = finish_sums<SP0>(st0);
  exps<SP1, false>(c, s, p1, st1);
  reg_fence(p1);
  wg_fence();
  issue_pv<SP1, true, 2>(c, o1, p1, dv);
  T2C(unit + 1, 54);
  bool have = EARLY_BEG;
  if (EARLY_BEG) {
    Ring t = r;
#pragma unroll
    for (int k = 0; k < 2 + SP0; k++) { have &= mbar_test(c.sb + BAR_FULL + t.slot * 8, t.phase); t.next(); }
  }
  const bool bad = finish_sums<SP1>(st1) | bad0;
  if ((PACK_EARLY >> (4 * SP0)) & 15) {
    wg_wait<1>();
    reg_fence(o0);
    o_first<SP0, 0>(c, item, o0, st0);
  }
  T2C(unit + 1, 55);
  if (EARLY_BEG && d < (2u << 30) && !__all_sync(0xffffffffu, have)) { Ring t = r; Slots u; begin_acquire<SP0>(c, t, u, true); }
  T2C(unit + 1, 56);
  wg_wait<0>();
  reg_fence(o0); reg_fence(o1);
  T2C(unit + 1, 57);
  release(c, sv);
  return bad;
}
template <int WG>
__device__ __forceinline__ bool wg_any(bool p) {
  uint32_t any;
  asm volatile("{\n.reg .pred p, q;\nsetp.ne.u32 p, %1, 0;\nbar.red.or.pred q, %2, 128, p;\nselp.u32 %0, 1, 0, q;\n}"
               : "=r"(any) : "r"((uint32_t)p), "n"(2 + WG) : "memory");
  return __any_sync(0xffffffffu, any);
}

template <int WG>
__device__ __forceinline__ void consumer(Ctx c, const __nv_bfloat16* const* kv) {
  c.wg = WG;
  Ring r{0, 0, 0};
  bool bad;
  float a0[64], a1[64], o1[64];
  Slots h;
  RowSum inv0, inv1;
  uint32_t d = blockIdx.x, dc = 0;
  int i = 0, nq;
begin:
  proj_begin<WG>(c, r, a0, h, true);
  proj_half<WG, true, 1>(c, a1, h.w, h.x);
  nq = 0;
#pragma unroll
  for (int k = 0; k < 64; k++) asm volatile("" : "=f"(o1[k]));
  asm volatile("" : "=f"(inv1.l0), "=f"(inv1.l1));
  while (true) {
    TRACE(i, 0); TRACE(i, 6);
    proj_main<WG>(c, r, a0, a1, h, d >> 30 ? ((d >> 16) & 63) + 1 : DM / 64, i, dc, nq, o1, inv1);
    dc = d;
    TRACE(i, 1);
    if (d >> 30) goto out_tile;
    bad = attention<WG>(c, r, i, d, a0, a1, o1, inv0, inv1, h, dc);
    if (!EARLY_BEG || d >= (2u << 30)) break;
    Ring t = r;
    begin_acquire<WG>(c, t, h, false);
    proj_half<WG, true, 0>(c, a0, h.w, h.x);
    T2C(i + 1, 58);
    reg_fence(a1);
    o_first<WG, 1>(c, dc, a1, inv0);
    if (__builtin_expect(wg_any<WG>(bad), 0)) {
      wg_wait<0>();
      acc_fence<WG>(a0);
      goto redo;
    }
    r = t;
    T2C(i + 1, 1);
    proj_half<WG, true, 1>(c, a1, h.w, h.x);
    if (WG) release(c, h.o);
    release_q<WG>(c);
    T2C(i + 1, 2);
    nq = O_STEPS;
    TRACE(i, 3); TRACE(i, 7);
    i++;
  }
  if (wg_any<WG>(bad)) goto redo;
  release_q<WG>(c);
  o_first<WG, 1>(c, dc, a1, inv0);
#pragma unroll
  for (int k = 1; k <= O_STEPS; k++) o_second<WG>(c, dc, k, o1, inv1);
  T2C(i + 1, 58);
next:
  TRACE(i, 3); TRACE(i, 7);
  if ((d >> 30) != 2) {
    i++;
    r.uniform();
    goto begin;
  }
  trace_dump(c);
  return;
out_tile:
  proj_end<WG>(c, a1, h);
  if (((d >> 28) & 3) == 2) {
    const int lane = lane_now(), mi = lane >> 3, r8 = lane & 7;
    const uint32_t off = c.sb + (WG ? stage_off(c) : (16 * c.warp + (mi & 1) * 8 + r8) * 128);
#pragma unroll 1
    for (int k = (d >> 5) & 3; k > 0; k--) {
      uint32_t s0, s1;
      if (WG) { acquire2(c, r, s0, s1); release(c, s0); release(c, s1); }
#pragma unroll
      for (int t = 0; t < 2; t++) {
        const uint32_t sp = acquire(c, r), base = off + sp * SLOT;
        if (WG) {
#pragma unroll
          for (int jj = 0; jj < (t ? 2 : 4); jj++) {
            add16<true>(base + jj * 2048, &a0[(t * 4 + jj) * 8]);
            add16<true>(base + jj * 2048 + (t ? 4096 : 8192), &a1[(t * 4 + jj) * 8]);
          }
        } else {
#pragma unroll
          for (int jj = 0; jj < 8; jj++) add16<false>(base + (jj >> 2) * 8192 + (((((2 * jj) & 7) + (mi >> 1)) ^ r8) << 4), t ? &a1[jj * 8] : &a0[jj * 8]);
        }
        release(c, sp);
      }
      if (!WG) { acquire2(c, r, s0, s1); release(c, s0); release(c, s1); }
    }
  }
  if (WG) { stage_t3<0, false>(c, a0, 1.f); stage_t3<1, false>(c, a1, 1.f); }
  else stage_rows(c, c.sb + QBUF_OFF, a0, 1.f);
  staged(c, 0);
  if (WG) { stage_t2<0>(c, a0, 1.f); stage_t2<1>(c, a1, 1.f); }
  else stage_rows(c, c.sb + QBUF_OFF + 16384, a1, 1.f);
  staged(c, 1);
  d = get_desc(c, i + 1);
  TRACE(i, 2);
  goto next;
redo:
  {
    const size_t hoff = (size_t)(dc & 511) * (SK * DH);
    const int br = (dc >> 9) & 1;
#pragma unroll 1
    for (int part = 0; part < 2; part++) {
      const int t = WG ? 3 - part : part;
      redo_tile(c, c.sb + QBUF_OFF + t * 16384, t == 3 ? 4096 : 8192, kv[br] + hoff, kv[2 + br] + hoff, dc,
                t * 64 + (t == 3 ? 8 : 16) * c.warp);
    }
    o_done(c);
    release_q<WG>(c);
  }
  goto next;
}

template <bool SIMPLE>
__global__ void __launch_bounds__(384, 1) mha_fused_kernel(const __grid_constant__ Params P) {
  extern __shared__ __align__(1024) uint8_t smem_raw[];
  const uint32_t sbase = smem_u32(smem_raw);
  const int tid = threadIdx.x;
  const int wg = __shfl_sync(0xffffffffu, tid >> 7, 0);
  const int warp = __shfl_sync(0xffffffffu, (tid >> 5) & 3, 0);
  const int lane = tid & 31;
  const int cta = blockIdx.x;

  if (tid == 0) T3(15, 0);
  if (tid >= 256 && tid < 256 + 18) asm volatile("prefetch.tensormap [%0];" ::"l"(&P.x[0][0] + (tid - 256)) : "memory");
  if (tid == 0) {
    if ((sbase & 1023) || sbase + SMEM_BYTES > 0x40000) __trap();
    for (int i = 0; i < NSX; i++) { mbar_init(sbase + BAR_FULL + i * 8, 1); mbar_init(sbase + BAR_EMPTY + i * 8, 8); }
    for (int i = 0; i < 4; i++) mbar_init(sbase + BAR_STG + i * 8, 4);
    mbar_init(sbase + BAR_OUT, 8);
    mbar_init(sbase + BAR_DESC, 1);
    mbar_init(sbase + BAR_GO, 1);
    asm volatile("fence.mbarrier_init.release.cluster;" ::: "memory");
  }
  __syncthreads();

  if (wg == 2) {
    asm volatile("setmaxnreg.dec.sync.aligned.u32 %0;" ::"n"(REG_P));
    if (warp == 1) {
      const uint32_t qb = sbase + QBUF_OFF;
      const uint32_t ep = __shfl_sync(0xffffffffu, *(volatile unsigned*)&g_epoch + 1, 0);
      asm volatile("st.volatile.shared.u32 [%0], %1;" ::"r"(sbase + EPOCH_OFF), "r"(ep) : "memory");
      uint32_t dc = cta, qi = 0, piece = 0, na = 0;
      TTAIL(0);
      for (int i = 0; (dc >> 30) != 2; i++) {
        mbar_wait_w(sbase + BAR_GO, i & 1);
        if (TLB_WARM && (dc >> 30) == 0) asm volatile(ELECT "st.global.u32 [%0], 0;\n}" ::"l"(g_o + dc * (2 * SQ * 64)) : "memory");
        if (piece == 0) {
          if (lane == 0) {
            qi = atomicAdd(&g_next, 1);
            if (qi == (SIMPLE ? NBETA * (NH + 5) : Q_RANGES) - 1) { g_next = 0; g_epoch = ep; }
          }
          qi = __shfl_sync(0xffffffffu, qi, 0) + (SIMPLE ? gridDim.x : NCTA);
        }
        uint32_t d;
        if (qi < Q_RANGES) { d = c_sched.queue[qi]; if (d & 0x8000) d ^= (1u << 30) | (63u << 16) | 0x8000; }
        else if (SIMPLE) { const uint32_t t = qi - NBETA * NH; d = t < NBETA * 5 ? (1u << 30) | (63u << 16) | (t % 5) << 8 | t / 5 : 2u << 30; }
        else { const uint32_t e = qi - Q_RANGES, g = e / 5; d = c_sched.piece[g][piece++] | (e - g * 5) << 8; }
        if ((d >> 30) == 1) {
          const uint32_t ok = __ballot_sync(0xffffffffu, reached(&g_cnt[lane & 1][d & 31], ep * (lane & 1 ? NH - H_LATE : H_LATE)));
          if (!(ok & 2)) d |= ((d >> 22) & 63) >= 2 * H_LATE - O_STEPS ? (2u << 30) | 128 : 128;
          if (!(ok & 1) || (O_STEPS > 4 && ((d >> 16) & 63) < O_STEPS)) d |= 2u << 30;
        }
        asm volatile("st.volatile.shared.u32 [%0], %1;" ::"r"(sbase + DESC_OFF + ((i + 1) & 3) * 4), "r"(d) : "memory");
        __syncwarp();
        mbar_arrive_warp(sbase + BAR_DESC);
        const Work w = decode(dc);
        dc = d;
        if (w.kind == 0) {
          mbar_wait_w(sbase + BAR_OUT, na++ & 1);
          TTAIL(1);
          T3(i, 0); T3(i, 1);
          asm volatile(ELECT "red.release.gpu.global.add.u32 [%0], 1;\n}" ::"l"(&g_cnt[w.sub >= H_LATE][w.beta]) : "memory");
          T3(i, 2);
          TTAIL(2);
          continue;
        }
        const bool fin = w.mode != 1;
        uint64_t pol, pol2;
        asm volatile("createpolicy.fractional.L2::evict_first.b64 %0, 1.0;" : "=l"(pol));
        asm volatile("createpolicy.fractional.L2::evict_normal.b64 %0, 1.0;" : "=l"(pol2));
        if (!fin) pol = pol2;
        const CUtensorMap* m = fin ? P.out_st : P.o_st;
        const int c1 = fin ? (w.beta & 15) * SQ : 0;
        const int c2 = fin ? (w.beta >> 4) * (DM / 64) + w.sub * 2 : NBETA * 64 + w.range * 2;
        uint32_t pend = 0;
#pragma unroll 1
        for (int e = 0; e < 4; e++) {
          const int t = (ST_ORDER >> (4 * e)) & 3;
          mbar_wait_w(sbase + BAR_STG + (t ^ (t >> 1)) * 8, (i - na) & 1);
          tma_st3_hint_w(m + (t == 3), qb + t * 16384, 0, c1 + t * 64, c2, pol);
          bulk_commit();
          T2P(i + 1, 5, 2 * e);
          if (pend) {
            bulk_wait_read<1>();
            mbar_arrive8_w(pend);
            T2P(i + 1, 5, 2 * e - 1);
          }
          pend = sbase + BAR_EMPTY + (NS + t) * 8;
          if ((ST_NOW >> e) & 1) {
            bulk_wait_read<0>();
            mbar_arrive8_w(pend);
            pend = 0;
            T2P(i + 1, 5, 2 * e + 1);
          }
        }
        T3(i, 0);
        if (piece >= 2) TTAIL(piece * 2 - 1);
        asm volatile("cp.async.bulk.wait_group 0;" ::: "memory");
        T3(i, 1);
        if (w.mode == 1) asm volatile(ELECT "st.release.gpu.global.u32 [%0], %1;\n}" ::"l"(&g_flag[w.range]), "r"(ep) : "memory");
        T3(i, 2);
        if (piece >= 2) TTAIL(piece * 2);
      }
      T3(15, 1);
    } else
    if (warp == 0) {
      Ring r{0, 1, 3};
      uint32_t d = cta;
      for (int i = 0;; i++) {
        const Work w = decode(d);
        if (w.kind == 2) break;
        const CUtensorMap* m = w.kind == 0 ? &P.wq[w.beta >> 4] : &P.wo[w.beta >> 4];
        for (int ks = 0; ks < w.nsteps; ks++) {
          const uint32_t b = borrow(ks, w.nsteps);
          r.next_if(b == 2);
          const uint32_t bar = sbase + BAR_FULL + r.slot * 8;
          mbar_wait_w(bar + (BAR_EMPTY - BAR_FULL), r.phase);
          if (w.kind == 0) tma_ld3_w(sbase + r.slot * SLOT, m, 0, ks * 64, w.sub * 2, bar, 16384);
          else tma_ld_wo_w(sbase + r.slot * SLOT, m, w.sub * 128, (w.k0 + ks) * 2, bar);
          if (ks < 10) T2P(i, 2, ks);
          if (w.kind != 0 && ks == max(w.nsteps - GO_P, 4)) mbar_arrive_warp(sbase + BAR_GO);
          r.next(); r.next_if(b == 2);
        }
        if (w.kind == 0) {
          r.phase ^= 1; r.next(); r.next();
        } else if (w.mode == 2) {
          for (int k = 1; k <= ((d >> 5) & 3); k++) {
            if (k == 1) TTAIL(9);
            wait_count(&g_flag[w.range + 5 * k], lds(sbase + EPOCH_OFF));
            TTAIL(10);
            asm volatile("fence.proxy.async.global;" ::: "memory");
#pragma unroll 1
            for (int t = 0; t < 4; t++) {
              mbar_wait_w(sbase + BAR_EMPTY + r.slot * 8, r.phase);
              tma_ld3_w(sbase + r.slot * SLOT, &P.o_st[t == 3], 0, t * 64, NBETA * 64 + (w.range + 5 * k) * 2, sbase + BAR_FULL + r.slot * 8,
                        t == 3 ? 8192 : 16384);
              r.next();
            }
          }
        }
        mbar_wait_w(sbase + BAR_DESC, i & 1);
        d = __shfl_sync(0xffffffffu, lds(sbase + DESC_OFF + ((i + 1) & 3) * 4), 0);
      }
    } else {
      const int hi = warp - 2;
      uint64_t pol_stream;
      asm volatile("createpolicy.fractional.L2::evict_first.b64 %0, 1.0;" : "=l"(pol_stream));
      Ring r{0, 1, 3};
      uint32_t d = cta;
      for (int i = 0;; i++) {
        const Work w = decode(d);
        if (w.kind == 2) break;
        const CUtensorMap* m = w.kind == 0 ? &P.x[hi][w.beta >> 4] : &P.o_ld[hi];
        int c1 = (w.kind == 0 ? (w.beta & 15) : w.beta * 64 + w.k0) * SQ + hi * 128;
        int k_late = -1;
        if (w.kind != 0) {
          if (!hi) T3(i, 3);
          if (d >= (3u << 30)) wait_count(&g_cnt[0][w.beta], lds(sbase + EPOCH_OFF) * H_LATE);
          if (d & 128) k_late = max(2 * H_LATE - w.k0, 0);
          if (!hi) T3(i, 4);
          asm volatile("fence.proxy.async.global;" ::: "memory");
          if (!hi) T3(i, 5);
        }
        for (int ks = 0; ks < w.nsteps; ks++) {
          if (ks == k_late) {
            if (!hi) T3(i, 6);
            wait_count(&g_cnt[1][d & 31], lds(sbase + EPOCH_OFF) * (NH - H_LATE));
            asm volatile("fence.proxy.async.global;" ::: "memory");
            if (!hi) T3(i, 7);
          }
          const uint32_t b = borrow(ks, w.nsteps);
          const bool bo = b != 2;
          r.next_if(hi && !bo); r.next_if(hi && !bo);
          const uint32_t sl = bo ? NS + (b ^ (3 * hi)) : r.slot, bar = sbase + BAR_FULL + sl * 8;
          mbar_wait_w(bar + (BAR_EMPTY - BAR_FULL), bo ? (r.xp >> b) & 1 : r.phase);
          if (w.kind == 0) tma_ld2_w(sbase + sl * SLOT, m, ks * 64, c1, bar, (hi ? 96 * 128 : 128 * 128) >> (DEV_HALF & 1));
          else if (O_LD_POL) { tma_ld2_hint_w(sbase + sl * SLOT, m, 0, c1, bar, (hi ? 96 * 128 : 128 * 128) >> (DEV_HALF >> 1), pol_stream); c1 += SQ; }
          else { tma_ld2_w(sbase + sl * SLOT, m, 0, c1, bar, hi ? 96 * 128 : 128 * 128); c1 += SQ; }
          if (PF_UNITS && w.kind == 0 && i < PF_UNITS && (((i ? PF_MASK : PF_MASK0) >> ks) & 1))
            asm volatile(ELECT "cp.async.bulk.prefetch.tensor.3d.L2.global.L2::cache_hint [%0, {0, %1, 0}], %2;\n}"
                         ::"l"(&P.kv[hi][w.beta >> 4]), "r"((d & 511) * SK + 64 * (PF_J0 + __popc((i ? PF_MASK : PF_MASK0) & ((1 << ks) - 1)))), "l"(pol_stream) : "memory");
          if (ks < 10) T2P(i, 3 + hi, ks);
          if (!hi && w.kind != 0 && !(ks & 3)) TCLK(i * 16 + (ks >> 2));
          r.next(); r.next_if(!hi && !bo); r.next_if(!hi && !bo);
          r.xp ^= 1 << b;
        }
        r.xp ^= 3;
        if (w.kind == 0) {
          m = &P.kv[hi][w.beta >> 4];
          c1 = (d & 511) * SK;
          for (int j = 0; j < 16; j++) {
            if (hi) r.next();
            const uint32_t bar = sbase + BAR_FULL + r.slot * 8;
            const bool tight = i < KV_WIN_UNITS && j < KV_WIN_TILES + ((KV_WIN_RAMP * ((int)d - KV_WIN_N * i)) >> 5);
            if (tight || (KV_WIN_D && j < KV_WIN_T2)) {
              const int s2 = (int)r.slot - (tight ? 2 : KV_WIN_D);
              mbar_wait_w(sbase + BAR_FULL + (s2 < 0 ? s2 + NS : s2) * 8, s2 < 0 ? r.phase : r.phase ^ 1);
            }
            if (j == 15 && hi) mbar_wait_w(sbase + BAR_DESC, i & 1);
            mbar_wait_w(sbase + BAR_EMPTY + r.slot * 8, r.phase);
            tma_ld3_hint_w(sbase + r.slot * SLOT, m, 0, c1, 0, bar, pol_stream);
            T2P(i, 3 + hi, 16 + j);
            if (!hi) TCLK(i * 16 + j);
            if (j == 14 && !hi) mbar_arrive_warp(sbase + BAR_GO);
            if (PF_X && j == PF_XJ && (d & 31) < 10 && d + PF_X * 32 < 1024)
              asm volatile(ELECT "cp.async.bulk.prefetch.tensor.2d.L2.global [%0, {%1, %2}];\n}"
                           ::"l"(&P.x[hi][(d + PF_X * 32) >> 9]), "r"((d & 31) * 64), "r"((((d >> 5) + PF_X) & 15) * SQ + hi * 128) : "memory");
            if (PF_W && j < 5 && (d >> 5) == PF_W)
              asm volatile(ELECT "cp.async.bulk.prefetch.tensor.3d.L2.global [%0, {0, %1, %2}];\n}"
                           ::"l"(&P.wq[1]), "r"((j * 2 + hi) * 64), "r"((d & 31) * 2) : "memory");
            c1 += 64;
            r.next();
            if (!hi) r.next();
          }
        }
        mbar_wait_w(sbase + BAR_DESC, i & 1);
        d = __shfl_sync(0xffffffffu, lds(sbase + DESC_OFF + ((i + 1) & 3) * 4), 0);
      }
    }
  } else {
    asm volatile("setmaxnreg.inc.sync.aligned.u32 %0;" ::"n"(REG_C));
    Ctx c;
    c.sb = sbase; c.wg = wg; c.warp = warp; c.src = 0; c.mqk = 0; c.mpv = 0; c.lead = lane == 0;
    if (wg == 0) consumer<0>(c, P.kp); else consumer<1>(c, P.kp);
  }
}

typedef CUresult (*EncodeFn)(CUtensorMap*, CUtensorMapDataType, cuuint32_t, void*, const cuuint64_t*, const cuuint64_t*,
                             const cuuint32_t*, const cuuint32_t*, CUtensorMapInterleave, CUtensorMapSwizzle,
                             CUtensorMapL2promotion, CUtensorMapFloatOOBfill);

void make_map(EncodeFn enc, CUtensorMap* m, const void* ptr, int rank, const cuuint64_t* dims, const cuuint64_t* strides,
              const cuuint32_t* box, int promo = 2) {
  cuuint32_t es[5] = {1, 1, 1, 1, 1};
  enc(m, CU_TENSOR_MAP_DATA_TYPE_BFLOAT16, rank, const_cast<void*>(ptr), dims, strides, box, es,
      CU_TENSOR_MAP_INTERLEAVE_NONE, CU_TENSOR_MAP_SWIZZLE_128B, promo == 2 ? CU_TENSOR_MAP_L2_PROMOTION_L2_256B : promo == 1 ? CU_TENSOR_MAP_L2_PROMOTION_L2_128B : CU_TENSOR_MAP_L2_PROMOTION_NONE,
      CU_TENSOR_MAP_FLOAT_OOB_FILL_NONE);
}

}

extern "C" void kernel_launch(void* const* d_in, const int* in_sizes, int n_in, void* d_out, int out_size) {
  (void)in_sizes; (void)n_in; (void)out_size;
  static EncodeFn enc = nullptr;
  static void* o_ptr = nullptr;
  static int n_sm = 0;
  if (!enc) {
    void* fn = nullptr;
    cudaDriverEntryPointQueryResult qr;
    cudaGetDriverEntryPoint("cuTensorMapEncodeTiled", &fn, cudaEnableDefault, &qr);
    enc = (EncodeFn)fn;
    cudaGetSymbolAddress(&o_ptr, g_o);
    cudaFuncSetAttribute(mha_fused_kernel<false>, cudaFuncAttributeMaxDynamicSharedMemorySize, SMEM_BYTES);
    cudaFuncSetAttribute(mha_fused_kernel<true>, cudaFuncAttributeMaxDynamicSharedMemorySize, SMEM_BYTES);
    int dev = 0;
    cudaGetDevice(&dev);
    cudaDeviceGetAttribute(&n_sm, cudaDevAttrMultiProcessorCount, dev);
  }
  Params P;
  for (int br = 0; br < 2; br++) {
    const void* x = d_in[br * 5 + 0]; const void* kc = d_in[br * 5 + 1]; const void* vc = d_in[br * 5 + 2];
    const void* wq = d_in[br * 5 + 3]; const void* wo = d_in[br * 5 + 4];
    { cuuint64_t d[2] = {DM, (cuuint64_t)NB * SQ}, s[1] = {DM * 2}; cuuint32_t b[2] = {64, 128 >> (DEV_HALF & 1)}, b2[2] = {64, 96 >> (DEV_HALF & 1)};
      make_map(enc, &P.x[0][br], x, 2, d, s, b, PR_X); make_map(enc, &P.x[1][br], x, 2, d, s, b2, PR_X); }
    { cuuint64_t d[3] = {64, DM, HD / 64}, s[2] = {HD * 2, 128}; cuuint32_t b[3] = {64, 64, 2}; make_map(enc, &P.wq[br], wq, 3, d, s, b, PR_W); }
    { cuuint64_t d[5] = {DM, 2, 4, 4, HD / 32}, s[4] = {DM * 2, 8 * DM * 2, 2 * DM * 2, 32 * DM * 2}; cuuint32_t b[5] = {64, 2, 4, 4, 2};
      make_map(enc, &P.wo[br], wo, 5, d, s, b, PR_W); }
    { cuuint64_t d[3] = {64, (cuuint64_t)NB * NH * SK, 2}, s[2] = {DH * 2, 128}; cuuint32_t b[3] = {64, 64, 2};
      make_map(enc, &P.kv[0][br], kc, 3, d, s, b, PR_KV); make_map(enc, &P.kv[1][br], vc, 3, d, s, b, PR_KV); }
    P.kp[br] = (const __nv_bfloat16*)kc; P.vp[br] = (const __nv_bfloat16*)vc;

  }
  { cuuint64_t d[2] = {64, (cuuint64_t)NBETA * 64 * SQ}, s[1] = {128}; cuuint32_t b[2] = {64, 128 >> (DEV_HALF >> 1)}, b2[2] = {64, 96 >> (DEV_HALF >> 1)};
    make_map(enc, &P.o_ld[0], o_ptr, 2, d, s, b); make_map(enc, &P.o_ld[1], o_ptr, 2, d, s, b2); }
  { cuuint64_t d[3] = {64, SQ, O_BLOCKS}, s[2] = {128, SQ * 128}; cuuint32_t b[3] = {64, 64, 2}, b2[3] = {64, 32, 2};
    make_map(enc, &P.o_st[0], o_ptr, 3, d, s, b); make_map(enc, &P.o_st[1], o_ptr, 3, d, s, b2); }
  { cuuint64_t d[3] = {64, (cuuint64_t)NB * SQ, 2 * DM / 64}, s[2] = {2 * DM * 2, 128}; cuuint32_t b[3] = {64, 64, 2}, b2[3] = {64, 32, 2};
    make_map(enc, &P.out_st[0], d_out, 3, d, s, b); make_map(enc, &P.out_st[1], d_out, 3, d, s, b2); }
  if (n_sm >= NCTA) mha_fused_kernel<false><<<NCTA, 384, SMEM_BYTES>>>(P);
  else mha_fused_kernel<true><<<n_sm, 384, SMEM_BYTES>>>(P);
}
```

```cpp
#include <cuda_runtime.h>
#include <cuda_bf16.h>
#include <cuda.h>
#include <stdint.h>
#include <stdlib.h>

namespace {

__device__ __forceinline__ void wgmma_proj(float (&d)[64], uint64_t da, uint64_t db, int scaleD) {
  asm volatile("{\n.reg .pred p;\nsetp.ne.b32 p, %66, 0;\n"
      "wgmma.mma_async.sync.aligned.m64n128k16.f32.bf16.bf16 "
      "{%0, %1, %2, %3, %4, %5, %6, %7, %8, %9, %10, %11, %12, %13, %14, %15, %16, %17, %18, %19, %20, %21, %22, %23, %24, %25, %26, %27, %28, %29, %30, "
      "%31, %32, %33, %34, %35, %36, %37, %38, %39, %40, %41, %42, %43, %44, %45, %46, %47, %48, %49, %50, %51, %52, %53, %54, %55, %56, %57, %58, %59, %60, "
      "%61, %62, %63}, "
      "%64, %65, p, 1, 1, 0, 1;\n}\n"
      : "+f"(d[0]), "+f"(d[1]), "+f"(d[2]), "+f"(d[3]), "+f"(d[4]), "+f"(d[5]), "+f"(d[6]), "+f"(d[7]), "+f"(d[8]), "+f"(d[9]), "+f"(d[10]), "+f"(d[11]),
        "+f"(d[12]), "+f"(d[13]), "+f"(d[14]), "+f"(d[15]), "+f"(d[16]), "+f"(d[17]), "+f"(d[18]), "+f"(d[19]), "+f"(d[20]), "+f"(d[21]), "+f"(d[22]),
        "+f"(d[23]), "+f"(d[24]), "+f"(d[25]), "+f"(d[26]), "+f"(d[27]), "+f"(d[28]), "+f"(d[29]), "+f"(d[30]), "+f"(d[31]), "+f"(d[32]), "+f"(d[33]),
        "+f"(d[34]), "+f"(d[35]), "+f"(d[36]), "+f"(d[37]), "+f"(d[38]), "+f"(d[39]), "+f"(d[40]), "+f"(d[41]), "+f"(d[42]), "+f"(d[43]), "+f"(d[44]),
        "+f"(d[45]), "+f"(d[46]), "+f"(d[47]), "+f"(d[48]), "+f"(d[49]), "+f"(d[50]), "+f"(d[51]), "+f"(d[52]), "+f"(d[53]), "+f"(d[54]), "+f"(d[55]),
        "+f"(d[56]), "+f"(d[57]), "+f"(d[58]), "+f"(d[59]), "+f"(d[60]), "+f"(d[61]), "+f"(d[62]), "+f"(d[63])
      : "l"(da), "l"(db), "r"(scaleD));
}
__device__ __forceinline__ void wgmma_proj96(float (&d)[64], uint64_t da, uint64_t db, int scaleD) {
  asm volatile("{\n.reg .pred p;\nsetp.ne.b32 p, %50, 0;\n"
      "wgmma.mma_async.sync.aligned.m64n96k16.f32.bf16.bf16 "
      "{%0, %1, %2, %3, %4, %5, %6, %7, %8, %9, %10, %11, %12, %13, %14, %15, %16, %17, %18, %19, %20, %21, %22, %23, %24, %25, %26, %27, %28, %29, %30, "
      "%31, %32, %33, %34, %35, %36, %37, %38, %39, %40, %41, %42, %43, %44, %45, %46, %47}, "
      "%48, %49, p, 1, 1, 1, 0;\n}\n"
      : "+f"(d[0]), "+f"(d[1]), "+f"(d[2]), "+f"(d[3]), "+f"(d[4]), "+f"(d[5]), "+f"(d[6]), "+f"(d[7]), "+f"(d[8]), "+f"(d[9]), "+f"(d[10]), "+f"(d[11]),
        "+f"(d[12]), "+f"(d[13]), "+f"(d[14]), "+f"(d[15]), "+f"(d[16]), "+f"(d[17]), "+f"(d[18]), "+f"(d[19]), "+f"(d[20]), "+f"(d[21]), "+f"(d[22]),
        "+f"(d[23]), "+f"(d[24]), "+f"(d[25]), "+f"(d[26]), "+f"(d[27]), "+f"(d[28]), "+f"(d[29]), "+f"(d[30]), "+f"(d[31]), "+f"(d[32]), "+f"(d[33]),
        "+f"(d[34]), "+f"(d[35]), "+f"(d[36]), "+f"(d[37]), "+f"(d[38]), "+f"(d[39]), "+f"(d[40]), "+f"(d[41]), "+f"(d[42]), "+f"(d[43]), "+f"(d[44]),
        "+f"(d[45]), "+f"(d[46]), "+f"(d[47])
      : "l"(da), "l"(db), "r"(scaleD));
}
__device__ __forceinline__ void wgmma_qk(float (&d)[32], uint64_t da, uint64_t db, int scaleD) {
  asm volatile("{\n.reg .pred p;\nsetp.ne.b32 p, %34, 0;\n"
      "wgmma.mma_async.sync.aligned.m64n64k16.f32.bf16.bf16 "
      "{%0, %1, %2, %3, %4, %5, %6, %7, %8, %9, %10, %11, %12, %13, %14, %15, %16, %17, %18, %19, %20, %21, %22, %23, %24, %25, %26, %27, %28, %29, %30, "
      "%31}, "
      "%32, %33, p, 1, 1, 0, 0;\n}\n"
      : "+f"(d[0]), "+f"(d[1]), "+f"(d[2]), "+f"(d[3]), "+f"(d[4]), "+f"(d[5]), "+f"(d[6]), "+f"(d[7]), "+f"(d[8]), "+f"(d[9]), "+f"(d[10]), "+f"(d[11]),
        "+f"(d[12]), "+f"(d[13]), "+f"(d[14]), "+f"(d[15]), "+f"(d[16]), "+f"(d[17]), "+f"(d[18]), "+f"(d[19]), "+f"(d[20]), "+f"(d[21]), "+f"(d[22]),
        "+f"(d[23]), "+f"(d[24]), "+f"(d[25]), "+f"(d[26]), "+f"(d[27]), "+f"(d[28]), "+f"(d[29]), "+f"(d[30]), "+f"(d[31])
      : "l"(da), "l"(db), "r"(scaleD));
}
__device__ __forceinline__ void wgmma_qk_rs(float (&d)[32], uint32_t a0, uint32_t a1, uint32_t a2, uint32_t a3, uint64_t db, int scaleD) {
  asm volatile("{\n.reg .pred p;\nsetp.ne.b32 p, %37, 0;\n"
      "wgmma.mma_async.sync.aligned.m64n64k16.f32.bf16.bf16 "
      "{%0, %1, %2, %3, %4, %5, %6, %7, %8, %9, %10, %11, %12, %13, %14, %15, %16, %17, %18, %19, %20, %21, %22, %23, %24, %25, %26, %27, %28, %29, %30, "
      "%31}, "
      "{%32, %33, %34, %35}, %36, p, 1, 1, 0;\n}\n"
      : "+f"(d[0]), "+f"(d[1]), "+f"(d[2]), "+f"(d[3]), "+f"(d[4]), "+f"(d[5]), "+f"(d[6]), "+f"(d[7]), "+f"(d[8]), "+f"(d[9]), "+f"(d[10]), "+f"(d[11]),
        "+f"(d[12]), "+f"(d[13]), "+f"(d[14]), "+f"(d[15]), "+f"(d[16]), "+f"(d[17]), "+f"(d[18]), "+f"(d[19]), "+f"(d[20]), "+f"(d[21]), "+f"(d[22]),
        "+f"(d[23]), "+f"(d[24]), "+f"(d[25]), "+f"(d[26]), "+f"(d[27]), "+f"(d[28]), "+f"(d[29]), "+f"(d[30]), "+f"(d[31])
      : "r"(a0), "r"(a1), "r"(a2), "r"(a3), "l"(db), "r"(scaleD));
}
__device__ __forceinline__ void wgmma_pv(float (&d)[64], uint32_t a0, uint32_t a1, uint32_t a2, uint32_t a3, uint64_t db, int scaleD) {
  asm volatile("{\n.reg .pred p;\nsetp.ne.b32 p, %69, 0;\n"
      "wgmma.mma_async.sync.aligned.m64n128k16.f32.bf16.bf16 "
      "{%0, %1, %2, %3, %4, %5, %6, %7, %8, %9, %10, %11, %12, %13, %14, %15, %16, %17, %18, %19, %20, %21, %22, %23, %24, %25, %26, %27, %28, %29, %30, "
      "%31, %32, %33, %34, %35, %36, %37, %38, %39, %40, %41, %42, %43, %44, %45, %46, %47, %48, %49, %50, %51, %52, %53, %54, %55, %56, %57, %58, %59, %60, "
      "%61, %62, %63}, "
      "{%64, %65, %66, %67}, %68, p, 1, 1, 1;\n}\n"
      : "+f"(d[0]), "+f"(d[1]), "+f"(d[2]), "+f"(d[3]), "+f"(d[4]), "+f"(d[5]), "+f"(d[6]), "+f"(d[7]), "+f"(d[8]), "+f"(d[9]), "+f"(d[10]), "+f"(d[11]),
        "+f"(d[12]), "+f"(d[13]), "+f"(d[14]), "+f"(d[15]), "+f"(d[16]), "+f"(d[17]), "+f"(d[18]), "+f"(d[19]), "+f"(d[20]), "+f"(d[21]), "+f"(d[22]),
        "+f"(d[23]), "+f"(d[24]), "+f"(d[25]), "+f"(d[26]), "+f"(d[27]), "+f"(d[28]), "+f"(d[29]), "+f"(d[30]), "+f"(d[31]), "+f"(d[32]), "+f"(d[33]),
        "+f"(d[34]), "+f"(d[35]), "+f"(d[36]), "+f"(d[37]), "+f"(d[38]), "+f"(d[39]), "+f"(d[40]), "+f"(d[41]), "+f"(d[42]), "+f"(d[43]), "+f"(d[44]),
        "+f"(d[45]), "+f"(d[46]), "+f"(d[47]), "+f"(d[48]), "+f"(d[49]), "+f"(d[50]), "+f"(d[51]), "+f"(d[52]), "+f"(d[53]), "+f"(d[54]), "+f"(d[55]),
        "+f"(d[56]), "+f"(d[57]), "+f"(d[58]), "+f"(d[59]), "+f"(d[60]), "+f"(d[61]), "+f"(d[62]), "+f"(d[63])
      : "r"(a0), "r"(a1), "r"(a2), "r"(a3), "l"(db), "r"(scaleD));
}
__device__ __forceinline__ void wgmma_qk_sp(float (&d)[32], uint32_t a0, uint32_t a1, uint32_t a2, uint32_t a3, uint64_t db, int scaleD, uint32_t meta) {
  asm volatile("{\n.reg .pred p;\nsetp.ne.b32 p, %37, 0;\n"
      "wgmma.mma_async.sp.sync.aligned.m64n64k32.f32.bf16.bf16 "
      "{%0, %1, %2, %3, %4, %5, %6, %7, %8, %9, %10, %11, %12, %13, %14, %15, %16, %17, %18, %19, %20, %21, %22, %23, %24, %25, %26, %27, %28, %29, %30, "
      "%31}, "
      "{%32, %33, %34, %35}, %36, %38, 0, p, 1, 1, 0;\n}\n"
      : "+f"(d[0]), "+f"(d[1]), "+f"(d[2]), "+f"(d[3]), "+f"(d[4]), "+f"(d[5]), "+f"(d[6]), "+f"(d[7]), "+f"(d[8]), "+f"(d[9]), "+f"(d[10]), "+f"(d[11]),
        "+f"(d[12]), "+f"(d[13]), "+f"(d[14]), "+f"(d[15]), "+f"(d[16]), "+f"(d[17]), "+f"(d[18]), "+f"(d[19]), "+f"(d[20]), "+f"(d[21]), "+f"(d[22]),
        "+f"(d[23]), "+f"(d[24]), "+f"(d[25]), "+f"(d[26]), "+f"(d[27]), "+f"(d[28]), "+f"(d[29]), "+f"(d[30]), "+f"(d[31])
      : "r"(a0), "r"(a1), "r"(a2), "r"(a3), "l"(db), "r"(scaleD), "r"(meta));
}
__device__ __forceinline__ void wgmma_pv_sp(float (&d)[64], uint32_t a0, uint32_t a1, uint32_t a2, uint32_t a3, uint64_t db, int scaleD, uint32_t meta) {
  asm volatile("{\n.reg .pred p;\nsetp.ne.b32 p, %69, 0;\n"
      "wgmma.mma_async.sp.sync.aligned.m64n128k32.f32.bf16.bf16 "
      "{%0, %1, %2, %3, %4, %5, %6, %7, %8, %9, %10, %11, %12, %13, %14, %15, %16, %17, %18, %19, %20, %21, %22, %23, %24, %25, %26, %27, %28, %29, %30, "
      "%31, %32, %33, %34, %35, %36, %37, %38, %39, %40, %41, %42, %43, %44, %45, %46, %47, %48, %49, %50, %51, %52, %53, %54, %55, %56, %57, %58, %59, %60, "
      "%61, %62, %63}, "
      "{%64, %65, %66, %67}, %68, %70, 0, p, 1, 1, 1;\n}\n"
      : "+f"(d[0]), "+f"(d[1]), "+f"(d[2]), "+f"(d[3]), "+f"(d[4]), "+f"(d[5]), "+f"(d[6]), "+f"(d[7]), "+f"(d[8]), "+f"(d[9]), "+f"(d[10]), "+f"(d[11]),
        "+f"(d[12]), "+f"(d[13]), "+f"(d[14]), "+f"(d[15]), "+f"(d[16]), "+f"(d[17]), "+f"(d[18]), "+f"(d[19]), "+f"(d[20]), "+f"(d[21]), "+f"(d[22]),
        "+f"(d[23]), "+f"(d[24]), "+f"(d[25]), "+f"(d[26]), "+f"(d[27]), "+f"(d[28]), "+f"(d[29]), "+f"(d[30]), "+f"(d[31]), "+f"(d[32]), "+f"(d[33]),
        "+f"(d[34]), "+f"(d[35]), "+f"(d[36]), "+f"(d[37]), "+f"(d[38]), "+f"(d[39]), "+f"(d[40]), "+f"(d[41]), "+f"(d[42]), "+f"(d[43]), "+f"(d[44]),
        "+f"(d[45]), "+f"(d[46]), "+f"(d[47]), "+f"(d[48]), "+f"(d[49]), "+f"(d[50]), "+f"(d[51]), "+f"(d[52]), "+f"(d[53]), "+f"(d[54]), "+f"(d[55]),
        "+f"(d[56]), "+f"(d[57]), "+f"(d[58]), "+f"(d[59]), "+f"(d[60]), "+f"(d[61]), "+f"(d[62]), "+f"(d[63])
      : "r"(a0), "r"(a1), "r"(a2), "r"(a3), "l"(db), "r"(scaleD), "r"(meta));
}
__device__ __forceinline__ void wgmma_proj_init(float (&d)[64], uint64_t da, uint64_t db, int scaleD) {
  asm volatile("{\n.reg .pred p;\nsetp.ne.b32 p, %66, 0;\n"
      "wgmma.mma_async.sync.aligned.m64n128k16.f32.bf16.bf16 "
      "{%0, %1, %2, %3, %4, %5, %6, %7, %8, %9, %10, %11, %12, %13, %14, %15, %16, %17, %18, %19, %20, %21, %22, %23, %24, %25, %26, %27, %28, %29, %30, "
      "%31, %32, %33, %34, %35, %36, %37, %38, %39, %40, %41, %42, %43, %44, %45, %46, %47, %48, %49, %50, %51, %52, %53, %54, %55, %56, %57, %58, %59, %60, "
      "%61, %62, %63}, "
      "%64, %65, p, 1, 1, 0, 1;\n}\n"
      : "=f"(d[0]), "=f"(d[1]), "=f"(d[2]), "=f"(d[3]), "=f"(d[4]), "=f"(d[5]), "=f"(d[6]), "=f"(d[7]), "=f"(d[8]), "=f"(d[9]), "=f"(d[10]), "=f"(d[11]),
        "=f"(d[12]), "=f"(d[13]), "=f"(d[14]), "=f"(d[15]), "=f"(d[16]), "=f"(d[17]), "=f"(d[18]), "=f"(d[19]), "=f"(d[20]), "=f"(d[21]), "=f"(d[22]),
        "=f"(d[23]), "=f"(d[24]), "=f"(d[25]), "=f"(d[26]), "=f"(d[27]), "=f"(d[28]), "=f"(d[29]), "=f"(d[30]), "=f"(d[31]), "=f"(d[32]), "=f"(d[33]),
        "=f"(d[34]), "=f"(d[35]), "=f"(d[36]), "=f"(d[37]), "=f"(d[38]), "=f"(d[39]), "=f"(d[40]), "=f"(d[41]), "=f"(d[42]), "=f"(d[43]), "=f"(d[44]),
        "=f"(d[45]), "=f"(d[46]), "=f"(d[47]), "=f"(d[48]), "=f"(d[49]), "=f"(d[50]), "=f"(d[51]), "=f"(d[52]), "=f"(d[53]), "=f"(d[54]), "=f"(d[55]),
        "=f"(d[56]), "=f"(d[57]), "=f"(d[58]), "=f"(d[59]), "=f"(d[60]), "=f"(d[61]), "=f"(d[62]), "=f"(d[63])
      : "l"(da), "l"(db), "r"(scaleD));
}
__device__ __forceinline__ void wgmma_proj96_init(float (&d)[64], uint64_t da, uint64_t db, int scaleD) {
  asm volatile("{\n.reg .pred p;\nsetp.ne.b32 p, %50, 0;\n"
      "wgmma.mma_async.sync.aligned.m64n96k16.f32.bf16.bf16 "
      "{%0, %1, %2, %3, %4, %5, %6, %7, %8, %9, %10, %11, %12, %13, %14, %15, %16, %17, %18, %19, %20, %21, %22, %23, %24, %25, %26, %27, %28, %29, %30, "
      "%31, %32, %33, %34, %35, %36, %37, %38, %39, %40, %41, %42, %43, %44, %45, %46, %47}, "
      "%48, %49, p, 1, 1, 1, 0;\n}\n"
      : "=f"(d[0]), "=f"(d[1]), "=f"(d[2]), "=f"(d[3]), "=f"(d[4]), "=f"(d[5]), "=f"(d[6]), "=f"(d[7]), "=f"(d[8]), "=f"(d[9]), "=f"(d[10]), "=f"(d[11]),
        "=f"(d[12]), "=f"(d[13]), "=f"(d[14]), "=f"(d[15]), "=f"(d[16]), "=f"(d[17]), "=f"(d[18]), "=f"(d[19]), "=f"(d[20]), "=f"(d[21]), "=f"(d[22]),
        "=f"(d[23]), "=f"(d[24]), "=f"(d[25]), "=f"(d[26]), "=f"(d[27]), "=f"(d[28]), "=f"(d[29]), "=f"(d[30]), "=f"(d[31]), "=f"(d[32]), "=f"(d[33]),
        "=f"(d[34]), "=f"(d[35]), "=f"(d[36]), "=f"(d[37]), "=f"(d[38]), "=f"(d[39]), "=f"(d[40]), "=f"(d[41]), "=f"(d[42]), "=f"(d[43]), "=f"(d[44]),
        "=f"(d[45]), "=f"(d[46]), "=f"(d[47])
      : "l"(da), "l"(db), "r"(scaleD));
}
__device__ __forceinline__ void wgmma_qk_init(float (&d)[32], uint64_t da, uint64_t db, int scaleD) {
  asm volatile("{\n.reg .pred p;\nsetp.ne.b32 p, %34, 0;\n"
      "wgmma.mma_async.sync.aligned.m64n64k16.f32.bf16.bf16 "
      "{%0, %1, %2, %3, %4, %5, %6, %7, %8, %9, %10, %11, %12, %13, %14, %15, %16, %17, %18, %19, %20, %21, %22, %23, %24, %25, %26, %27, %28, %29, %30, "
      "%31}, "
      "%32, %33, p, 1, 1, 0, 0;\n}\n"
      : "=f"(d[0]), "=f"(d[1]), "=f"(d[2]), "=f"(d[3]), "=f"(d[4]), "=f"(d[5]), "=f"(d[6]), "=f"(d[7]), "=f"(d[8]), "=f"(d[9]), "=f"(d[10]), "=f"(d[11]),
        "=f"(d[12]), "=f"(d[13]), "=f"(d[14]), "=f"(d[15]), "=f"(d[16]), "=f"(d[17]), "=f"(d[18]), "=f"(d[19]), "=f"(d[20]), "=f"(d[21]), "=f"(d[22]),
        "=f"(d[23]), "=f"(d[24]), "=f"(d[25]), "=f"(d[26]), "=f"(d[27]), "=f"(d[28]), "=f"(d[29]), "=f"(d[30]), "=f"(d[31])
      : "l"(da), "l"(db), "r"(scaleD));
}
__device__ __forceinline__ void wgmma_qk_rs_init(float (&d)[32], uint32_t a0, uint32_t a1, uint32_t a2, uint32_t a3, uint64_t db, int scaleD) {
  asm volatile("{\n.reg .pred p;\nsetp.ne.b32 p, %37, 0;\n"
      "wgmma.mma_async.sync.aligned.m64n64k16.f32.bf16.bf16 "
      "{%0, %1, %2, %3, %4, %5, %6, %7, %8, %9, %10, %11, %12, %13, %14, %15, %16, %17, %18, %19, %20, %21, %22, %23, %24, %25, %26, %27, %28, %29, %30, "
      "%31}, "
      "{%32, %33, %34, %35}, %36, p, 1, 1, 0;\n}\n"
      : "=f"(d[0]), "=f"(d[1]), "=f"(d[2]), "=f"(d[3]), "=f"(d[4]), "=f"(d[5]), "=f"(d[6]), "=f"(d[7]), "=f"(d[8]), "=f"(d[9]), "=f"(d[10]), "=f"(d[11]),
        "=f"(d[12]), "=f"(d[13]), "=f"(d[14]), "=f"(d[15]), "=f"(d[16]), "=f"(d[17]), "=f"(d[18]), "=f"(d[19]), "=f"(d[20]), "=f"(d[21]), "=f"(d[22]),
        "=f"(d[23]), "=f"(d[24]), "=f"(d[25]), "=f"(d[26]), "=f"(d[27]), "=f"(d[28]), "=f"(d[29]), "=f"(d[30]), "=f"(d[31])
      : "r"(a0), "r"(a1), "r"(a2), "r"(a3), "l"(db), "r"(scaleD));
}
__device__ __forceinline__ void wgmma_pv_init(float (&d)[64], uint32_t a0, uint32_t a1, uint32_t a2, uint32_t a3, uint64_t db, int scaleD) {
  asm volatile("{\n.reg .pred p;\nsetp.ne.b32 p, %69, 0;\n"
      "wgmma.mma_async.sync.aligned.m64n128k16.f32.bf16.bf16 "
      "{%0, %1, %2, %3, %4, %5, %6, %7, %8, %9, %10, %11, %12, %13, %14, %15, %16, %17, %18, %19, %20, %21, %22, %23, %24, %25, %26, %27, %28, %29, %30, "
      "%31, %32, %33, %34, %35, %36, %37, %38, %39, %40, %41, %42, %43, %44, %45, %46, %47, %48, %49, %50, %51, %52, %53, %54, %55, %56, %57, %58, %59, %60, "
      "%61, %62, %63}, "
      "{%64, %65, %66, %67}, %68, p, 1, 1, 1;\n}\n"
      : "=f"(d[0]), "=f"(d[1]), "=f"(d[2]), "=f"(d[3]), "=f"(d[4]), "=f"(d[5]), "=f"(d[6]), "=f"(d[7]), "=f"(d[8]), "=f"(d[9]), "=f"(d[10]), "=f"(d[11]),
        "=f"(d[12]), "=f"(d[13]), "=f"(d[14]), "=f"(d[15]), "=f"(d[16]), "=f"(d[17]), "=f"(d[18]), "=f"(d[19]), "=f"(d[20]), "=f"(d[21]), "=f"(d[22]),
        "=f"(d[23]), "=f"(d[24]), "=f"(d[25]), "=f"(d[26]), "=f"(d[27]), "=f"(d[28]), "=f"(d[29]), "=f"(d[30]), "=f"(d[31]), "=f"(d[32]), "=f"(d[33]),
        "=f"(d[34]), "=f"(d[35]), "=f"(d[36]), "=f"(d[37]), "=f"(d[38]), "=f"(d[39]), "=f"(d[40]), "=f"(d[41]), "=f"(d[42]), "=f"(d[43]), "=f"(d[44]),
        "=f"(d[45]), "=f"(d[46]), "=f"(d[47]), "=f"(d[48]), "=f"(d[49]), "=f"(d[50]), "=f"(d[51]), "=f"(d[52]), "=f"(d[53]), "=f"(d[54]), "=f"(d[55]),
        "=f"(d[56]), "=f"(d[57]), "=f"(d[58]), "=f"(d[59]), "=f"(d[60]), "=f"(d[61]), "=f"(d[62]), "=f"(d[63])
      : "r"(a0), "r"(a1), "r"(a2), "r"(a3), "l"(db), "r"(scaleD));
}
__device__ __forceinline__ void wgmma_qk_sp_init(float (&d)[32], uint32_t a0, uint32_t a1, uint32_t a2, uint32_t a3, uint64_t db, int scaleD, uint32_t meta) {
  asm volatile("{\n.reg .pred p;\nsetp.ne.b32 p, %37, 0;\n"
      "wgmma.mma_async.sp.sync.aligned.m64n64k32.f32.bf16.bf16 "
      "{%0, %1, %2, %3, %4, %5, %6, %7, %8, %9, %10, %11, %12, %13, %14, %15, %16, %17, %18, %19, %20, %21, %22, %23, %24, %25, %26, %27, %28, %29, %30, "
      "%31}, "
      "{%32, %33, %34, %35}, %36, %38, 0, p, 1, 1, 0;\n}\n"
      : "=f"(d[0]), "=f"(d[1]), "=f"(d[2]), "=f"(d[3]), "=f"(d[4]), "=f"(d[5]), "=f"(d[6]), "=f"(d[7]), "=f"(d[8]), "=f"(d[9]), "=f"(d[10]), "=f"(d[11]),
        "=f"(d[12]), "=f"(d[13]), "=f"(d[14]), "=f"(d[15]), "=f"(d[16]), "=f"(d[17]), "=f"(d[18]), "=f"(d[19]), "=f"(d[20]), "=f"(d[21]), "=f"(d[22]),
        "=f"(d[23]), "=f"(d[24]), "=f"(d[25]), "=f"(d[26]), "=f"(d[27]), "=f"(d[28]), "=f"(d[29]), "=f"(d[30]), "=f"(d[31])
      : "r"(a0), "r"(a1), "r"(a2), "r"(a3), "l"(db), "r"(scaleD), "r"(meta));
}
__device__ __forceinline__ void wgmma_pv_sp_init(float (&d)[64], uint32_t a0, uint32_t a1, uint32_t a2, uint32_t a3, uint64_t db, int scaleD, uint32_t meta) {
  asm volatile("{\n.reg .pred p;\nsetp.ne.b32 p, %69, 0;\n"
      "wgmma.mma_async.sp.sync.aligned.m64n128k32.f32.bf16.bf16 "
      "{%0, %1, %2, %3, %4, %5, %6, %7, %8, %9, %10, %11, %12, %13, %14, %15, %16, %17, %18, %19, %20, %21, %22, %23, %24, %25, %26, %27, %28, %29, %30, "
      "%31, %32, %33, %34, %35, %36, %37, %38, %39, %40, %41, %42, %43, %44, %45, %46, %47, %48, %49, %50, %51, %52, %53, %54, %55, %56, %57, %58, %59, %60, "
      "%61, %62, %63}, "
      "{%64, %65, %66, %67}, %68, %70, 0, p, 1, 1, 1;\n}\n"
      : "=f"(d[0]), "=f"(d[1]), "=f"(d[2]), "=f"(d[3]), "=f"(d[4]), "=f"(d[5]), "=f"(d[6]), "=f"(d[7]), "=f"(d[8]), "=f"(d[9]), "=f"(d[10]), "=f"(d[11]),
        "=f"(d[12]), "=f"(d[13]), "=f"(d[14]), "=f"(d[15]), "=f"(d[16]), "=f"(d[17]), "=f"(d[18]), "=f"(d[19]), "=f"(d[20]), "=f"(d[21]), "=f"(d[22]),
        "=f"(d[23]), "=f"(d[24]), "=f"(d[25]), "=f"(d[26]), "=f"(d[27]), "=f"(d[28]), "=f"(d[29]), "=f"(d[30]), "=f"(d[31]), "=f"(d[32]), "=f"(d[33]),
        "=f"(d[34]), "=f"(d[35]), "=f"(d[36]), "=f"(d[37]), "=f"(d[38]), "=f"(d[39]), "=f"(d[40]), "=f"(d[41]), "=f"(d[42]), "=f"(d[43]), "=f"(d[44]),
        "=f"(d[45]), "=f"(d[46]), "=f"(d[47]), "=f"(d[48]), "=f"(d[49]), "=f"(d[50]), "=f"(d[51]), "=f"(d[52]), "=f"(d[53]), "=f"(d[54]), "=f"(d[55]),
        "=f"(d[56]), "=f"(d[57]), "=f"(d[58]), "=f"(d[59]), "=f"(d[60]), "=f"(d[61]), "=f"(d[62]), "=f"(d[63])
      : "r"(a0), "r"(a1), "r"(a2), "r"(a3), "l"(db), "r"(scaleD), "r"(meta));
}

constexpr int NB = 16, SQ = 224, DM = 640, NH = 32, SK = 1024, DH = 128;
constexpr int HD = NH * DH;
constexpr int NBETA = 2 * NB;
constexpr int NCTA = 132;
constexpr int NS = 10;
constexpr int SLOT = 16384;
constexpr int QBUF_OFF = NS * SLOT;
constexpr int NSX = NS + 4;
constexpr int BAR_OFF = NSX * SLOT;
constexpr int BAR_FULL = BAR_OFF;
constexpr int BAR_EMPTY = BAR_OFF + 8 * NSX;
constexpr int BAR_STG = BAR_OFF + 16 * NSX;
constexpr int BAR_OUT = BAR_STG + 32;
constexpr int BAR_DESC = BAR_OUT + 8;
constexpr int BAR_GO = BAR_DESC + 8;
constexpr int DESC_OFF = BAR_GO + 8;
constexpr int EPOCH_OFF = DESC_OFF + 16;
constexpr int TRACE_OFF = EPOCH_OFF + 8;
constexpr int SMEM_BYTES = TRACE_OFF;
constexpr float SM_C = 0.08838834764831845f * 1.4426950408889634f;
constexpr float SUM_HI = 1099511627776.f, SUM_LO = 1.f / 1099511627776.f;
constexpr uint32_t META_QK = 0xEEEE4444u;
constexpr uint32_t META_PV = 0x44EEEE44u;

#define QK_EARLY_MASK 3
#define ST_ORDER 0x2130
#define LAG_BAR 5
#define ST_NOW 9
#define PF_UNITS 0
#define PF_MASK 0x2a8
#define PF_MASK0 PF_MASK
#define PF_X 0
#define PF_XJ 2
#define PF_W 0
#define KV_WIN_UNITS 2
#define KV_WIN_D 4
#define KV_WIN_T2 16
#define O_LD_POL 1
#define LAST_SYNC 0
#define RED_FIRST 2
#define PEEK 0
#define PACK_LATE 1
#define RS_STAGE 3
#define O_STEPS 4
#define TLB_WARM 0
#define DEV_HALF 0
#define DEV_IDLE 0
#define KV_WIN_RAMP 4
#define KV_WIN_N 132
#define BORROW_ALT 0
#define PF_J0 0
#define PDEPTH 0
#define EARLY_BEG 1
#define KV_WIN_TILES -2
#define PR_KV 2
#define PR_X 2
#define PR_W 2
#define REG_C 232
#define REG_P 40
#define GO_P 4
#define P_POS 224
#define P_STRIDE 32
#define B_LATE 28
#define H_LATE 24
#define P_EARLY 13
#define PIECE_TABLE 0x5026401a,0x68dc4034,0x50275816,0x695a5837,0x50295015,0x6a175036,0x501e080d,0x681f083c,0x50253812,0x69d8383a,0x403f980e,0x80000000,0x5036180f,0x80000000,0x50203011,0x69993032,0x50367019,0x80000000,0x50224814,0x6a954835,0x50246017,0x6b526038,0x502c6818,0x6dc86839,0x5017b813,0x69d8b85f,0x50102810,0x685e2831,0x646e2030,0x80000000,0x501f101c,0x6dc8102f,0x5017801b,0x6c8d805e,0x6627783b,0x80000000,0x6627b033,0x80000000,0x501a901e,0x80000000,0x56d6881e,0x80000000,0x501ca81d,0x80000000,0x6762a03d,0x80000000,0x67e0002d,0x80000000,0x5512c01f,0x80000000,0x5013c81f,0x80000000

struct Params {
  CUtensorMap x[2][2], wq[2], kv[2][2], wo[2];
  CUtensorMap o_ld[2], o_st[2], out_st[2];
  const __nv_bfloat16* kp[2];
  const __nv_bfloat16* vp[2];
};

constexpr int NPART = 32 * 5, O_BLOCKS = NBETA * 64 + 2 * NPART;
__device__ __align__(128) __nv_bfloat16 g_o[(size_t)O_BLOCKS * SQ * 64];
__device__ unsigned g_cnt[2][NBETA];
__device__ unsigned g_epoch, g_next;
__device__ unsigned g_flag[NPART];

__device__ __forceinline__ uint32_t smem_u32(const void* p) { return (uint32_t)__cvta_generic_to_shared(p); }
__device__ __forceinline__ void mbar_init(uint32_t bar, int cnt) {
  asm volatile("mbarrier.init.shared::cta.b64 [%0], %1;" ::"r"(bar), "r"(cnt) : "memory");
}
__device__ __forceinline__ void mbar_arrive(uint32_t bar) {
  asm volatile("mbarrier.arrive.shared::cta.b64 _, [%0];" ::"r"(bar) : "memory");
}
__device__ __forceinline__ void mbar_arrive_warp(uint32_t bar) {
  asm volatile("{\n.reg .pred p;\nelect.sync _|p, 0xffffffff;\n@p mbarrier.arrive.shared::cta.b64 _, [%0];\n}" ::"r"(bar) : "memory");
}
__device__ __forceinline__ int lane_now() { int l; asm volatile("mov.u32 %0, %%laneid;" : "=r"(l)); return l; }
__device__ __forceinline__ bool mbar_try(uint32_t bar, uint32_t parity) {
  uint32_t ok;
  asm volatile("{\n.reg .pred p;\nmbarrier.try_wait.parity.shared::cta.b64 p, [%1], %2;\nselp.u32 %0, 1, 0, p;\n}"
               : "=r"(ok) : "r"(bar), "r"(parity) : "memory");
  return ok;
}
__device__ __forceinline__ bool mbar_test(uint32_t bar, uint32_t parity) {
  uint32_t ok;
  asm volatile("{\n.reg .pred p;\nmbarrier.test_wait.parity.shared::cta.b64 p, [%1], %2;\nselp.u32 %0, 1, 0, p;\n}"
               : "=r"(ok) : "r"(bar), "r"(parity) : "memory");
  return ok;
}
__device__ __forceinline__ void mbar_wait_w(uint32_t bar, uint32_t parity) {
  uint32_t n = 0;
  while (!__all_sync(0xffffffffu, mbar_try(bar, parity))) {
    if (++n > (1u << 22)) __trap();
  }
}
#define ELECT "{\n.reg .pred p;\nelect.sync _|p, 0xffffffff;\n@p "
__device__ __forceinline__ void tma_st3_hint_w(const CUtensorMap* m, uint32_t src, int c0, int c1, int c2, uint64_t pol) {
  asm volatile(ELECT "cp.async.bulk.tensor.3d.global.shared::cta.bulk_group.L2::cache_hint [%0, {%2, %3, %4}], [%1], %5;\n}"
               ::"l"(m), "r"(src), "r"(c0), "r"(c1), "r"(c2), "l"(pol) : "memory");
}
#define EXPECT(bar, bytes) "mbarrier.arrive.expect_tx.shared::cta.b64 _, [" bar "], " bytes ";\n@p "
__device__ __forceinline__ void tma_ld2_w(uint32_t dst, const CUtensorMap* m, int c0, int c1, uint32_t bar, uint32_t bytes) {
  asm volatile(ELECT EXPECT("%2", "%5") "cp.async.bulk.tensor.2d.shared::cluster.global.mbarrier::complete_tx::bytes [%0], [%1, {%3, %4}], [%2];\n}"
               ::"r"(dst), "l"(m), "r"(bar), "r"(c0), "r"(c1), "r"(bytes) : "memory");
}
__device__ __forceinline__ void tma_ld2_hint_w(uint32_t dst, const CUtensorMap* m, int c0, int c1, uint32_t bar, uint32_t bytes, uint64_t pol) {
  asm volatile(ELECT EXPECT("%2", "%6") "cp.async.bulk.tensor.2d.shared::cluster.global.mbarrier::complete_tx::bytes.L2::cache_hint"
               " [%0], [%1, {%3, %4}], [%2], %5;\n}"
               ::"r"(dst), "l"(m), "r"(bar), "r"(c0), "r"(c1), "l"(pol), "r"(bytes) : "memory");
}
__device__ __forceinline__ void tma_ld3_w(uint32_t dst, const CUtensorMap* m, int c0, int c1, int c2, uint32_t bar, uint32_t bytes) {
  asm volatile(ELECT EXPECT("%2", "%6") "cp.async.bulk.tensor.3d.shared::cluster.global.mbarrier::complete_tx::bytes [%0], [%1, {%3, %4, %5}], [%2];\n}"
               ::"r"(dst), "l"(m), "r"(bar), "r"(c0), "r"(c1), "r"(c2), "r"(bytes) : "memory");
}
__device__ __forceinline__ void tma_ld3_hint_w(uint32_t dst, const CUtensorMap* m, int c0, int c1, int c2, uint32_t bar, uint64_t pol) {
  asm volatile(ELECT EXPECT("%2", "16384") "cp.async.bulk.tensor.3d.shared::cluster.global.mbarrier::complete_tx::bytes.L2::cache_hint"
               " [%0], [%1, {%3, %4, %5}], [%2], %6;\n}"
               ::"r"(dst), "l"(m), "r"(bar), "r"(c0), "r"(c1), "r"(c2), "l"(pol) : "memory");
}
__device__ __forceinline__ void tma_ld_wo_w(uint32_t dst, const CUtensorMap* m, int col, int grp, uint32_t bar) {
  asm volatile(ELECT EXPECT("%2", "16384") "cp.async.bulk.tensor.5d.shared::cluster.global.mbarrier::complete_tx::bytes [%0], [%1, {%3, 0, 0, 0, %4}], [%2];\n"
               "@p cp.async.bulk.tensor.5d.shared::cluster.global.mbarrier::complete_tx::bytes [%5], [%1, {%6, 0, 0, 0, %4}], [%2];\n}"
               ::"r"(dst), "l"(m), "r"(bar), "r"(col), "r"(grp), "r"(dst + 8192), "r"(col + 64) : "memory");
}
__device__ __forceinline__ void mbar_arrive8_w(uint32_t bar) {
  asm volatile(ELECT "mbarrier.arrive.shared::cta.b64 _, [%0], 8;\n}" ::"r"(bar) : "memory");
}
__device__ __forceinline__ void bulk_commit() { asm volatile("cp.async.bulk.commit_group;" ::: "memory"); }
template <int N> __device__ __forceinline__ void bulk_wait_read() { asm volatile("cp.async.bulk.wait_group.read %0;" ::"n"(N) : "memory"); }
__device__ __forceinline__ void wg_fence() { asm volatile("wgmma.fence.sync.aligned;" ::: "memory"); }
__device__ __forceinline__ void wg_commit() { asm volatile("wgmma.commit_group.sync.aligned;" ::: "memory"); }
template <int N> __device__ __forceinline__ void wg_wait() { asm volatile("wgmma.wait_group.sync.aligned %0;" ::"n"(N) : "memory"); }
__device__ __forceinline__ void fence_async_smem() { asm volatile("fence.proxy.async.shared::cta;" ::: "memory"); }
__device__ __forceinline__ void bar_sync(int id, int n) { asm volatile("bar.sync %0, %1;" ::"r"(id), "r"(n) : "memory"); }
template <int N> __device__ __forceinline__ void reg_fence(float (&a)[N]) {
#pragma unroll
  for (int i = 0; i < N; i++) asm volatile("" : "+f"(a[i])::"memory");
}
template <int N> __device__ __forceinline__ void reg_fence(uint32_t (&a)[N]) {
#pragma unroll
  for (int i = 0; i < N; i++) asm volatile("" : "+r"(a[i])::"memory");
}
__device__ __forceinline__ float ex2(float x) { float y; asm("ex2.approx.ftz.f32 %0, %1;" : "=f"(y) : "f"(x)); return y; }
__device__ __forceinline__ uint32_t pack_bf16(float lo, float hi) {
  uint32_t r; asm("cvt.rn.bf16x2.f32 %0, %1, %2;" : "=r"(r) : "f"(hi), "f"(lo)); return r;
}
__device__ __forceinline__ void stsm4(uint32_t a, uint32_t r0, uint32_t r1, uint32_t r2, uint32_t r3) {
  asm volatile("stmatrix.sync.aligned.m8n8.x4.shared.b16 [%0], {%1, %2, %3, %4};" ::"r"(a), "r"(r0), "r"(r1), "r"(r2), "r"(r3) : "memory");
}
__device__ __forceinline__ void stsm4t(uint32_t a, uint32_t r0, uint32_t r1, uint32_t r2, uint32_t r3) {
  asm volatile("stmatrix.sync.aligned.m8n8.x4.trans.shared.b16 [%0], {%1, %2, %3, %4};" ::"r"(a), "r"(r0), "r"(r1), "r"(r2), "r"(r3) : "memory");
}
__device__ __forceinline__ void ldsm4(uint32_t a, uint32_t& r0, uint32_t& r1, uint32_t& r2, uint32_t& r3) {
  asm volatile("ldmatrix.sync.aligned.m8n8.x4.shared.b16 {%0, %1, %2, %3}, [%4];" : "=r"(r0), "=r"(r1), "=r"(r2), "=r"(r3) : "r"(a) : "memory");
}
__device__ __forceinline__ void sts16(uint32_t a, uint32_t v) { asm volatile("st.shared.u16 [%0], %1;" ::"r"(a), "h"((uint16_t)v) : "memory"); }
__device__ __forceinline__ void mma16816(float& c0, float& c1, float& c2, float& c3, uint32_t a0, uint32_t a1, uint32_t a2, uint32_t a3,
                                         uint32_t b0, uint32_t b1) {
  asm volatile("mma.sync.aligned.m16n8k16.row.col.f32.bf16.bf16.f32 {%0, %1, %2, %3}, {%4, %5, %6, %7}, {%8, %9}, {%0, %1, %2, %3};"
               : "+f"(c0), "+f"(c1), "+f"(c2), "+f"(c3) : "r"(a0), "r"(a1), "r"(a2), "r"(a3), "r"(b0), "r"(b1));
}
__device__ __forceinline__ uint32_t sdesc(uint32_t addr, uint32_t lbo) { return (addr >> 4) + ((lbo >> 4) << 16); }
__device__ __forceinline__ uint64_t desc64(uint32_t lo, uint32_t hi) { uint64_t d; asm("mov.b64 %0, {%1, %2};" : "=l"(d) : "r"(lo), "r"(hi)); return d; }
__device__ __forceinline__ void dadd(uint64_t& d, uint32_t inc) {
  asm("{\n.reg .b32 l, h;\nmov.b64 {l, h}, %0;\nadd.u32 l, l, %1;\nmov.b64 %0, {l, h};\n}" : "+l"(d) : "r"(inc));
}

struct Ring {
  uint32_t slot, phase, xp;
  __device__ __forceinline__ void uniform() {
    slot = __shfl_sync(0xffffffffu, slot, 0); phase = __shfl_sync(0xffffffffu, phase, 0); xp = __shfl_sync(0xffffffffu, xp, 0);
  }
  __device__ __forceinline__ void next() { if (++slot == NS) { slot = 0; phase ^= 1; } }
  __device__ __forceinline__ void next_if(bool p) { slot += p; if (slot == NS) { slot = 0; phase ^= 1; } }
};
__device__ __forceinline__ uint32_t borrow(int ks, int n) {
  if (BORROW_ALT) return (ks & 1) && ks >= 3 && ks + 1 < n ? (~ks >> 1) & 1 : 2;
  const int k = ks + 1;
  return k >= 4 && !(k & 2) && k < n ? k & 1 : 2;
}

constexpr uint32_t Q_RANGES = NBETA * NH + P_EARLY * 5;
constexpr int TAIL_STEPS = (NBETA - P_EARLY) * 64, NRANGE = NCTA / 5;
struct Work { int kind, mode, k0, nsteps, range, beta, sub; };
struct Sched { uint16_t queue[Q_RANGES]; uint32_t piece[NRANGE + 1][4]; };
constexpr Sched make_sched() {
  Sched s{};
  int q = 0, a = 0;
  for (int pass = 0; pass < 2; pass++)
    for (int b = pass ? B_LATE : 0; b < NBETA; b++)
      for (int h = pass ? H_LATE : 0; h < (pass || b < B_LATE ? NH : H_LATE); h++) {
        if (a >= P_POS && (a - P_POS) % P_STRIDE == 0 && (a - P_POS) / P_STRIDE < P_EARLY)
          for (int col = 0; col < 5; col++) s.queue[q++] = 0x8000 | col << 8 | (a - P_POS) / P_STRIDE;
        s.queue[q++] = b << 5 | h;
        a++;
      }
  constexpr uint32_t T[NRANGE * 2] = {PIECE_TABLE};
  for (int g = 0; g <= NRANGE; g++)
    for (int n = 0; n < 4; n++) s.piece[g][n] = g < NRANGE && n < 2 ? T[2 * g + n] : 2u << 30;
  return s;
}
__constant__ Sched c_sched = make_sched();
__device__ __forceinline__ Work decode(uint32_t d) {
  Work w;
  w.kind = d >> 30; if (w.kind == 3) w.kind = 1;
  w.mode = (d >> 28) & 3; w.k0 = (d >> 22) & 63;
  if (w.kind == 0) { w.beta = (d >> 5) & 31; w.sub = d & 31; w.nsteps = DM / 64; }
  else { w.beta = d & 31; w.sub = (d >> 8) & 7; w.nsteps = ((d >> 16) & 63) + 1; }
  w.range = ((d >> 11) & 31) * 5 + w.sub;
  return w;
}

__device__ __forceinline__ bool reached(const unsigned* cnt, unsigned target) {
  unsigned v;
  asm volatile("ld.acquire.gpu.global.u32 %0, [%1];" : "=r"(v) : "l"(cnt) : "memory");
  return (int)(v - target) >= 0;
}
__device__ __forceinline__ void wait_count(const unsigned* cnt, unsigned target) {
  unsigned n = 0;
  while (!__all_sync(0xffffffffu, reached(cnt, target))) { if (++n > (1u << 24)) __trap(); }
}
__device__ __forceinline__ uint32_t lds(uint32_t a) { uint32_t v; asm volatile("ld.volatile.shared.u32 %0, [%1];" : "=r"(v) : "r"(a) : "memory"); return v; }

#define TRACE(u, e)
#define T3(u, e)
#define T2C(u, e)
#define T2P(u, r, e)
#define TTAIL(k)
#define TCLK(k)
#define TRACE_P(u, e)
#define TRACE_IN(u, e)

struct Ctx {
  uint32_t sb;
  int wg, warp;
  uint32_t mqk, mpv;
  bool lead;
  int src;
};
template <int N> __device__ __forceinline__ uint32_t dhi(uint32_t lo) { return 0x40000040u + (lo >> (26 + N)); }
__device__ __forceinline__ void release(const Ctx& c, uint32_t slot) {
  if (c.lead) mbar_arrive(c.sb + BAR_EMPTY + slot * 8);
}
__device__ __forceinline__ uint32_t acquire(const Ctx& c, Ring& r, bool have = false) {
  const uint32_t s = r.slot;
  if (!have) mbar_wait_w(c.sb + BAR_FULL + s * 8, r.phase);
  r.next();
  return s;
}
__device__ __forceinline__ void mbar_wait2_w(uint32_t b0, uint32_t p0, uint32_t b1, uint32_t p1) {
  uint32_t n = 0;
  while (!__all_sync(0xffffffffu, mbar_try(b0, p0) & mbar_try(b1, p1))) {
    if (++n > (1u << 22)) __trap();
  }
}
__device__ __forceinline__ void mbar_wait3_w(uint32_t b0, uint32_t p0, uint32_t b1, uint32_t p1, uint32_t b2, uint32_t p2) {
  uint32_t n = 0;
  while (!__all_sync(0xffffffffu, mbar_try(b0, p0) & mbar_try(b1, p1) & mbar_try(b2, p2))) {
    if (++n > (1u << 22)) __trap();
  }
}
__device__ __forceinline__ void acquire2(const Ctx& c, Ring& r, uint32_t& s0, uint32_t& s1, bool have = false) {
  const uint32_t p0 = r.phase;
  s0 = r.slot; r.next(); s1 = r.slot;
  if (!have) mbar_wait2_w(c.sb + BAR_FULL + s0 * 8, p0, c.sb + BAR_FULL + s1 * 8, r.phase);
  r.next();
}
template <int N>
__device__ __forceinline__ bool peek(const Ctx& c, Ring r) {
  bool ok = true;
#pragma unroll
  for (int k = 0; k < N; k++) { ok &= mbar_test(c.sb + BAR_FULL + r.slot * 8, r.phase); r.next(); }
  return ok;
}
__device__ __forceinline__ void staged(const Ctx& c, int part) {
  fence_async_smem();
  __syncwarp();
  mbar_arrive_warp(c.sb + BAR_STG + c.wg * 16 + part * 8);
}

template <int WG, bool FIRST, int H>
__device__ __forceinline__ void proj_half(const Ctx& c, float (&acc)[64], uint32_t w, uint32_t x, uint32_t sw) {
  uint64_t dx = desc64((c.sb + x * SLOT + (WG ? 0 : H * 8192)) >> 4, dhi<0>(x) + sw);
  uint64_t dw = desc64(WG ? (c.sb + w * SLOT + H * 8192) >> 4 : sdesc(c.sb + w * SLOT, 8192), dhi<1>(x));
  wg_fence();
  if (WG) { if (FIRST) wgmma_proj96_init(acc, dw, dx, 0); else wgmma_proj96(acc, dw, dx, 1); }
  else { if (FIRST) wgmma_proj_init(acc, dx, dw, 0); else wgmma_proj(acc, dx, dw, 1); }
#pragma unroll
  for (int k = 1; k < 4; k++) {
    dadd(dx, k == 2 ? 2 + (sw >> 30) * 28 : 2); dadd(dw, 128);
    if (WG) wgmma_proj96(acc, dw, dx, 1); else wgmma_proj(acc, dx, dw, 1);
  }
  wg_commit();
}

__device__ __forceinline__ void proj_store16(uint32_t a, const float* f, float sc) {
  stsm4t(a, pack_bf16(f[0] * sc, f[1] * sc), pack_bf16(f[2] * sc, f[3] * sc), pack_bf16(f[4] * sc, f[5] * sc), pack_bf16(f[6] * sc, f[7] * sc));
}

__device__ __forceinline__ uint32_t stage_off(const Ctx& c) {
  const int lane = lane_now(), mi = lane >> 3, r8 = lane & 7;
  return ((mi >> 1) * 8 + r8) * 128 + (((2 * c.warp + (mi & 1)) ^ r8) << 4);
}
__device__ __forceinline__ uint32_t q3_swz(uint32_t r8) { return ((r8 & 3) << 1) | (r8 >> 2); }
template <int H>
__device__ __forceinline__ void stage_t2(const Ctx& c, const float (&a)[64], float sc) {
  const uint32_t base = c.sb + QBUF_OFF + 2 * 16384 + H * 8192 + stage_off(c);
#pragma unroll
  for (int jj = 0; jj < 4; jj++) proj_store16(base + jj * 2048, &a[jj * 8], sc);
}
template <int H, bool IS_Q>
__device__ __forceinline__ void stage_t3(const Ctx& c, const float (&a)[64], float sc) {
  const uint32_t off = stage_off(c), r8 = (off >> 7) & 7;
  const uint32_t t3 = c.sb + QBUF_OFF + 3 * 16384 + H * 4096 + (IS_Q ? off ^ ((r8 ^ q3_swz(r8)) << 4) : off);
  proj_store16(t3, &a[32], sc);
  proj_store16(t3 + 2048, &a[40], sc);
}

template <bool TRANS>
__device__ __forceinline__ void add16(uint32_t a, float* f) {
  uint32_t r[4];
  if (TRANS) asm volatile("ldmatrix.sync.aligned.m8n8.x4.trans.shared.b16 {%0, %1, %2, %3}, [%4];"
                          : "=r"(r[0]), "=r"(r[1]), "=r"(r[2]), "=r"(r[3]) : "r"(a) : "memory");
  else ldsm4(a, r[0], r[1], r[2], r[3]);
#pragma unroll
  for (int i = 0; i < 4; i++) { f[2 * i] += __uint_as_float(r[i] << 16); f[2 * i + 1] += __uint_as_float(r[i] & 0xffff0000u); }
}

__device__ __forceinline__ void trace_dump(const Ctx& c) {
}
struct RowSum { float l0, l1; };
__device__ __forceinline__ const char* o_addr(uint32_t item, int row) {
  const int lane = lane_now();
  return reinterpret_cast<const char*>(g_o) + ((item * (2 * SQ) + row) * 128 + (lane ^ (lane >> 3)) * 16);
}
__device__ __forceinline__ void o_stg(const char* p, int i, const uint32_t* q) {
  asm volatile("st.global.v4.b32 [%0], {%1, %2, %3, %4};"
               ::"l"(p + (i >> 1) * (SQ * 128) + (i & 1) * 512), "r"(q[0]), "r"(q[1]), "r"(q[2]), "r"(q[3]) : "memory");
}
template <int MODE, int I0 = 0, int NI = 4>
__device__ __forceinline__ void o_emit(const char* p, const float (&o)[64], float inv) {
#pragma unroll
  for (int i = I0; i < I0 + NI; i++) {
    uint32_t q[4];
#pragma unroll
    for (int j = 0; j < 4; j++) q[j] = pack_bf16(o[16 * i + 4 * j + 2 * MODE] * inv, o[16 * i + 4 * j + 2 * MODE + 1] * inv);
    o_stg(p, i, q);
  }
}
__device__ __forceinline__ void o_done(const Ctx& c) {
  __syncwarp();
  mbar_arrive_warp(c.sb + BAR_OUT);
  __syncwarp();
}
__device__ __forceinline__ void pack3(float (&o)[64], const RowSum& inv, uint32_t (&q)[16]) {
  reg_fence(o);
#pragma unroll
  for (int j = 0; j < 16; j++) q[j] = pack_bf16((o[4 * j] + o[4 * j + 2]) * inv.l0, (o[4 * j + 1] + o[4 * j + 3]) * inv.l0);
  reg_fence(q);
}
template <int WG>
__device__ __forceinline__ void o_first(const Ctx& c, uint32_t item, const float (&o)[64], const RowSum& inv, const uint32_t (&q)[16]) {
  const char* p = o_addr(item, WG ? 192 + 8 * c.warp : 64 + 16 * c.warp);
  if (WG) {
#pragma unroll
    for (int i = 0; i < 4; i++) o_stg(p, i, q + 4 * i);
  } else { o_emit<0>(p, o, inv.l0); o_emit<1>(p + 1024, o, inv.l1); }
}
template <int K0, int K1>
__device__ __forceinline__ void o_piece(const Ctx& c, const char* p, int k, const float (&o)[64], const RowSum& inv) {
  constexpr int NI = 8 / O_STEPS, M = K0 * NI / 4;
  if constexpr (K1 - K0 == 1) {
    o_emit<M, K0 * NI % 4, NI>(p + M * 1024, o, M ? inv.l1 : inv.l0);
    if (K1 == O_STEPS) o_done(c);
  } else {
    if (k <= (K0 + K1) / 2) o_piece<K0, (K0 + K1) / 2>(c, p, k, o, inv); else o_piece<(K0 + K1) / 2, K1>(c, p, k, o, inv);
  }
}
template <int WG>
__device__ __forceinline__ void o_second(const Ctx& c, uint32_t item, int k, float (&o)[64], const RowSum& inv) {
  reg_fence(o);
  o_piece<0, O_STEPS>(c, o_addr(item, 128 * WG + 16 * c.warp), k, o, inv);
}
template <int WG>
__device__ __forceinline__ void release_q(const Ctx& c) {
#pragma unroll
  for (int t = 0; t < 2; t++)
    if (c.lead) asm volatile("mbarrier.arrive.shared::cta.b64 _, [%0], 2;" ::"r"(c.sb + BAR_EMPTY + (NS + 2 * WG + t) * 8) : "memory");
  __syncwarp();
}
struct Slots { uint32_t w, x, o, po; };
template <int WG>
__device__ __forceinline__ void acc_fence(float (&a)[64]) {
#pragma unroll
  for (int i = 0; i < (WG ? 48 : 64); i++) asm volatile("" : "+f"(a[i])::"memory");
}
template <int WG>
__device__ __forceinline__ void begin_acquire(const Ctx& c, Ring& r, Slots& h, bool wait) {
  const uint32_t s0 = r.slot, p0 = r.phase, f = c.sb + BAR_FULL;
  r.next();
  const uint32_t p1 = r.phase;
  h.w = r.slot; r.next();
  h.x = WG ? r.slot : s0; h.o = WG ? s0 : r.slot; h.po = r.phase;
  if (wait) { if (WG) mbar_wait3_w(f + s0 * 8, p0, f + h.w * 8, p1, f + h.x * 8, r.phase); else mbar_wait2_w(f + s0 * 8, p0, f + h.w * 8, p1); }
  r.next();
}
template <int WG>
__device__ __forceinline__ void proj_begin(const Ctx& c, Ring& r, float (&a0)[64], Slots& h, bool wait, uint32_t sw) {
  begin_acquire<WG>(c, r, h, wait);
  proj_half<WG, true, 0>(c, a0, h.w, h.x, sw);
  if (WG) release(c, h.o);
}
template <int WG>
__device__ __forceinline__ bool proj_main(const Ctx& c, Ring& r, float (&a0)[64], float (&a1)[64], Slots& h, int n, uint32_t sw, int unit,
                                          uint32_t item, int nq, float (&o1)[64], const RowSum& inv) {
  constexpr bool DEEP = (PDEPTH >> WG) & 1;
  T2C(unit, 3);
  int ks = 1;
#pragma unroll 1
  do {
    const Slots p = h;
    const uint32_t b = borrow(ks, n), tile = NS + (WG ? 3 - b : b), f = c.sb + BAR_FULL;
    const uint32_t s0 = b != 2 ? tile : r.slot, p0 = b != 2 ? (r.xp >> b) & 1 : r.phase;
    r.next_if(b == 2);
    const uint32_t p1 = r.phase;
    h.w = r.slot; r.next();
    const uint32_t s2 = b != 2 ? tile : r.slot;
    h.po = b != 2 ? p0 : r.phase;
    r.next_if(b == 2);
    r.xp ^= 1 << b;
    h.x = WG ? s2 : s0; h.o = WG ? s0 : s2;
    mbar_wait3_w(f + s0 * 8, p0, f + h.w * 8, p1, f + (WG ? s2 : p.o) * 8, WG ? h.po : p.po);
    if (ks < 10) T2C(unit, ks * 4);
    if (DEEP) {
      proj_half<WG, false, 0>(c, a0, h.w, h.x, sw);
      release(c, WG ? h.o : p.o);
      if (ks < 10) T2C(unit, ks * 4 + 1);
      wg_wait<1>();
      if (ks < 10) T2C(unit, ks * 4 + 2);
      release(c, p.x); release(c, p.w);
    } else {
      release(c, WG ? h.o : p.o);
      wg_wait<0>();
      release(c, p.x); release(c, p.w);
      if (LAST_SYNC && !WG) asm volatile("{\n.reg .pred p;\nsetp.eq.u32 p, %0, %1;\n@p bar.sync 5, 256;\n}" ::"r"(ks + LAST_SYNC), "r"(n) : "memory");
      if (ks < 10) T2C(unit, ks * 4 + 1);
      proj_half<WG, false, 0>(c, a0, h.w, h.x, sw);
      if (ks < 10) T2C(unit, ks * 4 + 2);
    }
    if (LAST_SYNC && WG && !DEEP) asm volatile("{\n.reg .pred p;\nsetp.eq.u32 p, %0, %1;\n@p bar.arrive 5, 256;\n}" ::"r"(ks + LAST_SYNC), "r"(n) : "memory");
    proj_half<WG, false, 1>(c, a1, h.w, h.x, sw);
    if (LAST_SYNC && WG && DEEP) asm volatile("{\n.reg .pred p;\nsetp.eq.u32 p, %0, %1;\n@p bar.arrive 5, 256;\n}" ::"r"(ks + LAST_SYNC), "r"(n) : "memory");
    if (ks < 10) T2C(unit, ks * 4 + 3);
    if (ks <= nq) o_second<WG>(c, item, ks, o1, inv);
  } while (++ks != n);
  {
    const uint32_t e0 = c.sb + BAR_EMPTY + (NS + 3 * WG) * 8, e1 = c.sb + BAR_EMPTY + (NS + 1 + WG) * 8;
    const uint32_t p0 = (r.xp ^ unit ^ 1) & 1, p1 = ((r.xp >> 1) ^ unit ^ 1) & 1;
    if (WG) mbar_wait2_w(e0, p0, e1, p1); else mbar_wait3_w(e0, p0, e1, p1, c.sb + BAR_FULL + h.o * 8, h.po);
  }
  const bool have = PEEK ? peek<3>(c, r) : false;
  if (!WG) release(c, h.o);
  wg_wait<1>();
  acc_fence<WG>(a0);
  return PEEK && __all_sync(0xffffffffu, have);
}
template <int WG>
__device__ __forceinline__ void proj_end(const Ctx& c, float (&a1)[64], const Slots& h) {
  wg_wait<0>();
  acc_fence<WG>(a1);
  release(c, h.x); release(c, h.w);
}
__device__ __forceinline__ uint32_t get_desc(const Ctx& c, int i) {
  uint32_t d;
  mbar_wait_w(c.sb + BAR_DESC, (i - 1) & 1);
  asm volatile("ld.volatile.shared.u32 %0, [%1];" : "=r"(d) : "r"(c.sb + DESC_OFF + (i & 3) * 4) : "memory");
  return __shfl_sync(0xffffffffu, d, 0);
}

__device__ __forceinline__ float quad_max(float x) {
  x = fmaxf(x, __shfl_xor_sync(0xffffffffu, x, 1));
  return fmaxf(x, __shfl_xor_sync(0xffffffffu, x, 2));
}
__device__ __forceinline__ float quad_sum(float x) {
  x += __shfl_xor_sync(0xffffffffu, x, 1);
  return x + __shfl_xor_sync(0xffffffffu, x, 2);
}
template <bool SP, bool FIRST>
__device__ __forceinline__ void exps(const Ctx& c, const float (&s)[32], uint32_t (&p)[SP ? 8 : 16], RowSum& st) {
  if constexpr (SP) {
    uint32_t q[8];
    float t;
#pragma unroll
    for (int j = 0; j < 8; j++) {
      const float e0 = ex2(s[4 * j] + s[4 * j + 2]), e1 = ex2(s[4 * j + 1] + s[4 * j + 3]);
      if (j == 0) t = e0 + e1; else t += e0 + e1;
      q[j] = pack_bf16(e0, e1);
    }
    const bool odd = c.src & 2;
#pragma unroll
    for (int g = 0; g < 4; g++) {
      p[2 * g] = __shfl_sync(0xffffffffu, odd ? q[2 * g + 1] : q[2 * g], c.src);
      p[2 * g + 1] = __shfl_sync(0xffffffffu, odd ? q[2 * g] : q[2 * g + 1], c.src ^ 1);
    }
    st.l0 = FIRST ? t : st.l0 + t;
  } else {
    float t0, t1;
#pragma unroll
    for (int j = 0; j < 8; j++) {
      const float e0 = ex2(s[4 * j]), e1 = ex2(s[4 * j + 1]), e2 = ex2(s[4 * j + 2]), e3 = ex2(s[4 * j + 3]);
      if (j == 0) { t0 = e0 + e1; t1 = e2 + e3; } else { t0 += e0 + e1; t1 += e2 + e3; }
      p[2 * j] = pack_bf16(e0, e1);
      p[2 * j + 1] = pack_bf16(e2, e3);
    }
    st.l0 = FIRST ? t0 : st.l0 + t0;
    st.l1 = FIRST ? t1 : st.l1 + t1;
  }
}
template <bool SP>
__device__ __forceinline__ bool finish_sums(RowSum& st) {
  const float a = quad_sum(st.l0), b = SP ? a : quad_sum(st.l1);
  st.l0 = __fdividef(1.f, a); st.l1 = __fdividef(1.f, b);
  return !DEV_HALF && !(a >= SUM_LO && a <= SUM_HI && b >= SUM_LO && b <= SUM_HI);
}
template <bool SP, bool INIT, int SITE, bool COMMIT = true>
__device__ __forceinline__ void issue_qk(const Ctx& c, float (&s)[32], const uint32_t (&qs)[16], uint32_t dq, uint32_t dk) {
  uint64_t a = desc64(dq, dhi<SITE & 1>(dk)), b = desc64(dk, dhi<1 - (SITE & 1)>(dk));
  if (SP) {
    if (INIT) wgmma_qk_sp_init(s, qs[0], qs[1], qs[2], qs[3], b, 0, c.mqk); else wgmma_qk_sp(s, qs[0], qs[1], qs[2], qs[3], b, 0, c.mqk);
#pragma unroll
    for (int k = 1; k < 4; k++) { dadd(b, k == 2 ? 508 : 4); wgmma_qk_sp(s, qs[4 * k], qs[4 * k + 1], qs[4 * k + 2], qs[4 * k + 3], b, 1, c.mqk); }
  } else {
    if (INIT) wgmma_qk_init(s, a, b, 0); else wgmma_qk(s, a, b, 0);
#pragma unroll
    for (int k = 1; k < 8; k++) { dadd(a, k == 4 ? 506 : 2); dadd(b, k == 4 ? 506 : 2); wgmma_qk(s, a, b, 1); }
  }
  if (COMMIT) wg_commit();
}
template <bool SP, bool ACC, int SITE, bool SPLIT = false>
__device__ __forceinline__ void issue_pv(const Ctx& c, float (&o)[64], const uint32_t (&p)[SP ? 8 : 16], uint32_t dv) {
  uint64_t b = desc64(dv, dhi<SITE & 1>(dv));
  if constexpr (SP) {
    if (ACC) wgmma_pv_sp(o, p[0], p[1], p[2], p[3], b, 1, c.mpv); else wgmma_pv_sp_init(o, p[0], p[1], p[2], p[3], b, 0, c.mpv);
    if (SPLIT) wg_commit();
    dadd(b, 256);
    wgmma_pv_sp(o, p[4], p[5], p[6], p[7], b, 1, c.mpv);
  } else {
    if (ACC) wgmma_pv(o, p[0], p[1], p[2], p[3], b, 1); else wgmma_pv_init(o, p[0], p[1], p[2], p[3], b, 0);
#pragma unroll
    for (int k = 1; k < 4; k++) { dadd(b, 128); wgmma_pv(o, p[4 * k], p[4 * k + 1], p[4 * k + 2], p[4 * k + 3], b, 1); }
  }
  wg_commit();
}
__device__ __forceinline__ void pack_rows(const float (&o)[64], float sc, uint32_t (&q)[32]) {
#pragma unroll
  for (int j = 0; j < 32; j++) q[j] = pack_bf16(o[2 * j] * sc, o[2 * j + 1] * sc);
}
__device__ __forceinline__ void stage_rows(const Ctx& c, uint32_t tile_addr, const uint32_t (&q)[32]) {
  const int lane = lane_now(), mi = lane >> 3, r8 = lane & 7;
  const uint32_t row_addr = tile_addr + (16 * c.warp + (mi & 1) * 8 + r8) * 128;
#pragma unroll
  for (int jj = 0; jj < 8; jj++)
    stsm4(row_addr + (jj >> 2) * 8192 + (((((2 * jj) & 7) + (mi >> 1)) ^ r8) << 4), q[4 * jj], q[4 * jj + 1], q[4 * jj + 2], q[4 * jj + 3]);
}
__device__ __forceinline__ void stage_rows(const Ctx& c, uint32_t tile_addr, const float (&o)[64], float sc) {
  uint32_t q[32];
  pack_rows(o, sc, q);
  stage_rows(c, tile_addr, q);
}
template <int SITE>
__device__ __forceinline__ void issue_qk_rs(float (&s)[32], uint32_t (&q)[32], uint32_t dk) {
  uint64_t b = desc64(dk, dhi<SITE>(dk));
  reg_fence(q);
  wg_fence();
  wgmma_qk_rs_init(s, q[0], q[1], q[2], q[3], b, 0);
#pragma unroll
  for (int k = 1; k < 8; k++) { dadd(b, k == 4 ? 506 : 2); wgmma_qk_rs(s, q[4 * k], q[4 * k + 1], q[4 * k + 2], q[4 * k + 3], b, 1); }
  wg_commit();
}

__device__ __forceinline__ void redo_tile(const Ctx& c, uint32_t q_addr, uint32_t half, const __nv_bfloat16* kp, const __nv_bfloat16* vp,
                                          uint32_t item, int row) {
  float o[64];
  const int lane = lane_now(), g = lane >> 2, cc = lane & 3, mi = lane >> 3, r8 = lane & 7;
  const uint32_t qa = q_addr + (half == 4096 ? 8 * c.warp + r8 : 16 * c.warp + (mi & 1) * 8 + r8) * 128, swz = half == 4096 ? q3_swz(r8) : r8;
  const uint32_t* kq = reinterpret_cast<const uint32_t*>(kp + g * DH) + cc;
  const unsigned short* vq = reinterpret_cast<const unsigned short*>(vp + 2 * cc * DH) + g;
  float m0 = -INFINITY, m1 = -INFINITY, l0 = 0.f, l1 = 0.f;
#pragma unroll
  for (int i = 0; i < 64; i++) o[i] = 0.f;
#pragma unroll 1
  for (int kb = 0; kb < SK / 16; kb++) {
    float z[8] = {0.f, 0.f, 0.f, 0.f, 0.f, 0.f, 0.f, 0.f};
#pragma unroll 2
    for (int kk = 0; kk < 8; kk++) {
      uint32_t a0, a1, a2, a3;
      ldsm4(qa + (kk >> 2) * half + ((((kk & 3) * 2 + (mi >> 1)) ^ swz) << 4), a0, a1, a2, a3);
      const uint32_t* kr = kq + kb * (16 * DH / 2) + kk * 8;
      mma16816(z[0], z[1], z[2], z[3], a0, a1, a2, a3, __ldg(kr), __ldg(kr + 4));
      mma16816(z[4], z[5], z[6], z[7], a0, a1, a2, a3, __ldg(kr + 8 * DH / 2), __ldg(kr + 8 * DH / 2 + 4));
    }
    const float n0 = fmaxf(m0, quad_max(fmaxf(fmaxf(z[0], z[1]), fmaxf(z[4], z[5]))));
    const float n1 = fmaxf(m1, quad_max(fmaxf(fmaxf(z[2], z[3]), fmaxf(z[6], z[7]))));
    const float al0 = ex2(m0 - n0), al1 = ex2(m1 - n1);
    m0 = n0; m1 = n1;
#pragma unroll
    for (int i = 0; i < 8; i++) z[i] = ex2(z[i] - ((i & 2) ? n1 : n0));
    l0 = l0 * al0 + (z[0] + z[1]) + (z[4] + z[5]);
    l1 = l1 * al1 + (z[2] + z[3]) + (z[6] + z[7]);
    const uint32_t a0 = pack_bf16(z[0], z[1]), a1 = pack_bf16(z[2], z[3]), a2 = pack_bf16(z[4], z[5]), a3 = pack_bf16(z[6], z[7]);
    const unsigned short* vr = vq + kb * (16 * DH);
#pragma unroll
    for (int nb = 0; nb < 16; nb++) {
      o[4 * nb] *= al0; o[4 * nb + 1] *= al0; o[4 * nb + 2] *= al1; o[4 * nb + 3] *= al1;
      const uint32_t b0 = __ldg(vr + nb * 8) | ((uint32_t)__ldg(vr + nb * 8 + DH) << 16);
      const uint32_t b1 = __ldg(vr + nb * 8 + 8 * DH) | ((uint32_t)__ldg(vr + nb * 8 + 9 * DH) << 16);
      mma16816(o[4 * nb], o[4 * nb + 1], o[4 * nb + 2], o[4 * nb + 3], a0, a1, a2, a3, b0, b1);
    }
  }
  const char* p = o_addr(item, row);
  o_emit<0>(p, o, __fdividef(1.f, quad_sum(l0)));
  o_emit<1>(half == 4096 ? p : p + 1024, o, __fdividef(1.f, quad_sum(l1)));
}

template <bool SPA, bool SPB, int SITE, int ID>
__device__ __forceinline__ void batch(const Ctx& c, float (&s)[32], const uint32_t (&qs)[16], uint32_t dq, uint32_t dk, float (&ob)[64],
                                      uint32_t (&pb)[SPB ? 8 : 16], uint32_t dv) {
  if constexpr (SPA) {
    reg_fence(pb);
    wg_fence();
    issue_pv<SPB, true, ID>(c, ob, pb, dv);
    issue_qk<SPA, false, ID>(c, s, qs, dq, dk);
  } else {
    constexpr bool EARLY = ((QK_EARLY_MASK >> (SITE + (SPB ? 2 : 0))) & 1) != 0;
    if (!EARLY) reg_fence(pb);
    wg_fence();
    issue_qk<SPA, false, ID, !SPB>(c, s, qs, dq, dk);
    if (EARLY) { reg_fence(pb); wg_fence(); }
    issue_pv<SPB, true, ID, SPB>(c, ob, pb, dv);
  }
}

template <bool SP0>
__device__ __forceinline__ bool attention(Ctx c, Ring& r, int unit, uint32_t& d, const float (&a0)[64], float (&o0)[64], float (&o1)[64],
                                          RowSum& st0, RowSum& st1, const Slots& h, uint32_t (&q3)[16], bool kv) {
  constexpr bool SP1 = false;
  if (SP0) { c.mqk = META_QK + (d >> 28); c.mpv = META_PV + (d >> 28); asm volatile("" : "+r"(c.mqk), "+r"(c.mpv)); }
  if (SP0) { const int lane = lane_now(); c.src = (lane & 28) | ((lane & 1) << 1) | ((lane >> 1) & 1); }
  float s[32];
  uint32_t p0[SP0 ? 8 : 16], p1[16];
  const uint32_t q0a = c.sb + QBUF_OFF + (SP0 ? 3 : 0) * 16384, q1a = c.sb + QBUF_OFF + (SP0 ? 2 : 1) * 16384;
  const uint32_t dq0 = sdesc(q0a, 0), dq1 = sdesc(q1a, 0);
  uint32_t sk, sv, sn;
  uint32_t qs[16];
  T2C(unit, 40);
  if (SP0) {
    stage_t3<0, true>(c, a0, SM_C);
    stage_t2<0>(c, a0, SM_C);
    T2C(unit, 41);
    proj_end<1>(c, o0, h);
    T2C(unit, 42);
    stage_t3<1, true>(c, o0, SM_C);
    stage_t2<1>(c, o0, SM_C);
    sk = acquire(c, r, kv);
    fence_async_smem();
    T2C(unit, 43);
    bar_sync(1, LAG_BAR & 30 ? 256 : 128);
    const int lane = lane_now(), g = lane >> 2, cc = lane & 3;
    const uint32_t qa = q0a + (8 * c.warp + g) * 128 + (cc & 1) * 8;
#pragma unroll
    for (int k = 0; k < 8; k++)
      asm volatile("ld.shared.v2.u32 {%0, %1}, [%2];" : "=r"(qs[2 * k]), "=r"(qs[2 * k + 1])
                   : "r"(qa + (k >> 2) * 4096 + ((((k & 3) * 2 + (cc >> 1)) ^ q3_swz(g)) << 4)) : "memory");
    TRACE(unit, 2);
    T2C(unit, 44);
    float s1[32];
    wg_fence();
    issue_qk<SP1, true, 1>(c, s1, qs, dq1, sdesc(c.sb + sk * SLOT, 0));
    reg_fence(qs);
    wg_fence();
    issue_qk<SP0, true, 0>(c, s, qs, dq0, sdesc(c.sb + sk * SLOT, 0));
    T2C(unit, 45);
    acquire2(c, r, sv, sn, kv);
    wg_wait<1>();
    reg_fence(s1);
    T2C(unit, 47);
    exps<SP1, true>(c, s1, p1, st1);
    reg_fence(p1);
    wg_fence();
    issue_pv<SP1, false, 1>(c, o1, p1, sdesc(c.sb + sv * SLOT, 8192));
    if (LAG_BAR & 1) asm volatile("bar.arrive 4, 256;" ::: "memory");
    wg_wait<1>();
    reg_fence(s);
    T2C(unit, 48);
    release(c, sk);
    sk = sn;
    exps<SP0, true>(c, s, p0, st0);
    reg_fence(p0);
    wg_fence();
    issue_pv<SP0, false, 0>(c, o0, p0, sdesc(c.sb + sv * SLOT, 8192));
    issue_qk<SP0, false, 2>(c, s, qs, dq0, sdesc(c.sb + sk * SLOT, 0));
    T2C(unit, 49);
    sn = acquire(c, r);
    T2C(unit, 50);
    wg_wait<0>();
    reg_fence(s);
  } else {
    float s1[32];
    uint32_t q0[32], q1[32];
    if (!PEEK) sk = acquire(c, r);
    pack_rows(a0, SM_C, q0);
    if (RS_STAGE & 1) stage_rows(c, q0a, q0);
    reg_fence(q0);
    if (PEEK) sk = acquire(c, r, kv);
    T2C(unit, 41);
    proj_end<0>(c, o1, h);
    TRACE(unit, 2);
    T2C(unit, 42);
    issue_qk_rs<0>(s, q0, sdesc(c.sb + sk * SLOT, 0));
    if (LAG_BAR & 8) asm volatile("bar.arrive 1, 256;" ::: "memory");
    T2C(unit, 43);
    reg_fence(o1);
    pack_rows(o1, SM_C, q1);
    if (RS_STAGE & 2) stage_rows(c, q1a, q1);
    T2C(unit, 44);
    if (LAG_BAR & 4) asm volatile("bar.arrive 1, 256;" ::: "memory");
    issue_qk_rs<1>(s1, q1, sdesc(c.sb + sk * SLOT, 0));
    if (LAG_BAR & 2) asm volatile("bar.arrive 1, 256;" ::: "memory");
    T2C(unit, 45);
    acquire2(c, r, sv, sn, kv);
    if (!(RS_STAGE & 5)) stage_rows(c, q0a, q0);
    if (!(RS_STAGE & 10)) stage_rows(c, q1a, q1);
    T2C(unit, 46);
    wg_wait<1>();
    reg_fence(s);
    if (LAG_BAR & 16) asm volatile("bar.arrive 1, 256;" ::: "memory");
    T2C(unit, 47);
    if (RS_STAGE & 4) { reg_fence(q0); stage_rows(c, q0a, q0); }
    exps<SP0, true>(c, s, p0, st0);
    reg_fence(p0);
    wg_wait<0>();
    reg_fence(s1);
    if (RS_STAGE & 8) { reg_fence(q1); stage_rows(c, q1a, q1); }
    fence_async_smem();
    __syncwarp();
    wg_fence();
    issue_qk<SP0, false, 2>(c, s, qs, dq0, sdesc(c.sb + sn * SLOT, 0));
    issue_pv<SP0, false, 0>(c, o0, p0, sdesc(c.sb + sv * SLOT, 8192));
    T2C(unit, 48);
    release(c, sk);
    sk = sn;
    exps<SP1, true>(c, s1, p1, st1);
    reg_fence(p1);
    wg_fence();
    issue_pv<SP1, false, 1>(c, o1, p1, sdesc(c.sb + sv * SLOT, 8192));
    T2C(unit, 49);
    sn = acquire(c, r);
    if (LAG_BAR & 1) bar_sync(4, 256);
    T2C(unit, 50);
    wg_wait<1>();
    reg_fence(s);
  }
  TRACE_IN(unit, 4);
  T2C(unit, 51);
#pragma unroll 1
  for (int j = 1; j < 15; j++) {
    const uint32_t sv_prev = sv, sk_prev = sk;
    sv = sn;
    const uint32_t dv = sdesc(c.sb + sv * SLOT, 8192);
    reg_fence(p0);
    exps<SP0, false>(c, s, p0, st0);
    batch<SP1, SP0, 0, 3>(c, s, qs, dq1, sdesc(c.sb + sk * SLOT, 0), o0, p0, dv);
    sk = acquire(c, r);
    wg_wait<1>();
    reg_fence(s); reg_fence(p1);
    release(c, sv_prev); release(c, sk_prev);
    exps<SP1, false>(c, s, p1, st1);
    batch<SP0, SP1, 1, 4>(c, s, qs, dq0, sdesc(c.sb + sk * SLOT, 0), o1, p1, dv);
    sn = acquire(c, r);
    if (SP0) wg_wait<0>(); else wg_wait<1>();
    reg_fence(s);
  }
  TRACE_IN(unit, 5);
  T2C(unit + 1, 52);
  const uint32_t sv_prev = sv;
  sv = sn;
  const uint32_t dv = sdesc(c.sb + sv * SLOT, 8192);
  reg_fence(p0);
  exps<SP0, false>(c, s, p0, st0);
  batch<SP1, SP0, 0, 5>(c, s, qs, dq1, sdesc(c.sb + sk * SLOT, 0), o0, p0, dv);
  asm volatile("ld.volatile.shared.u32 %0, [%1];" : "=r"(d) : "r"(c.sb + DESC_OFF + ((unit + 1) & 3) * 4) : "memory");
  wg_wait<1>();
  reg_fence(s); reg_fence(p1);
  T2C(unit + 1, 53);
  release(c, sv_prev); release(c, sk);
  d = __shfl_sync(0xffffffffu, d, 0);
  const bool bad0 = finish_sums<SP0>(st0);
  exps<SP1, false>(c, s, p1, st1);
  reg_fence(p1);
  wg_fence();
  issue_pv<SP1, true, 2>(c, o1, p1, dv);
  T2C(unit + 1, 54);
  const bool have = peek<2 + SP0>(c, r);
  const bool bad = finish_sums<SP1>(st1) | bad0;
  if (SP0 && !PACK_LATE) {
    wg_wait<1>();
    pack3(o0, st0, q3);
  }
  T2C(unit + 1, 55);
  if (EARLY_BEG && d < (2u << 30) && !__all_sync(0xffffffffu, have)) { Ring t = r; Slots u; begin_acquire<SP0>(c, t, u, true); }
  T2C(unit + 1, 56);
  wg_wait<0>();
  if (!SP0 || PACK_LATE) reg_fence(o0);
  reg_fence(o1);
  T2C(unit + 1, 57);
  release(c, sv);
  return bad;
}
template <int WG>
__device__ __forceinline__ bool wg_any(bool p) {
  uint32_t any;
  asm volatile("{\n.reg .pred p, q;\nsetp.ne.u32 p, %1, 0;\nbar.red.or.pred q, %2, 128, p;\nselp.u32 %0, 1, 0, q;\n}"
               : "=r"(any) : "r"((uint32_t)p), "n"(2 + WG) : "memory");
  return __any_sync(0xffffffffu, any);
}

template <int WG>
__device__ __forceinline__ void consumer(Ctx c, const __nv_bfloat16* const* kv) {
  c.wg = WG;
  Ring r{0, 0, 0};
  bool bad;
  uint32_t q3[16];
  float a0[64], a1[64], o1[64];
  Slots h;
  RowSum inv0, inv1;
  uint32_t d = blockIdx.x, dc = 0, sw;
  int i = 0, nq;
begin:
  sw = d & (1u << 30);
  proj_begin<WG>(c, r, a0, h, true, sw);
  proj_half<WG, true, 1>(c, a1, h.w, h.x, sw);
  nq = 0;
#pragma unroll
  for (int k = 0; k < 64; k++) asm volatile("" : "=f"(o1[k]));
  asm volatile("" : "=f"(inv1.l0), "=f"(inv1.l1));
  while (true) {
    TRACE(i, 0); TRACE(i, 6);
    bad = proj_main<WG>(c, r, a0, a1, h, d >> 30 ? ((d >> 16) & 63) + 1 : DM / 64, sw, i, dc, nq, o1, inv1);
    dc = d;
    TRACE(i, 1);
    if (d >> 30) goto out_tile;
    bad = WG ? attention<WG>(c, r, i, d, a0, a1, o1, inv0, inv1, h, q3, bad) : attention<WG>(c, r, i, d, a0, o1, a1, inv1, inv0, h, q3, bad);
    if (!EARLY_BEG || d >= (2u << 30)) break;
    Ring t = r;
    sw = d & (1u << 30);
    begin_acquire<WG>(c, t, h, false);
    proj_half<WG, true, 0>(c, a0, h.w, h.x, sw);
    if (WG && PACK_LATE) pack3(a1, inv0, q3);
    if (WG && RED_FIRST != 2) proj_half<WG, true, 1>(c, a1, h.w, h.x, sw); else if (!WG) reg_fence(a1);
    T2C(i + 1, 58);
    if (!WG || RED_FIRST != 1) o_first<WG>(c, dc, a1, inv0, q3);
    if (__builtin_expect(wg_any<WG>(bad), 0)) {
      wg_wait<0>();
      acc_fence<WG>(a0);
      if (WG && RED_FIRST != 2) acc_fence<WG>(a1);
      goto redo;
    }
    r = t;
    T2C(i + 1, 1);
    if (!WG || RED_FIRST == 2) proj_half<WG, true, 1>(c, a1, h.w, h.x, sw);
    if (WG) release(c, h.o);
    release_q<WG>(c);
    if (WG && RED_FIRST == 1) o_first<WG>(c, dc, a1, inv0, q3);
    T2C(i + 1, 2);
    nq = O_STEPS;
    TRACE(i, 3); TRACE(i, 7);
    i++;
  }
  if (wg_any<WG>(bad)) goto redo;
  release_q<WG>(c);
  if (WG && PACK_LATE) pack3(a1, inv0, q3);
  o_first<WG>(c, dc, a1, inv0, q3);
#pragma unroll
  for (int k = 1; k <= O_STEPS; k++) o_second<WG>(c, dc, k, o1, inv1);
  T2C(i + 1, 58);
next:
  TRACE(i, 3); TRACE(i, 7);
  if ((d >> 30) != 2) {
    i++;
    r.uniform();
    goto begin;
  }
  trace_dump(c);
  return;
out_tile:
  proj_end<WG>(c, a1, h);
  if (((d >> 28) & 3) == 2) {
    const int lane = lane_now(), mi = lane >> 3, r8 = lane & 7;
    const uint32_t off = c.sb + (WG ? stage_off(c) : (16 * c.warp + (mi & 1) * 8 + r8) * 128);
#pragma unroll 1
    for (int k = (d >> 5) & 3; k > 0; k--) {
      uint32_t s0, s1;
      if (WG) { acquire2(c, r, s0, s1); release(c, s0); release(c, s1); }
#pragma unroll
      for (int t = 0; t < 2; t++) {
        const uint32_t sp = acquire(c, r), base = off + sp * SLOT;
        if (WG) {
#pragma unroll
          for (int jj = 0; jj < (t ? 2 : 4); jj++) {
            add16<true>(base + jj * 2048, &a0[(t * 4 + jj) * 8]);
            add16<true>(base + jj * 2048 + (t ? 4096 : 8192), &a1[(t * 4 + jj) * 8]);
          }
        } else {
#pragma unroll
          for (int jj = 0; jj < 8; jj++) add16<false>(base + (jj >> 2) * 8192 + (((((2 * jj) & 7) + (mi >> 1)) ^ r8) << 4), t ? &a1[jj * 8] : &a0[jj * 8]);
        }
        release(c, sp);
      }
      if (!WG) { acquire2(c, r, s0, s1); release(c, s0); release(c, s1); }
    }
  }
  if (WG) { stage_t3<0, false>(c, a0, 1.f); stage_t3<1, false>(c, a1, 1.f); }
  else stage_rows(c, c.sb + QBUF_OFF, a0, 1.f);
  staged(c, 0);
  if (WG) { stage_t2<0>(c, a0, 1.f); stage_t2<1>(c, a1, 1.f); }
  else stage_rows(c, c.sb + QBUF_OFF + 16384, a1, 1.f);
  staged(c, 1);
  d = get_desc(c, i + 1);
  TRACE(i, 2);
  goto next;
redo:
  {
    const size_t hoff = (size_t)(dc & 511) * (SK * DH);
    const int br = (dc >> 9) & 1;
#pragma unroll 1
    for (int part = 0; part < 2; part++) {
      const int t = WG ? 3 - part : part;
      redo_tile(c, c.sb + QBUF_OFF + t * 16384, t == 3 ? 4096 : 8192, kv[br] + hoff, kv[2 + br] + hoff, dc,
                t * 64 + (t == 3 ? 8 : 16) * c.warp);
    }
    o_done(c);
    release_q<WG>(c);
  }
  goto next;
}

template <bool SIMPLE>
__global__ void __launch_bounds__(384, 1) mha_fused_kernel(const __grid_constant__ Params P) {
  extern __shared__ __align__(1024) uint8_t smem_raw[];
  const uint32_t sbase = smem_u32(smem_raw);
  const int tid = threadIdx.x;
  const int wg = __shfl_sync(0xffffffffu, tid >> 7, 0);
  const int warp = __shfl_sync(0xffffffffu, (tid >> 5) & 3, 0);
  const int lane = tid & 31;
  const int cta = blockIdx.x;

  if (tid == 0) T3(15, 0);
  if (tid >= 256 && tid < 256 + 18) asm volatile("prefetch.tensormap [%0];" ::"l"(&P.x[0][0] + (tid - 256)) : "memory");
  if (tid == 0) {
    if ((sbase & 1023) || sbase + SMEM_BYTES > 0x40000) __trap();
    for (int i = 0; i < NSX; i++) { mbar_init(sbase + BAR_FULL + i * 8, 1); mbar_init(sbase + BAR_EMPTY + i * 8, 8); }
    for (int i = 0; i < 4; i++) mbar_init(sbase + BAR_STG + i * 8, 4);
    mbar_init(sbase + BAR_OUT, 8);
    mbar_init(sbase + BAR_DESC, 1);
    mbar_init(sbase + BAR_GO, 1);
    asm volatile("fence.mbarrier_init.release.cluster;" ::: "memory");
  }
  __syncthreads();

  if (wg == 2) {
    asm volatile("setmaxnreg.dec.sync.aligned.u32 %0;" ::"n"(REG_P));
    if (warp == 1) {
      const uint32_t qb = sbase + QBUF_OFF;
      const uint32_t ep = __shfl_sync(0xffffffffu, *(volatile unsigned*)&g_epoch + 1, 0);
      asm volatile("st.volatile.shared.u32 [%0], %1;" ::"r"(sbase + EPOCH_OFF), "r"(ep) : "memory");
      uint32_t dc = cta, qi = 0, piece = 0, na = 0;
      TTAIL(0);
      for (int i = 0; (dc >> 30) != 2; i++) {
        mbar_wait_w(sbase + BAR_GO, i & 1);
        if (TLB_WARM && (dc >> 30) == 0) asm volatile(ELECT "st.global.u32 [%0], 0;\n}" ::"l"(g_o + dc * (2 * SQ * 64)) : "memory");
        if (piece == 0) {
          if (lane == 0) {
            qi = atomicAdd(&g_next, 1);
            if (qi == (SIMPLE ? NBETA * (NH + 5) : Q_RANGES) - 1) { g_next = 0; g_epoch = ep; }
          }
          qi = __shfl_sync(0xffffffffu, qi, 0) + (SIMPLE ? gridDim.x : NCTA);
        }
        uint32_t d;
        if (qi < Q_RANGES) { d = c_sched.queue[qi]; if (d & 0x8000) d ^= (1u << 30) | (63u << 16) | 0x8000; }
        else if (SIMPLE) { const uint32_t t = qi - NBETA * NH; d = t < NBETA * 5 ? (1u << 30) | (63u << 16) | (t % 5) << 8 | t / 5 : 2u << 30; }
        else { const uint32_t e = qi - Q_RANGES, g = e / 5; d = c_sched.piece[g][piece++] | (e - g * 5) << 8; }
        if ((d >> 30) == 1) {
          const uint32_t ok = __ballot_sync(0xffffffffu, reached(&g_cnt[lane & 1][d & 31], ep * (lane & 1 ? NH - H_LATE : H_LATE)));
          if (!(ok & 2)) d |= ((d >> 22) & 63) >= 2 * H_LATE - O_STEPS ? (2u << 30) | 128 : 128;
          if (!(ok & 1) || (O_STEPS > 4 && ((d >> 16) & 63) < O_STEPS)) d |= 2u << 30;
        }
        asm volatile("st.volatile.shared.u32 [%0], %1;" ::"r"(sbase + DESC_OFF + ((i + 1) & 3) * 4), "r"(d) : "memory");
        __syncwarp();
        mbar_arrive_warp(sbase + BAR_DESC);
        const Work w = decode(dc);
        dc = d;
        if (w.kind == 0) {
          mbar_wait_w(sbase + BAR_OUT, na++ & 1);
          TTAIL(1);
          T3(i, 0); T3(i, 1);
          asm volatile(ELECT "red.release.gpu.global.add.u32 [%0], 1;\n}" ::"l"(&g_cnt[w.sub >= H_LATE][w.beta]) : "memory");
          T3(i, 2);
          TTAIL(2);
          continue;
        }
        const bool fin = w.mode != 1;
        uint64_t pol, pol2;
        asm volatile("createpolicy.fractional.L2::evict_first.b64 %0, 1.0;" : "=l"(pol));
        asm volatile("createpolicy.fractional.L2::evict_normal.b64 %0, 1.0;" : "=l"(pol2));
        if (!fin) pol = pol2;
        const CUtensorMap* m = fin ? P.out_st : P.o_st;
        const int c1 = fin ? (w.beta & 15) * SQ : 0;
        const int c2 = fin ? (w.beta >> 4) * (DM / 64) + w.sub * 2 : NBETA * 64 + w.range * 2;
        uint32_t pend = 0;
#pragma unroll 1
        for (int e = 0; e < 4; e++) {
          const int t = (ST_ORDER >> (4 * e)) & 3;
          mbar_wait_w(sbase + BAR_STG + (t ^ (t >> 1)) * 8, (i - na) & 1);
          tma_st3_hint_w(m + (t == 3), qb + t * 16384, 0, c1 + t * 64, c2, pol);
          bulk_commit();
          T2P(i + 1, 5, 2 * e);
          if (pend) {
            bulk_wait_read<1>();
            mbar_arrive8_w(pend);
            T2P(i + 1, 5, 2 * e - 1);
          }
          pend = sbase + BAR_EMPTY + (NS + t) * 8;
          if ((ST_NOW >> e) & 1) {
            bulk_wait_read<0>();
            mbar_arrive8_w(pend);
            pend = 0;
            T2P(i + 1, 5, 2 * e + 1);
          }
        }
        T3(i, 0);
        if (piece >= 2) TTAIL(piece * 2 - 1);
        asm volatile("cp.async.bulk.wait_group 0;" ::: "memory");
        T3(i, 1);
        if (w.mode == 1) asm volatile(ELECT "st.release.gpu.global.u32 [%0], %1;\n}" ::"l"(&g_flag[w.range]), "r"(ep) : "memory");
        T3(i, 2);
        if (piece >= 2) TTAIL(piece * 2);
      }
      T3(15, 1);
    } else
    if (warp == 0) {
      Ring r{0, 1, 3};
      uint32_t d = cta;
      for (int i = 0;; i++) {
        const Work w = decode(d);
        if (w.kind == 2) break;
        const CUtensorMap* m = w.kind == 0 ? &P.wq[w.beta >> 4] : &P.wo[w.beta >> 4];
        for (int ks = 0; ks < w.nsteps; ks++) {
          const uint32_t b = borrow(ks, w.nsteps);
          r.next_if(b == 2);
          const uint32_t bar = sbase + BAR_FULL + r.slot * 8;
          mbar_wait_w(bar + (BAR_EMPTY - BAR_FULL), r.phase);
          if (w.kind == 0) tma_ld3_w(sbase + r.slot * SLOT, m, 0, ks * 64, w.sub * 2, bar, 16384);
          else tma_ld_wo_w(sbase + r.slot * SLOT, m, w.sub * 128, (w.k0 + ks) * 2, bar);
          if (ks < 10) T2P(i, 2, ks);
          if (w.kind != 0 && ks == max(w.nsteps - GO_P, 4)) mbar_arrive_warp(sbase + BAR_GO);
          r.next(); r.next_if(b == 2);
        }
        if (w.kind == 0) {
          r.phase ^= 1; r.next(); r.next();
        } else if (w.mode == 2) {
          for (int k = 1; k <= ((d >> 5) & 3); k++) {
            if (k == 1) TTAIL(9);
            wait_count(&g_flag[w.range + 5 * k], lds(sbase + EPOCH_OFF));
            TTAIL(10);
            asm volatile("fence.proxy.async.global;" ::: "memory");
#pragma unroll 1
            for (int t = 0; t < 4; t++) {
              mbar_wait_w(sbase + BAR_EMPTY + r.slot * 8, r.phase);
              tma_ld3_w(sbase + r.slot * SLOT, &P.o_st[t == 3], 0, t * 64, NBETA * 64 + (w.range + 5 * k) * 2, sbase + BAR_FULL + r.slot * 8,
                        t == 3 ? 8192 : 16384);
              r.next();
            }
          }
        }
        mbar_wait_w(sbase + BAR_DESC, i & 1);
        d = __shfl_sync(0xffffffffu, lds(sbase + DESC_OFF + ((i + 1) & 3) * 4), 0);
      }
    } else {
      const int hi = warp - 2;
      uint64_t pol_stream;
      asm volatile("createpolicy.fractional.L2::evict_first.b64 %0, 1.0;" : "=l"(pol_stream));
      Ring r{0, 1, 3};
      uint32_t d = cta;
      for (int i = 0;; i++) {
        const Work w = decode(d);
        if (w.kind == 2) break;
        const CUtensorMap* m = w.kind == 0 ? &P.x[hi][w.beta >> 4] : &P.o_ld[hi];
        int c1 = (w.kind == 0 ? (w.beta & 15) : w.beta * 64 + w.k0) * SQ + hi * 128;
        int k_late = -1;
        if (w.kind != 0) {
          if (!hi) T3(i, 3);
          if (d >= (3u << 30)) wait_count(&g_cnt[0][w.beta], lds(sbase + EPOCH_OFF) * H_LATE);
          if (d & 128) k_late = max(2 * H_LATE - w.k0, 0);
          if (!hi) T3(i, 4);
          asm volatile("fence.proxy.async.global;" ::: "memory");
          if (!hi) T3(i, 5);
        }
        for (int ks = 0; ks < w.nsteps; ks++) {
          if (ks == k_late) {
            if (!hi) T3(i, 6);
            wait_count(&g_cnt[1][d & 31], lds(sbase + EPOCH_OFF) * (NH - H_LATE));
            asm volatile("fence.proxy.async.global;" ::: "memory");
            if (!hi) T3(i, 7);
          }
          const uint32_t b = borrow(ks, w.nsteps);
          const bool bo = b != 2;
          r.next_if(hi && !bo); r.next_if(hi && !bo);
          const uint32_t sl = bo ? NS + (b ^ (3 * hi)) : r.slot, bar = sbase + BAR_FULL + sl * 8;
          mbar_wait_w(bar + (BAR_EMPTY - BAR_FULL), bo ? (r.xp >> b) & 1 : r.phase);
          if (w.kind == 0) tma_ld2_w(sbase + sl * SLOT, m, ks * 64, c1, bar, (hi ? 96 * 128 : 128 * 128) >> (DEV_HALF & 1));
          else if (O_LD_POL) { tma_ld2_hint_w(sbase + sl * SLOT, m, 0, c1, bar, (hi ? 96 * 128 : 128 * 128) >> (DEV_HALF >> 1), pol_stream); c1 += SQ; }
          else { tma_ld2_w(sbase + sl * SLOT, m, 0, c1, bar, hi ? 96 * 128 : 128 * 128); c1 += SQ; }
          if (PF_UNITS && w.kind == 0 && i < PF_UNITS && (((i ? PF_MASK : PF_MASK0) >> ks) & 1))
            asm volatile(ELECT "cp.async.bulk.prefetch.tensor.3d.L2.global.L2::cache_hint [%0, {0, %1, 0}], %2;\n}"
                         ::"l"(&P.kv[hi][w.beta >> 4]), "r"((d & 511) * SK + 64 * (PF_J0 + __popc((i ? PF_MASK : PF_MASK0) & ((1 << ks) - 1)))), "l"(pol_stream) : "memory");
          if (ks < 10) T2P(i, 3 + hi, ks);
          if (!hi && w.kind != 0 && !(ks & 3)) TCLK(i * 16 + (ks >> 2));
          r.next(); r.next_if(!hi && !bo); r.next_if(!hi && !bo);
          r.xp ^= 1 << b;
        }
        r.xp ^= 3;
        if (w.kind == 0) {
          m = &P.kv[hi][w.beta >> 4];
          c1 = (d & 511) * SK;
          for (int j = 0; j < 16; j++) {
            if (hi) r.next();
            const uint32_t bar = sbase + BAR_FULL + r.slot * 8;
            const bool tight = i < KV_WIN_UNITS && j < KV_WIN_TILES + ((KV_WIN_RAMP * ((int)d - KV_WIN_N * i)) >> 5);
            if (tight || (KV_WIN_D && j < KV_WIN_T2)) {
              const int s2 = (int)r.slot - (tight ? 2 : KV_WIN_D);
              mbar_wait_w(sbase + BAR_FULL + (s2 < 0 ? s2 + NS : s2) * 8, s2 < 0 ? r.phase : r.phase ^ 1);
            }
            if (j == 15 && hi) mbar_wait_w(sbase + BAR_DESC, i & 1);
            mbar_wait_w(sbase + BAR_EMPTY + r.slot * 8, r.phase);
            tma_ld3_hint_w(sbase + r.slot * SLOT, m, 0, c1, 0, bar, pol_stream);
            T2P(i, 3 + hi, 16 + j);
            if (!hi) TCLK(i * 16 + j);
            if (j == 14 && !hi) mbar_arrive_warp(sbase + BAR_GO);
            if (PF_X && j == PF_XJ && (d & 31) < 10 && d + PF_X * 32 < 1024)
              asm volatile(ELECT "cp.async.bulk.prefetch.tensor.2d.L2.global [%0, {%1, %2}];\n}"
                           ::"l"(&P.x[hi][(d + PF_X * 32) >> 9]), "r"((d & 31) * 64), "r"((((d >> 5) + PF_X) & 15) * SQ + hi * 128) : "memory");
            if (PF_W && j < 5 && (d >> 5) == PF_W)
              asm volatile(ELECT "cp.async.bulk.prefetch.tensor.3d.L2.global [%0, {0, %1, %2}];\n}"
                           ::"l"(&P.wq[1]), "r"((j * 2 + hi) * 64), "r"((d & 31) * 2) : "memory");
            c1 += 64;
            r.next();
            if (!hi) r.next();
          }
        }
        mbar_wait_w(sbase + BAR_DESC, i & 1);
        d = __shfl_sync(0xffffffffu, lds(sbase + DESC_OFF + ((i + 1) & 3) * 4), 0);
      }
    }
  } else {
    asm volatile("setmaxnreg.inc.sync.aligned.u32 %0;" ::"n"(REG_C));
    Ctx c;
    c.sb = sbase; c.wg = wg; c.warp = warp; c.src = 0; c.mqk = 0; c.mpv = 0; c.lead = lane == 0;
    if (wg == 0) consumer<0>(c, P.kp); else consumer<1>(c, P.kp);
  }
}

typedef CUresult (*EncodeFn)(CUtensorMap*, CUtensorMapDataType, cuuint32_t, void*, const cuuint64_t*, const cuuint64_t*,
                             const cuuint32_t*, const cuuint32_t*, CUtensorMapInterleave, CUtensorMapSwizzle,
                             CUtensorMapL2promotion, CUtensorMapFloatOOBfill);

void make_map(EncodeFn enc, CUtensorMap* m, const void* ptr, int rank, const cuuint64_t* dims, const cuuint64_t* strides,
              const cuuint32_t* box, int promo = 2, CUtensorMapSwizzle swz = CU_TENSOR_MAP_SWIZZLE_128B) {
  cuuint32_t es[5] = {1, 1, 1, 1, 1};
  enc(m, CU_TENSOR_MAP_DATA_TYPE_BFLOAT16, rank, const_cast<void*>(ptr), dims, strides, box, es,
      CU_TENSOR_MAP_INTERLEAVE_NONE, swz, promo == 2 ? CU_TENSOR_MAP_L2_PROMOTION_L2_256B : promo == 1 ? CU_TENSOR_MAP_L2_PROMOTION_L2_128B : CU_TENSOR_MAP_L2_PROMOTION_NONE,
      CU_TENSOR_MAP_FLOAT_OOB_FILL_NONE);
}

}

extern "C" void kernel_launch(void* const* d_in, const int* in_sizes, int n_in, void* d_out, int out_size) {
  (void)in_sizes; (void)n_in; (void)out_size;
  static EncodeFn enc = nullptr;
  static void* o_ptr = nullptr;
  static int n_sm = 0;
  if (!enc) {
    void* fn = nullptr;
    cudaDriverEntryPointQueryResult qr;
    cudaGetDriverEntryPoint("cuTensorMapEncodeTiled", &fn, cudaEnableDefault, &qr);
    enc = (EncodeFn)fn;
    cudaGetSymbolAddress(&o_ptr, g_o);
    cudaFuncSetAttribute(mha_fused_kernel<false>, cudaFuncAttributeMaxDynamicSharedMemorySize, SMEM_BYTES);
    cudaFuncSetAttribute(mha_fused_kernel<true>, cudaFuncAttributeMaxDynamicSharedMemorySize, SMEM_BYTES);
    int dev = 0;
    cudaGetDevice(&dev);
    cudaDeviceGetAttribute(&n_sm, cudaDevAttrMultiProcessorCount, dev);
  }
  Params P;
  for (int br = 0; br < 2; br++) {
    const void* x = d_in[br * 5 + 0]; const void* kc = d_in[br * 5 + 1]; const void* vc = d_in[br * 5 + 2];
    const void* wq = d_in[br * 5 + 3]; const void* wo = d_in[br * 5 + 4];
    { cuuint64_t d[2] = {DM, (cuuint64_t)NB * SQ}, s[1] = {DM * 2}; cuuint32_t b[2] = {64, 128 >> (DEV_HALF & 1)}, b2[2] = {64, 96 >> (DEV_HALF & 1)};
      make_map(enc, &P.x[0][br], x, 2, d, s, b, PR_X); make_map(enc, &P.x[1][br], x, 2, d, s, b2, PR_X); }
    { cuuint64_t d[3] = {64, DM, HD / 64}, s[2] = {HD * 2, 128}; cuuint32_t b[3] = {64, 64, 2}; make_map(enc, &P.wq[br], wq, 3, d, s, b, PR_W); }
    { cuuint64_t d[5] = {DM, 2, 4, 4, HD / 32}, s[4] = {DM * 2, 8 * DM * 2, 2 * DM * 2, 32 * DM * 2}; cuuint32_t b[5] = {64, 2, 4, 4, 2};
      make_map(enc, &P.wo[br], wo, 5, d, s, b, PR_W); }
    { cuuint64_t d[3] = {64, (cuuint64_t)NB * NH * SK, 2}, s[2] = {DH * 2, 128}; cuuint32_t b[3] = {64, 64, 2};
      make_map(enc, &P.kv[0][br], kc, 3, d, s, b, PR_KV); make_map(enc, &P.kv[1][br], vc, 3, d, s, b, PR_KV); }
    P.kp[br] = (const __nv_bfloat16*)kc; P.vp[br] = (const __nv_bfloat16*)vc;

  }
  { cuuint64_t d[2] = {64, (cuuint64_t)NBETA * 64 * SQ}, s[1] = {128}; cuuint32_t b[2] = {64, 128 >> (DEV_HALF >> 1)}, b2[2] = {64, 96 >> (DEV_HALF >> 1)};
    make_map(enc, &P.o_ld[0], o_ptr, 2, d, s, b, 2, CU_TENSOR_MAP_SWIZZLE_NONE); make_map(enc, &P.o_ld[1], o_ptr, 2, d, s, b2, 2, CU_TENSOR_MAP_SWIZZLE_NONE); }
  { cuuint64_t d[3] = {64, SQ, O_BLOCKS}, s[2] = {128, SQ * 128}; cuuint32_t b[3] = {64, 64, 2}, b2[3] = {64, 32, 2};
    make_map(enc, &P.o_st[0], o_ptr, 3, d, s, b); make_map(enc, &P.o_st[1], o_ptr, 3, d, s, b2); }
  { cuuint64_t d[3] = {64, (cuuint64_t)NB * SQ, 2 * DM / 64}, s[2] = {2 * DM * 2, 128}; cuuint32_t b[3] = {64, 64, 2}, b2[3] = {64, 32, 2};
    make_map(enc, &P.out_st[0], d_out, 3, d, s, b); make_map(enc, &P.out_st[1], d_out, 3, d, s, b2); }
  if (n_sm >= NCTA) mha_fused_kernel<false><<<NCTA, 384, SMEM_BYTES>>>(P);
  else mha_fused_kernel<true><<<n_sm, 384, SMEM_BYTES>>>(P);
}
```

```cpp
#include <cuda_runtime.h>
#include <cuda_bf16.h>
#include <cuda.h>
#include <stdint.h>
#include <stdlib.h>

namespace {

__device__ __forceinline__ void wgmma_proj(float (&d)[64], uint64_t da, uint64_t db, int scaleD) {
  asm volatile("{\n.reg .pred p;\nsetp.ne.b32 p, %66, 0;\n"
      "wgmma.mma_async.sync.aligned.m64n128k16.f32.bf16.bf16 "
      "{%0, %1, %2, %3, %4, %5, %6, %7, %8, %9, %10, %11, %12, %13, %14, %15, %16, %17, %18, %19, %20, %21, %22, %23, %24, %25, %26, %27, %28, %29, %30, "
      "%31, %32, %33, %34, %35, %36, %37, %38, %39, %40, %41, %42, %43, %44, %45, %46, %47, %48, %49, %50, %51, %52, %53, %54, %55, %56, %57, %58, %59, %60, "
      "%61, %62, %63}, "
      "%64, %65, p, 1, 1, 0, 1;\n}\n"
      : "+f"(d[0]), "+f"(d[1]), "+f"(d[2]), "+f"(d[3]), "+f"(d[4]), "+f"(d[5]), "+f"(d[6]), "+f"(d[7]), "+f"(d[8]), "+f"(d[9]), "+f"(d[10]), "+f"(d[11]),
        "+f"(d[12]), "+f"(d[13]), "+f"(d[14]), "+f"(d[15]), "+f"(d[16]), "+f"(d[17]), "+f"(d[18]), "+f"(d[19]), "+f"(d[20]), "+f"(d[21]), "+f"(d[22]),
        "+f"(d[23]), "+f"(d[24]), "+f"(d[25]), "+f"(d[26]), "+f"(d[27]), "+f"(d[28]), "+f"(d[29]), "+f"(d[30]), "+f"(d[31]), "+f"(d[32]), "+f"(d[33]),
        "+f"(d[34]), "+f"(d[35]), "+f"(d[36]), "+f"(d[37]), "+f"(d[38]), "+f"(d[39]), "+f"(d[40]), "+f"(d[41]), "+f"(d[42]), "+f"(d[43]), "+f"(d[44]),
        "+f"(d[45]), "+f"(d[46]), "+f"(d[47]), "+f"(d[48]), "+f"(d[49]), "+f"(d[50]), "+f"(d[51]), "+f"(d[52]), "+f"(d[53]), "+f"(d[54]), "+f"(d[55]),
        "+f"(d[56]), "+f"(d[57]), "+f"(d[58]), "+f"(d[59]), "+f"(d[60]), "+f"(d[61]), "+f"(d[62]), "+f"(d[63])
      : "l"(da), "l"(db), "r"(scaleD));
}
__device__ __forceinline__ void wgmma_proj96(float (&d)[64], uint64_t da, uint64_t db, int scaleD) {
  asm volatile("{\n.reg .pred p;\nsetp.ne.b32 p, %50, 0;\n"
      "wgmma.mma_async.sync.aligned.m64n96k16.f32.bf16.bf16 "
      "{%0, %1, %2, %3, %4, %5, %6, %7, %8, %9, %10, %11, %12, %13, %14, %15, %16, %17, %18, %19, %20, %21, %22, %23, %24, %25, %26, %27, %28, %29, %30, "
      "%31, %32, %33, %34, %35, %36, %37, %38, %39, %40, %41, %42, %43, %44, %45, %46, %47}, "
      "%48, %49, p, 1, 1, 1, 0;\n}\n"
      : "+f"(d[0]), "+f"(d[1]), "+f"(d[2]), "+f"(d[3]), "+f"(d[4]), "+f"(d[5]), "+f"(d[6]), "+f"(d[7]), "+f"(d[8]), "+f"(d[9]), "+f"(d[10]), "+f"(d[11]),
        "+f"(d[12]), "+f"(d[13]), "+f"(d[14]), "+f"(d[15]), "+f"(d[16]), "+f"(d[17]), "+f"(d[18]), "+f"(d[19]), "+f"(d[20]), "+f"(d[21]), "+f"(d[22]),
        "+f"(d[23]), "+f"(d[24]), "+f"(d[25]), "+f"(d[26]), "+f"(d[27]), "+f"(d[28]), "+f"(d[29]), "+f"(d[30]), "+f"(d[31]), "+f"(d[32]), "+f"(d[33]),
        "+f"(d[34]), "+f"(d[35]), "+f"(d[36]), "+f"(d[37]), "+f"(d[38]), "+f"(d[39]), "+f"(d[40]), "+f"(d[41]), "+f"(d[42]), "+f"(d[43]), "+f"(d[44]),
        "+f"(d[45]), "+f"(d[46]), "+f"(d[47])
      : "l"(da), "l"(db), "r"(scaleD));
}
__device__ __forceinline__ void wgmma_qk(float (&d)[32], uint64_t da, uint64_t db, int scaleD) {
  asm volatile("{\n.reg .pred p;\nsetp.ne.b32 p, %34, 0;\n"
      "wgmma.mma_async.sync.aligned.m64n64k16.f32.bf16.bf16 "
      "{%0, %1, %2, %3, %4, %5, %6, %7, %8, %9, %10, %11, %12, %13, %14, %15, %16, %17, %18, %19, %20, %21, %22, %23, %24, %25, %26, %27, %28, %29, %30, "
      "%31}, "
      "%32, %33, p, 1, 1, 0, 0;\n}\n"
      : "+f"(d[0]), "+f"(d[1]), "+f"(d[2]), "+f"(d[3]), "+f"(d[4]), "+f"(d[5]), "+f"(d[6]), "+f"(d[7]), "+f"(d[8]), "+f"(d[9]), "+f"(d[10]), "+f"(d[11]),
        "+f"(d[12]), "+f"(d[13]), "+f"(d[14]), "+f"(d[15]), "+f"(d[16]), "+f"(d[17]), "+f"(d[18]), "+f"(d[19]), "+f"(d[20]), "+f"(d[21]), "+f"(d[22]),
        "+f"(d[23]), "+f"(d[24]), "+f"(d[25]), "+f"(d[26]), "+f"(d[27]), "+f"(d[28]), "+f"(d[29]), "+f"(d[30]), "+f"(d[31])
      : "l"(da), "l"(db), "r"(scaleD));
}
__device__ __forceinline__ void wgmma_qk_rs(float (&d)[32], uint32_t a0, uint32_t a1, uint32_t a2, uint32_t a3, uint64_t db, int scaleD) {
  asm volatile("{\n.reg .pred p;\nsetp.ne.b32 p, %37, 0;\n"
      "wgmma.mma_async.sync.aligned.m64n64k16.f32.bf16.bf16 "
      "{%0, %1, %2, %3, %4, %5, %6, %7, %8, %9, %10, %11, %12, %13, %14, %15, %16, %17, %18, %19, %20, %21, %22, %23, %24, %25, %26, %27, %28, %29, %30, "
      "%31}, "
      "{%32, %33, %34, %35}, %36, p, 1, 1, 0;\n}\n"
      : "+f"(d[0]), "+f"(d[1]), "+f"(d[2]), "+f"(d[3]), "+f"(d[4]), "+f"(d[5]), "+f"(d[6]), "+f"(d[7]), "+f"(d[8]), "+f"(d[9]), "+f"(d[10]), "+f"(d[11]),
        "+f"(d[12]), "+f"(d[13]), "+f"(d[14]), "+f"(d[15]), "+f"(d[16]), "+f"(d[17]), "+f"(d[18]), "+f"(d[19]), "+f"(d[20]), "+f"(d[21]), "+f"(d[22]),
        "+f"(d[23]), "+f"(d[24]), "+f"(d[25]), "+f"(d[26]), "+f"(d[27]), "+f"(d[28]), "+f"(d[29]), "+f"(d[30]), "+f"(d[31])
      : "r"(a0), "r"(a1), "r"(a2), "r"(a3), "l"(db), "r"(scaleD));
}
__device__ __forceinline__ void wgmma_pv(float (&d)[64], uint32_t a0, uint32_t a1, uint32_t a2, uint32_t a3, uint64_t db, int scaleD) {
  asm volatile("{\n.reg .pred p;\nsetp.ne.b32 p, %69, 0;\n"
      "wgmma.mma_async.sync.aligned.m64n128k16.f32.bf16.bf16 "
      "{%0, %1, %2, %3, %4, %5, %6, %7, %8, %9, %10, %11, %12, %13, %14, %15, %16, %17, %18, %19, %20, %21, %22, %23, %24, %25, %26, %27, %28, %29, %30, "
      "%31, %32, %33, %34, %35, %36, %37, %38, %39, %40, %41, %42, %43, %44, %45, %46, %47, %48, %49, %50, %51, %52, %53, %54, %55, %56, %57, %58, %59, %60, "
      "%61, %62, %63}, "
      "{%64, %65, %66, %67}, %68, p, 1, 1, 1;\n}\n"
      : "+f"(d[0]), "+f"(d[1]), "+f"(d[2]), "+f"(d[3]), "+f"(d[4]), "+f"(d[5]), "+f"(d[6]), "+f"(d[7]), "+f"(d[8]), "+f"(d[9]), "+f"(d[10]), "+f"(d[11]),
        "+f"(d[12]), "+f"(d[13]), "+f"(d[14]), "+f"(d[15]), "+f"(d[16]), "+f"(d[17]), "+f"(d[18]), "+f"(d[19]), "+f"(d[20]), "+f"(d[21]), "+f"(d[22]),
        "+f"(d[23]), "+f"(d[24]), "+f"(d[25]), "+f"(d[26]), "+f"(d[27]), "+f"(d[28]), "+f"(d[29]), "+f"(d[30]), "+f"(d[31]), "+f"(d[32]), "+f"(d[33]),
        "+f"(d[34]), "+f"(d[35]), "+f"(d[36]), "+f"(d[37]), "+f"(d[38]), "+f"(d[39]), "+f"(d[40]), "+f"(d[41]), "+f"(d[42]), "+f"(d[43]), "+f"(d[44]),
        "+f"(d[45]), "+f"(d[46]), "+f"(d[47]), "+f"(d[48]), "+f"(d[49]), "+f"(d[50]), "+f"(d[51]), "+f"(d[52]), "+f"(d[53]), "+f"(d[54]), "+f"(d[55]),
        "+f"(d[56]), "+f"(d[57]), "+f"(d[58]), "+f"(d[59]), "+f"(d[60]), "+f"(d[61]), "+f"(d[62]), "+f"(d[63])
      : "r"(a0), "r"(a1), "r"(a2), "r"(a3), "l"(db), "r"(scaleD));
}
__device__ __forceinline__ void wgmma_qk_sp(float (&d)[32], uint32_t a0, uint32_t a1, uint32_t a2, uint32_t a3, uint64_t db, int scaleD, uint32_t meta) {
  asm volatile("{\n.reg .pred p;\nsetp.ne.b32 p, %37, 0;\n"
      "wgmma.mma_async.sp.sync.aligned.m64n64k32.f32.bf16.bf16 "
      "{%0, %1, %2, %3, %4, %5, %6, %7, %8, %9, %10, %11, %12, %13, %14, %15, %16, %17, %18, %19, %20, %21, %22, %23, %24, %25, %26, %27, %28, %29, %30, "
      "%31}, "
      "{%32, %33, %34, %35}, %36, %38, 0, p, 1, 1, 0;\n}\n"
      : "+f"(d[0]), "+f"(d[1]), "+f"(d[2]), "+f"(d[3]), "+f"(d[4]), "+f"(d[5]), "+f"(d[6]), "+f"(d[7]), "+f"(d[8]), "+f"(d[9]), "+f"(d[10]), "+f"(d[11]),
        "+f"(d[12]), "+f"(d[13]), "+f"(d[14]), "+f"(d[15]), "+f"(d[16]), "+f"(d[17]), "+f"(d[18]), "+f"(d[19]), "+f"(d[20]), "+f"(d[21]), "+f"(d[22]),
        "+f"(d[23]), "+f"(d[24]), "+f"(d[25]), "+f"(d[26]), "+f"(d[27]), "+f"(d[28]), "+f"(d[29]), "+f"(d[30]), "+f"(d[31])
      : "r"(a0), "r"(a1), "r"(a2), "r"(a3), "l"(db), "r"(scaleD), "r"(meta));
}
__device__ __forceinline__ void wgmma_pv_sp(float (&d)[64], uint32_t a0, uint32_t a1, uint32_t a2, uint32_t a3, uint64_t db, int scaleD, uint32_t meta) {
  asm volatile("{\n.reg .pred p;\nsetp.ne.b32 p, %69, 0;\n"
      "wgmma.mma_async.sp.sync.aligned.m64n128k32.f32.bf16.bf16 "
      "{%0, %1, %2, %3, %4, %5, %6, %7, %8, %9, %10, %11, %12, %13, %14, %15, %16, %17, %18, %19, %20, %21, %22, %23, %24, %25, %26, %27, %28, %29, %30, "
      "%31, %32, %33, %34, %35, %36, %37, %38, %39, %40, %41, %42, %43, %44, %45, %46, %47, %48, %49, %50, %51, %52, %53, %54, %55, %56, %57, %58, %59, %60, "
      "%61, %62, %63}, "
      "{%64, %65, %66, %67}, %68, %70, 0, p, 1, 1, 1;\n}\n"
      : "+f"(d[0]), "+f"(d[1]), "+f"(d[2]), "+f"(d[3]), "+f"(d[4]), "+f"(d[5]), "+f"(d[6]), "+f"(d[7]), "+f"(d[8]), "+f"(d[9]), "+f"(d[10]), "+f"(d[11]),
        "+f"(d[12]), "+f"(d[13]), "+f"(d[14]), "+f"(d[15]), "+f"(d[16]), "+f"(d[17]), "+f"(d[18]), "+f"(d[19]), "+f"(d[20]), "+f"(d[21]), "+f"(d[22]),
        "+f"(d[23]), "+f"(d[24]), "+f"(d[25]), "+f"(d[26]), "+f"(d[27]), "+f"(d[28]), "+f"(d[29]), "+f"(d[30]), "+f"(d[31]), "+f"(d[32]), "+f"(d[33]),
        "+f"(d[34]), "+f"(d[35]), "+f"(d[36]), "+f"(d[37]), "+f"(d[38]), "+f"(d[39]), "+f"(d[40]), "+f"(d[41]), "+f"(d[42]), "+f"(d[43]), "+f"(d[44]),
        "+f"(d[45]), "+f"(d[46]), "+f"(d[47]), "+f"(d[48]), "+f"(d[49]), "+f"(d[50]), "+f"(d[51]), "+f"(d[52]), "+f"(d[53]), "+f"(d[54]), "+f"(d[55]),
        "+f"(d[56]), "+f"(d[57]), "+f"(d[58]), "+f"(d[59]), "+f"(d[60]), "+f"(d[61]), "+f"(d[62]), "+f"(d[63])
      : "r"(a0), "r"(a1), "r"(a2), "r"(a3), "l"(db), "r"(scaleD), "r"(meta));
}
__device__ __forceinline__ void wgmma_proj_init(float (&d)[64], uint64_t da, uint64_t db, int scaleD) {
  asm volatile("{\n.reg .pred p;\nsetp.ne.b32 p, %66, 0;\n"
      "wgmma.mma_async.sync.aligned.m64n128k16.f32.bf16.bf16 "
      "{%0, %1, %2, %3, %4, %5, %6, %7, %8, %9, %10, %11, %12, %13, %14, %15, %16, %17, %18, %19, %20, %21, %22, %23, %24, %25, %26, %27, %28, %29, %30, "
      "%31, %32, %33, %34, %35, %36, %37, %38, %39, %40, %41, %42, %43, %44, %45, %46, %47, %48, %49, %50, %51, %52, %53, %54, %55, %56, %57, %58, %59, %60, "
      "%61, %62, %63}, "
      "%64, %65, p, 1, 1, 0, 1;\n}\n"
      : "=f"(d[0]), "=f"(d[1]), "=f"(d[2]), "=f"(d[3]), "=f"(d[4]), "=f"(d[5]), "=f"(d[6]), "=f"(d[7]), "=f"(d[8]), "=f"(d[9]), "=f"(d[10]), "=f"(d[11]),
        "=f"(d[12]), "=f"(d[13]), "=f"(d[14]), "=f"(d[15]), "=f"(d[16]), "=f"(d[17]), "=f"(d[18]), "=f"(d[19]), "=f"(d[20]), "=f"(d[21]), "=f"(d[22]),
        "=f"(d[23]), "=f"(d[24]), "=f"(d[25]), "=f"(d[26]), "=f"(d[27]), "=f"(d[28]), "=f"(d[29]), "=f"(d[30]), "=f"(d[31]), "=f"(d[32]), "=f"(d[33]),
        "=f"(d[34]), "=f"(d[35]), "=f"(d[36]), "=f"(d[37]), "=f"(d[38]), "=f"(d[39]), "=f"(d[40]), "=f"(d[41]), "=f"(d[42]), "=f"(d[43]), "=f"(d[44]),
        "=f"(d[45]), "=f"(d[46]), "=f"(d[47]), "=f"(d[48]), "=f"(d[49]), "=f"(d[50]), "=f"(d[51]), "=f"(d[52]), "=f"(d[53]), "=f"(d[54]), "=f"(d[55]),
        "=f"(d[56]), "=f"(d[57]), "=f"(d[58]), "=f"(d[59]), "=f"(d[60]), "=f"(d[61]), "=f"(d[62]), "=f"(d[63])
      : "l"(da), "l"(db), "r"(scaleD));
}
__device__ __forceinline__ void wgmma_proj96_init(float (&d)[64], uint64_t da, uint64_t db, int scaleD) {
  asm volatile("{\n.reg .pred p;\nsetp.ne.b32 p, %50, 0;\n"
      "wgmma.mma_async.sync.aligned.m64n96k16.f32.bf16.bf16 "
      "{%0, %1, %2, %3, %4, %5, %6, %7, %8, %9, %10, %11, %12, %13, %14, %15, %16, %17, %18, %19, %20, %21, %22, %23, %24, %25, %26, %27, %28, %29, %30, "
      "%31, %32, %33, %34, %35, %36, %37, %38, %39, %40, %41, %42, %43, %44, %45, %46, %47}, "
      "%48, %49, p, 1, 1, 1, 0;\n}\n"
      : "=f"(d[0]), "=f"(d[1]), "=f"(d[2]), "=f"(d[3]), "=f"(d[4]), "=f"(d[5]), "=f"(d[6]), "=f"(d[7]), "=f"(d[8]), "=f"(d[9]), "=f"(d[10]), "=f"(d[11]),
        "=f"(d[12]), "=f"(d[13]), "=f"(d[14]), "=f"(d[15]), "=f"(d[16]), "=f"(d[17]), "=f"(d[18]), "=f"(d[19]), "=f"(d[20]), "=f"(d[21]), "=f"(d[22]),
        "=f"(d[23]), "=f"(d[24]), "=f"(d[25]), "=f"(d[26]), "=f"(d[27]), "=f"(d[28]), "=f"(d[29]), "=f"(d[30]), "=f"(d[31]), "=f"(d[32]), "=f"(d[33]),
        "=f"(d[34]), "=f"(d[35]), "=f"(d[36]), "=f"(d[37]), "=f"(d[38]), "=f"(d[39]), "=f"(d[40]), "=f"(d[41]), "=f"(d[42]), "=f"(d[43]), "=f"(d[44]),
        "=f"(d[45]), "=f"(d[46]), "=f"(d[47])
      : "l"(da), "l"(db), "r"(scaleD));
}
__device__ __forceinline__ void wgmma_qk_init(float (&d)[32], uint64_t da, uint64_t db, int scaleD) {
  asm volatile("{\n.reg .pred p;\nsetp.ne.b32 p, %34, 0;\n"
      "wgmma.mma_async.sync.aligned.m64n64k16.f32.bf16.bf16 "
      "{%0, %1, %2, %3, %4, %5, %6, %7, %8, %9, %10, %11, %12, %13, %14, %15, %16, %17, %18, %19, %20, %21, %22, %23, %24, %25, %26, %27, %28, %29, %30, "
      "%31}, "
      "%32, %33, p, 1, 1, 0, 0;\n}\n"
      : "=f"(d[0]), "=f"(d[1]), "=f"(d[2]), "=f"(d[3]), "=f"(d[4]), "=f"(d[5]), "=f"(d[6]), "=f"(d[7]), "=f"(d[8]), "=f"(d[9]), "=f"(d[10]), "=f"(d[11]),
        "=f"(d[12]), "=f"(d[13]), "=f"(d[14]), "=f"(d[15]), "=f"(d[16]), "=f"(d[17]), "=f"(d[18]), "=f"(d[19]), "=f"(d[20]), "=f"(d[21]), "=f"(d[22]),
        "=f"(d[23]), "=f"(d[24]), "=f"(d[25]), "=f"(d[26]), "=f"(d[27]), "=f"(d[28]), "=f"(d[29]), "=f"(d[30]), "=f"(d[31])
      : "l"(da), "l"(db), "r"(scaleD));
}
__device__ __forceinline__ void wgmma_qk_rs_init(float (&d)[32], uint32_t a0, uint32_t a1, uint32_t a2, uint32_t a3, uint64_t db, int scaleD) {
  asm volatile("{\n.reg .pred p;\nsetp.ne.b32 p, %37, 0;\n"
      "wgmma.mma_async.sync.aligned.m64n64k16.f32.bf16.bf16 "
      "{%0, %1, %2, %3, %4, %5, %6, %7, %8, %9, %10, %11, %12, %13, %14, %15, %16, %17, %18, %19, %20, %21, %22, %23, %24, %25, %26, %27, %28, %29, %30, "
      "%31}, "
      "{%32, %33, %34, %35}, %36, p, 1, 1, 0;\n}\n"
      : "=f"(d[0]), "=f"(d[1]), "=f"(d[2]), "=f"(d[3]), "=f"(d[4]), "=f"(d[5]), "=f"(d[6]), "=f"(d[7]), "=f"(d[8]), "=f"(d[9]), "=f"(d[10]), "=f"(d[11]),
        "=f"(d[12]), "=f"(d[13]), "=f"(d[14]), "=f"(d[15]), "=f"(d[16]), "=f"(d[17]), "=f"(d[18]), "=f"(d[19]), "=f"(d[20]), "=f"(d[21]), "=f"(d[22]),
        "=f"(d[23]), "=f"(d[24]), "=f"(d[25]), "=f"(d[26]), "=f"(d[27]), "=f"(d[28]), "=f"(d[29]), "=f"(d[30]), "=f"(d[31])
      : "r"(a0), "r"(a1), "r"(a2), "r"(a3), "l"(db), "r"(scaleD));
}
__device__ __forceinline__ void wgmma_pv_init(float (&d)[64], uint32_t a0, uint32_t a1, uint32_t a2, uint32_t a3, uint64_t db, int scaleD) {
  asm volatile("{\n.reg .pred p;\nsetp.ne.b32 p, %69, 0;\n"
      "wgmma.mma_async.sync.aligned.m64n128k16.f32.bf16.bf16 "
      "{%0, %1, %2, %3, %4, %5, %6, %7, %8, %9, %10, %11, %12, %13, %14, %15, %16, %17, %18, %19, %20, %21, %22, %23, %24, %25, %26, %27, %28, %29, %30, "
      "%31, %32, %33, %34, %35, %36, %37, %38, %39, %40, %41, %42, %43, %44, %45, %46, %47, %48, %49, %50, %51, %52, %53, %54, %55, %56, %57, %58, %59, %60, "
      "%61, %62, %63}, "
      "{%64, %65, %66, %67}, %68, p, 1, 1, 1;\n}\n"
      : "=f"(d[0]), "=f"(d[1]), "=f"(d[2]), "=f"(d[3]), "=f"(d[4]), "=f"(d[5]), "=f"(d[6]), "=f"(d[7]), "=f"(d[8]), "=f"(d[9]), "=f"(d[10]), "=f"(d[11]),
        "=f"(d[12]), "=f"(d[13]), "=f"(d[14]), "=f"(d[15]), "=f"(d[16]), "=f"(d[17]), "=f"(d[18]), "=f"(d[19]), "=f"(d[20]), "=f"(d[21]), "=f"(d[22]),
        "=f"(d[23]), "=f"(d[24]), "=f"(d[25]), "=f"(d[26]), "=f"(d[27]), "=f"(d[28]), "=f"(d[29]), "=f"(d[30]), "=f"(d[31]), "=f"(d[32]), "=f"(d[33]),
        "=f"(d[34]), "=f"(d[35]), "=f"(d[36]), "=f"(d[37]), "=f"(d[38]), "=f"(d[39]), "=f"(d[40]), "=f"(d[41]), "=f"(d[42]), "=f"(d[43]), "=f"(d[44]),
        "=f"(d[45]), "=f"(d[46]), "=f"(d[47]), "=f"(d[48]), "=f"(d[49]), "=f"(d[50]), "=f"(d[51]), "=f"(d[52]), "=f"(d[53]), "=f"(d[54]), "=f"(d[55]),
        "=f"(d[56]), "=f"(d[57]), "=f"(d[58]), "=f"(d[59]), "=f"(d[60]), "=f"(d[61]), "=f"(d[62]), "=f"(d[63])
      : "r"(a0), "r"(a1), "r"(a2), "r"(a3), "l"(db), "r"(scaleD));
}
__device__ __forceinline__ void wgmma_qk_sp_init(float (&d)[32], uint32_t a0, uint32_t a1, uint32_t a2, uint32_t a3, uint64_t db, int scaleD, uint32_t meta) {
  asm volatile("{\n.reg .pred p;\nsetp.ne.b32 p, %37, 0;\n"
      "wgmma.mma_async.sp.sync.aligned.m64n64k32.f32.bf16.bf16 "
      "{%0, %1, %2, %3, %4, %5, %6, %7, %8, %9, %10, %11, %12, %13, %14, %15, %16, %17, %18, %19, %20, %21, %22, %23, %24, %25, %26, %27, %28, %29, %30, "
      "%31}, "
      "{%32, %33, %34, %35}, %36, %38, 0, p, 1, 1, 0;\n}\n"
      : "=f"(d[0]), "=f"(d[1]), "=f"(d[2]), "=f"(d[3]), "=f"(d[4]), "=f"(d[5]), "=f"(d[6]), "=f"(d[7]), "=f"(d[8]), "=f"(d[9]), "=f"(d[10]), "=f"(d[11]),
        "=f"(d[12]), "=f"(d[13]), "=f"(d[14]), "=f"(d[15]), "=f"(d[16]), "=f"(d[17]), "=f"(d[18]), "=f"(d[19]), "=f"(d[20]), "=f"(d[21]), "=f"(d[22]),
        "=f"(d[23]), "=f"(d[24]), "=f"(d[25]), "=f"(d[26]), "=f"(d[27]), "=f"(d[28]), "=f"(d[29]), "=f"(d[30]), "=f"(d[31])
      : "r"(a0), "r"(a1), "r"(a2), "r"(a3), "l"(db), "r"(scaleD), "r"(meta));
}
__device__ __forceinline__ void wgmma_pv_sp_init(float (&d)[64], uint32_t a0, uint32_t a1, uint32_t a2, uint32_t a3, uint64_t db, int scaleD, uint32_t meta) {
  asm volatile("{\n.reg .pred p;\nsetp.ne.b32 p, %69, 0;\n"
      "wgmma.mma_async.sp.sync.aligned.m64n128k32.f32.bf16.bf16 "
      "{%0, %1, %2, %3, %4, %5, %6, %7, %8, %9, %10, %11, %12, %13, %14, %15, %16, %17, %18, %19, %20, %21, %22, %23, %24, %25, %26, %27, %28, %29, %30, "
      "%31, %32, %33, %34, %35, %36, %37, %38, %39, %40, %41, %42, %43, %44, %45, %46, %47, %48, %49, %50, %51, %52, %53, %54, %55, %56, %57, %58, %59, %60, "
      "%61, %62, %63}, "
      "{%64, %65, %66, %67}, %68, %70, 0, p, 1, 1, 1;\n}\n"
      : "=f"(d[0]), "=f"(d[1]), "=f"(d[2]), "=f"(d[3]), "=f"(d[4]), "=f"(d[5]), "=f"(d[6]), "=f"(d[7]), "=f"(d[8]), "=f"(d[9]), "=f"(d[10]), "=f"(d[11]),
        "=f"(d[12]), "=f"(d[13]), "=f"(d[14]), "=f"(d[15]), "=f"(d[16]), "=f"(d[17]), "=f"(d[18]), "=f"(d[19]), "=f"(d[20]), "=f"(d[21]), "=f"(d[22]),
        "=f"(d[23]), "=f"(d[24]), "=f"(d[25]), "=f"(d[26]), "=f"(d[27]), "=f"(d[28]), "=f"(d[29]), "=f"(d[30]), "=f"(d[31]), "=f"(d[32]), "=f"(d[33]),
        "=f"(d[34]), "=f"(d[35]), "=f"(d[36]), "=f"(d[37]), "=f"(d[38]), "=f"(d[39]), "=f"(d[40]), "=f"(d[41]), "=f"(d[42]), "=f"(d[43]), "=f"(d[44]),
        "=f"(d[45]), "=f"(d[46]), "=f"(d[47]), "=f"(d[48]), "=f"(d[49]), "=f"(d[50]), "=f"(d[51]), "=f"(d[52]), "=f"(d[53]), "=f"(d[54]), "=f"(d[55]),
        "=f"(d[56]), "=f"(d[57]), "=f"(d[58]), "=f"(d[59]), "=f"(d[60]), "=f"(d[61]), "=f"(d[62]), "=f"(d[63])
      : "r"(a0), "r"(a1), "r"(a2), "r"(a3), "l"(db), "r"(scaleD), "r"(meta));
}

constexpr int NB = 16, SQ = 224, DM = 640, NH = 32, SK = 1024, DH = 128;
constexpr int HD = NH * DH;
constexpr int NBETA = 2 * NB;
constexpr int NCTA = 132;
constexpr int NS = 10;
constexpr int SLOT = 16384;
constexpr int QBUF_OFF = NS * SLOT;
constexpr int NSX = NS + 4;
constexpr int BAR_OFF = NSX * SLOT;
constexpr int BAR_FULL = BAR_OFF;
constexpr int BAR_EMPTY = BAR_OFF + 8 * NSX;
constexpr int BAR_STG = BAR_OFF + 16 * NSX;
constexpr int BAR_OUT = BAR_STG + 32;
constexpr int BAR_DESC = BAR_OUT + 8;
constexpr int BAR_GO = BAR_DESC + 8;
constexpr int DESC_OFF = BAR_GO + 8;
constexpr int EPOCH_OFF = DESC_OFF + 16;
constexpr int TRACE_OFF = EPOCH_OFF + 8;
constexpr int SMEM_BYTES = TRACE_OFF;
constexpr float SM_C = 0.08838834764831845f * 1.4426950408889634f;
constexpr float SUM_HI = 1099511627776.f, SUM_LO = 1.f / 1099511627776.f;
constexpr uint32_t META_QK = 0xEEEE4444u;
constexpr uint32_t META_PV = 0x44EEEE44u;

#define QK_EARLY_MASK 3
#define ST_ORDER 0x2130
#define LAG_BAR 5
#define ST_NOW 9
#define PF_UNITS 0
#define PF_MASK 0x2a8
#define PF_MASK0 PF_MASK
#define PF_X 0
#define PF_XJ 2
#define PF_W 0
#define KV_WIN_UNITS 2
#define KV_WIN_D 4
#define KV_WIN_T2 16
#define O_LD_POL 1
#define LAST_SYNC 0
#define RED_FIRST 2
#define PEEK 0
#define PACK_LATE 1
#define RS_STAGE 3
#define O_STEPS 4
#define TLB_WARM 0
#define DEV_HALF 0
#define DEV_IDLE 0
#define KV_WIN_RAMP 4
#define KV_WIN_N 132
#define BORROW_ALT 0
#define PF_J0 0
#define PDEPTH 0
#define EARLY_BEG 1
#define KV_WIN_TILES -2
#define PR_KV 2
#define PR_X 2
#define PR_W 2
#define REG_C 232
#define REG_P 40
#define GO_P 4
#define P_POS 224
#define P_STRIDE 32
#define B_LATE 28
#define H_LATE 24
#define P_EARLY 13
#define PIECE_TABLE 0x5026401a,0x68dc4034,0x50275816,0x695a5837,0x50295015,0x6a175036,0x501e080d,0x681f083c,0x50253812,0x69d8383a,0x403f980e,0x80000000,0x5036180f,0x80000000,0x50203011,0x69993032,0x50367019,0x80000000,0x50224814,0x6a954835,0x50246017,0x6b526038,0x502c6818,0x6dc86839,0x5017b813,0x69d8b85f,0x50102810,0x685e2831,0x646e2030,0x80000000,0x501f101c,0x6dc8102f,0x5017801b,0x6c8d805e,0x6627783b,0x80000000,0x6627b033,0x80000000,0x501a901e,0x80000000,0x56d6881e,0x80000000,0x501ca81d,0x80000000,0x6762a03d,0x80000000,0x67e0002d,0x80000000,0x5512c01f,0x80000000,0x5013c81f,0x80000000

struct Params {
  CUtensorMap x[2][2], wq[2], kv[2][2], wo[2];
  CUtensorMap o_ld[2], o_st[2], out_st[2];
  const __nv_bfloat16* kp[2];
  const __nv_bfloat16* vp[2];
};

constexpr int NPART = 32 * 5, O_BLOCKS = NBETA * 64 + 2 * NPART;
__device__ __align__(128) __nv_bfloat16 g_o[(size_t)O_BLOCKS * SQ * 64];
__device__ unsigned g_cnt[2][NBETA];
__device__ unsigned g_epoch, g_next;
__device__ unsigned g_flag[NPART];

__device__ __forceinline__ uint32_t smem_u32(const void* p) { return (uint32_t)__cvta_generic_to_shared(p); }
__device__ __forceinline__ void mbar_arrive(uint32_t bar) {
  asm volatile("mbarrier.arrive.shared::cta.b64 _, [%0];" ::"r"(bar) : "memory");
}
__device__ __forceinline__ void mbar_arrive_warp(uint32_t bar) {
  asm volatile("{\n.reg .pred p;\nelect.sync _|p, 0xffffffff;\n@p mbarrier.arrive.shared::cta.b64 _, [%0];\n}" ::"r"(bar) : "memory");
}
__device__ __forceinline__ int lane_now() { int l; asm volatile("mov.u32 %0, %%laneid;" : "=r"(l)); return l; }
__device__ __forceinline__ bool mbar_try(uint32_t bar, uint32_t parity) {
  uint32_t ok;
  asm volatile("{\n.reg .pred p;\nmbarrier.try_wait.parity.shared::cta.b64 p, [%1], %2;\nselp.u32 %0, 1, 0, p;\n}"
               : "=r"(ok) : "r"(bar), "r"(parity) : "memory");
  return ok;
}
__device__ __forceinline__ bool mbar_test(uint32_t bar, uint32_t parity) {
  uint32_t ok;
  asm volatile("{\n.reg .pred p;\nmbarrier.test_wait.parity.shared::cta.b64 p, [%1], %2;\nselp.u32 %0, 1, 0, p;\n}"
               : "=r"(ok) : "r"(bar), "r"(parity) : "memory");
  return ok;
}
__device__ __forceinline__ void mbar_wait_w(uint32_t bar, uint32_t parity) {
  uint32_t n = 0;
  while (!__all_sync(0xffffffffu, mbar_try(bar, parity))) {
    if (++n > (1u << 22)) __trap();
  }
}
#define ELECT "{\n.reg .pred p;\nelect.sync _|p, 0xffffffff;\n@p "
__device__ __forceinline__ void tma_st3_hint_w(const CUtensorMap* m, uint32_t src, int c0, int c1, int c2, uint64_t pol) {
  asm volatile(ELECT "cp.async.bulk.tensor.3d.global.shared::cta.bulk_group.L2::cache_hint [%0, {%2, %3, %4}], [%1], %5;\n}"
               ::"l"(m), "r"(src), "r"(c0), "r"(c1), "r"(c2), "l"(pol) : "memory");
}
#define EXPECT(bar, bytes) "mbarrier.arrive.expect_tx.shared::cta.b64 _, [" bar "], " bytes ";\n@p "
__device__ __forceinline__ void tma_ld2_w(uint32_t dst, const CUtensorMap* m, int c0, int c1, uint32_t bar, uint32_t bytes) {
  asm volatile(ELECT EXPECT("%2", "%5") "cp.async.bulk.tensor.2d.shared::cluster.global.mbarrier::complete_tx::bytes [%0], [%1, {%3, %4}], [%2];\n}"
               ::"r"(dst), "l"(m), "r"(bar), "r"(c0), "r"(c1), "r"(bytes) : "memory");
}
__device__ __forceinline__ void tma_ld2_hint_w(uint32_t dst, const CUtensorMap* m, int c0, int c1, uint32_t bar, uint32_t bytes, uint64_t pol) {
  asm volatile(ELECT EXPECT("%2", "%6") "cp.async.bulk.tensor.2d.shared::cluster.global.mbarrier::complete_tx::bytes.L2::cache_hint"
               " [%0], [%1, {%3, %4}], [%2], %5;\n}"
               ::"r"(dst), "l"(m), "r"(bar), "r"(c0), "r"(c1), "l"(pol), "r"(bytes) : "memory");
}
__device__ __forceinline__ void tma_ld3_w(uint32_t dst, const CUtensorMap* m, int c0, int c1, int c2, uint32_t bar, uint32_t bytes) {
  asm volatile(ELECT EXPECT("%2", "%6") "cp.async.bulk.tensor.3d.shared::cluster.global.mbarrier::complete_tx::bytes [%0], [%1, {%3, %4, %5}], [%2];\n}"
               ::"r"(dst), "l"(m), "r"(bar), "r"(c0), "r"(c1), "r"(c2), "r"(bytes) : "memory");
}
__device__ __forceinline__ void tma_ld3_hint_w(uint32_t dst, const CUtensorMap* m, int c0, int c1, int c2, uint32_t bar, uint64_t pol) {
  asm volatile(ELECT EXPECT("%2", "16384") "cp.async.bulk.tensor.3d.shared::cluster.global.mbarrier::complete_tx::bytes.L2::cache_hint"
               " [%0], [%1, {%3, %4, %5}], [%2], %6;\n}"
               ::"r"(dst), "l"(m), "r"(bar), "r"(c0), "r"(c1), "r"(c2), "l"(pol) : "memory");
}
__device__ __forceinline__ void tma_ld_wo_w(uint32_t dst, const CUtensorMap* m, int col, int grp, uint32_t bar) {
  asm volatile(ELECT EXPECT("%2", "16384") "cp.async.bulk.tensor.5d.shared::cluster.global.mbarrier::complete_tx::bytes [%0], [%1, {%3, 0, 0, 0, %4}], [%2];\n"
               "@p cp.async.bulk.tensor.5d.shared::cluster.global.mbarrier::complete_tx::bytes [%5], [%1, {%6, 0, 0, 0, %4}], [%2];\n}"
               ::"r"(dst), "l"(m), "r"(bar), "r"(col), "r"(grp), "r"(dst + 8192), "r"(col + 64) : "memory");
}
__device__ __forceinline__ void mbar_arrive8_w(uint32_t bar) {
  asm volatile(ELECT "mbarrier.arrive.shared::cta.b64 _, [%0], 8;\n}" ::"r"(bar) : "memory");
}
__device__ __forceinline__ void bulk_commit() { asm volatile("cp.async.bulk.commit_group;" ::: "memory"); }
template <int N> __device__ __forceinline__ void bulk_wait_read() { asm volatile("cp.async.bulk.wait_group.read %0;" ::"n"(N) : "memory"); }
__device__ __forceinline__ void wg_fence() { asm volatile("wgmma.fence.sync.aligned;" ::: "memory"); }
__device__ __forceinline__ void wg_commit() { asm volatile("wgmma.commit_group.sync.aligned;" ::: "memory"); }
template <int N> __device__ __forceinline__ void wg_wait() { asm volatile("wgmma.wait_group.sync.aligned %0;" ::"n"(N) : "memory"); }
__device__ __forceinline__ void fence_async_smem() { asm volatile("fence.proxy.async.shared::cta;" ::: "memory"); }
__device__ __forceinline__ void bar_sync(int id, int n) { asm volatile("bar.sync %0, %1;" ::"r"(id), "r"(n) : "memory"); }
template <int N> __device__ __forceinline__ void reg_fence(float (&a)[N]) {
#pragma unroll
  for (int i = 0; i < N; i++) asm volatile("" : "+f"(a[i])::"memory");
}
template <int N> __device__ __forceinline__ void reg_fence(uint32_t (&a)[N]) {
#pragma unroll
  for (int i = 0; i < N; i++) asm volatile("" : "+r"(a[i])::"memory");
}
__device__ __forceinline__ float ex2(float x) { float y; asm("ex2.approx.ftz.f32 %0, %1;" : "=f"(y) : "f"(x)); return y; }
__device__ __forceinline__ uint32_t pack_bf16(float lo, float hi) {
  uint32_t r; asm("cvt.rn.bf16x2.f32 %0, %1, %2;" : "=r"(r) : "f"(hi), "f"(lo)); return r;
}
__device__ __forceinline__ void stsm4(uint32_t a, uint32_t r0, uint32_t r1, uint32_t r2, uint32_t r3) {
  asm volatile("stmatrix.sync.aligned.m8n8.x4.shared.b16 [%0], {%1, %2, %3, %4};" ::"r"(a), "r"(r0), "r"(r1), "r"(r2), "r"(r3) : "memory");
}
__device__ __forceinline__ void stsm4t(uint32_t a, uint32_t r0, uint32_t r1, uint32_t r2, uint32_t r3) {
  asm volatile("stmatrix.sync.aligned.m8n8.x4.trans.shared.b16 [%0], {%1, %2, %3, %4};" ::"r"(a), "r"(r0), "r"(r1), "r"(r2), "r"(r3) : "memory");
}
__device__ __forceinline__ void ldsm4(uint32_t a, uint32_t& r0, uint32_t& r1, uint32_t& r2, uint32_t& r3) {
  asm volatile("ldmatrix.sync.aligned.m8n8.x4.shared.b16 {%0, %1, %2, %3}, [%4];" : "=r"(r0), "=r"(r1), "=r"(r2), "=r"(r3) : "r"(a) : "memory");
}
__device__ __forceinline__ void sts16(uint32_t a, uint32_t v) { asm volatile("st.shared.u16 [%0], %1;" ::"r"(a), "h"((uint16_t)v) : "memory"); }
__device__ __forceinline__ void mma16816(float& c0, float& c1, float& c2, float& c3, uint32_t a0, uint32_t a1, uint32_t a2, uint32_t a3,
                                         uint32_t b0, uint32_t b1) {
  asm volatile("mma.sync.aligned.m16n8k16.row.col.f32.bf16.bf16.f32 {%0, %1, %2, %3}, {%4, %5, %6, %7}, {%8, %9}, {%0, %1, %2, %3};"
               : "+f"(c0), "+f"(c1), "+f"(c2), "+f"(c3) : "r"(a0), "r"(a1), "r"(a2), "r"(a3), "r"(b0), "r"(b1));
}
__device__ __forceinline__ uint32_t sdesc(uint32_t addr, uint32_t lbo) { return (addr >> 4) + ((lbo >> 4) << 16); }
__device__ __forceinline__ uint64_t desc64(uint32_t lo, uint32_t hi) { uint64_t d; asm("mov.b64 %0, {%1, %2};" : "=l"(d) : "r"(lo), "r"(hi)); return d; }
__device__ __forceinline__ void dadd(uint64_t& d, uint32_t inc) {
  asm("{\n.reg .b32 l, h;\nmov.b64 {l, h}, %0;\nadd.u32 l, l, %1;\nmov.b64 %0, {l, h};\n}" : "+l"(d) : "r"(inc));
}

struct Ring {
  uint32_t slot, phase, xp;
  __device__ __forceinline__ void uniform() {
    slot = __shfl_sync(0xffffffffu, slot, 0); phase = __shfl_sync(0xffffffffu, phase, 0); xp = __shfl_sync(0xffffffffu, xp, 0);
  }
  __device__ __forceinline__ void next() { if (++slot == NS) { slot = 0; phase ^= 1; } }
  __device__ __forceinline__ void next_if(bool p) { slot += p; if (slot == NS) { slot = 0; phase ^= 1; } }
};
__device__ __forceinline__ uint32_t borrow(int ks, int n) {
  if (BORROW_ALT) return (ks & 1) && ks >= 3 && ks + 1 < n ? (~ks >> 1) & 1 : 2;
  const int k = ks + 1;
  return k >= 4 && !(k & 2) && k < n ? k & 1 : 2;
}

constexpr uint32_t Q_RANGES = NBETA * NH + P_EARLY * 5;
constexpr int TAIL_STEPS = (NBETA - P_EARLY) * 64, NRANGE = NCTA / 5;
struct Work { int kind, mode, k0, nsteps, range, beta, sub; };
struct Sched { uint16_t queue[Q_RANGES]; uint32_t piece[NRANGE + 1][4]; };
constexpr Sched make_sched() {
  Sched s{};
  int q = 0, a = 0;
  for (int pass = 0; pass < 2; pass++)
    for (int b = pass ? B_LATE : 0; b < NBETA; b++)
      for (int h = pass ? H_LATE : 0; h < (pass || b < B_LATE ? NH : H_LATE); h++) {
        if (a >= P_POS && (a - P_POS) % P_STRIDE == 0 && (a - P_POS) / P_STRIDE < P_EARLY)
          for (int col = 0; col < 5; col++) s.queue[q++] = 0x8000 | col << 8 | (a - P_POS) / P_STRIDE;
        s.queue[q++] = b << 5 | h;
        a++;
      }
  constexpr uint32_t T[NRANGE * 2] = {PIECE_TABLE};
  for (int g = 0; g <= NRANGE; g++)
    for (int n = 0; n < 4; n++) s.piece[g][n] = g < NRANGE && n < 2 ? T[2 * g + n] : 2u << 30;
  return s;
}
__constant__ Sched c_sched = make_sched();
__device__ __forceinline__ Work decode(uint32_t d) {
  Work w;
  w.kind = d >> 30; if (w.kind == 3) w.kind = 1;
  w.mode = (d >> 28) & 3; w.k0 = (d >> 22) & 63;
  if (w.kind == 0) { w.beta = (d >> 5) & 31; w.sub = d & 31; w.nsteps = DM / 64; }
  else { w.beta = d & 31; w.sub = (d >> 8) & 7; w.nsteps = ((d >> 16) & 63) + 1; }
  w.range = ((d >> 11) & 31) * 5 + w.sub;
  return w;
}

__device__ __forceinline__ bool reached(const unsigned* cnt, unsigned target) {
  unsigned v;
  asm volatile("ld.acquire.gpu.global.u32 %0, [%1];" : "=r"(v) : "l"(cnt) : "memory");
  return (int)(v - target) >= 0;
}
__device__ __forceinline__ void wait_count(const unsigned* cnt, unsigned target) {
  unsigned n = 0;
  while (!__all_sync(0xffffffffu, reached(cnt, target))) { if (++n > (1u << 24)) __trap(); }
}
__device__ __forceinline__ uint32_t lds(uint32_t a) { uint32_t v; asm volatile("ld.volatile.shared.u32 %0, [%1];" : "=r"(v) : "r"(a) : "memory"); return v; }

#define TRACE(u, e)
#define T3(u, e)
#define T2C(u, e)
#define T2P(u, r, e)
#define TTAIL(k)
#define TCLK(k)
#define TRACE_P(u, e)
#define TRACE_IN(u, e)

struct Ctx {
  uint32_t sb;
  int wg, warp;
  uint32_t mqk, mpv;
  bool lead;
  int src;
};
template <int N> __device__ __forceinline__ uint32_t dhi(uint32_t lo) { return 0x40000040u + (lo >> (26 + N)); }
__device__ __forceinline__ void release(const Ctx& c, uint32_t slot) {
  if (c.lead) mbar_arrive(c.sb + BAR_EMPTY + slot * 8);
}
__device__ __forceinline__ uint32_t acquire(const Ctx& c, Ring& r, bool have = false) {
  const uint32_t s = r.slot;
  if (!have) mbar_wait_w(c.sb + BAR_FULL + s * 8, r.phase);
  r.next();
  return s;
}
__device__ __forceinline__ void mbar_wait2_w(uint32_t b0, uint32_t p0, uint32_t b1, uint32_t p1) {
  uint32_t n = 0;
  while (!__all_sync(0xffffffffu, mbar_try(b0, p0) & mbar_try(b1, p1))) {
    if (++n > (1u << 22)) __trap();
  }
}
__device__ __forceinline__ void mbar_wait3_w(uint32_t b0, uint32_t p0, uint32_t b1, uint32_t p1, uint32_t b2, uint32_t p2) {
  uint32_t n = 0;
  while (!__all_sync(0xffffffffu, mbar_try(b0, p0) & mbar_try(b1, p1) & mbar_try(b2, p2))) {
    if (++n > (1u << 22)) __trap();
  }
}
__device__ __forceinline__ void acquire2(const Ctx& c, Ring& r, uint32_t& s0, uint32_t& s1, bool have = false) {
  const uint32_t p0 = r.phase;
  s0 = r.slot; r.next(); s1 = r.slot;
  if (!have) mbar_wait2_w(c.sb + BAR_FULL + s0 * 8, p0, c.sb + BAR_FULL + s1 * 8, r.phase);
  r.next();
}
template <int N>
__device__ __forceinline__ bool peek(const Ctx& c, Ring r) {
  bool ok = true;
#pragma unroll
  for (int k = 0; k < N; k++) { ok &= mbar_test(c.sb + BAR_FULL + r.slot * 8, r.phase); r.next(); }
  return ok;
}
__device__ __forceinline__ void staged(const Ctx& c, int part) {
  fence_async_smem();
  __syncwarp();
  mbar_arrive_warp(c.sb + BAR_STG + c.wg * 16 + part * 8);
}

template <int WG, bool FIRST, int H>
__device__ __forceinline__ void proj_half(const Ctx& c, float (&acc)[64], uint32_t w, uint32_t x, uint32_t sw) {
  uint64_t dx = desc64((c.sb + x * SLOT + (WG ? 0 : H * 8192)) >> 4, dhi<0>(x) + sw);
  uint64_t dw = desc64(WG ? (c.sb + w * SLOT + H * 8192) >> 4 : sdesc(c.sb + w * SLOT, 8192), dhi<1>(x));
  wg_fence();
  if (WG) { if (FIRST) wgmma_proj96_init(acc, dw, dx, 0); else wgmma_proj96(acc, dw, dx, 1); }
  else { if (FIRST) wgmma_proj_init(acc, dx, dw, 0); else wgmma_proj(acc, dx, dw, 1); }
#pragma unroll
  for (int k = 1; k < 4; k++) {
    dadd(dx, k == 2 ? 2 + (sw >> 30) * 28 : 2); dadd(dw, 128);
    if (WG) wgmma_proj96(acc, dw, dx, 1); else wgmma_proj(acc, dx, dw, 1);
  }
  wg_commit();
}

__device__ __forceinline__ void proj_store16(uint32_t a, const float* f, float sc) {
  stsm4t(a, pack_bf16(f[0] * sc, f[1] * sc), pack_bf16(f[2] * sc, f[3] * sc), pack_bf16(f[4] * sc, f[5] * sc), pack_bf16(f[6] * sc, f[7] * sc));
}

__device__ __forceinline__ uint32_t stage_off(const Ctx& c) {
  const int lane = lane_now(), mi = lane >> 3, r8 = lane & 7;
  return ((mi >> 1) * 8 + r8) * 128 + (((2 * c.warp + (mi & 1)) ^ r8) << 4);
}
__device__ __forceinline__ uint32_t q3_swz(uint32_t r8) { return ((r8 & 3) << 1) | (r8 >> 2); }
template <int H>
__device__ __forceinline__ void stage_t2(const Ctx& c, const float (&a)[64], float sc) {
  const uint32_t base = c.sb + QBUF_OFF + 2 * 16384 + H * 8192 + stage_off(c);
#pragma unroll
  for (int jj = 0; jj < 4; jj++) proj_store16(base + jj * 2048, &a[jj * 8], sc);
}
template <int H, bool IS_Q>
__device__ __forceinline__ void stage_t3(const Ctx& c, const float (&a)[64], float sc) {
  const uint32_t off = stage_off(c), r8 = (off >> 7) & 7;
  const uint32_t t3 = c.sb + QBUF_OFF + 3 * 16384 + H * 4096 + (IS_Q ? off ^ ((r8 ^ q3_swz(r8)) << 4) : off);
  proj_store16(t3, &a[32], sc);
  proj_store16(t3 + 2048, &a[40], sc);
}

template <bool TRANS>
__device__ __forceinline__ void add16(uint32_t a, float* f) {
  uint32_t r[4];
  if (TRANS) asm volatile("ldmatrix.sync.aligned.m8n8.x4.trans.shared.b16 {%0, %1, %2, %3}, [%4];"
                          : "=r"(r[0]), "=r"(r[1]), "=r"(r[2]), "=r"(r[3]) : "r"(a) : "memory");
  else ldsm4(a, r[0], r[1], r[2], r[3]);
#pragma unroll
  for (int i = 0; i < 4; i++) { f[2 * i] += __uint_as_float(r[i] << 16); f[2 * i + 1] += __uint_as_float(r[i] & 0xffff0000u); }
}

__device__ __forceinline__ void trace_dump(const Ctx& c) {
}
struct RowSum { float l0, l1; };
__device__ __forceinline__ const char* o_addr(uint32_t item, int row) {
  const int lane = lane_now();
  return reinterpret_cast<const char*>(g_o) + ((item * (2 * SQ) + row) * 128 + (lane ^ (lane >> 3)) * 16);
}
__device__ __forceinline__ void o_stg(const char* p, int i, const uint32_t* q) {
  asm volatile("st.global.v4.b32 [%0], {%1, %2, %3, %4};"
               ::"l"(p + (i >> 1) * (SQ * 128) + (i & 1) * 512), "r"(q[0]), "r"(q[1]), "r"(q[2]), "r"(q[3]) : "memory");
}
template <int MODE, int I0 = 0, int NI = 4>
__device__ __forceinline__ void o_emit(const char* p, const float (&o)[64], float inv) {
#pragma unroll
  for (int i = I0; i < I0 + NI; i++) {
    uint32_t q[4];
#pragma unroll
    for (int j = 0; j < 4; j++) q[j] = pack_bf16(o[16 * i + 4 * j + 2 * MODE] * inv, o[16 * i + 4 * j + 2 * MODE + 1] * inv);
    o_stg(p, i, q);
  }
}
__device__ __forceinline__ void o_done(const Ctx& c) {
  __syncwarp();
  mbar_arrive_warp(c.sb + BAR_OUT);
  __syncwarp();
}
__device__ __forceinline__ void pack3(float (&o)[64], const RowSum& inv, uint32_t (&q)[16]) {
  reg_fence(o);
#pragma unroll
  for (int j = 0; j < 16; j++) q[j] = pack_bf16((o[4 * j] + o[4 * j + 2]) * inv.l0, (o[4 * j + 1] + o[4 * j + 3]) * inv.l0);
  reg_fence(q);
}
template <int WG>
__device__ __forceinline__ void o_first(const Ctx& c, uint32_t item, const float (&o)[64], const RowSum& inv, const uint32_t (&q)[16]) {
  const char* p = o_addr(item, WG ? 192 + 8 * c.warp : 64 + 16 * c.warp);
  if (WG) {
#pragma unroll
    for (int i = 0; i < 4; i++) o_stg(p, i, q + 4 * i);
  } else { o_emit<0>(p, o, inv.l0); o_emit<1>(p + 1024, o, inv.l1); }
}
template <int K0, int K1>
__device__ __forceinline__ void o_piece(const Ctx& c, const char* p, int k, const float (&o)[64], const RowSum& inv) {
  constexpr int NI = 8 / O_STEPS, M = K0 * NI / 4;
  if constexpr (K1 - K0 == 1) {
    o_emit<M, K0 * NI % 4, NI>(p + M * 1024, o, M ? inv.l1 : inv.l0);
    if (K1 == O_STEPS) o_done(c);
  } else {
    if (k <= (K0 + K1) / 2) o_piece<K0, (K0 + K1) / 2>(c, p, k, o, inv); else o_piece<(K0 + K1) / 2, K1>(c, p, k, o, inv);
  }
}
template <int WG>
__device__ __forceinline__ void o_second(const Ctx& c, uint32_t item, int k, float (&o)[64], const RowSum& inv) {
  reg_fence(o);
  o_piece<0, O_STEPS>(c, o_addr(item, 128 * WG + 16 * c.warp), k, o, inv);
}
template <int WG>
__device__ __forceinline__ void release_q(const Ctx& c) {
#pragma unroll
  for (int t = 0; t < 2; t++)
    if (c.lead) asm volatile("mbarrier.arrive.shared::cta.b64 _, [%0], 2;" ::"r"(c.sb + BAR_EMPTY + (NS + 2 * WG + t) * 8) : "memory");
  __syncwarp();
}
struct Slots { uint32_t w, x, o, po; };
template <int WG>
__device__ __forceinline__ void acc_fence(float (&a)[64]) {
#pragma unroll
  for (int i = 0; i < (WG ? 48 : 64); i++) asm volatile("" : "+f"(a[i])::"memory");
}
template <int WG>
__device__ __forceinline__ void begin_acquire(const Ctx& c, Ring& r, Slots& h, bool wait) {
  const uint32_t s0 = r.slot, p0 = r.phase, f = c.sb + BAR_FULL;
  r.next();
  const uint32_t p1 = r.phase;
  h.w = r.slot; r.next();
  h.x = WG ? r.slot : s0; h.o = WG ? s0 : r.slot; h.po = r.phase;
  if (wait) { if (WG) mbar_wait3_w(f + s0 * 8, p0, f + h.w * 8, p1, f + h.x * 8, r.phase); else mbar_wait2_w(f + s0 * 8, p0, f + h.w * 8, p1); }
  r.next();
}
template <int WG>
__device__ __forceinline__ void proj_begin(const Ctx& c, Ring& r, float (&a0)[64], Slots& h, bool wait, uint32_t sw) {
  begin_acquire<WG>(c, r, h, wait);
  proj_half<WG, true, 0>(c, a0, h.w, h.x, sw);
  if (WG) release(c, h.o);
}
template <int WG>
__device__ __forceinline__ bool proj_main(const Ctx& c, Ring& r, float (&a0)[64], float (&a1)[64], Slots& h, int n, uint32_t sw, int unit,
                                          uint32_t item, int nq, float (&o1)[64], const RowSum& inv) {
  constexpr bool DEEP = (PDEPTH >> WG) & 1;
  T2C(unit, 3);
  int ks = 1;
#pragma unroll 1
  do {
    const Slots p = h;
    const uint32_t b = borrow(ks, n), tile = NS + (WG ? 3 - b : b), f = c.sb + BAR_FULL;
    const uint32_t s0 = b != 2 ? tile : r.slot, p0 = b != 2 ? (r.xp >> b) & 1 : r.phase;
    r.next_if(b == 2);
    const uint32_t p1 = r.phase;
    h.w = r.slot; r.next();
    const uint32_t s2 = b != 2 ? tile : r.slot;
    h.po = b != 2 ? p0 : r.phase;
    r.next_if(b == 2);
    r.xp ^= 1 << b;
    h.x = WG ? s2 : s0; h.o = WG ? s0 : s2;
    mbar_wait3_w(f + s0 * 8, p0, f + h.w * 8, p1, f + (WG ? s2 : p.o) * 8, WG ? h.po : p.po);
    if (ks < 10) T2C(unit, ks * 4);
    if (DEEP) {
      proj_half<WG, false, 0>(c, a0, h.w, h.x, sw);
      release(c, WG ? h.o : p.o);
      if (ks < 10) T2C(unit, ks * 4 + 1);
      wg_wait<1>();
      if (ks < 10) T2C(unit, ks * 4 + 2);
      release(c, p.x); release(c, p.w);
    } else {
      release(c, WG ? h.o : p.o);
      wg_wait<0>();
      release(c, p.x); release(c, p.w);
      if (LAST_SYNC && !WG) asm volatile("{\n.reg .pred p;\nsetp.eq.u32 p, %0, %1;\n@p bar.sync 5, 256;\n}" ::"r"(ks + LAST_SYNC), "r"(n) : "memory");
      if (ks < 10) T2C(unit, ks * 4 + 1);
      proj_half<WG, false, 0>(c, a0, h.w, h.x, sw);
      if (ks < 10) T2C(unit, ks * 4 + 2);
    }
    if (LAST_SYNC && WG && !DEEP) asm volatile("{\n.reg .pred p;\nsetp.eq.u32 p, %0, %1;\n@p bar.arrive 5, 256;\n}" ::"r"(ks + LAST_SYNC), "r"(n) : "memory");
    proj_half<WG, false, 1>(c, a1, h.w, h.x, sw);
    if (LAST_SYNC && WG && DEEP) asm volatile("{\n.reg .pred p;\nsetp.eq.u32 p, %0, %1;\n@p bar.arrive 5, 256;\n}" ::"r"(ks + LAST_SYNC), "r"(n) : "memory");
    if (ks < 10) T2C(unit, ks * 4 + 3);
    if (ks <= nq) o_second<WG>(c, item, ks, o1, inv);
  } while (++ks != n);
  {
    const uint32_t e0 = c.sb + BAR_EMPTY + (NS + 3 * WG) * 8, e1 = c.sb + BAR_EMPTY + (NS + 1 + WG) * 8;
    const uint32_t p0 = (r.xp ^ unit ^ 1) & 1, p1 = ((r.xp >> 1) ^ unit ^ 1) & 1;
    if (WG) mbar_wait2_w(e0, p0, e1, p1); else mbar_wait3_w(e0, p0, e1, p1, c.sb + BAR_FULL + h.o * 8, h.po);
  }
  const bool have = PEEK ? peek<3>(c, r) : false;
  if (!WG) release(c, h.o);
  wg_wait<1>();
  acc_fence<WG>(a0);
  return PEEK && __all_sync(0xffffffffu, have);
}
template <int WG>
__device__ __forceinline__ void proj_end(const Ctx& c, float (&a1)[64], const Slots& h) {
  wg_wait<0>();
  acc_fence<WG>(a1);
  release(c, h.x); release(c, h.w);
}
__device__ __forceinline__ uint32_t get_desc(const Ctx& c, int i) {
  uint32_t d;
  mbar_wait_w(c.sb + BAR_DESC, (i - 1) & 1);
  asm volatile("ld.volatile.shared.u32 %0, [%1];" : "=r"(d) : "r"(c.sb + DESC_OFF + (i & 3) * 4) : "memory");
  return __shfl_sync(0xffffffffu, d, 0);
}

__device__ __forceinline__ float quad_max(float x) {
  x = fmaxf(x, __shfl_xor_sync(0xffffffffu, x, 1));
  return fmaxf(x, __shfl_xor_sync(0xffffffffu, x, 2));
}
__device__ __forceinline__ float quad_sum(float x) {
  x += __shfl_xor_sync(0xffffffffu, x, 1);
  return x + __shfl_xor_sync(0xffffffffu, x, 2);
}
template <bool SP, bool FIRST>
__device__ __forceinline__ void exps(const Ctx& c, const float (&s)[32], uint32_t (&p)[SP ? 8 : 16], RowSum& st) {
  if constexpr (SP) {
    uint32_t q[8];
    float t;
#pragma unroll
    for (int j = 0; j < 8; j++) {
      const float e0 = ex2(s[4 * j] + s[4 * j + 2]), e1 = ex2(s[4 * j + 1] + s[4 * j + 3]);
      if (j == 0) t = e0 + e1; else t += e0 + e1;
      q[j] = pack_bf16(e0, e1);
    }
    const bool odd = c.src & 2;
#pragma unroll
    for (int g = 0; g < 4; g++) {
      p[2 * g] = __shfl_sync(0xffffffffu, odd ? q[2 * g + 1] : q[2 * g], c.src);
      p[2 * g + 1] = __shfl_sync(0xffffffffu, odd ? q[2 * g] : q[2 * g + 1], c.src ^ 1);
    }
    st.l0 = FIRST ? t : st.l0 + t;
  } else {
    float t0, t1;
#pragma unroll
    for (int j = 0; j < 8; j++) {
      const float e0 = ex2(s[4 * j]), e1 = ex2(s[4 * j + 1]), e2 = ex2(s[4 * j + 2]), e3 = ex2(s[4 * j + 3]);
      if (j == 0) { t0 = e0 + e1; t1 = e2 + e3; } else { t0 += e0 + e1; t1 += e2 + e3; }
      p[2 * j] = pack_bf16(e0, e1);
      p[2 * j + 1] = pack_bf16(e2, e3);
    }
    st.l0 = FIRST ? t0 : st.l0 + t0;
    st.l1 = FIRST ? t1 : st.l1 + t1;
  }
}
template <bool SP>
__device__ __forceinline__ bool finish_sums(RowSum& st) {
  const float a = quad_sum(st.l0), b = SP ? a : quad_sum(st.l1);
  st.l0 = __fdividef(1.f, a); st.l1 = __fdividef(1.f, b);
  return !DEV_HALF && !(a >= SUM_LO && a <= SUM_HI && b >= SUM_LO && b <= SUM_HI);
}
template <bool SP, bool INIT, int SITE, bool COMMIT = true>
__device__ __forceinline__ void issue_qk(const Ctx& c, float (&s)[32], const uint32_t (&qs)[16], uint32_t dq, uint32_t dk) {
  uint64_t a = desc64(dq, dhi<SITE & 1>(dk)), b = desc64(dk, dhi<1 - (SITE & 1)>(dk));
  if (SP) {
    if (INIT) wgmma_qk_sp_init(s, qs[0], qs[1], qs[2], qs[3], b, 0, c.mqk); else wgmma_qk_sp(s, qs[0], qs[1], qs[2], qs[3], b, 0, c.mqk);
#pragma unroll
    for (int k = 1; k < 4; k++) { dadd(b, k == 2 ? 508 : 4); wgmma_qk_sp(s, qs[4 * k], qs[4 * k + 1], qs[4 * k + 2], qs[4 * k + 3], b, 1, c.mqk); }
  } else {
    if (INIT) wgmma_qk_init(s, a, b, 0); else wgmma_qk(s, a, b, 0);
#pragma unroll
    for (int k = 1; k < 8; k++) { dadd(a, k == 4 ? 506 : 2); dadd(b, k == 4 ? 506 : 2); wgmma_qk(s, a, b, 1); }
  }
  if (COMMIT) wg_commit();
}
template <bool SP, bool ACC, int SITE, bool SPLIT = false>
__device__ __forceinline__ void issue_pv(const Ctx& c, float (&o)[64], const uint32_t (&p)[SP ? 8 : 16], uint32_t dv) {
  uint64_t b = desc64(dv, dhi<SITE & 1>(dv));
  if constexpr (SP) {
    if (ACC) wgmma_pv_sp(o, p[0], p[1], p[2], p[3], b, 1, c.mpv); else wgmma_pv_sp_init(o, p[0], p[1], p[2], p[3], b, 0, c.mpv);
    if (SPLIT) wg_commit();
    dadd(b, 256);
    wgmma_pv_sp(o, p[4], p[5], p[6], p[7], b, 1, c.mpv);
  } else {
    if (ACC) wgmma_pv(o, p[0], p[1], p[2], p[3], b, 1); else wgmma_pv_init(o, p[0], p[1], p[2], p[3], b, 0);
#pragma unroll
    for (int k = 1; k < 4; k++) { dadd(b, 128); wgmma_pv(o, p[4 * k], p[4 * k + 1], p[4 * k + 2], p[4 * k + 3], b, 1); }
  }
  wg_commit();
}
__device__ __forceinline__ void pack_rows(const float (&o)[64], float sc, uint32_t (&q)[32]) {
#pragma unroll
  for (int j = 0; j < 32; j++) q[j] = pack_bf16(o[2 * j] * sc, o[2 * j + 1] * sc);
}
__device__ __forceinline__ void stage_rows(const Ctx& c, uint32_t tile_addr, const uint32_t (&q)[32]) {
  const int lane = lane_now(), mi = lane >> 3, r8 = lane & 7;
  const uint32_t row_addr = tile_addr + (16 * c.warp + (mi & 1) * 8 + r8) * 128;
#pragma unroll
  for (int jj = 0; jj < 8; jj++)
    stsm4(row_addr + (jj >> 2) * 8192 + (((((2 * jj) & 7) + (mi >> 1)) ^ r8) << 4), q[4 * jj], q[4 * jj + 1], q[4 * jj + 2], q[4 * jj + 3]);
}
__device__ __forceinline__ void stage_rows(const Ctx& c, uint32_t tile_addr, const float (&o)[64], float sc) {
  uint32_t q[32];
  pack_rows(o, sc, q);
  stage_rows(c, tile_addr, q);
}
template <int SITE>
__device__ __forceinline__ void issue_qk_rs(float (&s)[32], uint32_t (&q)[32], uint32_t dk) {
  uint64_t b = desc64(dk, dhi<SITE>(dk));
  reg_fence(q);
  wg_fence();
  wgmma_qk_rs_init(s, q[0], q[1], q[2], q[3], b, 0);
#pragma unroll
  for (int k = 1; k < 8; k++) { dadd(b, k == 4 ? 506 : 2); wgmma_qk_rs(s, q[4 * k], q[4 * k + 1], q[4 * k + 2], q[4 * k + 3], b, 1); }
  wg_commit();
}

__device__ __forceinline__ void redo_tile(const Ctx& c, uint32_t q_addr, uint32_t half, const __nv_bfloat16* kp, const __nv_bfloat16* vp,
                                          uint32_t item, int row) {
  float o[64];
  const int lane = lane_now(), g = lane >> 2, cc = lane & 3, mi = lane >> 3, r8 = lane & 7;
  const uint32_t qa = q_addr + (half == 4096 ? 8 * c.warp + r8 : 16 * c.warp + (mi & 1) * 8 + r8) * 128, swz = half == 4096 ? q3_swz(r8) : r8;
  const uint32_t* kq = reinterpret_cast<const uint32_t*>(kp + g * DH) + cc;
  const unsigned short* vq = reinterpret_cast<const unsigned short*>(vp + 2 * cc * DH) + g;
  float m0 = -INFINITY, m1 = -INFINITY, l0 = 0.f, l1 = 0.f;
#pragma unroll
  for (int i = 0; i < 64; i++) o[i] = 0.f;
#pragma unroll 1
  for (int kb = 0; kb < SK / 16; kb++) {
    float z[8] = {0.f, 0.f, 0.f, 0.f, 0.f, 0.f, 0.f, 0.f};
#pragma unroll 2
    for (int kk = 0; kk < 8; kk++) {
      uint32_t a0, a1, a2, a3;
      ldsm4(qa + (kk >> 2) * half + ((((kk & 3) * 2 + (mi >> 1)) ^ swz) << 4), a0, a1, a2, a3);
      const uint32_t* kr = kq + kb * (16 * DH / 2) + kk * 8;
      mma16816(z[0], z[1], z[2], z[3], a0, a1, a2, a3, __ldg(kr), __ldg(kr + 4));
      mma16816(z[4], z[5], z[6], z[7], a0, a1, a2, a3, __ldg(kr + 8 * DH / 2), __ldg(kr + 8 * DH / 2 + 4));
    }
    const float n0 = fmaxf(m0, quad_max(fmaxf(fmaxf(z[0], z[1]), fmaxf(z[4], z[5]))));
    const float n1 = fmaxf(m1, quad_max(fmaxf(fmaxf(z[2], z[3]), fmaxf(z[6], z[7]))));
    const float al0 = ex2(m0 - n0), al1 = ex2(m1 - n1);
    m0 = n0; m1 = n1;
#pragma unroll
    for (int i = 0; i < 8; i++) z[i] = ex2(z[i] - ((i & 2) ? n1 : n0));
    l0 = l0 * al0 + (z[0] + z[1]) + (z[4] + z[5]);
    l1 = l1 * al1 + (z[2] + z[3]) + (z[6] + z[7]);
    const uint32_t a0 = pack_bf16(z[0], z[1]), a1 = pack_bf16(z[2], z[3]), a2 = pack_bf16(z[4], z[5]), a3 = pack_bf16(z[6], z[7]);
    const unsigned short* vr = vq + kb * (16 * DH);
#pragma unroll
    for (int nb = 0; nb < 16; nb++) {
      o[4 * nb] *= al0; o[4 * nb + 1] *= al0; o[4 * nb + 2] *= al1; o[4 * nb + 3] *= al1;
      const uint32_t b0 = __ldg(vr + nb * 8) | ((uint32_t)__ldg(vr + nb * 8 + DH) << 16);
      const uint32_t b1 = __ldg(vr + nb * 8 + 8 * DH) | ((uint32_t)__ldg(vr + nb * 8 + 9 * DH) << 16);
      mma16816(o[4 * nb], o[4 * nb + 1], o[4 * nb + 2], o[4 * nb + 3], a0, a1, a2, a3, b0, b1);
    }
  }
  const char* p = o_addr(item, row);
  o_emit<0>(p, o, __fdividef(1.f, quad_sum(l0)));
  o_emit<1>(half == 4096 ? p : p + 1024, o, __fdividef(1.f, quad_sum(l1)));
}

template <bool SPA, bool SPB, int SITE, int ID>
__device__ __forceinline__ void batch(const Ctx& c, float (&s)[32], const uint32_t (&qs)[16], uint32_t dq, uint32_t dk, float (&ob)[64],
                                      uint32_t (&pb)[SPB ? 8 : 16], uint32_t dv) {
  if constexpr (SPA) {
    reg_fence(pb);
    wg_fence();
    issue_pv<SPB, true, ID>(c, ob, pb, dv);
    issue_qk<SPA, false, ID>(c, s, qs, dq, dk);
  } else {
    constexpr bool EARLY = ((QK_EARLY_MASK >> (SITE + (SPB ? 2 : 0))) & 1) != 0;
    if (!EARLY) reg_fence(pb);
    wg_fence();
    issue_qk<SPA, false, ID, !SPB>(c, s, qs, dq, dk);
    if (EARLY) { reg_fence(pb); wg_fence(); }
    issue_pv<SPB, true, ID, SPB>(c, ob, pb, dv);
  }
}

template <bool SP0>
__device__ __forceinline__ bool attention(Ctx c, Ring& r, int unit, uint32_t& d, const float (&a0)[64], float (&o0)[64], float (&o1)[64],
                                          RowSum& st0, RowSum& st1, const Slots& h, uint32_t (&q3)[16], bool kv) {
  constexpr bool SP1 = false;
  if (SP0) { c.mqk = META_QK + (d >> 28); c.mpv = META_PV + (d >> 28); asm volatile("" : "+r"(c.mqk), "+r"(c.mpv)); }
  if (SP0) { const int lane = lane_now(); c.src = (lane & 28) | ((lane & 1) << 1) | ((lane >> 1) & 1); }
  float s[32];
  uint32_t p0[SP0 ? 8 : 16], p1[16];
  const uint32_t q0a = c.sb + QBUF_OFF + (SP0 ? 3 : 0) * 16384, q1a = c.sb + QBUF_OFF + (SP0 ? 2 : 1) * 16384;
  const uint32_t dq0 = sdesc(q0a, 0), dq1 = sdesc(q1a, 0);
  uint32_t sk, sv, sn;
  uint32_t qs[16];
  T2C(unit, 40);
  if (SP0) {
    stage_t3<0, true>(c, a0, SM_C);
    stage_t2<0>(c, a0, SM_C);
    T2C(unit, 41);
    proj_end<1>(c, o0, h);
    T2C(unit, 42);
    stage_t3<1, true>(c, o0, SM_C);
    stage_t2<1>(c, o0, SM_C);
    sk = acquire(c, r, kv);
    fence_async_smem();
    T2C(unit, 43);
    bar_sync(1, LAG_BAR & 30 ? 256 : 128);
    const int lane = lane_now(), g = lane >> 2, cc = lane & 3;
    const uint32_t qa = q0a + (8 * c.warp + g) * 128 + (cc & 1) * 8;
#pragma unroll
    for (int k = 0; k < 8; k++)
      asm volatile("ld.shared.v2.u32 {%0, %1}, [%2];" : "=r"(qs[2 * k]), "=r"(qs[2 * k + 1])
                   : "r"(qa + (k >> 2) * 4096 + ((((k & 3) * 2 + (cc >> 1)) ^ q3_swz(g)) << 4)) : "memory");
    TRACE(unit, 2);
    T2C(unit, 44);
    float s1[32];
    wg_fence();
    issue_qk<SP1, true, 1>(c, s1, qs, dq1, sdesc(c.sb + sk * SLOT, 0));
    reg_fence(qs);
    wg_fence();
    issue_qk<SP0, true, 0>(c, s, qs, dq0, sdesc(c.sb + sk * SLOT, 0));
    T2C(unit, 45);
    acquire2(c, r, sv, sn, kv);
    wg_wait<1>();
    reg_fence(s1);
    T2C(unit, 47);
    exps<SP1, true>(c, s1, p1, st1);
    reg_fence(p1);
    wg_fence();
    issue_pv<SP1, false, 1>(c, o1, p1, sdesc(c.sb + sv * SLOT, 8192));
    if (LAG_BAR & 1) asm volatile("bar.arrive 4, 256;" ::: "memory");
    wg_wait<1>();
    reg_fence(s);
    T2C(unit, 48);
    release(c, sk);
    sk = sn;
    exps<SP0, true>(c, s, p0, st0);
    reg_fence(p0);
    wg_fence();
    issue_pv<SP0, false, 0>(c, o0, p0, sdesc(c.sb + sv * SLOT, 8192));
    issue_qk<SP0, false, 2>(c, s, qs, dq0, sdesc(c.sb + sk * SLOT, 0));
    T2C(unit, 49);
    sn = acquire(c, r);
    T2C(unit, 50);
    wg_wait<0>();
    reg_fence(s);
  } else {
    float s1[32];
    uint32_t q0[32], q1[32];
    if (!PEEK) sk = acquire(c, r);
    pack_rows(a0, SM_C, q0);
    if (RS_STAGE & 1) stage_rows(c, q0a, q0);
    reg_fence(q0);
    if (PEEK) sk = acquire(c, r, kv);
    T2C(unit, 41);
    proj_end<0>(c, o1, h);
    TRACE(unit, 2);
    T2C(unit, 42);
    issue_qk_rs<0>(s, q0, sdesc(c.sb + sk * SLOT, 0));
    if (LAG_BAR & 8) asm volatile("bar.arrive 1, 256;" ::: "memory");
    T2C(unit, 43);
    reg_fence(o1);
    pack_rows(o1, SM_C, q1);
    if (RS_STAGE & 2) stage_rows(c, q1a, q1);
    T2C(unit, 44);
    if (LAG_BAR & 4) asm volatile("bar.arrive 1, 256;" ::: "memory");
    issue_qk_rs<1>(s1, q1, sdesc(c.sb + sk * SLOT, 0));
    if (LAG_BAR & 2) asm volatile("bar.arrive 1, 256;" ::: "memory");
    T2C(unit, 45);
    acquire2(c, r, sv, sn, kv);
    if (!(RS_STAGE & 5)) stage_rows(c, q0a, q0);
    if (!(RS_STAGE & 10)) stage_rows(c, q1a, q1);
    T2C(unit, 46);
    wg_wait<1>();
    reg_fence(s);
    if (LAG_BAR & 16) asm volatile("bar.arrive 1, 256;" ::: "memory");
    T2C(unit, 47);
    if (RS_STAGE & 4) { reg_fence(q0); stage_rows(c, q0a, q0); }
    exps<SP0, true>(c, s, p0, st0);
    reg_fence(p0);
    wg_wait<0>();
    reg_fence(s1);
    if (RS_STAGE & 8) { reg_fence(q1); stage_rows(c, q1a, q1); }
    fence_async_smem();
    __syncwarp();
    wg_fence();
    issue_qk<SP0, false, 2>(c, s, qs, dq0, sdesc(c.sb + sn * SLOT, 0));
    issue_pv<SP0, false, 0>(c, o0, p0, sdesc(c.sb + sv * SLOT, 8192));
    T2C(unit, 48);
    release(c, sk);
    sk = sn;
    exps<SP1, true>(c, s1, p1, st1);
    reg_fence(p1);
    wg_fence();
    issue_pv<SP1, false, 1>(c, o1, p1, sdesc(c.sb + sv * SLOT, 8192));
    T2C(unit, 49);
    sn = acquire(c, r);
    if (LAG_BAR & 1) bar_sync(4, 256);
    T2C(unit, 50);
    wg_wait<1>();
    reg_fence(s);
  }
  TRACE_IN(unit, 4);
  T2C(unit, 51);
#pragma unroll 1
  for (int j = 1; j < 15; j++) {
    const uint32_t sv_prev = sv, sk_prev = sk;
    sv = sn;
    const uint32_t dv = sdesc(c.sb + sv * SLOT, 8192);
    reg_fence(p0);
    exps<SP0, false>(c, s, p0, st0);
    batch<SP1, SP0, 0, 3>(c, s, qs, dq1, sdesc(c.sb + sk * SLOT, 0), o0, p0, dv);
    sk = acquire(c, r);
    wg_wait<1>();
    reg_fence(s); reg_fence(p1);
    release(c, sv_prev); release(c, sk_prev);
    exps<SP1, false>(c, s, p1, st1);
    batch<SP0, SP1, 1, 4>(c, s, qs, dq0, sdesc(c.sb + sk * SLOT, 0), o1, p1, dv);
    sn = acquire(c, r);
    if (SP0) wg_wait<0>(); else wg_wait<1>();
    reg_fence(s);
  }
  TRACE_IN(unit, 5);
  T2C(unit + 1, 52);
  const uint32_t sv_prev = sv;
  sv = sn;
  const uint32_t dv = sdesc(c.sb + sv * SLOT, 8192);
  reg_fence(p0);
  exps<SP0, false>(c, s, p0, st0);
  batch<SP1, SP0, 0, 5>(c, s, qs, dq1, sdesc(c.sb + sk * SLOT, 0), o0, p0, dv);
  asm volatile("ld.volatile.shared.u32 %0, [%1];" : "=r"(d) : "r"(c.sb + DESC_OFF + ((unit + 1) & 3) * 4) : "memory");
  wg_wait<1>();
  reg_fence(s); reg_fence(p1);
  T2C(unit + 1, 53);
  release(c, sv_prev); release(c, sk);
  d = __shfl_sync(0xffffffffu, d, 0);
  const bool bad0 = finish_sums<SP0>(st0);
  exps<SP1, false>(c, s, p1, st1);
  reg_fence(p1);
  wg_fence();
  issue_pv<SP1, true, 2>(c, o1, p1, dv);
  T2C(unit + 1, 54);
  const bool have = peek<2 + SP0>(c, r);
  const bool bad = finish_sums<SP1>(st1) | bad0;
  if (SP0 && !PACK_LATE) {
    wg_wait<1>();
    pack3(o0, st0, q3);
  }
  T2C(unit + 1, 55);
  if (EARLY_BEG && d < (2u << 30) && !__all_sync(0xffffffffu, have)) { Ring t = r; Slots u; begin_acquire<SP0>(c, t, u, true); }
  T2C(unit + 1, 56);
  wg_wait<0>();
  if (!SP0 || PACK_LATE) reg_fence(o0);
  reg_fence(o1);
  T2C(unit + 1, 57);
  release(c, sv);
  return bad;
}
template <int WG>
__device__ __forceinline__ bool wg_any(bool p) {
  uint32_t any;
  asm volatile("{\n.reg .pred p, q;\nsetp.ne.u32 p, %1, 0;\nbar.red.or.pred q, %2, 128, p;\nselp.u32 %0, 1, 0, q;\n}"
               : "=r"(any) : "r"((uint32_t)p), "n"(2 + WG) : "memory");
  return __any_sync(0xffffffffu, any);
}

template <int WG>
__device__ __forceinline__ void consumer(Ctx c, const __nv_bfloat16* const* kv) {
  c.wg = WG;
  Ring r{0, 0, 0};
  bool bad;
  uint32_t q3[16];
  float a0[64], a1[64], o1[64];
  Slots h;
  RowSum inv0, inv1;
  uint32_t d = blockIdx.x, dc = 0, sw;
  int i = 0, nq;
begin:
  sw = d & (1u << 30);
  proj_begin<WG>(c, r, a0, h, true, sw);
  proj_half<WG, true, 1>(c, a1, h.w, h.x, sw);
  nq = 0;
#pragma unroll
  for (int k = 0; k < 64; k++) asm volatile("" : "=f"(o1[k]));
  asm volatile("" : "=f"(inv1.l0), "=f"(inv1.l1));
  while (true) {
    TRACE(i, 0); TRACE(i, 6);
    bad = proj_main<WG>(c, r, a0, a1, h, d >> 30 ? ((d >> 16) & 63) + 1 : DM / 64, sw, i, dc, nq, o1, inv1);
    dc = d;
    TRACE(i, 1);
    if (d >> 30) goto out_tile;
    bad = WG ? attention<WG>(c, r, i, d, a0, a1, o1, inv0, inv1, h, q3, bad) : attention<WG>(c, r, i, d, a0, o1, a1, inv1, inv0, h, q3, bad);
    if (!EARLY_BEG || d >= (2u << 30)) break;
    Ring t = r;
    sw = d & (1u << 30);
    begin_acquire<WG>(c, t, h, false);
    proj_half<WG, true, 0>(c, a0, h.w, h.x, sw);
    if (WG && PACK_LATE) pack3(a1, inv0, q3);
    if (WG && RED_FIRST != 2) proj_half<WG, true, 1>(c, a1, h.w, h.x, sw); else if (!WG) reg_fence(a1);
    T2C(i + 1, 58);
    if (!WG || RED_FIRST != 1) o_first<WG>(c, dc, a1, inv0, q3);
    if (__builtin_expect(wg_any<WG>(bad), 0)) {
      wg_wait<0>();
      acc_fence<WG>(a0);
      if (WG && RED_FIRST != 2) acc_fence<WG>(a1);
      goto redo;
    }
    r = t;
    T2C(i + 1, 1);
    if (!WG || RED_FIRST == 2) proj_half<WG, true, 1>(c, a1, h.w, h.x, sw);
    if (WG) release(c, h.o);
    release_q<WG>(c);
    if (WG && RED_FIRST == 1) o_first<WG>(c, dc, a1, inv0, q3);
    T2C(i + 1, 2);
    nq = O_STEPS;
    TRACE(i, 3); TRACE(i, 7);
    i++;
  }
  if (wg_any<WG>(bad)) goto redo;
  release_q<WG>(c);
  if (WG && PACK_LATE) pack3(a1, inv0, q3);
  o_first<WG>(c, dc, a1, inv0, q3);
#pragma unroll
  for (int k = 1; k <= O_STEPS; k++) o_second<WG>(c, dc, k, o1, inv1);
  T2C(i + 1, 58);
next:
  TRACE(i, 3); TRACE(i, 7);
  if ((d >> 30) != 2) {
    i++;
    r.uniform();
    goto begin;
  }
  trace_dump(c);
  return;
out_tile:
  proj_end<WG>(c, a1, h);
  if (((d >> 28) & 3) == 2) {
    const int lane = lane_now(), mi = lane >> 3, r8 = lane & 7;
    const uint32_t off = c.sb + (WG ? stage_off(c) : (16 * c.warp + (mi & 1) * 8 + r8) * 128);
#pragma unroll 1
    for (int k = (d >> 5) & 3; k > 0; k--) {
      uint32_t s0, s1;
      if (WG) { acquire2(c, r, s0, s1); release(c, s0); release(c, s1); }
#pragma unroll
      for (int t = 0; t < 2; t++) {
        const uint32_t sp = acquire(c, r), base = off + sp * SLOT;
        if (WG) {
#pragma unroll
          for (int jj = 0; jj < (t ? 2 : 4); jj++) {
            add16<true>(base + jj * 2048, &a0[(t * 4 + jj) * 8]);
            add16<true>(base + jj * 2048 + (t ? 4096 : 8192), &a1[(t * 4 + jj) * 8]);
          }
        } else {
#pragma unroll
          for (int jj = 0; jj < 8; jj++) add16<false>(base + (jj >> 2) * 8192 + (((((2 * jj) & 7) + (mi >> 1)) ^ r8) << 4), t ? &a1[jj * 8] : &a0[jj * 8]);
        }
        release(c, sp);
      }
      if (!WG) { acquire2(c, r, s0, s1); release(c, s0); release(c, s1); }
    }
  }
  if (WG) { stage_t3<0, false>(c, a0, 1.f); stage_t3<1, false>(c, a1, 1.f); }
  else stage_rows(c, c.sb + QBUF_OFF, a0, 1.f);
  staged(c, 0);
  if (WG) { stage_t2<0>(c, a0, 1.f); stage_t2<1>(c, a1, 1.f); }
  else stage_rows(c, c.sb + QBUF_OFF + 16384, a1, 1.f);
  staged(c, 1);
  d = get_desc(c, i + 1);
  TRACE(i, 2);
  goto next;
redo:
  {
    const size_t hoff = (size_t)(dc & 511) * (SK * DH);
    const int br = (dc >> 9) & 1;
#pragma unroll 1
    for (int part = 0; part < 2; part++) {
      const int t = WG ? 3 - part : part;
      redo_tile(c, c.sb + QBUF_OFF + t * 16384, t == 3 ? 4096 : 8192, kv[br] + hoff, kv[2 + br] + hoff, dc,
                t * 64 + (t == 3 ? 8 : 16) * c.warp);
    }
    o_done(c);
    release_q<WG>(c);
  }
  goto next;
}

template <bool SIMPLE>
__global__ void __launch_bounds__(384, 1) mha_fused_kernel(const __grid_constant__ Params P) {
  extern __shared__ __align__(1024) uint8_t smem_raw[];
  const uint32_t sbase = smem_u32(smem_raw);
  const int tid = threadIdx.x;
  const int wg = __shfl_sync(0xffffffffu, tid >> 7, 0);
  const int warp = __shfl_sync(0xffffffffu, (tid >> 5) & 3, 0);
  const int lane = tid & 31;
  const int cta = blockIdx.x;

  if (tid == 0) T3(15, 0);
  if ((sbase & 1023) || sbase + SMEM_BYTES > 0x40000) __trap();
  {
    const int wi = wg * 4 + warp;
    asm volatile(ELECT "prefetch.tensormap [%0];\n}" ::"l"(&P.x[0][0] + wi) : "memory");
#pragma unroll
    for (int k = 0; k < 3; k++) {
      const int b = min(BAR_OFF + (wi * 3 + k) * 8, BAR_GO);
      asm volatile(ELECT "mbarrier.init.shared::cta.b64 [%0], %1;\n}"
                   ::"r"(sbase + b), "r"(b < BAR_EMPTY || b >= BAR_DESC ? 1 : b >= BAR_STG && b < BAR_OUT ? 4 : 8) : "memory");
    }
    asm volatile("fence.mbarrier_init.release.cluster;" ::: "memory");
    if (wi < 6) asm volatile(ELECT "prefetch.tensormap [%0];\n}" ::"l"(&P.x[0][0] + 12 + wi) : "memory");
  }
  __syncthreads();

  if (wg == 2) {
    asm volatile("setmaxnreg.dec.sync.aligned.u32 %0;" ::"n"(REG_P));
    if (warp == 1) {
      const uint32_t qb = sbase + QBUF_OFF;
      const uint32_t ep = __shfl_sync(0xffffffffu, *(volatile unsigned*)&g_epoch + 1, 0);
      asm volatile("st.volatile.shared.u32 [%0], %1;" ::"r"(sbase + EPOCH_OFF), "r"(ep) : "memory");
      uint32_t dc = cta, qi = 0, piece = 0, na = 0;
      TTAIL(0);
      for (int i = 0; (dc >> 30) != 2; i++) {
        mbar_wait_w(sbase + BAR_GO, i & 1);
        if (TLB_WARM && (dc >> 30) == 0) asm volatile(ELECT "st.global.u32 [%0], 0;\n}" ::"l"(g_o + dc * (2 * SQ * 64)) : "memory");
        if (piece == 0) {
          if (lane == 0) {
            qi = atomicAdd(&g_next, 1);
            if (qi == (SIMPLE ? NBETA * (NH + 5) : Q_RANGES) - 1) { g_next = 0; g_epoch = ep; }
          }
          qi = __shfl_sync(0xffffffffu, qi, 0) + (SIMPLE ? gridDim.x : NCTA);
        }
        uint32_t d;
        if (qi < Q_RANGES) { d = c_sched.queue[qi]; if (d & 0x8000) d ^= (1u << 30) | (63u << 16) | 0x8000; }
        else if (SIMPLE) { const uint32_t t = qi - NBETA * NH; d = t < NBETA * 5 ? (1u << 30) | (63u << 16) | (t % 5) << 8 | t / 5 : 2u << 30; }
        else { const uint32_t e = qi - Q_RANGES, g = e / 5; d = c_sched.piece[g][piece++] | (e - g * 5) << 8; }
        if ((d >> 30) == 1) {
          const uint32_t ok = __ballot_sync(0xffffffffu, reached(&g_cnt[lane & 1][d & 31], ep * (lane & 1 ? NH - H_LATE : H_LATE)));
          if (!(ok & 2)) d |= ((d >> 22) & 63) >= 2 * H_LATE - O_STEPS ? (2u << 30) | 128 : 128;
          if (!(ok & 1) || (O_STEPS > 4 && ((d >> 16) & 63) < O_STEPS)) d |= 2u << 30;
        }
        asm volatile("st.volatile.shared.u32 [%0], %1;" ::"r"(sbase + DESC_OFF + ((i + 1) & 3) * 4), "r"(d) : "memory");
        __syncwarp();
        mbar_arrive_warp(sbase + BAR_DESC);
        const Work w = decode(dc);
        dc = d;
        if (w.kind == 0) {
          mbar_wait_w(sbase + BAR_OUT, na++ & 1);
          TTAIL(1);
          T3(i, 0); T3(i, 1);
          asm volatile(ELECT "red.release.gpu.global.add.u32 [%0], 1;\n}" ::"l"(&g_cnt[w.sub >= H_LATE][w.beta]) : "memory");
          T3(i, 2);
          TTAIL(2);
          continue;
        }
        const bool fin = w.mode != 1;
        uint64_t pol, pol2;
        asm volatile("createpolicy.fractional.L2::evict_first.b64 %0, 1.0;" : "=l"(pol));
        asm volatile("createpolicy.fractional.L2::evict_normal.b64 %0, 1.0;" : "=l"(pol2));
        if (!fin) pol = pol2;
        const CUtensorMap* m = fin ? P.out_st : P.o_st;
        const int c1 = fin ? (w.beta & 15) * SQ : 0;
        const int c2 = fin ? (w.beta >> 4) * (DM / 64) + w.sub * 2 : NBETA * 64 + w.range * 2;
        uint32_t pend = 0;
#pragma unroll 1
        for (int e = 0; e < 4; e++) {
          const int t = (ST_ORDER >> (4 * e)) & 3;
          mbar_wait_w(sbase + BAR_STG + (t ^ (t >> 1)) * 8, (i - na) & 1);
          tma_st3_hint_w(m + (t == 3), qb + t * 16384, 0, c1 + t * 64, c2, pol);
          bulk_commit();
          T2P(i + 1, 5, 2 * e);
          if (pend) {
            bulk_wait_read<1>();
            mbar_arrive8_w(pend);
            T2P(i + 1, 5, 2 * e - 1);
          }
          pend = sbase + BAR_EMPTY + (NS + t) * 8;
          if ((ST_NOW >> e) & 1) {
            bulk_wait_read<0>();
            mbar_arrive8_w(pend);
            pend = 0;
            T2P(i + 1, 5, 2 * e + 1);
          }
        }
        T3(i, 0);
        if (piece >= 2) TTAIL(piece * 2 - 1);
        asm volatile("cp.async.bulk.wait_group 0;" ::: "memory");
        T3(i, 1);
        if (w.mode == 1) asm volatile(ELECT "st.release.gpu.global.u32 [%0], %1;\n}" ::"l"(&g_flag[w.range]), "r"(ep) : "memory");
        T3(i, 2);
        if (piece >= 2) TTAIL(piece * 2);
      }
      T3(15, 1);
    } else
    if (warp == 0) {
      Ring r{0, 1, 3};
      uint32_t d = cta;
      for (int i = 0;; i++) {
        const Work w = decode(d);
        if (w.kind == 2) break;
        const CUtensorMap* m = w.kind == 0 ? &P.wq[w.beta >> 4] : &P.wo[w.beta >> 4];
        for (int ks = 0; ks < w.nsteps; ks++) {
          const uint32_t b = borrow(ks, w.nsteps);
          r.next_if(b == 2);
          const uint32_t bar = sbase + BAR_FULL + r.slot * 8;
          mbar_wait_w(bar + (BAR_EMPTY - BAR_FULL), r.phase);
          if (w.kind == 0) tma_ld3_w(sbase + r.slot * SLOT, m, 0, ks * 64, w.sub * 2, bar, 16384);
          else tma_ld_wo_w(sbase + r.slot * SLOT, m, w.sub * 128, (w.k0 + ks) * 2, bar);
          if (ks < 10) T2P(i, 2, ks);
          if (w.kind != 0 && ks == max(w.nsteps - GO_P, 4)) mbar_arrive_warp(sbase + BAR_GO);
          r.next(); r.next_if(b == 2);
        }
        if (w.kind == 0) {
          r.phase ^= 1; r.next(); r.next();
        } else if (w.mode == 2) {
          for (int k = 1; k <= ((d >> 5) & 3); k++) {
            if (k == 1) TTAIL(9);
            wait_count(&g_flag[w.range + 5 * k], lds(sbase + EPOCH_OFF));
            TTAIL(10);
            asm volatile("fence.proxy.async.global;" ::: "memory");
#pragma unroll 1
            for (int t = 0; t < 4; t++) {
              mbar_wait_w(sbase + BAR_EMPTY + r.slot * 8, r.phase);
              tma_ld3_w(sbase + r.slot * SLOT, &P.o_st[t == 3], 0, t * 64, NBETA * 64 + (w.range + 5 * k) * 2, sbase + BAR_FULL + r.slot * 8,
                        t == 3 ? 8192 : 16384);
              r.next();
            }
          }
        }
        mbar_wait_w(sbase + BAR_DESC, i & 1);
        d = __shfl_sync(0xffffffffu, lds(sbase + DESC_OFF + ((i + 1) & 3) * 4), 0);
      }
    } else {
      const int hi = warp - 2;
      uint64_t pol_stream;
      asm volatile("createpolicy.fractional.L2::evict_first.b64 %0, 1.0;" : "=l"(pol_stream));
      Ring r{0, 1, 3};
      uint32_t d = cta;
      for (int i = 0;; i++) {
        const Work w = decode(d);
        if (w.kind == 2) break;
        const CUtensorMap* m = w.kind == 0 ? &P.x[hi][w.beta >> 4] : &P.o_ld[hi];
        int c1 = (w.kind == 0 ? (w.beta & 15) : w.beta * 64 + w.k0) * SQ + hi * 128;
        int k_late = -1;
        if (w.kind != 0) {
          if (!hi) T3(i, 3);
          if (d >= (3u << 30)) wait_count(&g_cnt[0][w.beta], lds(sbase + EPOCH_OFF) * H_LATE);
          if (d & 128) k_late = max(2 * H_LATE - w.k0, 0);
          if (!hi) T3(i, 4);
          asm volatile("fence.proxy.async.global;" ::: "memory");
          if (!hi) T3(i, 5);
        }
        for (int ks = 0; ks < w.nsteps; ks++) {
          if (ks == k_late) {
            if (!hi) T3(i, 6);
            wait_count(&g_cnt[1][d & 31], lds(sbase + EPOCH_OFF) * (NH - H_LATE));
            asm volatile("fence.proxy.async.global;" ::: "memory");
            if (!hi) T3(i, 7);
          }
          const uint32_t b = borrow(ks, w.nsteps);
          const bool bo = b != 2;
          r.next_if(hi && !bo); r.next_if(hi && !bo);
          const uint32_t sl = bo ? NS + (b ^ (3 * hi)) : r.slot, bar = sbase + BAR_FULL + sl * 8;
          mbar_wait_w(bar + (BAR_EMPTY - BAR_FULL), bo ? (r.xp >> b) & 1 : r.phase);
          if (w.kind == 0) tma_ld2_w(sbase + sl * SLOT, m, ks * 64, c1, bar, (hi ? 96 * 128 : 128 * 128) >> (DEV_HALF & 1));
          else if (O_LD_POL) { tma_ld2_hint_w(sbase + sl * SLOT, m, 0, c1, bar, (hi ? 96 * 128 : 128 * 128) >> (DEV_HALF >> 1), pol_stream); c1 += SQ; }
          else { tma_ld2_w(sbase + sl * SLOT, m, 0, c1, bar, hi ? 96 * 128 : 128 * 128); c1 += SQ; }
          if (PF_UNITS && w.kind == 0 && i < PF_UNITS && (((i ? PF_MASK : PF_MASK0) >> ks) & 1))
            asm volatile(ELECT "cp.async.bulk.prefetch.tensor.3d.L2.global.L2::cache_hint [%0, {0, %1, 0}], %2;\n}"
                         ::"l"(&P.kv[hi][w.beta >> 4]), "r"((d & 511) * SK + 64 * (PF_J0 + __popc((i ? PF_MASK : PF_MASK0) & ((1 << ks) - 1)))), "l"(pol_stream) : "memory");
          if (ks < 10) T2P(i, 3 + hi, ks);
          if (!hi && w.kind != 0 && !(ks & 3)) TCLK(i * 16 + (ks >> 2));
          r.next(); r.next_if(!hi && !bo); r.next_if(!hi && !bo);
          r.xp ^= 1 << b;
        }
        r.xp ^= 3;
        if (w.kind == 0) {
          m = &P.kv[hi][w.beta >> 4];
          c1 = (d & 511) * SK;
          for (int j = 0; j < 16; j++) {
            if (hi) r.next();
            const uint32_t bar = sbase + BAR_FULL + r.slot * 8;
            const bool tight = i < KV_WIN_UNITS && j < KV_WIN_TILES + ((KV_WIN_RAMP * ((int)d - KV_WIN_N * i)) >> 5);
            if (tight || (KV_WIN_D && j < KV_WIN_T2)) {
              const int s2 = (int)r.slot - (tight ? 2 : KV_WIN_D);
              mbar_wait_w(sbase + BAR_FULL + (s2 < 0 ? s2 + NS : s2) * 8, s2 < 0 ? r.phase : r.phase ^ 1);
            }
            if (j == 15 && hi) mbar_wait_w(sbase + BAR_DESC, i & 1);
            mbar_wait_w(sbase + BAR_EMPTY + r.slot * 8, r.phase);
            tma_ld3_hint_w(sbase + r.slot * SLOT, m, 0, c1, 0, bar, pol_stream);
            T2P(i, 3 + hi, 16 + j);
            if (!hi) TCLK(i * 16 + j);
            if (j == 14 && !hi) mbar_arrive_warp(sbase + BAR_GO);
            if (PF_X && j == PF_XJ && (d & 31) < 10 && d + PF_X * 32 < 1024)
              asm volatile(ELECT "cp.async.bulk.prefetch.tensor.2d.L2.global [%0, {%1, %2}];\n}"
                           ::"l"(&P.x[hi][(d + PF_X * 32) >> 9]), "r"((d & 31) * 64), "r"((((d >> 5) + PF_X) & 15) * SQ + hi * 128) : "memory");
            if (PF_W && j < 5 && (d >> 5) == PF_W)
              asm volatile(ELECT "cp.async.bulk.prefetch.tensor.3d.L2.global [%0, {0, %1, %2}];\n}"
                           ::"l"(&P.wq[1]), "r"((j * 2 + hi) * 64), "r"((d & 31) * 2) : "memory");
            c1 += 64;
            r.next();
            if (!hi) r.next();
          }
        }
        mbar_wait_w(sbase + BAR_DESC, i & 1);
        d = __shfl_sync(0xffffffffu, lds(sbase + DESC_OFF + ((i + 1) & 3) * 4), 0);
      }
    }
  } else {
    asm volatile("setmaxnreg.inc.sync.aligned.u32 %0;" ::"n"(REG_C));
    Ctx c;
    c.sb = sbase; c.wg = wg; c.warp = warp; c.src = 0; c.mqk = 0; c.mpv = 0; c.lead = lane == 0;
    if (wg == 0) consumer<0>(c, P.kp); else consumer<1>(c, P.kp);
  }
}

typedef CUresult (*EncodeFn)(CUtensorMap*, CUtensorMapDataType, cuuint32_t, void*, const cuuint64_t*, const cuuint64_t*,
                             const cuuint32_t*, const cuuint32_t*, CUtensorMapInterleave, CUtensorMapSwizzle,
                             CUtensorMapL2promotion, CUtensorMapFloatOOBfill);

void make_map(EncodeFn enc, CUtensorMap* m, const void* ptr, int rank, const cuuint64_t* dims, const cuuint64_t* strides,
              const cuuint32_t* box, int promo = 2, CUtensorMapSwizzle swz = CU_TENSOR_MAP_SWIZZLE_128B) {
  cuuint32_t es[5] = {1, 1, 1, 1, 1};
  enc(m, CU_TENSOR_MAP_DATA_TYPE_BFLOAT16, rank, const_cast<void*>(ptr), dims, strides, box, es,
      CU_TENSOR_MAP_INTERLEAVE_NONE, swz, promo == 2 ? CU_TENSOR_MAP_L2_PROMOTION_L2_256B : promo == 1 ? CU_TENSOR_MAP_L2_PROMOTION_L2_128B : CU_TENSOR_MAP_L2_PROMOTION_NONE,
      CU_TENSOR_MAP_FLOAT_OOB_FILL_NONE);
}

}

extern "C" void kernel_launch(void* const* d_in, const int* in_sizes, int n_in, void* d_out, int out_size) {
  (void)in_sizes; (void)n_in; (void)out_size;
  static EncodeFn enc = nullptr;
  static void* o_ptr = nullptr;
  static int n_sm = 0;
  if (!enc) {
    void* fn = nullptr;
    cudaDriverEntryPointQueryResult qr;
    cudaGetDriverEntryPoint("cuTensorMapEncodeTiled", &fn, cudaEnableDefault, &qr);
    enc = (EncodeFn)fn;
    cudaGetSymbolAddress(&o_ptr, g_o);
    cudaFuncSetAttribute(mha_fused_kernel<false>, cudaFuncAttributeMaxDynamicSharedMemorySize, SMEM_BYTES);
    cudaFuncSetAttribute(mha_fused_kernel<true>, cudaFuncAttributeMaxDynamicSharedMemorySize, SMEM_BYTES);
    int dev = 0;
    cudaGetDevice(&dev);
    cudaDeviceGetAttribute(&n_sm, cudaDevAttrMultiProcessorCount, dev);
  }
  Params P;
  for (int br = 0; br < 2; br++) {
    const void* x = d_in[br * 5 + 0]; const void* kc = d_in[br * 5 + 1]; const void* vc = d_in[br * 5 + 2];
    const void* wq = d_in[br * 5 + 3]; const void* wo = d_in[br * 5 + 4];
    { cuuint64_t d[2] = {DM, (cuuint64_t)NB * SQ}, s[1] = {DM * 2}; cuuint32_t b[2] = {64, 128 >> (DEV_HALF & 1)}, b2[2] = {64, 96 >> (DEV_HALF & 1)};
      make_map(enc, &P.x[0][br], x, 2, d, s, b, PR_X); make_map(enc, &P.x[1][br], x, 2, d, s, b2, PR_X); }
    { cuuint64_t d[3] = {64, DM, HD / 64}, s[2] = {HD * 2, 128}; cuuint32_t b[3] = {64, 64, 2}; make_map(enc, &P.wq[br], wq, 3, d, s, b, PR_W); }
    { cuuint64_t d[5] = {DM, 2, 4, 4, HD / 32}, s[4] = {DM * 2, 8 * DM * 2, 2 * DM * 2, 32 * DM * 2}; cuuint32_t b[5] = {64, 2, 4, 4, 2};
      make_map(enc, &P.wo[br], wo, 5, d, s, b, PR_W); }
    { cuuint64_t d[3] = {64, (cuuint64_t)NB * NH * SK, 2}, s[2] = {DH * 2, 128}; cuuint32_t b[3] = {64, 64, 2};
      make_map(enc, &P.kv[0][br], kc, 3, d, s, b, PR_KV); make_map(enc, &P.kv[1][br], vc, 3, d, s, b, PR_KV); }
    P.kp[br] = (const __nv_bfloat16*)kc; P.vp[br] = (const __nv_bfloat16*)vc;

  }
  { cuuint64_t d[2] = {64, (cuuint64_t)NBETA * 64 * SQ}, s[1] = {128}; cuuint32_t b[2] = {64, 128 >> (DEV_HALF >> 1)}, b2[2] = {64, 96 >> (DEV_HALF >> 1)};
    make_map(enc, &P.o_ld[0], o_ptr, 2, d, s, b, 2, CU_TENSOR_MAP_SWIZZLE_NONE); make_map(enc, &P.o_ld[1], o_ptr, 2, d, s, b2, 2, CU_TENSOR_MAP_SWIZZLE_NONE); }
  { cuuint64_t d[3] = {64, SQ, O_BLOCKS}, s[2] = {128, SQ * 128}; cuuint32_t b[3] = {64, 64, 2}, b2[3] = {64, 32, 2};
    make_map(enc, &P.o_st[0], o_ptr, 3, d, s, b); make_map(enc, &P.o_st[1], o_ptr, 3, d, s, b2); }
  { cuuint64_t d[3] = {64, (cuuint64_t)NB * SQ, 2 * DM / 64}, s[2] = {2 * DM * 2, 128}; cuuint32_t b[3] = {64, 64, 2}, b2[3] = {64, 32, 2};
    make_map(enc, &P.out_st[0], d_out, 3, d, s, b); make_map(enc, &P.out_st[1], d_out, 3, d, s, b2); }
  if (n_sm >= NCTA) mha_fused_kernel<false><<<NCTA, 384, SMEM_BYTES>>>(P);
  else mha_fused_kernel<true><<<n_sm, 384, SMEM_BYTES>>>(P);
}
```

```cpp
#include <cuda_runtime.h>
#include <cuda_bf16.h>
#include <cuda.h>
#include <stdint.h>
#include <stdlib.h>

namespace {

__device__ __forceinline__ void wgmma_proj(float (&d)[64], uint64_t da, uint64_t db, int scaleD) {
  asm volatile("{\n.reg .pred p;\nsetp.ne.b32 p, %66, 0;\n"
      "wgmma.mma_async.sync.aligned.m64n128k16.f32.bf16.bf16 "
      "{%0, %1, %2, %3, %4, %5, %6, %7, %8, %9, %10, %11, %12, %13, %14, %15, %16, %17, %18, %19, %20, %21, %22, %23, %24, %25, %26, %27, %28, %29, %30, "
      "%31, %32, %33, %34, %35, %36, %37, %38, %39, %40, %41, %42, %43, %44, %45, %46, %47, %48, %49, %50, %51, %52, %53, %54, %55, %56, %57, %58, %59, %60, "
      "%61, %62, %63}, "
      "%64, %65, p, 1, 1, 0, 1;\n}\n"
      : "+f"(d[0]), "+f"(d[1]), "+f"(d[2]), "+f"(d[3]), "+f"(d[4]), "+f"(d[5]), "+f"(d[6]), "+f"(d[7]), "+f"(d[8]), "+f"(d[9]), "+f"(d[10]), "+f"(d[11]),
        "+f"(d[12]), "+f"(d[13]), "+f"(d[14]), "+f"(d[15]), "+f"(d[16]), "+f"(d[17]), "+f"(d[18]), "+f"(d[19]), "+f"(d[20]), "+f"(d[21]), "+f"(d[22]),
        "+f"(d[23]), "+f"(d[24]), "+f"(d[25]), "+f"(d[26]), "+f"(d[27]), "+f"(d[28]), "+f"(d[29]), "+f"(d[30]), "+f"(d[31]), "+f"(d[32]), "+f"(d[33]),
        "+f"(d[34]), "+f"(d[35]), "+f"(d[36]), "+f"(d[37]), "+f"(d[38]), "+f"(d[39]), "+f"(d[40]), "+f"(d[41]), "+f"(d[42]), "+f"(d[43]), "+f"(d[44]),
        "+f"(d[45]), "+f"(d[46]), "+f"(d[47]), "+f"(d[48]), "+f"(d[49]), "+f"(d[50]), "+f"(d[51]), "+f"(d[52]), "+f"(d[53]), "+f"(d[54]), "+f"(d[55]),
        "+f"(d[56]), "+f"(d[57]), "+f"(d[58]), "+f"(d[59]), "+f"(d[60]), "+f"(d[61]), "+f"(d[62]), "+f"(d[63])
      : "l"(da), "l"(db), "r"(scaleD));
}
__device__ __forceinline__ void wgmma_proj96(float (&d)[64], uint64_t da, uint64_t db, int scaleD) {
  asm volatile("{\n.reg .pred p;\nsetp.ne.b32 p, %50, 0;\n"
      "wgmma.mma_async.sync.aligned.m64n96k16.f32.bf16.bf16 "
      "{%0, %1, %2, %3, %4, %5, %6, %7, %8, %9, %10, %11, %12, %13, %14, %15, %16, %17, %18, %19, %20, %21, %22, %23, %24, %25, %26, %27, %28, %29, %30, "
      "%31, %32, %33, %34, %35, %36, %37, %38, %39, %40, %41, %42, %43, %44, %45, %46, %47}, "
      "%48, %49, p, 1, 1, 1, 0;\n}\n"
      : "+f"(d[0]), "+f"(d[1]), "+f"(d[2]), "+f"(d[3]), "+f"(d[4]), "+f"(d[5]), "+f"(d[6]), "+f"(d[7]), "+f"(d[8]), "+f"(d[9]), "+f"(d[10]), "+f"(d[11]),
        "+f"(d[12]), "+f"(d[13]), "+f"(d[14]), "+f"(d[15]), "+f"(d[16]), "+f"(d[17]), "+f"(d[18]), "+f"(d[19]), "+f"(d[20]), "+f"(d[21]), "+f"(d[22]),
        "+f"(d[23]), "+f"(d[24]), "+f"(d[25]), "+f"(d[26]), "+f"(d[27]), "+f"(d[28]), "+f"(d[29]), "+f"(d[30]), "+f"(d[31]), "+f"(d[32]), "+f"(d[33]),
        "+f"(d[34]), "+f"(d[35]), "+f"(d[36]), "+f"(d[37]), "+f"(d[38]), "+f"(d[39]), "+f"(d[40]), "+f"(d[41]), "+f"(d[42]), "+f"(d[43]), "+f"(d[44]),
        "+f"(d[45]), "+f"(d[46]), "+f"(d[47])
      : "l"(da), "l"(db), "r"(scaleD));
}
__device__ __forceinline__ void wgmma_qk(float (&d)[32], uint64_t da, uint64_t db, int scaleD) {
  asm volatile("{\n.reg .pred p;\nsetp.ne.b32 p, %34, 0;\n"
      "wgmma.mma_async.sync.aligned.m64n64k16.f32.bf16.bf16 "
      "{%0, %1, %2, %3, %4, %5, %6, %7, %8, %9, %10, %11, %12, %13, %14, %15, %16, %17, %18, %19, %20, %21, %22, %23, %24, %25, %26, %27, %28, %29, %30, "
      "%31}, "
      "%32, %33, p, 1, 1, 0, 0;\n}\n"
      : "+f"(d[0]), "+f"(d[1]), "+f"(d[2]), "+f"(d[3]), "+f"(d[4]), "+f"(d[5]), "+f"(d[6]), "+f"(d[7]), "+f"(d[8]), "+f"(d[9]), "+f"(d[10]), "+f"(d[11]),
        "+f"(d[12]), "+f"(d[13]), "+f"(d[14]), "+f"(d[15]), "+f"(d[16]), "+f"(d[17]), "+f"(d[18]), "+f"(d[19]), "+f"(d[20]), "+f"(d[21]), "+f"(d[22]),
        "+f"(d[23]), "+f"(d[24]), "+f"(d[25]), "+f"(d[26]), "+f"(d[27]), "+f"(d[28]), "+f"(d[29]), "+f"(d[30]), "+f"(d[31])
      : "l"(da), "l"(db), "r"(scaleD));
}
__device__ __forceinline__ void wgmma_qk_rs(float (&d)[32], uint32_t a0, uint32_t a1, uint32_t a2, uint32_t a3, uint64_t db, int scaleD) {
  asm volatile("{\n.reg .pred p;\nsetp.ne.b32 p, %37, 0;\n"
      "wgmma.mma_async.sync.aligned.m64n64k16.f32.bf16.bf16 "
      "{%0, %1, %2, %3, %4, %5, %6, %7, %8, %9, %10, %11, %12, %13, %14, %15, %16, %17, %18, %19, %20, %21, %22, %23, %24, %25, %26, %27, %28, %29, %30, "
      "%31}, "
      "{%32, %33, %34, %35}, %36, p, 1, 1, 0;\n}\n"
      : "+f"(d[0]), "+f"(d[1]), "+f"(d[2]), "+f"(d[3]), "+f"(d[4]), "+f"(d[5]), "+f"(d[6]), "+f"(d[7]), "+f"(d[8]), "+f"(d[9]), "+f"(d[10]), "+f"(d[11]),
        "+f"(d[12]), "+f"(d[13]), "+f"(d[14]), "+f"(d[15]), "+f"(d[16]), "+f"(d[17]), "+f"(d[18]), "+f"(d[19]), "+f"(d[20]), "+f"(d[21]), "+f"(d[22]),
        "+f"(d[23]), "+f"(d[24]), "+f"(d[25]), "+f"(d[26]), "+f"(d[27]), "+f"(d[28]), "+f"(d[29]), "+f"(d[30]), "+f"(d[31])
      : "r"(a0), "r"(a1), "r"(a2), "r"(a3), "l"(db), "r"(scaleD));
}
__device__ __forceinline__ void wgmma_pv(float (&d)[64], uint32_t a0, uint32_t a1, uint32_t a2, uint32_t a3, uint64_t db, int scaleD) {
  asm volatile("{\n.reg .pred p;\nsetp.ne.b32 p, %69, 0;\n"
      "wgmma.mma_async.sync.aligned.m64n128k16.f32.bf16.bf16 "
      "{%0, %1, %2, %3, %4, %5, %6, %7, %8, %9, %10, %11, %12, %13, %14, %15, %16, %17, %18, %19, %20, %21, %22, %23, %24, %25, %26, %27, %28, %29, %30, "
      "%31, %32, %33, %34, %35, %36, %37, %38, %39, %40, %41, %42, %43, %44, %45, %46, %47, %48, %49, %50, %51, %52, %53, %54, %55, %56, %57, %58, %59, %60, "
      "%61, %62, %63}, "
      "{%64, %65, %66, %67}, %68, p, 1, 1, 1;\n}\n"
      : "+f"(d[0]), "+f"(d[1]), "+f"(d[2]), "+f"(d[3]), "+f"(d[4]), "+f"(d[5]), "+f"(d[6]), "+f"(d[7]), "+f"(d[8]), "+f"(d[9]), "+f"(d[10]), "+f"(d[11]),
        "+f"(d[12]), "+f"(d[13]), "+f"(d[14]), "+f"(d[15]), "+f"(d[16]), "+f"(d[17]), "+f"(d[18]), "+f"(d[19]), "+f"(d[20]), "+f"(d[21]), "+f"(d[22]),
        "+f"(d[23]), "+f"(d[24]), "+f"(d[25]), "+f"(d[26]), "+f"(d[27]), "+f"(d[28]), "+f"(d[29]), "+f"(d[30]), "+f"(d[31]), "+f"(d[32]), "+f"(d[33]),
        "+f"(d[34]), "+f"(d[35]), "+f"(d[36]), "+f"(d[37]), "+f"(d[38]), "+f"(d[39]), "+f"(d[40]), "+f"(d[41]), "+f"(d[42]), "+f"(d[43]), "+f"(d[44]),
        "+f"(d[45]), "+f"(d[46]), "+f"(d[47]), "+f"(d[48]), "+f"(d[49]), "+f"(d[50]), "+f"(d[51]), "+f"(d[52]), "+f"(d[53]), "+f"(d[54]), "+f"(d[55]),
        "+f"(d[56]), "+f"(d[57]), "+f"(d[58]), "+f"(d[59]), "+f"(d[60]), "+f"(d[61]), "+f"(d[62]), "+f"(d[63])
      : "r"(a0), "r"(a1), "r"(a2), "r"(a3), "l"(db), "r"(scaleD));
}
__device__ __forceinline__ void wgmma_qk_sp(float (&d)[32], uint32_t a0, uint32_t a1, uint32_t a2, uint32_t a3, uint64_t db, int scaleD, uint32_t meta) {
  asm volatile("{\n.reg .pred p;\nsetp.ne.b32 p, %37, 0;\n"
      "wgmma.mma_async.sp.sync.aligned.m64n64k32.f32.bf16.bf16 "
      "{%0, %1, %2, %3, %4, %5, %6, %7, %8, %9, %10, %11, %12, %13, %14, %15, %16, %17, %18, %19, %20, %21, %22, %23, %24, %25, %26, %27, %28, %29, %30, "
      "%31}, "
      "{%32, %33, %34, %35}, %36, %38, 0, p, 1, 1, 0;\n}\n"
      : "+f"(d[0]), "+f"(d[1]), "+f"(d[2]), "+f"(d[3]), "+f"(d[4]), "+f"(d[5]), "+f"(d[6]), "+f"(d[7]), "+f"(d[8]), "+f"(d[9]), "+f"(d[10]), "+f"(d[11]),
        "+f"(d[12]), "+f"(d[13]), "+f"(d[14]), "+f"(d[15]), "+f"(d[16]), "+f"(d[17]), "+f"(d[18]), "+f"(d[19]), "+f"(d[20]), "+f"(d[21]), "+f"(d[22]),
        "+f"(d[23]), "+f"(d[24]), "+f"(d[25]), "+f"(d[26]), "+f"(d[27]), "+f"(d[28]), "+f"(d[29]), "+f"(d[30]), "+f"(d[31])
      : "r"(a0), "r"(a1), "r"(a2), "r"(a3), "l"(db), "r"(scaleD), "r"(meta));
}
__device__ __forceinline__ void wgmma_pv_sp(float (&d)[64], uint32_t a0, uint32_t a1, uint32_t a2, uint32_t a3, uint64_t db, int scaleD, uint32_t meta) {
  asm volatile("{\n.reg .pred p;\nsetp.ne.b32 p, %69, 0;\n"
      "wgmma.mma_async.sp.sync.aligned.m64n128k32.f32.bf16.bf16 "
      "{%0, %1, %2, %3, %4, %5, %6, %7, %8, %9, %10, %11, %12, %13, %14, %15, %16, %17, %18, %19, %20, %21, %22, %23, %24, %25, %26, %27, %28, %29, %30, "
      "%31, %32, %33, %34, %35, %36, %37, %38, %39, %40, %41, %42, %43, %44, %45, %46, %47, %48, %49, %50, %51, %52, %53, %54, %55, %56, %57, %58, %59, %60, "
      "%61, %62, %63}, "
      "{%64, %65, %66, %67}, %68, %70, 0, p, 1, 1, 1;\n}\n"
      : "+f"(d[0]), "+f"(d[1]), "+f"(d[2]), "+f"(d[3]), "+f"(d[4]), "+f"(d[5]), "+f"(d[6]), "+f"(d[7]), "+f"(d[8]), "+f"(d[9]), "+f"(d[10]), "+f"(d[11]),
        "+f"(d[12]), "+f"(d[13]), "+f"(d[14]), "+f"(d[15]), "+f"(d[16]), "+f"(d[17]), "+f"(d[18]), "+f"(d[19]), "+f"(d[20]), "+f"(d[21]), "+f"(d[22]),
        "+f"(d[23]), "+f"(d[24]), "+f"(d[25]), "+f"(d[26]), "+f"(d[27]), "+f"(d[28]), "+f"(d[29]), "+f"(d[30]), "+f"(d[31]), "+f"(d[32]), "+f"(d[33]),
        "+f"(d[34]), "+f"(d[35]), "+f"(d[36]), "+f"(d[37]), "+f"(d[38]), "+f"(d[39]), "+f"(d[40]), "+f"(d[41]), "+f"(d[42]), "+f"(d[43]), "+f"(d[44]),
        "+f"(d[45]), "+f"(d[46]), "+f"(d[47]), "+f"(d[48]), "+f"(d[49]), "+f"(d[50]), "+f"(d[51]), "+f"(d[52]), "+f"(d[53]), "+f"(d[54]), "+f"(d[55]),
        "+f"(d[56]), "+f"(d[57]), "+f"(d[58]), "+f"(d[59]), "+f"(d[60]), "+f"(d[61]), "+f"(d[62]), "+f"(d[63])
      : "r"(a0), "r"(a1), "r"(a2), "r"(a3), "l"(db), "r"(scaleD), "r"(meta));
}
__device__ __forceinline__ void wgmma_proj_init(float (&d)[64], uint64_t da, uint64_t db, int scaleD) {
  asm volatile("{\n.reg .pred p;\nsetp.ne.b32 p, %66, 0;\n"
      "wgmma.mma_async.sync.aligned.m64n128k16.f32.bf16.bf16 "
      "{%0, %1, %2, %3, %4, %5, %6, %7, %8, %9, %10, %11, %12, %13, %14, %15, %16, %17, %18, %19, %20, %21, %22, %23, %24, %25, %26, %27, %28, %29, %30, "
      "%31, %32, %33, %34, %35, %36, %37, %38, %39, %40, %41, %42, %43, %44, %45, %46, %47, %48, %49, %50, %51, %52, %53, %54, %55, %56, %57, %58, %59, %60, "
      "%61, %62, %63}, "
      "%64, %65, p, 1, 1, 0, 1;\n}\n"
      : "=f"(d[0]), "=f"(d[1]), "=f"(d[2]), "=f"(d[3]), "=f"(d[4]), "=f"(d[5]), "=f"(d[6]), "=f"(d[7]), "=f"(d[8]), "=f"(d[9]), "=f"(d[10]), "=f"(d[11]),
        "=f"(d[12]), "=f"(d[13]), "=f"(d[14]), "=f"(d[15]), "=f"(d[16]), "=f"(d[17]), "=f"(d[18]), "=f"(d[19]), "=f"(d[20]), "=f"(d[21]), "=f"(d[22]),
        "=f"(d[23]), "=f"(d[24]), "=f"(d[25]), "=f"(d[26]), "=f"(d[27]), "=f"(d[28]), "=f"(d[29]), "=f"(d[30]), "=f"(d[31]), "=f"(d[32]), "=f"(d[33]),
        "=f"(d[34]), "=f"(d[35]), "=f"(d[36]), "=f"(d[37]), "=f"(d[38]), "=f"(d[39]), "=f"(d[40]), "=f"(d[41]), "=f"(d[42]), "=f"(d[43]), "=f"(d[44]),
        "=f"(d[45]), "=f"(d[46]), "=f"(d[47]), "=f"(d[48]), "=f"(d[49]), "=f"(d[50]), "=f"(d[51]), "=f"(d[52]), "=f"(d[53]), "=f"(d[54]), "=f"(d[55]),
        "=f"(d[56]), "=f"(d[57]), "=f"(d[58]), "=f"(d[59]), "=f"(d[60]), "=f"(d[61]), "=f"(d[62]), "=f"(d[63])
      : "l"(da), "l"(db), "r"(scaleD));
}
__device__ __forceinline__ void wgmma_proj96_init(float (&d)[64], uint64_t da, uint64_t db, int scaleD) {
  asm volatile("{\n.reg .pred p;\nsetp.ne.b32 p, %50, 0;\n"
      "wgmma.mma_async.sync.aligned.m64n96k16.f32.bf16.bf16 "
      "{%0, %1, %2, %3, %4, %5, %6, %7, %8, %9, %10, %11, %12, %13, %14, %15, %16, %17, %18, %19, %20, %21, %22, %23, %24, %25, %26, %27, %28, %29, %30, "
      "%31, %32, %33, %34, %35, %36, %37, %38, %39, %40, %41, %42, %43, %44, %45, %46, %47}, "
      "%48, %49, p, 1, 1, 1, 0;\n}\n"
      : "=f"(d[0]), "=f"(d[1]), "=f"(d[2]), "=f"(d[3]), "=f"(d[4]), "=f"(d[5]), "=f"(d[6]), "=f"(d[7]), "=f"(d[8]), "=f"(d[9]), "=f"(d[10]), "=f"(d[11]),
        "=f"(d[12]), "=f"(d[13]), "=f"(d[14]), "=f"(d[15]), "=f"(d[16]), "=f"(d[17]), "=f"(d[18]), "=f"(d[19]), "=f"(d[20]), "=f"(d[21]), "=f"(d[22]),
        "=f"(d[23]), "=f"(d[24]), "=f"(d[25]), "=f"(d[26]), "=f"(d[27]), "=f"(d[28]), "=f"(d[29]), "=f"(d[30]), "=f"(d[31]), "=f"(d[32]), "=f"(d[33]),
        "=f"(d[34]), "=f"(d[35]), "=f"(d[36]), "=f"(d[37]), "=f"(d[38]), "=f"(d[39]), "=f"(d[40]), "=f"(d[41]), "=f"(d[42]), "=f"(d[43]), "=f"(d[44]),
        "=f"(d[45]), "=f"(d[46]), "=f"(d[47])
      : "l"(da), "l"(db), "r"(scaleD));
}
__device__ __forceinline__ void wgmma_qk_init(float (&d)[32], uint64_t da, uint64_t db, int scaleD) {
  asm volatile("{\n.reg .pred p;\nsetp.ne.b32 p, %34, 0;\n"
      "wgmma.mma_async.sync.aligned.m64n64k16.f32.bf16.bf16 "
      "{%0, %1, %2, %3, %4, %5, %6, %7, %8, %9, %10, %11, %12, %13, %14, %15, %16, %17, %18, %19, %20, %21, %22, %23, %24, %25, %26, %27, %28, %29, %30, "
      "%31}, "
      "%32, %33, p, 1, 1, 0, 0;\n}\n"
      : "=f"(d[0]), "=f"(d[1]), "=f"(d[2]), "=f"(d[3]), "=f"(d[4]), "=f"(d[5]), "=f"(d[6]), "=f"(d[7]), "=f"(d[8]), "=f"(d[9]), "=f"(d[10]), "=f"(d[11]),
        "=f"(d[12]), "=f"(d[13]), "=f"(d[14]), "=f"(d[15]), "=f"(d[16]), "=f"(d[17]), "=f"(d[18]), "=f"(d[19]), "=f"(d[20]), "=f"(d[21]), "=f"(d[22]),
        "=f"(d[23]), "=f"(d[24]), "=f"(d[25]), "=f"(d[26]), "=f"(d[27]), "=f"(d[28]), "=f"(d[29]), "=f"(d[30]), "=f"(d[31])
      : "l"(da), "l"(db), "r"(scaleD));
}
__device__ __forceinline__ void wgmma_qk_rs_init(float (&d)[32], uint32_t a0, uint32_t a1, uint32_t a2, uint32_t a3, uint64_t db, int scaleD) {
  asm volatile("{\n.reg .pred p;\nsetp.ne.b32 p, %37, 0;\n"
      "wgmma.mma_async.sync.aligned.m64n64k16.f32.bf16.bf16 "
      "{%0, %1, %2, %3, %4, %5, %6, %7, %8, %9, %10, %11, %12, %13, %14, %15, %16, %17, %18, %19, %20, %21, %22, %23, %24, %25, %26, %27, %28, %29, %30, "
      "%31}, "
      "{%32, %33, %34, %35}, %36, p, 1, 1, 0;\n}\n"
      : "=f"(d[0]), "=f"(d[1]), "=f"(d[2]), "=f"(d[3]), "=f"(d[4]), "=f"(d[5]), "=f"(d[6]), "=f"(d[7]), "=f"(d[8]), "=f"(d[9]), "=f"(d[10]), "=f"(d[11]),
        "=f"(d[12]), "=f"(d[13]), "=f"(d[14]), "=f"(d[15]), "=f"(d[16]), "=f"(d[17]), "=f"(d[18]), "=f"(d[19]), "=f"(d[20]), "=f"(d[21]), "=f"(d[22]),
        "=f"(d[23]), "=f"(d[24]), "=f"(d[25]), "=f"(d[26]), "=f"(d[27]), "=f"(d[28]), "=f"(d[29]), "=f"(d[30]), "=f"(d[31])
      : "r"(a0), "r"(a1), "r"(a2), "r"(a3), "l"(db), "r"(scaleD));
}
__device__ __forceinline__ void wgmma_pv_init(float (&d)[64], uint32_t a0, uint32_t a1, uint32_t a2, uint32_t a3, uint64_t db, int scaleD) {
  asm volatile("{\n.reg .pred p;\nsetp.ne.b32 p, %69, 0;\n"
      "wgmma.mma_async.sync.aligned.m64n128k16.f32.bf16.bf16 "
      "{%0, %1, %2, %3, %4, %5, %6, %7, %8, %9, %10, %11, %12, %13, %14, %15, %16, %17, %18, %19, %20, %21, %22, %23, %24, %25, %26, %27, %28, %29, %30, "
      "%31, %32, %33, %34, %35, %36, %37, %38, %39, %40, %41, %42, %43, %44, %45, %46, %47, %48, %49, %50, %51, %52, %53, %54, %55, %56, %57, %58, %59, %60, "
      "%61, %62, %63}, "
      "{%64, %65, %66, %67}, %68, p, 1, 1, 1;\n}\n"
      : "=f"(d[0]), "=f"(d[1]), "=f"(d[2]), "=f"(d[3]), "=f"(d[4]), "=f"(d[5]), "=f"(d[6]), "=f"(d[7]), "=f"(d[8]), "=f"(d[9]), "=f"(d[10]), "=f"(d[11]),
        "=f"(d[12]), "=f"(d[13]), "=f"(d[14]), "=f"(d[15]), "=f"(d[16]), "=f"(d[17]), "=f"(d[18]), "=f"(d[19]), "=f"(d[20]), "=f"(d[21]), "=f"(d[22]),
        "=f"(d[23]), "=f"(d[24]), "=f"(d[25]), "=f"(d[26]), "=f"(d[27]), "=f"(d[28]), "=f"(d[29]), "=f"(d[30]), "=f"(d[31]), "=f"(d[32]), "=f"(d[33]),
        "=f"(d[34]), "=f"(d[35]), "=f"(d[36]), "=f"(d[37]), "=f"(d[38]), "=f"(d[39]), "=f"(d[40]), "=f"(d[41]), "=f"(d[42]), "=f"(d[43]), "=f"(d[44]),
        "=f"(d[45]), "=f"(d[46]), "=f"(d[47]), "=f"(d[48]), "=f"(d[49]), "=f"(d[50]), "=f"(d[51]), "=f"(d[52]), "=f"(d[53]), "=f"(d[54]), "=f"(d[55]),
        "=f"(d[56]), "=f"(d[57]), "=f"(d[58]), "=f"(d[59]), "=f"(d[60]), "=f"(d[61]), "=f"(d[62]), "=f"(d[63])
      : "r"(a0), "r"(a1), "r"(a2), "r"(a3), "l"(db), "r"(scaleD));
}
__device__ __forceinline__ void wgmma_qk_sp_init(float (&d)[32], uint32_t a0, uint32_t a1, uint32_t a2, uint32_t a3, uint64_t db, int scaleD, uint32_t meta) {
  asm volatile("{\n.reg .pred p;\nsetp.ne.b32 p, %37, 0;\n"
      "wgmma.mma_async.sp.sync.aligned.m64n64k32.f32.bf16.bf16 "
      "{%0, %1, %2, %3, %4, %5, %6, %7, %8, %9, %10, %11, %12, %13, %14, %15, %16, %17, %18, %19, %20, %21, %22, %23, %24, %25, %26, %27, %28, %29, %30, "
      "%31}, "
      "{%32, %33, %34, %35}, %36, %38, 0, p, 1, 1, 0;\n}\n"
      : "=f"(d[0]), "=f"(d[1]), "=f"(d[2]), "=f"(d[3]), "=f"(d[4]), "=f"(d[5]), "=f"(d[6]), "=f"(d[7]), "=f"(d[8]), "=f"(d[9]), "=f"(d[10]), "=f"(d[11]),
        "=f"(d[12]), "=f"(d[13]), "=f"(d[14]), "=f"(d[15]), "=f"(d[16]), "=f"(d[17]), "=f"(d[18]), "=f"(d[19]), "=f"(d[20]), "=f"(d[21]), "=f"(d[22]),
        "=f"(d[23]), "=f"(d[24]), "=f"(d[25]), "=f"(d[26]), "=f"(d[27]), "=f"(d[28]), "=f"(d[29]), "=f"(d[30]), "=f"(d[31])
      : "r"(a0), "r"(a1), "r"(a2), "r"(a3), "l"(db), "r"(scaleD), "r"(meta));
}
__device__ __forceinline__ void wgmma_pv_sp_init(float (&d)[64], uint32_t a0, uint32_t a1, uint32_t a2, uint32_t a3, uint64_t db, int scaleD, uint32_t meta) {
  asm volatile("{\n.reg .pred p;\nsetp.ne.b32 p, %69, 0;\n"
      "wgmma.mma_async.sp.sync.aligned.m64n128k32.f32.bf16.bf16 "
      "{%0, %1, %2, %3, %4, %5, %6, %7, %8, %9, %10, %11, %12, %13, %14, %15, %16, %17, %18, %19, %20, %21, %22, %23, %24, %25, %26, %27, %28, %29, %30, "
      "%31, %32, %33, %34, %35, %36, %37, %38, %39, %40, %41, %42, %43, %44, %45, %46, %47, %48, %49, %50, %51, %52, %53, %54, %55, %56, %57, %58, %59, %60, "
      "%61, %62, %63}, "
      "{%64, %65, %66, %67}, %68, %70, 0, p, 1, 1, 1;\n}\n"
      : "=f"(d[0]), "=f"(d[1]), "=f"(d[2]), "=f"(d[3]), "=f"(d[4]), "=f"(d[5]), "=f"(d[6]), "=f"(d[7]), "=f"(d[8]), "=f"(d[9]), "=f"(d[10]), "=f"(d[11]),
        "=f"(d[12]), "=f"(d[13]), "=f"(d[14]), "=f"(d[15]), "=f"(d[16]), "=f"(d[17]), "=f"(d[18]), "=f"(d[19]), "=f"(d[20]), "=f"(d[21]), "=f"(d[22]),
        "=f"(d[23]), "=f"(d[24]), "=f"(d[25]), "=f"(d[26]), "=f"(d[27]), "=f"(d[28]), "=f"(d[29]), "=f"(d[30]), "=f"(d[31]), "=f"(d[32]), "=f"(d[33]),
        "=f"(d[34]), "=f"(d[35]), "=f"(d[36]), "=f"(d[37]), "=f"(d[38]), "=f"(d[39]), "=f"(d[40]), "=f"(d[41]), "=f"(d[42]), "=f"(d[43]), "=f"(d[44]),
        "=f"(d[45]), "=f"(d[46]), "=f"(d[47]), "=f"(d[48]), "=f"(d[49]), "=f"(d[50]), "=f"(d[51]), "=f"(d[52]), "=f"(d[53]), "=f"(d[54]), "=f"(d[55]),
        "=f"(d[56]), "=f"(d[57]), "=f"(d[58]), "=f"(d[59]), "=f"(d[60]), "=f"(d[61]), "=f"(d[62]), "=f"(d[63])
      : "r"(a0), "r"(a1), "r"(a2), "r"(a3), "l"(db), "r"(scaleD), "r"(meta));
}

constexpr int NB = 16, SQ = 224, DM = 640, NH = 32, SK = 1024, DH = 128;
constexpr int HD = NH * DH;
constexpr int NBETA = 2 * NB;
constexpr int NCTA = 132;
constexpr int NS = 10;
constexpr int SLOT = 16384;
constexpr int QBUF_OFF = NS * SLOT;
constexpr int NSX = NS + 4;
constexpr int BAR_OFF = NSX * SLOT;
constexpr int BAR_FULL = BAR_OFF;
constexpr int BAR_EMPTY = BAR_OFF + 8 * NSX;
constexpr int BAR_STG = BAR_OFF + 16 * NSX;
constexpr int BAR_OUT = BAR_STG + 32;
constexpr int BAR_DESC = BAR_OUT + 8;
constexpr int BAR_GO = BAR_DESC + 8;
constexpr int DESC_OFF = BAR_GO + 8;
constexpr int EPOCH_OFF = DESC_OFF + 16;
constexpr int TRACE_OFF = EPOCH_OFF + 8;
constexpr int SMEM_BYTES = TRACE_OFF;
constexpr float SM_C = 0.08838834764831845f * 1.4426950408889634f;
constexpr float SUM_HI = 1099511627776.f, SUM_LO = 1.f / 1099511627776.f;
constexpr uint32_t META_QK = 0xEEEE4444u;
constexpr uint32_t META_PV = 0x44EEEE44u;

#define QK_EARLY_MASK 3
#define ST_ORDER 0x2130
#define LAG_BAR 5
#define ST_NOW 9
#define PF_UNITS 1
#define PF_MASK 0x20
#define PF_MASK0 PF_MASK
#define PF_X 0
#define PF_XJ 2
#define PF_W 0
#define KV_WIN_UNITS 2
#define KV_WIN_D 4
#define KV_WIN_T2 16
#define O_LD_POL 1
#define LAST_SYNC 0
#define RED_FIRST 2
#define PEEK 0
#define PACK_LATE 1
#define RS_STAGE 3
#define O_STEPS 4
#define TLB_WARM 0
#define DEV_HALF 0
#define DEV_IDLE 0
#define KV_WIN_RAMP 4
#define KV_WIN_N 132
#define BORROW_ALT 0
#define PF_J0 0
#define PDEPTH 0
#define EARLY_BEG 1
#define KV_WIN_TILES -2
#define PR_KV 2
#define PR_X 2
#define PR_W 2
#define REG_C 232
#define REG_P 40
#define GO_P 4
#define P_POS 224
#define B_LATE 28
#define H_LATE 24
#define EARLY_MASK 0x1fffu
#define PIECE_TABLE 0x5026401a,0x68dc4034,0x50275816,0x695a5837,0x50295015,0x6a175036,0x501e080d,0x681f083c,0x50253812,0x69d8383a,0x403f980e,0x80000000,0x5036180f,0x80000000,0x50203011,0x69993032,0x50367019,0x80000000,0x50224814,0x6a954835,0x50246017,0x6b526038,0x502c6818,0x6dc86839,0x5017b813,0x69d8b85f,0x50102810,0x685e2831,0x646e2030,0x80000000,0x501f101c,0x6dc8102f,0x5017801b,0x6c8d805e,0x6627783b,0x80000000,0x6627b033,0x80000000,0x501a901e,0x80000000,0x56d6881e,0x80000000,0x501ca81d,0x80000000,0x6762a03d,0x80000000,0x67e0002d,0x80000000,0x5512c01f,0x80000000,0x5013c81f,0x80000000

struct Params {
  CUtensorMap x[2][2], wq[2], kv[2][2], wo[2];
  CUtensorMap o_ld[2], o_st[2], out_st[2];
  const __nv_bfloat16* kp[2];
  const __nv_bfloat16* vp[2];
};

constexpr int NPART = 32 * 5, O_BLOCKS = NBETA * 64 + 2 * NPART;
__device__ __align__(128) __nv_bfloat16 g_o[(size_t)O_BLOCKS * SQ * 64];
__device__ unsigned g_cnt[2][NBETA];
__device__ unsigned g_epoch, g_next;
__device__ unsigned g_flag[NPART];

__device__ __forceinline__ uint32_t smem_u32(const void* p) { return (uint32_t)__cvta_generic_to_shared(p); }
__device__ __forceinline__ void mbar_arrive(uint32_t bar) {
  asm volatile("mbarrier.arrive.shared::cta.b64 _, [%0];" ::"r"(bar) : "memory");
}
__device__ __forceinline__ void mbar_arrive_warp(uint32_t bar) {
  asm volatile("{\n.reg .pred p;\nelect.sync _|p, 0xffffffff;\n@p mbarrier.arrive.shared::cta.b64 _, [%0];\n}" ::"r"(bar) : "memory");
}
__device__ __forceinline__ int lane_now() { int l; asm volatile("mov.u32 %0, %%laneid;" : "=r"(l)); return l; }
__device__ __forceinline__ bool mbar_try(uint32_t bar, uint32_t parity) {
  uint32_t ok;
  asm volatile("{\n.reg .pred p;\nmbarrier.try_wait.parity.shared::cta.b64 p, [%1], %2;\nselp.u32 %0, 1, 0, p;\n}"
               : "=r"(ok) : "r"(bar), "r"(parity) : "memory");
  return ok;
}
__device__ __forceinline__ bool mbar_test(uint32_t bar, uint32_t parity) {
  uint32_t ok;
  asm volatile("{\n.reg .pred p;\nmbarrier.test_wait.parity.shared::cta.b64 p, [%1], %2;\nselp.u32 %0, 1, 0, p;\n}"
               : "=r"(ok) : "r"(bar), "r"(parity) : "memory");
  return ok;
}
__device__ __forceinline__ void mbar_wait_w(uint32_t bar, uint32_t parity) {
  uint32_t n = 0;
  while (!__all_sync(0xffffffffu, mbar_try(bar, parity))) {
    if (++n > (1u << 22)) __trap();
  }
}
#define ELECT "{\n.reg .pred p;\nelect.sync _|p, 0xffffffff;\n@p "
__device__ __forceinline__ void tma_st3_hint_w(const CUtensorMap* m, uint32_t src, int c0, int c1, int c2, uint64_t pol) {
  asm volatile(ELECT "cp.async.bulk.tensor.3d.global.shared::cta.bulk_group.L2::cache_hint [%0, {%2, %3, %4}], [%1], %5;\n}"
               ::"l"(m), "r"(src), "r"(c0), "r"(c1), "r"(c2), "l"(pol) : "memory");
}
#define EXPECT(bar, bytes) "mbarrier.arrive.expect_tx.shared::cta.b64 _, [" bar "], " bytes ";\n@p "
__device__ __forceinline__ void tma_ld2_w(uint32_t dst, const CUtensorMap* m, int c0, int c1, uint32_t bar, uint32_t bytes) {
  asm volatile(ELECT EXPECT("%2", "%5") "cp.async.bulk.tensor.2d.shared::cluster.global.mbarrier::complete_tx::bytes [%0], [%1, {%3, %4}], [%2];\n}"
               ::"r"(dst), "l"(m), "r"(bar), "r"(c0), "r"(c1), "r"(bytes) : "memory");
}
__device__ __forceinline__ void tma_ld2_hint_w(uint32_t dst, const CUtensorMap* m, int c0, int c1, uint32_t bar, uint32_t bytes, uint64_t pol) {
  asm volatile(ELECT EXPECT("%2", "%6") "cp.async.bulk.tensor.2d.shared::cluster.global.mbarrier::complete_tx::bytes.L2::cache_hint"
               " [%0], [%1, {%3, %4}], [%2], %5;\n}"
               ::"r"(dst), "l"(m), "r"(bar), "r"(c0), "r"(c1), "l"(pol), "r"(bytes) : "memory");
}
__device__ __forceinline__ void tma_ld3_w(uint32_t dst, const CUtensorMap* m, int c0, int c1, int c2, uint32_t bar, uint32_t bytes) {
  asm volatile(ELECT EXPECT("%2", "%6") "cp.async.bulk.tensor.3d.shared::cluster.global.mbarrier::complete_tx::bytes [%0], [%1, {%3, %4, %5}], [%2];\n}"
               ::"r"(dst), "l"(m), "r"(bar), "r"(c0), "r"(c1), "r"(c2), "r"(bytes) : "memory");
}
__device__ __forceinline__ void tma_ld3_hint_w(uint32_t dst, const CUtensorMap* m, int c0, int c1, int c2, uint32_t bar, uint64_t pol) {
  asm volatile(ELECT EXPECT("%2", "16384") "cp.async.bulk.tensor.3d.shared::cluster.global.mbarrier::complete_tx::bytes.L2::cache_hint"
               " [%0], [%1, {%3, %4, %5}], [%2], %6;\n}"
               ::"r"(dst), "l"(m), "r"(bar), "r"(c0), "r"(c1), "r"(c2), "l"(pol) : "memory");
}
__device__ __forceinline__ void tma_ld_wo_w(uint32_t dst, const CUtensorMap* m, int col, int grp, uint32_t bar) {
  asm volatile(ELECT EXPECT("%2", "16384") "cp.async.bulk.tensor.5d.shared::cluster.global.mbarrier::complete_tx::bytes [%0], [%1, {%3, 0, 0, 0, %4}], [%2];\n"
               "@p cp.async.bulk.tensor.5d.shared::cluster.global.mbarrier::complete_tx::bytes [%5], [%1, {%6, 0, 0, 0, %4}], [%2];\n}"
               ::"r"(dst), "l"(m), "r"(bar), "r"(col), "r"(grp), "r"(dst + 8192), "r"(col + 64) : "memory");
}
__device__ __forceinline__ void mbar_arrive8_w(uint32_t bar) {
  asm volatile(ELECT "mbarrier.arrive.shared::cta.b64 _, [%0], 8;\n}" ::"r"(bar) : "memory");
}
__device__ __forceinline__ void bulk_commit() { asm volatile("cp.async.bulk.commit_group;" ::: "memory"); }
template <int N> __device__ __forceinline__ void bulk_wait_read() { asm volatile("cp.async.bulk.wait_group.read %0;" ::"n"(N) : "memory"); }
__device__ __forceinline__ void wg_fence() { asm volatile("wgmma.fence.sync.aligned;" ::: "memory"); }
__device__ __forceinline__ void wg_commit() { asm volatile("wgmma.commit_group.sync.aligned;" ::: "memory"); }
template <int N> __device__ __forceinline__ void wg_wait() { asm volatile("wgmma.wait_group.sync.aligned %0;" ::"n"(N) : "memory"); }
__device__ __forceinline__ void fence_async_smem() { asm volatile("fence.proxy.async.shared::cta;" ::: "memory"); }
__device__ __forceinline__ void bar_sync(int id, int n) { asm volatile("bar.sync %0, %1;" ::"r"(id), "r"(n) : "memory"); }
template <int N> __device__ __forceinline__ void reg_fence(float (&a)[N]) {
#pragma unroll
  for (int i = 0; i < N; i++) asm volatile("" : "+f"(a[i])::"memory");
}
template <int N> __device__ __forceinline__ void reg_fence(uint32_t (&a)[N]) {
#pragma unroll
  for (int i = 0; i < N; i++) asm volatile("" : "+r"(a[i])::"memory");
}
__device__ __forceinline__ float ex2(float x) { float y; asm("ex2.approx.ftz.f32 %0, %1;" : "=f"(y) : "f"(x)); return y; }
__device__ __forceinline__ uint32_t pack_bf16(float lo, float hi) {
  uint32_t r; asm("cvt.rn.bf16x2.f32 %0, %1, %2;" : "=r"(r) : "f"(hi), "f"(lo)); return r;
}
__device__ __forceinline__ void stsm4(uint32_t a, uint32_t r0, uint32_t r1, uint32_t r2, uint32_t r3) {
  asm volatile("stmatrix.sync.aligned.m8n8.x4.shared.b16 [%0], {%1, %2, %3, %4};" ::"r"(a), "r"(r0), "r"(r1), "r"(r2), "r"(r3) : "memory");
}
__device__ __forceinline__ void stsm4t(uint32_t a, uint32_t r0, uint32_t r1, uint32_t r2, uint32_t r3) {
  asm volatile("stmatrix.sync.aligned.m8n8.x4.trans.shared.b16 [%0], {%1, %2, %3, %4};" ::"r"(a), "r"(r0), "r"(r1), "r"(r2), "r"(r3) : "memory");
}
__device__ __forceinline__ void ldsm4(uint32_t a, uint32_t& r0, uint32_t& r1, uint32_t& r2, uint32_t& r3) {
  asm volatile("ldmatrix.sync.aligned.m8n8.x4.shared.b16 {%0, %1, %2, %3}, [%4];" : "=r"(r0), "=r"(r1), "=r"(r2), "=r"(r3) : "r"(a) : "memory");
}
__device__ __forceinline__ void sts16(uint32_t a, uint32_t v) { asm volatile("st.shared.u16 [%0], %1;" ::"r"(a), "h"((uint16_t)v) : "memory"); }
__device__ __forceinline__ void mma16816(float& c0, float& c1, float& c2, float& c3, uint32_t a0, uint32_t a1, uint32_t a2, uint32_t a3,
                                         uint32_t b0, uint32_t b1) {
  asm volatile("mma.sync.aligned.m16n8k16.row.col.f32.bf16.bf16.f32 {%0, %1, %2, %3}, {%4, %5, %6, %7}, {%8, %9}, {%0, %1, %2, %3};"
               : "+f"(c0), "+f"(c1), "+f"(c2), "+f"(c3) : "r"(a0), "r"(a1), "r"(a2), "r"(a3), "r"(b0), "r"(b1));
}
__device__ __forceinline__ uint32_t sdesc(uint32_t addr, uint32_t lbo) { return (addr >> 4) + ((lbo >> 4) << 16); }
__device__ __forceinline__ uint64_t desc64(uint32_t lo, uint32_t hi) { uint64_t d; asm("mov.b64 %0, {%1, %2};" : "=l"(d) : "r"(lo), "r"(hi)); return d; }
__device__ __forceinline__ void dadd(uint64_t& d, uint32_t inc) {
  asm("{\n.reg .b32 l, h;\nmov.b64 {l, h}, %0;\nadd.u32 l, l, %1;\nmov.b64 %0, {l, h};\n}" : "+l"(d) : "r"(inc));
}

struct Ring {
  uint32_t slot, phase, xp;
  __device__ __forceinline__ void uniform() {
    slot = __shfl_sync(0xffffffffu, slot, 0); phase = __shfl_sync(0xffffffffu, phase, 0); xp = __shfl_sync(0xffffffffu, xp, 0);
  }
  __device__ __forceinline__ void next() { if (++slot == NS) { slot = 0; phase ^= 1; } }
  __device__ __forceinline__ void next_if(bool p) { slot += p; if (slot == NS) { slot = 0; phase ^= 1; } }
};
__device__ __forceinline__ uint32_t borrow(int ks, int n) {
  if (BORROW_ALT) return (ks & 1) && ks >= 3 && ks + 1 < n ? (~ks >> 1) & 1 : 2;
  const int k = ks + 1;
  return k >= 4 && !(k & 2) && k < n ? k & 1 : 2;
}

constexpr uint32_t Q_RANGES = NBETA * NH + __builtin_popcount(EARLY_MASK) * 5, Q_ALL = NBETA * (NH + 5);
constexpr int NRANGE = NCTA / 5;
struct Work { int kind, mode, k0, nsteps, range, beta, sub; };
struct Sched { uint16_t queue[Q_ALL]; uint32_t piece[NRANGE + 1][4]; };
constexpr Sched make_sched() {
  Sched s{};
  int q = 0, a = 0;
  for (int pass = 0; pass < 2; pass++)
    for (int b = pass ? B_LATE : 0; b < NBETA; b++)
      for (int h = pass ? H_LATE : 0; h < (pass || b < B_LATE ? NH : H_LATE); h++) {
        if (a >= P_POS && (a - P_POS) % 32 == 0 && (EARLY_MASK >> ((a - P_POS) / 32) & 1))
          for (int col = 0; col < 5; col++) s.queue[q++] = 0x8000 | col << 8 | (a - P_POS) / 32;
        s.queue[q++] = b << 5 | h;
        a++;
      }
  for (int b = 0; b < NBETA; b++)
    for (int col = 0; col < 5 && !(EARLY_MASK >> b & 1); col++) s.queue[q++] = 0x8000 | col << 8 | b;
  constexpr uint32_t T[NRANGE * 2] = {PIECE_TABLE};
  for (int g = 0; g <= NRANGE; g++)
    for (int n = 0; n < 4; n++) s.piece[g][n] = g < NRANGE && n < 2 ? T[2 * g + n] : 2u << 30;
  return s;
}
__constant__ Sched c_sched = make_sched();
__device__ __forceinline__ Work decode(uint32_t d) {
  Work w;
  w.kind = d >> 30; if (w.kind == 3) w.kind = 1;
  w.mode = (d >> 28) & 3; w.k0 = (d >> 22) & 63;
  if (w.kind == 0) { w.beta = (d >> 5) & 31; w.sub = d & 31; w.nsteps = DM / 64; }
  else { w.beta = d & 31; w.sub = (d >> 8) & 7; w.nsteps = ((d >> 16) & 63) + 1; }
  w.range = ((d >> 11) & 31) * 5 + w.sub;
  return w;
}

__device__ __forceinline__ bool reached(const unsigned* cnt, unsigned target) {
  unsigned v;
  asm volatile("ld.acquire.gpu.global.u32 %0, [%1];" : "=r"(v) : "l"(cnt) : "memory");
  return (int)(v - target) >= 0;
}
__device__ __forceinline__ void wait_count(const unsigned* cnt, unsigned target) {
  unsigned n = 0;
  while (!__all_sync(0xffffffffu, reached(cnt, target))) { if (++n > (1u << 24)) __trap(); }
}
__device__ __forceinline__ uint32_t lds(uint32_t a) { uint32_t v; asm volatile("ld.volatile.shared.u32 %0, [%1];" : "=r"(v) : "r"(a) : "memory"); return v; }

#define TRACE(u, e)
#define T3(u, e)
#define T2C(u, e)
#define T2P(u, r, e)
#define TTAIL(k)
#define TCLK(k)
#define TRACE_P(u, e)
#define TRACE_IN(u, e)

struct Ctx {
  uint32_t sb;
  int wg, warp;
  uint32_t mqk, mpv;
  bool lead;
  int src;
};
template <int N> __device__ __forceinline__ uint32_t dhi(uint32_t lo) { return 0x40000040u + (lo >> (26 + N)); }
__device__ __forceinline__ void release(const Ctx& c, uint32_t slot) {
  if (c.lead) mbar_arrive(c.sb + BAR_EMPTY + slot * 8);
}
__device__ __forceinline__ uint32_t acquire(const Ctx& c, Ring& r, bool have = false) {
  const uint32_t s = r.slot;
  if (!have) mbar_wait_w(c.sb + BAR_FULL + s * 8, r.phase);
  r.next();
  return s;
}
__device__ __forceinline__ void mbar_wait2_w(uint32_t b0, uint32_t p0, uint32_t b1, uint32_t p1) {
  uint32_t n = 0;
  while (!__all_sync(0xffffffffu, mbar_try(b0, p0) & mbar_try(b1, p1))) {
    if (++n > (1u << 22)) __trap();
  }
}
__device__ __forceinline__ void mbar_wait3_w(uint32_t b0, uint32_t p0, uint32_t b1, uint32_t p1, uint32_t b2, uint32_t p2) {
  uint32_t n = 0;
  while (!__all_sync(0xffffffffu, mbar_try(b0, p0) & mbar_try(b1, p1) & mbar_try(b2, p2))) {
    if (++n > (1u << 22)) __trap();
  }
}
__device__ __forceinline__ void acquire2(const Ctx& c, Ring& r, uint32_t& s0, uint32_t& s1, bool have = false) {
  const uint32_t p0 = r.phase;
  s0 = r.slot; r.next(); s1 = r.slot;
  if (!have) mbar_wait2_w(c.sb + BAR_FULL + s0 * 8, p0, c.sb + BAR_FULL + s1 * 8, r.phase);
  r.next();
}
template <int N>
__device__ __forceinline__ bool peek(const Ctx& c, Ring r) {
  bool ok = true;
#pragma unroll
  for (int k = 0; k < N; k++) { ok &= mbar_test(c.sb + BAR_FULL + r.slot * 8, r.phase); r.next(); }
  return ok;
}
__device__ __forceinline__ void staged(const Ctx& c, int part) {
  fence_async_smem();
  __syncwarp();
  mbar_arrive_warp(c.sb + BAR_STG + c.wg * 16 + part * 8);
}

template <int WG, bool FIRST, int H>
__device__ __forceinline__ void proj_half(const Ctx& c, float (&acc)[64], uint32_t w, uint32_t x, uint32_t sw) {
  uint64_t dx = desc64((c.sb + x * SLOT + (WG ? 0 : H * 8192)) >> 4, dhi<0>(x) + sw);
  uint64_t dw = desc64(WG ? (c.sb + w * SLOT + H * 8192) >> 4 : sdesc(c.sb + w * SLOT, 8192), dhi<1>(x));
  wg_fence();
  if (WG) { if (FIRST) wgmma_proj96_init(acc, dw, dx, 0); else wgmma_proj96(acc, dw, dx, 1); }
  else { if (FIRST) wgmma_proj_init(acc, dx, dw, 0); else wgmma_proj(acc, dx, dw, 1); }
#pragma unroll
  for (int k = 1; k < 4; k++) {
    dadd(dx, k == 2 ? 2 + (sw >> 30) * 28 : 2); dadd(dw, 128);
    if (WG) wgmma_proj96(acc, dw, dx, 1); else wgmma_proj(acc, dx, dw, 1);
  }
  wg_commit();
}

__device__ __forceinline__ void proj_store16(uint32_t a, const float* f, float sc) {
  stsm4t(a, pack_bf16(f[0] * sc, f[1] * sc), pack_bf16(f[2] * sc, f[3] * sc), pack_bf16(f[4] * sc, f[5] * sc), pack_bf16(f[6] * sc, f[7] * sc));
}

__device__ __forceinline__ uint32_t stage_off(const Ctx& c) {
  const int lane = lane_now(), mi = lane >> 3, r8 = lane & 7;
  return ((mi >> 1) * 8 + r8) * 128 + (((2 * c.warp + (mi & 1)) ^ r8) << 4);
}
__device__ __forceinline__ uint32_t q3_swz(uint32_t r8) { return ((r8 & 3) << 1) | (r8 >> 2); }
template <int H>
__device__ __forceinline__ void stage_t2(const Ctx& c, const float (&a)[64], float sc) {
  const uint32_t base = c.sb + QBUF_OFF + 2 * 16384 + H * 8192 + stage_off(c);
#pragma unroll
  for (int jj = 0; jj < 4; jj++) proj_store16(base + jj * 2048, &a[jj * 8], sc);
}
template <int H, bool IS_Q>
__device__ __forceinline__ void stage_t3(const Ctx& c, const float (&a)[64], float sc) {
  const uint32_t off = stage_off(c), r8 = (off >> 7) & 7;
  const uint32_t t3 = c.sb + QBUF_OFF + 3 * 16384 + H * 4096 + (IS_Q ? off ^ ((r8 ^ q3_swz(r8)) << 4) : off);
  proj_store16(t3, &a[32], sc);
  proj_store16(t3 + 2048, &a[40], sc);
}

template <bool TRANS>
__device__ __forceinline__ void add16(uint32_t a, float* f) {
  uint32_t r[4];
  if (TRANS) asm volatile("ldmatrix.sync.aligned.m8n8.x4.trans.shared.b16 {%0, %1, %2, %3}, [%4];"
                          : "=r"(r[0]), "=r"(r[1]), "=r"(r[2]), "=r"(r[3]) : "r"(a) : "memory");
  else ldsm4(a, r[0], r[1], r[2], r[3]);
#pragma unroll
  for (int i = 0; i < 4; i++) { f[2 * i] += __uint_as_float(r[i] << 16); f[2 * i + 1] += __uint_as_float(r[i] & 0xffff0000u); }
}

__device__ __forceinline__ void trace_dump(const Ctx& c) {
}
struct RowSum { float l0, l1; };
__device__ __forceinline__ const char* o_addr(uint32_t item, int row) {
  const int lane = lane_now();
  return reinterpret_cast<const char*>(g_o) + ((item * (2 * SQ) + row) * 128 + (lane ^ (lane >> 3)) * 16);
}
__device__ __forceinline__ void o_stg(const char* p, int i, const uint32_t* q) {
  asm volatile("st.global.v4.b32 [%0], {%1, %2, %3, %4};"
               ::"l"(p + (i >> 1) * (SQ * 128) + (i & 1) * 512), "r"(q[0]), "r"(q[1]), "r"(q[2]), "r"(q[3]) : "memory");
}
template <int MODE, int I0 = 0, int NI = 4>
__device__ __forceinline__ void o_emit(const char* p, const float (&o)[64], float inv) {
#pragma unroll
  for (int i = I0; i < I0 + NI; i++) {
    uint32_t q[4];
#pragma unroll
    for (int j = 0; j < 4; j++) q[j] = pack_bf16(o[16 * i + 4 * j + 2 * MODE] * inv, o[16 * i + 4 * j + 2 * MODE + 1] * inv);
    o_stg(p, i, q);
  }
}
__device__ __forceinline__ void o_done(const Ctx& c) {
  __syncwarp();
  mbar_arrive_warp(c.sb + BAR_OUT);
  __syncwarp();
}
__device__ __forceinline__ void pack3(float (&o)[64], const RowSum& inv, uint32_t (&q)[16]) {
  reg_fence(o);
#pragma unroll
  for (int j = 0; j < 16; j++) q[j] = pack_bf16((o[4 * j] + o[4 * j + 2]) * inv.l0, (o[4 * j + 1] + o[4 * j + 3]) * inv.l0);
  reg_fence(q);
}
template <int WG>
__device__ __forceinline__ void o_first(const Ctx& c, uint32_t item, const float (&o)[64], const RowSum& inv, const uint32_t (&q)[16]) {
  const char* p = o_addr(item, WG ? 192 + 8 * c.warp : 64 + 16 * c.warp);
  if (WG) {
#pragma unroll
    for (int i = 0; i < 4; i++) o_stg(p, i, q + 4 * i);
  } else { o_emit<0>(p, o, inv.l0); o_emit<1>(p + 1024, o, inv.l1); }
}
template <int K0, int K1>
__device__ __forceinline__ void o_piece(const Ctx& c, const char* p, int k, const float (&o)[64], const RowSum& inv) {
  constexpr int NI = 8 / O_STEPS, M = K0 * NI / 4;
  if constexpr (K1 - K0 == 1) {
    o_emit<M, K0 * NI % 4, NI>(p + M * 1024, o, M ? inv.l1 : inv.l0);
    if (K1 == O_STEPS) o_done(c);
  } else {
    if (k <= (K0 + K1) / 2) o_piece<K0, (K0 + K1) / 2>(c, p, k, o, inv); else o_piece<(K0 + K1) / 2, K1>(c, p, k, o, inv);
  }
}
template <int WG>
__device__ __forceinline__ void o_second(const Ctx& c, uint32_t item, int k, float (&o)[64], const RowSum& inv) {
  reg_fence(o);
  o_piece<0, O_STEPS>(c, o_addr(item, 128 * WG + 16 * c.warp), k, o, inv);
}
template <int WG>
__device__ __forceinline__ void release_q(const Ctx& c) {
#pragma unroll
  for (int t = 0; t < 2; t++)
    if (c.lead) asm volatile("mbarrier.arrive.shared::cta.b64 _, [%0], 2;" ::"r"(c.sb + BAR_EMPTY + (NS + 2 * WG + t) * 8) : "memory");
  __syncwarp();
}
struct Slots { uint32_t w, x, o, po; };
template <int WG>
__device__ __forceinline__ void acc_fence(float (&a)[64]) {
#pragma unroll
  for (int i = 0; i < (WG ? 48 : 64); i++) asm volatile("" : "+f"(a[i])::"memory");
}
template <int WG>
__device__ __forceinline__ void begin_acquire(const Ctx& c, Ring& r, Slots& h, bool wait) {
  const uint32_t s0 = r.slot, p0 = r.phase, f = c.sb + BAR_FULL;
  r.next();
  const uint32_t p1 = r.phase;
  h.w = r.slot; r.next();
  h.x = WG ? r.slot : s0; h.o = WG ? s0 : r.slot; h.po = r.phase;
  if (wait) { if (WG) mbar_wait3_w(f + s0 * 8, p0, f + h.w * 8, p1, f + h.x * 8, r.phase); else mbar_wait2_w(f + s0 * 8, p0, f + h.w * 8, p1); }
  r.next();
}
template <int WG>
__device__ __forceinline__ void proj_begin(const Ctx& c, Ring& r, float (&a0)[64], Slots& h, bool wait, uint32_t sw) {
  begin_acquire<WG>(c, r, h, wait);
  proj_half<WG, true, 0>(c, a0, h.w, h.x, sw);
  if (WG) release(c, h.o);
}
template <int WG>
__device__ __forceinline__ bool proj_main(const Ctx& c, Ring& r, float (&a0)[64], float (&a1)[64], Slots& h, int n, uint32_t sw, int unit,
                                          uint32_t item, int nq, float (&o1)[64], const RowSum& inv) {
  constexpr bool DEEP = (PDEPTH >> WG) & 1;
  T2C(unit, 3);
  int ks = 1;
#pragma unroll 1
  do {
    const Slots p = h;
    const uint32_t b = borrow(ks, n), tile = NS + (WG ? 3 - b : b), f = c.sb + BAR_FULL;
    const uint32_t s0 = b != 2 ? tile : r.slot, p0 = b != 2 ? (r.xp >> b) & 1 : r.phase;
    r.next_if(b == 2);
    const uint32_t p1 = r.phase;
    h.w = r.slot; r.next();
    const uint32_t s2 = b != 2 ? tile : r.slot;
    h.po = b != 2 ? p0 : r.phase;
    r.next_if(b == 2);
    r.xp ^= 1 << b;
    h.x = WG ? s2 : s0; h.o = WG ? s0 : s2;
    mbar_wait3_w(f + s0 * 8, p0, f + h.w * 8, p1, f + (WG ? s2 : p.o) * 8, WG ? h.po : p.po);
    if (ks < 10) T2C(unit, ks * 4);
    if (DEEP) {
      proj_half<WG, false, 0>(c, a0, h.w, h.x, sw);
      release(c, WG ? h.o : p.o);
      if (ks < 10) T2C(unit, ks * 4 + 1);
      wg_wait<1>();
      if (ks < 10) T2C(unit, ks * 4 + 2);
      release(c, p.x); release(c, p.w);
    } else {
      release(c, WG ? h.o : p.o);
      wg_wait<0>();
      release(c, p.x); release(c, p.w);
      if (LAST_SYNC && !WG) asm volatile("{\n.reg .pred p;\nsetp.eq.u32 p, %0, %1;\n@p bar.sync 5, 256;\n}" ::"r"(ks + LAST_SYNC), "r"(n) : "memory");
      if (ks < 10) T2C(unit, ks * 4 + 1);
      proj_half<WG, false, 0>(c, a0, h.w, h.x, sw);
      if (ks < 10) T2C(unit, ks * 4 + 2);
    }
    if (LAST_SYNC && WG && !DEEP) asm volatile("{\n.reg .pred p;\nsetp.eq.u32 p, %0, %1;\n@p bar.arrive 5, 256;\n}" ::"r"(ks + LAST_SYNC), "r"(n) : "memory");
    proj_half<WG, false, 1>(c, a1, h.w, h.x, sw);
    if (LAST_SYNC && WG && DEEP) asm volatile("{\n.reg .pred p;\nsetp.eq.u32 p, %0, %1;\n@p bar.arrive 5, 256;\n}" ::"r"(ks + LAST_SYNC), "r"(n) : "memory");
    if (ks < 10) T2C(unit, ks * 4 + 3);
    if (ks <= nq) o_second<WG>(c, item, ks, o1, inv);
  } while (++ks != n);
  {
    const uint32_t e0 = c.sb + BAR_EMPTY + (NS + 3 * WG) * 8, e1 = c.sb + BAR_EMPTY + (NS + 1 + WG) * 8;
    const uint32_t p0 = (r.xp ^ unit ^ 1) & 1, p1 = ((r.xp >> 1) ^ unit ^ 1) & 1;
    if (WG) mbar_wait2_w(e0, p0, e1, p1); else mbar_wait3_w(e0, p0, e1, p1, c.sb + BAR_FULL + h.o * 8, h.po);
  }
  const bool have = PEEK ? peek<3>(c, r) : false;
  if (!WG) release(c, h.o);
  wg_wait<1>();
  acc_fence<WG>(a0);
  return PEEK && __all_sync(0xffffffffu, have);
}
template <int WG>
__device__ __forceinline__ void proj_end(const Ctx& c, float (&a1)[64], const Slots& h) {
  wg_wait<0>();
  acc_fence<WG>(a1);
  release(c, h.x); release(c, h.w);
}
__device__ __forceinline__ uint32_t get_desc(const Ctx& c, int i) {
  uint32_t d;
  mbar_wait_w(c.sb + BAR_DESC, (i - 1) & 1);
  asm volatile("ld.volatile.shared.u32 %0, [%1];" : "=r"(d) : "r"(c.sb + DESC_OFF + (i & 3) * 4) : "memory");
  return __shfl_sync(0xffffffffu, d, 0);
}

__device__ __forceinline__ float quad_max(float x) {
  x = fmaxf(x, __shfl_xor_sync(0xffffffffu, x, 1));
  return fmaxf(x, __shfl_xor_sync(0xffffffffu, x, 2));
}
__device__ __forceinline__ float quad_sum(float x) {
  x += __shfl_xor_sync(0xffffffffu, x, 1);
  return x + __shfl_xor_sync(0xffffffffu, x, 2);
}
template <bool SP, bool FIRST>
__device__ __forceinline__ void exps(const Ctx& c, const float (&s)[32], uint32_t (&p)[SP ? 8 : 16], RowSum& st) {
  if constexpr (SP) {
    uint32_t q[8];
    float t;
#pragma unroll
    for (int j = 0; j < 8; j++) {
      const float e0 = ex2(s[4 * j] + s[4 * j + 2]), e1 = ex2(s[4 * j + 1] + s[4 * j + 3]);
      if (j == 0) t = e0 + e1; else t += e0 + e1;
      q[j] = pack_bf16(e0, e1);
    }
    const bool odd = c.src & 2;
#pragma unroll
    for (int g = 0; g < 4; g++) {
      p[2 * g] = __shfl_sync(0xffffffffu, odd ? q[2 * g + 1] : q[2 * g], c.src);
      p[2 * g + 1] = __shfl_sync(0xffffffffu, odd ? q[2 * g] : q[2 * g + 1], c.src ^ 1);
    }
    st.l0 = FIRST ? t : st.l0 + t;
  } else {
    float t0, t1;
#pragma unroll
    for (int j = 0; j < 8; j++) {
      const float e0 = ex2(s[4 * j]), e1 = ex2(s[4 * j + 1]), e2 = ex2(s[4 * j + 2]), e3 = ex2(s[4 * j + 3]);
      if (j == 0) { t0 = e0 + e1; t1 = e2 + e3; } else { t0 += e0 + e1; t1 += e2 + e3; }
      p[2 * j] = pack_bf16(e0, e1);
      p[2 * j + 1] = pack_bf16(e2, e3);
    }
    st.l0 = FIRST ? t0 : st.l0 + t0;
    st.l1 = FIRST ? t1 : st.l1 + t1;
  }
}
template <bool SP>
__device__ __forceinline__ bool finish_sums(RowSum& st) {
  const float a = quad_sum(st.l0), b = SP ? a : quad_sum(st.l1);
  st.l0 = __fdividef(1.f, a); st.l1 = __fdividef(1.f, b);
  return !DEV_HALF && !(a >= SUM_LO && a <= SUM_HI && b >= SUM_LO && b <= SUM_HI);
}
template <bool SP, bool INIT, int SITE, bool COMMIT = true>
__device__ __forceinline__ void issue_qk(const Ctx& c, float (&s)[32], const uint32_t (&qs)[16], uint32_t dq, uint32_t dk) {
  uint64_t a = desc64(dq, dhi<SITE & 1>(dk)), b = desc64(dk, dhi<1 - (SITE & 1)>(dk));
  if (SP) {
    if (INIT) wgmma_qk_sp_init(s, qs[0], qs[1], qs[2], qs[3], b, 0, c.mqk); else wgmma_qk_sp(s, qs[0], qs[1], qs[2], qs[3], b, 0, c.mqk);
#pragma unroll
    for (int k = 1; k < 4; k++) { dadd(b, k == 2 ? 508 : 4); wgmma_qk_sp(s, qs[4 * k], qs[4 * k + 1], qs[4 * k + 2], qs[4 * k + 3], b, 1, c.mqk); }
  } else {
    if (INIT) wgmma_qk_init(s, a, b, 0); else wgmma_qk(s, a, b, 0);
#pragma unroll
    for (int k = 1; k < 8; k++) { dadd(a, k == 4 ? 506 : 2); dadd(b, k == 4 ? 506 : 2); wgmma_qk(s, a, b, 1); }
  }
  if (COMMIT) wg_commit();
}
template <bool SP, bool ACC, int SITE, bool SPLIT = false>
__device__ __forceinline__ void issue_pv(const Ctx& c, float (&o)[64], const uint32_t (&p)[SP ? 8 : 16], uint32_t dv) {
  uint64_t b = desc64(dv, dhi<SITE & 1>(dv));
  if constexpr (SP) {
    if (ACC) wgmma_pv_sp(o, p[0], p[1], p[2], p[3], b, 1, c.mpv); else wgmma_pv_sp_init(o, p[0], p[1], p[2], p[3], b, 0, c.mpv);
    if (SPLIT) wg_commit();
    dadd(b, 256);
    wgmma_pv_sp(o, p[4], p[5], p[6], p[7], b, 1, c.mpv);
  } else {
    if (ACC) wgmma_pv(o, p[0], p[1], p[2], p[3], b, 1); else wgmma_pv_init(o, p[0], p[1], p[2], p[3], b, 0);
#pragma unroll
    for (int k = 1; k < 4; k++) { dadd(b, 128); wgmma_pv(o, p[4 * k], p[4 * k + 1], p[4 * k + 2], p[4 * k + 3], b, 1); }
  }
  wg_commit();
}
__device__ __forceinline__ void pack_rows(const float (&o)[64], float sc, uint32_t (&q)[32]) {
#pragma unroll
  for (int j = 0; j < 32; j++) q[j] = pack_bf16(o[2 * j] * sc, o[2 * j + 1] * sc);
}
__device__ __forceinline__ void stage_rows(const Ctx& c, uint32_t tile_addr, const uint32_t (&q)[32]) {
  const int lane = lane_now(), mi = lane >> 3, r8 = lane & 7;
  const uint32_t row_addr = tile_addr + (16 * c.warp + (mi & 1) * 8 + r8) * 128;
#pragma unroll
  for (int jj = 0; jj < 8; jj++)
    stsm4(row_addr + (jj >> 2) * 8192 + (((((2 * jj) & 7) + (mi >> 1)) ^ r8) << 4), q[4 * jj], q[4 * jj + 1], q[4 * jj + 2], q[4 * jj + 3]);
}
__device__ __forceinline__ void stage_rows(const Ctx& c, uint32_t tile_addr, const float (&o)[64], float sc) {
  uint32_t q[32];
  pack_rows(o, sc, q);
  stage_rows(c, tile_addr, q);
}
template <int SITE>
__device__ __forceinline__ void issue_qk_rs(float (&s)[32], uint32_t (&q)[32], uint32_t dk) {
  uint64_t b = desc64(dk, dhi<SITE>(dk));
  reg_fence(q);
  wg_fence();
  wgmma_qk_rs_init(s, q[0], q[1], q[2], q[3], b, 0);
#pragma unroll
  for (int k = 1; k < 8; k++) { dadd(b, k == 4 ? 506 : 2); wgmma_qk_rs(s, q[4 * k], q[4 * k + 1], q[4 * k + 2], q[4 * k + 3], b, 1); }
  wg_commit();
}

__device__ __forceinline__ void redo_tile(const Ctx& c, uint32_t q_addr, uint32_t half, const __nv_bfloat16* kp, const __nv_bfloat16* vp,
                                          uint32_t item, int row) {
  float o[64];
  const int lane = lane_now(), g = lane >> 2, cc = lane & 3, mi = lane >> 3, r8 = lane & 7;
  const uint32_t qa = q_addr + (half == 4096 ? 8 * c.warp + r8 : 16 * c.warp + (mi & 1) * 8 + r8) * 128, swz = half == 4096 ? q3_swz(r8) : r8;
  const uint32_t* kq = reinterpret_cast<const uint32_t*>(kp + g * DH) + cc;
  const unsigned short* vq = reinterpret_cast<const unsigned short*>(vp + 2 * cc * DH) + g;
  float m0 = -INFINITY, m1 = -INFINITY, l0 = 0.f, l1 = 0.f;
#pragma unroll
  for (int i = 0; i < 64; i++) o[i] = 0.f;
#pragma unroll 1
  for (int kb = 0; kb < SK / 16; kb++) {
    float z[8] = {0.f, 0.f, 0.f, 0.f, 0.f, 0.f, 0.f, 0.f};
#pragma unroll 2
    for (int kk = 0; kk < 8; kk++) {
      uint32_t a0, a1, a2, a3;
      ldsm4(qa + (kk >> 2) * half + ((((kk & 3) * 2 + (mi >> 1)) ^ swz) << 4), a0, a1, a2, a3);
      const uint32_t* kr = kq + kb * (16 * DH / 2) + kk * 8;
      mma16816(z[0], z[1], z[2], z[3], a0, a1, a2, a3, __ldg(kr), __ldg(kr + 4));
      mma16816(z[4], z[5], z[6], z[7], a0, a1, a2, a3, __ldg(kr + 8 * DH / 2), __ldg(kr + 8 * DH / 2 + 4));
    }
    const float n0 = fmaxf(m0, quad_max(fmaxf(fmaxf(z[0], z[1]), fmaxf(z[4], z[5]))));
    const float n1 = fmaxf(m1, quad_max(fmaxf(fmaxf(z[2], z[3]), fmaxf(z[6], z[7]))));
    const float al0 = ex2(m0 - n0), al1 = ex2(m1 - n1);
    m0 = n0; m1 = n1;
#pragma unroll
    for (int i = 0; i < 8; i++) z[i] = ex2(z[i] - ((i & 2) ? n1 : n0));
    l0 = l0 * al0 + (z[0] + z[1]) + (z[4] + z[5]);
    l1 = l1 * al1 + (z[2] + z[3]) + (z[6] + z[7]);
    const uint32_t a0 = pack_bf16(z[0], z[1]), a1 = pack_bf16(z[2], z[3]), a2 = pack_bf16(z[4], z[5]), a3 = pack_bf16(z[6], z[7]);
    const unsigned short* vr = vq + kb * (16 * DH);
#pragma unroll
    for (int nb = 0; nb < 16; nb++) {
      o[4 * nb] *= al0; o[4 * nb + 1] *= al0; o[4 * nb + 2] *= al1; o[4 * nb + 3] *= al1;
      const uint32_t b0 = __ldg(vr + nb * 8) | ((uint32_t)__ldg(vr + nb * 8 + DH) << 16);
      const uint32_t b1 = __ldg(vr + nb * 8 + 8 * DH) | ((uint32_t)__ldg(vr + nb * 8 + 9 * DH) << 16);
      mma16816(o[4 * nb], o[4 * nb + 1], o[4 * nb + 2], o[4 * nb + 3], a0, a1, a2, a3, b0, b1);
    }
  }
  const char* p = o_addr(item, row);
  o_emit<0>(p, o, __fdividef(1.f, quad_sum(l0)));
  o_emit<1>(half == 4096 ? p : p + 1024, o, __fdividef(1.f, quad_sum(l1)));
}

template <bool SPA, bool SPB, int SITE, int ID>
__device__ __forceinline__ void batch(const Ctx& c, float (&s)[32], const uint32_t (&qs)[16], uint32_t dq, uint32_t dk, float (&ob)[64],
                                      uint32_t (&pb)[SPB ? 8 : 16], uint32_t dv) {
  if constexpr (SPA) {
    reg_fence(pb);
    wg_fence();
    issue_pv<SPB, true, ID>(c, ob, pb, dv);
    issue_qk<SPA, false, ID>(c, s, qs, dq, dk);
  } else {
    constexpr bool EARLY = ((QK_EARLY_MASK >> (SITE + (SPB ? 2 : 0))) & 1) != 0;
    if (!EARLY) reg_fence(pb);
    wg_fence();
    issue_qk<SPA, false, ID, !SPB>(c, s, qs, dq, dk);
    if (EARLY) { reg_fence(pb); wg_fence(); }
    issue_pv<SPB, true, ID, SPB>(c, ob, pb, dv);
  }
}

template <bool SP0>
__device__ __forceinline__ bool attention(Ctx c, Ring& r, int unit, uint32_t& d, const float (&a0)[64], float (&o0)[64], float (&o1)[64],
                                          RowSum& st0, RowSum& st1, const Slots& h, uint32_t (&q3)[16], bool kv) {
  constexpr bool SP1 = false;
  if (SP0) { c.mqk = META_QK + (d >> 28); c.mpv = META_PV + (d >> 28); asm volatile("" : "+r"(c.mqk), "+r"(c.mpv)); }
  if (SP0) { const int lane = lane_now(); c.src = (lane & 28) | ((lane & 1) << 1) | ((lane >> 1) & 1); }
  float s[32];
  uint32_t p0[SP0 ? 8 : 16], p1[16];
  const uint32_t q0a = c.sb + QBUF_OFF + (SP0 ? 3 : 0) * 16384, q1a = c.sb + QBUF_OFF + (SP0 ? 2 : 1) * 16384;
  const uint32_t dq0 = sdesc(q0a, 0), dq1 = sdesc(q1a, 0);
  uint32_t sk, sv, sn;
  uint32_t qs[16];
  T2C(unit, 40);
  if (SP0) {
    stage_t3<0, true>(c, a0, SM_C);
    stage_t2<0>(c, a0, SM_C);
    T2C(unit, 41);
    proj_end<1>(c, o0, h);
    T2C(unit, 42);
    stage_t3<1, true>(c, o0, SM_C);
    stage_t2<1>(c, o0, SM_C);
    sk = acquire(c, r, kv);
    fence_async_smem();
    T2C(unit, 43);
    bar_sync(1, LAG_BAR & 30 ? 256 : 128);
    const int lane = lane_now(), g = lane >> 2, cc = lane & 3;
    const uint32_t qa = q0a + (8 * c.warp + g) * 128 + (cc & 1) * 8;
#pragma unroll
    for (int k = 0; k < 8; k++)
      asm volatile("ld.shared.v2.u32 {%0, %1}, [%2];" : "=r"(qs[2 * k]), "=r"(qs[2 * k + 1])
                   : "r"(qa + (k >> 2) * 4096 + ((((k & 3) * 2 + (cc >> 1)) ^ q3_swz(g)) << 4)) : "memory");
    TRACE(unit, 2);
    T2C(unit, 44);
    float s1[32];
    wg_fence();
    issue_qk<SP1, true, 1>(c, s1, qs, dq1, sdesc(c.sb + sk * SLOT, 0));
    reg_fence(qs);
    wg_fence();
    issue_qk<SP0, true, 0>(c, s, qs, dq0, sdesc(c.sb + sk * SLOT, 0));
    T2C(unit, 45);
    acquire2(c, r, sv, sn, kv);
    wg_wait<1>();
    reg_fence(s1);
    T2C(unit, 47);
    exps<SP1, true>(c, s1, p1, st1);
    reg_fence(p1);
    wg_fence();
    issue_pv<SP1, false, 1>(c, o1, p1, sdesc(c.sb + sv * SLOT, 8192));
    if (LAG_BAR & 1) asm volatile("bar.arrive 4, 256;" ::: "memory");
    wg_wait<1>();
    reg_fence(s);
    T2C(unit, 48);
    release(c, sk);
    sk = sn;
    exps<SP0, true>(c, s, p0, st0);
    reg_fence(p0);
    wg_fence();
    issue_pv<SP0, false, 0>(c, o0, p0, sdesc(c.sb + sv * SLOT, 8192));
    issue_qk<SP0, false, 2>(c, s, qs, dq0, sdesc(c.sb + sk * SLOT, 0));
    T2C(unit, 49);
    sn = acquire(c, r);
    T2C(unit, 50);
    wg_wait<0>();
    reg_fence(s);
  } else {
    float s1[32];
    uint32_t q0[32], q1[32];
    if (!PEEK) sk = acquire(c, r);
    pack_rows(a0, SM_C, q0);
    if (RS_STAGE & 1) stage_rows(c, q0a, q0);
    reg_fence(q0);
    if (PEEK) sk = acquire(c, r, kv);
    T2C(unit, 41);
    proj_end<0>(c, o1, h);
    TRACE(unit, 2);
    T2C(unit, 42);
    issue_qk_rs<0>(s, q0, sdesc(c.sb + sk * SLOT, 0));
    if (LAG_BAR & 8) asm volatile("bar.arrive 1, 256;" ::: "memory");
    T2C(unit, 43);
    reg_fence(o1);
    pack_rows(o1, SM_C, q1);
    if (RS_STAGE & 2) stage_rows(c, q1a, q1);
    T2C(unit, 44);
    if (LAG_BAR & 4) asm volatile("bar.arrive 1, 256;" ::: "memory");
    issue_qk_rs<1>(s1, q1, sdesc(c.sb + sk * SLOT, 0));
    if (LAG_BAR & 2) asm volatile("bar.arrive 1, 256;" ::: "memory");
    T2C(unit, 45);
    acquire2(c, r, sv, sn, kv);
    if (!(RS_STAGE & 5)) stage_rows(c, q0a, q0);
    if (!(RS_STAGE & 10)) stage_rows(c, q1a, q1);
    T2C(unit, 46);
    wg_wait<1>();
    reg_fence(s);
    if (LAG_BAR & 16) asm volatile("bar.arrive 1, 256;" ::: "memory");
    T2C(unit, 47);
    if (RS_STAGE & 4) { reg_fence(q0); stage_rows(c, q0a, q0); }
    exps<SP0, true>(c, s, p0, st0);
    reg_fence(p0);
    wg_wait<0>();
    reg_fence(s1);
    if (RS_STAGE & 8) { reg_fence(q1); stage_rows(c, q1a, q1); }
    fence_async_smem();
    __syncwarp();
    wg_fence();
    issue_qk<SP0, false, 2>(c, s, qs, dq0, sdesc(c.sb + sn * SLOT, 0));
    issue_pv<SP0, false, 0>(c, o0, p0, sdesc(c.sb + sv * SLOT, 8192));
    T2C(unit, 48);
    release(c, sk);
    sk = sn;
    exps<SP1, true>(c, s1, p1, st1);
    reg_fence(p1);
    wg_fence();
    issue_pv<SP1, false, 1>(c, o1, p1, sdesc(c.sb + sv * SLOT, 8192));
    T2C(unit, 49);
    sn = acquire(c, r);
    if (LAG_BAR & 1) bar_sync(4, 256);
    T2C(unit, 50);
    wg_wait<1>();
    reg_fence(s);
  }
  TRACE_IN(unit, 4);
  T2C(unit, 51);
#pragma unroll 1
  for (int j = 1; j < 15; j++) {
    const uint32_t sv_prev = sv, sk_prev = sk;
    sv = sn;
    const uint32_t dv = sdesc(c.sb + sv * SLOT, 8192);
    reg_fence(p0);
    exps<SP0, false>(c, s, p0, st0);
    batch<SP1, SP0, 0, 3>(c, s, qs, dq1, sdesc(c.sb + sk * SLOT, 0), o0, p0, dv);
    sk = acquire(c, r);
    wg_wait<1>();
    reg_fence(s); reg_fence(p1);
    release(c, sv_prev); release(c, sk_prev);
    exps<SP1, false>(c, s, p1, st1);
    batch<SP0, SP1, 1, 4>(c, s, qs, dq0, sdesc(c.sb + sk * SLOT, 0), o1, p1, dv);
    sn = acquire(c, r);
    if (SP0) wg_wait<0>(); else wg_wait<1>();
    reg_fence(s);
  }
  TRACE_IN(unit, 5);
  T2C(unit + 1, 52);
  const uint32_t sv_prev = sv;
  sv = sn;
  const uint32_t dv = sdesc(c.sb + sv * SLOT, 8192);
  reg_fence(p0);
  exps<SP0, false>(c, s, p0, st0);
  batch<SP1, SP0, 0, 5>(c, s, qs, dq1, sdesc(c.sb + sk * SLOT, 0), o0, p0, dv);
  asm volatile("ld.volatile.shared.u32 %0, [%1];" : "=r"(d) : "r"(c.sb + DESC_OFF + ((unit + 1) & 3) * 4) : "memory");
  wg_wait<1>();
  reg_fence(s); reg_fence(p1);
  T2C(unit + 1, 53);
  release(c, sv_prev); release(c, sk);
  d = __shfl_sync(0xffffffffu, d, 0);
  const bool bad0 = finish_sums<SP0>(st0);
  exps<SP1, false>(c, s, p1, st1);
  reg_fence(p1);
  wg_fence();
  issue_pv<SP1, true, 2>(c, o1, p1, dv);
  T2C(unit + 1, 54);
  const bool have = peek<2 + SP0>(c, r);
  const bool bad = finish_sums<SP1>(st1) | bad0;
  if (SP0 && !PACK_LATE) {
    wg_wait<1>();
    pack3(o0, st0, q3);
  }
  T2C(unit + 1, 55);
  if (EARLY_BEG && d < (2u << 30) && !__all_sync(0xffffffffu, have)) { Ring t = r; Slots u; begin_acquire<SP0>(c, t, u, true); }
  T2C(unit + 1, 56);
  wg_wait<0>();
  if (!SP0 || PACK_LATE) reg_fence(o0);
  reg_fence(o1);
  T2C(unit + 1, 57);
  release(c, sv);
  return bad;
}
template <int WG>
__device__ __forceinline__ bool wg_any(bool p) {
  uint32_t any;
  asm volatile("{\n.reg .pred p, q;\nsetp.ne.u32 p, %1, 0;\nbar.red.or.pred q, %2, 128, p;\nselp.u32 %0, 1, 0, q;\n}"
               : "=r"(any) : "r"((uint32_t)p), "n"(2 + WG) : "memory");
  return __any_sync(0xffffffffu, any);
}

template <int WG>
__device__ __forceinline__ void consumer(Ctx c, const __nv_bfloat16* const* kv) {
  c.wg = WG;
  Ring r{0, 0, 0};
  bool bad;
  uint32_t q3[16];
  float a0[64], a1[64], o1[64];
  Slots h;
  RowSum inv0, inv1;
  uint32_t d = blockIdx.x, dc = 0, sw;
  int i = 0, nq;
begin:
  sw = d & (1u << 30);
  proj_begin<WG>(c, r, a0, h, true, sw);
  proj_half<WG, true, 1>(c, a1, h.w, h.x, sw);
  nq = 0;
#pragma unroll
  for (int k = 0; k < 64; k++) asm volatile("" : "=f"(o1[k]));
  asm volatile("" : "=f"(inv1.l0), "=f"(inv1.l1));
  while (true) {
    TRACE(i, 0); TRACE(i, 6);
    bad = proj_main<WG>(c, r, a0, a1, h, d >> 30 ? ((d >> 16) & 63) + 1 : DM / 64, sw, i, dc, nq, o1, inv1);
    dc = d;
    TRACE(i, 1);
    if (d >> 30) goto out_tile;
    bad = WG ? attention<WG>(c, r, i, d, a0, a1, o1, inv0, inv1, h, q3, bad) : attention<WG>(c, r, i, d, a0, o1, a1, inv1, inv0, h, q3, bad);
    if (!EARLY_BEG || d >= (2u << 30)) break;
    Ring t = r;
    sw = d & (1u << 30);
    begin_acquire<WG>(c, t, h, false);
    proj_half<WG, true, 0>(c, a0, h.w, h.x, sw);
    if (WG && PACK_LATE) pack3(a1, inv0, q3);
    if (WG && RED_FIRST != 2) proj_half<WG, true, 1>(c, a1, h.w, h.x, sw); else if (!WG) reg_fence(a1);
    T2C(i + 1, 58);
    if (!WG || RED_FIRST != 1) o_first<WG>(c, dc, a1, inv0, q3);
    if (__builtin_expect(wg_any<WG>(bad), 0)) {
      wg_wait<0>();
      acc_fence<WG>(a0);
      if (WG && RED_FIRST != 2) acc_fence<WG>(a1);
      goto redo;
    }
    r = t;
    T2C(i + 1, 1);
    if (!WG || RED_FIRST == 2) proj_half<WG, true, 1>(c, a1, h.w, h.x, sw);
    if (WG) release(c, h.o);
    release_q<WG>(c);
    if (WG && RED_FIRST == 1) o_first<WG>(c, dc, a1, inv0, q3);
    T2C(i + 1, 2);
    nq = O_STEPS;
    TRACE(i, 3); TRACE(i, 7);
    i++;
  }
  if (wg_any<WG>(bad)) goto redo;
  release_q<WG>(c);
  if (WG && PACK_LATE) pack3(a1, inv0, q3);
  o_first<WG>(c, dc, a1, inv0, q3);
#pragma unroll
  for (int k = 1; k <= O_STEPS; k++) o_second<WG>(c, dc, k, o1, inv1);
  T2C(i + 1, 58);
next:
  TRACE(i, 3); TRACE(i, 7);
  if ((d >> 30) != 2) {
    i++;
    r.uniform();
    goto begin;
  }
  trace_dump(c);
  return;
out_tile:
  proj_end<WG>(c, a1, h);
  if (((d >> 28) & 3) == 2) {
    const int lane = lane_now(), mi = lane >> 3, r8 = lane & 7;
    const uint32_t off = c.sb + (WG ? stage_off(c) : (16 * c.warp + (mi & 1) * 8 + r8) * 128);
#pragma unroll 1
    for (int k = (d >> 5) & 3; k > 0; k--) {
      uint32_t s0, s1;
      if (WG) { acquire2(c, r, s0, s1); release(c, s0); release(c, s1); }
#pragma unroll
      for (int t = 0; t < 2; t++) {
        const uint32_t sp = acquire(c, r), base = off + sp * SLOT;
        if (WG) {
#pragma unroll
          for (int jj = 0; jj < (t ? 2 : 4); jj++) {
            add16<true>(base + jj * 2048, &a0[(t * 4 + jj) * 8]);
            add16<true>(base + jj * 2048 + (t ? 4096 : 8192), &a1[(t * 4 + jj) * 8]);
          }
        } else {
#pragma unroll
          for (int jj = 0; jj < 8; jj++) add16<false>(base + (jj >> 2) * 8192 + (((((2 * jj) & 7) + (mi >> 1)) ^ r8) << 4), t ? &a1[jj * 8] : &a0[jj * 8]);
        }
        release(c, sp);
      }
      if (!WG) { acquire2(c, r, s0, s1); release(c, s0); release(c, s1); }
    }
  }
  if (WG) { stage_t3<0, false>(c, a0, 1.f); stage_t3<1, false>(c, a1, 1.f); }
  else stage_rows(c, c.sb + QBUF_OFF, a0, 1.f);
  staged(c, 0);
  if (WG) { stage_t2<0>(c, a0, 1.f); stage_t2<1>(c, a1, 1.f); }
  else stage_rows(c, c.sb + QBUF_OFF + 16384, a1, 1.f);
  staged(c, 1);
  d = get_desc(c, i + 1);
  TRACE(i, 2);
  goto next;
redo:
  {
    const size_t hoff = (size_t)(dc & 511) * (SK * DH);
    const int br = (dc >> 9) & 1;
#pragma unroll 1
    for (int part = 0; part < 2; part++) {
      const int t = WG ? 3 - part : part;
      redo_tile(c, c.sb + QBUF_OFF + t * 16384, t == 3 ? 4096 : 8192, kv[br] + hoff, kv[2 + br] + hoff, dc,
                t * 64 + (t == 3 ? 8 : 16) * c.warp);
    }
    o_done(c);
    release_q<WG>(c);
  }
  goto next;
}

template <bool SIMPLE>
__global__ void __launch_bounds__(384, 1) mha_fused_kernel(const __grid_constant__ Params P) {
  extern __shared__ __align__(1024) uint8_t smem_raw[];
  const uint32_t sbase = smem_u32(smem_raw);
  const int tid = threadIdx.x;
  const int wg = __shfl_sync(0xffffffffu, tid >> 7, 0);
  const int warp = __shfl_sync(0xffffffffu, (tid >> 5) & 3, 0);
  const int lane = tid & 31;
  const int cta = blockIdx.x;

  if (tid == 0) T3(15, 0);
  if ((sbase & 1023) || sbase + SMEM_BYTES > 0x40000) __trap();
  {
    const int wi = wg * 4 + warp;
    asm volatile(ELECT "prefetch.tensormap [%0];\n}" ::"l"(&P.x[0][0] + wi) : "memory");
#pragma unroll
    for (int k = 0; k < 3; k++) {
      const int b = min(BAR_OFF + (wi * 3 + k) * 8, BAR_GO);
      asm volatile(ELECT "mbarrier.init.shared::cta.b64 [%0], %1;\n}"
                   ::"r"(sbase + b), "r"(b < BAR_EMPTY || b >= BAR_DESC ? 1 : b >= BAR_STG && b < BAR_OUT ? 4 : 8) : "memory");
    }
    asm volatile("fence.mbarrier_init.release.cluster;" ::: "memory");
    if (wi < 6) asm volatile(ELECT "prefetch.tensormap [%0];\n}" ::"l"(&P.x[0][0] + 12 + wi) : "memory");
  }
  __syncthreads();

  if (wg == 2) {
    asm volatile("setmaxnreg.dec.sync.aligned.u32 %0;" ::"n"(REG_P));
    if (warp == 1) {
      const uint32_t qb = sbase + QBUF_OFF;
      const uint32_t ep = __shfl_sync(0xffffffffu, *(volatile unsigned*)&g_epoch + 1, 0);
      asm volatile("st.volatile.shared.u32 [%0], %1;" ::"r"(sbase + EPOCH_OFF), "r"(ep) : "memory");
      uint32_t dc = cta, qi = 0, piece = 0, na = 0;
      TTAIL(0);
      for (int i = 0; (dc >> 30) != 2; i++) {
        mbar_wait_w(sbase + BAR_GO, i & 1);
        if (TLB_WARM && (dc >> 30) == 0) asm volatile(ELECT "st.global.u32 [%0], 0;\n}" ::"l"(g_o + dc * (2 * SQ * 64)) : "memory");
        if (piece == 0) {
          if (lane == 0) {
            qi = atomicAdd(&g_next, 1);
            if (qi == (SIMPLE ? Q_ALL : Q_RANGES) - 1) { g_next = 0; g_epoch = ep; }
          }
          qi = __shfl_sync(0xffffffffu, qi, 0) + (SIMPLE ? gridDim.x : NCTA);
        }
        uint32_t d;
        if (qi < (SIMPLE ? Q_ALL : Q_RANGES)) { d = c_sched.queue[qi]; if (d & 0x8000) d ^= (1u << 30) | (63u << 16) | 0x8000; }
        else if (SIMPLE) d = 2u << 30;
        else { const uint32_t e = qi - Q_RANGES, g = e / 5; d = c_sched.piece[g][piece++] | (e - g * 5) << 8; }
        if ((d >> 30) == 1) {
          const uint32_t ok = __ballot_sync(0xffffffffu, reached(&g_cnt[lane & 1][d & 31], ep * (lane & 1 ? NH - H_LATE : H_LATE)));
          if (!(ok & 2)) d |= ((d >> 22) & 63) >= 2 * H_LATE - O_STEPS ? (2u << 30) | 128 : 128;
          if (!(ok & 1) || (O_STEPS > 4 && ((d >> 16) & 63) < O_STEPS)) d |= 2u << 30;
        }
        asm volatile("st.volatile.shared.u32 [%0], %1;" ::"r"(sbase + DESC_OFF + ((i + 1) & 3) * 4), "r"(d) : "memory");
        __syncwarp();
        mbar_arrive_warp(sbase + BAR_DESC);
        const Work w = decode(dc);
        dc = d;
        if (w.kind == 0) {
          mbar_wait_w(sbase + BAR_OUT, na++ & 1);
          TTAIL(1);
          T3(i, 0); T3(i, 1);
          asm volatile(ELECT "red.release.gpu.global.add.u32 [%0], 1;\n}" ::"l"(&g_cnt[w.sub >= H_LATE][w.beta]) : "memory");
          T3(i, 2);
          TTAIL(2);
          continue;
        }
        const bool fin = w.mode != 1;
        uint64_t pol, pol2;
        asm volatile("createpolicy.fractional.L2::evict_first.b64 %0, 1.0;" : "=l"(pol));
        asm volatile("createpolicy.fractional.L2::evict_normal.b64 %0, 1.0;" : "=l"(pol2));
        if (!fin) pol = pol2;
        const CUtensorMap* m = fin ? P.out_st : P.o_st;
        const int c1 = fin ? (w.beta & 15) * SQ : 0;
        const int c2 = fin ? (w.beta >> 4) * (DM / 64) + w.sub * 2 : NBETA * 64 + w.range * 2;
        uint32_t pend = 0;
#pragma unroll 1
        for (int e = 0; e < 4; e++) {
          const int t = (ST_ORDER >> (4 * e)) & 3;
          mbar_wait_w(sbase + BAR_STG + (t ^ (t >> 1)) * 8, (i - na) & 1);
          tma_st3_hint_w(m + (t == 3), qb + t * 16384, 0, c1 + t * 64, c2, pol);
          bulk_commit();
          T2P(i + 1, 5, 2 * e);
          if (pend) {
            bulk_wait_read<1>();
            mbar_arrive8_w(pend);
            T2P(i + 1, 5, 2 * e - 1);
          }
          pend = sbase + BAR_EMPTY + (NS + t) * 8;
          if ((ST_NOW >> e) & 1) {
            bulk_wait_read<0>();
            mbar_arrive8_w(pend);
            pend = 0;
            T2P(i + 1, 5, 2 * e + 1);
          }
        }
        T3(i, 0);
        if (piece >= 2) TTAIL(piece * 2 - 1);
        asm volatile("cp.async.bulk.wait_group 0;" ::: "memory");
        T3(i, 1);
        if (w.mode == 1) asm volatile(ELECT "st.release.gpu.global.u32 [%0], %1;\n}" ::"l"(&g_flag[w.range]), "r"(ep) : "memory");
        T3(i, 2);
        if (piece >= 2) TTAIL(piece * 2);
      }
      T3(15, 1);
    } else
    if (warp == 0) {
      Ring r{0, 1, 3};
      uint32_t d = cta;
      for (int i = 0;; i++) {
        const Work w = decode(d);
        if (w.kind == 2) break;
        const CUtensorMap* m = w.kind == 0 ? &P.wq[w.beta >> 4] : &P.wo[w.beta >> 4];
        for (int ks = 0; ks < w.nsteps; ks++) {
          const uint32_t b = borrow(ks, w.nsteps);
          r.next_if(b == 2);
          const uint32_t bar = sbase + BAR_FULL + r.slot * 8;
          mbar_wait_w(bar + (BAR_EMPTY - BAR_FULL), r.phase);
          if (w.kind == 0) tma_ld3_w(sbase + r.slot * SLOT, m, 0, ks * 64, w.sub * 2, bar, 16384);
          else tma_ld_wo_w(sbase + r.slot * SLOT, m, w.sub * 128, (w.k0 + ks) * 2, bar);
          if (ks < 10) T2P(i, 2, ks);
          if (w.kind != 0 && ks == max(w.nsteps - GO_P, 4)) mbar_arrive_warp(sbase + BAR_GO);
          r.next(); r.next_if(b == 2);
        }
        if (w.kind == 0) {
          r.phase ^= 1; r.next(); r.next();
        } else if (w.mode == 2) {
          for (int k = 1; k <= ((d >> 5) & 3); k++) {
            if (k == 1) TTAIL(9);
            wait_count(&g_flag[w.range + 5 * k], lds(sbase + EPOCH_OFF));
            TTAIL(10);
            asm volatile("fence.proxy.async.global;" ::: "memory");
#pragma unroll 1
            for (int t = 0; t < 4; t++) {
              mbar_wait_w(sbase + BAR_EMPTY + r.slot * 8, r.phase);
              tma_ld3_w(sbase + r.slot * SLOT, &P.o_st[t == 3], 0, t * 64, NBETA * 64 + (w.range + 5 * k) * 2, sbase + BAR_FULL + r.slot * 8,
                        t == 3 ? 8192 : 16384);
              r.next();
            }
          }
        }
        mbar_wait_w(sbase + BAR_DESC, i & 1);
        d = __shfl_sync(0xffffffffu, lds(sbase + DESC_OFF + ((i + 1) & 3) * 4), 0);
      }
    } else {
      const int hi = warp - 2;
      uint64_t pol_stream;
      asm volatile("createpolicy.fractional.L2::evict_first.b64 %0, 1.0;" : "=l"(pol_stream));
      Ring r{0, 1, 3};
      uint32_t d = cta;
      for (int i = 0;; i++) {
        const Work w = decode(d);
        if (w.kind == 2) break;
        const CUtensorMap* m = w.kind == 0 ? &P.x[hi][w.beta >> 4] : &P.o_ld[hi];
        int c1 = (w.kind == 0 ? (w.beta & 15) : w.beta * 64 + w.k0) * SQ + hi * 128;
        int k_late = -1;
        if (w.kind != 0) {
          if (!hi) T3(i, 3);
          if (d >= (3u << 30)) wait_count(&g_cnt[0][w.beta], lds(sbase + EPOCH_OFF) * H_LATE);
          if (d & 128) k_late = max(2 * H_LATE - w.k0, 0);
          if (!hi) T3(i, 4);
          asm volatile("fence.proxy.async.global;" ::: "memory");
          if (!hi) T3(i, 5);
        }
        for (int ks = 0; ks < w.nsteps; ks++) {
          if (ks == k_late) {
            if (!hi) T3(i, 6);
            wait_count(&g_cnt[1][d & 31], lds(sbase + EPOCH_OFF) * (NH - H_LATE));
            asm volatile("fence.proxy.async.global;" ::: "memory");
            if (!hi) T3(i, 7);
          }
          const uint32_t b = borrow(ks, w.nsteps);
          const bool bo = b != 2;
          r.next_if(hi && !bo); r.next_if(hi && !bo);
          const uint32_t sl = bo ? NS + (b ^ (3 * hi)) : r.slot, bar = sbase + BAR_FULL + sl * 8;
          mbar_wait_w(bar + (BAR_EMPTY - BAR_FULL), bo ? (r.xp >> b) & 1 : r.phase);
          if (w.kind == 0) tma_ld2_w(sbase + sl * SLOT, m, ks * 64, c1, bar, (hi ? 96 * 128 : 128 * 128) >> (DEV_HALF & 1));
          else if (O_LD_POL) { tma_ld2_hint_w(sbase + sl * SLOT, m, 0, c1, bar, (hi ? 96 * 128 : 128 * 128) >> (DEV_HALF >> 1), pol_stream); c1 += SQ; }
          else { tma_ld2_w(sbase + sl * SLOT, m, 0, c1, bar, hi ? 96 * 128 : 128 * 128); c1 += SQ; }
          if (PF_UNITS && w.kind == 0 && i < PF_UNITS && (((i ? PF_MASK : PF_MASK0) >> ks) & 1))
            asm volatile(ELECT "cp.async.bulk.prefetch.tensor.3d.L2.global.L2::cache_hint [%0, {0, %1, 0}], %2;\n}"
                         ::"l"(&P.kv[hi][w.beta >> 4]), "r"((d & 511) * SK + 64 * (PF_J0 + __popc((i ? PF_MASK : PF_MASK0) & ((1 << ks) - 1)))), "l"(pol_stream) : "memory");
          if (ks < 10) T2P(i, 3 + hi, ks);
          if (!hi && w.kind != 0 && !(ks & 3)) TCLK(i * 16 + (ks >> 2));
          r.next(); r.next_if(!hi && !bo); r.next_if(!hi && !bo);
          r.xp ^= 1 << b;
        }
        r.xp ^= 3;
        if (w.kind == 0) {
          m = &P.kv[hi][w.beta >> 4];
          c1 = (d & 511) * SK;
          for (int j = 0; j < 16; j++) {
            if (hi) r.next();
            const uint32_t bar = sbase + BAR_FULL + r.slot * 8;
            const bool tight = i < KV_WIN_UNITS && j < KV_WIN_TILES + ((KV_WIN_RAMP * ((int)d - KV_WIN_N * i)) >> 5);
            if (tight || (KV_WIN_D && j < KV_WIN_T2)) {
              const int s2 = (int)r.slot - (tight ? 2 : KV_WIN_D);
              mbar_wait_w(sbase + BAR_FULL + (s2 < 0 ? s2 + NS : s2) * 8, s2 < 0 ? r.phase : r.phase ^ 1);
            }
            if (j == 15 && hi) mbar_wait_w(sbase + BAR_DESC, i & 1);
            mbar_wait_w(sbase + BAR_EMPTY + r.slot * 8, r.phase);
            tma_ld3_hint_w(sbase + r.slot * SLOT, m, 0, c1, 0, bar, pol_stream);
            T2P(i, 3 + hi, 16 + j);
            if (!hi) TCLK(i * 16 + j);
            if (j == 14 && !hi) mbar_arrive_warp(sbase + BAR_GO);
            if (PF_X && j == PF_XJ && (d & 31) < 10 && d + PF_X * 32 < 1024)
              asm volatile(ELECT "cp.async.bulk.prefetch.tensor.2d.L2.global [%0, {%1, %2}];\n}"
                           ::"l"(&P.x[hi][(d + PF_X * 32) >> 9]), "r"((d & 31) * 64), "r"((((d >> 5) + PF_X) & 15) * SQ + hi * 128) : "memory");
            if (PF_W && j < 5 && (d >> 5) == PF_W)
              asm volatile(ELECT "cp.async.bulk.prefetch.tensor.3d.L2.global [%0, {0, %1, %2}];\n}"
                           ::"l"(&P.wq[1]), "r"((j * 2 + hi) * 64), "r"((d & 31) * 2) : "memory");
            c1 += 64;
            r.next();
            if (!hi) r.next();
          }
        }
        mbar_wait_w(sbase + BAR_DESC, i & 1);
        d = __shfl_sync(0xffffffffu, lds(sbase + DESC_OFF + ((i + 1) & 3) * 4), 0);
      }
    }
  } else {
    asm volatile("setmaxnreg.inc.sync.aligned.u32 %0;" ::"n"(REG_C));
    Ctx c;
    c.sb = sbase; c.wg = wg; c.warp = warp; c.src = 0; c.mqk = 0; c.mpv = 0; c.lead = lane == 0;
    if (wg == 0) consumer<0>(c, P.kp); else consumer<1>(c, P.kp);
  }
}

typedef CUresult (*EncodeFn)(CUtensorMap*, CUtensorMapDataType, cuuint32_t, void*, const cuuint64_t*, const cuuint64_t*,
                             const cuuint32_t*, const cuuint32_t*, CUtensorMapInterleave, CUtensorMapSwizzle,
                             CUtensorMapL2promotion, CUtensorMapFloatOOBfill);

void make_map(EncodeFn enc, CUtensorMap* m, const void* ptr, int rank, const cuuint64_t* dims, const cuuint64_t* strides,
              const cuuint32_t* box, int promo = 2, CUtensorMapSwizzle swz = CU_TENSOR_MAP_SWIZZLE_128B) {
  cuuint32_t es[5] = {1, 1, 1, 1, 1};
  enc(m, CU_TENSOR_MAP_DATA_TYPE_BFLOAT16, rank, const_cast<void*>(ptr), dims, strides, box, es,
      CU_TENSOR_MAP_INTERLEAVE_NONE, swz, promo == 2 ? CU_TENSOR_MAP_L2_PROMOTION_L2_256B : promo == 1 ? CU_TENSOR_MAP_L2_PROMOTION_L2_128B : CU_TENSOR_MAP_L2_PROMOTION_NONE,
      CU_TENSOR_MAP_FLOAT_OOB_FILL_NONE);
}

}

extern "C" void kernel_launch(void* const* d_in, const int* in_sizes, int n_in, void* d_out, int out_size) {
  (void)in_sizes; (void)n_in; (void)out_size;
  static EncodeFn enc = nullptr;
  static void* o_ptr = nullptr;
  static int n_sm = 0;
  if (!enc) {
    void* fn = nullptr;
    cudaDriverEntryPointQueryResult qr;
    cudaGetDriverEntryPoint("cuTensorMapEncodeTiled", &fn, cudaEnableDefault, &qr);
    enc = (EncodeFn)fn;
    cudaGetSymbolAddress(&o_ptr, g_o);
    cudaFuncSetAttribute(mha_fused_kernel<false>, cudaFuncAttributeMaxDynamicSharedMemorySize, SMEM_BYTES);
    cudaFuncSetAttribute(mha_fused_kernel<true>, cudaFuncAttributeMaxDynamicSharedMemorySize, SMEM_BYTES);
    int dev = 0;
    cudaGetDevice(&dev);
    cudaDeviceGetAttribute(&n_sm, cudaDevAttrMultiProcessorCount, dev);
  }
  Params P;
  for (int br = 0; br < 2; br++) {
    const void* x = d_in[br * 5 + 0]; const void* kc = d_in[br * 5 + 1]; const void* vc = d_in[br * 5 + 2];
    const void* wq = d_in[br * 5 + 3]; const void* wo = d_in[br * 5 + 4];
    { cuuint64_t d[2] = {DM, (cuuint64_t)NB * SQ}, s[1] = {DM * 2}; cuuint32_t b[2] = {64, 128 >> (DEV_HALF & 1)}, b2[2] = {64, 96 >> (DEV_HALF & 1)};
      make_map(enc, &P.x[0][br], x, 2, d, s, b, PR_X); make_map(enc, &P.x[1][br], x, 2, d, s, b2, PR_X); }
    { cuuint64_t d[3] = {64, DM, HD / 64}, s[2] = {HD * 2, 128}; cuuint32_t b[3] = {64, 64, 2}; make_map(enc, &P.wq[br], wq, 3, d, s, b, PR_W); }
    { cuuint64_t d[5] = {DM, 2, 4, 4, HD / 32}, s[4] = {DM * 2, 8 * DM * 2, 2 * DM * 2, 32 * DM * 2}; cuuint32_t b[5] = {64, 2, 4, 4, 2};
      make_map(enc, &P.wo[br], wo, 5, d, s, b, PR_W); }
    { cuuint64_t d[3] = {64, (cuuint64_t)NB * NH * SK, 2}, s[2] = {DH * 2, 128}; cuuint32_t b[3] = {64, 64, 2};
      make_map(enc, &P.kv[0][br], kc, 3, d, s, b, PR_KV); make_map(enc, &P.kv[1][br], vc, 3, d, s, b, PR_KV); }
    P.kp[br] = (const __nv_bfloat16*)kc; P.vp[br] = (const __nv_bfloat16*)vc;

  }
  { cuuint64_t d[2] = {64, (cuuint64_t)NBETA * 64 * SQ}, s[1] = {128}; cuuint32_t b[2] = {64, 128 >> (DEV_HALF >> 1)}, b2[2] = {64, 96 >> (DEV_HALF >> 1)};
    make_map(enc, &P.o_ld[0], o_ptr, 2, d, s, b, 2, CU_TENSOR_MAP_SWIZZLE_NONE); make_map(enc, &P.o_ld[1], o_ptr, 2, d, s, b2, 2, CU_TENSOR_MAP_SWIZZLE_NONE); }
  { cuuint64_t d[3] = {64, SQ, O_BLOCKS}, s[2] = {128, SQ * 128}; cuuint32_t b[3] = {64, 64, 2}, b2[3] = {64, 32, 2};
    make_map(enc, &P.o_st[0], o_ptr, 3, d, s, b); make_map(enc, &P.o_st[1], o_ptr, 3, d, s, b2); }
  { cuuint64_t d[3] = {64, (cuuint64_t)NB * SQ, 2 * DM / 64}, s[2] = {2 * DM * 2, 128}; cuuint32_t b[3] = {64, 64, 2}, b2[3] = {64, 32, 2};
    make_map(enc, &P.out_st[0], d_out, 3, d, s, b); make_map(enc, &P.out_st[1], d_out, 3, d, s, b2); }
  if (n_sm >= NCTA) mha_fused_kernel<false><<<NCTA, 384, SMEM_BYTES>>>(P);
  else mha_fused_kernel<true><<<n_sm, 384, SMEM_BYTES>>>(P);
}
```

```cpp
#include <cuda_runtime.h>
#include <cuda_bf16.h>
#include <cuda.h>
#include <stdint.h>
#include <stdlib.h>

namespace {

__device__ __forceinline__ void wgmma_proj(float (&d)[64], uint64_t da, uint64_t db, int scaleD) {
  asm volatile("{\n.reg .pred p;\nsetp.ne.b32 p, %66, 0;\n"
      "wgmma.mma_async.sync.aligned.m64n128k16.f32.bf16.bf16 "
      "{%0, %1, %2, %3, %4, %5, %6, %7, %8, %9, %10, %11, %12, %13, %14, %15, %16, %17, %18, %19, %20, %21, %22, %23, %24, %25, %26, %27, %28, %29, %30, "
      "%31, %32, %33, %34, %35, %36, %37, %38, %39, %40, %41, %42, %43, %44, %45, %46, %47, %48, %49, %50, %51, %52, %53, %54, %55, %56, %57, %58, %59, %60, "
      "%61, %62, %63}, "
      "%64, %65, p, 1, 1, 0, 1;\n}\n"
      : "+f"(d[0]), "+f"(d[1]), "+f"(d[2]), "+f"(d[3]), "+f"(d[4]), "+f"(d[5]), "+f"(d[6]), "+f"(d[7]), "+f"(d[8]), "+f"(d[9]), "+f"(d[10]), "+f"(d[11]),
        "+f"(d[12]), "+f"(d[13]), "+f"(d[14]), "+f"(d[15]), "+f"(d[16]), "+f"(d[17]), "+f"(d[18]), "+f"(d[19]), "+f"(d[20]), "+f"(d[21]), "+f"(d[22]),
        "+f"(d[23]), "+f"(d[24]), "+f"(d[25]), "+f"(d[26]), "+f"(d[27]), "+f"(d[28]), "+f"(d[29]), "+f"(d[30]), "+f"(d[31]), "+f"(d[32]), "+f"(d[33]),
        "+f"(d[34]), "+f"(d[35]), "+f"(d[36]), "+f"(d[37]), "+f"(d[38]), "+f"(d[39]), "+f"(d[40]), "+f"(d[41]), "+f"(d[42]), "+f"(d[43]), "+f"(d[44]),
        "+f"(d[45]), "+f"(d[46]), "+f"(d[47]), "+f"(d[48]), "+f"(d[49]), "+f"(d[50]), "+f"(d[51]), "+f"(d[52]), "+f"(d[53]), "+f"(d[54]), "+f"(d[55]),
        "+f"(d[56]), "+f"(d[57]), "+f"(d[58]), "+f"(d[59]), "+f"(d[60]), "+f"(d[61]), "+f"(d[62]), "+f"(d[63])
      : "l"(da), "l"(db), "r"(scaleD));
}
__device__ __forceinline__ void wgmma_proj96(float (&d)[64], uint64_t da, uint64_t db, int scaleD) {
  asm volatile("{\n.reg .pred p;\nsetp.ne.b32 p, %50, 0;\n"
      "wgmma.mma_async.sync.aligned.m64n96k16.f32.bf16.bf16 "
      "{%0, %1, %2, %3, %4, %5, %6, %7, %8, %9, %10, %11, %12, %13, %14, %15, %16, %17, %18, %19, %20, %21, %22, %23, %24, %25, %26, %27, %28, %29, %30, "
      "%31, %32, %33, %34, %35, %36, %37, %38, %39, %40, %41, %42, %43, %44, %45, %46, %47}, "
      "%48, %49, p, 1, 1, 1, 0;\n}\n"
      : "+f"(d[0]), "+f"(d[1]), "+f"(d[2]), "+f"(d[3]), "+f"(d[4]), "+f"(d[5]), "+f"(d[6]), "+f"(d[7]), "+f"(d[8]), "+f"(d[9]), "+f"(d[10]), "+f"(d[11]),
        "+f"(d[12]), "+f"(d[13]), "+f"(d[14]), "+f"(d[15]), "+f"(d[16]), "+f"(d[17]), "+f"(d[18]), "+f"(d[19]), "+f"(d[20]), "+f"(d[21]), "+f"(d[22]),
        "+f"(d[23]), "+f"(d[24]), "+f"(d[25]), "+f"(d[26]), "+f"(d[27]), "+f"(d[28]), "+f"(d[29]), "+f"(d[30]), "+f"(d[31]), "+f"(d[32]), "+f"(d[33]),
        "+f"(d[34]), "+f"(d[35]), "+f"(d[36]), "+f"(d[37]), "+f"(d[38]), "+f"(d[39]), "+f"(d[40]), "+f"(d[41]), "+f"(d[42]), "+f"(d[43]), "+f"(d[44]),
        "+f"(d[45]), "+f"(d[46]), "+f"(d[47])
      : "l"(da), "l"(db), "r"(scaleD));
}
__device__ __forceinline__ void wgmma_qk(float (&d)[32], uint64_t da, uint64_t db, int scaleD) {
  asm volatile("{\n.reg .pred p;\nsetp.ne.b32 p, %34, 0;\n"
      "wgmma.mma_async.sync.aligned.m64n64k16.f32.bf16.bf16 "
      "{%0, %1, %2, %3, %4, %5, %6, %7, %8, %9, %10, %11, %12, %13, %14, %15, %16, %17, %18, %19, %20, %21, %22, %23, %24, %25, %26, %27, %28, %29, %30, "
      "%31}, "
      "%32, %33, p, 1, 1, 0, 0;\n}\n"
      : "+f"(d[0]), "+f"(d[1]), "+f"(d[2]), "+f"(d[3]), "+f"(d[4]), "+f"(d[5]), "+f"(d[6]), "+f"(d[7]), "+f"(d[8]), "+f"(d[9]), "+f"(d[10]), "+f"(d[11]),
        "+f"(d[12]), "+f"(d[13]), "+f"(d[14]), "+f"(d[15]), "+f"(d[16]), "+f"(d[17]), "+f"(d[18]), "+f"(d[19]), "+f"(d[20]), "+f"(d[21]), "+f"(d[22]),
        "+f"(d[23]), "+f"(d[24]), "+f"(d[25]), "+f"(d[26]), "+f"(d[27]), "+f"(d[28]), "+f"(d[29]), "+f"(d[30]), "+f"(d[31])
      : "l"(da), "l"(db), "r"(scaleD));
}
__device__ __forceinline__ void wgmma_qk_rs(float (&d)[32], uint32_t a0, uint32_t a1, uint32_t a2, uint32_t a3, uint64_t db, int scaleD) {
  asm volatile("{\n.reg .pred p;\nsetp.ne.b32 p, %37, 0;\n"
      "wgmma.mma_async.sync.aligned.m64n64k16.f32.bf16.bf16 "
      "{%0, %1, %2, %3, %4, %5, %6, %7, %8, %9, %10, %11, %12, %13, %14, %15, %16, %17, %18, %19, %20, %21, %22, %23, %24, %25, %26, %27, %28, %29, %30, "
      "%31}, "
      "{%32, %33, %34, %35}, %36, p, 1, 1, 0;\n}\n"
      : "+f"(d[0]), "+f"(d[1]), "+f"(d[2]), "+f"(d[3]), "+f"(d[4]), "+f"(d[5]), "+f"(d[6]), "+f"(d[7]), "+f"(d[8]), "+f"(d[9]), "+f"(d[10]), "+f"(d[11]),
        "+f"(d[12]), "+f"(d[13]), "+f"(d[14]), "+f"(d[15]), "+f"(d[16]), "+f"(d[17]), "+f"(d[18]), "+f"(d[19]), "+f"(d[20]), "+f"(d[21]), "+f"(d[22]),
        "+f"(d[23]), "+f"(d[24]), "+f"(d[25]), "+f"(d[26]), "+f"(d[27]), "+f"(d[28]), "+f"(d[29]), "+f"(d[30]), "+f"(d[31])
      : "r"(a0), "r"(a1), "r"(a2), "r"(a3), "l"(db), "r"(scaleD));
}
__device__ __forceinline__ void wgmma_pv(float (&d)[64], uint32_t a0, uint32_t a1, uint32_t a2, uint32_t a3, uint64_t db, int scaleD) {
  asm volatile("{\n.reg .pred p;\nsetp.ne.b32 p, %69, 0;\n"
      "wgmma.mma_async.sync.aligned.m64n128k16.f32.bf16.bf16 "
      "{%0, %1, %2, %3, %4, %5, %6, %7, %8, %9, %10, %11, %12, %13, %14, %15, %16, %17, %18, %19, %20, %21, %22, %23, %24, %25, %26, %27, %28, %29, %30, "
      "%31, %32, %33, %34, %35, %36, %37, %38, %39, %40, %41, %42, %43, %44, %45, %46, %47, %48, %49, %50, %51, %52, %53, %54, %55, %56, %57, %58, %59, %60, "
      "%61, %62, %63}, "
      "{%64, %65, %66, %67}, %68, p, 1, 1, 1;\n}\n"
      : "+f"(d[0]), "+f"(d[1]), "+f"(d[2]), "+f"(d[3]), "+f"(d[4]), "+f"(d[5]), "+f"(d[6]), "+f"(d[7]), "+f"(d[8]), "+f"(d[9]), "+f"(d[10]), "+f"(d[11]),
        "+f"(d[12]), "+f"(d[13]), "+f"(d[14]), "+f"(d[15]), "+f"(d[16]), "+f"(d[17]), "+f"(d[18]), "+f"(d[19]), "+f"(d[20]), "+f"(d[21]), "+f"(d[22]),
        "+f"(d[23]), "+f"(d[24]), "+f"(d[25]), "+f"(d[26]), "+f"(d[27]), "+f"(d[28]), "+f"(d[29]), "+f"(d[30]), "+f"(d[31]), "+f"(d[32]), "+f"(d[33]),
        "+f"(d[34]), "+f"(d[35]), "+f"(d[36]), "+f"(d[37]), "+f"(d[38]), "+f"(d[39]), "+f"(d[40]), "+f"(d[41]), "+f"(d[42]), "+f"(d[43]), "+f"(d[44]),
        "+f"(d[45]), "+f"(d[46]), "+f"(d[47]), "+f"(d[48]), "+f"(d[49]), "+f"(d[50]), "+f"(d[51]), "+f"(d[52]), "+f"(d[53]), "+f"(d[54]), "+f"(d[55]),
        "+f"(d[56]), "+f"(d[57]), "+f"(d[58]), "+f"(d[59]), "+f"(d[60]), "+f"(d[61]), "+f"(d[62]), "+f"(d[63])
      : "r"(a0), "r"(a1), "r"(a2), "r"(a3), "l"(db), "r"(scaleD));
}
__device__ __forceinline__ void wgmma_qk_sp(float (&d)[32], uint32_t a0, uint32_t a1, uint32_t a2, uint32_t a3, uint64_t db, int scaleD, uint32_t meta) {
  asm volatile("{\n.reg .pred p;\nsetp.ne.b32 p, %37, 0;\n"
      "wgmma.mma_async.sp.sync.aligned.m64n64k32.f32.bf16.bf16 "
      "{%0, %1, %2, %3, %4, %5, %6, %7, %8, %9, %10, %11, %12, %13, %14, %15, %16, %17, %18, %19, %20, %21, %22, %23, %24, %25, %26, %27, %28, %29, %30, "
      "%31}, "
      "{%32, %33, %34, %35}, %36, %38, 0, p, 1, 1, 0;\n}\n"
      : "+f"(d[0]), "+f"(d[1]), "+f"(d[2]), "+f"(d[3]), "+f"(d[4]), "+f"(d[5]), "+f"(d[6]), "+f"(d[7]), "+f"(d[8]), "+f"(d[9]), "+f"(d[10]), "+f"(d[11]),
        "+f"(d[12]), "+f"(d[13]), "+f"(d[14]), "+f"(d[15]), "+f"(d[16]), "+f"(d[17]), "+f"(d[18]), "+f"(d[19]), "+f"(d[20]), "+f"(d[21]), "+f"(d[22]),
        "+f"(d[23]), "+f"(d[24]), "+f"(d[25]), "+f"(d[26]), "+f"(d[27]), "+f"(d[28]), "+f"(d[29]), "+f"(d[30]), "+f"(d[31])
      : "r"(a0), "r"(a1), "r"(a2), "r"(a3), "l"(db), "r"(scaleD), "r"(meta));
}
__device__ __forceinline__ void wgmma_pv_sp(float (&d)[64], uint32_t a0, uint32_t a1, uint32_t a2, uint32_t a3, uint64_t db, int scaleD, uint32_t meta) {
  asm volatile("{\n.reg .pred p;\nsetp.ne.b32 p, %69, 0;\n"
      "wgmma.mma_async.sp.sync.aligned.m64n128k32.f32.bf16.bf16 "
      "{%0, %1, %2, %3, %4, %5, %6, %7, %8, %9, %10, %11, %12, %13, %14, %15, %16, %17, %18, %19, %20, %21, %22, %23, %24, %25, %26, %27, %28, %29, %30, "
      "%31, %32, %33, %34, %35, %36, %37, %38, %39, %40, %41, %42, %43, %44, %45, %46, %47, %48, %49, %50, %51, %52, %53, %54, %55, %56, %57, %58, %59, %60, "
      "%61, %62, %63}, "
      "{%64, %65, %66, %67}, %68, %70, 0, p, 1, 1, 1;\n}\n"
      : "+f"(d[0]), "+f"(d[1]), "+f"(d[2]), "+f"(d[3]), "+f"(d[4]), "+f"(d[5]), "+f"(d[6]), "+f"(d[7]), "+f"(d[8]), "+f"(d[9]), "+f"(d[10]), "+f"(d[11]),
        "+f"(d[12]), "+f"(d[13]), "+f"(d[14]), "+f"(d[15]), "+f"(d[16]), "+f"(d[17]), "+f"(d[18]), "+f"(d[19]), "+f"(d[20]), "+f"(d[21]), "+f"(d[22]),
        "+f"(d[23]), "+f"(d[24]), "+f"(d[25]), "+f"(d[26]), "+f"(d[27]), "+f"(d[28]), "+f"(d[29]), "+f"(d[30]), "+f"(d[31]), "+f"(d[32]), "+f"(d[33]),
        "+f"(d[34]), "+f"(d[35]), "+f"(d[36]), "+f"(d[37]), "+f"(d[38]), "+f"(d[39]), "+f"(d[40]), "+f"(d[41]), "+f"(d[42]), "+f"(d[43]), "+f"(d[44]),
        "+f"(d[45]), "+f"(d[46]), "+f"(d[47]), "+f"(d[48]), "+f"(d[49]), "+f"(d[50]), "+f"(d[51]), "+f"(d[52]), "+f"(d[53]), "+f"(d[54]), "+f"(d[55]),
        "+f"(d[56]), "+f"(d[57]), "+f"(d[58]), "+f"(d[59]), "+f"(d[60]), "+f"(d[61]), "+f"(d[62]), "+f"(d[63])
      : "r"(a0), "r"(a1), "r"(a2), "r"(a3), "l"(db), "r"(scaleD), "r"(meta));
}
__device__ __forceinline__ void wgmma_proj_init(float (&d)[64], uint64_t da, uint64_t db, int scaleD) {
  asm volatile("{\n.reg .pred p;\nsetp.ne.b32 p, %66, 0;\n"
      "wgmma.mma_async.sync.aligned.m64n128k16.f32.bf16.bf16 "
      "{%0, %1, %2, %3, %4, %5, %6, %7, %8, %9, %10, %11, %12, %13, %14, %15, %16, %17, %18, %19, %20, %21, %22, %23, %24, %25, %26, %27, %28, %29, %30, "
      "%31, %32, %33, %34, %35, %36, %37, %38, %39, %40, %41, %42, %43, %44, %45, %46, %47, %48, %49, %50, %51, %52, %53, %54, %55, %56, %57, %58, %59, %60, "
      "%61, %62, %63}, "
      "%64, %65, p, 1, 1, 0, 1;\n}\n"
      : "=f"(d[0]), "=f"(d[1]), "=f"(d[2]), "=f"(d[3]), "=f"(d[4]), "=f"(d[5]), "=f"(d[6]), "=f"(d[7]), "=f"(d[8]), "=f"(d[9]), "=f"(d[10]), "=f"(d[11]),
        "=f"(d[12]), "=f"(d[13]), "=f"(d[14]), "=f"(d[15]), "=f"(d[16]), "=f"(d[17]), "=f"(d[18]), "=f"(d[19]), "=f"(d[20]), "=f"(d[21]), "=f"(d[22]),
        "=f"(d[23]), "=f"(d[24]), "=f"(d[25]), "=f"(d[26]), "=f"(d[27]), "=f"(d[28]), "=f"(d[29]), "=f"(d[30]), "=f"(d[31]), "=f"(d[32]), "=f"(d[33]),
        "=f"(d[34]), "=f"(d[35]), "=f"(d[36]), "=f"(d[37]), "=f"(d[38]), "=f"(d[39]), "=f"(d[40]), "=f"(d[41]), "=f"(d[42]), "=f"(d[43]), "=f"(d[44]),
        "=f"(d[45]), "=f"(d[46]), "=f"(d[47]), "=f"(d[48]), "=f"(d[49]), "=f"(d[50]), "=f"(d[51]), "=f"(d[52]), "=f"(d[53]), "=f"(d[54]), "=f"(d[55]),
        "=f"(d[56]), "=f"(d[57]), "=f"(d[58]), "=f"(d[59]), "=f"(d[60]), "=f"(d[61]), "=f"(d[62]), "=f"(d[63])
      : "l"(da), "l"(db), "r"(scaleD));
}
__device__ __forceinline__ void wgmma_proj96_init(float (&d)[64], uint64_t da, uint64_t db, int scaleD) {
  asm volatile("{\n.reg .pred p;\nsetp.ne.b32 p, %50, 0;\n"
      "wgmma.mma_async.sync.aligned.m64n96k16.f32.bf16.bf16 "
      "{%0, %1, %2, %3, %4, %5, %6, %7, %8, %9, %10, %11, %12, %13, %14, %15, %16, %17, %18, %19, %20, %21, %22, %23, %24, %25, %26, %27, %28, %29, %30, "
      "%31, %32, %33, %34, %35, %36, %37, %38, %39, %40, %41, %42, %43, %44, %45, %46, %47}, "
      "%48, %49, p, 1, 1, 1, 0;\n}\n"
      : "=f"(d[0]), "=f"(d[1]), "=f"(d[2]), "=f"(d[3]), "=f"(d[4]), "=f"(d[5]), "=f"(d[6]), "=f"(d[7]), "=f"(d[8]), "=f"(d[9]), "=f"(d[10]), "=f"(d[11]),
        "=f"(d[12]), "=f"(d[13]), "=f"(d[14]), "=f"(d[15]), "=f"(d[16]), "=f"(d[17]), "=f"(d[18]), "=f"(d[19]), "=f"(d[20]), "=f"(d[21]), "=f"(d[22]),
        "=f"(d[23]), "=f"(d[24]), "=f"(d[25]), "=f"(d[26]), "=f"(d[27]), "=f"(d[28]), "=f"(d[29]), "=f"(d[30]), "=f"(d[31]), "=f"(d[32]), "=f"(d[33]),
        "=f"(d[34]), "=f"(d[35]), "=f"(d[36]), "=f"(d[37]), "=f"(d[38]), "=f"(d[39]), "=f"(d[40]), "=f"(d[41]), "=f"(d[42]), "=f"(d[43]), "=f"(d[44]),
        "=f"(d[45]), "=f"(d[46]), "=f"(d[47])
      : "l"(da), "l"(db), "r"(scaleD));
}
__device__ __forceinline__ void wgmma_qk_init(float (&d)[32], uint64_t da, uint64_t db, int scaleD) {
  asm volatile("{\n.reg .pred p;\nsetp.ne.b32 p, %34, 0;\n"
      "wgmma.mma_async.sync.aligned.m64n64k16.f32.bf16.bf16 "
      "{%0, %1, %2, %3, %4, %5, %6, %7, %8, %9, %10, %11, %12, %13, %14, %15, %16, %17, %18, %19, %20, %21, %22, %23, %24, %25, %26, %27, %28, %29, %30, "
      "%31}, "
      "%32, %33, p, 1, 1, 0, 0;\n}\n"
      : "=f"(d[0]), "=f"(d[1]), "=f"(d[2]), "=f"(d[3]), "=f"(d[4]), "=f"(d[5]), "=f"(d[6]), "=f"(d[7]), "=f"(d[8]), "=f"(d[9]), "=f"(d[10]), "=f"(d[11]),
        "=f"(d[12]), "=f"(d[13]), "=f"(d[14]), "=f"(d[15]), "=f"(d[16]), "=f"(d[17]), "=f"(d[18]), "=f"(d[19]), "=f"(d[20]), "=f"(d[21]), "=f"(d[22]),
        "=f"(d[23]), "=f"(d[24]), "=f"(d[25]), "=f"(d[26]), "=f"(d[27]), "=f"(d[28]), "=f"(d[29]), "=f"(d[30]), "=f"(d[31])
      : "l"(da), "l"(db), "r"(scaleD));
}
__device__ __forceinline__ void wgmma_qk_rs_init(float (&d)[32], uint32_t a0, uint32_t a1, uint32_t a2, uint32_t a3, uint64_t db, int scaleD) {
  asm volatile("{\n.reg .pred p;\nsetp.ne.b32 p, %37, 0;\n"
      "wgmma.mma_async.sync.aligned.m64n64k16.f32.bf16.bf16 "
      "{%0, %1, %2, %3, %4, %5, %6, %7, %8, %9, %10, %11, %12, %13, %14, %15, %16, %17, %18, %19, %20, %21, %22, %23, %24, %25, %26, %27, %28, %29, %30, "
      "%31}, "
      "{%32, %33, %34, %35}, %36, p, 1, 1, 0;\n}\n"
      : "=f"(d[0]), "=f"(d[1]), "=f"(d[2]), "=f"(d[3]), "=f"(d[4]), "=f"(d[5]), "=f"(d[6]), "=f"(d[7]), "=f"(d[8]), "=f"(d[9]), "=f"(d[10]), "=f"(d[11]),
        "=f"(d[12]), "=f"(d[13]), "=f"(d[14]), "=f"(d[15]), "=f"(d[16]), "=f"(d[17]), "=f"(d[18]), "=f"(d[19]), "=f"(d[20]), "=f"(d[21]), "=f"(d[22]),
        "=f"(d[23]), "=f"(d[24]), "=f"(d[25]), "=f"(d[26]), "=f"(d[27]), "=f"(d[28]), "=f"(d[29]), "=f"(d[30]), "=f"(d[31])
      : "r"(a0), "r"(a1), "r"(a2), "r"(a3), "l"(db), "r"(scaleD));
}
__device__ __forceinline__ void wgmma_pv_init(float (&d)[64], uint32_t a0, uint32_t a1, uint32_t a2, uint32_t a3, uint64_t db, int scaleD) {
  asm volatile("{\n.reg .pred p;\nsetp.ne.b32 p, %69, 0;\n"
      "wgmma.mma_async.sync.aligned.m64n128k16.f32.bf16.bf16 "
      "{%0, %1, %2, %3, %4, %5, %6, %7, %8, %9, %10, %11, %12, %13, %14, %15, %16, %17, %18, %19, %20, %21, %22, %23, %24, %25, %26, %27, %28, %29, %30, "
      "%31, %32, %33, %34, %35, %36, %37, %38, %39, %40, %41, %42, %43, %44, %45, %46, %47, %48, %49, %50, %51, %52, %53, %54, %55, %56, %57, %58, %59, %60, "
      "%61, %62, %63}, "
      "{%64, %65, %66, %67}, %68, p, 1, 1, 1;\n}\n"
      : "=f"(d[0]), "=f"(d[1]), "=f"(d[2]), "=f"(d[3]), "=f"(d[4]), "=f"(d[5]), "=f"(d[6]), "=f"(d[7]), "=f"(d[8]), "=f"(d[9]), "=f"(d[10]), "=f"(d[11]),
        "=f"(d[12]), "=f"(d[13]), "=f"(d[14]), "=f"(d[15]), "=f"(d[16]), "=f"(d[17]), "=f"(d[18]), "=f"(d[19]), "=f"(d[20]), "=f"(d[21]), "=f"(d[22]),
        "=f"(d[23]), "=f"(d[24]), "=f"(d[25]), "=f"(d[26]), "=f"(d[27]), "=f"(d[28]), "=f"(d[29]), "=f"(d[30]), "=f"(d[31]), "=f"(d[32]), "=f"(d[33]),
        "=f"(d[34]), "=f"(d[35]), "=f"(d[36]), "=f"(d[37]), "=f"(d[38]), "=f"(d[39]), "=f"(d[40]), "=f"(d[41]), "=f"(d[42]), "=f"(d[43]), "=f"(d[44]),
        "=f"(d[45]), "=f"(d[46]), "=f"(d[47]), "=f"(d[48]), "=f"(d[49]), "=f"(d[50]), "=f"(d[51]), "=f"(d[52]), "=f"(d[53]), "=f"(d[54]), "=f"(d[55]),
        "=f"(d[56]), "=f"(d[57]), "=f"(d[58]), "=f"(d[59]), "=f"(d[60]), "=f"(d[61]), "=f"(d[62]), "=f"(d[63])
      : "r"(a0), "r"(a1), "r"(a2), "r"(a3), "l"(db), "r"(scaleD));
}
__device__ __forceinline__ void wgmma_qk_sp_init(float (&d)[32], uint32_t a0, uint32_t a1, uint32_t a2, uint32_t a3, uint64_t db, int scaleD, uint32_t meta) {
  asm volatile("{\n.reg .pred p;\nsetp.ne.b32 p, %37, 0;\n"
      "wgmma.mma_async.sp.sync.aligned.m64n64k32.f32.bf16.bf16 "
      "{%0, %1, %2, %3, %4, %5, %6, %7, %8, %9, %10, %11, %12, %13, %14, %15, %16, %17, %18, %19, %20, %21, %22, %23, %24, %25, %26, %27, %28, %29, %30, "
      "%31}, "
      "{%32, %33, %34, %35}, %36, %38, 0, p, 1, 1, 0;\n}\n"
      : "=f"(d[0]), "=f"(d[1]), "=f"(d[2]), "=f"(d[3]), "=f"(d[4]), "=f"(d[5]), "=f"(d[6]), "=f"(d[7]), "=f"(d[8]), "=f"(d[9]), "=f"(d[10]), "=f"(d[11]),
        "=f"(d[12]), "=f"(d[13]), "=f"(d[14]), "=f"(d[15]), "=f"(d[16]), "=f"(d[17]), "=f"(d[18]), "=f"(d[19]), "=f"(d[20]), "=f"(d[21]), "=f"(d[22]),
        "=f"(d[23]), "=f"(d[24]), "=f"(d[25]), "=f"(d[26]), "=f"(d[27]), "=f"(d[28]), "=f"(d[29]), "=f"(d[30]), "=f"(d[31])
      : "r"(a0), "r"(a1), "r"(a2), "r"(a3), "l"(db), "r"(scaleD), "r"(meta));
}
__device__ __forceinline__ void wgmma_pv_sp_init(float (&d)[64], uint32_t a0, uint32_t a1, uint32_t a2, uint32_t a3, uint64_t db, int scaleD, uint32_t meta) {
  asm volatile("{\n.reg .pred p;\nsetp.ne.b32 p, %69, 0;\n"
      "wgmma.mma_async.sp.sync.aligned.m64n128k32.f32.bf16.bf16 "
      "{%0, %1, %2, %3, %4, %5, %6, %7, %8, %9, %10, %11, %12, %13, %14, %15, %16, %17, %18, %19, %20, %21, %22, %23, %24, %25, %26, %27, %28, %29, %30, "
      "%31, %32, %33, %34, %35, %36, %37, %38, %39, %40, %41, %42, %43, %44, %45, %46, %47, %48, %49, %50, %51, %52, %53, %54, %55, %56, %57, %58, %59, %60, "
      "%61, %62, %63}, "
      "{%64, %65, %66, %67}, %68, %70, 0, p, 1, 1, 1;\n}\n"
      : "=f"(d[0]), "=f"(d[1]), "=f"(d[2]), "=f"(d[3]), "=f"(d[4]), "=f"(d[5]), "=f"(d[6]), "=f"(d[7]), "=f"(d[8]), "=f"(d[9]), "=f"(d[10]), "=f"(d[11]),
        "=f"(d[12]), "=f"(d[13]), "=f"(d[14]), "=f"(d[15]), "=f"(d[16]), "=f"(d[17]), "=f"(d[18]), "=f"(d[19]), "=f"(d[20]), "=f"(d[21]), "=f"(d[22]),
        "=f"(d[23]), "=f"(d[24]), "=f"(d[25]), "=f"(d[26]), "=f"(d[27]), "=f"(d[28]), "=f"(d[29]), "=f"(d[30]), "=f"(d[31]), "=f"(d[32]), "=f"(d[33]),
        "=f"(d[34]), "=f"(d[35]), "=f"(d[36]), "=f"(d[37]), "=f"(d[38]), "=f"(d[39]), "=f"(d[40]), "=f"(d[41]), "=f"(d[42]), "=f"(d[43]), "=f"(d[44]),
        "=f"(d[45]), "=f"(d[46]), "=f"(d[47]), "=f"(d[48]), "=f"(d[49]), "=f"(d[50]), "=f"(d[51]), "=f"(d[52]), "=f"(d[53]), "=f"(d[54]), "=f"(d[55]),
        "=f"(d[56]), "=f"(d[57]), "=f"(d[58]), "=f"(d[59]), "=f"(d[60]), "=f"(d[61]), "=f"(d[62]), "=f"(d[63])
      : "r"(a0), "r"(a1), "r"(a2), "r"(a3), "l"(db), "r"(scaleD), "r"(meta));
}

constexpr int NB = 16, SQ = 224, DM = 640, NH = 32, SK = 1024, DH = 128;
constexpr int HD = NH * DH;
constexpr int NBETA = 2 * NB;
constexpr int NCTA = 132;
constexpr int NS = 10;
constexpr int SLOT = 16384;
constexpr int QBUF_OFF = NS * SLOT;
constexpr int NSX = NS + 4;
constexpr int BAR_OFF = NSX * SLOT;
constexpr int BAR_FULL = BAR_OFF;
constexpr int BAR_EMPTY = BAR_OFF + 8 * NSX;
constexpr int BAR_STG = BAR_OFF + 16 * NSX;
constexpr int BAR_OUT = BAR_STG + 32;
constexpr int BAR_DESC = BAR_OUT + 8;
constexpr int BAR_GO = BAR_DESC + 8;
constexpr int DESC_OFF = BAR_GO + 8;
constexpr int EPOCH_OFF = DESC_OFF + 16;
constexpr int TRACE_OFF = EPOCH_OFF + 8;
constexpr int SMEM_BYTES = TRACE_OFF;
constexpr float SM_C = 0.08838834764831845f * 1.4426950408889634f;
constexpr float SUM_HI = 1099511627776.f, SUM_LO = 1.f / 1099511627776.f;
constexpr uint32_t META_QK = 0xEEEE4444u;
constexpr uint32_t META_PV = 0x44EEEE44u;

#define QK_EARLY_MASK 3
#define ST_ORDER 0x2130
#define LAG_BAR 5
#define ST_NOW 9
#define PF_STEP 5
#define KV_WIN_UNITS 2
#define KV_WIN_D 4
#define SF 0xffff
#define PRO 0
#define O_STEPS 4
#define KV_WIN_RAMP 4
#define PDEPTH 0
#define KV_WIN_TILES -2
#define PR_KV 2
#define PR_X 2
#define PR_W 2
#define REG_C 232
#define REG_P 40
#define GO_P 4
#define P_POS 224
#define B_LATE 28
#define H_LATE 24
#define EARLY_MASK 0x1fffu
#define PIECE_TABLE 0x5026401a,0x68dc4034,0x50275816,0x695a5837,0x50295015,0x6a175036,0x501e080d,0x681f083c,0x50253812,0x69d8383a,0x403f980e,0x80000000,0x5036180f,0x80000000,0x50203011,0x69993032,0x50367019,0x80000000,0x50224814,0x6a954835,0x50246017,0x6b526038,0x502c6818,0x6dc86839,0x5017b813,0x69d8b85f,0x50102810,0x685e2831,0x646e2030,0x80000000,0x501f101c,0x6dc8102f,0x5017801b,0x6c8d805e,0x6627783b,0x80000000,0x6627b033,0x80000000,0x501a901e,0x80000000,0x56d6881e,0x80000000,0x501ca81d,0x80000000,0x6762a03d,0x80000000,0x67e0002d,0x80000000,0x5512c01f,0x80000000,0x5013c81f,0x80000000

struct Params {
  CUtensorMap x[2][2], wq[2], kv[2][2], wo[2];
  CUtensorMap o_ld[2], o_st[2], out_st[2];
  const __nv_bfloat16* kp[2];
  const __nv_bfloat16* vp[2];
};

constexpr int NPART = 32 * 5, O_BLOCKS = NBETA * 64 + 2 * NPART;
__device__ __align__(128) __nv_bfloat16 g_o[(size_t)O_BLOCKS * SQ * 64];
__device__ unsigned g_cnt[2][NBETA];
__device__ unsigned g_epoch, g_next;
__device__ unsigned g_flag[NPART];

__device__ __forceinline__ uint32_t smem_u32(const void* p) { return (uint32_t)__cvta_generic_to_shared(p); }
__device__ __forceinline__ void mbar_arrive(uint32_t bar) {
  asm volatile("mbarrier.arrive.shared::cta.b64 _, [%0];" ::"r"(bar) : "memory");
}
__device__ __forceinline__ void mbar_arrive_warp(uint32_t bar) {
  asm volatile("{\n.reg .pred p;\nelect.sync _|p, 0xffffffff;\n@p mbarrier.arrive.shared::cta.b64 _, [%0];\n}" ::"r"(bar) : "memory");
}
__device__ __forceinline__ int lane_now() { int l; asm volatile("mov.u32 %0, %%laneid;" : "=r"(l)); return l; }
__device__ __forceinline__ bool mbar_try(uint32_t bar, uint32_t parity) {
  uint32_t ok;
  asm volatile("{\n.reg .pred p;\nmbarrier.try_wait.parity.shared::cta.b64 p, [%1], %2;\nselp.u32 %0, 1, 0, p;\n}"
               : "=r"(ok) : "r"(bar), "r"(parity) : "memory");
  return ok;
}
__device__ __forceinline__ bool mbar_test(uint32_t bar, uint32_t parity) {
  uint32_t ok;
  asm volatile("{\n.reg .pred p;\nmbarrier.test_wait.parity.shared::cta.b64 p, [%1], %2;\nselp.u32 %0, 1, 0, p;\n}"
               : "=r"(ok) : "r"(bar), "r"(parity) : "memory");
  return ok;
}
__device__ __forceinline__ void mbar_wait_w(uint32_t bar, uint32_t parity) {
  uint32_t n = 0;
  while (!__all_sync(0xffffffffu, mbar_try(bar, parity))) {
    if (++n > (1u << 22)) __trap();
  }
}
#define ELECT "{\n.reg .pred p;\nelect.sync _|p, 0xffffffff;\n@p "
__device__ __forceinline__ void tma_st3_hint_w(const CUtensorMap* m, uint32_t src, int c0, int c1, int c2, uint64_t pol) {
  asm volatile(ELECT "cp.async.bulk.tensor.3d.global.shared::cta.bulk_group.L2::cache_hint [%0, {%2, %3, %4}], [%1], %5;\n}"
               ::"l"(m), "r"(src), "r"(c0), "r"(c1), "r"(c2), "l"(pol) : "memory");
}
#define EXPECT(bar, bytes) "mbarrier.arrive.expect_tx.shared::cta.b64 _, [" bar "], " bytes ";\n@p "
__device__ __forceinline__ void tma_ld2_w(uint32_t dst, const CUtensorMap* m, int c0, int c1, uint32_t bar, uint32_t bytes) {
  asm volatile(ELECT EXPECT("%2", "%5") "cp.async.bulk.tensor.2d.shared::cluster.global.mbarrier::complete_tx::bytes [%0], [%1, {%3, %4}], [%2];\n}"
               ::"r"(dst), "l"(m), "r"(bar), "r"(c0), "r"(c1), "r"(bytes) : "memory");
}
__device__ __forceinline__ void tma_ld2_hint_w(uint32_t dst, const CUtensorMap* m, int c0, int c1, uint32_t bar, uint32_t bytes, uint64_t pol) {
  asm volatile(ELECT EXPECT("%2", "%6") "cp.async.bulk.tensor.2d.shared::cluster.global.mbarrier::complete_tx::bytes.L2::cache_hint"
               " [%0], [%1, {%3, %4}], [%2], %5;\n}"
               ::"r"(dst), "l"(m), "r"(bar), "r"(c0), "r"(c1), "l"(pol), "r"(bytes) : "memory");
}
__device__ __forceinline__ void tma_ld3_w(uint32_t dst, const CUtensorMap* m, int c0, int c1, int c2, uint32_t bar, uint32_t bytes) {
  asm volatile(ELECT EXPECT("%2", "%6") "cp.async.bulk.tensor.3d.shared::cluster.global.mbarrier::complete_tx::bytes [%0], [%1, {%3, %4, %5}], [%2];\n}"
               ::"r"(dst), "l"(m), "r"(bar), "r"(c0), "r"(c1), "r"(c2), "r"(bytes) : "memory");
}
__device__ __forceinline__ void tma_ld3_hint_w(uint32_t dst, const CUtensorMap* m, int c0, int c1, int c2, uint32_t bar, uint64_t pol) {
  asm volatile(ELECT EXPECT("%2", "16384") "cp.async.bulk.tensor.3d.shared::cluster.global.mbarrier::complete_tx::bytes.L2::cache_hint"
               " [%0], [%1, {%3, %4, %5}], [%2], %6;\n}"
               ::"r"(dst), "l"(m), "r"(bar), "r"(c0), "r"(c1), "r"(c2), "l"(pol) : "memory");
}
__device__ __forceinline__ void tma_ld_wo_w(uint32_t dst, const CUtensorMap* m, int col, int grp, uint32_t bar) {
  asm volatile(ELECT EXPECT("%2", "16384") "cp.async.bulk.tensor.5d.shared::cluster.global.mbarrier::complete_tx::bytes [%0], [%1, {%3, 0, 0, 0, %4}], [%2];\n"
               "@p cp.async.bulk.tensor.5d.shared::cluster.global.mbarrier::complete_tx::bytes [%5], [%1, {%6, 0, 0, 0, %4}], [%2];\n}"
               ::"r"(dst), "l"(m), "r"(bar), "r"(col), "r"(grp), "r"(dst + 8192), "r"(col + 64) : "memory");
}
__device__ __forceinline__ void mbar_arrive8_w(uint32_t bar) {
  asm volatile(ELECT "mbarrier.arrive.shared::cta.b64 _, [%0], 8;\n}" ::"r"(bar) : "memory");
}
__device__ __forceinline__ void bulk_commit() { asm volatile("cp.async.bulk.commit_group;" ::: "memory"); }
template <int N> __device__ __forceinline__ void bulk_wait_read() { asm volatile("cp.async.bulk.wait_group.read %0;" ::"n"(N) : "memory"); }
__device__ __forceinline__ void wg_fence() { asm volatile("wgmma.fence.sync.aligned;" ::: "memory"); }
__device__ __forceinline__ void wg_commit() { asm volatile("wgmma.commit_group.sync.aligned;" ::: "memory"); }
template <int N> __device__ __forceinline__ void wg_wait() { asm volatile("wgmma.wait_group.sync.aligned %0;" ::"n"(N) : "memory"); }
__device__ __forceinline__ void fence_async_smem() { asm volatile("fence.proxy.async.shared::cta;" ::: "memory"); }
__device__ __forceinline__ void bar_sync(int id, int n) { asm volatile("bar.sync %0, %1;" ::"r"(id), "r"(n) : "memory"); }
__device__ __forceinline__ void touch(float& a) { asm volatile("neg.f32 %0, %0;" : "+f"(a)); }
__device__ __forceinline__ void touch(uint32_t& a) { asm volatile("not.b32 %0, %0;" : "+r"(a)); }
template <typename T, int N> __device__ __forceinline__ void touch(T (&a)[N]) {
#pragma unroll
  for (int i = 0; i < N; i++) touch(a[i]);
}
template <int ID, typename... A> __device__ __forceinline__ void sched_fence(uint32_t x, A&... a) {
  if (!((SF >> ID) & 1)) return;
  asm volatile("" : "+r"(x)::"memory");
#pragma unroll 1
  for (; __builtin_expect(x >= 100 + ID, 0); x >>= 1) (touch(a), ...);
}
template <int N> __device__ __forceinline__ void reg_fence(float (&a)[N]) {
#pragma unroll
  for (int i = 0; i < N; i++) asm volatile("" : "+f"(a[i])::"memory");
}
template <int N> __device__ __forceinline__ void reg_fence(uint32_t (&a)[N]) {
#pragma unroll
  for (int i = 0; i < N; i++) asm volatile("" : "+r"(a[i])::"memory");
}
__device__ __forceinline__ float ex2(float x) { float y; asm("ex2.approx.ftz.f32 %0, %1;" : "=f"(y) : "f"(x)); return y; }
__device__ __forceinline__ uint32_t pack_bf16(float lo, float hi) {
  uint32_t r; asm("cvt.rn.bf16x2.f32 %0, %1, %2;" : "=r"(r) : "f"(hi), "f"(lo)); return r;
}
__device__ __forceinline__ void stsm4(uint32_t a, uint32_t r0, uint32_t r1, uint32_t r2, uint32_t r3) {
  asm volatile("stmatrix.sync.aligned.m8n8.x4.shared.b16 [%0], {%1, %2, %3, %4};" ::"r"(a), "r"(r0), "r"(r1), "r"(r2), "r"(r3) : "memory");
}
__device__ __forceinline__ void stsm4t(uint32_t a, uint32_t r0, uint32_t r1, uint32_t r2, uint32_t r3) {
  asm volatile("stmatrix.sync.aligned.m8n8.x4.trans.shared.b16 [%0], {%1, %2, %3, %4};" ::"r"(a), "r"(r0), "r"(r1), "r"(r2), "r"(r3) : "memory");
}
__device__ __forceinline__ void ldsm4(uint32_t a, uint32_t& r0, uint32_t& r1, uint32_t& r2, uint32_t& r3) {
  asm volatile("ldmatrix.sync.aligned.m8n8.x4.shared.b16 {%0, %1, %2, %3}, [%4];" : "=r"(r0), "=r"(r1), "=r"(r2), "=r"(r3) : "r"(a) : "memory");
}
__device__ __forceinline__ void sts16(uint32_t a, uint32_t v) { asm volatile("st.shared.u16 [%0], %1;" ::"r"(a), "h"((uint16_t)v) : "memory"); }
__device__ __forceinline__ void mma16816(float& c0, float& c1, float& c2, float& c3, uint32_t a0, uint32_t a1, uint32_t a2, uint32_t a3,
                                         uint32_t b0, uint32_t b1) {
  asm volatile("mma.sync.aligned.m16n8k16.row.col.f32.bf16.bf16.f32 {%0, %1, %2, %3}, {%4, %5, %6, %7}, {%8, %9}, {%0, %1, %2, %3};"
               : "+f"(c0), "+f"(c1), "+f"(c2), "+f"(c3) : "r"(a0), "r"(a1), "r"(a2), "r"(a3), "r"(b0), "r"(b1));
}
__device__ __forceinline__ uint32_t sdesc(uint32_t addr, uint32_t lbo) { return (addr >> 4) + ((lbo >> 4) << 16); }
__device__ __forceinline__ uint64_t desc64(uint32_t lo, uint32_t hi) { uint64_t d; asm("mov.b64 %0, {%1, %2};" : "=l"(d) : "r"(lo), "r"(hi)); return d; }
__device__ __forceinline__ void dadd(uint64_t& d, uint32_t inc) {
  asm("{\n.reg .b32 l, h;\nmov.b64 {l, h}, %0;\nadd.u32 l, l, %1;\nmov.b64 %0, {l, h};\n}" : "+l"(d) : "r"(inc));
}

struct Ring {
  uint32_t slot, phase, xp;
  __device__ __forceinline__ void uniform() {
    slot = __shfl_sync(0xffffffffu, slot, 0); phase = __shfl_sync(0xffffffffu, phase, 0); xp = __shfl_sync(0xffffffffu, xp, 0);
  }
  __device__ __forceinline__ void next() { if (++slot == NS) { slot = 0; phase ^= 1; } }
  __device__ __forceinline__ void next_if(bool p) { slot += p; if (slot == NS) { slot = 0; phase ^= 1; } }
};
__device__ __forceinline__ uint32_t borrow(int ks, int n) {
  const int k = ks + 1;
  return k >= 4 && !(k & 2) && k < n ? k & 1 : 2;
}

constexpr uint32_t Q_RANGES = NBETA * NH + __builtin_popcount(EARLY_MASK) * 5, Q_ALL = NBETA * (NH + 5);
constexpr int NRANGE = NCTA / 5;
struct Work { int kind, mode, k0, nsteps, range, beta, sub; };
struct Sched { uint16_t queue[Q_ALL]; uint32_t piece[NRANGE + 1][4]; };
constexpr Sched make_sched() {
  Sched s{};
  int q = 0, a = 0;
  for (int pass = 0; pass < 2; pass++)
    for (int b = pass ? B_LATE : 0; b < NBETA; b++)
      for (int h = pass ? H_LATE : 0; h < (pass || b < B_LATE ? NH : H_LATE); h++) {
        if (a >= P_POS && (a - P_POS) % 32 == 0 && (EARLY_MASK >> ((a - P_POS) / 32) & 1))
          for (int col = 0; col < 5; col++) s.queue[q++] = 0x8000 | col << 8 | (a - P_POS) / 32;
        s.queue[q++] = b << 5 | h;
        a++;
      }
  for (int b = 0; b < NBETA; b++)
    for (int col = 0; col < 5 && !(EARLY_MASK >> b & 1); col++) s.queue[q++] = 0x8000 | col << 8 | b;
  constexpr uint32_t T[NRANGE * 2] = {PIECE_TABLE};
  for (int g = 0; g <= NRANGE; g++)
    for (int n = 0; n < 4; n++) s.piece[g][n] = g < NRANGE && n < 2 ? T[2 * g + n] : 2u << 30;
  return s;
}
__constant__ Sched c_sched = make_sched();
__device__ __forceinline__ Work decode(uint32_t d) {
  Work w;
  w.kind = d >> 30; if (w.kind == 3) w.kind = 1;
  w.mode = (d >> 28) & 3; w.k0 = (d >> 22) & 63;
  if (w.kind == 0) { w.beta = (d >> 5) & 31; w.sub = d & 31; w.nsteps = DM / 64; }
  else { w.beta = d & 31; w.sub = (d >> 8) & 7; w.nsteps = ((d >> 16) & 63) + 1; }
  w.range = ((d >> 11) & 31) * 5 + w.sub;
  return w;
}

__device__ __forceinline__ bool reached(const unsigned* cnt, unsigned target) {
  unsigned v;
  asm volatile("ld.acquire.gpu.global.u32 %0, [%1];" : "=r"(v) : "l"(cnt) : "memory");
  return (int)(v - target) >= 0;
}
__device__ __forceinline__ void wait_count(const unsigned* cnt, unsigned target) {
  unsigned n = 0;
  while (!__all_sync(0xffffffffu, reached(cnt, target))) { if (++n > (1u << 24)) __trap(); }
}
__device__ __forceinline__ uint32_t lds(uint32_t a) { uint32_t v; asm volatile("ld.volatile.shared.u32 %0, [%1];" : "=r"(v) : "r"(a) : "memory"); return v; }

#define TRACE(u, e)
#define T3(u, e)
#define T2C(u, e)
#define T2P(u, r, e)
#define TTAIL(k)
#define TCLK(k)
#define TRACE_P(u, e)
#define TRACE_IN(u, e)

struct Ctx {
  uint32_t sb;
  int wg, warp;
  uint32_t mqk, mpv;
  bool lead;
  int src;
};
template <int N> __device__ __forceinline__ uint32_t dhi(uint32_t lo) { return 0x40000040u + (lo >> (26 + N)); }
__device__ __forceinline__ void release(const Ctx& c, uint32_t slot) {
  if (c.lead) mbar_arrive(c.sb + BAR_EMPTY + slot * 8);
}
__device__ __forceinline__ uint32_t acquire(const Ctx& c, Ring& r) {
  const uint32_t s = r.slot;
  mbar_wait_w(c.sb + BAR_FULL + s * 8, r.phase);
  r.next();
  return s;
}
__device__ __forceinline__ void mbar_wait2_w(uint32_t b0, uint32_t p0, uint32_t b1, uint32_t p1) {
  uint32_t n = 0;
  while (!__all_sync(0xffffffffu, mbar_try(b0, p0) & mbar_try(b1, p1))) {
    if (++n > (1u << 22)) __trap();
  }
}
__device__ __forceinline__ void mbar_wait3_w(uint32_t b0, uint32_t p0, uint32_t b1, uint32_t p1, uint32_t b2, uint32_t p2) {
  uint32_t n = 0;
  while (!__all_sync(0xffffffffu, mbar_try(b0, p0) & mbar_try(b1, p1) & mbar_try(b2, p2))) {
    if (++n > (1u << 22)) __trap();
  }
}
__device__ __forceinline__ void acquire2(const Ctx& c, Ring& r, uint32_t& s0, uint32_t& s1) {
  const uint32_t p0 = r.phase;
  s0 = r.slot; r.next(); s1 = r.slot;
  mbar_wait2_w(c.sb + BAR_FULL + s0 * 8, p0, c.sb + BAR_FULL + s1 * 8, r.phase);
  r.next();
}
template <int N>
__device__ __forceinline__ bool peek(const Ctx& c, Ring r) {
  bool ok = true;
#pragma unroll
  for (int k = 0; k < N; k++) { ok &= mbar_test(c.sb + BAR_FULL + r.slot * 8, r.phase); r.next(); }
  return ok;
}
__device__ __forceinline__ void staged(const Ctx& c, int part) {
  fence_async_smem();
  __syncwarp();
  mbar_arrive_warp(c.sb + BAR_STG + c.wg * 16 + part * 8);
}

template <int WG, bool FIRST, int H>
__device__ __forceinline__ void proj_half(const Ctx& c, float (&acc)[64], uint32_t w, uint32_t x, uint32_t sw) {
  uint64_t dx = desc64((c.sb + x * SLOT + (WG ? 0 : H * 8192)) >> 4, dhi<0>(x) + sw);
  uint64_t dw = desc64(WG ? (c.sb + w * SLOT + H * 8192) >> 4 : sdesc(c.sb + w * SLOT, 8192), dhi<1>(x));
  wg_fence();
  if (WG) { if (FIRST) wgmma_proj96_init(acc, dw, dx, 0); else wgmma_proj96(acc, dw, dx, 1); }
  else { if (FIRST) wgmma_proj_init(acc, dx, dw, 0); else wgmma_proj(acc, dx, dw, 1); }
#pragma unroll
  for (int k = 1; k < 4; k++) {
    dadd(dx, k == 2 ? 2 + (sw >> 30) * 28 : 2); dadd(dw, 128);
    if (WG) wgmma_proj96(acc, dw, dx, 1); else wgmma_proj(acc, dx, dw, 1);
  }
  wg_commit();
}

__device__ __forceinline__ void proj_store16(uint32_t a, const float* f, float sc) {
  stsm4t(a, pack_bf16(f[0] * sc, f[1] * sc), pack_bf16(f[2] * sc, f[3] * sc), pack_bf16(f[4] * sc, f[5] * sc), pack_bf16(f[6] * sc, f[7] * sc));
}

__device__ __forceinline__ uint32_t stage_off(const Ctx& c) {
  const int lane = lane_now(), mi = lane >> 3, r8 = lane & 7;
  return ((mi >> 1) * 8 + r8) * 128 + (((2 * c.warp + (mi & 1)) ^ r8) << 4);
}
__device__ __forceinline__ uint32_t q3_swz(uint32_t r8) { return ((r8 & 3) << 1) | (r8 >> 2); }
template <int H>
__device__ __forceinline__ void stage_t2(const Ctx& c, const float (&a)[64], float sc) {
  const uint32_t base = c.sb + QBUF_OFF + 2 * 16384 + H * 8192 + stage_off(c);
#pragma unroll
  for (int jj = 0; jj < 4; jj++) proj_store16(base + jj * 2048, &a[jj * 8], sc);
}
template <int H, bool IS_Q>
__device__ __forceinline__ void stage_t3(const Ctx& c, const float (&a)[64], float sc) {
  const uint32_t off = stage_off(c), r8 = (off >> 7) & 7;
  const uint32_t t3 = c.sb + QBUF_OFF + 3 * 16384 + H * 4096 + (IS_Q ? off ^ ((r8 ^ q3_swz(r8)) << 4) : off);
  proj_store16(t3, &a[32], sc);
  proj_store16(t3 + 2048, &a[40], sc);
}

template <bool TRANS>
__device__ __forceinline__ void add16(uint32_t a, float* f) {
  uint32_t r[4];
  if (TRANS) asm volatile("ldmatrix.sync.aligned.m8n8.x4.trans.shared.b16 {%0, %1, %2, %3}, [%4];"
                          : "=r"(r[0]), "=r"(r[1]), "=r"(r[2]), "=r"(r[3]) : "r"(a) : "memory");
  else ldsm4(a, r[0], r[1], r[2], r[3]);
#pragma unroll
  for (int i = 0; i < 4; i++) { f[2 * i] += __uint_as_float(r[i] << 16); f[2 * i + 1] += __uint_as_float(r[i] & 0xffff0000u); }
}

__device__ __forceinline__ void trace_dump(const Ctx& c) {
}
struct RowSum { float l0, l1; };
__device__ __forceinline__ const char* o_addr(uint32_t item, int row) {
  const int lane = lane_now();
  return reinterpret_cast<const char*>(g_o) + ((item * (2 * SQ) + row) * 128 + (lane ^ (lane >> 3)) * 16);
}
__device__ __forceinline__ void o_stg(const char* p, int i, const uint32_t* q) {
  asm volatile("st.global.v4.b32 [%0], {%1, %2, %3, %4};"
               ::"l"(p + (i >> 1) * (SQ * 128) + (i & 1) * 512), "r"(q[0]), "r"(q[1]), "r"(q[2]), "r"(q[3]) : "memory");
}
template <int MODE, int I0 = 0, int NI = 4>
__device__ __forceinline__ void o_emit(const char* p, const float (&o)[64], float inv) {
#pragma unroll
  for (int i = I0; i < I0 + NI; i++) {
    uint32_t q[4];
#pragma unroll
    for (int j = 0; j < 4; j++) q[j] = pack_bf16(o[16 * i + 4 * j + 2 * MODE] * inv, o[16 * i + 4 * j + 2 * MODE + 1] * inv);
    o_stg(p, i, q);
  }
}
__device__ __forceinline__ void o_done(const Ctx& c) {
  __syncwarp();
  mbar_arrive_warp(c.sb + BAR_OUT);
  __syncwarp();
}
template <int WG>
__device__ __forceinline__ void o_first(const Ctx& c, uint32_t item, float (&o)[64], const RowSum& inv) {
  const char* p = o_addr(item, WG ? 192 + 8 * c.warp : 64 + 16 * c.warp);
  reg_fence(o);
  if (WG) {
    uint32_t q[16];
#pragma unroll
    for (int j = 0; j < 16; j++) q[j] = pack_bf16((o[4 * j] + o[4 * j + 2]) * inv.l0, (o[4 * j + 1] + o[4 * j + 3]) * inv.l0);
#pragma unroll
    for (int i = 0; i < 4; i++) o_stg(p, i, q + 4 * i);
  } else { o_emit<0>(p, o, inv.l0); o_emit<1>(p + 1024, o, inv.l1); }
}
template <int K0, int K1>
__device__ __forceinline__ void o_piece(const Ctx& c, const char* p, int k, const float (&o)[64], const RowSum& inv) {
  constexpr int NI = 8 / O_STEPS, M = K0 * NI / 4;
  if constexpr (K1 - K0 == 1) {
    o_emit<M, K0 * NI % 4, NI>(p + M * 1024, o, M ? inv.l1 : inv.l0);
    if (K1 == O_STEPS) o_done(c);
  } else {
    if (k <= (K0 + K1) / 2) o_piece<K0, (K0 + K1) / 2>(c, p, k, o, inv); else o_piece<(K0 + K1) / 2, K1>(c, p, k, o, inv);
  }
}
template <int WG>
__device__ __forceinline__ void o_second(const Ctx& c, uint32_t item, int k, float (&o)[64], const RowSum& inv) {
  reg_fence(o);
  o_piece<0, O_STEPS>(c, o_addr(item, 128 * WG + 16 * c.warp), k, o, inv);
}
template <int WG>
__device__ __forceinline__ void release_q(const Ctx& c) {
#pragma unroll
  for (int t = 0; t < 2; t++)
    if (c.lead) asm volatile("mbarrier.arrive.shared::cta.b64 _, [%0], 2;" ::"r"(c.sb + BAR_EMPTY + (NS + 2 * WG + t) * 8) : "memory");
  __syncwarp();
}
struct Slots { uint32_t w, x, o, po; };
template <int WG>
__device__ __forceinline__ void acc_fence(float (&a)[64]) {
#pragma unroll
  for (int i = 0; i < (WG ? 48 : 64); i++) asm volatile("" : "+f"(a[i])::"memory");
}
template <int WG>
__device__ __forceinline__ void begin_acquire(const Ctx& c, Ring& r, Slots& h, bool wait) {
  const uint32_t s0 = r.slot, p0 = r.phase, f = c.sb + BAR_FULL;
  r.next();
  const uint32_t p1 = r.phase;
  h.w = r.slot; r.next();
  h.x = WG ? r.slot : s0; h.o = WG ? s0 : r.slot; h.po = r.phase;
  if (wait) { if (WG) mbar_wait3_w(f + s0 * 8, p0, f + h.w * 8, p1, f + h.x * 8, r.phase); else mbar_wait2_w(f + s0 * 8, p0, f + h.w * 8, p1); }
  r.next();
}
template <int WG>
__device__ __forceinline__ void proj_begin(const Ctx& c, Ring& r, float (&a0)[64], Slots& h, bool wait, uint32_t sw) {
  begin_acquire<WG>(c, r, h, wait);
  proj_half<WG, true, 0>(c, a0, h.w, h.x, sw);
  if (WG) release(c, h.o);
}
template <int WG>
__device__ __forceinline__ void proj_main(const Ctx& c, Ring& r, float (&a0)[64], float (&a1)[64], Slots& h, int n, uint32_t sw, int unit,
                                          uint32_t item, int nq, float (&o1)[64], const RowSum& inv) {
  constexpr bool DEEP = (PDEPTH >> WG) & 1;
  T2C(unit, 3);
  int ks = 1;
#pragma unroll 1
  do {
    const Slots p = h;
    const uint32_t b = borrow(ks, n), tile = NS + (WG ? 3 - b : b), f = c.sb + BAR_FULL;
    const uint32_t s0 = b != 2 ? tile : r.slot, p0 = b != 2 ? (r.xp >> b) & 1 : r.phase;
    r.next_if(b == 2);
    const uint32_t p1 = r.phase;
    h.w = r.slot; r.next();
    const uint32_t s2 = b != 2 ? tile : r.slot;
    h.po = b != 2 ? p0 : r.phase;
    r.next_if(b == 2);
    r.xp ^= 1 << b;
    h.x = WG ? s2 : s0; h.o = WG ? s0 : s2;
    mbar_wait3_w(f + s0 * 8, p0, f + h.w * 8, p1, f + (WG ? s2 : p.o) * 8, WG ? h.po : p.po);
    if (ks < 10) T2C(unit, ks * 4);
    if (DEEP) {
      proj_half<WG, false, 0>(c, a0, h.w, h.x, sw);
      release(c, WG ? h.o : p.o);
      if (ks < 10) T2C(unit, ks * 4 + 1);
      wg_wait<1>();
      if (ks < 10) T2C(unit, ks * 4 + 2);
      release(c, p.x); release(c, p.w);
    } else {
      release(c, WG ? h.o : p.o);
      wg_wait<0>();
      release(c, p.x); release(c, p.w);
      if (ks < 10) T2C(unit, ks * 4 + 1);
      proj_half<WG, false, 0>(c, a0, h.w, h.x, sw);
      if (ks < 10) T2C(unit, ks * 4 + 2);
    }
    proj_half<WG, false, 1>(c, a1, h.w, h.x, sw);
    if (ks < 10) T2C(unit, ks * 4 + 3);
    if (ks <= nq) o_second<WG>(c, item, ks, o1, inv);
  } while (++ks != n);
  {
    const uint32_t e0 = c.sb + BAR_EMPTY + (NS + 3 * WG) * 8, e1 = c.sb + BAR_EMPTY + (NS + 1 + WG) * 8;
    const uint32_t p0 = (r.xp ^ unit ^ 1) & 1, p1 = ((r.xp >> 1) ^ unit ^ 1) & 1;
    if (WG) mbar_wait2_w(e0, p0, e1, p1); else mbar_wait3_w(e0, p0, e1, p1, c.sb + BAR_FULL + h.o * 8, h.po);
  }
  if (!WG) release(c, h.o);
  wg_wait<1>();
  acc_fence<WG>(a0);
}
template <int WG>
__device__ __forceinline__ void proj_end(const Ctx& c, float (&a1)[64], const Slots& h) {
  wg_wait<0>();
  acc_fence<WG>(a1);
  release(c, h.x); release(c, h.w);
}
__device__ __forceinline__ uint32_t get_desc(const Ctx& c, int i) {
  uint32_t d;
  mbar_wait_w(c.sb + BAR_DESC, (i - 1) & 1);
  asm volatile("ld.volatile.shared.u32 %0, [%1];" : "=r"(d) : "r"(c.sb + DESC_OFF + (i & 3) * 4) : "memory");
  return __shfl_sync(0xffffffffu, d, 0);
}

__device__ __forceinline__ float quad_max(float x) {
  x = fmaxf(x, __shfl_xor_sync(0xffffffffu, x, 1));
  return fmaxf(x, __shfl_xor_sync(0xffffffffu, x, 2));
}
__device__ __forceinline__ float quad_sum(float x) {
  x += __shfl_xor_sync(0xffffffffu, x, 1);
  return x + __shfl_xor_sync(0xffffffffu, x, 2);
}
template <bool SP, bool FIRST>
__device__ __forceinline__ void exps(const Ctx& c, const float (&s)[32], uint32_t (&p)[SP ? 8 : 16], RowSum& st) {
  if constexpr (SP) {
    uint32_t q[8];
    float t;
#pragma unroll
    for (int j = 0; j < 8; j++) {
      const float e0 = ex2(s[4 * j] + s[4 * j + 2]), e1 = ex2(s[4 * j + 1] + s[4 * j + 3]);
      if (j == 0) t = e0 + e1; else t += e0 + e1;
      q[j] = pack_bf16(e0, e1);
    }
    const bool odd = c.src & 2;
#pragma unroll
    for (int g = 0; g < 4; g++) {
      p[2 * g] = __shfl_sync(0xffffffffu, odd ? q[2 * g + 1] : q[2 * g], c.src);
      p[2 * g + 1] = __shfl_sync(0xffffffffu, odd ? q[2 * g] : q[2 * g + 1], c.src ^ 1);
    }
    st.l0 = FIRST ? t : st.l0 + t;
  } else {
    float t0, t1;
#pragma unroll
    for (int j = 0; j < 8; j++) {
      const float e0 = ex2(s[4 * j]), e1 = ex2(s[4 * j + 1]), e2 = ex2(s[4 * j + 2]), e3 = ex2(s[4 * j + 3]);
      if (j == 0) { t0 = e0 + e1; t1 = e2 + e3; } else { t0 += e0 + e1; t1 += e2 + e3; }
      p[2 * j] = pack_bf16(e0, e1);
      p[2 * j + 1] = pack_bf16(e2, e3);
    }
    st.l0 = FIRST ? t0 : st.l0 + t0;
    st.l1 = FIRST ? t1 : st.l1 + t1;
  }
}
template <bool SP>
__device__ __forceinline__ bool finish_sums(RowSum& st) {
  const float a = quad_sum(st.l0), b = SP ? a : quad_sum(st.l1);
  st.l0 = __fdividef(1.f, a); st.l1 = __fdividef(1.f, b);
  return !(a >= SUM_LO && a <= SUM_HI && b >= SUM_LO && b <= SUM_HI);
}
template <bool SP, bool INIT, int SITE, bool COMMIT = true>
__device__ __forceinline__ void issue_qk(const Ctx& c, float (&s)[32], const uint32_t (&qs)[16], uint32_t dq, uint32_t dk) {
  uint64_t a = desc64(dq, dhi<SITE & 1>(dk)), b = desc64(dk, dhi<1 - (SITE & 1)>(dk));
  if (SP) {
    if (INIT) wgmma_qk_sp_init(s, qs[0], qs[1], qs[2], qs[3], b, 0, c.mqk); else wgmma_qk_sp(s, qs[0], qs[1], qs[2], qs[3], b, 0, c.mqk);
#pragma unroll
    for (int k = 1; k < 4; k++) { dadd(b, k == 2 ? 508 : 4); wgmma_qk_sp(s, qs[4 * k], qs[4 * k + 1], qs[4 * k + 2], qs[4 * k + 3], b, 1, c.mqk); }
  } else {
    if (INIT) wgmma_qk_init(s, a, b, 0); else wgmma_qk(s, a, b, 0);
#pragma unroll
    for (int k = 1; k < 8; k++) { dadd(a, k == 4 ? 506 : 2); dadd(b, k == 4 ? 506 : 2); wgmma_qk(s, a, b, 1); }
  }
  if (COMMIT) wg_commit();
}
template <bool SP, bool ACC, int SITE, bool SPLIT = false>
__device__ __forceinline__ void issue_pv(const Ctx& c, float (&o)[64], const uint32_t (&p)[SP ? 8 : 16], uint32_t dv) {
  uint64_t b = desc64(dv, dhi<SITE & 1>(dv));
  if constexpr (SP) {
    if (ACC) wgmma_pv_sp(o, p[0], p[1], p[2], p[3], b, 1, c.mpv); else wgmma_pv_sp_init(o, p[0], p[1], p[2], p[3], b, 0, c.mpv);
    if (SPLIT) wg_commit();
    dadd(b, 256);
    wgmma_pv_sp(o, p[4], p[5], p[6], p[7], b, 1, c.mpv);
  } else {
    if (ACC) wgmma_pv(o, p[0], p[1], p[2], p[3], b, 1); else wgmma_pv_init(o, p[0], p[1], p[2], p[3], b, 0);
#pragma unroll
    for (int k = 1; k < 4; k++) { dadd(b, 128); wgmma_pv(o, p[4 * k], p[4 * k + 1], p[4 * k + 2], p[4 * k + 3], b, 1); }
  }
  wg_commit();
}
__device__ __forceinline__ void pack_rows(const float (&o)[64], float sc, uint32_t (&q)[32]) {
#pragma unroll
  for (int j = 0; j < 32; j++) q[j] = pack_bf16(o[2 * j] * sc, o[2 * j + 1] * sc);
}
__device__ __forceinline__ void stage_rows(const Ctx& c, uint32_t tile_addr, const uint32_t (&q)[32]) {
  const int lane = lane_now(), mi = lane >> 3, r8 = lane & 7;
  const uint32_t row_addr = tile_addr + (16 * c.warp + (mi & 1) * 8 + r8) * 128;
#pragma unroll
  for (int jj = 0; jj < 8; jj++)
    stsm4(row_addr + (jj >> 2) * 8192 + (((((2 * jj) & 7) + (mi >> 1)) ^ r8) << 4), q[4 * jj], q[4 * jj + 1], q[4 * jj + 2], q[4 * jj + 3]);
}
__device__ __forceinline__ void stage_rows(const Ctx& c, uint32_t tile_addr, const float (&o)[64], float sc) {
  uint32_t q[32];
  pack_rows(o, sc, q);
  stage_rows(c, tile_addr, q);
}
template <int SITE>
__device__ __forceinline__ void issue_qk_rs(float (&s)[32], uint32_t (&q)[32], uint32_t dk) {
  uint64_t b = desc64(dk, dhi<SITE>(dk));
  reg_fence(q);
  wg_fence();
  wgmma_qk_rs_init(s, q[0], q[1], q[2], q[3], b, 0);
#pragma unroll
  for (int k = 1; k < 8; k++) { dadd(b, k == 4 ? 506 : 2); wgmma_qk_rs(s, q[4 * k], q[4 * k + 1], q[4 * k + 2], q[4 * k + 3], b, 1); }
  wg_commit();
}

__device__ __forceinline__ void redo_tile(const Ctx& c, uint32_t q_addr, uint32_t half, const __nv_bfloat16* kp, const __nv_bfloat16* vp,
                                          uint32_t item, int row) {
  float o[64];
  const int lane = lane_now(), g = lane >> 2, cc = lane & 3, mi = lane >> 3, r8 = lane & 7;
  const uint32_t qa = q_addr + (half == 4096 ? 8 * c.warp + r8 : 16 * c.warp + (mi & 1) * 8 + r8) * 128, swz = half == 4096 ? q3_swz(r8) : r8;
  const uint32_t* kq = reinterpret_cast<const uint32_t*>(kp + g * DH) + cc;
  const unsigned short* vq = reinterpret_cast<const unsigned short*>(vp + 2 * cc * DH) + g;
  float m0 = -INFINITY, m1 = -INFINITY, l0 = 0.f, l1 = 0.f;
#pragma unroll
  for (int i = 0; i < 64; i++) o[i] = 0.f;
#pragma unroll 1
  for (int kb = 0; kb < SK / 16; kb++) {
    float z[8] = {0.f, 0.f, 0.f, 0.f, 0.f, 0.f, 0.f, 0.f};
#pragma unroll 2
    for (int kk = 0; kk < 8; kk++) {
      uint32_t a0, a1, a2, a3;
      ldsm4(qa + (kk >> 2) * half + ((((kk & 3) * 2 + (mi >> 1)) ^ swz) << 4), a0, a1, a2, a3);
      const uint32_t* kr = kq + kb * (16 * DH / 2) + kk * 8;
      mma16816(z[0], z[1], z[2], z[3], a0, a1, a2, a3, __ldg(kr), __ldg(kr + 4));
      mma16816(z[4], z[5], z[6], z[7], a0, a1, a2, a3, __ldg(kr + 8 * DH / 2), __ldg(kr + 8 * DH / 2 + 4));
    }
    const float n0 = fmaxf(m0, quad_max(fmaxf(fmaxf(z[0], z[1]), fmaxf(z[4], z[5]))));
    const float n1 = fmaxf(m1, quad_max(fmaxf(fmaxf(z[2], z[3]), fmaxf(z[6], z[7]))));
    const float al0 = ex2(m0 - n0), al1 = ex2(m1 - n1);
    m0 = n0; m1 = n1;
#pragma unroll
    for (int i = 0; i < 8; i++) z[i] = ex2(z[i] - ((i & 2) ? n1 : n0));
    l0 = l0 * al0 + (z[0] + z[1]) + (z[4] + z[5]);
    l1 = l1 * al1 + (z[2] + z[3]) + (z[6] + z[7]);
    const uint32_t a0 = pack_bf16(z[0], z[1]), a1 = pack_bf16(z[2], z[3]), a2 = pack_bf16(z[4], z[5]), a3 = pack_bf16(z[6], z[7]);
    const unsigned short* vr = vq + kb * (16 * DH);
#pragma unroll
    for (int nb = 0; nb < 16; nb++) {
      o[4 * nb] *= al0; o[4 * nb + 1] *= al0; o[4 * nb + 2] *= al1; o[4 * nb + 3] *= al1;
      const uint32_t b0 = __ldg(vr + nb * 8) | ((uint32_t)__ldg(vr + nb * 8 + DH) << 16);
      const uint32_t b1 = __ldg(vr + nb * 8 + 8 * DH) | ((uint32_t)__ldg(vr + nb * 8 + 9 * DH) << 16);
      mma16816(o[4 * nb], o[4 * nb + 1], o[4 * nb + 2], o[4 * nb + 3], a0, a1, a2, a3, b0, b1);
    }
  }
  const char* p = o_addr(item, row);
  o_emit<0>(p, o, __fdividef(1.f, quad_sum(l0)));
  o_emit<1>(half == 4096 ? p : p + 1024, o, __fdividef(1.f, quad_sum(l1)));
}

template <bool SPA, bool SPB, int SITE, int ID>
__device__ __forceinline__ void batch(const Ctx& c, float (&s)[32], const uint32_t (&qs)[16], uint32_t dq, uint32_t dk, float (&ob)[64],
                                      uint32_t (&pb)[SPB ? 8 : 16], uint32_t dv) {
  if constexpr (SPA) {
    reg_fence(pb);
    wg_fence();
    issue_pv<SPB, true, ID>(c, ob, pb, dv);
    issue_qk<SPA, false, ID>(c, s, qs, dq, dk);
  } else {
    constexpr bool EARLY = ((QK_EARLY_MASK >> (SITE + (SPB ? 2 : 0))) & 1) != 0;
    if (!EARLY) reg_fence(pb);
    wg_fence();
    issue_qk<SPA, false, ID, !SPB>(c, s, qs, dq, dk);
    if (EARLY) { reg_fence(pb); wg_fence(); }
    issue_pv<SPB, true, ID, SPB>(c, ob, pb, dv);
  }
}

template <bool SP0>
__device__ __forceinline__ bool attention(Ctx c, Ring& r, int unit, uint32_t& d, const float (&a0)[64], float (&o0)[64], float (&o1)[64],
                                          RowSum& st0, RowSum& st1, const Slots& h) {
  constexpr bool SP1 = false;
  if (SP0) { c.mqk = META_QK + (d >> 28); c.mpv = META_PV + (d >> 28); asm volatile("" : "+r"(c.mqk), "+r"(c.mpv)); }
  if (SP0) { const int lane = lane_now(); c.src = (lane & 28) | ((lane & 1) << 1) | ((lane >> 1) & 1); }
  float s[32];
  uint32_t p0[SP0 ? 8 : 16], p1[16];
  const uint32_t q0a = c.sb + QBUF_OFF + (SP0 ? 3 : 0) * 16384, q1a = c.sb + QBUF_OFF + (SP0 ? 2 : 1) * 16384;
  const uint32_t dq0 = sdesc(q0a, 0), dq1 = sdesc(q1a, 0);
  uint32_t sk, sv, sn;
  uint32_t qs[16];
  T2C(unit, 40);
  if (SP0) {
    float s1[32], sc = SM_C;
    if (PRO & 32) sk = acquire(c, r);
    if (!(PRO & 128)) stage_t3<0, true>(c, a0, SM_C);
    stage_t2<0>(c, a0, SM_C);
    T2C(unit, 41);
    proj_end<1>(c, o0, h);
    T2C(unit, 42);
    if (!(PRO & 64)) stage_t3<1, true>(c, o0, SM_C);
    stage_t2<1>(c, o0, SM_C);
    if (!(PRO & 32)) sk = acquire(c, r);
    fence_async_smem();
    T2C(unit, 43);
    bar_sync(1, LAG_BAR & 30 ? 256 : 128);
    if (PRO & 64) {
      TRACE(unit, 2);
      wg_fence();
      issue_qk<SP1, true, 1>(c, s1, qs, dq1, sdesc(c.sb + sk * SLOT, 0));
      sched_fence<11>(sk, sc);
      if (PRO & 128) stage_t3<0, true>(c, a0, sc);
      stage_t3<1, true>(c, o0, sc);
      bar_sync(5, 128);
    }
    const int lane = lane_now(), g = lane >> 2, cc = lane & 3;
    const uint32_t qa = q0a + (8 * c.warp + g) * 128 + (cc & 1) * 8;
#pragma unroll
    for (int k = 0; k < 8; k++)
      asm volatile("ld.shared.v2.u32 {%0, %1}, [%2];" : "=r"(qs[2 * k]), "=r"(qs[2 * k + 1])
                   : "r"(qa + (k >> 2) * 4096 + ((((k & 3) * 2 + (cc >> 1)) ^ q3_swz(g)) << 4)) : "memory");
    T2C(unit, 44);
    if (!(PRO & 64)) {
      TRACE(unit, 2);
      wg_fence();
      issue_qk<SP1, true, 1>(c, s1, qs, dq1, sdesc(c.sb + sk * SLOT, 0));
    }
    reg_fence(qs);
    wg_fence();
    issue_qk<SP0, true, 0>(c, s, qs, dq0, sdesc(c.sb + sk * SLOT, 0));
    T2C(unit, 45);
    acquire2(c, r, sv, sn);
    wg_wait<1>();
    reg_fence(s1);
    T2C(unit, 47);
    exps<SP1, true>(c, s1, p1, st1);
    reg_fence(p1);
    wg_fence();
    issue_pv<SP1, false, 1>(c, o1, p1, sdesc(c.sb + sv * SLOT, 8192));
    if (LAG_BAR & 1) asm volatile("bar.arrive 4, 256;" ::: "memory");
    wg_wait<1>();
    reg_fence(s);
    T2C(unit, 48);
    release(c, sk);
    sk = sn;
    exps<SP0, true>(c, s, p0, st0);
    reg_fence(p0);
    wg_fence();
    issue_pv<SP0, false, 0>(c, o0, p0, sdesc(c.sb + sv * SLOT, 8192));
    issue_qk<SP0, false, 2>(c, s, qs, dq0, sdesc(c.sb + sk * SLOT, 0));
    T2C(unit, 49);
    sn = acquire(c, r);
    T2C(unit, 50);
    wg_wait<0>();
    reg_fence(s);
  } else {
    float s1[32];
    uint32_t q0[32], q1[32];
    sk = acquire(c, r);
    pack_rows(a0, SM_C, q0);
    if (!(PRO & 2)) stage_rows(c, q0a, q0);
    reg_fence(q0);
    T2C(unit, 41);
    proj_end<0>(c, o1, h);
    TRACE(unit, 2);
    T2C(unit, 42);
    float sc = SM_C;
    if (PRO & 1) { pack_rows(o1, SM_C, q1); sched_fence<0>(sk, q1); }
    issue_qk_rs<0>(s, q0, sdesc(c.sb + sk * SLOT, 0));
    if (!(PRO & 1)) sched_fence<0>(sk, sc);
    if (LAG_BAR & 8) asm volatile("bar.arrive 1, 256;" ::: "memory");
    T2C(unit, 43);
    if (!(PRO & 1)) { reg_fence(o1); pack_rows(o1, sc, q1); }
    if (PRO & 2) stage_rows(c, q0a, q0);
    if (!(PRO & 20)) stage_rows(c, q1a, q1);
    T2C(unit, 44);
    if (LAG_BAR & 4) asm volatile("bar.arrive 1, 256;" ::: "memory");
    issue_qk_rs<1>(s1, q1, sdesc(c.sb + sk * SLOT, 0));
    if (LAG_BAR & 2) asm volatile("bar.arrive 1, 256;" ::: "memory");
    T2C(unit, 45);
    if (!(PRO & 8)) acquire2(c, r, sv, sn);
    if (PRO & 4) stage_rows(c, q1a, q1);
    T2C(unit, 46);
    wg_wait<1>();
    reg_fence(s);
    if (LAG_BAR & 16) asm volatile("bar.arrive 1, 256;" ::: "memory");
    T2C(unit, 47);
    exps<SP0, true>(c, s, p0, st0);
    reg_fence(p0);
    sched_fence<1>(sk, p0);
    if (PRO & 16) stage_rows(c, q1a, q1);
    if (PRO & 8) acquire2(c, r, sv, sn);
    wg_wait<0>();
    reg_fence(s1);
    fence_async_smem();
    __syncwarp();
    wg_fence();
    issue_qk<SP0, false, 2>(c, s, qs, dq0, sdesc(c.sb + sn * SLOT, 0));
    issue_pv<SP0, false, 0>(c, o0, p0, sdesc(c.sb + sv * SLOT, 8192));
    sched_fence<2>(sk, s1);
    reg_fence(s1);
    T2C(unit, 48);
    release(c, sk);
    sk = sn;
    exps<SP1, true>(c, s1, p1, st1);
    reg_fence(p1);
    wg_fence();
    issue_pv<SP1, false, 1>(c, o1, p1, sdesc(c.sb + sv * SLOT, 8192));
    T2C(unit, 49);
    sn = acquire(c, r);
    if (LAG_BAR & 1) bar_sync(4, 256);
    T2C(unit, 50);
    wg_wait<1>();
    reg_fence(s);
  }
  TRACE_IN(unit, 4);
  T2C(unit, 51);
#pragma unroll 1
  for (int j = 1; j < 15; j++) {
    const uint32_t sv_prev = sv, sk_prev = sk;
    sv = sn;
    const uint32_t dv = sdesc(c.sb + sv * SLOT, 8192);
    reg_fence(p0);
    exps<SP0, false>(c, s, p0, st0);
    batch<SP1, SP0, 0, 3>(c, s, qs, dq1, sdesc(c.sb + sk * SLOT, 0), o0, p0, dv);
    sk = acquire(c, r);
    wg_wait<1>();
    reg_fence(s); reg_fence(p1);
    release(c, sv_prev); release(c, sk_prev);
    exps<SP1, false>(c, s, p1, st1);
    batch<SP0, SP1, 1, 4>(c, s, qs, dq0, sdesc(c.sb + sk * SLOT, 0), o1, p1, dv);
    sn = acquire(c, r);
    if (SP0) wg_wait<0>(); else wg_wait<1>();
    reg_fence(s);
  }
  TRACE_IN(unit, 5);
  T2C(unit + 1, 52);
  const uint32_t sv_prev = sv;
  sv = sn;
  const uint32_t dv = sdesc(c.sb + sv * SLOT, 8192);
  reg_fence(p0);
  exps<SP0, false>(c, s, p0, st0);
  batch<SP1, SP0, 0, 5>(c, s, qs, dq1, sdesc(c.sb + sk * SLOT, 0), o0, p0, dv);
  if (SP0) sched_fence<4>(sk, st0.l0); else sched_fence<3>(sk, st0.l0, st0.l1);
  const bool bad0 = finish_sums<SP0>(st0);
  asm volatile("ld.volatile.shared.u32 %0, [%1];" : "=r"(d) : "r"(c.sb + DESC_OFF + ((unit + 1) & 3) * 4) : "memory");
  d = __shfl_sync(0xffffffffu, d, 0);
  if (SP0) sched_fence<10>(sk, st0.l0); else sched_fence<9>(sk, st0.l0, st0.l1);
  wg_wait<1>();
  reg_fence(s); reg_fence(p1);
  T2C(unit + 1, 53);
  release(c, sv_prev); release(c, sk);
  exps<SP1, false>(c, s, p1, st1);
  reg_fence(p1);
  wg_fence();
  issue_pv<SP1, true, 2>(c, o1, p1, dv);
  sched_fence<5 + SP0>(sk, st1.l0, st1.l1);
  T2C(unit + 1, 54);
  const bool have = peek<2 + SP0>(c, r);
  const bool bad = finish_sums<SP1>(st1) | bad0;
  T2C(unit + 1, 55);
  if (d < (2u << 30) && !__all_sync(0xffffffffu, have)) { Ring t = r; Slots u; begin_acquire<SP0>(c, t, u, true); }
  T2C(unit + 1, 56);
  wg_wait<0>();
  reg_fence(o0); reg_fence(o1);
  T2C(unit + 1, 57);
  release(c, sv);
  return bad;
}
template <int WG>
__device__ __forceinline__ bool wg_any(bool p) {
  uint32_t any;
  asm volatile("{\n.reg .pred p, q;\nsetp.ne.u32 p, %1, 0;\nbar.red.or.pred q, %2, 128, p;\nselp.u32 %0, 1, 0, q;\n}"
               : "=r"(any) : "r"((uint32_t)p), "n"(2 + WG) : "memory");
  return __any_sync(0xffffffffu, any);
}

template <int WG>
__device__ __forceinline__ void consumer(Ctx c, const __nv_bfloat16* const* kv) {
  asm volatile("setmaxnreg.inc.sync.aligned.u32 %0;" ::"n"(WG ? REG_C : 504 - REG_C - REG_P));
  c.wg = WG;
  Ring r{0, 0, 0};
  bool bad;
  float a0[64], a1[64], o1[64];
  Slots h;
  RowSum inv0, inv1;
  uint32_t d = blockIdx.x, dc = 0, sw;
  int i = 0, nq;
begin:
  sw = d & (1u << 30);
  proj_begin<WG>(c, r, a0, h, true, sw);
  proj_half<WG, true, 1>(c, a1, h.w, h.x, sw);
  nq = 0;
#pragma unroll
  for (int k = 0; k < 64; k++) asm volatile("" : "=f"(o1[k]));
  asm volatile("" : "=f"(inv1.l0), "=f"(inv1.l1));
  while (true) {
    TRACE(i, 0); TRACE(i, 6);
    proj_main<WG>(c, r, a0, a1, h, d >> 30 ? ((d >> 16) & 63) + 1 : DM / 64, sw, i, dc, nq, o1, inv1);
    dc = d;
    TRACE(i, 1);
    if (d >> 30) goto out_tile;
    bad = WG ? attention<WG>(c, r, i, d, a0, a1, o1, inv0, inv1, h) : attention<WG>(c, r, i, d, a0, o1, a1, inv1, inv0, h);
    if (d >= (2u << 30)) break;
    Ring t = r;
    sw = d & (1u << 30);
    begin_acquire<WG>(c, t, h, false);
    proj_half<WG, true, 0>(c, a0, h.w, h.x, sw);
    if (WG) sched_fence<8>(h.w, inv0.l0, inv1.l0, inv1.l1); else sched_fence<7>(h.w, inv0.l0, inv0.l1);
    T2C(i + 1, 58);
    o_first<WG>(c, dc, a1, inv0);
    if (__builtin_expect(wg_any<WG>(bad), 0)) {
      wg_wait<0>();
      acc_fence<WG>(a0);
      goto redo;
    }
    r = t;
    T2C(i + 1, 1);
    proj_half<WG, true, 1>(c, a1, h.w, h.x, sw);
    if (WG) release(c, h.o);
    release_q<WG>(c);
    T2C(i + 1, 2);
    nq = O_STEPS;
    TRACE(i, 3); TRACE(i, 7);
    i++;
  }
  if (wg_any<WG>(bad)) goto redo;
  release_q<WG>(c);
  o_first<WG>(c, dc, a1, inv0);
#pragma unroll
  for (int k = 1; k <= O_STEPS; k++) o_second<WG>(c, dc, k, o1, inv1);
next:
  TRACE(i, 3); TRACE(i, 7);
  if ((d >> 30) != 2) {
    i++;
    r.uniform();
    goto begin;
  }
  trace_dump(c);
  return;
out_tile:
  proj_end<WG>(c, a1, h);
  if (((d >> 28) & 3) == 2) {
    const int lane = lane_now(), mi = lane >> 3, r8 = lane & 7;
    const uint32_t off = c.sb + (WG ? stage_off(c) : (16 * c.warp + (mi & 1) * 8 + r8) * 128);
#pragma unroll 1
    for (int k = (d >> 5) & 3; k > 0; k--) {
      uint32_t s0, s1;
      if (WG) { acquire2(c, r, s0, s1); release(c, s0); release(c, s1); }
#pragma unroll
      for (int t = 0; t < 2; t++) {
        const uint32_t sp = acquire(c, r), base = off + sp * SLOT;
        if (WG) {
#pragma unroll
          for (int jj = 0; jj < (t ? 2 : 4); jj++) {
            add16<true>(base + jj * 2048, &a0[(t * 4 + jj) * 8]);
            add16<true>(base + jj * 2048 + (t ? 4096 : 8192), &a1[(t * 4 + jj) * 8]);
          }
        } else {
#pragma unroll
          for (int jj = 0; jj < 8; jj++) add16<false>(base + (jj >> 2) * 8192 + (((((2 * jj) & 7) + (mi >> 1)) ^ r8) << 4), t ? &a1[jj * 8] : &a0[jj * 8]);
        }
        release(c, sp);
      }
      if (!WG) { acquire2(c, r, s0, s1); release(c, s0); release(c, s1); }
    }
  }
  if (WG) { stage_t3<0, false>(c, a0, 1.f); stage_t3<1, false>(c, a1, 1.f); }
  else stage_rows(c, c.sb + QBUF_OFF, a0, 1.f);
  staged(c, 0);
  if (WG) { stage_t2<0>(c, a0, 1.f); stage_t2<1>(c, a1, 1.f); }
  else stage_rows(c, c.sb + QBUF_OFF + 16384, a1, 1.f);
  staged(c, 1);
  d = get_desc(c, i + 1);
  TRACE(i, 2);
  goto next;
redo:
  {
    const size_t hoff = (size_t)(dc & 511) * (SK * DH);
    const int br = (dc >> 9) & 1;
#pragma unroll 1
    for (int part = 0; part < 2; part++) {
      const int t = WG ? 3 - part : part;
      redo_tile(c, c.sb + QBUF_OFF + t * 16384, t == 3 ? 4096 : 8192, kv[br] + hoff, kv[2 + br] + hoff, dc,
                t * 64 + (t == 3 ? 8 : 16) * c.warp);
    }
    o_done(c);
    release_q<WG>(c);
  }
  goto next;
}

template <bool SIMPLE>
__global__ void __launch_bounds__(384, 1) mha_fused_kernel(const __grid_constant__ Params P) {
  extern __shared__ __align__(1024) uint8_t smem_raw[];
  const uint32_t sbase = smem_u32(smem_raw);
  const int tid = threadIdx.x;
  const int wg = __shfl_sync(0xffffffffu, tid >> 7, 0);
  const int warp = __shfl_sync(0xffffffffu, (tid >> 5) & 3, 0);
  const int lane = tid & 31;
  const int cta = blockIdx.x;

  if (tid == 0) T3(15, 0);
  if ((sbase & 1023) || sbase + SMEM_BYTES > 0x40000) __trap();
  {
    const int wi = wg * 4 + warp;
    asm volatile(ELECT "prefetch.tensormap [%0];\n}" ::"l"(&P.x[0][0] + wi) : "memory");
#pragma unroll
    for (int k = 0; k < 3; k++) {
      const int b = min(BAR_OFF + (wi * 3 + k) * 8, BAR_GO);
      asm volatile(ELECT "mbarrier.init.shared::cta.b64 [%0], %1;\n}"
                   ::"r"(sbase + b), "r"(b < BAR_EMPTY || b >= BAR_DESC ? 1 : b >= BAR_STG && b < BAR_OUT ? 4 : 8) : "memory");
    }
    asm volatile("fence.mbarrier_init.release.cluster;" ::: "memory");
    if (wi < 6) asm volatile(ELECT "prefetch.tensormap [%0];\n}" ::"l"(&P.x[0][0] + 12 + wi) : "memory");
  }
  __syncthreads();

  if (wg == 2) {
    asm volatile("setmaxnreg.dec.sync.aligned.u32 %0;" ::"n"(REG_P));
    if (warp == 1) {
      const uint32_t qb = sbase + QBUF_OFF;
      const uint32_t ep = __shfl_sync(0xffffffffu, *(volatile unsigned*)&g_epoch + 1, 0);
      asm volatile("st.volatile.shared.u32 [%0], %1;" ::"r"(sbase + EPOCH_OFF), "r"(ep) : "memory");
      uint32_t dc = cta, qi = 0, piece = 0, na = 0;
      TTAIL(0);
      for (int i = 0; (dc >> 30) != 2; i++) {
        mbar_wait_w(sbase + BAR_GO, i & 1);
        if (piece == 0) {
          if (lane == 0) {
            qi = atomicAdd(&g_next, 1);
            if (qi == (SIMPLE ? Q_ALL : Q_RANGES) - 1) { g_next = 0; g_epoch = ep; }
          }
          qi = __shfl_sync(0xffffffffu, qi, 0) + (SIMPLE ? gridDim.x : NCTA);
        }
        uint32_t d;
        if (qi < (SIMPLE ? Q_ALL : Q_RANGES)) { d = c_sched.queue[qi]; if (d & 0x8000) d ^= (1u << 30) | (63u << 16) | 0x8000; }
        else if (SIMPLE) d = 2u << 30;
        else { const uint32_t e = qi - Q_RANGES, g = e / 5; d = c_sched.piece[g][piece++] | (e - g * 5) << 8; }
        if ((d >> 30) == 1) {
          const uint32_t ok = __ballot_sync(0xffffffffu, reached(&g_cnt[lane & 1][d & 31], ep * (lane & 1 ? NH - H_LATE : H_LATE)));
          if (!(ok & 2)) d |= ((d >> 22) & 63) >= 2 * H_LATE - O_STEPS ? (2u << 30) | 128 : 128;
          if (!(ok & 1) || (O_STEPS > 4 && ((d >> 16) & 63) < O_STEPS)) d |= 2u << 30;
        }
        asm volatile("st.volatile.shared.u32 [%0], %1;" ::"r"(sbase + DESC_OFF + ((i + 1) & 3) * 4), "r"(d) : "memory");
        __syncwarp();
        mbar_arrive_warp(sbase + BAR_DESC);
        const Work w = decode(dc);
        dc = d;
        if (w.kind == 0) {
          mbar_wait_w(sbase + BAR_OUT, na++ & 1);
          TTAIL(1);
          T3(i, 0); T3(i, 1);
          asm volatile(ELECT "red.release.gpu.global.add.u32 [%0], 1;\n}" ::"l"(&g_cnt[w.sub >= H_LATE][w.beta]) : "memory");
          T3(i, 2);
          TTAIL(2);
          continue;
        }
        const bool fin = w.mode != 1;
        uint64_t pol, pol2;
        asm volatile("createpolicy.fractional.L2::evict_first.b64 %0, 1.0;" : "=l"(pol));
        asm volatile("createpolicy.fractional.L2::evict_normal.b64 %0, 1.0;" : "=l"(pol2));
        if (!fin) pol = pol2;
        const CUtensorMap* m = fin ? P.out_st : P.o_st;
        const int c1 = fin ? (w.beta & 15) * SQ : 0;
        const int c2 = fin ? (w.beta >> 4) * (DM / 64) + w.sub * 2 : NBETA * 64 + w.range * 2;
        uint32_t pend = 0;
#pragma unroll 1
        for (int e = 0; e < 4; e++) {
          const int t = (ST_ORDER >> (4 * e)) & 3;
          mbar_wait_w(sbase + BAR_STG + (t ^ (t >> 1)) * 8, (i - na) & 1);
          tma_st3_hint_w(m + (t == 3), qb + t * 16384, 0, c1 + t * 64, c2, pol);
          bulk_commit();
          T2P(i + 1, 5, 2 * e);
          if (pend) {
            bulk_wait_read<1>();
            mbar_arrive8_w(pend);
            T2P(i + 1, 5, 2 * e - 1);
          }
          pend = sbase + BAR_EMPTY + (NS + t) * 8;
          if ((ST_NOW >> e) & 1) {
            bulk_wait_read<0>();
            mbar_arrive8_w(pend);
            pend = 0;
            T2P(i + 1, 5, 2 * e + 1);
          }
        }
        T3(i, 0);
        if (piece >= 2) TTAIL(piece * 2 - 1);
        asm volatile("cp.async.bulk.wait_group 0;" ::: "memory");
        T3(i, 1);
        if (w.mode == 1) asm volatile(ELECT "st.release.gpu.global.u32 [%0], %1;\n}" ::"l"(&g_flag[w.range]), "r"(ep) : "memory");
        T3(i, 2);
        if (piece >= 2) TTAIL(piece * 2);
      }
      T3(15, 1);
    } else
    if (warp == 0) {
      Ring r{0, 1, 3};
      uint32_t d = cta;
      for (int i = 0;; i++) {
        const Work w = decode(d);
        if (w.kind == 2) break;
        const CUtensorMap* m = w.kind == 0 ? &P.wq[w.beta >> 4] : &P.wo[w.beta >> 4];
        for (int ks = 0; ks < w.nsteps; ks++) {
          const uint32_t b = borrow(ks, w.nsteps);
          r.next_if(b == 2);
          const uint32_t bar = sbase + BAR_FULL + r.slot * 8;
          mbar_wait_w(bar + (BAR_EMPTY - BAR_FULL), r.phase);
          if (w.kind == 0) tma_ld3_w(sbase + r.slot * SLOT, m, 0, ks * 64, w.sub * 2, bar, 16384);
          else tma_ld_wo_w(sbase + r.slot * SLOT, m, w.sub * 128, (w.k0 + ks) * 2, bar);
          if (ks < 10) T2P(i, 2, ks);
          if (w.kind != 0 && ks == max(w.nsteps - GO_P, 4)) mbar_arrive_warp(sbase + BAR_GO);
          r.next(); r.next_if(b == 2);
        }
        if (w.kind == 0) {
          r.phase ^= 1; r.next(); r.next();
        } else if (w.mode == 2) {
          for (int k = 1; k <= ((d >> 5) & 3); k++) {
            if (k == 1) TTAIL(9);
            wait_count(&g_flag[w.range + 5 * k], lds(sbase + EPOCH_OFF));
            TTAIL(10);
            asm volatile("fence.proxy.async.global;" ::: "memory");
#pragma unroll 1
            for (int t = 0; t < 4; t++) {
              mbar_wait_w(sbase + BAR_EMPTY + r.slot * 8, r.phase);
              tma_ld3_w(sbase + r.slot * SLOT, &P.o_st[t == 3], 0, t * 64, NBETA * 64 + (w.range + 5 * k) * 2, sbase + BAR_FULL + r.slot * 8,
                        t == 3 ? 8192 : 16384);
              r.next();
            }
          }
        }
        mbar_wait_w(sbase + BAR_DESC, i & 1);
        d = __shfl_sync(0xffffffffu, lds(sbase + DESC_OFF + ((i + 1) & 3) * 4), 0);
      }
    } else {
      const int hi = warp - 2;
      uint64_t pol_stream;
      asm volatile("createpolicy.fractional.L2::evict_first.b64 %0, 1.0;" : "=l"(pol_stream));
      Ring r{0, 1, 3};
      uint32_t d = cta;
      for (int i = 0;; i++) {
        const Work w = decode(d);
        if (w.kind == 2) break;
        const CUtensorMap* m = w.kind == 0 ? &P.x[hi][w.beta >> 4] : &P.o_ld[hi];
        int c1 = (w.kind == 0 ? (w.beta & 15) : w.beta * 64 + w.k0) * SQ + hi * 128;
        int k_late = -1;
        if (w.kind != 0) {
          if (!hi) T3(i, 3);
          if (d >= (3u << 30)) wait_count(&g_cnt[0][w.beta], lds(sbase + EPOCH_OFF) * H_LATE);
          if (d & 128) k_late = max(2 * H_LATE - w.k0, 0);
          if (!hi) T3(i, 4);
          asm volatile("fence.proxy.async.global;" ::: "memory");
          if (!hi) T3(i, 5);
        }
        for (int ks = 0; ks < w.nsteps; ks++) {
          if (ks == k_late) {
            if (!hi) T3(i, 6);
            wait_count(&g_cnt[1][d & 31], lds(sbase + EPOCH_OFF) * (NH - H_LATE));
            asm volatile("fence.proxy.async.global;" ::: "memory");
            if (!hi) T3(i, 7);
          }
          const uint32_t b = borrow(ks, w.nsteps);
          const bool bo = b != 2;
          r.next_if(hi && !bo); r.next_if(hi && !bo);
          const uint32_t sl = bo ? NS + (b ^ (3 * hi)) : r.slot, bar = sbase + BAR_FULL + sl * 8;
          mbar_wait_w(bar + (BAR_EMPTY - BAR_FULL), bo ? (r.xp >> b) & 1 : r.phase);
          if (w.kind == 0) tma_ld2_w(sbase + sl * SLOT, m, ks * 64, c1, bar, (hi ? 96 * 128 : 128 * 128));
          else { tma_ld2_hint_w(sbase + sl * SLOT, m, 0, c1, bar, hi ? 96 * 128 : 128 * 128, pol_stream); c1 += SQ; }
          if (i == 0 && ks == PF_STEP)
            asm volatile(ELECT "cp.async.bulk.prefetch.tensor.3d.L2.global.L2::cache_hint [%0, {0, %1, 0}], %2;\n}"
                         ::"l"(&P.kv[hi][0]), "r"(d * SK), "l"(pol_stream) : "memory");
          if (ks < 10) T2P(i, 3 + hi, ks);
          if (!hi && w.kind != 0 && !(ks & 3)) TCLK(i * 16 + (ks >> 2));
          r.next(); r.next_if(!hi && !bo); r.next_if(!hi && !bo);
          r.xp ^= 1 << b;
        }
        r.xp ^= 3;
        if (w.kind == 0) {
          m = &P.kv[hi][w.beta >> 4];
          c1 = (d & 511) * SK;
          for (int j = 0; j < 16; j++) {
            if (hi) r.next();
            const uint32_t bar = sbase + BAR_FULL + r.slot * 8;
            const bool tight = i < KV_WIN_UNITS && j < KV_WIN_TILES + ((KV_WIN_RAMP * ((int)d - NCTA * i)) >> 5);
            {
              const int s2 = (int)r.slot - (tight ? 2 : KV_WIN_D);
              mbar_wait_w(sbase + BAR_FULL + (s2 < 0 ? s2 + NS : s2) * 8, s2 < 0 ? r.phase : r.phase ^ 1);
            }
            if (j == 15 && hi) mbar_wait_w(sbase + BAR_DESC, i & 1);
            mbar_wait_w(sbase + BAR_EMPTY + r.slot * 8, r.phase);
            tma_ld3_hint_w(sbase + r.slot * SLOT, m, 0, c1, 0, bar, pol_stream);
            T2P(i, 3 + hi, 16 + j);
            if (!hi) TCLK(i * 16 + j);
            if (j == 14 && !hi) mbar_arrive_warp(sbase + BAR_GO);
            c1 += 64;
            r.next();
            if (!hi) r.next();
          }
        }
        mbar_wait_w(sbase + BAR_DESC, i & 1);
        d = __shfl_sync(0xffffffffu, lds(sbase + DESC_OFF + ((i + 1) & 3) * 4), 0);
      }
    }
  } else {
    Ctx c;
    c.sb = sbase; c.wg = wg; c.warp = warp; c.src = 0; c.mqk = 0; c.mpv = 0; c.lead = lane == 0;
    if (wg == 0) consumer<0>(c, P.kp); else consumer<1>(c, P.kp);
  }
}

typedef CUresult (*EncodeFn)(CUtensorMap*, CUtensorMapDataType, cuuint32_t, void*, const cuuint64_t*, const cuuint64_t*,
                             const cuuint32_t*, const cuuint32_t*, CUtensorMapInterleave, CUtensorMapSwizzle,
                             CUtensorMapL2promotion, CUtensorMapFloatOOBfill);

void make_map(EncodeFn enc, CUtensorMap* m, const void* ptr, int rank, const cuuint64_t* dims, const cuuint64_t* strides,
              const cuuint32_t* box, int promo = 2, CUtensorMapSwizzle swz = CU_TENSOR_MAP_SWIZZLE_128B) {
  cuuint32_t es[5] = {1, 1, 1, 1, 1};
  enc(m, CU_TENSOR_MAP_DATA_TYPE_BFLOAT16, rank, const_cast<void*>(ptr), dims, strides, box, es,
      CU_TENSOR_MAP_INTERLEAVE_NONE, swz, promo == 2 ? CU_TENSOR_MAP_L2_PROMOTION_L2_256B : promo == 1 ? CU_TENSOR_MAP_L2_PROMOTION_L2_128B : CU_TENSOR_MAP_L2_PROMOTION_NONE,
      CU_TENSOR_MAP_FLOAT_OOB_FILL_NONE);
}

}

extern "C" void kernel_launch(void* const* d_in, const int* in_sizes, int n_in, void* d_out, int out_size) {
  (void)in_sizes; (void)n_in; (void)out_size;
  static EncodeFn enc = nullptr;
  static void* o_ptr = nullptr;
  static int n_sm = 0;
  if (!enc) {
    void* fn = nullptr;
    cudaDriverEntryPointQueryResult qr;
    cudaGetDriverEntryPoint("cuTensorMapEncodeTiled", &fn, cudaEnableDefault, &qr);
    enc = (EncodeFn)fn;
    cudaGetSymbolAddress(&o_ptr, g_o);
    cudaFuncSetAttribute(mha_fused_kernel<false>, cudaFuncAttributeMaxDynamicSharedMemorySize, SMEM_BYTES);
    cudaFuncSetAttribute(mha_fused_kernel<true>, cudaFuncAttributeMaxDynamicSharedMemorySize, SMEM_BYTES);
    int dev = 0;
    cudaGetDevice(&dev);
    cudaDeviceGetAttribute(&n_sm, cudaDevAttrMultiProcessorCount, dev);
  }
  Params P;
  for (int br = 0; br < 2; br++) {
    const void* x = d_in[br * 5 + 0]; const void* kc = d_in[br * 5 + 1]; const void* vc = d_in[br * 5 + 2];
    const void* wq = d_in[br * 5 + 3]; const void* wo = d_in[br * 5 + 4];
    { cuuint64_t d[2] = {DM, (cuuint64_t)NB * SQ}, s[1] = {DM * 2}; cuuint32_t b[2] = {64, 128}, b2[2] = {64, 96};
      make_map(enc, &P.x[0][br], x, 2, d, s, b, PR_X); make_map(enc, &P.x[1][br], x, 2, d, s, b2, PR_X); }
    { cuuint64_t d[3] = {64, DM, HD / 64}, s[2] = {HD * 2, 128}; cuuint32_t b[3] = {64, 64, 2}; make_map(enc, &P.wq[br], wq, 3, d, s, b, PR_W); }
    { cuuint64_t d[5] = {DM, 2, 4, 4, HD / 32}, s[4] = {DM * 2, 8 * DM * 2, 2 * DM * 2, 32 * DM * 2}; cuuint32_t b[5] = {64, 2, 4, 4, 2};
      make_map(enc, &P.wo[br], wo, 5, d, s, b, PR_W); }
    { cuuint64_t d[3] = {64, (cuuint64_t)NB * NH * SK, 2}, s[2] = {DH * 2, 128}; cuuint32_t b[3] = {64, 64, 2};
      make_map(enc, &P.kv[0][br], kc, 3, d, s, b, PR_KV); make_map(enc, &P.kv[1][br], vc, 3, d, s, b, PR_KV); }
    P.kp[br] = (const __nv_bfloat16*)kc; P.vp[br] = (const __nv_bfloat16*)vc;

  }
  { cuuint64_t d[2] = {64, (cuuint64_t)NBETA * 64 * SQ}, s[1] = {128}; cuuint32_t b[2] = {64, 128}, b2[2] = {64, 96};
    make_map(enc, &P.o_ld[0], o_ptr, 2, d, s, b, 2, CU_TENSOR_MAP_SWIZZLE_NONE); make_map(enc, &P.o_ld[1], o_ptr, 2, d, s, b2, 2, CU_TENSOR_MAP_SWIZZLE_NONE); }
  { cuuint64_t d[3] = {64, SQ, O_BLOCKS}, s[2] = {128, SQ * 128}; cuuint32_t b[3] = {64, 64, 2}, b2[3] = {64, 32, 2};
    make_map(enc, &P.o_st[0], o_ptr, 3, d, s, b); make_map(enc, &P.o_st[1], o_ptr, 3, d, s, b2); }
  { cuuint64_t d[3] = {64, (cuuint64_t)NB * SQ, 2 * DM / 64}, s[2] = {2 * DM * 2, 128}; cuuint32_t b[3] = {64, 64, 2}, b2[3] = {64, 32, 2};
    make_map(enc, &P.out_st[0], d_out, 3, d, s, b); make_map(enc, &P.out_st[1], d_out, 3, d, s, b2); }
  if (n_sm >= NCTA) mha_fused_kernel<false><<<NCTA, 384, SMEM_BYTES>>>(P);
  else mha_fused_kernel<true><<<n_sm, 384, SMEM_BYTES>>>(P);
}
```

```cpp
#include <cuda_runtime.h>
#include <cuda_bf16.h>
#include <cuda.h>
#include <stdint.h>
#include <stdlib.h>

namespace {

__device__ __forceinline__ void wgmma_proj(float (&d)[64], uint64_t da, uint64_t db, int scaleD) {
  asm volatile("{\n.reg .pred p;\nsetp.ne.b32 p, %66, 0;\n"
      "wgmma.mma_async.sync.aligned.m64n128k16.f32.bf16.bf16 "
      "{%0, %1, %2, %3, %4, %5, %6, %7, %8, %9, %10, %11, %12, %13, %14, %15, %16, %17, %18, %19, %20, %21, %22, %23, %24, %25, %26, %27, %28, %29, %30, "
      "%31, %32, %33, %34, %35, %36, %37, %38, %39, %40, %41, %42, %43, %44, %45, %46, %47, %48, %49, %50, %51, %52, %53, %54, %55, %56, %57, %58, %59, %60, "
      "%61, %62, %63}, "
      "%64, %65, p, 1, 1, 0, 1;\n}\n"
      : "+f"(d[0]), "+f"(d[1]), "+f"(d[2]), "+f"(d[3]), "+f"(d[4]), "+f"(d[5]), "+f"(d[6]), "+f"(d[7]), "+f"(d[8]), "+f"(d[9]), "+f"(d[10]), "+f"(d[11]),
        "+f"(d[12]), "+f"(d[13]), "+f"(d[14]), "+f"(d[15]), "+f"(d[16]), "+f"(d[17]), "+f"(d[18]), "+f"(d[19]), "+f"(d[20]), "+f"(d[21]), "+f"(d[22]),
        "+f"(d[23]), "+f"(d[24]), "+f"(d[25]), "+f"(d[26]), "+f"(d[27]), "+f"(d[28]), "+f"(d[29]), "+f"(d[30]), "+f"(d[31]), "+f"(d[32]), "+f"(d[33]),
        "+f"(d[34]), "+f"(d[35]), "+f"(d[36]), "+f"(d[37]), "+f"(d[38]), "+f"(d[39]), "+f"(d[40]), "+f"(d[41]), "+f"(d[42]), "+f"(d[43]), "+f"(d[44]),
        "+f"(d[45]), "+f"(d[46]), "+f"(d[47]), "+f"(d[48]), "+f"(d[49]), "+f"(d[50]), "+f"(d[51]), "+f"(d[52]), "+f"(d[53]), "+f"(d[54]), "+f"(d[55]),
        "+f"(d[56]), "+f"(d[57]), "+f"(d[58]), "+f"(d[59]), "+f"(d[60]), "+f"(d[61]), "+f"(d[62]), "+f"(d[63])
      : "l"(da), "l"(db), "r"(scaleD));
}
__device__ __forceinline__ void wgmma_proj96(float (&d)[64], uint64_t da, uint64_t db, int scaleD) {
  asm volatile("{\n.reg .pred p;\nsetp.ne.b32 p, %50, 0;\n"
      "wgmma.mma_async.sync.aligned.m64n96k16.f32.bf16.bf16 "
      "{%0, %1, %2, %3, %4, %5, %6, %7, %8, %9, %10, %11, %12, %13, %14, %15, %16, %17, %18, %19, %20, %21, %22, %23, %24, %25, %26, %27, %28, %29, %30, "
      "%31, %32, %33, %34, %35, %36, %37, %38, %39, %40, %41, %42, %43, %44, %45, %46, %47}, "
      "%48, %49, p, 1, 1, 1, 0;\n}\n"
      : "+f"(d[0]), "+f"(d[1]), "+f"(d[2]), "+f"(d[3]), "+f"(d[4]), "+f"(d[5]), "+f"(d[6]), "+f"(d[7]), "+f"(d[8]), "+f"(d[9]), "+f"(d[10]), "+f"(d[11]),
        "+f"(d[12]), "+f"(d[13]), "+f"(d[14]), "+f"(d[15]), "+f"(d[16]), "+f"(d[17]), "+f"(d[18]), "+f"(d[19]), "+f"(d[20]), "+f"(d[21]), "+f"(d[22]),
        "+f"(d[23]), "+f"(d[24]), "+f"(d[25]), "+f"(d[26]), "+f"(d[27]), "+f"(d[28]), "+f"(d[29]), "+f"(d[30]), "+f"(d[31]), "+f"(d[32]), "+f"(d[33]),
        "+f"(d[34]), "+f"(d[35]), "+f"(d[36]), "+f"(d[37]), "+f"(d[38]), "+f"(d[39]), "+f"(d[40]), "+f"(d[41]), "+f"(d[42]), "+f"(d[43]), "+f"(d[44]),
        "+f"(d[45]), "+f"(d[46]), "+f"(d[47])
      : "l"(da), "l"(db), "r"(scaleD));
}
__device__ __forceinline__ void wgmma_qk(float (&d)[32], uint64_t da, uint64_t db, int scaleD) {
  asm volatile("{\n.reg .pred p;\nsetp.ne.b32 p, %34, 0;\n"
      "wgmma.mma_async.sync.aligned.m64n64k16.f32.bf16.bf16 "
      "{%0, %1, %2, %3, %4, %5, %6, %7, %8, %9, %10, %11, %12, %13, %14, %15, %16, %17, %18, %19, %20, %21, %22, %23, %24, %25, %26, %27, %28, %29, %30, "
      "%31}, "
      "%32, %33, p, 1, 1, 0, 0;\n}\n"
      : "+f"(d[0]), "+f"(d[1]), "+f"(d[2]), "+f"(d[3]), "+f"(d[4]), "+f"(d[5]), "+f"(d[6]), "+f"(d[7]), "+f"(d[8]), "+f"(d[9]), "+f"(d[10]), "+f"(d[11]),
        "+f"(d[12]), "+f"(d[13]), "+f"(d[14]), "+f"(d[15]), "+f"(d[16]), "+f"(d[17]), "+f"(d[18]), "+f"(d[19]), "+f"(d[20]), "+f"(d[21]), "+f"(d[22]),
        "+f"(d[23]), "+f"(d[24]), "+f"(d[25]), "+f"(d[26]), "+f"(d[27]), "+f"(d[28]), "+f"(d[29]), "+f"(d[30]), "+f"(d[31])
      : "l"(da), "l"(db), "r"(scaleD));
}
__device__ __forceinline__ void wgmma_qk_rs(float (&d)[32], uint32_t a0, uint32_t a1, uint32_t a2, uint32_t a3, uint64_t db, int scaleD) {
  asm volatile("{\n.reg .pred p;\nsetp.ne.b32 p, %37, 0;\n"
      "wgmma.mma_async.sync.aligned.m64n64k16.f32.bf16.bf16 "
      "{%0, %1, %2, %3, %4, %5, %6, %7, %8, %9, %10, %11, %12, %13, %14, %15, %16, %17, %18, %19, %20, %21, %22, %23, %24, %25, %26, %27, %28, %29, %30, "
      "%31}, "
      "{%32, %33, %34, %35}, %36, p, 1, 1, 0;\n}\n"
      : "+f"(d[0]), "+f"(d[1]), "+f"(d[2]), "+f"(d[3]), "+f"(d[4]), "+f"(d[5]), "+f"(d[6]), "+f"(d[7]), "+f"(d[8]), "+f"(d[9]), "+f"(d[10]), "+f"(d[11]),
        "+f"(d[12]), "+f"(d[13]), "+f"(d[14]), "+f"(d[15]), "+f"(d[16]), "+f"(d[17]), "+f"(d[18]), "+f"(d[19]), "+f"(d[20]), "+f"(d[21]), "+f"(d[22]),
        "+f"(d[23]), "+f"(d[24]), "+f"(d[25]), "+f"(d[26]), "+f"(d[27]), "+f"(d[28]), "+f"(d[29]), "+f"(d[30]), "+f"(d[31])
      : "r"(a0), "r"(a1), "r"(a2), "r"(a3), "l"(db), "r"(scaleD));
}
__device__ __forceinline__ void wgmma_pv(float (&d)[64], uint32_t a0, uint32_t a1, uint32_t a2, uint32_t a3, uint64_t db, int scaleD) {
  asm volatile("{\n.reg .pred p;\nsetp.ne.b32 p, %69, 0;\n"
      "wgmma.mma_async.sync.aligned.m64n128k16.f32.bf16.bf16 "
      "{%0, %1, %2, %3, %4, %5, %6, %7, %8, %9, %10, %11, %12, %13, %14, %15, %16, %17, %18, %19, %20, %21, %22, %23, %24, %25, %26, %27, %28, %29, %30, "
      "%31, %32, %33, %34, %35, %36, %37, %38, %39, %40, %41, %42, %43, %44, %45, %46, %47, %48, %49, %50, %51, %52, %53, %54, %55, %56, %57, %58, %59, %60, "
      "%61, %62, %63}, "
      "{%64, %65, %66, %67}, %68, p, 1, 1, 1;\n}\n"
      : "+f"(d[0]), "+f"(d[1]), "+f"(d[2]), "+f"(d[3]), "+f"(d[4]), "+f"(d[5]), "+f"(d[6]), "+f"(d[7]), "+f"(d[8]), "+f"(d[9]), "+f"(d[10]), "+f"(d[11]),
        "+f"(d[12]), "+f"(d[13]), "+f"(d[14]), "+f"(d[15]), "+f"(d[16]), "+f"(d[17]), "+f"(d[18]), "+f"(d[19]), "+f"(d[20]), "+f"(d[21]), "+f"(d[22]),
        "+f"(d[23]), "+f"(d[24]), "+f"(d[25]), "+f"(d[26]), "+f"(d[27]), "+f"(d[28]), "+f"(d[29]), "+f"(d[30]), "+f"(d[31]), "+f"(d[32]), "+f"(d[33]),
        "+f"(d[34]), "+f"(d[35]), "+f"(d[36]), "+f"(d[37]), "+f"(d[38]), "+f"(d[39]), "+f"(d[40]), "+f"(d[41]), "+f"(d[42]), "+f"(d[43]), "+f"(d[44]),
        "+f"(d[45]), "+f"(d[46]), "+f"(d[47]), "+f"(d[48]), "+f"(d[49]), "+f"(d[50]), "+f"(d[51]), "+f"(d[52]), "+f"(d[53]), "+f"(d[54]), "+f"(d[55]),
        "+f"(d[56]), "+f"(d[57]), "+f"(d[58]), "+f"(d[59]), "+f"(d[60]), "+f"(d[61]), "+f"(d[62]), "+f"(d[63])
      : "r"(a0), "r"(a1), "r"(a2), "r"(a3), "l"(db), "r"(scaleD));
}
__device__ __forceinline__ void wgmma_qk_sp(float (&d)[32], uint32_t a0, uint32_t a1, uint32_t a2, uint32_t a3, uint64_t db, int scaleD, uint32_t meta) {
  asm volatile("{\n.reg .pred p;\nsetp.ne.b32 p, %37, 0;\n"
      "wgmma.mma_async.sp.sync.aligned.m64n64k32.f32.bf16.bf16 "
      "{%0, %1, %2, %3, %4, %5, %6, %7, %8, %9, %10, %11, %12, %13, %14, %15, %16, %17, %18, %19, %20, %21, %22, %23, %24, %25, %26, %27, %28, %29, %30, "
      "%31}, "
      "{%32, %33, %34, %35}, %36, %38, 0, p, 1, 1, 0;\n}\n"
      : "+f"(d[0]), "+f"(d[1]), "+f"(d[2]), "+f"(d[3]), "+f"(d[4]), "+f"(d[5]), "+f"(d[6]), "+f"(d[7]), "+f"(d[8]), "+f"(d[9]), "+f"(d[10]), "+f"(d[11]),
        "+f"(d[12]), "+f"(d[13]), "+f"(d[14]), "+f"(d[15]), "+f"(d[16]), "+f"(d[17]), "+f"(d[18]), "+f"(d[19]), "+f"(d[20]), "+f"(d[21]), "+f"(d[22]),
        "+f"(d[23]), "+f"(d[24]), "+f"(d[25]), "+f"(d[26]), "+f"(d[27]), "+f"(d[28]), "+f"(d[29]), "+f"(d[30]), "+f"(d[31])
      : "r"(a0), "r"(a1), "r"(a2), "r"(a3), "l"(db), "r"(scaleD), "r"(meta));
}
__device__ __forceinline__ void wgmma_pv_sp(float (&d)[64], uint32_t a0, uint32_t a1, uint32_t a2, uint32_t a3, uint64_t db, int scaleD, uint32_t meta) {
  asm volatile("{\n.reg .pred p;\nsetp.ne.b32 p, %69, 0;\n"
      "wgmma.mma_async.sp.sync.aligned.m64n128k32.f32.bf16.bf16 "
      "{%0, %1, %2, %3, %4, %5, %6, %7, %8, %9, %10, %11, %12, %13, %14, %15, %16, %17, %18, %19, %20, %21, %22, %23, %24, %25, %26, %27, %28, %29, %30, "
      "%31, %32, %33, %34, %35, %36, %37, %38, %39, %40, %41, %42, %43, %44, %45, %46, %47, %48, %49, %50, %51, %52, %53, %54, %55, %56, %57, %58, %59, %60, "
      "%61, %62, %63}, "
      "{%64, %65, %66, %67}, %68, %70, 0, p, 1, 1, 1;\n}\n"
      : "+f"(d[0]), "+f"(d[1]), "+f"(d[2]), "+f"(d[3]), "+f"(d[4]), "+f"(d[5]), "+f"(d[6]), "+f"(d[7]), "+f"(d[8]), "+f"(d[9]), "+f"(d[10]), "+f"(d[11]),
        "+f"(d[12]), "+f"(d[13]), "+f"(d[14]), "+f"(d[15]), "+f"(d[16]), "+f"(d[17]), "+f"(d[18]), "+f"(d[19]), "+f"(d[20]), "+f"(d[21]), "+f"(d[22]),
        "+f"(d[23]), "+f"(d[24]), "+f"(d[25]), "+f"(d[26]), "+f"(d[27]), "+f"(d[28]), "+f"(d[29]), "+f"(d[30]), "+f"(d[31]), "+f"(d[32]), "+f"(d[33]),
        "+f"(d[34]), "+f"(d[35]), "+f"(d[36]), "+f"(d[37]), "+f"(d[38]), "+f"(d[39]), "+f"(d[40]), "+f"(d[41]), "+f"(d[42]), "+f"(d[43]), "+f"(d[44]),
        "+f"(d[45]), "+f"(d[46]), "+f"(d[47]), "+f"(d[48]), "+f"(d[49]), "+f"(d[50]), "+f"(d[51]), "+f"(d[52]), "+f"(d[53]), "+f"(d[54]), "+f"(d[55]),
        "+f"(d[56]), "+f"(d[57]), "+f"(d[58]), "+f"(d[59]), "+f"(d[60]), "+f"(d[61]), "+f"(d[62]), "+f"(d[63])
      : "r"(a0), "r"(a1), "r"(a2), "r"(a3), "l"(db), "r"(scaleD), "r"(meta));
}
__device__ __forceinline__ void wgmma_proj_init(float (&d)[64], uint64_t da, uint64_t db, int scaleD) {
  asm volatile("{\n.reg .pred p;\nsetp.ne.b32 p, %66, 0;\n"
      "wgmma.mma_async.sync.aligned.m64n128k16.f32.bf16.bf16 "
      "{%0, %1, %2, %3, %4, %5, %6, %7, %8, %9, %10, %11, %12, %13, %14, %15, %16, %17, %18, %19, %20, %21, %22, %23, %24, %25, %26, %27, %28, %29, %30, "
      "%31, %32, %33, %34, %35, %36, %37, %38, %39, %40, %41, %42, %43, %44, %45, %46, %47, %48, %49, %50, %51, %52, %53, %54, %55, %56, %57, %58, %59, %60, "
      "%61, %62, %63}, "
      "%64, %65, p, 1, 1, 0, 1;\n}\n"
      : "=f"(d[0]), "=f"(d[1]), "=f"(d[2]), "=f"(d[3]), "=f"(d[4]), "=f"(d[5]), "=f"(d[6]), "=f"(d[7]), "=f"(d[8]), "=f"(d[9]), "=f"(d[10]), "=f"(d[11]),
        "=f"(d[12]), "=f"(d[13]), "=f"(d[14]), "=f"(d[15]), "=f"(d[16]), "=f"(d[17]), "=f"(d[18]), "=f"(d[19]), "=f"(d[20]), "=f"(d[21]), "=f"(d[22]),
        "=f"(d[23]), "=f"(d[24]), "=f"(d[25]), "=f"(d[26]), "=f"(d[27]), "=f"(d[28]), "=f"(d[29]), "=f"(d[30]), "=f"(d[31]), "=f"(d[32]), "=f"(d[33]),
        "=f"(d[34]), "=f"(d[35]), "=f"(d[36]), "=f"(d[37]), "=f"(d[38]), "=f"(d[39]), "=f"(d[40]), "=f"(d[41]), "=f"(d[42]), "=f"(d[43]), "=f"(d[44]),
        "=f"(d[45]), "=f"(d[46]), "=f"(d[47]), "=f"(d[48]), "=f"(d[49]), "=f"(d[50]), "=f"(d[51]), "=f"(d[52]), "=f"(d[53]), "=f"(d[54]), "=f"(d[55]),
        "=f"(d[56]), "=f"(d[57]), "=f"(d[58]), "=f"(d[59]), "=f"(d[60]), "=f"(d[61]), "=f"(d[62]), "=f"(d[63])
      : "l"(da), "l"(db), "r"(scaleD));
}
__device__ __forceinline__ void wgmma_proj96_init(float (&d)[64], uint64_t da, uint64_t db, int scaleD) {
  asm volatile("{\n.reg .pred p;\nsetp.ne.b32 p, %50, 0;\n"
      "wgmma.mma_async.sync.aligned.m64n96k16.f32.bf16.bf16 "
      "{%0, %1, %2, %3, %4, %5, %6, %7, %8, %9, %10, %11, %12, %13, %14, %15, %16, %17, %18, %19, %20, %21, %22, %23, %24, %25, %26, %27, %28, %29, %30, "
      "%31, %32, %33, %34, %35, %36, %37, %38, %39, %40, %41, %42, %43, %44, %45, %46, %47}, "
      "%48, %49, p, 1, 1, 1, 0;\n}\n"
      : "=f"(d[0]), "=f"(d[1]), "=f"(d[2]), "=f"(d[3]), "=f"(d[4]), "=f"(d[5]), "=f"(d[6]), "=f"(d[7]), "=f"(d[8]), "=f"(d[9]), "=f"(d[10]), "=f"(d[11]),
        "=f"(d[12]), "=f"(d[13]), "=f"(d[14]), "=f"(d[15]), "=f"(d[16]), "=f"(d[17]), "=f"(d[18]), "=f"(d[19]), "=f"(d[20]), "=f"(d[21]), "=f"(d[22]),
        "=f"(d[23]), "=f"(d[24]), "=f"(d[25]), "=f"(d[26]), "=f"(d[27]), "=f"(d[28]), "=f"(d[29]), "=f"(d[30]), "=f"(d[31]), "=f"(d[32]), "=f"(d[33]),
        "=f"(d[34]), "=f"(d[35]), "=f"(d[36]), "=f"(d[37]), "=f"(d[38]), "=f"(d[39]), "=f"(d[40]), "=f"(d[41]), "=f"(d[42]), "=f"(d[43]), "=f"(d[44]),
        "=f"(d[45]), "=f"(d[46]), "=f"(d[47])
      : "l"(da), "l"(db), "r"(scaleD));
}
__device__ __forceinline__ void wgmma_qk_init(float (&d)[32], uint64_t da, uint64_t db, int scaleD) {
  asm volatile("{\n.reg .pred p;\nsetp.ne.b32 p, %34, 0;\n"
      "wgmma.mma_async.sync.aligned.m64n64k16.f32.bf16.bf16 "
      "{%0, %1, %2, %3, %4, %5, %6, %7, %8, %9, %10, %11, %12, %13, %14, %15, %16, %17, %18, %19, %20, %21, %22, %23, %24, %25, %26, %27, %28, %29, %30, "
      "%31}, "
      "%32, %33, p, 1, 1, 0, 0;\n}\n"
      : "=f"(d[0]), "=f"(d[1]), "=f"(d[2]), "=f"(d[3]), "=f"(d[4]), "=f"(d[5]), "=f"(d[6]), "=f"(d[7]), "=f"(d[8]), "=f"(d[9]), "=f"(d[10]), "=f"(d[11]),
        "=f"(d[12]), "=f"(d[13]), "=f"(d[14]), "=f"(d[15]), "=f"(d[16]), "=f"(d[17]), "=f"(d[18]), "=f"(d[19]), "=f"(d[20]), "=f"(d[21]), "=f"(d[22]),
        "=f"(d[23]), "=f"(d[24]), "=f"(d[25]), "=f"(d[26]), "=f"(d[27]), "=f"(d[28]), "=f"(d[29]), "=f"(d[30]), "=f"(d[31])
      : "l"(da), "l"(db), "r"(scaleD));
}
__device__ __forceinline__ void wgmma_qk_rs_init(float (&d)[32], uint32_t a0, uint32_t a1, uint32_t a2, uint32_t a3, uint64_t db, int scaleD) {
  asm volatile("{\n.reg .pred p;\nsetp.ne.b32 p, %37, 0;\n"
      "wgmma.mma_async.sync.aligned.m64n64k16.f32.bf16.bf16 "
      "{%0, %1, %2, %3, %4, %5, %6, %7, %8, %9, %10, %11, %12, %13, %14, %15, %16, %17, %18, %19, %20, %21, %22, %23, %24, %25, %26, %27, %28, %29, %30, "
      "%31}, "
      "{%32, %33, %34, %35}, %36, p, 1, 1, 0;\n}\n"
      : "=f"(d[0]), "=f"(d[1]), "=f"(d[2]), "=f"(d[3]), "=f"(d[4]), "=f"(d[5]), "=f"(d[6]), "=f"(d[7]), "=f"(d[8]), "=f"(d[9]), "=f"(d[10]), "=f"(d[11]),
        "=f"(d[12]), "=f"(d[13]), "=f"(d[14]), "=f"(d[15]), "=f"(d[16]), "=f"(d[17]), "=f"(d[18]), "=f"(d[19]), "=f"(d[20]), "=f"(d[21]), "=f"(d[22]),
        "=f"(d[23]), "=f"(d[24]), "=f"(d[25]), "=f"(d[26]), "=f"(d[27]), "=f"(d[28]), "=f"(d[29]), "=f"(d[30]), "=f"(d[31])
      : "r"(a0), "r"(a1), "r"(a2), "r"(a3), "l"(db), "r"(scaleD));
}
__device__ __forceinline__ void wgmma_pv_init(float (&d)[64], uint32_t a0, uint32_t a1, uint32_t a2, uint32_t a3, uint64_t db, int scaleD) {
  asm volatile("{\n.reg .pred p;\nsetp.ne.b32 p, %69, 0;\n"
      "wgmma.mma_async.sync.aligned.m64n128k16.f32.bf16.bf16 "
      "{%0, %1, %2, %3, %4, %5, %6, %7, %8, %9, %10, %11, %12, %13, %14, %15, %16, %17, %18, %19, %20, %21, %22, %23, %24, %25, %26, %27, %28, %29, %30, "
      "%31, %32, %33, %34, %35, %36, %37, %38, %39, %40, %41, %42, %43, %44, %45, %46, %47, %48, %49, %50, %51, %52, %53, %54, %55, %56, %57, %58, %59, %60, "
      "%61, %62, %63}, "
      "{%64, %65, %66, %67}, %68, p, 1, 1, 1;\n}\n"
      : "=f"(d[0]), "=f"(d[1]), "=f"(d[2]), "=f"(d[3]), "=f"(d[4]), "=f"(d[5]), "=f"(d[6]), "=f"(d[7]), "=f"(d[8]), "=f"(d[9]), "=f"(d[10]), "=f"(d[11]),
        "=f"(d[12]), "=f"(d[13]), "=f"(d[14]), "=f"(d[15]), "=f"(d[16]), "=f"(d[17]), "=f"(d[18]), "=f"(d[19]), "=f"(d[20]), "=f"(d[21]), "=f"(d[22]),
        "=f"(d[23]), "=f"(d[24]), "=f"(d[25]), "=f"(d[26]), "=f"(d[27]), "=f"(d[28]), "=f"(d[29]), "=f"(d[30]), "=f"(d[31]), "=f"(d[32]), "=f"(d[33]),
        "=f"(d[34]), "=f"(d[35]), "=f"(d[36]), "=f"(d[37]), "=f"(d[38]), "=f"(d[39]), "=f"(d[40]), "=f"(d[41]), "=f"(d[42]), "=f"(d[43]), "=f"(d[44]),
        "=f"(d[45]), "=f"(d[46]), "=f"(d[47]), "=f"(d[48]), "=f"(d[49]), "=f"(d[50]), "=f"(d[51]), "=f"(d[52]), "=f"(d[53]), "=f"(d[54]), "=f"(d[55]),
        "=f"(d[56]), "=f"(d[57]), "=f"(d[58]), "=f"(d[59]), "=f"(d[60]), "=f"(d[61]), "=f"(d[62]), "=f"(d[63])
      : "r"(a0), "r"(a1), "r"(a2), "r"(a3), "l"(db), "r"(scaleD));
}
__device__ __forceinline__ void wgmma_qk_sp_init(float (&d)[32], uint32_t a0, uint32_t a1, uint32_t a2, uint32_t a3, uint64_t db, int scaleD, uint32_t meta) {
  asm volatile("{\n.reg .pred p;\nsetp.ne.b32 p, %37, 0;\n"
      "wgmma.mma_async.sp.sync.aligned.m64n64k32.f32.bf16.bf16 "
      "{%0, %1, %2, %3, %4, %5, %6, %7, %8, %9, %10, %11, %12, %13, %14, %15, %16, %17, %18, %19, %20, %21, %22, %23, %24, %25, %26, %27, %28, %29, %30, "
      "%31}, "
      "{%32, %33, %34, %35}, %36, %38, 0, p, 1, 1, 0;\n}\n"
      : "=f"(d[0]), "=f"(d[1]), "=f"(d[2]), "=f"(d[3]), "=f"(d[4]), "=f"(d[5]), "=f"(d[6]), "=f"(d[7]), "=f"(d[8]), "=f"(d[9]), "=f"(d[10]), "=f"(d[11]),
        "=f"(d[12]), "=f"(d[13]), "=f"(d[14]), "=f"(d[15]), "=f"(d[16]), "=f"(d[17]), "=f"(d[18]), "=f"(d[19]), "=f"(d[20]), "=f"(d[21]), "=f"(d[22]),
        "=f"(d[23]), "=f"(d[24]), "=f"(d[25]), "=f"(d[26]), "=f"(d[27]), "=f"(d[28]), "=f"(d[29]), "=f"(d[30]), "=f"(d[31])
      : "r"(a0), "r"(a1), "r"(a2), "r"(a3), "l"(db), "r"(scaleD), "r"(meta));
}
__device__ __forceinline__ void wgmma_pv_sp_init(float (&d)[64], uint32_t a0, uint32_t a1, uint32_t a2, uint32_t a3, uint64_t db, int scaleD, uint32_t meta) {
  asm volatile("{\n.reg .pred p;\nsetp.ne.b32 p, %69, 0;\n"
      "wgmma.mma_async.sp.sync.aligned.m64n128k32.f32.bf16.bf16 "
      "{%0, %1, %2, %3, %4, %5, %6, %7, %8, %9, %10, %11, %12, %13, %14, %15, %16, %17, %18, %19, %20, %21, %22, %23, %24, %25, %26, %27, %28, %29, %30, "
      "%31, %32, %33, %34, %35, %36, %37, %38, %39, %40, %41, %42, %43, %44, %45, %46, %47, %48, %49, %50, %51, %52, %53, %54, %55, %56, %57, %58, %59, %60, "
      "%61, %62, %63}, "
      "{%64, %65, %66, %67}, %68, %70, 0, p, 1, 1, 1;\n}\n"
      : "=f"(d[0]), "=f"(d[1]), "=f"(d[2]), "=f"(d[3]), "=f"(d[4]), "=f"(d[5]), "=f"(d[6]), "=f"(d[7]), "=f"(d[8]), "=f"(d[9]), "=f"(d[10]), "=f"(d[11]),
        "=f"(d[12]), "=f"(d[13]), "=f"(d[14]), "=f"(d[15]), "=f"(d[16]), "=f"(d[17]), "=f"(d[18]), "=f"(d[19]), "=f"(d[20]), "=f"(d[21]), "=f"(d[22]),
        "=f"(d[23]), "=f"(d[24]), "=f"(d[25]), "=f"(d[26]), "=f"(d[27]), "=f"(d[28]), "=f"(d[29]), "=f"(d[30]), "=f"(d[31]), "=f"(d[32]), "=f"(d[33]),
        "=f"(d[34]), "=f"(d[35]), "=f"(d[36]), "=f"(d[37]), "=f"(d[38]), "=f"(d[39]), "=f"(d[40]), "=f"(d[41]), "=f"(d[42]), "=f"(d[43]), "=f"(d[44]),
        "=f"(d[45]), "=f"(d[46]), "=f"(d[47]), "=f"(d[48]), "=f"(d[49]), "=f"(d[50]), "=f"(d[51]), "=f"(d[52]), "=f"(d[53]), "=f"(d[54]), "=f"(d[55]),
        "=f"(d[56]), "=f"(d[57]), "=f"(d[58]), "=f"(d[59]), "=f"(d[60]), "=f"(d[61]), "=f"(d[62]), "=f"(d[63])
      : "r"(a0), "r"(a1), "r"(a2), "r"(a3), "l"(db), "r"(scaleD), "r"(meta));
}

constexpr int NB = 16, SQ = 224, DM = 640, NH = 32, SK = 1024, DH = 128;
constexpr int HD = NH * DH;
constexpr int NBETA = 2 * NB;
constexpr int NCTA = 132;
constexpr int NS = 10;
constexpr int SLOT = 16384;
constexpr int QBUF_OFF = NS * SLOT;
constexpr int NSX = NS + 4;
constexpr int BAR_OFF = NSX * SLOT;
constexpr int BAR_FULL = BAR_OFF;
constexpr int BAR_EMPTY = BAR_OFF + 8 * NSX;
constexpr int BAR_STG = BAR_OFF + 16 * NSX;
constexpr int BAR_OUT = BAR_STG + 32;
constexpr int BAR_DESC = BAR_OUT + 8;
constexpr int BAR_GO = BAR_DESC + 8;
constexpr int DESC_OFF = BAR_GO + 8;
constexpr int EPOCH_OFF = DESC_OFF + 16;
constexpr int TRACE_OFF = EPOCH_OFF + 8;
constexpr int SMEM_BYTES = TRACE_OFF;
constexpr float SM_C = 0.08838834764831845f * 1.4426950408889634f;
constexpr float SUM_HI = 1099511627776.f, SUM_LO = 1.f / 1099511627776.f;
constexpr uint32_t META_QK = 0xEEEE4444u;
constexpr uint32_t META_PV = 0x44EEEE44u;

#define QK_EARLY_MASK 3
#define ST_ORDER 0x2130
#define LAG_BAR 5
#define ST_NOW 9
#define PF_STEP 5
#define KV_WIN_UNITS 2
#define KV_WIN_D 4
#define SF 0xfe1f
#define O_STEPS 4
#define KV_WIN_RAMP 4
#define PDEPTH 0
#define KV_WIN_TILES -2
#define PR_KV 2
#define PR_X 2
#define PR_W 2
#define REG_C 232
#define REG_P 40
#define GO_P 4
#define P_POS 224
#define B_LATE 28
#define H_LATE 24
#define EARLY_MASK 0x1fffu
#define PIECE_TABLE 0x5026401a,0x68dc4034,0x50275816,0x695a5837,0x50295015,0x6a175036,0x501e080d,0x681f083c,0x50253812,0x69d8383a,0x403f980e,0x80000000,0x5036180f,0x80000000,0x50203011,0x69993032,0x50367019,0x80000000,0x50224814,0x6a954835,0x50246017,0x6b526038,0x502c6818,0x6dc86839,0x5017b813,0x69d8b85f,0x50102810,0x685e2831,0x646e2030,0x80000000,0x501f101c,0x6dc8102f,0x5017801b,0x6c8d805e,0x6627783b,0x80000000,0x6627b033,0x80000000,0x501a901e,0x80000000,0x56d6881e,0x80000000,0x501ca81d,0x80000000,0x6762a03d,0x80000000,0x67e0002d,0x80000000,0x5512c01f,0x80000000,0x5013c81f,0x80000000

struct Params {
  CUtensorMap x[2][2], wq[2], kv[2][2], wo[2];
  CUtensorMap o_ld[2], o_st[2], out_st[2];
  const __nv_bfloat16* kp[2];
  const __nv_bfloat16* vp[2];
};

constexpr int NPART = 32 * 5, O_BLOCKS = NBETA * 64 + 2 * NPART;
__device__ __align__(128) __nv_bfloat16 g_o[(size_t)O_BLOCKS * SQ * 64];
__device__ unsigned g_cnt[2][NBETA];
__device__ unsigned g_epoch, g_next;
__device__ unsigned g_flag[NPART];

__device__ __forceinline__ uint32_t smem_u32(const void* p) { return (uint32_t)__cvta_generic_to_shared(p); }
__device__ __forceinline__ void mbar_arrive(uint32_t bar) {
  asm volatile("mbarrier.arrive.shared::cta.b64 _, [%0];" ::"r"(bar) : "memory");
}
__device__ __forceinline__ void mbar_arrive_warp(uint32_t bar) {
  asm volatile("{\n.reg .pred p;\nelect.sync _|p, 0xffffffff;\n@p mbarrier.arrive.shared::cta.b64 _, [%0];\n}" ::"r"(bar) : "memory");
}
__device__ __forceinline__ int lane_now() { int l; asm volatile("mov.u32 %0, %%laneid;" : "=r"(l)); return l; }
__device__ __forceinline__ bool mbar_try(uint32_t bar, uint32_t parity) {
  uint32_t ok;
  asm volatile("{\n.reg .pred p;\nmbarrier.try_wait.parity.shared::cta.b64 p, [%1], %2;\nselp.u32 %0, 1, 0, p;\n}"
               : "=r"(ok) : "r"(bar), "r"(parity) : "memory");
  return ok;
}
__device__ __forceinline__ bool mbar_test(uint32_t bar, uint32_t parity) {
  uint32_t ok;
  asm volatile("{\n.reg .pred p;\nmbarrier.test_wait.parity.shared::cta.b64 p, [%1], %2;\nselp.u32 %0, 1, 0, p;\n}"
               : "=r"(ok) : "r"(bar), "r"(parity) : "memory");
  return ok;
}
__device__ __forceinline__ void mbar_wait_w(uint32_t bar, uint32_t parity) {
  uint32_t n = 0;
  while (!__all_sync(0xffffffffu, mbar_try(bar, parity))) {
    if (++n > (1u << 22)) __trap();
  }
}
#define ELECT "{\n.reg .pred p;\nelect.sync _|p, 0xffffffff;\n@p "
__device__ __forceinline__ void tma_st3_hint_w(const CUtensorMap* m, uint32_t src, int c0, int c1, int c2, uint64_t pol) {
  asm volatile(ELECT "cp.async.bulk.tensor.3d.global.shared::cta.bulk_group.L2::cache_hint [%0, {%2, %3, %4}], [%1], %5;\n}"
               ::"l"(m), "r"(src), "r"(c0), "r"(c1), "r"(c2), "l"(pol) : "memory");
}
#define EXPECT(bar, bytes) "mbarrier.arrive.expect_tx.shared::cta.b64 _, [" bar "], " bytes ";\n@p "
__device__ __forceinline__ void tma_ld2_w(uint32_t dst, const CUtensorMap* m, int c0, int c1, uint32_t bar, uint32_t bytes) {
  asm volatile(ELECT EXPECT("%2", "%5") "cp.async.bulk.tensor.2d.shared::cluster.global.mbarrier::complete_tx::bytes [%0], [%1, {%3, %4}], [%2];\n}"
               ::"r"(dst), "l"(m), "r"(bar), "r"(c0), "r"(c1), "r"(bytes) : "memory");
}
__device__ __forceinline__ void tma_ld2_hint_w(uint32_t dst, const CUtensorMap* m, int c0, int c1, uint32_t bar, uint32_t bytes, uint64_t pol) {
  asm volatile(ELECT EXPECT("%2", "%6") "cp.async.bulk.tensor.2d.shared::cluster.global.mbarrier::complete_tx::bytes.L2::cache_hint"
               " [%0], [%1, {%3, %4}], [%2], %5;\n}"
               ::"r"(dst), "l"(m), "r"(bar), "r"(c0), "r"(c1), "l"(pol), "r"(bytes) : "memory");
}
__device__ __forceinline__ void tma_ld3_w(uint32_t dst, const CUtensorMap* m, int c0, int c1, int c2, uint32_t bar, uint32_t bytes) {
  asm volatile(ELECT EXPECT("%2", "%6") "cp.async.bulk.tensor.3d.shared::cluster.global.mbarrier::complete_tx::bytes [%0], [%1, {%3, %4, %5}], [%2];\n}"
               ::"r"(dst), "l"(m), "r"(bar), "r"(c0), "r"(c1), "r"(c2), "r"(bytes) : "memory");
}
__device__ __forceinline__ void tma_ld3_hint_w(uint32_t dst, const CUtensorMap* m, int c0, int c1, int c2, uint32_t bar, uint64_t pol) {
  asm volatile(ELECT EXPECT("%2", "16384") "cp.async.bulk.tensor.3d.shared::cluster.global.mbarrier::complete_tx::bytes.L2::cache_hint"
               " [%0], [%1, {%3, %4, %5}], [%2], %6;\n}"
               ::"r"(dst), "l"(m), "r"(bar), "r"(c0), "r"(c1), "r"(c2), "l"(pol) : "memory");
}
__device__ __forceinline__ void tma_ld_wo_w(uint32_t dst, const CUtensorMap* m, int col, int grp, uint32_t bar) {
  asm volatile(ELECT EXPECT("%2", "16384") "cp.async.bulk.tensor.5d.shared::cluster.global.mbarrier::complete_tx::bytes [%0], [%1, {%3, 0, 0, 0, %4}], [%2];\n"
               "@p cp.async.bulk.tensor.5d.shared::cluster.global.mbarrier::complete_tx::bytes [%5], [%1, {%6, 0, 0, 0, %4}], [%2];\n}"
               ::"r"(dst), "l"(m), "r"(bar), "r"(col), "r"(grp), "r"(dst + 8192), "r"(col + 64) : "memory");
}
__device__ __forceinline__ void mbar_arrive8_w(uint32_t bar) {
  asm volatile(ELECT "mbarrier.arrive.shared::cta.b64 _, [%0], 8;\n}" ::"r"(bar) : "memory");
}
__device__ __forceinline__ void bulk_commit() { asm volatile("cp.async.bulk.commit_group;" ::: "memory"); }
template <int N> __device__ __forceinline__ void bulk_wait_read() { asm volatile("cp.async.bulk.wait_group.read %0;" ::"n"(N) : "memory"); }
__device__ __forceinline__ void wg_fence() { asm volatile("wgmma.fence.sync.aligned;" ::: "memory"); }
__device__ __forceinline__ void wg_commit() { asm volatile("wgmma.commit_group.sync.aligned;" ::: "memory"); }
template <int N> __device__ __forceinline__ void wg_wait() { asm volatile("wgmma.wait_group.sync.aligned %0;" ::"n"(N) : "memory"); }
__device__ __forceinline__ void fence_async_smem() { asm volatile("fence.proxy.async.shared::cta;" ::: "memory"); }
__device__ __forceinline__ void bar_sync(int id, int n) { asm volatile("bar.sync %0, %1;" ::"r"(id), "r"(n) : "memory"); }
__device__ __forceinline__ void touch(float& a) { asm volatile("neg.f32 %0, %0;" : "+f"(a)); }
__device__ __forceinline__ void touch(uint32_t& a) { asm volatile("not.b32 %0, %0;" : "+r"(a)); }
template <typename T, int N> __device__ __forceinline__ void touch(T (&a)[N]) {
#pragma unroll
  for (int i = 0; i < N; i++) touch(a[i]);
}
template <int ID, typename... A> __device__ __forceinline__ void sched_fence(uint32_t x, A&... a) {
  if (!((SF >> ID) & 1)) return;
  asm volatile("" : "+r"(x)::"memory");
#pragma unroll 1
  for (; __builtin_expect(x >= 100 + ID, 0); x >>= 1) { (touch(a), ...); __nanosleep(x); }
}
template <int N> __device__ __forceinline__ void reg_fence(float (&a)[N]) {
#pragma unroll
  for (int i = 0; i < N; i++) asm volatile("" : "+f"(a[i])::"memory");
}
template <int N> __device__ __forceinline__ void reg_fence(uint32_t (&a)[N]) {
#pragma unroll
  for (int i = 0; i < N; i++) asm volatile("" : "+r"(a[i])::"memory");
}
__device__ __forceinline__ float ex2(float x) { float y; asm("ex2.approx.ftz.f32 %0, %1;" : "=f"(y) : "f"(x)); return y; }
__device__ __forceinline__ uint32_t pack_bf16(float lo, float hi) {
  uint32_t r; asm("cvt.rn.bf16x2.f32 %0, %1, %2;" : "=r"(r) : "f"(hi), "f"(lo)); return r;
}
__device__ __forceinline__ void stsm4(uint32_t a, uint32_t r0, uint32_t r1, uint32_t r2, uint32_t r3) {
  asm volatile("stmatrix.sync.aligned.m8n8.x4.shared.b16 [%0], {%1, %2, %3, %4};" ::"r"(a), "r"(r0), "r"(r1), "r"(r2), "r"(r3) : "memory");
}
__device__ __forceinline__ void stsm4t(uint32_t a, uint32_t r0, uint32_t r1, uint32_t r2, uint32_t r3) {
  asm volatile("stmatrix.sync.aligned.m8n8.x4.trans.shared.b16 [%0], {%1, %2, %3, %4};" ::"r"(a), "r"(r0), "r"(r1), "r"(r2), "r"(r3) : "memory");
}
__device__ __forceinline__ void ldsm4(uint32_t a, uint32_t& r0, uint32_t& r1, uint32_t& r2, uint32_t& r3) {
  asm volatile("ldmatrix.sync.aligned.m8n8.x4.shared.b16 {%0, %1, %2, %3}, [%4];" : "=r"(r0), "=r"(r1), "=r"(r2), "=r"(r3) : "r"(a) : "memory");
}
__device__ __forceinline__ void sts16(uint32_t a, uint32_t v) { asm volatile("st.shared.u16 [%0], %1;" ::"r"(a), "h"((uint16_t)v) : "memory"); }
__device__ __forceinline__ void mma16816(float& c0, float& c1, float& c2, float& c3, uint32_t a0, uint32_t a1, uint32_t a2, uint32_t a3,
                                         uint32_t b0, uint32_t b1) {
  asm volatile("mma.sync.aligned.m16n8k16.row.col.f32.bf16.bf16.f32 {%0, %1, %2, %3}, {%4, %5, %6, %7}, {%8, %9}, {%0, %1, %2, %3};"
               : "+f"(c0), "+f"(c1), "+f"(c2), "+f"(c3) : "r"(a0), "r"(a1), "r"(a2), "r"(a3), "r"(b0), "r"(b1));
}
__device__ __forceinline__ uint32_t sdesc(uint32_t addr, uint32_t lbo) { return (addr >> 4) + ((lbo >> 4) << 16); }
__device__ __forceinline__ uint64_t desc64(uint32_t lo, uint32_t hi) { uint64_t d; asm("mov.b64 %0, {%1, %2};" : "=l"(d) : "r"(lo), "r"(hi)); return d; }
__device__ __forceinline__ void dadd(uint64_t& d, uint32_t inc) {
  asm("{\n.reg .b32 l, h;\nmov.b64 {l, h}, %0;\nadd.u32 l, l, %1;\nmov.b64 %0, {l, h};\n}" : "+l"(d) : "r"(inc));
}

struct Ring {
  uint32_t slot, phase, xp;
  __device__ __forceinline__ void uniform() {
    slot = __shfl_sync(0xffffffffu, slot, 0); phase = __shfl_sync(0xffffffffu, phase, 0); xp = __shfl_sync(0xffffffffu, xp, 0);
  }
  __device__ __forceinline__ void next() { if (++slot == NS) { slot = 0; phase ^= 1; } }
  __device__ __forceinline__ void next_if(bool p) { slot += p; if (slot == NS) { slot = 0; phase ^= 1; } }
};
__device__ __forceinline__ uint32_t borrow(int ks, int n) {
  const int k = ks + 1;
  return k >= 4 && !(k & 2) && k < n ? k & 1 : 2;
}

constexpr uint32_t Q_RANGES = NBETA * NH + __builtin_popcount(EARLY_MASK) * 5, Q_ALL = NBETA * (NH + 5);
constexpr int NRANGE = NCTA / 5;
struct Work { int kind, mode, k0, nsteps, range, beta, sub; };
struct Sched { uint16_t queue[Q_ALL]; uint32_t piece[NRANGE + 1][4]; };
constexpr Sched make_sched() {
  Sched s{};
  int q = 0, a = 0;
  for (int pass = 0; pass < 2; pass++)
    for (int b = pass ? B_LATE : 0; b < NBETA; b++)
      for (int h = pass ? H_LATE : 0; h < (pass || b < B_LATE ? NH : H_LATE); h++) {
        if (a >= P_POS && (a - P_POS) % 32 == 0 && (EARLY_MASK >> ((a - P_POS) / 32) & 1))
          for (int col = 0; col < 5; col++) s.queue[q++] = 0x8000 | col << 8 | (a - P_POS) / 32;
        s.queue[q++] = b << 5 | h;
        a++;
      }
  for (int b = 0; b < NBETA; b++)
    for (int col = 0; col < 5 && !(EARLY_MASK >> b & 1); col++) s.queue[q++] = 0x8000 | col << 8 | b;
  constexpr uint32_t T[NRANGE * 2] = {PIECE_TABLE};
  for (int g = 0; g <= NRANGE; g++)
    for (int n = 0; n < 4; n++) s.piece[g][n] = g < NRANGE && n < 2 ? T[2 * g + n] : 2u << 30;
  return s;
}
__constant__ Sched c_sched = make_sched();
__device__ __forceinline__ Work decode(uint32_t d) {
  Work w;
  w.kind = d >> 30; if (w.kind == 3) w.kind = 1;
  w.mode = (d >> 28) & 3; w.k0 = (d >> 22) & 63;
  if (w.kind == 0) { w.beta = (d >> 5) & 31; w.sub = d & 31; w.nsteps = DM / 64; }
  else { w.beta = d & 31; w.sub = (d >> 8) & 7; w.nsteps = ((d >> 16) & 63) + 1; }
  w.range = ((d >> 11) & 31) * 5 + w.sub;
  return w;
}

__device__ __forceinline__ bool reached(const unsigned* cnt, unsigned target) {
  unsigned v;
  asm volatile("ld.acquire.gpu.global.u32 %0, [%1];" : "=r"(v) : "l"(cnt) : "memory");
  return (int)(v - target) >= 0;
}
__device__ __forceinline__ void wait_count(const unsigned* cnt, unsigned target) {
  unsigned n = 0;
  while (!__all_sync(0xffffffffu, reached(cnt, target))) { if (++n > (1u << 24)) __trap(); }
}
__device__ __forceinline__ uint32_t lds(uint32_t a) { uint32_t v; asm volatile("ld.volatile.shared.u32 %0, [%1];" : "=r"(v) : "r"(a) : "memory"); return v; }

#define TRACE(u, e)
#define T3(u, e)
#define T2C(u, e)
#define T2P(u, r, e)
#define TTAIL(k)
#define TCLK(k)
#define TRACE_P(u, e)
#define TRACE_IN(u, e)

struct Ctx {
  uint32_t sb;
  int wg, warp;
  uint32_t mqk, mpv;
  bool lead;
  int lane0, lane;
  int src;
};
template <int N> __device__ __forceinline__ uint32_t dhi(uint32_t lo) { return 0x40000040u + (lo >> (26 + N)); }
__device__ __forceinline__ void release(const Ctx& c, uint32_t slot) {
  if (c.lead) mbar_arrive(c.sb + BAR_EMPTY + slot * 8);
}
__device__ __forceinline__ uint32_t acquire(const Ctx& c, Ring& r, bool have = false) {
  const uint32_t s = r.slot;
  if (!have) mbar_wait_w(c.sb + BAR_FULL + s * 8, r.phase);
  r.next();
  return s;
}
__device__ __forceinline__ void mbar_wait2_w(uint32_t b0, uint32_t p0, uint32_t b1, uint32_t p1) {
  uint32_t n = 0;
  while (!__all_sync(0xffffffffu, mbar_try(b0, p0) & mbar_try(b1, p1))) {
    if (++n > (1u << 22)) __trap();
  }
}
__device__ __forceinline__ void mbar_wait3_w(uint32_t b0, uint32_t p0, uint32_t b1, uint32_t p1, uint32_t b2, uint32_t p2) {
  uint32_t n = 0;
  while (!__all_sync(0xffffffffu, mbar_try(b0, p0) & mbar_try(b1, p1) & mbar_try(b2, p2))) {
    if (++n > (1u << 22)) __trap();
  }
}
__device__ __forceinline__ void acquire2(const Ctx& c, Ring& r, uint32_t& s0, uint32_t& s1, bool have = false) {
  const uint32_t p0 = r.phase;
  s0 = r.slot; r.next(); s1 = r.slot;
  if (!have) mbar_wait2_w(c.sb + BAR_FULL + s0 * 8, p0, c.sb + BAR_FULL + s1 * 8, r.phase);
  r.next();
}
template <int N>
__device__ __forceinline__ bool peek(const Ctx& c, Ring r) {
  bool ok = true;
#pragma unroll
  for (int k = 0; k < N; k++) { ok &= mbar_test(c.sb + BAR_FULL + r.slot * 8, r.phase); r.next(); }
  return ok;
}
__device__ __forceinline__ void staged(const Ctx& c, int part) {
  fence_async_smem();
  __syncwarp();
  mbar_arrive_warp(c.sb + BAR_STG + c.wg * 16 + part * 8);
}

template <int WG, bool FIRST, int H>
__device__ __forceinline__ void proj_half(const Ctx& c, float (&acc)[64], uint32_t w, uint32_t x, uint32_t sw) {
  uint64_t dx = desc64((c.sb + x * SLOT + (WG ? 0 : H * 8192)) >> 4, dhi<0>(x) + sw);
  uint64_t dw = desc64(WG ? (c.sb + w * SLOT + H * 8192) >> 4 : sdesc(c.sb + w * SLOT, 8192), dhi<1>(x));
  wg_fence();
  if (WG) { if (FIRST) wgmma_proj96_init(acc, dw, dx, 0); else wgmma_proj96(acc, dw, dx, 1); }
  else { if (FIRST) wgmma_proj_init(acc, dx, dw, 0); else wgmma_proj(acc, dx, dw, 1); }
#pragma unroll
  for (int k = 1; k < 4; k++) {
    dadd(dx, k == 2 ? 2 + (sw >> 30) * 28 : 2); dadd(dw, 128);
    if (WG) wgmma_proj96(acc, dw, dx, 1); else wgmma_proj(acc, dx, dw, 1);
  }
  wg_commit();
}

__device__ __forceinline__ void proj_store16(uint32_t a, const float* f, float sc) {
  stsm4t(a, pack_bf16(f[0] * sc, f[1] * sc), pack_bf16(f[2] * sc, f[3] * sc), pack_bf16(f[4] * sc, f[5] * sc), pack_bf16(f[6] * sc, f[7] * sc));
}

__device__ __forceinline__ uint32_t stage_off(const Ctx& c) {
  const int lane = c.lane, mi = lane >> 3, r8 = lane & 7;
  return ((mi >> 1) * 8 + r8) * 128 + (((2 * c.warp + (mi & 1)) ^ r8) << 4);
}
__device__ __forceinline__ uint32_t q3_swz(uint32_t r8) { return ((r8 & 3) << 1) | (r8 >> 2); }
template <int H>
__device__ __forceinline__ void stage_t2(const Ctx& c, const float (&a)[64], float sc) {
  const uint32_t base = c.sb + QBUF_OFF + 2 * 16384 + H * 8192 + stage_off(c);
#pragma unroll
  for (int jj = 0; jj < 4; jj++) proj_store16(base + jj * 2048, &a[jj * 8], sc);
}
template <int H, bool IS_Q>
__device__ __forceinline__ void stage_t3(const Ctx& c, const float (&a)[64], float sc) {
  const uint32_t off = stage_off(c), r8 = (off >> 7) & 7;
  const uint32_t t3 = c.sb + QBUF_OFF + 3 * 16384 + H * 4096 + (IS_Q ? off ^ ((r8 ^ q3_swz(r8)) << 4) : off);
  proj_store16(t3, &a[32], sc);
  proj_store16(t3 + 2048, &a[40], sc);
}

template <bool TRANS>
__device__ __forceinline__ void add16(uint32_t a, float* f) {
  uint32_t r[4];
  if (TRANS) asm volatile("ldmatrix.sync.aligned.m8n8.x4.trans.shared.b16 {%0, %1, %2, %3}, [%4];"
                          : "=r"(r[0]), "=r"(r[1]), "=r"(r[2]), "=r"(r[3]) : "r"(a) : "memory");
  else ldsm4(a, r[0], r[1], r[2], r[3]);
#pragma unroll
  for (int i = 0; i < 4; i++) { f[2 * i] += __uint_as_float(r[i] << 16); f[2 * i + 1] += __uint_as_float(r[i] & 0xffff0000u); }
}

__device__ __forceinline__ void trace_dump(const Ctx& c) {
}
struct RowSum { float l0, l1; };
__device__ __forceinline__ const char* o_addr(uint32_t item, int row, int lane) {
  return reinterpret_cast<const char*>(g_o) + ((item * (2 * SQ) + row) * 128 + (lane ^ (lane >> 3)) * 16);
}
__device__ __forceinline__ void o_stg(const char* p, int i, const uint32_t* q) {
  asm volatile("st.global.v4.b32 [%0], {%1, %2, %3, %4};"
               ::"l"(p + (i >> 1) * (SQ * 128) + (i & 1) * 512), "r"(q[0]), "r"(q[1]), "r"(q[2]), "r"(q[3]) : "memory");
}
template <int MODE, int I0 = 0, int NI = 4>
__device__ __forceinline__ void o_emit(const char* p, const float (&o)[64], float inv) {
#pragma unroll
  for (int i = I0; i < I0 + NI; i++) {
    uint32_t q[4];
#pragma unroll
    for (int j = 0; j < 4; j++) q[j] = pack_bf16(o[16 * i + 4 * j + 2 * MODE] * inv, o[16 * i + 4 * j + 2 * MODE + 1] * inv);
    o_stg(p, i, q);
  }
}
__device__ __forceinline__ void o_done(const Ctx& c) {
  __syncwarp();
  mbar_arrive_warp(c.sb + BAR_OUT);
  __syncwarp();
}
template <int WG>
__device__ __forceinline__ void o_first(const Ctx& c, uint32_t item, float (&o)[64], const RowSum& inv) {
  const char* p = o_addr(item, WG ? 192 + 8 * c.warp : 64 + 16 * c.warp, c.lane);
  reg_fence(o);
  if (WG) {
    uint32_t q[16];
#pragma unroll
    for (int j = 0; j < 16; j++) q[j] = pack_bf16((o[4 * j] + o[4 * j + 2]) * inv.l0, (o[4 * j + 1] + o[4 * j + 3]) * inv.l0);
#pragma unroll
    for (int i = 0; i < 4; i++) o_stg(p, i, q + 4 * i);
  } else { o_emit<0>(p, o, inv.l0); o_emit<1>(p + 1024, o, inv.l1); }
}
template <int K0, int K1>
__device__ __forceinline__ void o_piece(const Ctx& c, const char* p, int k, const float (&o)[64], const RowSum& inv) {
  constexpr int NI = 8 / O_STEPS, M = K0 * NI / 4;
  if constexpr (K1 - K0 == 1) {
    o_emit<M, K0 * NI % 4, NI>(p + M * 1024, o, M ? inv.l1 : inv.l0);
    if (K1 == O_STEPS) o_done(c);
  } else {
    if (k <= (K0 + K1) / 2) o_piece<K0, (K0 + K1) / 2>(c, p, k, o, inv); else o_piece<(K0 + K1) / 2, K1>(c, p, k, o, inv);
  }
}
template <int WG>
__device__ __forceinline__ void o_second(const Ctx& c, uint32_t item, int k, float (&o)[64], const RowSum& inv) {
  reg_fence(o);
  o_piece<0, O_STEPS>(c, o_addr(item, 128 * WG + 16 * c.warp, c.lane0 + (k >> 8)), k, o, inv);
}
template <int WG>
__device__ __forceinline__ void release_q(const Ctx& c) {
#pragma unroll
  for (int t = 0; t < 2; t++)
    if (c.lead) asm volatile("mbarrier.arrive.shared::cta.b64 _, [%0], 2;" ::"r"(c.sb + BAR_EMPTY + (NS + 2 * WG + t) * 8) : "memory");
  __syncwarp();
}
struct Slots { uint32_t w, x, o, po; };
template <int WG>
__device__ __forceinline__ void acc_fence(float (&a)[64]) {
#pragma unroll
  for (int i = 0; i < (WG ? 48 : 64); i++) asm volatile("" : "+f"(a[i])::"memory");
}
template <int WG>
__device__ __forceinline__ void begin_acquire(const Ctx& c, Ring& r, Slots& h, bool wait) {
  const uint32_t s0 = r.slot, p0 = r.phase, f = c.sb + BAR_FULL;
  r.next();
  const uint32_t p1 = r.phase;
  h.w = r.slot; r.next();
  h.x = WG ? r.slot : s0; h.o = WG ? s0 : r.slot; h.po = r.phase;
  if (wait) { if (WG) mbar_wait3_w(f + s0 * 8, p0, f + h.w * 8, p1, f + h.x * 8, r.phase); else mbar_wait2_w(f + s0 * 8, p0, f + h.w * 8, p1); }
  r.next();
}
template <int WG>
__device__ __forceinline__ void proj_begin(const Ctx& c, Ring& r, float (&a0)[64], Slots& h, bool wait, uint32_t sw) {
  begin_acquire<WG>(c, r, h, wait);
  proj_half<WG, true, 0>(c, a0, h.w, h.x, sw);
  if (WG) release(c, h.o);
}
template <int WG>
__device__ __forceinline__ void proj_main(Ctx& c, Ring& r, float (&a0)[64], float (&a1)[64], Slots& h, int n, uint32_t sw, int unit,
                                          uint32_t item, int nq, float (&o1)[64], const RowSum& inv) {
  constexpr bool DEEP = (PDEPTH >> WG) & 1;
  T2C(unit, 3);
  int ks = 1;
#pragma unroll 1
  do {
    const Slots p = h;
    const uint32_t b = borrow(ks, n), tile = NS + (WG ? 3 - b : b), f = c.sb + BAR_FULL;
    const uint32_t s0 = b != 2 ? tile : r.slot, p0 = b != 2 ? (r.xp >> b) & 1 : r.phase;
    r.next_if(b == 2);
    const uint32_t p1 = r.phase;
    h.w = r.slot; r.next();
    const uint32_t s2 = b != 2 ? tile : r.slot;
    h.po = b != 2 ? p0 : r.phase;
    r.next_if(b == 2);
    r.xp ^= 1 << b;
    h.x = WG ? s2 : s0; h.o = WG ? s0 : s2;
    mbar_wait3_w(f + s0 * 8, p0, f + h.w * 8, p1, f + (WG ? s2 : p.o) * 8, WG ? h.po : p.po);
    if (ks < 10) T2C(unit, ks * 4);
    if (DEEP) {
      proj_half<WG, false, 0>(c, a0, h.w, h.x, sw);
      release(c, WG ? h.o : p.o);
      if (ks < 10) T2C(unit, ks * 4 + 1);
      wg_wait<1>();
      if (ks < 10) T2C(unit, ks * 4 + 2);
      release(c, p.x); release(c, p.w);
    } else {
      release(c, WG ? h.o : p.o);
      wg_wait<0>();
      release(c, p.x); release(c, p.w);
      if (ks < 10) T2C(unit, ks * 4 + 1);
      proj_half<WG, false, 0>(c, a0, h.w, h.x, sw);
      if (ks < 10) T2C(unit, ks * 4 + 2);
    }
    proj_half<WG, false, 1>(c, a1, h.w, h.x, sw);
    if (ks < 10) T2C(unit, ks * 4 + 3);
    if (ks <= nq) o_second<WG>(c, item, ks, o1, inv);
  } while (++ks != n);
  {
    const uint32_t e0 = c.sb + BAR_EMPTY + (NS + 3 * WG) * 8, e1 = c.sb + BAR_EMPTY + (NS + 1 + WG) * 8;
    const uint32_t p0 = (r.xp ^ unit ^ 1) & 1, p1 = ((r.xp >> 1) ^ unit ^ 1) & 1;
    const uint32_t k0 = sw ? e0 : c.sb + BAR_FULL + r.slot * 8, pk = sw ? p0 : r.phase;
    uint32_t cnt = 0;
    while (!__all_sync(0xffffffffu, mbar_try(e0, p0) & mbar_try(e1, p1) & mbar_try(k0, pk) & (WG || mbar_try(c.sb + BAR_FULL + h.o * 8, h.po)))) {
      if (++cnt > (1u << 22)) __trap();
    }
  }
  c.lane = c.lane0 + (h.w >> 5);
  if (!WG) release(c, h.o);
  wg_wait<1>();
  acc_fence<WG>(a0);
}
template <int WG>
__device__ __forceinline__ void proj_end(const Ctx& c, float (&a1)[64], const Slots& h) {
  wg_wait<0>();
  acc_fence<WG>(a1);
  release(c, h.x); release(c, h.w);
}
__device__ __forceinline__ uint32_t get_desc(const Ctx& c, int i) {
  uint32_t d;
  mbar_wait_w(c.sb + BAR_DESC, (i - 1) & 1);
  asm volatile("ld.volatile.shared.u32 %0, [%1];" : "=r"(d) : "r"(c.sb + DESC_OFF + (i & 3) * 4) : "memory");
  return __shfl_sync(0xffffffffu, d, 0);
}

__device__ __forceinline__ float quad_max(float x) {
  x = fmaxf(x, __shfl_xor_sync(0xffffffffu, x, 1));
  return fmaxf(x, __shfl_xor_sync(0xffffffffu, x, 2));
}
__device__ __forceinline__ float quad_sum(float x) {
  x += __shfl_xor_sync(0xffffffffu, x, 1);
  return x + __shfl_xor_sync(0xffffffffu, x, 2);
}
template <bool SP, bool FIRST>
__device__ __forceinline__ void exps(const Ctx& c, const float (&s)[32], uint32_t (&p)[SP ? 8 : 16], RowSum& st) {
  if constexpr (SP) {
    uint32_t q[8];
    float t;
#pragma unroll
    for (int j = 0; j < 8; j++) {
      const float e0 = ex2(s[4 * j] + s[4 * j + 2]), e1 = ex2(s[4 * j + 1] + s[4 * j + 3]);
      if (j == 0) t = e0 + e1; else t += e0 + e1;
      q[j] = pack_bf16(e0, e1);
    }
    const bool odd = c.src & 2;
#pragma unroll
    for (int g = 0; g < 4; g++) {
      p[2 * g] = __shfl_sync(0xffffffffu, odd ? q[2 * g + 1] : q[2 * g], c.src);
      p[2 * g + 1] = __shfl_sync(0xffffffffu, odd ? q[2 * g] : q[2 * g + 1], c.src ^ 1);
    }
    st.l0 = FIRST ? t : st.l0 + t;
  } else {
    float t0, t1;
#pragma unroll
    for (int j = 0; j < 8; j++) {
      const float e0 = ex2(s[4 * j]), e1 = ex2(s[4 * j + 1]), e2 = ex2(s[4 * j + 2]), e3 = ex2(s[4 * j + 3]);
      if (j == 0) { t0 = e0 + e1; t1 = e2 + e3; } else { t0 += e0 + e1; t1 += e2 + e3; }
      p[2 * j] = pack_bf16(e0, e1);
      p[2 * j + 1] = pack_bf16(e2, e3);
    }
    st.l0 = FIRST ? t0 : st.l0 + t0;
    st.l1 = FIRST ? t1 : st.l1 + t1;
  }
}
template <bool SP>
__device__ __forceinline__ bool finish_sums(RowSum& st) {
  const float a = quad_sum(st.l0), b = SP ? a : quad_sum(st.l1);
  st.l0 = __fdividef(1.f, a); st.l1 = __fdividef(1.f, b);
  return !(a >= SUM_LO && a <= SUM_HI && b >= SUM_LO && b <= SUM_HI);
}
template <bool SP, bool INIT, int SITE, bool COMMIT = true>
__device__ __forceinline__ void issue_qk(const Ctx& c, float (&s)[32], const uint32_t (&qs)[16], uint32_t dq, uint32_t dk) {
  uint64_t a = desc64(dq, dhi<SITE & 1>(dk)), b = desc64(dk, dhi<1 - (SITE & 1)>(dk));
  if (SP) {
    if (INIT) wgmma_qk_sp_init(s, qs[0], qs[1], qs[2], qs[3], b, 0, c.mqk); else wgmma_qk_sp(s, qs[0], qs[1], qs[2], qs[3], b, 0, c.mqk);
#pragma unroll
    for (int k = 1; k < 4; k++) { dadd(b, k == 2 ? 508 : 4); wgmma_qk_sp(s, qs[4 * k], qs[4 * k + 1], qs[4 * k + 2], qs[4 * k + 3], b, 1, c.mqk); }
  } else {
    if (INIT) wgmma_qk_init(s, a, b, 0); else wgmma_qk(s, a, b, 0);
#pragma unroll
    for (int k = 1; k < 8; k++) { dadd(a, k == 4 ? 506 : 2); dadd(b, k == 4 ? 506 : 2); wgmma_qk(s, a, b, 1); }
  }
  if (COMMIT) wg_commit();
}
template <bool SP, bool ACC, int SITE, bool SPLIT = false>
__device__ __forceinline__ void issue_pv(const Ctx& c, float (&o)[64], const uint32_t (&p)[SP ? 8 : 16], uint32_t dv) {
  uint64_t b = desc64(dv, dhi<SITE & 1>(dv));
  if constexpr (SP) {
    if (ACC) wgmma_pv_sp(o, p[0], p[1], p[2], p[3], b, 1, c.mpv); else wgmma_pv_sp_init(o, p[0], p[1], p[2], p[3], b, 0, c.mpv);
    if (SPLIT) wg_commit();
    dadd(b, 256);
    wgmma_pv_sp(o, p[4], p[5], p[6], p[7], b, 1, c.mpv);
  } else {
    if (ACC) wgmma_pv(o, p[0], p[1], p[2], p[3], b, 1); else wgmma_pv_init(o, p[0], p[1], p[2], p[3], b, 0);
#pragma unroll
    for (int k = 1; k < 4; k++) { dadd(b, 128); wgmma_pv(o, p[4 * k], p[4 * k + 1], p[4 * k + 2], p[4 * k + 3], b, 1); }
  }
  wg_commit();
}
__device__ __forceinline__ void pack_rows(const float (&o)[64], float sc, uint32_t (&q)[32]) {
#pragma unroll
  for (int j = 0; j < 32; j++) q[j] = pack_bf16(o[2 * j] * sc, o[2 * j + 1] * sc);
}
__device__ __forceinline__ void stage_rows(const Ctx& c, uint32_t tile_addr, const uint32_t (&q)[32]) {
  const int lane = c.lane, mi = lane >> 3, r8 = lane & 7;
  const uint32_t row_addr = tile_addr + (16 * c.warp + (mi & 1) * 8 + r8) * 128;
#pragma unroll
  for (int jj = 0; jj < 8; jj++)
    stsm4(row_addr + (jj >> 2) * 8192 + (((((2 * jj) & 7) + (mi >> 1)) ^ r8) << 4), q[4 * jj], q[4 * jj + 1], q[4 * jj + 2], q[4 * jj + 3]);
}
__device__ __forceinline__ void stage_rows(const Ctx& c, uint32_t tile_addr, const float (&o)[64], float sc) {
  uint32_t q[32];
  pack_rows(o, sc, q);
  stage_rows(c, tile_addr, q);
}
template <int SITE>
__device__ __forceinline__ void issue_qk_rs(float (&s)[32], uint32_t (&q)[32], uint32_t dk) {
  uint64_t b = desc64(dk, dhi<SITE>(dk));
  reg_fence(q);
  wg_fence();
  wgmma_qk_rs_init(s, q[0], q[1], q[2], q[3], b, 0);
#pragma unroll
  for (int k = 1; k < 8; k++) { dadd(b, k == 4 ? 506 : 2); wgmma_qk_rs(s, q[4 * k], q[4 * k + 1], q[4 * k + 2], q[4 * k + 3], b, 1); }
  wg_commit();
}

__device__ __forceinline__ void redo_tile(const Ctx& c, uint32_t q_addr, uint32_t half, const __nv_bfloat16* kp, const __nv_bfloat16* vp,
                                          uint32_t item, int row) {
  float o[64];
  const int lane = lane_now(), g = lane >> 2, cc = lane & 3, mi = lane >> 3, r8 = lane & 7;
  const uint32_t qa = q_addr + (half == 4096 ? 8 * c.warp + r8 : 16 * c.warp + (mi & 1) * 8 + r8) * 128, swz = half == 4096 ? q3_swz(r8) : r8;
  const uint32_t* kq = reinterpret_cast<const uint32_t*>(kp + g * DH) + cc;
  const unsigned short* vq = reinterpret_cast<const unsigned short*>(vp + 2 * cc * DH) + g;
  float m0 = -INFINITY, m1 = -INFINITY, l0 = 0.f, l1 = 0.f;
#pragma unroll
  for (int i = 0; i < 64; i++) o[i] = 0.f;
#pragma unroll 1
  for (int kb = 0; kb < SK / 16; kb++) {
    float z[8] = {0.f, 0.f, 0.f, 0.f, 0.f, 0.f, 0.f, 0.f};
#pragma unroll 2
    for (int kk = 0; kk < 8; kk++) {
      uint32_t a0, a1, a2, a3;
      ldsm4(qa + (kk >> 2) * half + ((((kk & 3) * 2 + (mi >> 1)) ^ swz) << 4), a0, a1, a2, a3);
      const uint32_t* kr = kq + kb * (16 * DH / 2) + kk * 8;
      mma16816(z[0], z[1], z[2], z[3], a0, a1, a2, a3, __ldg(kr), __ldg(kr + 4));
      mma16816(z[4], z[5], z[6], z[7], a0, a1, a2, a3, __ldg(kr + 8 * DH / 2), __ldg(kr + 8 * DH / 2 + 4));
    }
    const float n0 = fmaxf(m0, quad_max(fmaxf(fmaxf(z[0], z[1]), fmaxf(z[4], z[5]))));
    const float n1 = fmaxf(m1, quad_max(fmaxf(fmaxf(z[2], z[3]), fmaxf(z[6], z[7]))));
    const float al0 = ex2(m0 - n0), al1 = ex2(m1 - n1);
    m0 = n0; m1 = n1;
#pragma unroll
    for (int i = 0; i < 8; i++) z[i] = ex2(z[i] - ((i & 2) ? n1 : n0));
    l0 = l0 * al0 + (z[0] + z[1]) + (z[4] + z[5]);
    l1 = l1 * al1 + (z[2] + z[3]) + (z[6] + z[7]);
    const uint32_t a0 = pack_bf16(z[0], z[1]), a1 = pack_bf16(z[2], z[3]), a2 = pack_bf16(z[4], z[5]), a3 = pack_bf16(z[6], z[7]);
    const unsigned short* vr = vq + kb * (16 * DH);
#pragma unroll
    for (int nb = 0; nb < 16; nb++) {
      o[4 * nb] *= al0; o[4 * nb + 1] *= al0; o[4 * nb + 2] *= al1; o[4 * nb + 3] *= al1;
      const uint32_t b0 = __ldg(vr + nb * 8) | ((uint32_t)__ldg(vr + nb * 8 + DH) << 16);
      const uint32_t b1 = __ldg(vr + nb * 8 + 8 * DH) | ((uint32_t)__ldg(vr + nb * 8 + 9 * DH) << 16);
      mma16816(o[4 * nb], o[4 * nb + 1], o[4 * nb + 2], o[4 * nb + 3], a0, a1, a2, a3, b0, b1);
    }
  }
  const char* p = o_addr(item, row, lane);
  o_emit<0>(p, o, __fdividef(1.f, quad_sum(l0)));
  o_emit<1>(half == 4096 ? p : p + 1024, o, __fdividef(1.f, quad_sum(l1)));
}

template <bool SPA, bool SPB, int SITE, int ID>
__device__ __forceinline__ void batch(const Ctx& c, float (&s)[32], const uint32_t (&qs)[16], uint32_t dq, uint32_t dk, float (&ob)[64],
                                      uint32_t (&pb)[SPB ? 8 : 16], uint32_t dv) {
  if constexpr (SPA) {
    reg_fence(pb);
    wg_fence();
    issue_pv<SPB, true, ID>(c, ob, pb, dv);
    issue_qk<SPA, false, ID>(c, s, qs, dq, dk);
  } else {
    constexpr bool EARLY = ((QK_EARLY_MASK >> (SITE + (SPB ? 2 : 0))) & 1) != 0;
    if (!EARLY) reg_fence(pb);
    wg_fence();
    issue_qk<SPA, false, ID, !SPB>(c, s, qs, dq, dk);
    if (EARLY) { reg_fence(pb); wg_fence(); }
    issue_pv<SPB, true, ID, SPB>(c, ob, pb, dv);
  }
}

template <bool SP0>
__device__ __forceinline__ bool attention(Ctx& c, Ring& r, int unit, uint32_t& d, const float (&a0)[64], float (&o0)[64], float (&o1)[64],
                                          RowSum& st0, RowSum& st1, const Slots& h) {
  constexpr bool SP1 = false;
  if (SP0) { c.mqk = META_QK + (d >> 28); c.mpv = META_PV + (d >> 28); asm volatile("" : "+r"(c.mqk), "+r"(c.mpv)); }
  if (SP0) c.src = (c.lane & 28) | ((c.lane & 1) << 1) | ((c.lane >> 1) & 1);
  float s[32];
  uint32_t p0[SP0 ? 8 : 16], p1[16];
  const uint32_t q0a = c.sb + QBUF_OFF + (SP0 ? 3 : 0) * 16384, q1a = c.sb + QBUF_OFF + (SP0 ? 2 : 1) * 16384;
  const uint32_t dq0 = sdesc(q0a, 0), dq1 = sdesc(q1a, 0);
  uint32_t sk = acquire(c, r, true), sv, sn;
  uint32_t qs[16];
  float s1[32];
  if (SP0) {
    stage_t3<0, true>(c, a0, SM_C);
    stage_t2<0>(c, a0, SM_C);
    proj_end<1>(c, o0, h);
    stage_t3<1, true>(c, o0, SM_C);
    stage_t2<1>(c, o0, SM_C);
    fence_async_smem();
    bar_sync(1, LAG_BAR & 30 ? 256 : 128);
    const int g = c.lane >> 2, cc = c.lane & 3;
    const uint32_t qa = q0a + (8 * c.warp + g) * 128 + (cc & 1) * 8;
#pragma unroll
    for (int k = 0; k < 8; k++)
      asm volatile("ld.shared.v2.u32 {%0, %1}, [%2];" : "=r"(qs[2 * k]), "=r"(qs[2 * k + 1])
                   : "r"(qa + (k >> 2) * 4096 + ((((k & 3) * 2 + (cc >> 1)) ^ q3_swz(g)) << 4)) : "memory");
    TRACE(unit, 2);
    wg_fence();
    issue_qk<SP1, true, 1>(c, s1, qs, dq1, sdesc(c.sb + sk * SLOT, 0));
    reg_fence(qs);
    wg_fence();
    issue_qk<SP0, true, 0>(c, s, qs, dq0, sdesc(c.sb + sk * SLOT, 0));
    const bool have = peek<2>(c, r);
    wg_wait<1>();
    reg_fence(s1);
    exps<SP1, true>(c, s1, p1, st1);
    sched_fence<11>(sk, p1);
    acquire2(c, r, sv, sn, __all_sync(0xffffffffu, have));
    wg_wait<0>();
    wg_fence();
    issue_pv<SP1, false, 1>(c, o1, p1, sdesc(c.sb + sv * SLOT, 8192));
    if (LAG_BAR & 1) asm volatile("bar.arrive 4, 256;" ::: "memory");
    sched_fence<12>(sk, s);
    release(c, sk);
    sk = sn;
    exps<SP0, true>(c, s, p0, st0);
    reg_fence(p0);
    wg_fence();
    issue_pv<SP0, false, 0>(c, o0, p0, sdesc(c.sb + sv * SLOT, 8192));
    issue_qk<SP0, true, 2>(c, s, qs, dq0, sdesc(c.sb + sk * SLOT, 0));
    sn = acquire(c, r);
    wg_wait<0>();
    reg_fence(s);
  } else {
    uint32_t q0[32], q1[32];
    pack_rows(a0, SM_C, q0);
    stage_rows(c, q0a, q0);
    proj_end<0>(c, o1, h);
    TRACE(unit, 2);
    float sc = SM_C;
    issue_qk_rs<0>(s, q0, sdesc(c.sb + sk * SLOT, 0));
    sched_fence<0>(sk, sc);
    if (LAG_BAR & 8) asm volatile("bar.arrive 1, 256;" ::: "memory");
    pack_rows(o1, sc, q1);
    stage_rows(c, q1a, q1);
    if (LAG_BAR & 4) asm volatile("bar.arrive 1, 256;" ::: "memory");
    issue_qk_rs<1>(s1, q1, sdesc(c.sb + sk * SLOT, 0));
    if (LAG_BAR & 2) asm volatile("bar.arrive 1, 256;" ::: "memory");
    bool have = peek<2>(c, r);
    wg_wait<1>();
    reg_fence(s);
    exps<SP0, true>(c, s, p0, st0);
    sched_fence<1>(sk, p0);
    if (LAG_BAR & 16) asm volatile("bar.arrive 1, 256;" ::: "memory");
    acquire2(c, r, sv, sn, __all_sync(0xffffffffu, have));
    wg_wait<0>();
    reg_fence(s1);
    fence_async_smem();
    __syncwarp();
    wg_fence();
    issue_qk<SP0, false, 2>(c, s, qs, dq0, sdesc(c.sb + sn * SLOT, 0));
    issue_pv<SP0, false, 0>(c, o0, p0, sdesc(c.sb + sv * SLOT, 8192));
    sched_fence<2>(sk, s1);
    release(c, sk);
    have = peek<1>(c, r);
    sk = sn;
    exps<SP1, true>(c, s1, p1, st1);
    reg_fence(p1);
    wg_fence();
    issue_pv<SP1, false, 1>(c, o1, p1, sdesc(c.sb + sv * SLOT, 8192));
    sn = acquire(c, r, __all_sync(0xffffffffu, have));
    if (LAG_BAR & 1) bar_sync(4, 256);
    wg_wait<1>();
    reg_fence(s);
  }
  TRACE_IN(unit, 4);
  T2C(unit, 51);
#pragma unroll 1
  for (int j = 1; j < 15; j++) {
    const uint32_t sv_prev = sv, sk_prev = sk;
    sv = sn;
    const uint32_t dv = sdesc(c.sb + sv * SLOT, 8192);
    reg_fence(p0);
    exps<SP0, false>(c, s, p0, st0);
    batch<SP1, SP0, 0, 3>(c, s, qs, dq1, sdesc(c.sb + sk * SLOT, 0), o0, p0, dv);
    sk = acquire(c, r);
    wg_wait<1>();
    reg_fence(s); reg_fence(p1);
    release(c, sv_prev); release(c, sk_prev);
    exps<SP1, false>(c, s, p1, st1);
    batch<SP0, SP1, 1, 4>(c, s, qs, dq0, sdesc(c.sb + sk * SLOT, 0), o1, p1, dv);
    sn = acquire(c, r);
    if (SP0) wg_wait<0>(); else wg_wait<1>();
    reg_fence(s);
  }
  TRACE_IN(unit, 5);
  T2C(unit + 1, 52);
  const uint32_t sv_prev = sv;
  sv = sn;
  const uint32_t dv = sdesc(c.sb + sv * SLOT, 8192);
  reg_fence(p0);
  exps<SP0, false>(c, s, p0, st0);
  batch<SP1, SP0, 0, 5>(c, s, qs, dq1, sdesc(c.sb + sk * SLOT, 0), o0, p0, dv);
  asm volatile("ld.volatile.shared.u32 %0, [%1];" : "=r"(d) : "r"(c.sb + DESC_OFF + ((unit + 1) & 3) * 4) : "memory");
  const bool have = peek<2 + SP0>(c, r);
  wg_wait<1>();
  reg_fence(s); reg_fence(p1);
  release(c, sv_prev); release(c, sk);
  exps<SP1, false>(c, s, p1, st1);
  reg_fence(p1);
  wg_fence();
  issue_pv<SP1, true, 2>(c, o1, p1, dv);
  if (SP0) sched_fence<6>(sk, st0.l0, st1.l0, st1.l1); else sched_fence<5>(sk, st0.l0, st0.l1, st1.l0, st1.l1);
  c.lane = c.lane0 + (sk >> 5);
  const bool bad = finish_sums<SP0>(st0) | finish_sums<SP1>(st1);
  uint32_t any;
  asm volatile("{\n.reg .pred p, q;\nsetp.ne.u32 p, %1, 0;\nbar.red.or.pred q, %2, 128, p;\nselp.u32 %0, 1, 0, q;\n}"
               : "=r"(any) : "r"((uint32_t)bad), "n"(2 + SP0) : "memory");
  any = __any_sync(0xffffffffu, any);
  d = __shfl_sync(0xffffffffu, d, 0);
  if (d < (2u << 30) && !__all_sync(0xffffffffu, have)) { Ring t = r; Slots u; begin_acquire<SP0>(c, t, u, true); }
  wg_wait<0>();
  reg_fence(o0); reg_fence(o1);
  release(c, sv);
  return any;
}

template <int WG>
__device__ __forceinline__ void consumer(Ctx c, const __nv_bfloat16* const* kv) {
  asm volatile("setmaxnreg.inc.sync.aligned.u32 %0;" ::"n"(WG ? REG_C : 504 - REG_C - REG_P));
  c.wg = WG;
  Ring r{0, 0, 0};
  float a0[64], a1[64], o1[64];
  Slots h;
  RowSum inv0, inv1;
  uint32_t d = blockIdx.x, dc = 0, sw;
  int i = 0, nq;
begin:
  sw = d & (1u << 30);
  proj_begin<WG>(c, r, a0, h, true, sw);
  proj_half<WG, true, 1>(c, a1, h.w, h.x, sw);
  nq = 0;
#pragma unroll
  for (int k = 0; k < 64; k++) asm volatile("" : "=f"(o1[k]));
  asm volatile("" : "=f"(inv1.l0), "=f"(inv1.l1));
  while (true) {
    TRACE(i, 0); TRACE(i, 6);
    proj_main<WG>(c, r, a0, a1, h, d >> 30 ? ((d >> 16) & 63) + 1 : DM / 64, sw, i, dc, nq, o1, inv1);
    dc = d;
    TRACE(i, 1);
    if (d >> 30) goto out_tile;
    if (WG ? attention<WG>(c, r, i, d, a0, a1, o1, inv0, inv1, h) : attention<WG>(c, r, i, d, a0, o1, a1, inv1, inv0, h)) goto redo;
    if (d >= (2u << 30)) break;
    sw = d & (1u << 30);
    proj_begin<WG>(c, r, a0, h, false, sw);
    release_q<WG>(c);
    if (WG) sched_fence<8>(h.w, inv0.l0); else sched_fence<7>(h.w, inv0.l0, inv0.l1);
    o_first<WG>(c, dc, a1, inv0);
    sched_fence<9>(h.w, inv1.l0);
    proj_half<WG, true, 1>(c, a1, h.w, h.x, sw);
    nq = O_STEPS;
    TRACE(i, 3); TRACE(i, 7);
    i++;
  }
  release_q<WG>(c);
  o_first<WG>(c, dc, a1, inv0);
#pragma unroll
  for (int k = 1; k <= O_STEPS; k++) o_second<WG>(c, dc, k, o1, inv1);
next:
  TRACE(i, 3); TRACE(i, 7);
  if ((d >> 30) != 2) {
    i++;
    r.uniform();
    goto begin;
  }
  trace_dump(c);
  return;
out_tile:
  proj_end<WG>(c, a1, h);
  if (((d >> 28) & 3) == 2) {
    const int lane = c.lane, mi = lane >> 3, r8 = lane & 7;
    const uint32_t off = c.sb + (WG ? stage_off(c) : (16 * c.warp + (mi & 1) * 8 + r8) * 128);
#pragma unroll 1
    for (int k = (d >> 5) & 3; k > 0; k--) {
      uint32_t s0, s1;
      if (WG) { acquire2(c, r, s0, s1); release(c, s0); release(c, s1); }
#pragma unroll
      for (int t = 0; t < 2; t++) {
        const uint32_t sp = acquire(c, r), base = off + sp * SLOT;
        if (WG) {
#pragma unroll
          for (int jj = 0; jj < (t ? 2 : 4); jj++) {
            add16<true>(base + jj * 2048, &a0[(t * 4 + jj) * 8]);
            add16<true>(base + jj * 2048 + (t ? 4096 : 8192), &a1[(t * 4 + jj) * 8]);
          }
        } else {
#pragma unroll
          for (int jj = 0; jj < 8; jj++) add16<false>(base + (jj >> 2) * 8192 + (((((2 * jj) & 7) + (mi >> 1)) ^ r8) << 4), t ? &a1[jj * 8] : &a0[jj * 8]);
        }
        release(c, sp);
      }
      if (!WG) { acquire2(c, r, s0, s1); release(c, s0); release(c, s1); }
    }
  }
  if (WG) { stage_t3<0, false>(c, a0, 1.f); stage_t3<1, false>(c, a1, 1.f); }
  else stage_rows(c, c.sb + QBUF_OFF, a0, 1.f);
  staged(c, 0);
  if (WG) { stage_t2<0>(c, a0, 1.f); stage_t2<1>(c, a1, 1.f); }
  else stage_rows(c, c.sb + QBUF_OFF + 16384, a1, 1.f);
  staged(c, 1);
  d = get_desc(c, i + 1);
  TRACE(i, 2);
  goto next;
redo:
  {
    const size_t hoff = (size_t)(dc & 511) * (SK * DH);
    const int br = (dc >> 9) & 1;
#pragma unroll 1
    for (int part = 0; part < 2; part++) {
      const int t = WG ? 3 - part : part;
      redo_tile(c, c.sb + QBUF_OFF + t * 16384, t == 3 ? 4096 : 8192, kv[br] + hoff, kv[2 + br] + hoff, dc,
                t * 64 + (t == 3 ? 8 : 16) * c.warp);
    }
    o_done(c);
    release_q<WG>(c);
  }
  goto next;
}

template <bool SIMPLE>
__global__ void __launch_bounds__(384, 1) mha_fused_kernel(const __grid_constant__ Params P) {
  extern __shared__ __align__(1024) uint8_t smem_raw[];
  const uint32_t sbase = smem_u32(smem_raw);
  const int tid = threadIdx.x;
  const int wg = __shfl_sync(0xffffffffu, tid >> 7, 0);
  const int warp = __shfl_sync(0xffffffffu, (tid >> 5) & 3, 0);
  const int lane = tid & 31;
  const int cta = blockIdx.x;

  if (tid == 0) T3(15, 0);
  if ((sbase & 1023) || sbase + SMEM_BYTES > 0x40000) __trap();
  {
    const int wi = wg * 4 + warp;
    asm volatile(ELECT "prefetch.tensormap [%0];\n}" ::"l"(&P.x[0][0] + wi) : "memory");
#pragma unroll
    for (int k = 0; k < 3; k++) {
      const int b = min(BAR_OFF + (wi * 3 + k) * 8, BAR_GO);
      asm volatile(ELECT "mbarrier.init.shared::cta.b64 [%0], %1;\n}"
                   ::"r"(sbase + b), "r"(b < BAR_EMPTY || b >= BAR_DESC ? 1 : b >= BAR_STG && b < BAR_OUT ? 4 : 8) : "memory");
    }
    asm volatile("fence.mbarrier_init.release.cluster;" ::: "memory");
    if (wi < 6) asm volatile(ELECT "prefetch.tensormap [%0];\n}" ::"l"(&P.x[0][0] + 12 + wi) : "memory");
  }
  __syncthreads();

  if (wg == 2) {
    asm volatile("setmaxnreg.dec.sync.aligned.u32 %0;" ::"n"(REG_P));
    if (warp == 1) {
      const uint32_t qb = sbase + QBUF_OFF;
      const uint32_t ep = __shfl_sync(0xffffffffu, *(volatile unsigned*)&g_epoch + 1, 0);
      asm volatile("st.volatile.shared.u32 [%0], %1;" ::"r"(sbase + EPOCH_OFF), "r"(ep) : "memory");
      uint32_t dc = cta, qi = 0, piece = 0, na = 0;
      TTAIL(0);
      for (int i = 0; (dc >> 30) != 2; i++) {
        mbar_wait_w(sbase + BAR_GO, i & 1);
        if (piece == 0) {
          if (lane == 0) {
            qi = atomicAdd(&g_next, 1);
            if (qi == (SIMPLE ? Q_ALL : Q_RANGES) - 1) { g_next = 0; g_epoch = ep; }
          }
          qi = __shfl_sync(0xffffffffu, qi, 0) + (SIMPLE ? gridDim.x : NCTA);
        }
        uint32_t d;
        if (qi < (SIMPLE ? Q_ALL : Q_RANGES)) { d = c_sched.queue[qi]; if (d & 0x8000) d ^= (1u << 30) | (63u << 16) | 0x8000; }
        else if (SIMPLE) d = 2u << 30;
        else { const uint32_t e = qi - Q_RANGES, g = e / 5; d = c_sched.piece[g][piece++] | (e - g * 5) << 8; }
        if ((d >> 30) == 1) {
          const uint32_t ok = __ballot_sync(0xffffffffu, reached(&g_cnt[lane & 1][d & 31], ep * (lane & 1 ? NH - H_LATE : H_LATE)));
          if (!(ok & 2)) d |= ((d >> 22) & 63) >= 2 * H_LATE - O_STEPS ? (2u << 30) | 128 : 128;
          if (!(ok & 1) || (O_STEPS > 4 && ((d >> 16) & 63) < O_STEPS)) d |= 2u << 30;
        }
        asm volatile("st.volatile.shared.u32 [%0], %1;" ::"r"(sbase + DESC_OFF + ((i + 1) & 3) * 4), "r"(d) : "memory");
        __syncwarp();
        mbar_arrive_warp(sbase + BAR_DESC);
        const Work w = decode(dc);
        dc = d;
        if (w.kind == 0) {
          mbar_wait_w(sbase + BAR_OUT, na++ & 1);
          TTAIL(1);
          T3(i, 0); T3(i, 1);
          asm volatile(ELECT "red.release.gpu.global.add.u32 [%0], 1;\n}" ::"l"(&g_cnt[w.sub >= H_LATE][w.beta]) : "memory");
          T3(i, 2);
          TTAIL(2);
          continue;
        }
        const bool fin = w.mode != 1;
        uint64_t pol, pol2;
        asm volatile("createpolicy.fractional.L2::evict_first.b64 %0, 1.0;" : "=l"(pol));
        asm volatile("createpolicy.fractional.L2::evict_normal.b64 %0, 1.0;" : "=l"(pol2));
        if (!fin) pol = pol2;
        const CUtensorMap* m = fin ? P.out_st : P.o_st;
        const int c1 = fin ? (w.beta & 15) * SQ : 0;
        const int c2 = fin ? (w.beta >> 4) * (DM / 64) + w.sub * 2 : NBETA * 64 + w.range * 2;
        uint32_t pend = 0;
#pragma unroll 1
        for (int e = 0; e < 4; e++) {
          const int t = (ST_ORDER >> (4 * e)) & 3;
          mbar_wait_w(sbase + BAR_STG + (t ^ (t >> 1)) * 8, (i - na) & 1);
          tma_st3_hint_w(m + (t == 3), qb + t * 16384, 0, c1 + t * 64, c2, pol);
          bulk_commit();
          T2P(i + 1, 5, 2 * e);
          if (pend) {
            bulk_wait_read<1>();
            mbar_arrive8_w(pend);
            T2P(i + 1, 5, 2 * e - 1);
          }
          pend = sbase + BAR_EMPTY + (NS + t) * 8;
          if ((ST_NOW >> e) & 1) {
            bulk_wait_read<0>();
            mbar_arrive8_w(pend);
            pend = 0;
            T2P(i + 1, 5, 2 * e + 1);
          }
        }
        T3(i, 0);
        if (piece >= 2) TTAIL(piece * 2 - 1);
        asm volatile("cp.async.bulk.wait_group 0;" ::: "memory");
        T3(i, 1);
        if (w.mode == 1) asm volatile(ELECT "st.release.gpu.global.u32 [%0], %1;\n}" ::"l"(&g_flag[w.range]), "r"(ep) : "memory");
        T3(i, 2);
        if (piece >= 2) TTAIL(piece * 2);
      }
      T3(15, 1);
    } else
    if (warp == 0) {
      Ring r{0, 1, 3};
      uint32_t d = cta;
      for (int i = 0;; i++) {
        const Work w = decode(d);
        if (w.kind == 2) break;
        const CUtensorMap* m = w.kind == 0 ? &P.wq[w.beta >> 4] : &P.wo[w.beta >> 4];
        for (int ks = 0; ks < w.nsteps; ks++) {
          const uint32_t b = borrow(ks, w.nsteps);
          r.next_if(b == 2);
          const uint32_t bar = sbase + BAR_FULL + r.slot * 8;
          mbar_wait_w(bar + (BAR_EMPTY - BAR_FULL), r.phase);
          if (w.kind == 0) tma_ld3_w(sbase + r.slot * SLOT, m, 0, ks * 64, w.sub * 2, bar, 16384);
          else tma_ld_wo_w(sbase + r.slot * SLOT, m, w.sub * 128, (w.k0 + ks) * 2, bar);
          if (ks < 10) T2P(i, 2, ks);
          if (w.kind != 0 && ks == max(w.nsteps - GO_P, 4)) mbar_arrive_warp(sbase + BAR_GO);
          r.next(); r.next_if(b == 2);
        }
        if (w.kind == 0) {
          r.phase ^= 1; r.next(); r.next();
        } else if (w.mode == 2) {
          for (int k = 1; k <= ((d >> 5) & 3); k++) {
            if (k == 1) TTAIL(9);
            wait_count(&g_flag[w.range + 5 * k], lds(sbase + EPOCH_OFF));
            TTAIL(10);
            asm volatile("fence.proxy.async.global;" ::: "memory");
#pragma unroll 1
            for (int t = 0; t < 4; t++) {
              mbar_wait_w(sbase + BAR_EMPTY + r.slot * 8, r.phase);
              tma_ld3_w(sbase + r.slot * SLOT, &P.o_st[t == 3], 0, t * 64, NBETA * 64 + (w.range + 5 * k) * 2, sbase + BAR_FULL + r.slot * 8,
                        t == 3 ? 8192 : 16384);
              r.next();
            }
          }
        }
        mbar_wait_w(sbase + BAR_DESC, i & 1);
        d = __shfl_sync(0xffffffffu, lds(sbase + DESC_OFF + ((i + 1) & 3) * 4), 0);
      }
    } else {
      const int hi = warp - 2;
      uint64_t pol_stream;
      asm volatile("createpolicy.fractional.L2::evict_first.b64 %0, 1.0;" : "=l"(pol_stream));
      Ring r{0, 1, 3};
      uint32_t d = cta;
      for (int i = 0;; i++) {
        const Work w = decode(d);
        if (w.kind == 2) break;
        const CUtensorMap* m = w.kind == 0 ? &P.x[hi][w.beta >> 4] : &P.o_ld[hi];
        int c1 = (w.kind == 0 ? (w.beta & 15) : w.beta * 64 + w.k0) * SQ + hi * 128;
        int k_late = -1;
        if (w.kind != 0) {
          if (!hi) T3(i, 3);
          if (d >= (3u << 30)) wait_count(&g_cnt[0][w.beta], lds(sbase + EPOCH_OFF) * H_LATE);
          if (d & 128) k_late = max(2 * H_LATE - w.k0, 0);
          if (!hi) T3(i, 4);
          asm volatile("fence.proxy.async.global;" ::: "memory");
          if (!hi) T3(i, 5);
        }
        for (int ks = 0; ks < w.nsteps; ks++) {
          if (ks == k_late) {
            if (!hi) T3(i, 6);
            wait_count(&g_cnt[1][d & 31], lds(sbase + EPOCH_OFF) * (NH - H_LATE));
            asm volatile("fence.proxy.async.global;" ::: "memory");
            if (!hi) T3(i, 7);
          }
          const uint32_t b = borrow(ks, w.nsteps);
          const bool bo = b != 2;
          r.next_if(hi && !bo); r.next_if(hi && !bo);
          const uint32_t sl = bo ? NS + (b ^ (3 * hi)) : r.slot, bar = sbase + BAR_FULL + sl * 8;
          mbar_wait_w(bar + (BAR_EMPTY - BAR_FULL), bo ? (r.xp >> b) & 1 : r.phase);
          if (w.kind == 0) tma_ld2_w(sbase + sl * SLOT, m, ks * 64, c1, bar, (hi ? 96 * 128 : 128 * 128));
          else { tma_ld2_hint_w(sbase + sl * SLOT, m, 0, c1, bar, hi ? 96 * 128 : 128 * 128, pol_stream); c1 += SQ; }
          if (i == 0 && ks == PF_STEP)
            asm volatile(ELECT "cp.async.bulk.prefetch.tensor.3d.L2.global.L2::cache_hint [%0, {0, %1, 0}], %2;\n}"
                         ::"l"(&P.kv[hi][0]), "r"(d * SK), "l"(pol_stream) : "memory");
          if (ks < 10) T2P(i, 3 + hi, ks);
          if (!hi && w.kind != 0 && !(ks & 3)) TCLK(i * 16 + (ks >> 2));
          r.next(); r.next_if(!hi && !bo); r.next_if(!hi && !bo);
          r.xp ^= 1 << b;
        }
        r.xp ^= 3;
        if (w.kind == 0) {
          m = &P.kv[hi][w.beta >> 4];
          c1 = (d & 511) * SK;
          for (int j = 0; j < 16; j++) {
            if (hi) r.next();
            const uint32_t bar = sbase + BAR_FULL + r.slot * 8;
            const bool tight = i < KV_WIN_UNITS && j < KV_WIN_TILES + ((KV_WIN_RAMP * ((int)d - NCTA * i)) >> 5);
            {
              const int s2 = (int)r.slot - (tight ? 2 : KV_WIN_D);
              mbar_wait_w(sbase + BAR_FULL + (s2 < 0 ? s2 + NS : s2) * 8, s2 < 0 ? r.phase : r.phase ^ 1);
            }
            if (j == 15 && hi) mbar_wait_w(sbase + BAR_DESC, i & 1);
            mbar_wait_w(sbase + BAR_EMPTY + r.slot * 8, r.phase);
            tma_ld3_hint_w(sbase + r.slot * SLOT, m, 0, c1, 0, bar, pol_stream);
            T2P(i, 3 + hi, 16 + j);
            if (!hi) TCLK(i * 16 + j);
            if (j == 14 && !hi) mbar_arrive_warp(sbase + BAR_GO);
            c1 += 64;
            r.next();
            if (!hi) r.next();
          }
        }
        mbar_wait_w(sbase + BAR_DESC, i & 1);
        d = __shfl_sync(0xffffffffu, lds(sbase + DESC_OFF + ((i + 1) & 3) * 4), 0);
      }
    }
  } else {
    Ctx c;
    c.sb = sbase; c.wg = wg; c.warp = warp; c.src = 0; c.mqk = 0; c.mpv = 0; c.lead = lane == 0; c.lane0 = c.lane = lane;
    if (wg == 0) consumer<0>(c, P.kp); else consumer<1>(c, P.kp);
  }
}

typedef CUresult (*EncodeFn)(CUtensorMap*, CUtensorMapDataType, cuuint32_t, void*, const cuuint64_t*, const cuuint64_t*,
                             const cuuint32_t*, const cuuint32_t*, CUtensorMapInterleave, CUtensorMapSwizzle,
                             CUtensorMapL2promotion, CUtensorMapFloatOOBfill);

void make_map(EncodeFn enc, CUtensorMap* m, const void* ptr, int rank, const cuuint64_t* dims, const cuuint64_t* strides,
              const cuuint32_t* box, int promo = 2, CUtensorMapSwizzle swz = CU_TENSOR_MAP_SWIZZLE_128B) {
  cuuint32_t es[5] = {1, 1, 1, 1, 1};
  enc(m, CU_TENSOR_MAP_DATA_TYPE_BFLOAT16, rank, const_cast<void*>(ptr), dims, strides, box, es,
      CU_TENSOR_MAP_INTERLEAVE_NONE, swz, promo == 2 ? CU_TENSOR_MAP_L2_PROMOTION_L2_256B : promo == 1 ? CU_TENSOR_MAP_L2_PROMOTION_L2_128B : CU_TENSOR_MAP_L2_PROMOTION_NONE,
      CU_TENSOR_MAP_FLOAT_OOB_FILL_NONE);
}

}

extern "C" void kernel_launch(void* const* d_in, const int* in_sizes, int n_in, void* d_out, int out_size) {
  (void)in_sizes; (void)n_in; (void)out_size;
  static EncodeFn enc = nullptr;
  static void* o_ptr = nullptr;
  static int n_sm = 0;
  if (!enc) {
    void* fn = nullptr;
    cudaDriverEntryPointQueryResult qr;
    cudaGetDriverEntryPoint("cuTensorMapEncodeTiled", &fn, cudaEnableDefault, &qr);
    enc = (EncodeFn)fn;
    cudaGetSymbolAddress(&o_ptr, g_o);
    cudaFuncSetAttribute(mha_fused_kernel<false>, cudaFuncAttributeMaxDynamicSharedMemorySize, SMEM_BYTES);
    cudaFuncSetAttribute(mha_fused_kernel<true>, cudaFuncAttributeMaxDynamicSharedMemorySize, SMEM_BYTES);
    int dev = 0;
    cudaGetDevice(&dev);
    cudaDeviceGetAttribute(&n_sm, cudaDevAttrMultiProcessorCount, dev);
  }
  Params P;
  for (int br = 0; br < 2; br++) {
    const void* x = d_in[br * 5 + 0]; const void* kc = d_in[br * 5 + 1]; const void* vc = d_in[br * 5 + 2];
    const void* wq = d_in[br * 5 + 3]; const void* wo = d_in[br * 5 + 4];
    { cuuint64_t d[2] = {DM, (cuuint64_t)NB * SQ}, s[1] = {DM * 2}; cuuint32_t b[2] = {64, 128}, b2[2] = {64, 96};
      make_map(enc, &P.x[0][br], x, 2, d, s, b, PR_X); make_map(enc, &P.x[1][br], x, 2, d, s, b2, PR_X); }
    { cuuint64_t d[3] = {64, DM, HD / 64}, s[2] = {HD * 2, 128}; cuuint32_t b[3] = {64, 64, 2}; make_map(enc, &P.wq[br], wq, 3, d, s, b, PR_W); }
    { cuuint64_t d[5] = {DM, 2, 4, 4, HD / 32}, s[4] = {DM * 2, 8 * DM * 2, 2 * DM * 2, 32 * DM * 2}; cuuint32_t b[5] = {64, 2, 4, 4, 2};
      make_map(enc, &P.wo[br], wo, 5, d, s, b, PR_W); }
    { cuuint64_t d[3] = {64, (cuuint64_t)NB * NH * SK, 2}, s[2] = {DH * 2, 128}; cuuint32_t b[3] = {64, 64, 2};
      make_map(enc, &P.kv[0][br], kc, 3, d, s, b, PR_KV); make_map(enc, &P.kv[1][br], vc, 3, d, s, b, PR_KV); }
    P.kp[br] = (const __nv_bfloat16*)kc; P.vp[br] = (const __nv_bfloat16*)vc;

  }
  { cuuint64_t d[2] = {64, (cuuint64_t)NBETA * 64 * SQ}, s[1] = {128}; cuuint32_t b[2] = {64, 128}, b2[2] = {64, 96};
    make_map(enc, &P.o_ld[0], o_ptr, 2, d, s, b, 2, CU_TENSOR_MAP_SWIZZLE_NONE); make_map(enc, &P.o_ld[1], o_ptr, 2, d, s, b2, 2, CU_TENSOR_MAP_SWIZZLE_NONE); }
  { cuuint64_t d[3] = {64, SQ, O_BLOCKS}, s[2] = {128, SQ * 128}; cuuint32_t b[3] = {64, 64, 2}, b2[3] = {64, 32, 2};
    make_map(enc, &P.o_st[0], o_ptr, 3, d, s, b); make_map(enc, &P.o_st[1], o_ptr, 3, d, s, b2); }
  { cuuint64_t d[3] = {64, (cuuint64_t)NB * SQ, 2 * DM / 64}, s[2] = {2 * DM * 2, 128}; cuuint32_t b[3] = {64, 64, 2}, b2[3] = {64, 32, 2};
    make_map(enc, &P.out_st[0], d_out, 3, d, s, b); make_map(enc, &P.out_st[1], d_out, 3, d, s, b2); }
  if (n_sm >= NCTA) mha_fused_kernel<false><<<NCTA, 384, SMEM_BYTES>>>(P);
  else mha_fused_kernel<true><<<n_sm, 384, SMEM_BYTES>>>(P);
}
```

```cpp
#include <cuda_runtime.h>
#include <cuda_bf16.h>
#include <cuda.h>
#include <stdint.h>
#include <stdlib.h>

namespace {

__device__ __forceinline__ void wgmma_proj(float (&d)[64], uint64_t da, uint64_t db, int scaleD) {
  asm volatile("{\n.reg .pred p;\nsetp.ne.b32 p, %66, 0;\n"
      "wgmma.mma_async.sync.aligned.m64n128k16.f32.bf16.bf16 "
      "{%0, %1, %2, %3, %4, %5, %6, %7, %8, %9, %10, %11, %12, %13, %14, %15, %16, %17, %18, %19, %20, %21, %22, %23, %24, %25, %26, %27, %28, %29, %30, "
      "%31, %32, %33, %34, %35, %36, %37, %38, %39, %40, %41, %42, %43, %44, %45, %46, %47, %48, %49, %50, %51, %52, %53, %54, %55, %56, %57, %58, %59, %60, "
      "%61, %62, %63}, "
      "%64, %65, p, 1, 1, 0, 1;\n}\n"
      : "+f"(d[0]), "+f"(d[1]), "+f"(d[2]), "+f"(d[3]), "+f"(d[4]), "+f"(d[5]), "+f"(d[6]), "+f"(d[7]), "+f"(d[8]), "+f"(d[9]), "+f"(d[10]), "+f"(d[11]),
        "+f"(d[12]), "+f"(d[13]), "+f"(d[14]), "+f"(d[15]), "+f"(d[16]), "+f"(d[17]), "+f"(d[18]), "+f"(d[19]), "+f"(d[20]), "+f"(d[21]), "+f"(d[22]),
        "+f"(d[23]), "+f"(d[24]), "+f"(d[25]), "+f"(d[26]), "+f"(d[27]), "+f"(d[28]), "+f"(d[29]), "+f"(d[30]), "+f"(d[31]), "+f"(d[32]), "+f"(d[33]),
        "+f"(d[34]), "+f"(d[35]), "+f"(d[36]), "+f"(d[37]), "+f"(d[38]), "+f"(d[39]), "+f"(d[40]), "+f"(d[41]), "+f"(d[42]), "+f"(d[43]), "+f"(d[44]),
        "+f"(d[45]), "+f"(d[46]), "+f"(d[47]), "+f"(d[48]), "+f"(d[49]), "+f"(d[50]), "+f"(d[51]), "+f"(d[52]), "+f"(d[53]), "+f"(d[54]), "+f"(d[55]),
        "+f"(d[56]), "+f"(d[57]), "+f"(d[58]), "+f"(d[59]), "+f"(d[60]), "+f"(d[61]), "+f"(d[62]), "+f"(d[63])
      : "l"(da), "l"(db), "r"(scaleD));
}
__device__ __forceinline__ void wgmma_proj96(float (&d)[64], uint64_t da, uint64_t db, int scaleD) {
  asm volatile("{\n.reg .pred p;\nsetp.ne.b32 p, %50, 0;\n"
      "wgmma.mma_async.sync.aligned.m64n96k16.f32.bf16.bf16 "
      "{%0, %1, %2, %3, %4, %5, %6, %7, %8, %9, %10, %11, %12, %13, %14, %15, %16, %17, %18, %19, %20, %21, %22, %23, %24, %25, %26, %27, %28, %29, %30, "
      "%31, %32, %33, %34, %35, %36, %37, %38, %39, %40, %41, %42, %43, %44, %45, %46, %47}, "
      "%48, %49, p, 1, 1, 1, 0;\n}\n"
      : "+f"(d[0]), "+f"(d[1]), "+f"(d[2]), "+f"(d[3]), "+f"(d[4]), "+f"(d[5]), "+f"(d[6]), "+f"(d[7]), "+f"(d[8]), "+f"(d[9]), "+f"(d[10]), "+f"(d[11]),
        "+f"(d[12]), "+f"(d[13]), "+f"(d[14]), "+f"(d[15]), "+f"(d[16]), "+f"(d[17]), "+f"(d[18]), "+f"(d[19]), "+f"(d[20]), "+f"(d[21]), "+f"(d[22]),
        "+f"(d[23]), "+f"(d[24]), "+f"(d[25]), "+f"(d[26]), "+f"(d[27]), "+f"(d[28]), "+f"(d[29]), "+f"(d[30]), "+f"(d[31]), "+f"(d[32]), "+f"(d[33]),
        "+f"(d[34]), "+f"(d[35]), "+f"(d[36]), "+f"(d[37]), "+f"(d[38]), "+f"(d[39]), "+f"(d[40]), "+f"(d[41]), "+f"(d[42]), "+f"(d[43]), "+f"(d[44]),
        "+f"(d[45]), "+f"(d[46]), "+f"(d[47])
      : "l"(da), "l"(db), "r"(scaleD));
}
__device__ __forceinline__ void wgmma_qk(float (&d)[32], uint64_t da, uint64_t db, int scaleD) {
  asm volatile("{\n.reg .pred p;\nsetp.ne.b32 p, %34, 0;\n"
      "wgmma.mma_async.sync.aligned.m64n64k16.f32.bf16.bf16 "
      "{%0, %1, %2, %3, %4, %5, %6, %7, %8, %9, %10, %11, %12, %13, %14, %15, %16, %17, %18, %19, %20, %21, %22, %23, %24, %25, %26, %27, %28, %29, %30, "
      "%31}, "
      "%32, %33, p, 1, 1, 0, 0;\n}\n"
      : "+f"(d[0]), "+f"(d[1]), "+f"(d[2]), "+f"(d[3]), "+f"(d[4]), "+f"(d[5]), "+f"(d[6]), "+f"(d[7]), "+f"(d[8]), "+f"(d[9]), "+f"(d[10]), "+f"(d[11]),
        "+f"(d[12]), "+f"(d[13]), "+f"(d[14]), "+f"(d[15]), "+f"(d[16]), "+f"(d[17]), "+f"(d[18]), "+f"(d[19]), "+f"(d[20]), "+f"(d[21]), "+f"(d[22]),
        "+f"(d[23]), "+f"(d[24]), "+f"(d[25]), "+f"(d[26]), "+f"(d[27]), "+f"(d[28]), "+f"(d[29]), "+f"(d[30]), "+f"(d[31])
      : "l"(da), "l"(db), "r"(scaleD));
}
__device__ __forceinline__ void wgmma_qk_rs(float (&d)[32], uint32_t a0, uint32_t a1, uint32_t a2, uint32_t a3, uint64_t db, int scaleD) {
  asm volatile("{\n.reg .pred p;\nsetp.ne.b32 p, %37, 0;\n"
      "wgmma.mma_async.sync.aligned.m64n64k16.f32.bf16.bf16 "
      "{%0, %1, %2, %3, %4, %5, %6, %7, %8, %9, %10, %11, %12, %13, %14, %15, %16, %17, %18, %19, %20, %21, %22, %23, %24, %25, %26, %27, %28, %29, %30, "
      "%31}, "
      "{%32, %33, %34, %35}, %36, p, 1, 1, 0;\n}\n"
      : "+f"(d[0]), "+f"(d[1]), "+f"(d[2]), "+f"(d[3]), "+f"(d[4]), "+f"(d[5]), "+f"(d[6]), "+f"(d[7]), "+f"(d[8]), "+f"(d[9]), "+f"(d[10]), "+f"(d[11]),
        "+f"(d[12]), "+f"(d[13]), "+f"(d[14]), "+f"(d[15]), "+f"(d[16]), "+f"(d[17]), "+f"(d[18]), "+f"(d[19]), "+f"(d[20]), "+f"(d[21]), "+f"(d[22]),
        "+f"(d[23]), "+f"(d[24]), "+f"(d[25]), "+f"(d[26]), "+f"(d[27]), "+f"(d[28]), "+f"(d[29]), "+f"(d[30]), "+f"(d[31])
      : "r"(a0), "r"(a1), "r"(a2), "r"(a3), "l"(db), "r"(scaleD));
}
__device__ __forceinline__ void wgmma_pv(float (&d)[64], uint32_t a0, uint32_t a1, uint32_t a2, uint32_t a3, uint64_t db, int scaleD) {
  asm volatile("{\n.reg .pred p;\nsetp.ne.b32 p, %69, 0;\n"
      "wgmma.mma_async.sync.aligned.m64n128k16.f32.bf16.bf16 "
      "{%0, %1, %2, %3, %4, %5, %6, %7, %8, %9, %10, %11, %12, %13, %14, %15, %16, %17, %18, %19, %20, %21, %22, %23, %24, %25, %26, %27, %28, %29, %30, "
      "%31, %32, %33, %34, %35, %36, %37, %38, %39, %40, %41, %42, %43, %44, %45, %46, %47, %48, %49, %50, %51, %52, %53, %54, %55, %56, %57, %58, %59, %60, "
      "%61, %62, %63}, "
      "{%64, %65, %66, %67}, %68, p, 1, 1, 1;\n}\n"
      : "+f"(d[0]), "+f"(d[1]), "+f"(d[2]), "+f"(d[3]), "+f"(d[4]), "+f"(d[5]), "+f"(d[6]), "+f"(d[7]), "+f"(d[8]), "+f"(d[9]), "+f"(d[10]), "+f"(d[11]),
        "+f"(d[12]), "+f"(d[13]), "+f"(d[14]), "+f"(d[15]), "+f"(d[16]), "+f"(d[17]), "+f"(d[18]), "+f"(d[19]), "+f"(d[20]), "+f"(d[21]), "+f"(d[22]),
        "+f"(d[23]), "+f"(d[24]), "+f"(d[25]), "+f"(d[26]), "+f"(d[27]), "+f"(d[28]), "+f"(d[29]), "+f"(d[30]), "+f"(d[31]), "+f"(d[32]), "+f"(d[33]),
        "+f"(d[34]), "+f"(d[35]), "+f"(d[36]), "+f"(d[37]), "+f"(d[38]), "+f"(d[39]), "+f"(d[40]), "+f"(d[41]), "+f"(d[42]), "+f"(d[43]), "+f"(d[44]),
        "+f"(d[45]), "+f"(d[46]), "+f"(d[47]), "+f"(d[48]), "+f"(d[49]), "+f"(d[50]), "+f"(d[51]), "+f"(d[52]), "+f"(d[53]), "+f"(d[54]), "+f"(d[55]),
        "+f"(d[56]), "+f"(d[57]), "+f"(d[58]), "+f"(d[59]), "+f"(d[60]), "+f"(d[61]), "+f"(d[62]), "+f"(d[63])
      : "r"(a0), "r"(a1), "r"(a2), "r"(a3), "l"(db), "r"(scaleD));
}
__device__ __forceinline__ void wgmma_qk_sp(float (&d)[32], uint32_t a0, uint32_t a1, uint32_t a2, uint32_t a3, uint64_t db, int scaleD, uint32_t meta) {
  asm volatile("{\n.reg .pred p;\nsetp.ne.b32 p, %37, 0;\n"
      "wgmma.mma_async.sp.sync.aligned.m64n64k32.f32.bf16.bf16 "
      "{%0, %1, %2, %3, %4, %5, %6, %7, %8, %9, %10, %11, %12, %13, %14, %15, %16, %17, %18, %19, %20, %21, %22, %23, %24, %25, %26, %27, %28, %29, %30, "
      "%31}, "
      "{%32, %33, %34, %35}, %36, %38, 0, p, 1, 1, 0;\n}\n"
      : "+f"(d[0]), "+f"(d[1]), "+f"(d[2]), "+f"(d[3]), "+f"(d[4]), "+f"(d[5]), "+f"(d[6]), "+f"(d[7]), "+f"(d[8]), "+f"(d[9]), "+f"(d[10]), "+f"(d[11]),
        "+f"(d[12]), "+f"(d[13]), "+f"(d[14]), "+f"(d[15]), "+f"(d[16]), "+f"(d[17]), "+f"(d[18]), "+f"(d[19]), "+f"(d[20]), "+f"(d[21]), "+f"(d[22]),
        "+f"(d[23]), "+f"(d[24]), "+f"(d[25]), "+f"(d[26]), "+f"(d[27]), "+f"(d[28]), "+f"(d[29]), "+f"(d[30]), "+f"(d[31])
      : "r"(a0), "r"(a1), "r"(a2), "r"(a3), "l"(db), "r"(scaleD), "r"(meta));
}
__device__ __forceinline__ void wgmma_pv_sp(float (&d)[64], uint32_t a0, uint32_t a1, uint32_t a2, uint32_t a3, uint64_t db, int scaleD, uint32_t meta) {
  asm volatile("{\n.reg .pred p;\nsetp.ne.b32 p, %69, 0;\n"
      "wgmma.mma_async.sp.sync.aligned.m64n128k32.f32.bf16.bf16 "
      "{%0, %1, %2, %3, %4, %5, %6, %7, %8, %9, %10, %11, %12, %13, %14, %15, %16, %17, %18, %19, %20, %21, %22, %23, %24, %25, %26, %27, %28, %29, %30, "
      "%31, %32, %33, %34, %35, %36, %37, %38, %39, %40, %41, %42, %43, %44, %45, %46, %47, %48, %49, %50, %51, %52, %53, %54, %55, %56, %57, %58, %59, %60, "
      "%61, %62, %63}, "
      "{%64, %65, %66, %67}, %68, %70, 0, p, 1, 1, 1;\n}\n"
      : "+f"(d[0]), "+f"(d[1]), "+f"(d[2]), "+f"(d[3]), "+f"(d[4]), "+f"(d[5]), "+f"(d[6]), "+f"(d[7]), "+f"(d[8]), "+f"(d[9]), "+f"(d[10]), "+f"(d[11]),
        "+f"(d[12]), "+f"(d[13]), "+f"(d[14]), "+f"(d[15]), "+f"(d[16]), "+f"(d[17]), "+f"(d[18]), "+f"(d[19]), "+f"(d[20]), "+f"(d[21]), "+f"(d[22]),
        "+f"(d[23]), "+f"(d[24]), "+f"(d[25]), "+f"(d[26]), "+f"(d[27]), "+f"(d[28]), "+f"(d[29]), "+f"(d[30]), "+f"(d[31]), "+f"(d[32]), "+f"(d[33]),
        "+f"(d[34]), "+f"(d[35]), "+f"(d[36]), "+f"(d[37]), "+f"(d[38]), "+f"(d[39]), "+f"(d[40]), "+f"(d[41]), "+f"(d[42]), "+f"(d[43]), "+f"(d[44]),
        "+f"(d[45]), "+f"(d[46]), "+f"(d[47]), "+f"(d[48]), "+f"(d[49]), "+f"(d[50]), "+f"(d[51]), "+f"(d[52]), "+f"(d[53]), "+f"(d[54]), "+f"(d[55]),
        "+f"(d[56]), "+f"(d[57]), "+f"(d[58]), "+f"(d[59]), "+f"(d[60]), "+f"(d[61]), "+f"(d[62]), "+f"(d[63])
      : "r"(a0), "r"(a1), "r"(a2), "r"(a3), "l"(db), "r"(scaleD), "r"(meta));
}
__device__ __forceinline__ void wgmma_proj_init(float (&d)[64], uint64_t da, uint64_t db, int scaleD) {
  asm volatile("{\n.reg .pred p;\nsetp.ne.b32 p, %66, 0;\n"
      "wgmma.mma_async.sync.aligned.m64n128k16.f32.bf16.bf16 "
      "{%0, %1, %2, %3, %4, %5, %6, %7, %8, %9, %10, %11, %12, %13, %14, %15, %16, %17, %18, %19, %20, %21, %22, %23, %24, %25, %26, %27, %28, %29, %30, "
      "%31, %32, %33, %34, %35, %36, %37, %38, %39, %40, %41, %42, %43, %44, %45, %46, %47, %48, %49, %50, %51, %52, %53, %54, %55, %56, %57, %58, %59, %60, "
      "%61, %62, %63}, "
      "%64, %65, p, 1, 1, 0, 1;\n}\n"
      : "=f"(d[0]), "=f"(d[1]), "=f"(d[2]), "=f"(d[3]), "=f"(d[4]), "=f"(d[5]), "=f"(d[6]), "=f"(d[7]), "=f"(d[8]), "=f"(d[9]), "=f"(d[10]), "=f"(d[11]),
        "=f"(d[12]), "=f"(d[13]), "=f"(d[14]), "=f"(d[15]), "=f"(d[16]), "=f"(d[17]), "=f"(d[18]), "=f"(d[19]), "=f"(d[20]), "=f"(d[21]), "=f"(d[22]),
        "=f"(d[23]), "=f"(d[24]), "=f"(d[25]), "=f"(d[26]), "=f"(d[27]), "=f"(d[28]), "=f"(d[29]), "=f"(d[30]), "=f"(d[31]), "=f"(d[32]), "=f"(d[33]),
        "=f"(d[34]), "=f"(d[35]), "=f"(d[36]), "=f"(d[37]), "=f"(d[38]), "=f"(d[39]), "=f"(d[40]), "=f"(d[41]), "=f"(d[42]), "=f"(d[43]), "=f"(d[44]),
        "=f"(d[45]), "=f"(d[46]), "=f"(d[47]), "=f"(d[48]), "=f"(d[49]), "=f"(d[50]), "=f"(d[51]), "=f"(d[52]), "=f"(d[53]), "=f"(d[54]), "=f"(d[55]),
        "=f"(d[56]), "=f"(d[57]), "=f"(d[58]), "=f"(d[59]), "=f"(d[60]), "=f"(d[61]), "=f"(d[62]), "=f"(d[63])
      : "l"(da), "l"(db), "r"(scaleD));
}
__device__ __forceinline__ void wgmma_proj96_init(float (&d)[64], uint64_t da, uint64_t db, int scaleD) {
  asm volatile("{\n.reg .pred p;\nsetp.ne.b32 p, %50, 0;\n"
      "wgmma.mma_async.sync.aligned.m64n96k16.f32.bf16.bf16 "
      "{%0, %1, %2, %3, %4, %5, %6, %7, %8, %9, %10, %11, %12, %13, %14, %15, %16, %17, %18, %19, %20, %21, %22, %23, %24, %25, %26, %27, %28, %29, %30, "
      "%31, %32, %33, %34, %35, %36, %37, %38, %39, %40, %41, %42, %43, %44, %45, %46, %47}, "
      "%48, %49, p, 1, 1, 1, 0;\n}\n"
      : "=f"(d[0]), "=f"(d[1]), "=f"(d[2]), "=f"(d[3]), "=f"(d[4]), "=f"(d[5]), "=f"(d[6]), "=f"(d[7]), "=f"(d[8]), "=f"(d[9]), "=f"(d[10]), "=f"(d[11]),
        "=f"(d[12]), "=f"(d[13]), "=f"(d[14]), "=f"(d[15]), "=f"(d[16]), "=f"(d[17]), "=f"(d[18]), "=f"(d[19]), "=f"(d[20]), "=f"(d[21]), "=f"(d[22]),
        "=f"(d[23]), "=f"(d[24]), "=f"(d[25]), "=f"(d[26]), "=f"(d[27]), "=f"(d[28]), "=f"(d[29]), "=f"(d[30]), "=f"(d[31]), "=f"(d[32]), "=f"(d[33]),
        "=f"(d[34]), "=f"(d[35]), "=f"(d[36]), "=f"(d[37]), "=f"(d[38]), "=f"(d[39]), "=f"(d[40]), "=f"(d[41]), "=f"(d[42]), "=f"(d[43]), "=f"(d[44]),
        "=f"(d[45]), "=f"(d[46]), "=f"(d[47])
      : "l"(da), "l"(db), "r"(scaleD));
}
__device__ __forceinline__ void wgmma_qk_init(float (&d)[32], uint64_t da, uint64_t db, int scaleD) {
  asm volatile("{\n.reg .pred p;\nsetp.ne.b32 p, %34, 0;\n"
      "wgmma.mma_async.sync.aligned.m64n64k16.f32.bf16.bf16 "
      "{%0, %1, %2, %3, %4, %5, %6, %7, %8, %9, %10, %11, %12, %13, %14, %15, %16, %17, %18, %19, %20, %21, %22, %23, %24, %25, %26, %27, %28, %29, %30, "
      "%31}, "
      "%32, %33, p, 1, 1, 0, 0;\n}\n"
      : "=f"(d[0]), "=f"(d[1]), "=f"(d[2]), "=f"(d[3]), "=f"(d[4]), "=f"(d[5]), "=f"(d[6]), "=f"(d[7]), "=f"(d[8]), "=f"(d[9]), "=f"(d[10]), "=f"(d[11]),
        "=f"(d[12]), "=f"(d[13]), "=f"(d[14]), "=f"(d[15]), "=f"(d[16]), "=f"(d[17]), "=f"(d[18]), "=f"(d[19]), "=f"(d[20]), "=f"(d[21]), "=f"(d[22]),
        "=f"(d[23]), "=f"(d[24]), "=f"(d[25]), "=f"(d[26]), "=f"(d[27]), "=f"(d[28]), "=f"(d[29]), "=f"(d[30]), "=f"(d[31])
      : "l"(da), "l"(db), "r"(scaleD));
}
__device__ __forceinline__ void wgmma_qk_rs_init(float (&d)[32], uint32_t a0, uint32_t a1, uint32_t a2, uint32_t a3, uint64_t db, int scaleD) {
  asm volatile("{\n.reg .pred p;\nsetp.ne.b32 p, %37, 0;\n"
      "wgmma.mma_async.sync.aligned.m64n64k16.f32.bf16.bf16 "
      "{%0, %1, %2, %3, %4, %5, %6, %7, %8, %9, %10, %11, %12, %13, %14, %15, %16, %17, %18, %19, %20, %21, %22, %23, %24, %25, %26, %27, %28, %29, %30, "
      "%31}, "
      "{%32, %33, %34, %35}, %36, p, 1, 1, 0;\n}\n"
      : "=f"(d[0]), "=f"(d[1]), "=f"(d[2]), "=f"(d[3]), "=f"(d[4]), "=f"(d[5]), "=f"(d[6]), "=f"(d[7]), "=f"(d[8]), "=f"(d[9]), "=f"(d[10]), "=f"(d[11]),
        "=f"(d[12]), "=f"(d[13]), "=f"(d[14]), "=f"(d[15]), "=f"(d[16]), "=f"(d[17]), "=f"(d[18]), "=f"(d[19]), "=f"(d[20]), "=f"(d[21]), "=f"(d[22]),
        "=f"(d[23]), "=f"(d[24]), "=f"(d[25]), "=f"(d[26]), "=f"(d[27]), "=f"(d[28]), "=f"(d[29]), "=f"(d[30]), "=f"(d[31])
      : "r"(a0), "r"(a1), "r"(a2), "r"(a3), "l"(db), "r"(scaleD));
}
__device__ __forceinline__ void wgmma_pv_init(float (&d)[64], uint32_t a0, uint32_t a1, uint32_t a2, uint32_t a3, uint64_t db, int scaleD) {
  asm volatile("{\n.reg .pred p;\nsetp.ne.b32 p, %69, 0;\n"
      "wgmma.mma_async.sync.aligned.m64n128k16.f32.bf16.bf16 "
      "{%0, %1, %2, %3, %4, %5, %6, %7, %8, %9, %10, %11, %12, %13, %14, %15, %16, %17, %18, %19, %20, %21, %22, %23, %24, %25, %26, %27, %28, %29, %30, "
      "%31, %32, %33, %34, %35, %36, %37, %38, %39, %40, %41, %42, %43, %44, %45, %46, %47, %48, %49, %50, %51, %52, %53, %54, %55, %56, %57, %58, %59, %60, "
      "%61, %62, %63}, "
      "{%64, %65, %66, %67}, %68, p, 1, 1, 1;\n}\n"
      : "=f"(d[0]), "=f"(d[1]), "=f"(d[2]), "=f"(d[3]), "=f"(d[4]), "=f"(d[5]), "=f"(d[6]), "=f"(d[7]), "=f"(d[8]), "=f"(d[9]), "=f"(d[10]), "=f"(d[11]),
        "=f"(d[12]), "=f"(d[13]), "=f"(d[14]), "=f"(d[15]), "=f"(d[16]), "=f"(d[17]), "=f"(d[18]), "=f"(d[19]), "=f"(d[20]), "=f"(d[21]), "=f"(d[22]),
        "=f"(d[23]), "=f"(d[24]), "=f"(d[25]), "=f"(d[26]), "=f"(d[27]), "=f"(d[28]), "=f"(d[29]), "=f"(d[30]), "=f"(d[31]), "=f"(d[32]), "=f"(d[33]),
        "=f"(d[34]), "=f"(d[35]), "=f"(d[36]), "=f"(d[37]), "=f"(d[38]), "=f"(d[39]), "=f"(d[40]), "=f"(d[41]), "=f"(d[42]), "=f"(d[43]), "=f"(d[44]),
        "=f"(d[45]), "=f"(d[46]), "=f"(d[47]), "=f"(d[48]), "=f"(d[49]), "=f"(d[50]), "=f"(d[51]), "=f"(d[52]), "=f"(d[53]), "=f"(d[54]), "=f"(d[55]),
        "=f"(d[56]), "=f"(d[57]), "=f"(d[58]), "=f"(d[59]), "=f"(d[60]), "=f"(d[61]), "=f"(d[62]), "=f"(d[63])
      : "r"(a0), "r"(a1), "r"(a2), "r"(a3), "l"(db), "r"(scaleD));
}
__device__ __forceinline__ void wgmma_qk_sp_init(float (&d)[32], uint32_t a0, uint32_t a1, uint32_t a2, uint32_t a3, uint64_t db, int scaleD, uint32_t meta) {
  asm volatile("{\n.reg .pred p;\nsetp.ne.b32 p, %37, 0;\n"
      "wgmma.mma_async.sp.sync.aligned.m64n64k32.f32.bf16.bf16 "
      "{%0, %1, %2, %3, %4, %5, %6, %7, %8, %9, %10, %11, %12, %13, %14, %15, %16, %17, %18, %19, %20, %21, %22, %23, %24, %25, %26, %27, %28, %29, %30, "
      "%31}, "
      "{%32, %33, %34, %35}, %36, %38, 0, p, 1, 1, 0;\n}\n"
      : "=f"(d[0]), "=f"(d[1]), "=f"(d[2]), "=f"(d[3]), "=f"(d[4]), "=f"(d[5]), "=f"(d[6]), "=f"(d[7]), "=f"(d[8]), "=f"(d[9]), "=f"(d[10]), "=f"(d[11]),
        "=f"(d[12]), "=f"(d[13]), "=f"(d[14]), "=f"(d[15]), "=f"(d[16]), "=f"(d[17]), "=f"(d[18]), "=f"(d[19]), "=f"(d[20]), "=f"(d[21]), "=f"(d[22]),
        "=f"(d[23]), "=f"(d[24]), "=f"(d[25]), "=f"(d[26]), "=f"(d[27]), "=f"(d[28]), "=f"(d[29]), "=f"(d[30]), "=f"(d[31])
      : "r"(a0), "r"(a1), "r"(a2), "r"(a3), "l"(db), "r"(scaleD), "r"(meta));
}
__device__ __forceinline__ void wgmma_pv_sp_init(float (&d)[64], uint32_t a0, uint32_t a1, uint32_t a2, uint32_t a3, uint64_t db, int scaleD, uint32_t meta) {
  asm volatile("{\n.reg .pred p;\nsetp.ne.b32 p, %69, 0;\n"
      "wgmma.mma_async.sp.sync.aligned.m64n128k32.f32.bf16.bf16 "
      "{%0, %1, %2, %3, %4, %5, %6, %7, %8, %9, %10, %11, %12, %13, %14, %15, %16, %17, %18, %19, %20, %21, %22, %23, %24, %25, %26, %27, %28, %29, %30, "
      "%31, %32, %33, %34, %35, %36, %37, %38, %39, %40, %41, %42, %43, %44, %45, %46, %47, %48, %49, %50, %51, %52, %53, %54, %55, %56, %57, %58, %59, %60, "
      "%61, %62, %63}, "
      "{%64, %65, %66, %67}, %68, %70, 0, p, 1, 1, 1;\n}\n"
      : "=f"(d[0]), "=f"(d[1]), "=f"(d[2]), "=f"(d[3]), "=f"(d[4]), "=f"(d[5]), "=f"(d[6]), "=f"(d[7]), "=f"(d[8]), "=f"(d[9]), "=f"(d[10]), "=f"(d[11]),
        "=f"(d[12]), "=f"(d[13]), "=f"(d[14]), "=f"(d[15]), "=f"(d[16]), "=f"(d[17]), "=f"(d[18]), "=f"(d[19]), "=f"(d[20]), "=f"(d[21]), "=f"(d[22]),
        "=f"(d[23]), "=f"(d[24]), "=f"(d[25]), "=f"(d[26]), "=f"(d[27]), "=f"(d[28]), "=f"(d[29]), "=f"(d[30]), "=f"(d[31]), "=f"(d[32]), "=f"(d[33]),
        "=f"(d[34]), "=f"(d[35]), "=f"(d[36]), "=f"(d[37]), "=f"(d[38]), "=f"(d[39]), "=f"(d[40]), "=f"(d[41]), "=f"(d[42]), "=f"(d[43]), "=f"(d[44]),
        "=f"(d[45]), "=f"(d[46]), "=f"(d[47]), "=f"(d[48]), "=f"(d[49]), "=f"(d[50]), "=f"(d[51]), "=f"(d[52]), "=f"(d[53]), "=f"(d[54]), "=f"(d[55]),
        "=f"(d[56]), "=f"(d[57]), "=f"(d[58]), "=f"(d[59]), "=f"(d[60]), "=f"(d[61]), "=f"(d[62]), "=f"(d[63])
      : "r"(a0), "r"(a1), "r"(a2), "r"(a3), "l"(db), "r"(scaleD), "r"(meta));
}

constexpr int NB = 16, SQ = 224, DM = 640, NH = 32, SK = 1024, DH = 128;
constexpr int HD = NH * DH;
constexpr int NBETA = 2 * NB;
constexpr int NCTA = 132;
constexpr int NS = 10;
constexpr int SLOT = 16384;
constexpr int QBUF_OFF = NS * SLOT;
constexpr int NSX = NS + 4;
constexpr int BAR_OFF = NSX * SLOT;
constexpr int BAR_FULL = BAR_OFF;
constexpr int BAR_EMPTY = BAR_OFF + 8 * NSX;
constexpr int BAR_STG = BAR_OFF + 16 * NSX;
constexpr int BAR_OUT = BAR_STG + 32;
constexpr int BAR_DESC = BAR_OUT + 8;
constexpr int BAR_GO = BAR_DESC + 8;
constexpr int DESC_OFF = BAR_GO + 8;
constexpr int EPOCH_OFF = DESC_OFF + 16;
constexpr int TRACE_OFF = EPOCH_OFF + 8;
constexpr int SMEM_BYTES = TRACE_OFF;
constexpr float SM_C = 0.08838834764831845f * 1.4426950408889634f;
constexpr float SUM_HI = 1099511627776.f, SUM_LO = 1.f / 1099511627776.f;
constexpr uint32_t META_QK = 0xEEEE4444u;
constexpr uint32_t META_PV = 0x44EEEE44u;

#define QK_EARLY_MASK 3
#define ST_ORDER 0x2130
#define LAG_BAR 5
#define ST_NOW 9
#define PF_STEP 5
#define KV_WIN_UNITS 2
#define KV_WIN_D 4
#define SF 0xfe1f
#define O_STEPS 4
#define KV_WIN_RAMP 4
#define PDEPTH 0
#define KV_WIN_TILES -2
#define PR_KV 2
#define PR_X 2
#define PR_W 2
#define REG_C 232
#define REG_P 40
#define GO_P 4
#define P_POS 216
#define OR 6
#define OR0 2
#define KG 5
#define PK 44
#define EARLY_MASK 0x1fffu
#define PIECE_TABLE 0x50327013,0x6c4e705f,0x50199018,0x65e8902e,0x5025c01c,0x695ac02f,0x5024a812,0x69d8a85e,0x5026181a,0x6a561834,0x403f580d,0x80000000,0x50273810,0x6b133831,0x5021101b,0x69d8103a,0x501da017,0x695aa032,0x5016980e,0x67a19837,0x502b4011,0x6dc8405d,0x62f42839,0x80000000,0x50120816,0x689d083b,0x50282014,0x80000000,0x646e6035,0x80000000,0x64ec0036,0x80000000,0x5024c80f,0x80000000,0x500db81e,0x6999b83c,0x501f801f,0x80000000,0x66a58838,0x80000000,0x500a3019,0x6a173030,0x501c501d,0x80000000,0x5759481d,0x80000000,0x5398b01e,0x80000000,0x50106815,0x6ccc6833,0x5810781f,0x80000000

struct Params {
  CUtensorMap x[2][2], wq[2], kv[2][2], wo[2];
  CUtensorMap o_ld[2], o_st[2], out_st[2];
  const __nv_bfloat16* kp[2];
  const __nv_bfloat16* vp[2];
};

constexpr int NPART = 32 * 5, O_BLOCKS = NBETA * 64 + 2 * NPART;
__device__ __align__(128) __nv_bfloat16 g_o[(size_t)O_BLOCKS * SQ * 64];
__device__ unsigned g_cnt[NBETA][8];
__device__ unsigned g_rd[NBETA][8];
__device__ unsigned g_epoch, g_next;
__device__ unsigned g_flag[NPART];

__device__ __forceinline__ uint32_t smem_u32(const void* p) { return (uint32_t)__cvta_generic_to_shared(p); }
__device__ __forceinline__ void mbar_arrive(uint32_t bar) {
  asm volatile("mbarrier.arrive.shared::cta.b64 _, [%0];" ::"r"(bar) : "memory");
}
__device__ __forceinline__ void mbar_arrive_warp(uint32_t bar) {
  asm volatile("{\n.reg .pred p;\nelect.sync _|p, 0xffffffff;\n@p mbarrier.arrive.shared::cta.b64 _, [%0];\n}" ::"r"(bar) : "memory");
}
__device__ __forceinline__ int lane_now() { int l; asm volatile("mov.u32 %0, %%laneid;" : "=r"(l)); return l; }
__device__ __forceinline__ bool mbar_try(uint32_t bar, uint32_t parity) {
  uint32_t ok;
  asm volatile("{\n.reg .pred p;\nmbarrier.try_wait.parity.shared::cta.b64 p, [%1], %2;\nselp.u32 %0, 1, 0, p;\n}"
               : "=r"(ok) : "r"(bar), "r"(parity) : "memory");
  return ok;
}
__device__ __forceinline__ bool mbar_test(uint32_t bar, uint32_t parity) {
  uint32_t ok;
  asm volatile("{\n.reg .pred p;\nmbarrier.test_wait.parity.shared::cta.b64 p, [%1], %2;\nselp.u32 %0, 1, 0, p;\n}"
               : "=r"(ok) : "r"(bar), "r"(parity) : "memory");
  return ok;
}
__device__ __forceinline__ void mbar_wait_w(uint32_t bar, uint32_t parity) {
  uint32_t n = 0;
  while (!__all_sync(0xffffffffu, mbar_try(bar, parity))) {
    if (++n > (1u << 22)) __trap();
  }
}
#define ELECT "{\n.reg .pred p;\nelect.sync _|p, 0xffffffff;\n@p "
__device__ __forceinline__ void tma_st3_hint_w(const CUtensorMap* m, uint32_t src, int c0, int c1, int c2, uint64_t pol) {
  asm volatile(ELECT "cp.async.bulk.tensor.3d.global.shared::cta.bulk_group.L2::cache_hint [%0, {%2, %3, %4}], [%1], %5;\n}"
               ::"l"(m), "r"(src), "r"(c0), "r"(c1), "r"(c2), "l"(pol) : "memory");
}
#define EXPECT(bar, bytes) "mbarrier.arrive.expect_tx.shared::cta.b64 _, [" bar "], " bytes ";\n@p "
__device__ __forceinline__ void tma_ld2_w(uint32_t dst, const CUtensorMap* m, int c0, int c1, uint32_t bar, uint32_t bytes) {
  asm volatile(ELECT EXPECT("%2", "%5") "cp.async.bulk.tensor.2d.shared::cluster.global.mbarrier::complete_tx::bytes [%0], [%1, {%3, %4}], [%2];\n}"
               ::"r"(dst), "l"(m), "r"(bar), "r"(c0), "r"(c1), "r"(bytes) : "memory");
}
__device__ __forceinline__ void tma_ld2_hint_w(uint32_t dst, const CUtensorMap* m, int c0, int c1, uint32_t bar, uint32_t bytes, uint64_t pol) {
  asm volatile(ELECT EXPECT("%2", "%6") "cp.async.bulk.tensor.2d.shared::cluster.global.mbarrier::complete_tx::bytes.L2::cache_hint"
               " [%0], [%1, {%3, %4}], [%2], %5;\n}"
               ::"r"(dst), "l"(m), "r"(bar), "r"(c0), "r"(c1), "l"(pol), "r"(bytes) : "memory");
}
__device__ __forceinline__ void tma_ld3_w(uint32_t dst, const CUtensorMap* m, int c0, int c1, int c2, uint32_t bar, uint32_t bytes) {
  asm volatile(ELECT EXPECT("%2", "%6") "cp.async.bulk.tensor.3d.shared::cluster.global.mbarrier::complete_tx::bytes [%0], [%1, {%3, %4, %5}], [%2];\n}"
               ::"r"(dst), "l"(m), "r"(bar), "r"(c0), "r"(c1), "r"(c2), "r"(bytes) : "memory");
}
__device__ __forceinline__ void tma_ld3_hint_w(uint32_t dst, const CUtensorMap* m, int c0, int c1, int c2, uint32_t bar, uint64_t pol) {
  asm volatile(ELECT EXPECT("%2", "16384") "cp.async.bulk.tensor.3d.shared::cluster.global.mbarrier::complete_tx::bytes.L2::cache_hint"
               " [%0], [%1, {%3, %4, %5}], [%2], %6;\n}"
               ::"r"(dst), "l"(m), "r"(bar), "r"(c0), "r"(c1), "r"(c2), "l"(pol) : "memory");
}
__device__ __forceinline__ void tma_ld_wo_w(uint32_t dst, const CUtensorMap* m, int col, int grp, uint32_t bar) {
  asm volatile(ELECT EXPECT("%2", "16384") "cp.async.bulk.tensor.5d.shared::cluster.global.mbarrier::complete_tx::bytes [%0], [%1, {%3, 0, 0, 0, %4}], [%2];\n"
               "@p cp.async.bulk.tensor.5d.shared::cluster.global.mbarrier::complete_tx::bytes [%5], [%1, {%6, 0, 0, 0, %4}], [%2];\n}"
               ::"r"(dst), "l"(m), "r"(bar), "r"(col), "r"(grp), "r"(dst + 8192), "r"(col + 64) : "memory");
}
__device__ __forceinline__ void mbar_arrive8_w(uint32_t bar) {
  asm volatile(ELECT "mbarrier.arrive.shared::cta.b64 _, [%0], 8;\n}" ::"r"(bar) : "memory");
}
__device__ __forceinline__ void bulk_commit() { asm volatile("cp.async.bulk.commit_group;" ::: "memory"); }
template <int N> __device__ __forceinline__ void bulk_wait_read() { asm volatile("cp.async.bulk.wait_group.read %0;" ::"n"(N) : "memory"); }
__device__ __forceinline__ void wg_fence() { asm volatile("wgmma.fence.sync.aligned;" ::: "memory"); }
__device__ __forceinline__ void wg_commit() { asm volatile("wgmma.commit_group.sync.aligned;" ::: "memory"); }
template <int N> __device__ __forceinline__ void wg_wait() { asm volatile("wgmma.wait_group.sync.aligned %0;" ::"n"(N) : "memory"); }
__device__ __forceinline__ void fence_async_smem() { asm volatile("fence.proxy.async.shared::cta;" ::: "memory"); }
__device__ __forceinline__ void bar_sync(int id, int n) { asm volatile("bar.sync %0, %1;" ::"r"(id), "r"(n) : "memory"); }
__device__ __forceinline__ void touch(float& a) { asm volatile("neg.f32 %0, %0;" : "+f"(a)); }
__device__ __forceinline__ void touch(uint32_t& a) { asm volatile("not.b32 %0, %0;" : "+r"(a)); }
template <typename T, int N> __device__ __forceinline__ void touch(T (&a)[N]) {
#pragma unroll
  for (int i = 0; i < N; i++) touch(a[i]);
}
template <int ID, typename... A> __device__ __forceinline__ void sched_fence(uint32_t x, A&... a) {
  if (!((SF >> ID) & 1)) return;
  asm volatile("" : "+r"(x)::"memory");
#pragma unroll 1
  for (; __builtin_expect(x >= 100 + ID, 0); x >>= 1) { (touch(a), ...); __nanosleep(x); }
}
template <int N> __device__ __forceinline__ void reg_fence(float (&a)[N]) {
#pragma unroll
  for (int i = 0; i < N; i++) asm volatile("" : "+f"(a[i])::"memory");
}
template <int N> __device__ __forceinline__ void reg_fence(uint32_t (&a)[N]) {
#pragma unroll
  for (int i = 0; i < N; i++) asm volatile("" : "+r"(a[i])::"memory");
}
__device__ __forceinline__ float ex2(float x) { float y; asm("ex2.approx.ftz.f32 %0, %1;" : "=f"(y) : "f"(x)); return y; }
__device__ __forceinline__ uint32_t pack_bf16(float lo, float hi) {
  uint32_t r; asm("cvt.rn.bf16x2.f32 %0, %1, %2;" : "=r"(r) : "f"(hi), "f"(lo)); return r;
}
__device__ __forceinline__ void stsm4(uint32_t a, uint32_t r0, uint32_t r1, uint32_t r2, uint32_t r3) {
  asm volatile("stmatrix.sync.aligned.m8n8.x4.shared.b16 [%0], {%1, %2, %3, %4};" ::"r"(a), "r"(r0), "r"(r1), "r"(r2), "r"(r3) : "memory");
}
__device__ __forceinline__ void stsm4t(uint32_t a, uint32_t r0, uint32_t r1, uint32_t r2, uint32_t r3) {
  asm volatile("stmatrix.sync.aligned.m8n8.x4.trans.shared.b16 [%0], {%1, %2, %3, %4};" ::"r"(a), "r"(r0), "r"(r1), "r"(r2), "r"(r3) : "memory");
}
__device__ __forceinline__ void ldsm4(uint32_t a, uint32_t& r0, uint32_t& r1, uint32_t& r2, uint32_t& r3) {
  asm volatile("ldmatrix.sync.aligned.m8n8.x4.shared.b16 {%0, %1, %2, %3}, [%4];" : "=r"(r0), "=r"(r1), "=r"(r2), "=r"(r3) : "r"(a) : "memory");
}
__device__ __forceinline__ void sts16(uint32_t a, uint32_t v) { asm volatile("st.shared.u16 [%0], %1;" ::"r"(a), "h"((uint16_t)v) : "memory"); }
__device__ __forceinline__ void mma16816(float& c0, float& c1, float& c2, float& c3, uint32_t a0, uint32_t a1, uint32_t a2, uint32_t a3,
                                         uint32_t b0, uint32_t b1) {
  asm volatile("mma.sync.aligned.m16n8k16.row.col.f32.bf16.bf16.f32 {%0, %1, %2, %3}, {%4, %5, %6, %7}, {%8, %9}, {%0, %1, %2, %3};"
               : "+f"(c0), "+f"(c1), "+f"(c2), "+f"(c3) : "r"(a0), "r"(a1), "r"(a2), "r"(a3), "r"(b0), "r"(b1));
}
__device__ __forceinline__ uint32_t sdesc(uint32_t addr, uint32_t lbo) { return (addr >> 4) + ((lbo >> 4) << 16); }
__device__ __forceinline__ uint64_t desc64(uint32_t lo, uint32_t hi) { uint64_t d; asm("mov.b64 %0, {%1, %2};" : "=l"(d) : "r"(lo), "r"(hi)); return d; }
__device__ __forceinline__ void dadd(uint64_t& d, uint32_t inc) {
  asm("{\n.reg .b32 l, h;\nmov.b64 {l, h}, %0;\nadd.u32 l, l, %1;\nmov.b64 %0, {l, h};\n}" : "+l"(d) : "r"(inc));
}

struct Ring {
  uint32_t slot, phase, xp;
  __device__ __forceinline__ void uniform() {
    slot = __shfl_sync(0xffffffffu, slot, 0); phase = __shfl_sync(0xffffffffu, phase, 0); xp = __shfl_sync(0xffffffffu, xp, 0);
  }
  __device__ __forceinline__ void next() { if (++slot == NS) { slot = 0; phase ^= 1; } }
  __device__ __forceinline__ void next_if(bool p) { slot += p; if (slot == NS) { slot = 0; phase ^= 1; } }
};
__device__ __forceinline__ uint32_t borrow(int ks, int n) {
  const int k = ks + 1;
  return k >= 4 && !(k & 2) && k < n ? k & 1 : 2;
}

constexpr uint32_t Q_RANGES = NBETA * NH + __builtin_popcount(EARLY_MASK) * 5, Q_ALL = NBETA * (NH + 5);
constexpr int NRANGE = NCTA / 5;
struct Work { int kind, mode, k0, nsteps, range, beta, sub; };
struct Sched { uint16_t queue[Q_ALL]; uint32_t piece[NRANGE + 1][4]; };
constexpr Sched make_sched() {
  Sched s{};
  int q = 0, a = 0;
  for (int t = 0, e = 0; a < NBETA * NH; t++) {
    for (; e < NBETA && 8 * e + PK <= t && a >= P_POS; e++)
      for (int col = 0; col < 5 && (EARLY_MASK >> e & 1); col++) s.queue[q++] = 0x8000 | col << 8 | e;
    for (int b = 0; b < NBETA; b++)
      for (int h = 0; h < NH; h++)
        if (8 * b + KG * (h >> 2) == t) { s.queue[q++] = b << 5 | h; a++; }
  }
  for (int b = 0; b < NBETA; b++)
    for (int col = 0; col < 5 && !(EARLY_MASK >> b & 1); col++) s.queue[q++] = 0x8000 | col << 8 | b;
  constexpr uint32_t T[NRANGE * 2] = {PIECE_TABLE};
  for (int g = 0; g <= NRANGE; g++)
    for (int n = 0; n < 4; n++) s.piece[g][n] = g < NRANGE && n < 2 ? T[2 * g + n] : 2u << 30;
  return s;
}
__constant__ Sched c_sched = make_sched();
constexpr int N_EARLY = __builtin_popcount(EARLY_MASK);
template <bool SIMPLE> __device__ __forceinline__ bool o_reuse(uint32_t b) { return !SIMPLE && b - (OR0 + OR) < N_EARLY - OR0; }
template <bool SIMPLE> __device__ __forceinline__ uint32_t o_slot(uint32_t b) { return o_reuse<SIMPLE>(b) ? OR0 + (b - OR0) % OR : b; }
__device__ __forceinline__ Work decode(uint32_t d) {
  Work w;
  w.kind = d >> 30; if (w.kind == 3) w.kind = 1;
  w.mode = (d >> 28) & 3; w.k0 = (d >> 22) & 63;
  if (w.kind == 0) { w.beta = (d >> 5) & 31; w.sub = d & 31; w.nsteps = DM / 64; }
  else { w.beta = d & 31; w.sub = (d >> 8) & 7; w.nsteps = ((d >> 16) & 63) + 1; }
  w.range = ((d >> 11) & 31) * 5 + w.sub;
  return w;
}

__device__ __forceinline__ bool reached(const unsigned* cnt, unsigned target) {
  unsigned v;
  asm volatile("ld.acquire.gpu.global.u32 %0, [%1];" : "=r"(v) : "l"(cnt) : "memory");
  return (int)(v - target) >= 0;
}
__device__ __forceinline__ void wait_count(const unsigned* cnt, unsigned target) {
  unsigned n = 0;
  while (!__all_sync(0xffffffffu, reached(cnt, target))) { if (++n > (1u << 24)) __trap(); }
}
__device__ __forceinline__ uint32_t lds(uint32_t a) { uint32_t v; asm volatile("ld.volatile.shared.u32 %0, [%1];" : "=r"(v) : "r"(a) : "memory"); return v; }

#define TRACE(u, e)
#define T3(u, e)
#define T2C(u, e)
#define T2P(u, r, e)
#define TTAIL(k)
#define TCLK(k)
#define TRACE_P(u, e)
#define TRACE_IN(u, e)

struct Ctx {
  uint32_t sb;
  int wg, warp;
  uint32_t mqk, mpv;
  bool lead;
  int lane0, lane;
  int src;
};
template <int N> __device__ __forceinline__ uint32_t dhi(uint32_t lo) { return 0x40000040u + (lo >> (26 + N)); }
__device__ __forceinline__ void release(const Ctx& c, uint32_t slot) {
  if (c.lead) mbar_arrive(c.sb + BAR_EMPTY + slot * 8);
}
__device__ __forceinline__ uint32_t acquire(const Ctx& c, Ring& r, bool have = false) {
  const uint32_t s = r.slot;
  if (!have) mbar_wait_w(c.sb + BAR_FULL + s * 8, r.phase);
  r.next();
  return s;
}
__device__ __forceinline__ void mbar_wait2_w(uint32_t b0, uint32_t p0, uint32_t b1, uint32_t p1) {
  uint32_t n = 0;
  while (!__all_sync(0xffffffffu, mbar_try(b0, p0) & mbar_try(b1, p1))) {
    if (++n > (1u << 22)) __trap();
  }
}
__device__ __forceinline__ void mbar_wait3_w(uint32_t b0, uint32_t p0, uint32_t b1, uint32_t p1, uint32_t b2, uint32_t p2) {
  uint32_t n = 0;
  while (!__all_sync(0xffffffffu, mbar_try(b0, p0) & mbar_try(b1, p1) & mbar_try(b2, p2))) {
    if (++n > (1u << 22)) __trap();
  }
}
__device__ __forceinline__ void acquire2(const Ctx& c, Ring& r, uint32_t& s0, uint32_t& s1, bool have = false) {
  const uint32_t p0 = r.phase;
  s0 = r.slot; r.next(); s1 = r.slot;
  if (!have) mbar_wait2_w(c.sb + BAR_FULL + s0 * 8, p0, c.sb + BAR_FULL + s1 * 8, r.phase);
  r.next();
}
template <int N>
__device__ __forceinline__ bool peek(const Ctx& c, Ring r) {
  bool ok = true;
#pragma unroll
  for (int k = 0; k < N; k++) { ok &= mbar_test(c.sb + BAR_FULL + r.slot * 8, r.phase); r.next(); }
  return ok;
}
__device__ __forceinline__ void staged(const Ctx& c, int part) {
  fence_async_smem();
  __syncwarp();
  mbar_arrive_warp(c.sb + BAR_STG + c.wg * 16 + part * 8);
}

template <int WG, bool FIRST, int H>
__device__ __forceinline__ void proj_half(const Ctx& c, float (&acc)[64], uint32_t w, uint32_t x, uint32_t sw) {
  uint64_t dx = desc64((c.sb + x * SLOT + (WG ? 0 : H * 8192)) >> 4, dhi<0>(x) + sw);
  uint64_t dw = desc64(WG ? (c.sb + w * SLOT + H * 8192) >> 4 : sdesc(c.sb + w * SLOT, 8192), dhi<1>(x));
  wg_fence();
  if (WG) { if (FIRST) wgmma_proj96_init(acc, dw, dx, 0); else wgmma_proj96(acc, dw, dx, 1); }
  else { if (FIRST) wgmma_proj_init(acc, dx, dw, 0); else wgmma_proj(acc, dx, dw, 1); }
#pragma unroll
  for (int k = 1; k < 4; k++) {
    dadd(dx, k == 2 ? 2 + (sw >> 30) * 28 : 2); dadd(dw, 128);
    if (WG) wgmma_proj96(acc, dw, dx, 1); else wgmma_proj(acc, dx, dw, 1);
  }
  wg_commit();
}

__device__ __forceinline__ void proj_store16(uint32_t a, const float* f, float sc) {
  stsm4t(a, pack_bf16(f[0] * sc, f[1] * sc), pack_bf16(f[2] * sc, f[3] * sc), pack_bf16(f[4] * sc, f[5] * sc), pack_bf16(f[6] * sc, f[7] * sc));
}

__device__ __forceinline__ uint32_t stage_off(const Ctx& c) {
  const int lane = c.lane, mi = lane >> 3, r8 = lane & 7;
  return ((mi >> 1) * 8 + r8) * 128 + (((2 * c.warp + (mi & 1)) ^ r8) << 4);
}
__device__ __forceinline__ uint32_t q3_swz(uint32_t r8) { return ((r8 & 3) << 1) | (r8 >> 2); }
template <int H>
__device__ __forceinline__ void stage_t2(const Ctx& c, const float (&a)[64], float sc) {
  const uint32_t base = c.sb + QBUF_OFF + 2 * 16384 + H * 8192 + stage_off(c);
#pragma unroll
  for (int jj = 0; jj < 4; jj++) proj_store16(base + jj * 2048, &a[jj * 8], sc);
}
template <int H, bool IS_Q>
__device__ __forceinline__ void stage_t3(const Ctx& c, const float (&a)[64], float sc) {
  const uint32_t off = stage_off(c), r8 = (off >> 7) & 7;
  const uint32_t t3 = c.sb + QBUF_OFF + 3 * 16384 + H * 4096 + (IS_Q ? off ^ ((r8 ^ q3_swz(r8)) << 4) : off);
  proj_store16(t3, &a[32], sc);
  proj_store16(t3 + 2048, &a[40], sc);
}

template <bool TRANS>
__device__ __forceinline__ void add16(uint32_t a, float* f) {
  uint32_t r[4];
  if (TRANS) asm volatile("ldmatrix.sync.aligned.m8n8.x4.trans.shared.b16 {%0, %1, %2, %3}, [%4];"
                          : "=r"(r[0]), "=r"(r[1]), "=r"(r[2]), "=r"(r[3]) : "r"(a) : "memory");
  else ldsm4(a, r[0], r[1], r[2], r[3]);
#pragma unroll
  for (int i = 0; i < 4; i++) { f[2 * i] += __uint_as_float(r[i] << 16); f[2 * i + 1] += __uint_as_float(r[i] & 0xffff0000u); }
}

__device__ __forceinline__ void trace_dump(const Ctx& c) {
}
struct RowSum { float l0, l1; };
__device__ __forceinline__ const char* o_addr(uint32_t item, int row, int lane) {
  return reinterpret_cast<const char*>(g_o) + (((item >> 10) * (2 * SQ) + row) * 128 + (lane ^ (lane >> 3)) * 16);
}
__device__ __forceinline__ void o_stg(const char* p, int i, const uint32_t* q) {
  asm volatile("st.global.v4.b32 [%0], {%1, %2, %3, %4};"
               ::"l"(p + (i >> 1) * (SQ * 128) + (i & 1) * 512), "r"(q[0]), "r"(q[1]), "r"(q[2]), "r"(q[3]) : "memory");
}
template <int MODE, int I0 = 0, int NI = 4>
__device__ __forceinline__ void o_emit(const char* p, const float (&o)[64], float inv) {
#pragma unroll
  for (int i = I0; i < I0 + NI; i++) {
    uint32_t q[4];
#pragma unroll
    for (int j = 0; j < 4; j++) q[j] = pack_bf16(o[16 * i + 4 * j + 2 * MODE] * inv, o[16 * i + 4 * j + 2 * MODE + 1] * inv);
    o_stg(p, i, q);
  }
}
__device__ __forceinline__ void o_done(const Ctx& c) {
  __syncwarp();
  mbar_arrive_warp(c.sb + BAR_OUT);
  __syncwarp();
}
template <int WG>
__device__ __forceinline__ void o_first(const Ctx& c, uint32_t item, float (&o)[64], const RowSum& inv) {
  const char* p = o_addr(item, WG ? 192 + 8 * c.warp : 64 + 16 * c.warp, c.lane);
  reg_fence(o);
  if (WG) {
    uint32_t q[16];
#pragma unroll
    for (int j = 0; j < 16; j++) q[j] = pack_bf16((o[4 * j] + o[4 * j + 2]) * inv.l0, (o[4 * j + 1] + o[4 * j + 3]) * inv.l0);
#pragma unroll
    for (int i = 0; i < 4; i++) o_stg(p, i, q + 4 * i);
  } else { o_emit<0>(p, o, inv.l0); o_emit<1>(p + 1024, o, inv.l1); }
}
template <int K0, int K1>
__device__ __forceinline__ void o_piece(const Ctx& c, const char* p, int k, const float (&o)[64], const RowSum& inv) {
  constexpr int NI = 8 / O_STEPS, M = K0 * NI / 4;
  if constexpr (K1 - K0 == 1) {
    o_emit<M, K0 * NI % 4, NI>(p + M * 1024, o, M ? inv.l1 : inv.l0);
    if (K1 == O_STEPS) o_done(c);
  } else {
    if (k <= (K0 + K1) / 2) o_piece<K0, (K0 + K1) / 2>(c, p, k, o, inv); else o_piece<(K0 + K1) / 2, K1>(c, p, k, o, inv);
  }
}
template <int WG>
__device__ __forceinline__ void o_second(const Ctx& c, uint32_t item, int k, float (&o)[64], const RowSum& inv) {
  reg_fence(o);
  o_piece<0, O_STEPS>(c, o_addr(item, 128 * WG + 16 * c.warp, c.lane0 + (k >> 8)), k, o, inv);
}
template <int WG>
__device__ __forceinline__ void release_q(const Ctx& c) {
#pragma unroll
  for (int t = 0; t < 2; t++)
    if (c.lead) asm volatile("mbarrier.arrive.shared::cta.b64 _, [%0], 2;" ::"r"(c.sb + BAR_EMPTY + (NS + 2 * WG + t) * 8) : "memory");
  __syncwarp();
}
struct Slots { uint32_t w, x, o, po; };
template <int WG>
__device__ __forceinline__ void acc_fence(float (&a)[64]) {
#pragma unroll
  for (int i = 0; i < (WG ? 48 : 64); i++) asm volatile("" : "+f"(a[i])::"memory");
}
template <int WG>
__device__ __forceinline__ void begin_acquire(const Ctx& c, Ring& r, Slots& h, bool wait) {
  const uint32_t s0 = r.slot, p0 = r.phase, f = c.sb + BAR_FULL;
  r.next();
  const uint32_t p1 = r.phase;
  h.w = r.slot; r.next();
  h.x = WG ? r.slot : s0; h.o = WG ? s0 : r.slot; h.po = r.phase;
  if (wait) { if (WG) mbar_wait3_w(f + s0 * 8, p0, f + h.w * 8, p1, f + h.x * 8, r.phase); else mbar_wait2_w(f + s0 * 8, p0, f + h.w * 8, p1); }
  r.next();
}
template <int WG>
__device__ __forceinline__ void proj_begin(const Ctx& c, Ring& r, float (&a0)[64], Slots& h, bool wait, uint32_t sw) {
  begin_acquire<WG>(c, r, h, wait);
  proj_half<WG, true, 0>(c, a0, h.w, h.x, sw);
  if (WG) release(c, h.o);
}
template <int WG>
__device__ __forceinline__ void proj_main(Ctx& c, Ring& r, float (&a0)[64], float (&a1)[64], Slots& h, int n, uint32_t sw, int unit,
                                          uint32_t item, int nq, float (&o1)[64], const RowSum& inv) {
  constexpr bool DEEP = (PDEPTH >> WG) & 1;
  T2C(unit, 3);
  int ks = 1;
#pragma unroll 1
  do {
    const Slots p = h;
    const uint32_t b = borrow(ks, n), tile = NS + (WG ? 3 - b : b), f = c.sb + BAR_FULL;
    const uint32_t s0 = b != 2 ? tile : r.slot, p0 = b != 2 ? (r.xp >> b) & 1 : r.phase;
    r.next_if(b == 2);
    const uint32_t p1 = r.phase;
    h.w = r.slot; r.next();
    const uint32_t s2 = b != 2 ? tile : r.slot;
    h.po = b != 2 ? p0 : r.phase;
    r.next_if(b == 2);
    r.xp ^= 1 << b;
    h.x = WG ? s2 : s0; h.o = WG ? s0 : s2;
    mbar_wait3_w(f + s0 * 8, p0, f + h.w * 8, p1, f + (WG ? s2 : p.o) * 8, WG ? h.po : p.po);
    if (ks < 10) T2C(unit, ks * 4);
    if (DEEP) {
      proj_half<WG, false, 0>(c, a0, h.w, h.x, sw);
      release(c, WG ? h.o : p.o);
      if (ks < 10) T2C(unit, ks * 4 + 1);
      wg_wait<1>();
      if (ks < 10) T2C(unit, ks * 4 + 2);
      release(c, p.x); release(c, p.w);
    } else {
      release(c, WG ? h.o : p.o);
      wg_wait<0>();
      release(c, p.x); release(c, p.w);
      if (ks < 10) T2C(unit, ks * 4 + 1);
      proj_half<WG, false, 0>(c, a0, h.w, h.x, sw);
      if (ks < 10) T2C(unit, ks * 4 + 2);
    }
    proj_half<WG, false, 1>(c, a1, h.w, h.x, sw);
    if (ks < 10) T2C(unit, ks * 4 + 3);
    if (ks <= nq) o_second<WG>(c, item, ks, o1, inv);
  } while (++ks != n);
  {
    const uint32_t e0 = c.sb + BAR_EMPTY + (NS + 3 * WG) * 8, e1 = c.sb + BAR_EMPTY + (NS + 1 + WG) * 8;
    const uint32_t p0 = (r.xp ^ unit ^ 1) & 1, p1 = ((r.xp >> 1) ^ unit ^ 1) & 1;
    const uint32_t k0 = sw ? e0 : c.sb + BAR_FULL + r.slot * 8, pk = sw ? p0 : r.phase;
    uint32_t cnt = 0;
    while (!__all_sync(0xffffffffu, mbar_try(e0, p0) & mbar_try(e1, p1) & mbar_try(k0, pk) & (WG || mbar_try(c.sb + BAR_FULL + h.o * 8, h.po)))) {
      if (++cnt > (1u << 22)) __trap();
    }
  }
  c.lane = c.lane0 + (h.w >> 5);
  if (!WG) release(c, h.o);
  wg_wait<1>();
  acc_fence<WG>(a0);
}
template <int WG>
__device__ __forceinline__ void proj_end(const Ctx& c, float (&a1)[64], const Slots& h) {
  wg_wait<0>();
  acc_fence<WG>(a1);
  release(c, h.x); release(c, h.w);
}
__device__ __forceinline__ uint32_t get_desc(const Ctx& c, int i) {
  uint32_t d;
  mbar_wait_w(c.sb + BAR_DESC, (i - 1) & 1);
  asm volatile("ld.volatile.shared.u32 %0, [%1];" : "=r"(d) : "r"(c.sb + DESC_OFF + (i & 3) * 4) : "memory");
  return __shfl_sync(0xffffffffu, d, 0);
}

__device__ __forceinline__ float quad_max(float x) {
  x = fmaxf(x, __shfl_xor_sync(0xffffffffu, x, 1));
  return fmaxf(x, __shfl_xor_sync(0xffffffffu, x, 2));
}
__device__ __forceinline__ float quad_sum(float x) {
  x += __shfl_xor_sync(0xffffffffu, x, 1);
  return x + __shfl_xor_sync(0xffffffffu, x, 2);
}
template <bool SP, bool FIRST>
__device__ __forceinline__ void exps(const Ctx& c, const float (&s)[32], uint32_t (&p)[SP ? 8 : 16], RowSum& st) {
  if constexpr (SP) {
    uint32_t q[8];
    float t;
#pragma unroll
    for (int j = 0; j < 8; j++) {
      const float e0 = ex2(s[4 * j] + s[4 * j + 2]), e1 = ex2(s[4 * j + 1] + s[4 * j + 3]);
      if (j == 0) t = e0 + e1; else t += e0 + e1;
      q[j] = pack_bf16(e0, e1);
    }
    const bool odd = c.src & 2;
#pragma unroll
    for (int g = 0; g < 4; g++) {
      p[2 * g] = __shfl_sync(0xffffffffu, odd ? q[2 * g + 1] : q[2 * g], c.src);
      p[2 * g + 1] = __shfl_sync(0xffffffffu, odd ? q[2 * g] : q[2 * g + 1], c.src ^ 1);
    }
    st.l0 = FIRST ? t : st.l0 + t;
  } else {
    float t0, t1;
#pragma unroll
    for (int j = 0; j < 8; j++) {
      const float e0 = ex2(s[4 * j]), e1 = ex2(s[4 * j + 1]), e2 = ex2(s[4 * j + 2]), e3 = ex2(s[4 * j + 3]);
      if (j == 0) { t0 = e0 + e1; t1 = e2 + e3; } else { t0 += e0 + e1; t1 += e2 + e3; }
      p[2 * j] = pack_bf16(e0, e1);
      p[2 * j + 1] = pack_bf16(e2, e3);
    }
    st.l0 = FIRST ? t0 : st.l0 + t0;
    st.l1 = FIRST ? t1 : st.l1 + t1;
  }
}
template <bool SP>
__device__ __forceinline__ bool finish_sums(RowSum& st) {
  const float a = quad_sum(st.l0), b = SP ? a : quad_sum(st.l1);
  st.l0 = __fdividef(1.f, a); st.l1 = __fdividef(1.f, b);
  return !(a >= SUM_LO && a <= SUM_HI && b >= SUM_LO && b <= SUM_HI);
}
template <bool SP, bool INIT, int SITE, bool COMMIT = true>
__device__ __forceinline__ void issue_qk(const Ctx& c, float (&s)[32], const uint32_t (&qs)[16], uint32_t dq, uint32_t dk) {
  uint64_t a = desc64(dq, dhi<SITE & 1>(dk)), b = desc64(dk, dhi<1 - (SITE & 1)>(dk));
  if (SP) {
    if (INIT) wgmma_qk_sp_init(s, qs[0], qs[1], qs[2], qs[3], b, 0, c.mqk); else wgmma_qk_sp(s, qs[0], qs[1], qs[2], qs[3], b, 0, c.mqk);
#pragma unroll
    for (int k = 1; k < 4; k++) { dadd(b, k == 2 ? 508 : 4); wgmma_qk_sp(s, qs[4 * k], qs[4 * k + 1], qs[4 * k + 2], qs[4 * k + 3], b, 1, c.mqk); }
  } else {
    if (INIT) wgmma_qk_init(s, a, b, 0); else wgmma_qk(s, a, b, 0);
#pragma unroll
    for (int k = 1; k < 8; k++) { dadd(a, k == 4 ? 506 : 2); dadd(b, k == 4 ? 506 : 2); wgmma_qk(s, a, b, 1); }
  }
  if (COMMIT) wg_commit();
}
template <bool SP, bool ACC, int SITE, bool SPLIT = false>
__device__ __forceinline__ void issue_pv(const Ctx& c, float (&o)[64], const uint32_t (&p)[SP ? 8 : 16], uint32_t dv) {
  uint64_t b = desc64(dv, dhi<SITE & 1>(dv));
  if constexpr (SP) {
    if (ACC) wgmma_pv_sp(o, p[0], p[1], p[2], p[3], b, 1, c.mpv); else wgmma_pv_sp_init(o, p[0], p[1], p[2], p[3], b, 0, c.mpv);
    if (SPLIT) wg_commit();
    dadd(b, 256);
    wgmma_pv_sp(o, p[4], p[5], p[6], p[7], b, 1, c.mpv);
  } else {
    if (ACC) wgmma_pv(o, p[0], p[1], p[2], p[3], b, 1); else wgmma_pv_init(o, p[0], p[1], p[2], p[3], b, 0);
#pragma unroll
    for (int k = 1; k < 4; k++) { dadd(b, 128); wgmma_pv(o, p[4 * k], p[4 * k + 1], p[4 * k + 2], p[4 * k + 3], b, 1); }
  }
  wg_commit();
}
__device__ __forceinline__ void pack_rows(const float (&o)[64], float sc, uint32_t (&q)[32]) {
#pragma unroll
  for (int j = 0; j < 32; j++) q[j] = pack_bf16(o[2 * j] * sc, o[2 * j + 1] * sc);
}
__device__ __forceinline__ void stage_rows(const Ctx& c, uint32_t tile_addr, const uint32_t (&q)[32]) {
  const int lane = c.lane, mi = lane >> 3, r8 = lane & 7;
  const uint32_t row_addr = tile_addr + (16 * c.warp + (mi & 1) * 8 + r8) * 128;
#pragma unroll
  for (int jj = 0; jj < 8; jj++)
    stsm4(row_addr + (jj >> 2) * 8192 + (((((2 * jj) & 7) + (mi >> 1)) ^ r8) << 4), q[4 * jj], q[4 * jj + 1], q[4 * jj + 2], q[4 * jj + 3]);
}
__device__ __forceinline__ void stage_rows(const Ctx& c, uint32_t tile_addr, const float (&o)[64], float sc) {
  uint32_t q[32];
  pack_rows(o, sc, q);
  stage_rows(c, tile_addr, q);
}
template <int SITE>
__device__ __forceinline__ void issue_qk_rs(float (&s)[32], uint32_t (&q)[32], uint32_t dk) {
  uint64_t b = desc64(dk, dhi<SITE>(dk));
  reg_fence(q);
  wg_fence();
  wgmma_qk_rs_init(s, q[0], q[1], q[2], q[3], b, 0);
#pragma unroll
  for (int k = 1; k < 8; k++) { dadd(b, k == 4 ? 506 : 2); wgmma_qk_rs(s, q[4 * k], q[4 * k + 1], q[4 * k + 2], q[4 * k + 3], b, 1); }
  wg_commit();
}

__device__ __forceinline__ void redo_tile(const Ctx& c, uint32_t q_addr, uint32_t half, const __nv_bfloat16* kp, const __nv_bfloat16* vp,
                                          uint32_t item, int row) {
  float o[64];
  const int lane = lane_now(), g = lane >> 2, cc = lane & 3, mi = lane >> 3, r8 = lane & 7;
  const uint32_t qa = q_addr + (half == 4096 ? 8 * c.warp + r8 : 16 * c.warp + (mi & 1) * 8 + r8) * 128, swz = half == 4096 ? q3_swz(r8) : r8;
  const uint32_t* kq = reinterpret_cast<const uint32_t*>(kp + g * DH) + cc;
  const unsigned short* vq = reinterpret_cast<const unsigned short*>(vp + 2 * cc * DH) + g;
  float m0 = -INFINITY, m1 = -INFINITY, l0 = 0.f, l1 = 0.f;
#pragma unroll
  for (int i = 0; i < 64; i++) o[i] = 0.f;
#pragma unroll 1
  for (int kb = 0; kb < SK / 16; kb++) {
    float z[8] = {0.f, 0.f, 0.f, 0.f, 0.f, 0.f, 0.f, 0.f};
#pragma unroll 2
    for (int kk = 0; kk < 8; kk++) {
      uint32_t a0, a1, a2, a3;
      ldsm4(qa + (kk >> 2) * half + ((((kk & 3) * 2 + (mi >> 1)) ^ swz) << 4), a0, a1, a2, a3);
      const uint32_t* kr = kq + kb * (16 * DH / 2) + kk * 8;
      mma16816(z[0], z[1], z[2], z[3], a0, a1, a2, a3, __ldg(kr), __ldg(kr + 4));
      mma16816(z[4], z[5], z[6], z[7], a0, a1, a2, a3, __ldg(kr + 8 * DH / 2), __ldg(kr + 8 * DH / 2 + 4));
    }
    const float n0 = fmaxf(m0, quad_max(fmaxf(fmaxf(z[0], z[1]), fmaxf(z[4], z[5]))));
    const float n1 = fmaxf(m1, quad_max(fmaxf(fmaxf(z[2], z[3]), fmaxf(z[6], z[7]))));
    const float al0 = ex2(m0 - n0), al1 = ex2(m1 - n1);
    m0 = n0; m1 = n1;
#pragma unroll
    for (int i = 0; i < 8; i++) z[i] = ex2(z[i] - ((i & 2) ? n1 : n0));
    l0 = l0 * al0 + (z[0] + z[1]) + (z[4] + z[5]);
    l1 = l1 * al1 + (z[2] + z[3]) + (z[6] + z[7]);
    const uint32_t a0 = pack_bf16(z[0], z[1]), a1 = pack_bf16(z[2], z[3]), a2 = pack_bf16(z[4], z[5]), a3 = pack_bf16(z[6], z[7]);
    const unsigned short* vr = vq + kb * (16 * DH);
#pragma unroll
    for (int nb = 0; nb < 16; nb++) {
      o[4 * nb] *= al0; o[4 * nb + 1] *= al0; o[4 * nb + 2] *= al1; o[4 * nb + 3] *= al1;
      const uint32_t b0 = __ldg(vr + nb * 8) | ((uint32_t)__ldg(vr + nb * 8 + DH) << 16);
      const uint32_t b1 = __ldg(vr + nb * 8 + 8 * DH) | ((uint32_t)__ldg(vr + nb * 8 + 9 * DH) << 16);
      mma16816(o[4 * nb], o[4 * nb + 1], o[4 * nb + 2], o[4 * nb + 3], a0, a1, a2, a3, b0, b1);
    }
  }
  const char* p = o_addr(item, row, lane);
  o_emit<0>(p, o, __fdividef(1.f, quad_sum(l0)));
  o_emit<1>(half == 4096 ? p : p + 1024, o, __fdividef(1.f, quad_sum(l1)));
}

template <bool SPA, bool SPB, int SITE, int ID>
__device__ __forceinline__ void batch(const Ctx& c, float (&s)[32], const uint32_t (&qs)[16], uint32_t dq, uint32_t dk, float (&ob)[64],
                                      uint32_t (&pb)[SPB ? 8 : 16], uint32_t dv) {
  if constexpr (SPA) {
    reg_fence(pb);
    wg_fence();
    issue_pv<SPB, true, ID>(c, ob, pb, dv);
    issue_qk<SPA, false, ID>(c, s, qs, dq, dk);
  } else {
    constexpr bool EARLY = ((QK_EARLY_MASK >> (SITE + (SPB ? 2 : 0))) & 1) != 0;
    if (!EARLY) reg_fence(pb);
    wg_fence();
    issue_qk<SPA, false, ID, !SPB>(c, s, qs, dq, dk);
    if (EARLY) { reg_fence(pb); wg_fence(); }
    issue_pv<SPB, true, ID, SPB>(c, ob, pb, dv);
  }
}

template <bool SP0>
__device__ __forceinline__ bool attention(Ctx& c, Ring& r, int unit, uint32_t& d, const float (&a0)[64], float (&o0)[64], float (&o1)[64],
                                          RowSum& st0, RowSum& st1, const Slots& h) {
  constexpr bool SP1 = false;
  if (SP0) { c.mqk = META_QK + (d >> 28); c.mpv = META_PV + (d >> 28); asm volatile("" : "+r"(c.mqk), "+r"(c.mpv)); }
  if (SP0) c.src = (c.lane & 28) | ((c.lane & 1) << 1) | ((c.lane >> 1) & 1);
  float s[32];
  uint32_t p0[SP0 ? 8 : 16], p1[16];
  const uint32_t q0a = c.sb + QBUF_OFF + (SP0 ? 3 : 0) * 16384, q1a = c.sb + QBUF_OFF + (SP0 ? 2 : 1) * 16384;
  const uint32_t dq0 = sdesc(q0a, 0), dq1 = sdesc(q1a, 0);
  uint32_t sk = acquire(c, r, true), sv, sn;
  uint32_t qs[16];
  float s1[32];
  if (SP0) {
    stage_t3<0, true>(c, a0, SM_C);
    stage_t2<0>(c, a0, SM_C);
    proj_end<1>(c, o0, h);
    stage_t3<1, true>(c, o0, SM_C);
    stage_t2<1>(c, o0, SM_C);
    fence_async_smem();
    bar_sync(1, LAG_BAR & 30 ? 256 : 128);
    const int g = c.lane >> 2, cc = c.lane & 3;
    const uint32_t qa = q0a + (8 * c.warp + g) * 128 + (cc & 1) * 8;
#pragma unroll
    for (int k = 0; k < 8; k++)
      asm volatile("ld.shared.v2.u32 {%0, %1}, [%2];" : "=r"(qs[2 * k]), "=r"(qs[2 * k + 1])
                   : "r"(qa + (k >> 2) * 4096 + ((((k & 3) * 2 + (cc >> 1)) ^ q3_swz(g)) << 4)) : "memory");
    TRACE(unit, 2);
    wg_fence();
    issue_qk<SP1, true, 1>(c, s1, qs, dq1, sdesc(c.sb + sk * SLOT, 0));
    reg_fence(qs);
    wg_fence();
    issue_qk<SP0, true, 0>(c, s, qs, dq0, sdesc(c.sb + sk * SLOT, 0));
    const bool have = peek<2>(c, r);
    wg_wait<1>();
    reg_fence(s1);
    exps<SP1, true>(c, s1, p1, st1);
    sched_fence<11>(sk, p1);
    acquire2(c, r, sv, sn, __all_sync(0xffffffffu, have));
    wg_wait<0>();
    wg_fence();
    issue_pv<SP1, false, 1>(c, o1, p1, sdesc(c.sb + sv * SLOT, 8192));
    if (LAG_BAR & 1) asm volatile("bar.arrive 4, 256;" ::: "memory");
    sched_fence<12>(sk, s);
    release(c, sk);
    sk = sn;
    exps<SP0, true>(c, s, p0, st0);
    reg_fence(p0);
    wg_fence();
    issue_pv<SP0, false, 0>(c, o0, p0, sdesc(c.sb + sv * SLOT, 8192));
    issue_qk<SP0, true, 2>(c, s, qs, dq0, sdesc(c.sb + sk * SLOT, 0));
    sn = acquire(c, r);
    wg_wait<0>();
    reg_fence(s);
  } else {
    uint32_t q0[32], q1[32];
    pack_rows(a0, SM_C, q0);
    stage_rows(c, q0a, q0);
    proj_end<0>(c, o1, h);
    TRACE(unit, 2);
    float sc = SM_C;
    issue_qk_rs<0>(s, q0, sdesc(c.sb + sk * SLOT, 0));
    sched_fence<0>(sk, sc);
    if (LAG_BAR & 8) asm volatile("bar.arrive 1, 256;" ::: "memory");
    pack_rows(o1, sc, q1);
    stage_rows(c, q1a, q1);
    if (LAG_BAR & 4) asm volatile("bar.arrive 1, 256;" ::: "memory");
    issue_qk_rs<1>(s1, q1, sdesc(c.sb + sk * SLOT, 0));
    if (LAG_BAR & 2) asm volatile("bar.arrive 1, 256;" ::: "memory");
    bool have = peek<2>(c, r);
    wg_wait<1>();
    reg_fence(s);
    exps<SP0, true>(c, s, p0, st0);
    sched_fence<1>(sk, p0);
    if (LAG_BAR & 16) asm volatile("bar.arrive 1, 256;" ::: "memory");
    acquire2(c, r, sv, sn, __all_sync(0xffffffffu, have));
    wg_wait<0>();
    reg_fence(s1);
    fence_async_smem();
    __syncwarp();
    wg_fence();
    issue_qk<SP0, false, 2>(c, s, qs, dq0, sdesc(c.sb + sn * SLOT, 0));
    issue_pv<SP0, false, 0>(c, o0, p0, sdesc(c.sb + sv * SLOT, 8192));
    sched_fence<2>(sk, s1);
    release(c, sk);
    have = peek<1>(c, r);
    sk = sn;
    exps<SP1, true>(c, s1, p1, st1);
    reg_fence(p1);
    wg_fence();
    issue_pv<SP1, false, 1>(c, o1, p1, sdesc(c.sb + sv * SLOT, 8192));
    sn = acquire(c, r, __all_sync(0xffffffffu, have));
    if (LAG_BAR & 1) bar_sync(4, 256);
    wg_wait<1>();
    reg_fence(s);
  }
  TRACE_IN(unit, 4);
  T2C(unit, 51);
#pragma unroll 1
  for (int j = 1; j < 15; j++) {
    const uint32_t sv_prev = sv, sk_prev = sk;
    sv = sn;
    const uint32_t dv = sdesc(c.sb + sv * SLOT, 8192);
    reg_fence(p0);
    exps<SP0, false>(c, s, p0, st0);
    batch<SP1, SP0, 0, 3>(c, s, qs, dq1, sdesc(c.sb + sk * SLOT, 0), o0, p0, dv);
    sk = acquire(c, r);
    wg_wait<1>();
    reg_fence(s); reg_fence(p1);
    release(c, sv_prev); release(c, sk_prev);
    exps<SP1, false>(c, s, p1, st1);
    batch<SP0, SP1, 1, 4>(c, s, qs, dq0, sdesc(c.sb + sk * SLOT, 0), o1, p1, dv);
    sn = acquire(c, r);
    if (SP0) wg_wait<0>(); else wg_wait<1>();
    reg_fence(s);
  }
  TRACE_IN(unit, 5);
  T2C(unit + 1, 52);
  const uint32_t sv_prev = sv;
  sv = sn;
  const uint32_t dv = sdesc(c.sb + sv * SLOT, 8192);
  reg_fence(p0);
  exps<SP0, false>(c, s, p0, st0);
  batch<SP1, SP0, 0, 5>(c, s, qs, dq1, sdesc(c.sb + sk * SLOT, 0), o0, p0, dv);
  asm volatile("ld.volatile.shared.u32 %0, [%1];" : "=r"(d) : "r"(c.sb + DESC_OFF + ((unit + 1) & 3) * 4) : "memory");
  const bool have = peek<2 + SP0>(c, r);
  wg_wait<1>();
  reg_fence(s); reg_fence(p1);
  release(c, sv_prev); release(c, sk);
  exps<SP1, false>(c, s, p1, st1);
  reg_fence(p1);
  wg_fence();
  issue_pv<SP1, true, 2>(c, o1, p1, dv);
  if (SP0) sched_fence<6>(sk, st0.l0, st1.l0, st1.l1); else sched_fence<5>(sk, st0.l0, st0.l1, st1.l0, st1.l1);
  c.lane = c.lane0 + (sk >> 5);
  const bool bad = finish_sums<SP0>(st0) | finish_sums<SP1>(st1);
  uint32_t any;
  asm volatile("{\n.reg .pred p, q;\nsetp.ne.u32 p, %1, 0;\nbar.red.or.pred q, %2, 128, p;\nselp.u32 %0, 1, 0, q;\n}"
               : "=r"(any) : "r"((uint32_t)bad), "n"(2 + SP0) : "memory");
  any = __any_sync(0xffffffffu, any);
  d = __shfl_sync(0xffffffffu, d, 0);
  if (d < (2u << 30) && !__all_sync(0xffffffffu, have)) { Ring t = r; Slots u; begin_acquire<SP0>(c, t, u, true); }
  wg_wait<0>();
  reg_fence(o0); reg_fence(o1);
  release(c, sv);
  return any;
}

template <int WG>
__device__ __forceinline__ void consumer(Ctx c, const __nv_bfloat16* const* kv) {
  asm volatile("setmaxnreg.inc.sync.aligned.u32 %0;" ::"n"(WG ? REG_C : 504 - REG_C - REG_P));
  c.wg = WG;
  Ring r{0, 0, 0};
  float a0[64], a1[64], o1[64];
  Slots h;
  RowSum inv0, inv1;
  uint32_t d = c_sched.queue[blockIdx.x] * 1025, dc = 0, sw;
  int i = 0, nq;
begin:
  sw = d & (1u << 30);
  proj_begin<WG>(c, r, a0, h, true, sw);
  proj_half<WG, true, 1>(c, a1, h.w, h.x, sw);
  nq = 0;
#pragma unroll
  for (int k = 0; k < 64; k++) asm volatile("" : "=f"(o1[k]));
  asm volatile("" : "=f"(inv1.l0), "=f"(inv1.l1));
  while (true) {
    TRACE(i, 0); TRACE(i, 6);
    proj_main<WG>(c, r, a0, a1, h, d >> 30 ? ((d >> 16) & 63) + 1 : DM / 64, sw, i, dc, nq, o1, inv1);
    dc = d;
    TRACE(i, 1);
    if (d >> 30) goto out_tile;
    if (WG ? attention<WG>(c, r, i, d, a0, a1, o1, inv0, inv1, h) : attention<WG>(c, r, i, d, a0, o1, a1, inv1, inv0, h)) goto redo;
    if (d >= (2u << 30)) break;
    sw = d & (1u << 30);
    proj_begin<WG>(c, r, a0, h, false, sw);
    release_q<WG>(c);
    if (WG) sched_fence<8>(h.w, inv0.l0); else sched_fence<7>(h.w, inv0.l0, inv0.l1);
    o_first<WG>(c, dc, a1, inv0);
    sched_fence<9>(h.w, inv1.l0);
    proj_half<WG, true, 1>(c, a1, h.w, h.x, sw);
    nq = O_STEPS;
    TRACE(i, 3); TRACE(i, 7);
    i++;
  }
  release_q<WG>(c);
  o_first<WG>(c, dc, a1, inv0);
#pragma unroll
  for (int k = 1; k <= O_STEPS; k++) o_second<WG>(c, dc, k, o1, inv1);
next:
  TRACE(i, 3); TRACE(i, 7);
  if ((d >> 30) != 2) {
    i++;
    r.uniform();
    goto begin;
  }
  trace_dump(c);
  return;
out_tile:
  proj_end<WG>(c, a1, h);
  if (((d >> 28) & 3) == 2) {
    const int lane = c.lane, mi = lane >> 3, r8 = lane & 7;
    const uint32_t off = c.sb + (WG ? stage_off(c) : (16 * c.warp + (mi & 1) * 8 + r8) * 128);
#pragma unroll 1
    for (int k = (d >> 5) & 3; k > 0; k--) {
      uint32_t s0, s1;
      if (WG) { acquire2(c, r, s0, s1); release(c, s0); release(c, s1); }
#pragma unroll
      for (int t = 0; t < 2; t++) {
        const uint32_t sp = acquire(c, r), base = off + sp * SLOT;
        if (WG) {
#pragma unroll
          for (int jj = 0; jj < (t ? 2 : 4); jj++) {
            add16<true>(base + jj * 2048, &a0[(t * 4 + jj) * 8]);
            add16<true>(base + jj * 2048 + (t ? 4096 : 8192), &a1[(t * 4 + jj) * 8]);
          }
        } else {
#pragma unroll
          for (int jj = 0; jj < 8; jj++) add16<false>(base + (jj >> 2) * 8192 + (((((2 * jj) & 7) + (mi >> 1)) ^ r8) << 4), t ? &a1[jj * 8] : &a0[jj * 8]);
        }
        release(c, sp);
      }
      if (!WG) { acquire2(c, r, s0, s1); release(c, s0); release(c, s1); }
    }
  }
  if (WG) { stage_t3<0, false>(c, a0, 1.f); stage_t3<1, false>(c, a1, 1.f); }
  else stage_rows(c, c.sb + QBUF_OFF, a0, 1.f);
  staged(c, 0);
  if (WG) { stage_t2<0>(c, a0, 1.f); stage_t2<1>(c, a1, 1.f); }
  else stage_rows(c, c.sb + QBUF_OFF + 16384, a1, 1.f);
  staged(c, 1);
  d = get_desc(c, i + 1);
  TRACE(i, 2);
  goto next;
redo:
  {
    const size_t hoff = (size_t)(dc & 511) * (SK * DH);
    const int br = (dc >> 9) & 1;
#pragma unroll 1
    for (int part = 0; part < 2; part++) {
      const int t = WG ? 3 - part : part;
      redo_tile(c, c.sb + QBUF_OFF + t * 16384, t == 3 ? 4096 : 8192, kv[br] + hoff, kv[2 + br] + hoff, dc,
                t * 64 + (t == 3 ? 8 : 16) * c.warp);
    }
    o_done(c);
    release_q<WG>(c);
  }
  goto next;
}

template <bool SIMPLE>
__global__ void __launch_bounds__(384, 1) mha_fused_kernel(const __grid_constant__ Params P) {
  extern __shared__ __align__(1024) uint8_t smem_raw[];
  const uint32_t sbase = smem_u32(smem_raw);
  const int tid = threadIdx.x;
  const int wg = __shfl_sync(0xffffffffu, tid >> 7, 0);
  const int warp = __shfl_sync(0xffffffffu, (tid >> 5) & 3, 0);
  const int lane = tid & 31;
  const int cta = blockIdx.x;

  if (tid == 0) T3(15, 0);
  if ((sbase & 1023) || sbase + SMEM_BYTES > 0x40000) __trap();
  {
    const int wi = wg * 4 + warp;
    asm volatile(ELECT "prefetch.tensormap [%0];\n}" ::"l"(&P.x[0][0] + wi) : "memory");
#pragma unroll
    for (int k = 0; k < 3; k++) {
      const int b = min(BAR_OFF + (wi * 3 + k) * 8, BAR_GO);
      asm volatile(ELECT "mbarrier.init.shared::cta.b64 [%0], %1;\n}"
                   ::"r"(sbase + b), "r"(b < BAR_EMPTY || b >= BAR_DESC ? 1 : b >= BAR_STG && b < BAR_OUT ? 4 : 8) : "memory");
    }
    asm volatile("fence.mbarrier_init.release.cluster;" ::: "memory");
    if (wi < 6) asm volatile(ELECT "prefetch.tensormap [%0];\n}" ::"l"(&P.x[0][0] + 12 + wi) : "memory");
  }
  __syncthreads();

  if (wg == 2) {
    asm volatile("setmaxnreg.dec.sync.aligned.u32 %0;" ::"n"(REG_P));
    if (warp == 1) {
      const uint32_t qb = sbase + QBUF_OFF;
      const uint32_t ep = __shfl_sync(0xffffffffu, *(volatile unsigned*)&g_epoch + 1, 0);
      asm volatile("st.volatile.shared.u32 [%0], %1;" ::"r"(sbase + EPOCH_OFF), "r"(ep) : "memory");
      uint32_t dc = c_sched.queue[cta], qi = 0, piece = 0, na = 0;
      TTAIL(0);
      for (int i = 0; (dc >> 30) != 2; i++) {
        if (!(dc >> 30) && o_reuse<SIMPLE>((dc >> 5) & 31)) {
          const unsigned* rd = &g_rd[0][0] + ((dc & 1023) >> 2) - OR * 8;
          for (uint32_t n = 0; !__all_sync(0xffffffffu, reached(rd, ep * 5)); __nanosleep(300)) if (++n > (1u << 22)) __trap();
        }
        mbar_wait_w(sbase + BAR_GO, i & 1);
        if (piece == 0) {
          if (lane == 0) {
            qi = atomicAdd(&g_next, 1);
            if (qi == (SIMPLE ? Q_ALL : Q_RANGES) - 1) { g_next = 0; g_epoch = ep; }
          }
          qi = __shfl_sync(0xffffffffu, qi, 0) + (SIMPLE ? gridDim.x : NCTA);
        }
        uint32_t d;
        if (qi < (SIMPLE ? Q_ALL : Q_RANGES)) { d = c_sched.queue[qi]; if (d & 0x8000) d ^= (1u << 30) | (63u << 16) | 0x8000; else d |= o_slot<SIMPLE>(d >> 5) << 15 | (d & 31) << 10; }
        else if (SIMPLE) d = 2u << 30;
        else { const uint32_t e = qi - Q_RANGES, g = e / 5; d = c_sched.piece[g][piece++] | (e - g * 5) << 8; }
        if ((d >> 30) == 1) {
          const uint32_t k0 = (d >> 22) & 63;
          const uint32_t run = __ffs(__ballot_sync(0xffffffffu, !reached(&g_cnt[d & 31][lane & 7], ep * 4)) & (0xffu << (k0 >> 3))) - 1;
          if (run <= (k0 + ((d >> 16) & 63)) >> 3) d |= run <= (k0 + O_STEPS) >> 3 ? (2u << 30) | 128 : 128;
        }
        asm volatile("st.volatile.shared.u32 [%0], %1;" ::"r"(sbase + EPOCH_OFF + 4), "r"(qi) : "memory");
        asm volatile("st.volatile.shared.u32 [%0], %1;" ::"r"(sbase + DESC_OFF + ((i + 1) & 3) * 4), "r"(d) : "memory");
        __syncwarp();
        mbar_arrive_warp(sbase + BAR_DESC);
        const Work w = decode(dc);
        dc = d;
        if (w.kind == 0) {
          mbar_wait_w(sbase + BAR_OUT, na++ & 1);
          TTAIL(1);
          T3(i, 0); T3(i, 1);
          asm volatile(ELECT "red.release.gpu.global.add.u32 [%0], 1;\n}" ::"l"(&g_cnt[w.beta][w.sub >> 2]) : "memory");
          T3(i, 2);
          TTAIL(2);
          continue;
        }
        const bool fin = w.mode != 1;
        uint64_t pol, pol2;
        asm volatile("createpolicy.fractional.L2::evict_first.b64 %0, 1.0;" : "=l"(pol));
        asm volatile("createpolicy.fractional.L2::evict_normal.b64 %0, 1.0;" : "=l"(pol2));
        if (!fin) pol = pol2;
        const CUtensorMap* m = fin ? P.out_st : P.o_st;
        const int c1 = fin ? (w.beta & 15) * SQ : 0;
        const int c2 = fin ? (w.beta >> 4) * (DM / 64) + w.sub * 2 : NBETA * 64 + w.range * 2;
        uint32_t pend = 0;
#pragma unroll 1
        for (int e = 0; e < 4; e++) {
          const int t = (ST_ORDER >> (4 * e)) & 3;
          mbar_wait_w(sbase + BAR_STG + (t ^ (t >> 1)) * 8, (i - na) & 1);
          tma_st3_hint_w(m + (t == 3), qb + t * 16384, 0, c1 + t * 64, c2, pol);
          bulk_commit();
          T2P(i + 1, 5, 2 * e);
          if (pend) {
            bulk_wait_read<1>();
            mbar_arrive8_w(pend);
            T2P(i + 1, 5, 2 * e - 1);
          }
          pend = sbase + BAR_EMPTY + (NS + t) * 8;
          if ((ST_NOW >> e) & 1) {
            bulk_wait_read<0>();
            mbar_arrive8_w(pend);
            pend = 0;
            T2P(i + 1, 5, 2 * e + 1);
          }
        }
        if (w.beta < N_EARLY) asm volatile(ELECT "red.relaxed.gpu.global.add.u32 [%0], 1;\n}" ::"l"(&g_rd[w.beta][7]) : "memory");
        T3(i, 0);
        if (piece >= 2) TTAIL(piece * 2 - 1);
        asm volatile("cp.async.bulk.wait_group 0;" ::: "memory");
        T3(i, 1);
        if (w.mode == 1) asm volatile(ELECT "st.release.gpu.global.u32 [%0], %1;\n}" ::"l"(&g_flag[w.range]), "r"(ep) : "memory");
        T3(i, 2);
        if (piece >= 2) TTAIL(piece * 2);
      }
      T3(15, 1);
    } else
    if (warp == 0) {
      Ring r{0, 1, 3};
      uint32_t d = c_sched.queue[cta];
      for (int i = 0;; i++) {
        const Work w = decode(d);
        if (w.kind == 2) break;
        const CUtensorMap* m = w.kind == 0 ? &P.wq[w.beta >> 4] : &P.wo[w.beta >> 4];
        for (int ks = 0; ks < w.nsteps; ks++) {
          const uint32_t b = borrow(ks, w.nsteps);
          r.next_if(b == 2);
          const uint32_t bar = sbase + BAR_FULL + r.slot * 8;
          mbar_wait_w(bar + (BAR_EMPTY - BAR_FULL), r.phase);
          if (w.kind == 0) tma_ld3_w(sbase + r.slot * SLOT, m, 0, ks * 64, w.sub * 2, bar, 16384);
          else tma_ld_wo_w(sbase + r.slot * SLOT, m, w.sub * 128, (w.k0 + ks) * 2, bar);
          if (w.kind != 0 && w.beta < N_EARLY && (ks & 7) == 5 && ks > 5)
            asm volatile(ELECT "red.relaxed.gpu.global.add.u32 [%0], 1;\n}" ::"l"(&g_rd[w.beta][(ks >> 3) - 1]) : "memory");
          if (ks < 10) T2P(i, 2, ks);
          if (w.kind != 0 && ks == max(w.nsteps - GO_P, 4)) mbar_arrive_warp(sbase + BAR_GO);
          r.next(); r.next_if(b == 2);
        }
        if (w.kind == 0) {
          r.phase ^= 1; r.next(); r.next();
        } else if (w.mode == 2) {
          for (int k = 1; k <= ((d >> 5) & 3); k++) {
            if (k == 1) TTAIL(9);
            wait_count(&g_flag[w.range + 5 * k], lds(sbase + EPOCH_OFF));
            TTAIL(10);
            asm volatile("fence.proxy.async.global;" ::: "memory");
#pragma unroll 1
            for (int t = 0; t < 4; t++) {
              mbar_wait_w(sbase + BAR_EMPTY + r.slot * 8, r.phase);
              tma_ld3_w(sbase + r.slot * SLOT, &P.o_st[t == 3], 0, t * 64, NBETA * 64 + (w.range + 5 * k) * 2, sbase + BAR_FULL + r.slot * 8,
                        t == 3 ? 8192 : 16384);
              r.next();
            }
          }
        }
        mbar_wait_w(sbase + BAR_DESC, i & 1);
        d = __shfl_sync(0xffffffffu, lds(sbase + DESC_OFF + ((i + 1) & 3) * 4), 0);
      }
    } else {
      const int hi = warp - 2;
      uint64_t pol_stream;
      asm volatile("createpolicy.fractional.L2::evict_first.b64 %0, 1.0;" : "=l"(pol_stream));
      Ring r{0, 1, 3};
      uint32_t d = c_sched.queue[cta];
      for (int i = 0;; i++) {
        const Work w = decode(d);
        if (w.kind == 2) break;
        const CUtensorMap* m = w.kind == 0 ? &P.x[hi][w.beta >> 4] : &P.o_ld[hi];
        int c1 = (w.kind == 0 ? (w.beta & 15) : o_slot<SIMPLE>(w.beta) * 64 + w.k0) * SQ + hi * 128;
        int k_wait = -1;
        if (w.kind != 0) {
          if (d & 128) k_wait = d >= (3u << 30) ? 0 : 8 - (w.k0 & 7);
          asm volatile("fence.proxy.async.global;" ::: "memory");
        }
        const int rank = i == 0 ? cta : __shfl_sync(0xffffffffu, lds(sbase + EPOCH_OFF + 4), 0) - NCTA;
        for (int ks = 0; ks < w.nsteps; ks++) {
          if (ks == k_wait) {
            wait_count(&g_cnt[d & 31][(w.k0 + ks) >> 3], lds(sbase + EPOCH_OFF) * 4);
            asm volatile("fence.proxy.async.global;" ::: "memory");
            k_wait = ((w.k0 + ks) | 7) + 1 - w.k0;
          }
          const uint32_t b = borrow(ks, w.nsteps);
          const bool bo = b != 2;
          r.next_if(hi && !bo); r.next_if(hi && !bo);
          const uint32_t sl = bo ? NS + (b ^ (3 * hi)) : r.slot, bar = sbase + BAR_FULL + sl * 8;
          mbar_wait_w(bar + (BAR_EMPTY - BAR_FULL), bo ? (r.xp >> b) & 1 : r.phase);
          if (w.kind == 0) tma_ld2_w(sbase + sl * SLOT, m, ks * 64, c1, bar, (hi ? 96 * 128 : 128 * 128));
          else { tma_ld2_hint_w(sbase + sl * SLOT, m, 0, c1, bar, hi ? 96 * 128 : 128 * 128, pol_stream); c1 += SQ; }
          if (i == 0 && ks == PF_STEP)
            asm volatile(ELECT "cp.async.bulk.prefetch.tensor.3d.L2.global.L2::cache_hint [%0, {0, %1, 0}], %2;\n}"
                         ::"l"(&P.kv[hi][0]), "r"(d * SK), "l"(pol_stream) : "memory");
          if (ks < 10) T2P(i, 3 + hi, ks);
          if (!hi && w.kind != 0 && !(ks & 3)) TCLK(i * 16 + (ks >> 2));
          r.next(); r.next_if(!hi && !bo); r.next_if(!hi && !bo);
          r.xp ^= 1 << b;
        }
        r.xp ^= 3;
        if (w.kind == 0) {
          m = &P.kv[hi][w.beta >> 4];
          c1 = (d & 511) * SK;
          for (int j = 0; j < 16; j++) {
            if (hi) r.next();
            const uint32_t bar = sbase + BAR_FULL + r.slot * 8;
            const bool tight = i < KV_WIN_UNITS && j < KV_WIN_TILES + ((KV_WIN_RAMP * rank) >> 5);
            {
              const int s2 = (int)r.slot - (tight ? 2 : KV_WIN_D);
              mbar_wait_w(sbase + BAR_FULL + (s2 < 0 ? s2 + NS : s2) * 8, s2 < 0 ? r.phase : r.phase ^ 1);
            }
            if (j == 15 && hi) mbar_wait_w(sbase + BAR_DESC, i & 1);
            mbar_wait_w(sbase + BAR_EMPTY + r.slot * 8, r.phase);
            tma_ld3_hint_w(sbase + r.slot * SLOT, m, 0, c1, 0, bar, pol_stream);
            T2P(i, 3 + hi, 16 + j);
            if (!hi) TCLK(i * 16 + j);
            if (j == 14 && !hi) mbar_arrive_warp(sbase + BAR_GO);
            c1 += 64;
            r.next();
            if (!hi) r.next();
          }
        }
        mbar_wait_w(sbase + BAR_DESC, i & 1);
        d = __shfl_sync(0xffffffffu, lds(sbase + DESC_OFF + ((i + 1) & 3) * 4), 0);
      }
    }
  } else {
    Ctx c;
    c.sb = sbase; c.wg = wg; c.warp = warp; c.src = 0; c.mqk = 0; c.mpv = 0; c.lead = lane == 0; c.lane0 = c.lane = lane;
    if (wg == 0) consumer<0>(c, P.kp); else consumer<1>(c, P.kp);
  }
}

typedef CUresult (*EncodeFn)(CUtensorMap*, CUtensorMapDataType, cuuint32_t, void*, const cuuint64_t*, const cuuint64_t*,
                             const cuuint32_t*, const cuuint32_t*, CUtensorMapInterleave, CUtensorMapSwizzle,
                             CUtensorMapL2promotion, CUtensorMapFloatOOBfill);

void make_map(EncodeFn enc, CUtensorMap* m, const void* ptr, int rank, const cuuint64_t* dims, const cuuint64_t* strides,
              const cuuint32_t* box, int promo = 2, CUtensorMapSwizzle swz = CU_TENSOR_MAP_SWIZZLE_128B) {
  cuuint32_t es[5] = {1, 1, 1, 1, 1};
  enc(m, CU_TENSOR_MAP_DATA_TYPE_BFLOAT16, rank, const_cast<void*>(ptr), dims, strides, box, es,
      CU_TENSOR_MAP_INTERLEAVE_NONE, swz, promo == 2 ? CU_TENSOR_MAP_L2_PROMOTION_L2_256B : promo == 1 ? CU_TENSOR_MAP_L2_PROMOTION_L2_128B : CU_TENSOR_MAP_L2_PROMOTION_NONE,
      CU_TENSOR_MAP_FLOAT_OOB_FILL_NONE);
}

}

extern "C" void kernel_launch(void* const* d_in, const int* in_sizes, int n_in, void* d_out, int out_size) {
  (void)in_sizes; (void)n_in; (void)out_size;
  static EncodeFn enc = nullptr;
  static void* o_ptr = nullptr;
  static int n_sm = 0;
  if (!enc) {
    void* fn = nullptr;
    cudaDriverEntryPointQueryResult qr;
    cudaGetDriverEntryPoint("cuTensorMapEncodeTiled", &fn, cudaEnableDefault, &qr);
    enc = (EncodeFn)fn;
    cudaGetSymbolAddress(&o_ptr, g_o);
    cudaFuncSetAttribute(mha_fused_kernel<false>, cudaFuncAttributeMaxDynamicSharedMemorySize, SMEM_BYTES);
    cudaFuncSetAttribute(mha_fused_kernel<true>, cudaFuncAttributeMaxDynamicSharedMemorySize, SMEM_BYTES);
    int dev = 0;
    cudaGetDevice(&dev);
    cudaDeviceGetAttribute(&n_sm, cudaDevAttrMultiProcessorCount, dev);
  }
  Params P;
  for (int br = 0; br < 2; br++) {
    const void* x = d_in[br * 5 + 0]; const void* kc = d_in[br * 5 + 1]; const void* vc = d_in[br * 5 + 2];
    const void* wq = d_in[br * 5 + 3]; const void* wo = d_in[br * 5 + 4];
    { cuuint64_t d[2] = {DM, (cuuint64_t)NB * SQ}, s[1] = {DM * 2}; cuuint32_t b[2] = {64, 128}, b2[2] = {64, 96};
      make_map(enc, &P.x[0][br], x, 2, d, s, b, PR_X); make_map(enc, &P.x[1][br], x, 2, d, s, b2, PR_X); }
    { cuuint64_t d[3] = {64, DM, HD / 64}, s[2] = {HD * 2, 128}; cuuint32_t b[3] = {64, 64, 2}; make_map(enc, &P.wq[br], wq, 3, d, s, b, PR_W); }
    { cuuint64_t d[5] = {DM, 2, 4, 4, HD / 32}, s[4] = {DM * 2, 8 * DM * 2, 2 * DM * 2, 32 * DM * 2}; cuuint32_t b[5] = {64, 2, 4, 4, 2};
      make_map(enc, &P.wo[br], wo, 5, d, s, b, PR_W); }
    { cuuint64_t d[3] = {64, (cuuint64_t)NB * NH * SK, 2}, s[2] = {DH * 2, 128}; cuuint32_t b[3] = {64, 64, 2};
      make_map(enc, &P.kv[0][br], kc, 3, d, s, b, PR_KV); make_map(enc, &P.kv[1][br], vc, 3, d, s, b, PR_KV); }
    P.kp[br] = (const __nv_bfloat16*)kc; P.vp[br] = (const __nv_bfloat16*)vc;

  }
  { cuuint64_t d[2] = {64, (cuuint64_t)NBETA * 64 * SQ}, s[1] = {128}; cuuint32_t b[2] = {64, 128}, b2[2] = {64, 96};
    make_map(enc, &P.o_ld[0], o_ptr, 2, d, s, b, 2, CU_TENSOR_MAP_SWIZZLE_NONE); make_map(enc, &P.o_ld[1], o_ptr, 2, d, s, b2, 2, CU_TENSOR_MAP_SWIZZLE_NONE); }
  { cuuint64_t d[3] = {64, SQ, O_BLOCKS}, s[2] = {128, SQ * 128}; cuuint32_t b[3] = {64, 64, 2}, b2[3] = {64, 32, 2};
    make_map(enc, &P.o_st[0], o_ptr, 3, d, s, b); make_map(enc, &P.o_st[1], o_ptr, 3, d, s, b2); }
  { cuuint64_t d[3] = {64, (cuuint64_t)NB * SQ, 2 * DM / 64}, s[2] = {2 * DM * 2, 128}; cuuint32_t b[3] = {64, 64, 2}, b2[3] = {64, 32, 2};
    make_map(enc, &P.out_st[0], d_out, 3, d, s, b); make_map(enc, &P.out_st[1], d_out, 3, d, s, b2); }
  if (n_sm >= NCTA) mha_fused_kernel<false><<<NCTA, 384, SMEM_BYTES>>>(P);
  else mha_fused_kernel<true><<<n_sm, 384, SMEM_BYTES>>>(P);
}
```

```cpp
#include <cuda_runtime.h>
#include <cuda_bf16.h>
#include <cuda.h>
#include <stdint.h>
#include <stdlib.h>

namespace {

__device__ __forceinline__ void wgmma_proj(float (&d)[64], uint64_t da, uint64_t db, int scaleD) {
  asm volatile("{\n.reg .pred p;\nsetp.ne.b32 p, %66, 0;\n"
      "wgmma.mma_async.sync.aligned.m64n128k16.f32.bf16.bf16 "
      "{%0, %1, %2, %3, %4, %5, %6, %7, %8, %9, %10, %11, %12, %13, %14, %15, %16, %17, %18, %19, %20, %21, %22, %23, %24, %25, %26, %27, %28, %29, %30, "
      "%31, %32, %33, %34, %35, %36, %37, %38, %39, %40, %41, %42, %43, %44, %45, %46, %47, %48, %49, %50, %51, %52, %53, %54, %55, %56, %57, %58, %59, %60, "
      "%61, %62, %63}, "
      "%64, %65, p, 1, 1, 0, 1;\n}\n"
      : "+f"(d[0]), "+f"(d[1]), "+f"(d[2]), "+f"(d[3]), "+f"(d[4]), "+f"(d[5]), "+f"(d[6]), "+f"(d[7]), "+f"(d[8]), "+f"(d[9]), "+f"(d[10]), "+f"(d[11]),
        "+f"(d[12]), "+f"(d[13]), "+f"(d[14]), "+f"(d[15]), "+f"(d[16]), "+f"(d[17]), "+f"(d[18]), "+f"(d[19]), "+f"(d[20]), "+f"(d[21]), "+f"(d[22]),
        "+f"(d[23]), "+f"(d[24]), "+f"(d[25]), "+f"(d[26]), "+f"(d[27]), "+f"(d[28]), "+f"(d[29]), "+f"(d[30]), "+f"(d[31]), "+f"(d[32]), "+f"(d[33]),
        "+f"(d[34]), "+f"(d[35]), "+f"(d[36]), "+f"(d[37]), "+f"(d[38]), "+f"(d[39]), "+f"(d[40]), "+f"(d[41]), "+f"(d[42]), "+f"(d[43]), "+f"(d[44]),
        "+f"(d[45]), "+f"(d[46]), "+f"(d[47]), "+f"(d[48]), "+f"(d[49]), "+f"(d[50]), "+f"(d[51]), "+f"(d[52]), "+f"(d[53]), "+f"(d[54]), "+f"(d[55]),
        "+f"(d[56]), "+f"(d[57]), "+f"(d[58]), "+f"(d[59]), "+f"(d[60]), "+f"(d[61]), "+f"(d[62]), "+f"(d[63])
      : "l"(da), "l"(db), "r"(scaleD));
}
__device__ __forceinline__ void wgmma_proj96(float (&d)[64], uint64_t da, uint64_t db, int scaleD) {
  asm volatile("{\n.reg .pred p;\nsetp.ne.b32 p, %50, 0;\n"
      "wgmma.mma_async.sync.aligned.m64n96k16.f32.bf16.bf16 "
      "{%0, %1, %2, %3, %4, %5, %6, %7, %8, %9, %10, %11, %12, %13, %14, %15, %16, %17, %18, %19, %20, %21, %22, %23, %24, %25, %26, %27, %28, %29, %30, "
      "%31, %32, %33, %34, %35, %36, %37, %38, %39, %40, %41, %42, %43, %44, %45, %46, %47}, "
      "%48, %49, p, 1, 1, 1, 0;\n}\n"
      : "+f"(d[0]), "+f"(d[1]), "+f"(d[2]), "+f"(d[3]), "+f"(d[4]), "+f"(d[5]), "+f"(d[6]), "+f"(d[7]), "+f"(d[8]), "+f"(d[9]), "+f"(d[10]), "+f"(d[11]),
        "+f"(d[12]), "+f"(d[13]), "+f"(d[14]), "+f"(d[15]), "+f"(d[16]), "+f"(d[17]), "+f"(d[18]), "+f"(d[19]), "+f"(d[20]), "+f"(d[21]), "+f"(d[22]),
        "+f"(d[23]), "+f"(d[24]), "+f"(d[25]), "+f"(d[26]), "+f"(d[27]), "+f"(d[28]), "+f"(d[29]), "+f"(d[30]), "+f"(d[31]), "+f"(d[32]), "+f"(d[33]),
        "+f"(d[34]), "+f"(d[35]), "+f"(d[36]), "+f"(d[37]), "+f"(d[38]), "+f"(d[39]), "+f"(d[40]), "+f"(d[41]), "+f"(d[42]), "+f"(d[43]), "+f"(d[44]),
        "+f"(d[45]), "+f"(d[46]), "+f"(d[47])
      : "l"(da), "l"(db), "r"(scaleD));
}
__device__ __forceinline__ void wgmma_qk(float (&d)[32], uint64_t da, uint64_t db, int scaleD) {
  asm volatile("{\n.reg .pred p;\nsetp.ne.b32 p, %34, 0;\n"
      "wgmma.mma_async.sync.aligned.m64n64k16.f32.bf16.bf16 "
      "{%0, %1, %2, %3, %4, %5, %6, %7, %8, %9, %10, %11, %12, %13, %14, %15, %16, %17, %18, %19, %20, %21, %22, %23, %24, %25, %26, %27, %28, %29, %30, "
      "%31}, "
      "%32, %33, p, 1, 1, 0, 0;\n}\n"
      : "+f"(d[0]), "+f"(d[1]), "+f"(d[2]), "+f"(d[3]), "+f"(d[4]), "+f"(d[5]), "+f"(d[6]), "+f"(d[7]), "+f"(d[8]), "+f"(d[9]), "+f"(d[10]), "+f"(d[11]),
        "+f"(d[12]), "+f"(d[13]), "+f"(d[14]), "+f"(d[15]), "+f"(d[16]), "+f"(d[17]), "+f"(d[18]), "+f"(d[19]), "+f"(d[20]), "+f"(d[21]), "+f"(d[22]),
        "+f"(d[23]), "+f"(d[24]), "+f"(d[25]), "+f"(d[26]), "+f"(d[27]), "+f"(d[28]), "+f"(d[29]), "+f"(d[30]), "+f"(d[31])
      : "l"(da), "l"(db), "r"(scaleD));
}
__device__ __forceinline__ void wgmma_qk_rs(float (&d)[32], uint32_t a0, uint32_t a1, uint32_t a2, uint32_t a3, uint64_t db, int scaleD) {
  asm volatile("{\n.reg .pred p;\nsetp.ne.b32 p, %37, 0;\n"
      "wgmma.mma_async.sync.aligned.m64n64k16.f32.bf16.bf16 "
      "{%0, %1, %2, %3, %4, %5, %6, %7, %8, %9, %10, %11, %12, %13, %14, %15, %16, %17, %18, %19, %20, %21, %22, %23, %24, %25, %26, %27, %28, %29, %30, "
      "%31}, "
      "{%32, %33, %34, %35}, %36, p, 1, 1, 0;\n}\n"
      : "+f"(d[0]), "+f"(d[1]), "+f"(d[2]), "+f"(d[3]), "+f"(d[4]), "+f"(d[5]), "+f"(d[6]), "+f"(d[7]), "+f"(d[8]), "+f"(d[9]), "+f"(d[10]), "+f"(d[11]),
        "+f"(d[12]), "+f"(d[13]), "+f"(d[14]), "+f"(d[15]), "+f"(d[16]), "+f"(d[17]), "+f"(d[18]), "+f"(d[19]), "+f"(d[20]), "+f"(d[21]), "+f"(d[22]),
        "+f"(d[23]), "+f"(d[24]), "+f"(d[25]), "+f"(d[26]), "+f"(d[27]), "+f"(d[28]), "+f"(d[29]), "+f"(d[30]), "+f"(d[31])
      : "r"(a0), "r"(a1), "r"(a2), "r"(a3), "l"(db), "r"(scaleD));
}
__device__ __forceinline__ void wgmma_pv(float (&d)[64], uint32_t a0, uint32_t a1, uint32_t a2, uint32_t a3, uint64_t db, int scaleD) {
  asm volatile("{\n.reg .pred p;\nsetp.ne.b32 p, %69, 0;\n"
      "wgmma.mma_async.sync.aligned.m64n128k16.f32.bf16.bf16 "
      "{%0, %1, %2, %3, %4, %5, %6, %7, %8, %9, %10, %11, %12, %13, %14, %15, %16, %17, %18, %19, %20, %21, %22, %23, %24, %25, %26, %27, %28, %29, %30, "
      "%31, %32, %33, %34, %35, %36, %37, %38, %39, %40, %41, %42, %43, %44, %45, %46, %47, %48, %49, %50, %51, %52, %53, %54, %55, %56, %57, %58, %59, %60, "
      "%61, %62, %63}, "
      "{%64, %65, %66, %67}, %68, p, 1, 1, 1;\n}\n"
      : "+f"(d[0]), "+f"(d[1]), "+f"(d[2]), "+f"(d[3]), "+f"(d[4]), "+f"(d[5]), "+f"(d[6]), "+f"(d[7]), "+f"(d[8]), "+f"(d[9]), "+f"(d[10]), "+f"(d[11]),
        "+f"(d[12]), "+f"(d[13]), "+f"(d[14]), "+f"(d[15]), "+f"(d[16]), "+f"(d[17]), "+f"(d[18]), "+f"(d[19]), "+f"(d[20]), "+f"(d[21]), "+f"(d[22]),
        "+f"(d[23]), "+f"(d[24]), "+f"(d[25]), "+f"(d[26]), "+f"(d[27]), "+f"(d[28]), "+f"(d[29]), "+f"(d[30]), "+f"(d[31]), "+f"(d[32]), "+f"(d[33]),
        "+f"(d[34]), "+f"(d[35]), "+f"(d[36]), "+f"(d[37]), "+f"(d[38]), "+f"(d[39]), "+f"(d[40]), "+f"(d[41]), "+f"(d[42]), "+f"(d[43]), "+f"(d[44]),
        "+f"(d[45]), "+f"(d[46]), "+f"(d[47]), "+f"(d[48]), "+f"(d[49]), "+f"(d[50]), "+f"(d[51]), "+f"(d[52]), "+f"(d[53]), "+f"(d[54]), "+f"(d[55]),
        "+f"(d[56]), "+f"(d[57]), "+f"(d[58]), "+f"(d[59]), "+f"(d[60]), "+f"(d[61]), "+f"(d[62]), "+f"(d[63])
      : "r"(a0), "r"(a1), "r"(a2), "r"(a3), "l"(db), "r"(scaleD));
}
__device__ __forceinline__ void wgmma_qk_sp(float (&d)[32], uint32_t a0, uint32_t a1, uint32_t a2, uint32_t a3, uint64_t db, int scaleD, uint32_t meta) {
  asm volatile("{\n.reg .pred p;\nsetp.ne.b32 p, %37, 0;\n"
      "wgmma.mma_async.sp.sync.aligned.m64n64k32.f32.bf16.bf16 "
      "{%0, %1, %2, %3, %4, %5, %6, %7, %8, %9, %10, %11, %12, %13, %14, %15, %16, %17, %18, %19, %20, %21, %22, %23, %24, %25, %26, %27, %28, %29, %30, "
      "%31}, "
      "{%32, %33, %34, %35}, %36, %38, 0, p, 1, 1, 0;\n}\n"
      : "+f"(d[0]), "+f"(d[1]), "+f"(d[2]), "+f"(d[3]), "+f"(d[4]), "+f"(d[5]), "+f"(d[6]), "+f"(d[7]), "+f"(d[8]), "+f"(d[9]), "+f"(d[10]), "+f"(d[11]),
        "+f"(d[12]), "+f"(d[13]), "+f"(d[14]), "+f"(d[15]), "+f"(d[16]), "+f"(d[17]), "+f"(d[18]), "+f"(d[19]), "+f"(d[20]), "+f"(d[21]), "+f"(d[22]),
        "+f"(d[23]), "+f"(d[24]), "+f"(d[25]), "+f"(d[26]), "+f"(d[27]), "+f"(d[28]), "+f"(d[29]), "+f"(d[30]), "+f"(d[31])
      : "r"(a0), "r"(a1), "r"(a2), "r"(a3), "l"(db), "r"(scaleD), "r"(meta));
}
__device__ __forceinline__ void wgmma_pv_sp(float (&d)[64], uint32_t a0, uint32_t a1, uint32_t a2, uint32_t a3, uint64_t db, int scaleD, uint32_t meta) {
  asm volatile("{\n.reg .pred p;\nsetp.ne.b32 p, %69, 0;\n"
      "wgmma.mma_async.sp.sync.aligned.m64n128k32.f32.bf16.bf16 "
      "{%0, %1, %2, %3, %4, %5, %6, %7, %8, %9, %10, %11, %12, %13, %14, %15, %16, %17, %18, %19, %20, %21, %22, %23, %24, %25, %26, %27, %28, %29, %30, "
      "%31, %32, %33, %34, %35, %36, %37, %38, %39, %40, %41, %42, %43, %44, %45, %46, %47, %48, %49, %50, %51, %52, %53, %54, %55, %56, %57, %58, %59, %60, "
      "%61, %62, %63}, "
      "{%64, %65, %66, %67}, %68, %70, 0, p, 1, 1, 1;\n}\n"
      : "+f"(d[0]), "+f"(d[1]), "+f"(d[2]), "+f"(d[3]), "+f"(d[4]), "+f"(d[5]), "+f"(d[6]), "+f"(d[7]), "+f"(d[8]), "+f"(d[9]), "+f"(d[10]), "+f"(d[11]),
        "+f"(d[12]), "+f"(d[13]), "+f"(d[14]), "+f"(d[15]), "+f"(d[16]), "+f"(d[17]), "+f"(d[18]), "+f"(d[19]), "+f"(d[20]), "+f"(d[21]), "+f"(d[22]),
        "+f"(d[23]), "+f"(d[24]), "+f"(d[25]), "+f"(d[26]), "+f"(d[27]), "+f"(d[28]), "+f"(d[29]), "+f"(d[30]), "+f"(d[31]), "+f"(d[32]), "+f"(d[33]),
        "+f"(d[34]), "+f"(d[35]), "+f"(d[36]), "+f"(d[37]), "+f"(d[38]), "+f"(d[39]), "+f"(d[40]), "+f"(d[41]), "+f"(d[42]), "+f"(d[43]), "+f"(d[44]),
        "+f"(d[45]), "+f"(d[46]), "+f"(d[47]), "+f"(d[48]), "+f"(d[49]), "+f"(d[50]), "+f"(d[51]), "+f"(d[52]), "+f"(d[53]), "+f"(d[54]), "+f"(d[55]),
        "+f"(d[56]), "+f"(d[57]), "+f"(d[58]), "+f"(d[59]), "+f"(d[60]), "+f"(d[61]), "+f"(d[62]), "+f"(d[63])
      : "r"(a0), "r"(a1), "r"(a2), "r"(a3), "l"(db), "r"(scaleD), "r"(meta));
}
__device__ __forceinline__ void wgmma_proj_init(float (&d)[64], uint64_t da, uint64_t db, int scaleD) {
  asm volatile("{\n.reg .pred p;\nsetp.ne.b32 p, %66, 0;\n"
      "wgmma.mma_async.sync.aligned.m64n128k16.f32.bf16.bf16 "
      "{%0, %1, %2, %3, %4, %5, %6, %7, %8, %9, %10, %11, %12, %13, %14, %15, %16, %17, %18, %19, %20, %21, %22, %23, %24, %25, %26, %27, %28, %29, %30, "
      "%31, %32, %33, %34, %35, %36, %37, %38, %39, %40, %41, %42, %43, %44, %45, %46, %47, %48, %49, %50, %51, %52, %53, %54, %55, %56, %57, %58, %59, %60, "
      "%61, %62, %63}, "
      "%64, %65, p, 1, 1, 0, 1;\n}\n"
      : "=f"(d[0]), "=f"(d[1]), "=f"(d[2]), "=f"(d[3]), "=f"(d[4]), "=f"(d[5]), "=f"(d[6]), "=f"(d[7]), "=f"(d[8]), "=f"(d[9]), "=f"(d[10]), "=f"(d[11]),
        "=f"(d[12]), "=f"(d[13]), "=f"(d[14]), "=f"(d[15]), "=f"(d[16]), "=f"(d[17]), "=f"(d[18]), "=f"(d[19]), "=f"(d[20]), "=f"(d[21]), "=f"(d[22]),
        "=f"(d[23]), "=f"(d[24]), "=f"(d[25]), "=f"(d[26]), "=f"(d[27]), "=f"(d[28]), "=f"(d[29]), "=f"(d[30]), "=f"(d[31]), "=f"(d[32]), "=f"(d[33]),
        "=f"(d[34]), "=f"(d[35]), "=f"(d[36]), "=f"(d[37]), "=f"(d[38]), "=f"(d[39]), "=f"(d[40]), "=f"(d[41]), "=f"(d[42]), "=f"(d[43]), "=f"(d[44]),
        "=f"(d[45]), "=f"(d[46]), "=f"(d[47]), "=f"(d[48]), "=f"(d[49]), "=f"(d[50]), "=f"(d[51]), "=f"(d[52]), "=f"(d[53]), "=f"(d[54]), "=f"(d[55]),
        "=f"(d[56]), "=f"(d[57]), "=f"(d[58]), "=f"(d[59]), "=f"(d[60]), "=f"(d[61]), "=f"(d[62]), "=f"(d[63])
      : "l"(da), "l"(db), "r"(scaleD));
}
__device__ __forceinline__ void wgmma_proj96_init(float (&d)[64], uint64_t da, uint64_t db, int scaleD) {
  asm volatile("{\n.reg .pred p;\nsetp.ne.b32 p, %50, 0;\n"
      "wgmma.mma_async.sync.aligned.m64n96k16.f32.bf16.bf16 "
      "{%0, %1, %2, %3, %4, %5, %6, %7, %8, %9, %10, %11, %12, %13, %14, %15, %16, %17, %18, %19, %20, %21, %22, %23, %24, %25, %26, %27, %28, %29, %30, "
      "%31, %32, %33, %34, %35, %36, %37, %38, %39, %40, %41, %42, %43, %44, %45, %46, %47}, "
      "%48, %49, p, 1, 1, 1, 0;\n}\n"
      : "=f"(d[0]), "=f"(d[1]), "=f"(d[2]), "=f"(d[3]), "=f"(d[4]), "=f"(d[5]), "=f"(d[6]), "=f"(d[7]), "=f"(d[8]), "=f"(d[9]), "=f"(d[10]), "=f"(d[11]),
        "=f"(d[12]), "=f"(d[13]), "=f"(d[14]), "=f"(d[15]), "=f"(d[16]), "=f"(d[17]), "=f"(d[18]), "=f"(d[19]), "=f"(d[20]), "=f"(d[21]), "=f"(d[22]),
        "=f"(d[23]), "=f"(d[24]), "=f"(d[25]), "=f"(d[26]), "=f"(d[27]), "=f"(d[28]), "=f"(d[29]), "=f"(d[30]), "=f"(d[31]), "=f"(d[32]), "=f"(d[33]),
        "=f"(d[34]), "=f"(d[35]), "=f"(d[36]), "=f"(d[37]), "=f"(d[38]), "=f"(d[39]), "=f"(d[40]), "=f"(d[41]), "=f"(d[42]), "=f"(d[43]), "=f"(d[44]),
        "=f"(d[45]), "=f"(d[46]), "=f"(d[47])
      : "l"(da), "l"(db), "r"(scaleD));
}
__device__ __forceinline__ void wgmma_qk_init(float (&d)[32], uint64_t da, uint64_t db, int scaleD) {
  asm volatile("{\n.reg .pred p;\nsetp.ne.b32 p, %34, 0;\n"
      "wgmma.mma_async.sync.aligned.m64n64k16.f32.bf16.bf16 "
      "{%0, %1, %2, %3, %4, %5, %6, %7, %8, %9, %10, %11, %12, %13, %14, %15, %16, %17, %18, %19, %20, %21, %22, %23, %24, %25, %26, %27, %28, %29, %30, "
      "%31}, "
      "%32, %33, p, 1, 1, 0, 0;\n}\n"
      : "=f"(d[0]), "=f"(d[1]), "=f"(d[2]), "=f"(d[3]), "=f"(d[4]), "=f"(d[5]), "=f"(d[6]), "=f"(d[7]), "=f"(d[8]), "=f"(d[9]), "=f"(d[10]), "=f"(d[11]),
        "=f"(d[12]), "=f"(d[13]), "=f"(d[14]), "=f"(d[15]), "=f"(d[16]), "=f"(d[17]), "=f"(d[18]), "=f"(d[19]), "=f"(d[20]), "=f"(d[21]), "=f"(d[22]),
        "=f"(d[23]), "=f"(d[24]), "=f"(d[25]), "=f"(d[26]), "=f"(d[27]), "=f"(d[28]), "=f"(d[29]), "=f"(d[30]), "=f"(d[31])
      : "l"(da), "l"(db), "r"(scaleD));
}
__device__ __forceinline__ void wgmma_qk_rs_init(float (&d)[32], uint32_t a0, uint32_t a1, uint32_t a2, uint32_t a3, uint64_t db, int scaleD) {
  asm volatile("{\n.reg .pred p;\nsetp.ne.b32 p, %37, 0;\n"
      "wgmma.mma_async.sync.aligned.m64n64k16.f32.bf16.bf16 "
      "{%0, %1, %2, %3, %4, %5, %6, %7, %8, %9, %10, %11, %12, %13, %14, %15, %16, %17, %18, %19, %20, %21, %22, %23, %24, %25, %26, %27, %28, %29, %30, "
      "%31}, "
      "{%32, %33, %34, %35}, %36, p, 1, 1, 0;\n}\n"
      : "=f"(d[0]), "=f"(d[1]), "=f"(d[2]), "=f"(d[3]), "=f"(d[4]), "=f"(d[5]), "=f"(d[6]), "=f"(d[7]), "=f"(d[8]), "=f"(d[9]), "=f"(d[10]), "=f"(d[11]),
        "=f"(d[12]), "=f"(d[13]), "=f"(d[14]), "=f"(d[15]), "=f"(d[16]), "=f"(d[17]), "=f"(d[18]), "=f"(d[19]), "=f"(d[20]), "=f"(d[21]), "=f"(d[22]),
        "=f"(d[23]), "=f"(d[24]), "=f"(d[25]), "=f"(d[26]), "=f"(d[27]), "=f"(d[28]), "=f"(d[29]), "=f"(d[30]), "=f"(d[31])
      : "r"(a0), "r"(a1), "r"(a2), "r"(a3), "l"(db), "r"(scaleD));
}
__device__ __forceinline__ void wgmma_pv_init(float (&d)[64], uint32_t a0, uint32_t a1, uint32_t a2, uint32_t a3, uint64_t db, int scaleD) {
  asm volatile("{\n.reg .pred p;\nsetp.ne.b32 p, %69, 0;\n"
      "wgmma.mma_async.sync.aligned.m64n128k16.f32.bf16.bf16 "
      "{%0, %1, %2, %3, %4, %5, %6, %7, %8, %9, %10, %11, %12, %13, %14, %15, %16, %17, %18, %19, %20, %21, %22, %23, %24, %25, %26, %27, %28, %29, %30, "
      "%31, %32, %33, %34, %35, %36, %37, %38, %39, %40, %41, %42, %43, %44, %45, %46, %47, %48, %49, %50, %51, %52, %53, %54, %55, %56, %57, %58, %59, %60, "
      "%61, %62, %63}, "
      "{%64, %65, %66, %67}, %68, p, 1, 1, 1;\n}\n"
      : "=f"(d[0]), "=f"(d[1]), "=f"(d[2]), "=f"(d[3]), "=f"(d[4]), "=f"(d[5]), "=f"(d[6]), "=f"(d[7]), "=f"(d[8]), "=f"(d[9]), "=f"(d[10]), "=f"(d[11]),
        "=f"(d[12]), "=f"(d[13]), "=f"(d[14]), "=f"(d[15]), "=f"(d[16]), "=f"(d[17]), "=f"(d[18]), "=f"(d[19]), "=f"(d[20]), "=f"(d[21]), "=f"(d[22]),
        "=f"(d[23]), "=f"(d[24]), "=f"(d[25]), "=f"(d[26]), "=f"(d[27]), "=f"(d[28]), "=f"(d[29]), "=f"(d[30]), "=f"(d[31]), "=f"(d[32]), "=f"(d[33]),
        "=f"(d[34]), "=f"(d[35]), "=f"(d[36]), "=f"(d[37]), "=f"(d[38]), "=f"(d[39]), "=f"(d[40]), "=f"(d[41]), "=f"(d[42]), "=f"(d[43]), "=f"(d[44]),
        "=f"(d[45]), "=f"(d[46]), "=f"(d[47]), "=f"(d[48]), "=f"(d[49]), "=f"(d[50]), "=f"(d[51]), "=f"(d[52]), "=f"(d[53]), "=f"(d[54]), "=f"(d[55]),
        "=f"(d[56]), "=f"(d[57]), "=f"(d[58]), "=f"(d[59]), "=f"(d[60]), "=f"(d[61]), "=f"(d[62]), "=f"(d[63])
      : "r"(a0), "r"(a1), "r"(a2), "r"(a3), "l"(db), "r"(scaleD));
}
__device__ __forceinline__ void wgmma_qk_sp_init(float (&d)[32], uint32_t a0, uint32_t a1, uint32_t a2, uint32_t a3, uint64_t db, int scaleD, uint32_t meta) {
  asm volatile("{\n.reg .pred p;\nsetp.ne.b32 p, %37, 0;\n"
      "wgmma.mma_async.sp.sync.aligned.m64n64k32.f32.bf16.bf16 "
      "{%0, %1, %2, %3, %4, %5, %6, %7, %8, %9, %10, %11, %12, %13, %14, %15, %16, %17, %18, %19, %20, %21, %22, %23, %24, %25, %26, %27, %28, %29, %30, "
      "%31}, "
      "{%32, %33, %34, %35}, %36, %38, 0, p, 1, 1, 0;\n}\n"
      : "=f"(d[0]), "=f"(d[1]), "=f"(d[2]), "=f"(d[3]), "=f"(d[4]), "=f"(d[5]), "=f"(d[6]), "=f"(d[7]), "=f"(d[8]), "=f"(d[9]), "=f"(d[10]), "=f"(d[11]),
        "=f"(d[12]), "=f"(d[13]), "=f"(d[14]), "=f"(d[15]), "=f"(d[16]), "=f"(d[17]), "=f"(d[18]), "=f"(d[19]), "=f"(d[20]), "=f"(d[21]), "=f"(d[22]),
        "=f"(d[23]), "=f"(d[24]), "=f"(d[25]), "=f"(d[26]), "=f"(d[27]), "=f"(d[28]), "=f"(d[29]), "=f"(d[30]), "=f"(d[31])
      : "r"(a0), "r"(a1), "r"(a2), "r"(a3), "l"(db), "r"(scaleD), "r"(meta));
}
__device__ __forceinline__ void wgmma_pv_sp_init(float (&d)[64], uint32_t a0, uint32_t a1, uint32_t a2, uint32_t a3, uint64_t db, int scaleD, uint32_t meta) {
  asm volatile("{\n.reg .pred p;\nsetp.ne.b32 p, %69, 0;\n"
      "wgmma.mma_async.sp.sync.aligned.m64n128k32.f32.bf16.bf16 "
      "{%0, %1, %2, %3, %4, %5, %6, %7, %8, %9, %10, %11, %12, %13, %14, %15, %16, %17, %18, %19, %20, %21, %22, %23, %24, %25, %26, %27, %28, %29, %30, "
      "%31, %32, %33, %34, %35, %36, %37, %38, %39, %40, %41, %42, %43, %44, %45, %46, %47, %48, %49, %50, %51, %52, %53, %54, %55, %56, %57, %58, %59, %60, "
      "%61, %62, %63}, "
      "{%64, %65, %66, %67}, %68, %70, 0, p, 1, 1, 1;\n}\n"
      : "=f"(d[0]), "=f"(d[1]), "=f"(d[2]), "=f"(d[3]), "=f"(d[4]), "=f"(d[5]), "=f"(d[6]), "=f"(d[7]), "=f"(d[8]), "=f"(d[9]), "=f"(d[10]), "=f"(d[11]),
        "=f"(d[12]), "=f"(d[13]), "=f"(d[14]), "=f"(d[15]), "=f"(d[16]), "=f"(d[17]), "=f"(d[18]), "=f"(d[19]), "=f"(d[20]), "=f"(d[21]), "=f"(d[22]),
        "=f"(d[23]), "=f"(d[24]), "=f"(d[25]), "=f"(d[26]), "=f"(d[27]), "=f"(d[28]), "=f"(d[29]), "=f"(d[30]), "=f"(d[31]), "=f"(d[32]), "=f"(d[33]),
        "=f"(d[34]), "=f"(d[35]), "=f"(d[36]), "=f"(d[37]), "=f"(d[38]), "=f"(d[39]), "=f"(d[40]), "=f"(d[41]), "=f"(d[42]), "=f"(d[43]), "=f"(d[44]),
        "=f"(d[45]), "=f"(d[46]), "=f"(d[47]), "=f"(d[48]), "=f"(d[49]), "=f"(d[50]), "=f"(d[51]), "=f"(d[52]), "=f"(d[53]), "=f"(d[54]), "=f"(d[55]),
        "=f"(d[56]), "=f"(d[57]), "=f"(d[58]), "=f"(d[59]), "=f"(d[60]), "=f"(d[61]), "=f"(d[62]), "=f"(d[63])
      : "r"(a0), "r"(a1), "r"(a2), "r"(a3), "l"(db), "r"(scaleD), "r"(meta));
}

constexpr int NB = 16, SQ = 224, DM = 640, NH = 32, SK = 1024, DH = 128;
constexpr int HD = NH * DH;
constexpr int NBETA = 2 * NB;
constexpr int NCTA = 132;
constexpr int NS = 10;
constexpr int SLOT = 16384;
constexpr int QBUF_OFF = NS * SLOT;
constexpr int NSX = NS + 4;
constexpr int BAR_OFF = NSX * SLOT;
constexpr int BAR_FULL = BAR_OFF;
constexpr int BAR_EMPTY = BAR_OFF + 8 * NSX;
constexpr int BAR_STG = BAR_OFF + 16 * NSX;
constexpr int BAR_OUT = BAR_STG + 32;
constexpr int BAR_DESC = BAR_OUT + 8;
constexpr int BAR_GO = BAR_DESC + 8;
constexpr int DESC_OFF = BAR_GO + 8;
constexpr int EPOCH_OFF = DESC_OFF + 16;
constexpr int TRACE_OFF = EPOCH_OFF + 8;
constexpr int SMEM_BYTES = TRACE_OFF;
constexpr float SM_C = 0.08838834764831845f * 1.4426950408889634f;
constexpr float SUM_HI = 1099511627776.f, SUM_LO = 1.f / 1099511627776.f;
constexpr uint32_t META_QK = 0xEEEE4444u;
constexpr uint32_t META_PV = 0x44EEEE44u;

#define QK_EARLY_MASK 3
#define ST_ORDER 0x2310
#define LAG_BAR 5
#define ST_NOW 8
#define PF_STEP 5
#define KV_WIN_UNITS 2
#define KV_WIN_D 4
#define SF 0xfe1f
#define O_STEPS 4
#define KV_WIN_RAMP 4
#define PDEPTH 0
#define KV_WIN_TILES -2
#define PR_KV 2
#define PR_X 2
#define PR_W 2
#define REG_C 232
#define REG_P 40
#define GO_P 4
#define P_POS 216
#define OR 6
#define OR0 2
#define EARLY_BEGIN 0
#define B_LATE 23
#define H_LATE 24
#define KG 5
#define PK 44
#define EARLY_MASK 0x7fffu
#define PIECE_TABLE 0x5025601a,0x69996056,0x5030b812,0x6d4ab85f,0x501a381b,0x67a1383c,0x403f1017,0x80000000,0x5026a818,0x6ad4a83d,0x501d2013,0x695a2034,0x502ab01d,0x6c4eb032,0x50219015,0x6b139030,0x5022780f,0x6c4e7859,0x502b9810,0x80000000,0x50108819,0x689d8835,0x500f7016,0x68dc702f,0x50242814,0x80000000,0x5024081e,0x80000000,0x5022c81f,0x80000000,0x545f8019,0x80000000,0x66a54831,0x80000000,0x66e4303b,0x80000000,0x501d401c,0x80000000,0x67a11833,0x80000000,0x695a003e,0x80000000,0x50195011,0x80000000,0x54156816,0x80000000,0x58d1c01f,0x80000000,0x6999583a,0x80000000,0x69d8a038,0x80000000

struct Params {
  CUtensorMap x[2][2], wq[2], kv[2][2], wo[2];
  CUtensorMap o_ld[2], o_st[2], out_st[2];
  const __nv_bfloat16* kp[2];
  const __nv_bfloat16* vp[2];
};

constexpr int NPART = 32 * 5, O_BLOCKS = NBETA * 64 + 2 * NPART;
__device__ __align__(128) __nv_bfloat16 g_o[(size_t)O_BLOCKS * SQ * 64];
__device__ unsigned g_cnt[NBETA][8];
__device__ unsigned g_rd[NBETA][8];
__device__ unsigned g_epoch, g_next;
__device__ unsigned g_flag[NPART];

__device__ __forceinline__ uint32_t smem_u32(const void* p) { return (uint32_t)__cvta_generic_to_shared(p); }
__device__ __forceinline__ void mbar_arrive(uint32_t bar) {
  asm volatile("mbarrier.arrive.shared::cta.b64 _, [%0];" ::"r"(bar) : "memory");
}
__device__ __forceinline__ void mbar_arrive_warp(uint32_t bar) {
  asm volatile("{\n.reg .pred p;\nelect.sync _|p, 0xffffffff;\n@p mbarrier.arrive.shared::cta.b64 _, [%0];\n}" ::"r"(bar) : "memory");
}
__device__ __forceinline__ int lane_now() { int l; asm volatile("mov.u32 %0, %%laneid;" : "=r"(l)); return l; }
__device__ __forceinline__ bool mbar_try(uint32_t bar, uint32_t parity) {
  uint32_t ok;
  asm volatile("{\n.reg .pred p;\nmbarrier.try_wait.parity.shared::cta.b64 p, [%1], %2;\nselp.u32 %0, 1, 0, p;\n}"
               : "=r"(ok) : "r"(bar), "r"(parity) : "memory");
  return ok;
}
__device__ __forceinline__ bool mbar_test(uint32_t bar, uint32_t parity) {
  uint32_t ok;
  asm volatile("{\n.reg .pred p;\nmbarrier.test_wait.parity.shared::cta.b64 p, [%1], %2;\nselp.u32 %0, 1, 0, p;\n}"
               : "=r"(ok) : "r"(bar), "r"(parity) : "memory");
  return ok;
}
__device__ __forceinline__ void mbar_wait_w(uint32_t bar, uint32_t parity) {
  uint32_t n = 0;
  while (!__all_sync(0xffffffffu, mbar_try(bar, parity))) {
    if (++n > (1u << 22)) __trap();
  }
}
#define ELECT "{\n.reg .pred p;\nelect.sync _|p, 0xffffffff;\n@p "
__device__ __forceinline__ void tma_st3_hint_w(const CUtensorMap* m, uint32_t src, int c0, int c1, int c2, uint64_t pol) {
  asm volatile(ELECT "cp.async.bulk.tensor.3d.global.shared::cta.bulk_group.L2::cache_hint [%0, {%2, %3, %4}], [%1], %5;\n}"
               ::"l"(m), "r"(src), "r"(c0), "r"(c1), "r"(c2), "l"(pol) : "memory");
}
#define EXPECT(bar, bytes) "mbarrier.arrive.expect_tx.shared::cta.b64 _, [" bar "], " bytes ";\n@p "
__device__ __forceinline__ void tma_ld2_w(uint32_t dst, const CUtensorMap* m, int c0, int c1, uint32_t bar, uint32_t bytes) {
  asm volatile(ELECT EXPECT("%2", "%5") "cp.async.bulk.tensor.2d.shared::cluster.global.mbarrier::complete_tx::bytes [%0], [%1, {%3, %4}], [%2];\n}"
               ::"r"(dst), "l"(m), "r"(bar), "r"(c0), "r"(c1), "r"(bytes) : "memory");
}
__device__ __forceinline__ void tma_ld2_hint_w(uint32_t dst, const CUtensorMap* m, int c0, int c1, uint32_t bar, uint32_t bytes, uint64_t pol) {
  asm volatile(ELECT EXPECT("%2", "%6") "cp.async.bulk.tensor.2d.shared::cluster.global.mbarrier::complete_tx::bytes.L2::cache_hint"
               " [%0], [%1, {%3, %4}], [%2], %5;\n}"
               ::"r"(dst), "l"(m), "r"(bar), "r"(c0), "r"(c1), "l"(pol), "r"(bytes) : "memory");
}
__device__ __forceinline__ void tma_ld3_w(uint32_t dst, const CUtensorMap* m, int c0, int c1, int c2, uint32_t bar, uint32_t bytes) {
  asm volatile(ELECT EXPECT("%2", "%6") "cp.async.bulk.tensor.3d.shared::cluster.global.mbarrier::complete_tx::bytes [%0], [%1, {%3, %4, %5}], [%2];\n}"
               ::"r"(dst), "l"(m), "r"(bar), "r"(c0), "r"(c1), "r"(c2), "r"(bytes) : "memory");
}
__device__ __forceinline__ void tma_ld3_hint_w(uint32_t dst, const CUtensorMap* m, int c0, int c1, int c2, uint32_t bar, uint64_t pol) {
  asm volatile(ELECT EXPECT("%2", "16384") "cp.async.bulk.tensor.3d.shared::cluster.global.mbarrier::complete_tx::bytes.L2::cache_hint"
               " [%0], [%1, {%3, %4, %5}], [%2], %6;\n}"
               ::"r"(dst), "l"(m), "r"(bar), "r"(c0), "r"(c1), "r"(c2), "l"(pol) : "memory");
}
__device__ __forceinline__ void tma_ld_wo_w(uint32_t dst, const CUtensorMap* m, int col, int grp, uint32_t bar) {
  asm volatile(ELECT EXPECT("%2", "16384") "cp.async.bulk.tensor.5d.shared::cluster.global.mbarrier::complete_tx::bytes [%0], [%1, {%3, 0, 0, 0, %4}], [%2];\n"
               "@p cp.async.bulk.tensor.5d.shared::cluster.global.mbarrier::complete_tx::bytes [%5], [%1, {%6, 0, 0, 0, %4}], [%2];\n}"
               ::"r"(dst), "l"(m), "r"(bar), "r"(col), "r"(grp), "r"(dst + 8192), "r"(col + 64) : "memory");
}
__device__ __forceinline__ void mbar_arrive8_w(uint32_t bar) {
  asm volatile(ELECT "mbarrier.arrive.shared::cta.b64 _, [%0], 8;\n}" ::"r"(bar) : "memory");
}
__device__ __forceinline__ void bulk_commit() { asm volatile("cp.async.bulk.commit_group;" ::: "memory"); }
template <int N> __device__ __forceinline__ void bulk_wait_read() { asm volatile("cp.async.bulk.wait_group.read %0;" ::"n"(N) : "memory"); }
__device__ __forceinline__ void wg_fence() { asm volatile("wgmma.fence.sync.aligned;" ::: "memory"); }
__device__ __forceinline__ void wg_commit() { asm volatile("wgmma.commit_group.sync.aligned;" ::: "memory"); }
template <int N> __device__ __forceinline__ void wg_wait() { asm volatile("wgmma.wait_group.sync.aligned %0;" ::"n"(N) : "memory"); }
__device__ __forceinline__ void fence_async_smem() { asm volatile("fence.proxy.async.shared::cta;" ::: "memory"); }
__device__ __forceinline__ void bar_sync(int id, int n) { asm volatile("bar.sync %0, %1;" ::"r"(id), "r"(n) : "memory"); }
__device__ __forceinline__ void touch(float& a) { asm volatile("neg.f32 %0, %0;" : "+f"(a)); }
__device__ __forceinline__ void touch(uint32_t& a) { asm volatile("not.b32 %0, %0;" : "+r"(a)); }
template <typename T, int N> __device__ __forceinline__ void touch(T (&a)[N]) {
#pragma unroll
  for (int i = 0; i < N; i++) touch(a[i]);
}
template <int ID, typename... A> __device__ __forceinline__ void sched_fence(uint32_t x, A&... a) {
  if (!((SF >> ID) & 1)) return;
  asm volatile("" : "+r"(x)::"memory");
#pragma unroll 1
  for (; __builtin_expect(x >= 100 + ID, 0); x >>= 1) { (touch(a), ...); __nanosleep(x); }
}
template <int N> __device__ __forceinline__ void reg_fence(float (&a)[N]) {
#pragma unroll
  for (int i = 0; i < N; i++) asm volatile("" : "+f"(a[i])::"memory");
}
template <int N> __device__ __forceinline__ void reg_fence(uint32_t (&a)[N]) {
#pragma unroll
  for (int i = 0; i < N; i++) asm volatile("" : "+r"(a[i])::"memory");
}
__device__ __forceinline__ float ex2(float x) { float y; asm("ex2.approx.ftz.f32 %0, %1;" : "=f"(y) : "f"(x)); return y; }
__device__ __forceinline__ uint32_t pack_bf16(float lo, float hi) {
  uint32_t r; asm("cvt.rn.bf16x2.f32 %0, %1, %2;" : "=r"(r) : "f"(hi), "f"(lo)); return r;
}
__device__ __forceinline__ void stsm4(uint32_t a, uint32_t r0, uint32_t r1, uint32_t r2, uint32_t r3) {
  asm volatile("stmatrix.sync.aligned.m8n8.x4.shared.b16 [%0], {%1, %2, %3, %4};" ::"r"(a), "r"(r0), "r"(r1), "r"(r2), "r"(r3) : "memory");
}
__device__ __forceinline__ void stsm4t(uint32_t a, uint32_t r0, uint32_t r1, uint32_t r2, uint32_t r3) {
  asm volatile("stmatrix.sync.aligned.m8n8.x4.trans.shared.b16 [%0], {%1, %2, %3, %4};" ::"r"(a), "r"(r0), "r"(r1), "r"(r2), "r"(r3) : "memory");
}
__device__ __forceinline__ void ldsm4(uint32_t a, uint32_t& r0, uint32_t& r1, uint32_t& r2, uint32_t& r3) {
  asm volatile("ldmatrix.sync.aligned.m8n8.x4.shared.b16 {%0, %1, %2, %3}, [%4];" : "=r"(r0), "=r"(r1), "=r"(r2), "=r"(r3) : "r"(a) : "memory");
}
__device__ __forceinline__ void sts16(uint32_t a, uint32_t v) { asm volatile("st.shared.u16 [%0], %1;" ::"r"(a), "h"((uint16_t)v) : "memory"); }
__device__ __forceinline__ void mma16816(float& c0, float& c1, float& c2, float& c3, uint32_t a0, uint32_t a1, uint32_t a2, uint32_t a3,
                                         uint32_t b0, uint32_t b1) {
  asm volatile("mma.sync.aligned.m16n8k16.row.col.f32.bf16.bf16.f32 {%0, %1, %2, %3}, {%4, %5, %6, %7}, {%8, %9}, {%0, %1, %2, %3};"
               : "+f"(c0), "+f"(c1), "+f"(c2), "+f"(c3) : "r"(a0), "r"(a1), "r"(a2), "r"(a3), "r"(b0), "r"(b1));
}
__device__ __forceinline__ uint32_t sdesc(uint32_t addr, uint32_t lbo) { return (addr >> 4) + ((lbo >> 4) << 16); }
__device__ __forceinline__ uint64_t desc64(uint32_t lo, uint32_t hi) { uint64_t d; asm("mov.b64 %0, {%1, %2};" : "=l"(d) : "r"(lo), "r"(hi)); return d; }
__device__ __forceinline__ void dadd(uint64_t& d, uint32_t inc) {
  asm("{\n.reg .b32 l, h;\nmov.b64 {l, h}, %0;\nadd.u32 l, l, %1;\nmov.b64 %0, {l, h};\n}" : "+l"(d) : "r"(inc));
}

struct Ring {
  uint32_t slot, phase, xp;
  __device__ __forceinline__ void uniform() {
    slot = __shfl_sync(0xffffffffu, slot, 0); phase = __shfl_sync(0xffffffffu, phase, 0); xp = __shfl_sync(0xffffffffu, xp, 0);
  }
  __device__ __forceinline__ void next() { if (++slot == NS) { slot = 0; phase ^= 1; } }
  __device__ __forceinline__ void next_if(bool p) { slot += p; if (slot == NS) { slot = 0; phase ^= 1; } }
};
__device__ __forceinline__ uint32_t borrow(int ks, int n) {
  const int k = ks + 1;
  return k >= 4 && !(k & 2) && k < n ? k & 1 : 2;
}

constexpr uint32_t Q_RANGES = NBETA * NH + __builtin_popcount(EARLY_MASK) * 5, Q_ALL = NBETA * (NH + 5);
constexpr int NRANGE = NCTA / 5;
struct Work { int kind, mode, k0, nsteps, range, beta, sub; };
struct Sched { uint16_t queue[Q_ALL]; uint32_t piece[NRANGE + 1][4]; };
constexpr Sched make_sched() {
  Sched s{};
  int q = 0, a = 0;
  for (int t = 0, e = 0; a < NBETA * NH; t++) {
    for (; e < NBETA && 8 * e + PK <= t && a >= P_POS; e++)
      for (int col = 0; col < 5 && (EARLY_MASK >> e & 1); col++) s.queue[q++] = 0x8000 | col << 8 | e;
    for (int b = 0; b < NBETA; b++)
      for (int h = 0; h < NH; h++)
        if ((b >= B_LATE && h >= H_LATE ? 300 + b : 8 * b + KG * (h >> 2)) == t) { s.queue[q++] = b << 5 | h; a++; }
  }
  for (int b = 0; b < NBETA; b++)
    for (int col = 0; col < 5 && !(EARLY_MASK >> b & 1); col++) s.queue[q++] = 0x8000 | col << 8 | b;
  constexpr uint32_t T[NRANGE * 2] = {PIECE_TABLE};
  for (int g = 0; g <= NRANGE; g++)
    for (int n = 0; n < 4; n++) s.piece[g][n] = g < NRANGE && n < 2 ? T[2 * g + n] : 2u << 30;
  return s;
}
__constant__ Sched c_sched = make_sched();
constexpr int N_EARLY = __builtin_popcount(EARLY_MASK);
template <bool SIMPLE> __device__ __forceinline__ bool o_reuse(uint32_t b) { return !SIMPLE && b - (OR0 + OR) < N_EARLY - OR0; }
template <bool SIMPLE> __device__ __forceinline__ uint32_t o_slot(uint32_t b) { return o_reuse<SIMPLE>(b) ? OR0 + (b - OR0) % OR : b; }
__device__ __forceinline__ Work decode(uint32_t d) {
  Work w;
  w.kind = d >> 30; if (w.kind == 3) w.kind = 1;
  w.mode = (d >> 28) & 3; w.k0 = (d >> 22) & 63;
  if (w.kind == 0) { w.beta = (d >> 5) & 31; w.sub = d & 31; w.nsteps = DM / 64; }
  else { w.beta = d & 31; w.sub = (d >> 8) & 7; w.nsteps = ((d >> 16) & 63) + 1; }
  w.range = ((d >> 11) & 31) * 5 + w.sub;
  return w;
}

__device__ __forceinline__ bool reached(const unsigned* cnt, unsigned target) {
  unsigned v;
  asm volatile("ld.acquire.gpu.global.u32 %0, [%1];" : "=r"(v) : "l"(cnt) : "memory");
  return (int)(v - target) >= 0;
}
__device__ __forceinline__ void wait_count(const unsigned* cnt, unsigned target) {
  unsigned n = 0;
  while (!__all_sync(0xffffffffu, reached(cnt, target))) { if (++n > (1u << 24)) __trap(); }
}
__device__ __forceinline__ uint32_t lds(uint32_t a) { uint32_t v; asm volatile("ld.volatile.shared.u32 %0, [%1];" : "=r"(v) : "r"(a) : "memory"); return v; }

#define TRACE(u, e)
#define T3(u, e)
#define T2C(u, e)
#define T2P(u, r, e)
#define TTAIL(k)
#define TCLK(k)
#define TO -1
#define TRACE_O(k) if (TO == k) TRACE(i, 5)
#define TRACE_P(u, e)
#define TRACE_IN(u, e)

struct Ctx {
  uint32_t sb;
  int wg, warp;
  uint32_t mqk, mpv;
  bool lead;
  int lane0, lane;
  int src;
};
template <int N> __device__ __forceinline__ uint32_t dhi(uint32_t lo) { return 0x40000040u + (lo >> (26 + N)); }
__device__ __forceinline__ void release(const Ctx& c, uint32_t slot) {
  if (c.lead) mbar_arrive(c.sb + BAR_EMPTY + slot * 8);
}
__device__ __forceinline__ uint32_t acquire(const Ctx& c, Ring& r, bool have = false) {
  const uint32_t s = r.slot;
  if (!have) mbar_wait_w(c.sb + BAR_FULL + s * 8, r.phase);
  r.next();
  return s;
}
__device__ __forceinline__ void mbar_wait2_w(uint32_t b0, uint32_t p0, uint32_t b1, uint32_t p1) {
  uint32_t n = 0;
  while (!__all_sync(0xffffffffu, mbar_try(b0, p0) & mbar_try(b1, p1))) {
    if (++n > (1u << 22)) __trap();
  }
}
__device__ __forceinline__ void mbar_wait3_w(uint32_t b0, uint32_t p0, uint32_t b1, uint32_t p1, uint32_t b2, uint32_t p2) {
  uint32_t n = 0;
  while (!__all_sync(0xffffffffu, mbar_try(b0, p0) & mbar_try(b1, p1) & mbar_try(b2, p2))) {
    if (++n > (1u << 22)) __trap();
  }
}
__device__ __forceinline__ void acquire2(const Ctx& c, Ring& r, uint32_t& s0, uint32_t& s1, bool have = false) {
  const uint32_t p0 = r.phase;
  s0 = r.slot; r.next(); s1 = r.slot;
  if (!have) mbar_wait2_w(c.sb + BAR_FULL + s0 * 8, p0, c.sb + BAR_FULL + s1 * 8, r.phase);
  r.next();
}
template <int N>
__device__ __forceinline__ bool peek(const Ctx& c, Ring r) {
  bool ok = true;
#pragma unroll
  for (int k = 0; k < N; k++) { ok &= mbar_test(c.sb + BAR_FULL + r.slot * 8, r.phase); r.next(); }
  return ok;
}
__device__ __forceinline__ void staged(const Ctx& c, int part) {
  fence_async_smem();
  __syncwarp();
  mbar_arrive_warp(c.sb + BAR_STG + c.wg * 16 + part * 8);
}

template <int WG, bool FIRST, int H>
__device__ __forceinline__ void proj_half(const Ctx& c, float (&acc)[64], uint32_t w, uint32_t x, uint32_t sw) {
  uint64_t dx = desc64((c.sb + x * SLOT + (WG ? 0 : H * 8192)) >> 4, dhi<0>(x) + sw);
  uint64_t dw = desc64(WG ? (c.sb + w * SLOT + H * 8192) >> 4 : sdesc(c.sb + w * SLOT, 8192), dhi<1>(x));
  wg_fence();
  if (WG) { if (FIRST) wgmma_proj96_init(acc, dw, dx, 0); else wgmma_proj96(acc, dw, dx, 1); }
  else { if (FIRST) wgmma_proj_init(acc, dx, dw, 0); else wgmma_proj(acc, dx, dw, 1); }
#pragma unroll
  for (int k = 1; k < 4; k++) {
    dadd(dx, k == 2 ? 2 + (sw >> 30) * 28 : 2); dadd(dw, 128);
    if (WG) wgmma_proj96(acc, dw, dx, 1); else wgmma_proj(acc, dx, dw, 1);
  }
  wg_commit();
}

__device__ __forceinline__ void proj_store16(uint32_t a, const float* f, float sc) {
  stsm4t(a, pack_bf16(f[0] * sc, f[1] * sc), pack_bf16(f[2] * sc, f[3] * sc), pack_bf16(f[4] * sc, f[5] * sc), pack_bf16(f[6] * sc, f[7] * sc));
}

__device__ __forceinline__ uint32_t stage_off(const Ctx& c) {
  const int lane = c.lane, mi = lane >> 3, r8 = lane & 7;
  return ((mi >> 1) * 8 + r8) * 128 + (((2 * c.warp + (mi & 1)) ^ r8) << 4);
}
__device__ __forceinline__ uint32_t q3_swz(uint32_t r8) { return ((r8 & 3) << 1) | (r8 >> 2); }
template <int H>
__device__ __forceinline__ void stage_t2(const Ctx& c, const float (&a)[64], float sc) {
  const uint32_t base = c.sb + QBUF_OFF + 2 * 16384 + H * 8192 + stage_off(c);
#pragma unroll
  for (int jj = 0; jj < 4; jj++) proj_store16(base + jj * 2048, &a[jj * 8], sc);
}
template <int H, bool IS_Q>
__device__ __forceinline__ void stage_t3(const Ctx& c, const float (&a)[64], float sc) {
  const uint32_t off = stage_off(c), r8 = (off >> 7) & 7;
  const uint32_t t3 = c.sb + QBUF_OFF + 3 * 16384 + H * 4096 + (IS_Q ? off ^ ((r8 ^ q3_swz(r8)) << 4) : off);
  proj_store16(t3, &a[32], sc);
  proj_store16(t3 + 2048, &a[40], sc);
}

template <int WG, int h>
__device__ __forceinline__ void load_part(const Ctx& c, Ring r, uint32_t (&q)[32]) {
  uint32_t n = 0;
  while (!h && !__all_sync(0xffffffffu, peek<4>(c, r))) {
    if (++n > (1u << 26)) __trap();
  }
  const int lane = c.lane, mi = lane >> 3, r8 = lane & 7;
  if (WG) { r.next(); r.next(); }
  const uint32_t off = c.sb + (WG ? stage_off(c) : (16 * c.warp + (mi & 1) * 8 + r8) * 128), t0 = off + r.slot * SLOT;
  r.next();
  const uint32_t t1 = off + r.slot * SLOT;
#pragma unroll
    for (int jj = 0; jj < (WG ? 6 : 8); jj++) {
      uint32_t* p = &q[4 * jj];
      if (WG) asm volatile("ldmatrix.sync.aligned.m8n8.x4.trans.shared.b16 {%0, %1, %2, %3}, [%4];" : "=r"(p[0]), "=r"(p[1]), "=r"(p[2]), "=r"(p[3])
                           : "r"((jj < 4 ? t0 + h * 8192 : t1 + h * 4096) + (jj & 3) * 2048) : "memory");
      else ldsm4((h ? t1 : t0) + (jj >> 2) * 8192 + (((((2 * jj) & 7) + (mi >> 1)) ^ r8) << 4), p[0], p[1], p[2], p[3]);
    }
}
template <int WG>
__device__ __forceinline__ void add_part(const Ctx& c, const uint32_t (&q)[32], float (&a)[64]) {
  const uint32_t one = (c.lane >> 3) == (c.lane & 3) ? 0x3f80u << (c.lane & 4) * 4 : 0;
#pragma unroll
  for (int i = 0; i < (WG ? 12 : 16); i++)
    asm("mma.sync.aligned.m16n8k8.row.col.f32.bf16.bf16.f32 {%0, %1, %2, %3}, {%4, %5}, {%6}, {%0, %1, %2, %3};"
        : "+f"(a[4 * i]), "+f"(a[4 * i + 1]), "+f"(a[4 * i + 2]), "+f"(a[4 * i + 3]) : "r"(q[2 * i]), "r"(q[2 * i + 1]), "r"(one));
}

__device__ __forceinline__ void trace_dump(const Ctx& c) {
}
struct RowSum { float l0, l1; };
__device__ __forceinline__ const char* o_addr(uint32_t item, int row, int lane) {
  return reinterpret_cast<const char*>(g_o) + (((item >> 10) * (2 * SQ) + row) * 128 + (lane ^ (lane >> 3)) * 16);
}
__device__ __forceinline__ void o_stg(const char* p, int i, const uint32_t* q) {
  asm volatile("st.global.v4.b32 [%0], {%1, %2, %3, %4};"
               ::"l"(p + (i >> 1) * (SQ * 128) + (i & 1) * 512), "r"(q[0]), "r"(q[1]), "r"(q[2]), "r"(q[3]) : "memory");
}
template <int MODE, int I0 = 0, int NI = 4>
__device__ __forceinline__ void o_emit(const char* p, const float (&o)[64], float inv) {
#pragma unroll
  for (int i = I0; i < I0 + NI; i++) {
    uint32_t q[4];
#pragma unroll
    for (int j = 0; j < 4; j++) q[j] = pack_bf16(o[16 * i + 4 * j + 2 * MODE] * inv, o[16 * i + 4 * j + 2 * MODE + 1] * inv);
    o_stg(p, i, q);
  }
}
__device__ __forceinline__ void o_done(const Ctx& c) {
  __syncwarp();
  mbar_arrive_warp(c.sb + BAR_OUT);
  __syncwarp();
}
template <int WG>
__device__ __forceinline__ void o_first(const Ctx& c, uint32_t item, float (&o)[64], const RowSum& inv) {
  const char* p = o_addr(item, WG ? 192 + 8 * c.warp : 64 + 16 * c.warp, c.lane);
  reg_fence(o);
  if (WG) {
    uint32_t q[16];
#pragma unroll
    for (int j = 0; j < 16; j++) q[j] = pack_bf16((o[4 * j] + o[4 * j + 2]) * inv.l0, (o[4 * j + 1] + o[4 * j + 3]) * inv.l0);
#pragma unroll
    for (int i = 0; i < 4; i++) o_stg(p, i, q + 4 * i);
  } else { o_emit<0>(p, o, inv.l0); o_emit<1>(p + 1024, o, inv.l1); }
}
template <int K0, int K1>
__device__ __forceinline__ void o_piece(const Ctx& c, const char* p, int k, const float (&o)[64], const RowSum& inv) {
  constexpr int NI = 8 / O_STEPS, M = K0 * NI / 4;
  if constexpr (K1 - K0 == 1) {
    o_emit<M, K0 * NI % 4, NI>(p + M * 1024, o, M ? inv.l1 : inv.l0);
    if (K1 == O_STEPS) o_done(c);
  } else {
    if (k <= (K0 + K1) / 2) o_piece<K0, (K0 + K1) / 2>(c, p, k, o, inv); else o_piece<(K0 + K1) / 2, K1>(c, p, k, o, inv);
  }
}
template <int WG>
__device__ __forceinline__ void o_second(const Ctx& c, uint32_t item, int k, float (&o)[64], const RowSum& inv) {
  reg_fence(o);
  o_piece<0, O_STEPS>(c, o_addr(item, 128 * WG + 16 * c.warp, c.lane0 + (k >> 8)), k, o, inv);
}
template <int WG>
__device__ __forceinline__ void release_q(const Ctx& c) {
#pragma unroll
  for (int t = 0; t < 2; t++)
    if (c.lead) asm volatile("mbarrier.arrive.shared::cta.b64 _, [%0], 2;" ::"r"(c.sb + BAR_EMPTY + (NS + 2 * WG + t) * 8) : "memory");
  __syncwarp();
}
struct Slots { uint32_t w, x, o, po; };
template <int WG>
__device__ __forceinline__ void acc_fence(float (&a)[64]) {
#pragma unroll
  for (int i = 0; i < (WG ? 48 : 64); i++) asm volatile("" : "+f"(a[i])::"memory");
}
template <int WG>
__device__ __forceinline__ void begin_acquire(const Ctx& c, Ring& r, Slots& h, bool wait) {
  const uint32_t s0 = r.slot, p0 = r.phase, f = c.sb + BAR_FULL;
  r.next();
  const uint32_t p1 = r.phase;
  h.w = r.slot; r.next();
  h.x = WG ? r.slot : s0; h.o = WG ? s0 : r.slot; h.po = r.phase;
  if (wait) { if (WG) mbar_wait3_w(f + s0 * 8, p0, f + h.w * 8, p1, f + h.x * 8, r.phase); else mbar_wait2_w(f + s0 * 8, p0, f + h.w * 8, p1); }
  r.next();
}
template <int WG>
__device__ __forceinline__ void proj_begin(const Ctx& c, Ring& r, float (&a0)[64], Slots& h, bool wait, uint32_t sw) {
  begin_acquire<WG>(c, r, h, wait);
  proj_half<WG, true, 0>(c, a0, h.w, h.x, sw);
  if (WG) release(c, h.o);
}
template <int WG>
__device__ __forceinline__ void proj_main(Ctx& c, Ring& r, float (&a0)[64], float (&a1)[64], Slots& h, int n, uint32_t sw, int unit,
                                          uint32_t item, int nq, float (&o1)[64], const RowSum& inv) {
  constexpr bool DEEP = (PDEPTH >> WG) & 1;
  T2C(unit, 3);
  int ks = 1;
#pragma unroll 1
  do {
    const Slots p = h;
    const uint32_t b = borrow(ks, n), tile = NS + (WG ? 3 - b : b), f = c.sb + BAR_FULL;
    const uint32_t s0 = b != 2 ? tile : r.slot, p0 = b != 2 ? (r.xp >> b) & 1 : r.phase;
    r.next_if(b == 2);
    const uint32_t p1 = r.phase;
    h.w = r.slot; r.next();
    const uint32_t s2 = b != 2 ? tile : r.slot;
    h.po = b != 2 ? p0 : r.phase;
    r.next_if(b == 2);
    r.xp ^= 1 << b;
    h.x = WG ? s2 : s0; h.o = WG ? s0 : s2;
    mbar_wait3_w(f + s0 * 8, p0, f + h.w * 8, p1, f + (WG ? s2 : p.o) * 8, WG ? h.po : p.po);
    if (ks < 10) T2C(unit, ks * 4);
    if (DEEP) {
      proj_half<WG, false, 0>(c, a0, h.w, h.x, sw);
      release(c, WG ? h.o : p.o);
      if (ks < 10) T2C(unit, ks * 4 + 1);
      wg_wait<1>();
      if (ks < 10) T2C(unit, ks * 4 + 2);
      release(c, p.x); release(c, p.w);
    } else {
      release(c, WG ? h.o : p.o);
      wg_wait<0>();
      release(c, p.x); release(c, p.w);
      if (ks < 10) T2C(unit, ks * 4 + 1);
      proj_half<WG, false, 0>(c, a0, h.w, h.x, sw);
      if (ks < 10) T2C(unit, ks * 4 + 2);
    }
    proj_half<WG, false, 1>(c, a1, h.w, h.x, sw);
    if (ks < 10) T2C(unit, ks * 4 + 3);
    if (ks <= nq) o_second<WG>(c, item, ks, o1, inv);
  } while (++ks != n);
  {
    const uint32_t e0 = c.sb + BAR_EMPTY + (NS + 3 * WG) * 8, e1 = c.sb + BAR_EMPTY + (NS + 1 + WG) * 8;
    const uint32_t p0 = (r.xp ^ unit ^ 1) & 1, p1 = ((r.xp >> 1) ^ unit ^ 1) & 1;
    const uint32_t k0 = sw ? e0 : c.sb + BAR_FULL + r.slot * 8, pk = sw ? p0 : r.phase;
    uint32_t cnt = 0;
    while (!__all_sync(0xffffffffu, mbar_try(e0, p0) & mbar_try(e1, p1) & mbar_try(k0, pk) & (WG || mbar_try(c.sb + BAR_FULL + h.o * 8, h.po)))) {
      if (++cnt > (1u << 22)) __trap();
    }
  }
  c.lane = c.lane0 + (h.w >> 5);
  if (!WG) release(c, h.o);
}
template <int WG>
__device__ __forceinline__ void proj_end(const Ctx& c, float (&a1)[64], const Slots& h) {
  wg_wait<0>();
  acc_fence<WG>(a1);
  release(c, h.x); release(c, h.w);
}
__device__ __forceinline__ uint32_t get_desc(const Ctx& c, int i) {
  uint32_t d;
  mbar_wait_w(c.sb + BAR_DESC, (i - 1) & 1);
  asm volatile("ld.volatile.shared.u32 %0, [%1];" : "=r"(d) : "r"(c.sb + DESC_OFF + (i & 3) * 4) : "memory");
  return __shfl_sync(0xffffffffu, d, 0);
}

__device__ __forceinline__ float quad_max(float x) {
  x = fmaxf(x, __shfl_xor_sync(0xffffffffu, x, 1));
  return fmaxf(x, __shfl_xor_sync(0xffffffffu, x, 2));
}
__device__ __forceinline__ float quad_sum(float x) {
  x += __shfl_xor_sync(0xffffffffu, x, 1);
  return x + __shfl_xor_sync(0xffffffffu, x, 2);
}
template <bool SP, bool FIRST>
__device__ __forceinline__ void exps(const Ctx& c, const float (&s)[32], uint32_t (&p)[SP ? 8 : 16], RowSum& st) {
  if constexpr (SP) {
    uint32_t q[8];
    float t;
#pragma unroll
    for (int j = 0; j < 8; j++) {
      const float e0 = ex2(s[4 * j] + s[4 * j + 2]), e1 = ex2(s[4 * j + 1] + s[4 * j + 3]);
      if (j == 0) t = e0 + e1; else t += e0 + e1;
      q[j] = pack_bf16(e0, e1);
    }
    const bool odd = c.src & 2;
#pragma unroll
    for (int g = 0; g < 4; g++) {
      p[2 * g] = __shfl_sync(0xffffffffu, odd ? q[2 * g + 1] : q[2 * g], c.src);
      p[2 * g + 1] = __shfl_sync(0xffffffffu, odd ? q[2 * g] : q[2 * g + 1], c.src ^ 1);
    }
    st.l0 = FIRST ? t : st.l0 + t;
  } else {
    float t0, t1;
#pragma unroll
    for (int j = 0; j < 8; j++) {
      const float e0 = ex2(s[4 * j]), e1 = ex2(s[4 * j + 1]), e2 = ex2(s[4 * j + 2]), e3 = ex2(s[4 * j + 3]);
      if (j == 0) { t0 = e0 + e1; t1 = e2 + e3; } else { t0 += e0 + e1; t1 += e2 + e3; }
      p[2 * j] = pack_bf16(e0, e1);
      p[2 * j + 1] = pack_bf16(e2, e3);
    }
    st.l0 = FIRST ? t0 : st.l0 + t0;
    st.l1 = FIRST ? t1 : st.l1 + t1;
  }
}
template <bool SP>
__device__ __forceinline__ bool finish_sums(RowSum& st) {
  const float a = quad_sum(st.l0), b = SP ? a : quad_sum(st.l1);
  st.l0 = __fdividef(1.f, a); st.l1 = __fdividef(1.f, b);
  return !(a >= SUM_LO && a <= SUM_HI && b >= SUM_LO && b <= SUM_HI);
}
template <bool SP, bool INIT, int SITE, bool COMMIT = true>
__device__ __forceinline__ void issue_qk(const Ctx& c, float (&s)[32], const uint32_t (&qs)[16], uint32_t dq, uint32_t dk) {
  uint64_t a = desc64(dq, dhi<SITE & 1>(dk)), b = desc64(dk, dhi<1 - (SITE & 1)>(dk));
  if (SP) {
    if (INIT) wgmma_qk_sp_init(s, qs[0], qs[1], qs[2], qs[3], b, 0, c.mqk); else wgmma_qk_sp(s, qs[0], qs[1], qs[2], qs[3], b, 0, c.mqk);
#pragma unroll
    for (int k = 1; k < 4; k++) { dadd(b, k == 2 ? 508 : 4); wgmma_qk_sp(s, qs[4 * k], qs[4 * k + 1], qs[4 * k + 2], qs[4 * k + 3], b, 1, c.mqk); }
  } else {
    if (INIT) wgmma_qk_init(s, a, b, 0); else wgmma_qk(s, a, b, 0);
#pragma unroll
    for (int k = 1; k < 8; k++) { dadd(a, k == 4 ? 506 : 2); dadd(b, k == 4 ? 506 : 2); wgmma_qk(s, a, b, 1); }
  }
  if (COMMIT) wg_commit();
}
template <bool SP, bool ACC, int SITE, bool SPLIT = false>
__device__ __forceinline__ void issue_pv(const Ctx& c, float (&o)[64], const uint32_t (&p)[SP ? 8 : 16], uint32_t dv) {
  uint64_t b = desc64(dv, dhi<SITE & 1>(dv));
  if constexpr (SP) {
    if (ACC) wgmma_pv_sp(o, p[0], p[1], p[2], p[3], b, 1, c.mpv); else wgmma_pv_sp_init(o, p[0], p[1], p[2], p[3], b, 0, c.mpv);
    if (SPLIT) wg_commit();
    dadd(b, 256);
    wgmma_pv_sp(o, p[4], p[5], p[6], p[7], b, 1, c.mpv);
  } else {
    if (ACC) wgmma_pv(o, p[0], p[1], p[2], p[3], b, 1); else wgmma_pv_init(o, p[0], p[1], p[2], p[3], b, 0);
#pragma unroll
    for (int k = 1; k < 4; k++) { dadd(b, 128); wgmma_pv(o, p[4 * k], p[4 * k + 1], p[4 * k + 2], p[4 * k + 3], b, 1); }
  }
  wg_commit();
}
__device__ __forceinline__ void pack_rows(const float (&o)[64], float sc, uint32_t (&q)[32]) {
#pragma unroll
  for (int j = 0; j < 32; j++) q[j] = pack_bf16(o[2 * j] * sc, o[2 * j + 1] * sc);
}
__device__ __forceinline__ void stage_rows(const Ctx& c, uint32_t tile_addr, const uint32_t (&q)[32]) {
  const int lane = c.lane, mi = lane >> 3, r8 = lane & 7;
  const uint32_t row_addr = tile_addr + (16 * c.warp + (mi & 1) * 8 + r8) * 128;
#pragma unroll
  for (int jj = 0; jj < 8; jj++)
    stsm4(row_addr + (jj >> 2) * 8192 + (((((2 * jj) & 7) + (mi >> 1)) ^ r8) << 4), q[4 * jj], q[4 * jj + 1], q[4 * jj + 2], q[4 * jj + 3]);
}
__device__ __forceinline__ void stage_rows(const Ctx& c, uint32_t tile_addr, const float (&o)[64], float sc) {
  uint32_t q[32];
  pack_rows(o, sc, q);
  stage_rows(c, tile_addr, q);
}
template <int WG, int H>
__device__ __forceinline__ void stage_out(const Ctx& c, const float (&a)[64]) {
  if (WG) { stage_t3<H, false>(c, a, 1.f); if (H) staged(c, 0); stage_t2<H>(c, a, 1.f); }
  else stage_rows(c, c.sb + QBUF_OFF + H * 16384, a, 1.f);
  if (H || !WG) staged(c, H);
}
template <int SITE>
__device__ __forceinline__ void issue_qk_rs(float (&s)[32], uint32_t (&q)[32], uint32_t dk) {
  uint64_t b = desc64(dk, dhi<SITE>(dk));
  reg_fence(q);
  wg_fence();
  wgmma_qk_rs_init(s, q[0], q[1], q[2], q[3], b, 0);
#pragma unroll
  for (int k = 1; k < 8; k++) { dadd(b, k == 4 ? 506 : 2); wgmma_qk_rs(s, q[4 * k], q[4 * k + 1], q[4 * k + 2], q[4 * k + 3], b, 1); }
  wg_commit();
}

__device__ __forceinline__ void redo_tile(const Ctx& c, uint32_t q_addr, uint32_t half, const __nv_bfloat16* kp, const __nv_bfloat16* vp,
                                          uint32_t item, int row) {
  float o[64];
  const int lane = lane_now(), g = lane >> 2, cc = lane & 3, mi = lane >> 3, r8 = lane & 7;
  const uint32_t qa = q_addr + (half == 4096 ? 8 * c.warp + r8 : 16 * c.warp + (mi & 1) * 8 + r8) * 128, swz = half == 4096 ? q3_swz(r8) : r8;
  const uint32_t* kq = reinterpret_cast<const uint32_t*>(kp + g * DH) + cc;
  const unsigned short* vq = reinterpret_cast<const unsigned short*>(vp + 2 * cc * DH) + g;
  float m0 = -INFINITY, m1 = -INFINITY, l0 = 0.f, l1 = 0.f;
#pragma unroll
  for (int i = 0; i < 64; i++) o[i] = 0.f;
#pragma unroll 1
  for (int kb = 0; kb < SK / 16; kb++) {
    float z[8] = {0.f, 0.f, 0.f, 0.f, 0.f, 0.f, 0.f, 0.f};
#pragma unroll 2
    for (int kk = 0; kk < 8; kk++) {
      uint32_t a0, a1, a2, a3;
      ldsm4(qa + (kk >> 2) * half + ((((kk & 3) * 2 + (mi >> 1)) ^ swz) << 4), a0, a1, a2, a3);
      const uint32_t* kr = kq + kb * (16 * DH / 2) + kk * 8;
      mma16816(z[0], z[1], z[2], z[3], a0, a1, a2, a3, __ldg(kr), __ldg(kr + 4));
      mma16816(z[4], z[5], z[6], z[7], a0, a1, a2, a3, __ldg(kr + 8 * DH / 2), __ldg(kr + 8 * DH / 2 + 4));
    }
    const float n0 = fmaxf(m0, quad_max(fmaxf(fmaxf(z[0], z[1]), fmaxf(z[4], z[5]))));
    const float n1 = fmaxf(m1, quad_max(fmaxf(fmaxf(z[2], z[3]), fmaxf(z[6], z[7]))));
    const float al0 = ex2(m0 - n0), al1 = ex2(m1 - n1);
    m0 = n0; m1 = n1;
#pragma unroll
    for (int i = 0; i < 8; i++) z[i] = ex2(z[i] - ((i & 2) ? n1 : n0));
    l0 = l0 * al0 + (z[0] + z[1]) + (z[4] + z[5]);
    l1 = l1 * al1 + (z[2] + z[3]) + (z[6] + z[7]);
    const uint32_t a0 = pack_bf16(z[0], z[1]), a1 = pack_bf16(z[2], z[3]), a2 = pack_bf16(z[4], z[5]), a3 = pack_bf16(z[6], z[7]);
    const unsigned short* vr = vq + kb * (16 * DH);
#pragma unroll
    for (int nb = 0; nb < 16; nb++) {
      o[4 * nb] *= al0; o[4 * nb + 1] *= al0; o[4 * nb + 2] *= al1; o[4 * nb + 3] *= al1;
      const uint32_t b0 = __ldg(vr + nb * 8) | ((uint32_t)__ldg(vr + nb * 8 + DH) << 16);
      const uint32_t b1 = __ldg(vr + nb * 8 + 8 * DH) | ((uint32_t)__ldg(vr + nb * 8 + 9 * DH) << 16);
      mma16816(o[4 * nb], o[4 * nb + 1], o[4 * nb + 2], o[4 * nb + 3], a0, a1, a2, a3, b0, b1);
    }
  }
  const char* p = o_addr(item, row, lane);
  o_emit<0>(p, o, __fdividef(1.f, quad_sum(l0)));
  o_emit<1>(half == 4096 ? p : p + 1024, o, __fdividef(1.f, quad_sum(l1)));
}

template <bool SPA, bool SPB, int SITE, int ID>
__device__ __forceinline__ void batch(const Ctx& c, float (&s)[32], const uint32_t (&qs)[16], uint32_t dq, uint32_t dk, float (&ob)[64],
                                      uint32_t (&pb)[SPB ? 8 : 16], uint32_t dv) {
  if constexpr (SPA) {
    reg_fence(pb);
    wg_fence();
    issue_pv<SPB, true, ID>(c, ob, pb, dv);
    issue_qk<SPA, false, ID>(c, s, qs, dq, dk);
  } else {
    constexpr bool EARLY = ((QK_EARLY_MASK >> (SITE + (SPB ? 2 : 0))) & 1) != 0;
    if (!EARLY) reg_fence(pb);
    wg_fence();
    issue_qk<SPA, false, ID, !SPB>(c, s, qs, dq, dk);
    if (EARLY) { reg_fence(pb); wg_fence(); }
    issue_pv<SPB, true, ID, SPB>(c, ob, pb, dv);
  }
}

template <bool SP0>
__device__ __forceinline__ bool attention(Ctx& c, Ring& r, int unit, uint32_t& d, const float (&a0)[64], float (&o0)[64], float (&o1)[64],
                                          RowSum& st0, RowSum& st1, const Slots& h) {
  constexpr bool SP1 = false;
  if (SP0) { c.mqk = META_QK + (d >> 28); c.mpv = META_PV + (d >> 28); asm volatile("" : "+r"(c.mqk), "+r"(c.mpv)); }
  if (SP0) c.src = (c.lane & 28) | ((c.lane & 1) << 1) | ((c.lane >> 1) & 1);
  float s[32];
  uint32_t p0[SP0 ? 8 : 16], p1[16];
  const uint32_t q0a = c.sb + QBUF_OFF + (SP0 ? 3 : 0) * 16384, q1a = c.sb + QBUF_OFF + (SP0 ? 2 : 1) * 16384;
  const uint32_t dq0 = sdesc(q0a, 0), dq1 = sdesc(q1a, 0);
  uint32_t sk = acquire(c, r, true), sv, sn;
  uint32_t qs[16];
  float s1[32];
  if (SP0) {
    stage_t3<0, true>(c, a0, SM_C);
    stage_t2<0>(c, a0, SM_C);
    proj_end<1>(c, o0, h);
    stage_t3<1, true>(c, o0, SM_C);
    stage_t2<1>(c, o0, SM_C);
    fence_async_smem();
    bar_sync(1, LAG_BAR & 30 ? 256 : 128);
    const int g = c.lane >> 2, cc = c.lane & 3;
    const uint32_t qa = q0a + (8 * c.warp + g) * 128 + (cc & 1) * 8;
#pragma unroll
    for (int k = 0; k < 8; k++)
      asm volatile("ld.shared.v2.u32 {%0, %1}, [%2];" : "=r"(qs[2 * k]), "=r"(qs[2 * k + 1])
                   : "r"(qa + (k >> 2) * 4096 + ((((k & 3) * 2 + (cc >> 1)) ^ q3_swz(g)) << 4)) : "memory");
    TRACE(unit, 2);
    wg_fence();
    issue_qk<SP1, true, 1>(c, s1, qs, dq1, sdesc(c.sb + sk * SLOT, 0));
    reg_fence(qs);
    wg_fence();
    issue_qk<SP0, true, 0>(c, s, qs, dq0, sdesc(c.sb + sk * SLOT, 0));
    const bool have = peek<2>(c, r);
    wg_wait<1>();
    reg_fence(s1);
    exps<SP1, true>(c, s1, p1, st1);
    sched_fence<11>(sk, p1);
    acquire2(c, r, sv, sn, __all_sync(0xffffffffu, have));
    wg_wait<0>();
    wg_fence();
    issue_pv<SP1, false, 1>(c, o1, p1, sdesc(c.sb + sv * SLOT, 8192));
    if (LAG_BAR & 1) asm volatile("bar.arrive 4, 256;" ::: "memory");
    sched_fence<12>(sk, s);
    release(c, sk);
    sk = sn;
    exps<SP0, true>(c, s, p0, st0);
    reg_fence(p0);
    wg_fence();
    issue_pv<SP0, false, 0>(c, o0, p0, sdesc(c.sb + sv * SLOT, 8192));
    issue_qk<SP0, true, 2>(c, s, qs, dq0, sdesc(c.sb + sk * SLOT, 0));
    sn = acquire(c, r);
    wg_wait<0>();
    reg_fence(s);
  } else {
    uint32_t q0[32], q1[32];
    pack_rows(a0, SM_C, q0);
    stage_rows(c, q0a, q0);
    proj_end<0>(c, o1, h);
    TRACE(unit, 2);
    float sc = SM_C;
    issue_qk_rs<0>(s, q0, sdesc(c.sb + sk * SLOT, 0));
    sched_fence<0>(sk, sc);
    if (LAG_BAR & 8) asm volatile("bar.arrive 1, 256;" ::: "memory");
    pack_rows(o1, sc, q1);
    stage_rows(c, q1a, q1);
    if (LAG_BAR & 4) asm volatile("bar.arrive 1, 256;" ::: "memory");
    issue_qk_rs<1>(s1, q1, sdesc(c.sb + sk * SLOT, 0));
    if (LAG_BAR & 2) asm volatile("bar.arrive 1, 256;" ::: "memory");
    bool have = peek<2>(c, r);
    wg_wait<1>();
    reg_fence(s);
    exps<SP0, true>(c, s, p0, st0);
    sched_fence<1>(sk, p0);
    if (LAG_BAR & 16) asm volatile("bar.arrive 1, 256;" ::: "memory");
    acquire2(c, r, sv, sn, __all_sync(0xffffffffu, have));
    wg_wait<0>();
    reg_fence(s1);
    fence_async_smem();
    __syncwarp();
    wg_fence();
    issue_qk<SP0, false, 2>(c, s, qs, dq0, sdesc(c.sb + sn * SLOT, 0));
    issue_pv<SP0, false, 0>(c, o0, p0, sdesc(c.sb + sv * SLOT, 8192));
    sched_fence<2>(sk, s1);
    release(c, sk);
    have = peek<1>(c, r);
    sk = sn;
    exps<SP1, true>(c, s1, p1, st1);
    reg_fence(p1);
    wg_fence();
    issue_pv<SP1, false, 1>(c, o1, p1, sdesc(c.sb + sv * SLOT, 8192));
    sn = acquire(c, r, __all_sync(0xffffffffu, have));
    if (LAG_BAR & 1) bar_sync(4, 256);
    wg_wait<1>();
    reg_fence(s);
  }
  TRACE_IN(unit, 4);
  T2C(unit, 51);
#pragma unroll 1
  for (int j = 1; j < 15; j++) {
    const uint32_t sv_prev = sv, sk_prev = sk;
    sv = sn;
    const uint32_t dv = sdesc(c.sb + sv * SLOT, 8192);
    reg_fence(p0);
    exps<SP0, false>(c, s, p0, st0);
    batch<SP1, SP0, 0, 3>(c, s, qs, dq1, sdesc(c.sb + sk * SLOT, 0), o0, p0, dv);
    sk = acquire(c, r);
    wg_wait<1>();
    reg_fence(s); reg_fence(p1);
    release(c, sv_prev); release(c, sk_prev);
    exps<SP1, false>(c, s, p1, st1);
    batch<SP0, SP1, 1, 4>(c, s, qs, dq0, sdesc(c.sb + sk * SLOT, 0), o1, p1, dv);
    sn = acquire(c, r);
    if (SP0) wg_wait<0>(); else wg_wait<1>();
    reg_fence(s);
  }
  TRACE_IN(unit, 5);
  T2C(unit + 1, 52);
  const uint32_t sv_prev = sv;
  sv = sn;
  const uint32_t dv = sdesc(c.sb + sv * SLOT, 8192);
  reg_fence(p0);
  exps<SP0, false>(c, s, p0, st0);
  batch<SP1, SP0, 0, 5>(c, s, qs, dq1, sdesc(c.sb + sk * SLOT, 0), o0, p0, dv);
  asm volatile("ld.volatile.shared.u32 %0, [%1];" : "=r"(d) : "r"(c.sb + DESC_OFF + ((unit + 1) & 3) * 4) : "memory");
  const bool have = peek<2 + SP0>(c, r);
  wg_wait<1>();
  reg_fence(s); reg_fence(p1);
  release(c, sv_prev); release(c, sk);
  exps<SP1, false>(c, s, p1, st1);
  reg_fence(p1);
  wg_fence();
  issue_pv<SP1, true, 2>(c, o1, p1, dv);
  if (SP0) sched_fence<6>(sk, st0.l0, st1.l0, st1.l1); else sched_fence<5>(sk, st0.l0, st0.l1, st1.l0, st1.l1);
  c.lane = c.lane0 + (sk >> 5);
  const bool bad = finish_sums<SP0>(st0) | finish_sums<SP1>(st1);
  uint32_t any;
  asm volatile("{\n.reg .pred p, q;\nsetp.ne.u32 p, %1, 0;\nbar.red.or.pred q, %2, 128, p;\nselp.u32 %0, 1, 0, q;\n}"
               : "=r"(any) : "r"((uint32_t)bad), "n"(2 + SP0) : "memory");
  any = __any_sync(0xffffffffu, any);
  d = __shfl_sync(0xffffffffu, d, 0);
  if (d < (2u << 30) && !__all_sync(0xffffffffu, have)) { Ring t = r; Slots u; begin_acquire<SP0>(c, t, u, true); }
  wg_wait<0>();
  reg_fence(o0); reg_fence(o1);
  release(c, sv);
  return any;
}

template <int WG>
__device__ __forceinline__ void consumer(Ctx c, const __nv_bfloat16* const* kv) {
  asm volatile("setmaxnreg.inc.sync.aligned.u32 %0;" ::"n"(WG ? REG_C : 504 - REG_C - REG_P));
  c.wg = WG;
  Ring r{0, 0, 0};
  float a0[64], a1[64], o1[64];
  Slots h;
  RowSum inv0, inv1;
  uint32_t d = c_sched.queue[blockIdx.x] * 1025, dc = 0, sw;
  int i = 0, nq;
begin:
  sw = d & (1u << 30);
  proj_begin<WG>(c, r, a0, h, true, sw);
begin1:
  proj_half<WG, true, 1>(c, a1, h.w, h.x, sw);
  nq = 0;
#pragma unroll
  for (int k = 0; k < 64; k++) asm volatile("" : "=f"(o1[k]));
  asm volatile("" : "=f"(inv1.l0), "=f"(inv1.l1));
  while (true) {
    TRACE(i, 0); TRACE(i, 6);
    proj_main<WG>(c, r, a0, a1, h, d >> 30 ? ((d >> 16) & 63) + 1 : DM / 64, sw, i, dc, nq, o1, inv1);
    dc = d;
    TRACE(i, 1);
    if (d >> 30) goto out_tile;
    wg_wait<1>();
    acc_fence<WG>(a0);
    if (WG ? attention<WG>(c, r, i, d, a0, a1, o1, inv0, inv1, h) : attention<WG>(c, r, i, d, a0, o1, a1, inv1, inv0, h)) goto redo;
    if (d >= (2u << 30)) break;
    sw = d & (1u << 30);
    proj_begin<WG>(c, r, a0, h, false, sw);
    release_q<WG>(c);
    if (WG) sched_fence<8>(h.w, inv0.l0); else sched_fence<7>(h.w, inv0.l0, inv0.l1);
    o_first<WG>(c, dc, a1, inv0);
    sched_fence<9>(h.w, inv1.l0);
    proj_half<WG, true, 1>(c, a1, h.w, h.x, sw);
    nq = O_STEPS;
    TRACE(i, 3); TRACE(i, 7);
    i++;
  }
  release_q<WG>(c);
  o_first<WG>(c, dc, a1, inv0);
#pragma unroll
  for (int k = 1; k <= O_STEPS; k++) o_second<WG>(c, dc, k, o1, inv1);
next:
  TRACE(i, 3); TRACE(i, 7);
  if ((d >> 30) != 2) {
    i++;
    r.uniform();
    goto begin;
  }
  trace_dump(c);
  return;
out_tile:
  if (d & 96) goto finish;
  d = get_desc(c, i + 1);
  wg_wait<1>();
  acc_fence<WG>(a0);
  TRACE_O(0);
  stage_out<WG, 0>(c, a0);
  TRACE_O(1);
  proj_end<WG>(c, a1, h);
  TRACE_O(2);
  if (!EARLY_BEGIN || d >= (2u << 30)) { stage_out<WG, 1>(c, a1); TRACE(i, 2); goto next; }
  sw = d & (1u << 30);
  proj_begin<WG>(c, r, a0, h, true, sw);
  TRACE_O(3);
  stage_out<WG, 1>(c, a1);
  TRACE(i, 2); TRACE(i, 3); TRACE(i, 7);
  i++;
  goto begin1;
finish:
  {
    uint32_t q[32];
#pragma unroll 1
    for (int k = (d >> 5) & 3; k > 1; k--) {
      wg_wait<0>();
      acc_fence<WG>(a0); acc_fence<WG>(a1);
      if (k == ((d >> 5) & 3)) { release(c, h.x); release(c, h.w); }
      load_part<WG, 0>(c, r, q); add_part<WG>(c, q, a0);
      load_part<WG, 1>(c, r, q); add_part<WG>(c, q, a1);
#pragma unroll
      for (int t = 0; t < 4; t++) { release(c, r.slot); r.next(); }
    }
    load_part<WG, 0>(c, r, q);
    wg_wait<1>();
    acc_fence<WG>(a0);
    TRACE_O(0);
    add_part<WG>(c, q, a0);
    stage_out<WG, 0>(c, a0);
    TRACE_O(1);
    load_part<WG, 1>(c, r, q);
    wg_wait<0>();
    acc_fence<WG>(a1);
    TRACE_O(2);
    add_part<WG>(c, q, a1);
    stage_out<WG, 1>(c, a1);
    TRACE(i, 2); TRACE(i, 3); TRACE(i, 7);
    trace_dump(c);
    return;
  }
redo:
  {
    const size_t hoff = (size_t)(dc & 511) * (SK * DH);
    const int br = (dc >> 9) & 1;
#pragma unroll 1
    for (int part = 0; part < 2; part++) {
      const int t = WG ? 3 - part : part;
      redo_tile(c, c.sb + QBUF_OFF + t * 16384, t == 3 ? 4096 : 8192, kv[br] + hoff, kv[2 + br] + hoff, dc,
                t * 64 + (t == 3 ? 8 : 16) * c.warp);
    }
    o_done(c);
    release_q<WG>(c);
  }
  goto next;
}

template <bool SIMPLE>
__global__ void __launch_bounds__(384, 1) mha_fused_kernel(const __grid_constant__ Params P) {
  extern __shared__ __align__(1024) uint8_t smem_raw[];
  const uint32_t sbase = smem_u32(smem_raw);
  const int tid = threadIdx.x;
  const int wg = __shfl_sync(0xffffffffu, tid >> 7, 0);
  const int warp = __shfl_sync(0xffffffffu, (tid >> 5) & 3, 0);
  const int lane = tid & 31;
  const int cta = blockIdx.x;

  if (tid == 0) T3(15, 0);
  if ((sbase & 1023) || sbase + SMEM_BYTES > 0x40000) __trap();
  {
    const int wi = wg * 4 + warp;
    asm volatile(ELECT "prefetch.tensormap [%0];\n}" ::"l"(&P.x[0][0] + wi) : "memory");
#pragma unroll
    for (int k = 0; k < 3; k++) {
      const int b = min(BAR_OFF + (wi * 3 + k) * 8, BAR_GO);
      asm volatile(ELECT "mbarrier.init.shared::cta.b64 [%0], %1;\n}"
                   ::"r"(sbase + b), "r"(b < BAR_EMPTY || b >= BAR_DESC ? 1 : b >= BAR_STG && b < BAR_OUT ? 4 : 8) : "memory");
    }
    asm volatile("fence.mbarrier_init.release.cluster;" ::: "memory");
    if (wi < 6) asm volatile(ELECT "prefetch.tensormap [%0];\n}" ::"l"(&P.x[0][0] + 12 + wi) : "memory");
  }
  __syncthreads();

  if (wg == 2) {
    asm volatile("setmaxnreg.dec.sync.aligned.u32 %0;" ::"n"(REG_P));
    if (warp == 1) {
      const uint32_t qb = sbase + QBUF_OFF;
      const uint32_t ep = __shfl_sync(0xffffffffu, *(volatile unsigned*)&g_epoch + 1, 0);
      asm volatile("st.volatile.shared.u32 [%0], %1;" ::"r"(sbase + EPOCH_OFF), "r"(ep) : "memory");
      uint32_t dc = c_sched.queue[cta], qi = 0, piece = 0, na = 0;
      TTAIL(0);
      for (int i = 0; (dc >> 30) != 2; i++) {
        if (!(dc >> 30) && o_reuse<SIMPLE>((dc >> 5) & 31)) {
          const unsigned* rd = &g_rd[0][0] + ((dc & 1023) >> 2) - OR * 8;
          for (uint32_t n = 0; !__all_sync(0xffffffffu, reached(rd, ep * 5)); __nanosleep(300)) if (++n > (1u << 22)) __trap();
        }
        mbar_wait_w(sbase + BAR_GO, i & 1);
        if (piece == 0) {
          if (lane == 0) {
            qi = atomicAdd(&g_next, 1);
            if (qi == (SIMPLE ? Q_ALL : Q_RANGES) - 1) { g_next = 0; g_epoch = ep; }
          }
          qi = __shfl_sync(0xffffffffu, qi, 0) + (SIMPLE ? gridDim.x : NCTA);
        }
        uint32_t d;
        if (qi < (SIMPLE ? Q_ALL : Q_RANGES)) { d = c_sched.queue[qi]; if (d & 0x8000) d ^= (1u << 30) | (63u << 16) | 0x8000; else d |= o_slot<SIMPLE>(d >> 5) << 15 | (d & 31) << 10; }
        else if (SIMPLE) d = 2u << 30;
        else { const uint32_t e = qi - Q_RANGES, g = e / 5; d = c_sched.piece[g][piece++] | (e - g * 5) << 8; }
        if ((d >> 30) == 1) {
          const uint32_t k0 = (d >> 22) & 63;
          const uint32_t run = __ffs(__ballot_sync(0xffffffffu, !reached(&g_cnt[d & 31][lane & 7], ep * 4)) & (0xffu << (k0 >> 3))) - 1;
          if (run <= (k0 + ((d >> 16) & 63)) >> 3) d |= run <= (k0 + O_STEPS) >> 3 ? (2u << 30) | 128 : 128;
        }
        asm volatile("st.volatile.shared.u32 [%0], %1;" ::"r"(sbase + EPOCH_OFF + 4), "r"(qi) : "memory");
        asm volatile("st.volatile.shared.u32 [%0], %1;" ::"r"(sbase + DESC_OFF + ((i + 1) & 3) * 4), "r"(d) : "memory");
        __syncwarp();
        mbar_arrive_warp(sbase + BAR_DESC);
        const Work w = decode(dc);
        dc = d;
        if (w.kind == 0) {
          mbar_wait_w(sbase + BAR_OUT, na++ & 1);
          TTAIL(1);
          T3(i, 0); T3(i, 1);
          asm volatile(ELECT "red.release.gpu.global.add.u32 [%0], 1;\n}" ::"l"(&g_cnt[w.beta][w.sub >> 2]) : "memory");
          T3(i, 2);
          TTAIL(2);
          continue;
        }
        const bool fin = w.mode != 1;
        uint64_t pol, pol2;
        asm volatile("createpolicy.fractional.L2::evict_first.b64 %0, 1.0;" : "=l"(pol));
        asm volatile("createpolicy.fractional.L2::evict_normal.b64 %0, 1.0;" : "=l"(pol2));
        if (!fin) pol = pol2;
        const CUtensorMap* m = fin ? P.out_st : P.o_st;
        const int c1 = fin ? (w.beta & 15) * SQ : 0;
        const int c2 = fin ? (w.beta >> 4) * (DM / 64) + w.sub * 2 : NBETA * 64 + w.range * 2;
        uint32_t pend = 0;
#pragma unroll 1
        for (int e = 0; e < 4; e++) {
          const int t = (ST_ORDER >> (4 * e)) & 3;
          mbar_wait_w(sbase + BAR_STG + (t ^ (t >> 1)) * 8, (i - na) & 1);
          tma_st3_hint_w(m + (t == 3), qb + t * 16384, 0, c1 + t * 64, c2, pol);
          bulk_commit();
          T2P(i + 1, 5, 2 * e);
          if (pend) {
            bulk_wait_read<1>();
            mbar_arrive8_w(pend);
            T2P(i + 1, 5, 2 * e - 1);
          }
          pend = sbase + BAR_EMPTY + (NS + t) * 8;
          if ((ST_NOW >> e) & 1) {
            bulk_wait_read<0>();
            mbar_arrive8_w(pend);
            pend = 0;
            T2P(i + 1, 5, 2 * e + 1);
          }
        }
        if (w.beta < N_EARLY) asm volatile(ELECT "red.relaxed.gpu.global.add.u32 [%0], 1;\n}" ::"l"(&g_rd[w.beta][7]) : "memory");
        T3(i, 0);
        if (piece >= 2) TTAIL(piece * 2 - 1);
        asm volatile("cp.async.bulk.wait_group 0;" ::: "memory");
        T3(i, 1);
        if (w.mode == 1) asm volatile(ELECT "st.release.gpu.global.u32 [%0], %1;\n}" ::"l"(&g_flag[w.range]), "r"(ep) : "memory");
        T3(i, 2);
        if (piece >= 2) TTAIL(piece * 2);
      }
      T3(15, 1);
    } else
    if (warp == 0) {
      Ring r{0, 1, 3};
      uint32_t d = c_sched.queue[cta];
      for (int i = 0;; i++) {
        const Work w = decode(d);
        if (w.kind == 2) break;
        const CUtensorMap* m = w.kind == 0 ? &P.wq[w.beta >> 4] : &P.wo[w.beta >> 4];
        for (int ks = 0; ks < w.nsteps; ks++) {
          const uint32_t b = borrow(ks, w.nsteps);
          r.next_if(b == 2);
          const uint32_t bar = sbase + BAR_FULL + r.slot * 8;
          mbar_wait_w(bar + (BAR_EMPTY - BAR_FULL), r.phase);
          if (w.kind == 0) tma_ld3_w(sbase + r.slot * SLOT, m, 0, ks * 64, w.sub * 2, bar, 16384);
          else tma_ld_wo_w(sbase + r.slot * SLOT, m, w.sub * 128, (w.k0 + ks) * 2, bar);
          if (w.kind != 0 && w.beta < N_EARLY && (ks & 7) == 5 && ks > 5)
            asm volatile(ELECT "red.relaxed.gpu.global.add.u32 [%0], 1;\n}" ::"l"(&g_rd[w.beta][(ks >> 3) - 1]) : "memory");
          if (ks < 10) T2P(i, 2, ks);
          if (w.kind != 0 && ks == max(w.nsteps - GO_P, 4)) mbar_arrive_warp(sbase + BAR_GO);
          r.next(); r.next_if(b == 2);
        }
        if (w.kind == 0) {
          r.phase ^= 1; r.next(); r.next();
        } else if (w.mode == 2) {
          for (int k = 1; k <= ((d >> 5) & 3); k++) {
            if (k == 1) TTAIL(9);
            wait_count(&g_flag[w.range + 5 * k], lds(sbase + EPOCH_OFF));
            TTAIL(10);
            asm volatile("fence.proxy.async.global;" ::: "memory");
#pragma unroll 1
            for (int t = 0; t < 4; t++) {
              mbar_wait_w(sbase + BAR_EMPTY + r.slot * 8, r.phase);
              tma_ld3_w(sbase + r.slot * SLOT, &P.o_st[t == 3], 0, t * 64, NBETA * 64 + (w.range + 5 * k) * 2, sbase + BAR_FULL + r.slot * 8,
                        t == 3 ? 8192 : 16384);
              r.next();
            }
          }
        }
        mbar_wait_w(sbase + BAR_DESC, i & 1);
        d = __shfl_sync(0xffffffffu, lds(sbase + DESC_OFF + ((i + 1) & 3) * 4), 0);
      }
    } else {
      const int hi = warp - 2;
      uint64_t pol_stream;
      asm volatile("createpolicy.fractional.L2::evict_first.b64 %0, 1.0;" : "=l"(pol_stream));
      Ring r{0, 1, 3};
      uint32_t d = c_sched.queue[cta];
      for (int i = 0;; i++) {
        const Work w = decode(d);
        if (w.kind == 2) break;
        const CUtensorMap* m = w.kind == 0 ? &P.x[hi][w.beta >> 4] : &P.o_ld[hi];
        int c1 = (w.kind == 0 ? (w.beta & 15) : o_slot<SIMPLE>(w.beta) * 64 + w.k0) * SQ + hi * 128;
        int k_wait = -1;
        if (w.kind != 0) {
          if (d & 128) k_wait = d >= (3u << 30) ? 0 : 8 - (w.k0 & 7);
          asm volatile("fence.proxy.async.global;" ::: "memory");
        }
        const int rank = i == 0 ? cta : __shfl_sync(0xffffffffu, lds(sbase + EPOCH_OFF + 4), 0) - NCTA;
        for (int ks = 0; ks < w.nsteps; ks++) {
          if (ks == k_wait) {
            wait_count(&g_cnt[d & 31][(w.k0 + ks) >> 3], lds(sbase + EPOCH_OFF) * 4);
            asm volatile("fence.proxy.async.global;" ::: "memory");
            k_wait = ((w.k0 + ks) | 7) + 1 - w.k0;
          }
          const uint32_t b = borrow(ks, w.nsteps);
          const bool bo = b != 2;
          r.next_if(hi && !bo); r.next_if(hi && !bo);
          const uint32_t sl = bo ? NS + (b ^ (3 * hi)) : r.slot, bar = sbase + BAR_FULL + sl * 8;
          mbar_wait_w(bar + (BAR_EMPTY - BAR_FULL), bo ? (r.xp >> b) & 1 : r.phase);
          if (w.kind == 0) tma_ld2_w(sbase + sl * SLOT, m, ks * 64, c1, bar, (hi ? 96 * 128 : 128 * 128));
          else { tma_ld2_hint_w(sbase + sl * SLOT, m, 0, c1, bar, hi ? 96 * 128 : 128 * 128, pol_stream); c1 += SQ; }
          if (i == 0 && ks == PF_STEP)
            asm volatile(ELECT "cp.async.bulk.prefetch.tensor.3d.L2.global.L2::cache_hint [%0, {0, %1, 0}], %2;\n}"
                         ::"l"(&P.kv[hi][0]), "r"(d * SK), "l"(pol_stream) : "memory");
          if (ks < 10) T2P(i, 3 + hi, ks);
          if (!hi && w.kind != 0 && !(ks & 3)) TCLK(i * 16 + (ks >> 2));
          r.next(); r.next_if(!hi && !bo); r.next_if(!hi && !bo);
          r.xp ^= 1 << b;
        }
        r.xp ^= 3;
        if (w.kind == 0) {
          m = &P.kv[hi][w.beta >> 4];
          c1 = (d & 511) * SK;
          for (int j = 0; j < 16; j++) {
            if (hi) r.next();
            const uint32_t bar = sbase + BAR_FULL + r.slot * 8;
            const bool tight = i < KV_WIN_UNITS && j < KV_WIN_TILES + ((KV_WIN_RAMP * rank) >> 5);
            {
              const int s2 = (int)r.slot - (tight ? 2 : KV_WIN_D);
              mbar_wait_w(sbase + BAR_FULL + (s2 < 0 ? s2 + NS : s2) * 8, s2 < 0 ? r.phase : r.phase ^ 1);
            }
            if (j == 15 && hi) mbar_wait_w(sbase + BAR_DESC, i & 1);
            mbar_wait_w(sbase + BAR_EMPTY + r.slot * 8, r.phase);
            tma_ld3_hint_w(sbase + r.slot * SLOT, m, 0, c1, 0, bar, pol_stream);
            T2P(i, 3 + hi, 16 + j);
            if (!hi) TCLK(i * 16 + j);
            if (j == 14 && !hi) mbar_arrive_warp(sbase + BAR_GO);
            c1 += 64;
            r.next();
            if (!hi) r.next();
          }
        }
        mbar_wait_w(sbase + BAR_DESC, i & 1);
        d = __shfl_sync(0xffffffffu, lds(sbase + DESC_OFF + ((i + 1) & 3) * 4), 0);
      }
    }
  } else {
    Ctx c;
    c.sb = sbase; c.wg = wg; c.warp = warp; c.src = 0; c.mqk = 0; c.mpv = 0; c.lead = lane == 0; c.lane0 = c.lane = lane;
    if (wg == 0) consumer<0>(c, P.kp); else consumer<1>(c, P.kp);
  }
}

typedef CUresult (*EncodeFn)(CUtensorMap*, CUtensorMapDataType, cuuint32_t, void*, const cuuint64_t*, const cuuint64_t*,
                             const cuuint32_t*, const cuuint32_t*, CUtensorMapInterleave, CUtensorMapSwizzle,
                             CUtensorMapL2promotion, CUtensorMapFloatOOBfill);

void make_map(EncodeFn enc, CUtensorMap* m, const void* ptr, int rank, const cuuint64_t* dims, const cuuint64_t* strides,
              const cuuint32_t* box, int promo = 2, CUtensorMapSwizzle swz = CU_TENSOR_MAP_SWIZZLE_128B) {
  cuuint32_t es[5] = {1, 1, 1, 1, 1};
  enc(m, CU_TENSOR_MAP_DATA_TYPE_BFLOAT16, rank, const_cast<void*>(ptr), dims, strides, box, es,
      CU_TENSOR_MAP_INTERLEAVE_NONE, swz, promo == 2 ? CU_TENSOR_MAP_L2_PROMOTION_L2_256B : promo == 1 ? CU_TENSOR_MAP_L2_PROMOTION_L2_128B : CU_TENSOR_MAP_L2_PROMOTION_NONE,
      CU_TENSOR_MAP_FLOAT_OOB_FILL_NONE);
}

}

extern "C" void kernel_launch(void* const* d_in, const int* in_sizes, int n_in, void* d_out, int out_size) {
  (void)in_sizes; (void)n_in; (void)out_size;
  static EncodeFn enc = nullptr;
  static void* o_ptr = nullptr;
  static int n_sm = 0;
  if (!enc) {
    void* fn = nullptr;
    cudaDriverEntryPointQueryResult qr;
    cudaGetDriverEntryPoint("cuTensorMapEncodeTiled", &fn, cudaEnableDefault, &qr);
    enc = (EncodeFn)fn;
    cudaGetSymbolAddress(&o_ptr, g_o);
    cudaFuncSetAttribute(mha_fused_kernel<false>, cudaFuncAttributeMaxDynamicSharedMemorySize, SMEM_BYTES);
    cudaFuncSetAttribute(mha_fused_kernel<true>, cudaFuncAttributeMaxDynamicSharedMemorySize, SMEM_BYTES);
    int dev = 0;
    cudaGetDevice(&dev);
    cudaDeviceGetAttribute(&n_sm, cudaDevAttrMultiProcessorCount, dev);
  }
  Params P;
  for (int br = 0; br < 2; br++) {
    const void* x = d_in[br * 5 + 0]; const void* kc = d_in[br * 5 + 1]; const void* vc = d_in[br * 5 + 2];
    const void* wq = d_in[br * 5 + 3]; const void* wo = d_in[br * 5 + 4];
    { cuuint64_t d[2] = {DM, (cuuint64_t)NB * SQ}, s[1] = {DM * 2}; cuuint32_t b[2] = {64, 128}, b2[2] = {64, 96};
      make_map(enc, &P.x[0][br], x, 2, d, s, b, PR_X); make_map(enc, &P.x[1][br], x, 2, d, s, b2, PR_X); }
    { cuuint64_t d[3] = {64, DM, HD / 64}, s[2] = {HD * 2, 128}; cuuint32_t b[3] = {64, 64, 2}; make_map(enc, &P.wq[br], wq, 3, d, s, b, PR_W); }
    { cuuint64_t d[5] = {DM, 2, 4, 4, HD / 32}, s[4] = {DM * 2, 8 * DM * 2, 2 * DM * 2, 32 * DM * 2}; cuuint32_t b[5] = {64, 2, 4, 4, 2};
      make_map(enc, &P.wo[br], wo, 5, d, s, b, PR_W); }
    { cuuint64_t d[3] = {64, (cuuint64_t)NB * NH * SK, 2}, s[2] = {DH * 2, 128}; cuuint32_t b[3] = {64, 64, 2};
      make_map(enc, &P.kv[0][br], kc, 3, d, s, b, PR_KV); make_map(enc, &P.kv[1][br], vc, 3, d, s, b, PR_KV); }
    P.kp[br] = (const __nv_bfloat16*)kc; P.vp[br] = (const __nv_bfloat16*)vc;

  }
  { cuuint64_t d[2] = {64, (cuuint64_t)NBETA * 64 * SQ}, s[1] = {128}; cuuint32_t b[2] = {64, 128}, b2[2] = {64, 96};
    make_map(enc, &P.o_ld[0], o_ptr, 2, d, s, b, 2, CU_TENSOR_MAP_SWIZZLE_NONE); make_map(enc, &P.o_ld[1], o_ptr, 2, d, s, b2, 2, CU_TENSOR_MAP_SWIZZLE_NONE); }
  { cuuint64_t d[3] = {64, SQ, O_BLOCKS}, s[2] = {128, SQ * 128}; cuuint32_t b[3] = {64, 64, 2}, b2[3] = {64, 32, 2};
    make_map(enc, &P.o_st[0], o_ptr, 3, d, s, b); make_map(enc, &P.o_st[1], o_ptr, 3, d, s, b2); }
  { cuuint64_t d[3] = {64, (cuuint64_t)NB * SQ, 2 * DM / 64}, s[2] = {2 * DM * 2, 128}; cuuint32_t b[3] = {64, 64, 2}, b2[3] = {64, 32, 2};
    make_map(enc, &P.out_st[0], d_out, 3, d, s, b); make_map(enc, &P.out_st[1], d_out, 3, d, s, b2); }
  if (n_sm >= NCTA) mha_fused_kernel<false><<<NCTA, 384, SMEM_BYTES>>>(P);
  else mha_fused_kernel<true><<<n_sm, 384, SMEM_BYTES>>>(P);
}
```

```cpp
#include <cuda_runtime.h>
#include <cuda_bf16.h>
#include <cuda.h>
#include <stdint.h>
#include <stdlib.h>

namespace {

__device__ __forceinline__ void wgmma_proj(float (&d)[64], uint64_t da, uint64_t db, int scaleD) {
  asm volatile("{\n.reg .pred p;\nsetp.ne.b32 p, %66, 0;\n"
      "wgmma.mma_async.sync.aligned.m64n128k16.f32.bf16.bf16 "
      "{%0, %1, %2, %3, %4, %5, %6, %7, %8, %9, %10, %11, %12, %13, %14, %15, %16, %17, %18, %19, %20, %21, %22, %23, %24, %25, %26, %27, %28, %29, %30, "
      "%31, %32, %33, %34, %35, %36, %37, %38, %39, %40, %41, %42, %43, %44, %45, %46, %47, %48, %49, %50, %51, %52, %53, %54, %55, %56, %57, %58, %59, %60, "
      "%61, %62, %63}, "
      "%64, %65, p, 1, 1, 0, 1;\n}\n"
      : "+f"(d[0]), "+f"(d[1]), "+f"(d[2]), "+f"(d[3]), "+f"(d[4]), "+f"(d[5]), "+f"(d[6]), "+f"(d[7]), "+f"(d[8]), "+f"(d[9]), "+f"(d[10]), "+f"(d[11]),
        "+f"(d[12]), "+f"(d[13]), "+f"(d[14]), "+f"(d[15]), "+f"(d[16]), "+f"(d[17]), "+f"(d[18]), "+f"(d[19]), "+f"(d[20]), "+f"(d[21]), "+f"(d[22]),
        "+f"(d[23]), "+f"(d[24]), "+f"(d[25]), "+f"(d[26]), "+f"(d[27]), "+f"(d[28]), "+f"(d[29]), "+f"(d[30]), "+f"(d[31]), "+f"(d[32]), "+f"(d[33]),
        "+f"(d[34]), "+f"(d[35]), "+f"(d[36]), "+f"(d[37]), "+f"(d[38]), "+f"(d[39]), "+f"(d[40]), "+f"(d[41]), "+f"(d[42]), "+f"(d[43]), "+f"(d[44]),
        "+f"(d[45]), "+f"(d[46]), "+f"(d[47]), "+f"(d[48]), "+f"(d[49]), "+f"(d[50]), "+f"(d[51]), "+f"(d[52]), "+f"(d[53]), "+f"(d[54]), "+f"(d[55]),
        "+f"(d[56]), "+f"(d[57]), "+f"(d[58]), "+f"(d[59]), "+f"(d[60]), "+f"(d[61]), "+f"(d[62]), "+f"(d[63])
      : "l"(da), "l"(db), "r"(scaleD));
}
__device__ __forceinline__ void wgmma_proj96(float (&d)[64], uint64_t da, uint64_t db, int scaleD) {
  asm volatile("{\n.reg .pred p;\nsetp.ne.b32 p, %50, 0;\n"
      "wgmma.mma_async.sync.aligned.m64n96k16.f32.bf16.bf16 "
      "{%0, %1, %2, %3, %4, %5, %6, %7, %8, %9, %10, %11, %12, %13, %14, %15, %16, %17, %18, %19, %20, %21, %22, %23, %24, %25, %26, %27, %28, %29, %30, "
      "%31, %32, %33, %34, %35, %36, %37, %38, %39, %40, %41, %42, %43, %44, %45, %46, %47}, "
      "%48, %49, p, 1, 1, 1, 0;\n}\n"
      : "+f"(d[0]), "+f"(d[1]), "+f"(d[2]), "+f"(d[3]), "+f"(d[4]), "+f"(d[5]), "+f"(d[6]), "+f"(d[7]), "+f"(d[8]), "+f"(d[9]), "+f"(d[10]), "+f"(d[11]),
        "+f"(d[12]), "+f"(d[13]), "+f"(d[14]), "+f"(d[15]), "+f"(d[16]), "+f"(d[17]), "+f"(d[18]), "+f"(d[19]), "+f"(d[20]), "+f"(d[21]), "+f"(d[22]),
        "+f"(d[23]), "+f"(d[24]), "+f"(d[25]), "+f"(d[26]), "+f"(d[27]), "+f"(d[28]), "+f"(d[29]), "+f"(d[30]), "+f"(d[31]), "+f"(d[32]), "+f"(d[33]),
        "+f"(d[34]), "+f"(d[35]), "+f"(d[36]), "+f"(d[37]), "+f"(d[38]), "+f"(d[39]), "+f"(d[40]), "+f"(d[41]), "+f"(d[42]), "+f"(d[43]), "+f"(d[44]),
        "+f"(d[45]), "+f"(d[46]), "+f"(d[47])
      : "l"(da), "l"(db), "r"(scaleD));
}
__device__ __forceinline__ void wgmma_qk(float (&d)[32], uint64_t da, uint64_t db, int scaleD) {
  asm volatile("{\n.reg .pred p;\nsetp.ne.b32 p, %34, 0;\n"
      "wgmma.mma_async.sync.aligned.m64n64k16.f32.bf16.bf16 "
      "{%0, %1, %2, %3, %4, %5, %6, %7, %8, %9, %10, %11, %12, %13, %14, %15, %16, %17, %18, %19, %20, %21, %22, %23, %24, %25, %26, %27, %28, %29, %30, "
      "%31}, "
      "%32, %33, p, 1, 1, 0, 0;\n}\n"
      : "+f"(d[0]), "+f"(d[1]), "+f"(d[2]), "+f"(d[3]), "+f"(d[4]), "+f"(d[5]), "+f"(d[6]), "+f"(d[7]), "+f"(d[8]), "+f"(d[9]), "+f"(d[10]), "+f"(d[11]),
        "+f"(d[12]), "+f"(d[13]), "+f"(d[14]), "+f"(d[15]), "+f"(d[16]), "+f"(d[17]), "+f"(d[18]), "+f"(d[19]), "+f"(d[20]), "+f"(d[21]), "+f"(d[22]),
        "+f"(d[23]), "+f"(d[24]), "+f"(d[25]), "+f"(d[26]), "+f"(d[27]), "+f"(d[28]), "+f"(d[29]), "+f"(d[30]), "+f"(d[31])
      : "l"(da), "l"(db), "r"(scaleD));
}
__device__ __forceinline__ void wgmma_qk_rs(float (&d)[32], uint32_t a0, uint32_t a1, uint32_t a2, uint32_t a3, uint64_t db, int scaleD) {
  asm volatile("{\n.reg .pred p;\nsetp.ne.b32 p, %37, 0;\n"
      "wgmma.mma_async.sync.aligned.m64n64k16.f32.bf16.bf16 "
      "{%0, %1, %2, %3, %4, %5, %6, %7, %8, %9, %10, %11, %12, %13, %14, %15, %16, %17, %18, %19, %20, %21, %22, %23, %24, %25, %26, %27, %28, %29, %30, "
      "%31}, "
      "{%32, %33, %34, %35}, %36, p, 1, 1, 0;\n}\n"
      : "+f"(d[0]), "+f"(d[1]), "+f"(d[2]), "+f"(d[3]), "+f"(d[4]), "+f"(d[5]), "+f"(d[6]), "+f"(d[7]), "+f"(d[8]), "+f"(d[9]), "+f"(d[10]), "+f"(d[11]),
        "+f"(d[12]), "+f"(d[13]), "+f"(d[14]), "+f"(d[15]), "+f"(d[16]), "+f"(d[17]), "+f"(d[18]), "+f"(d[19]), "+f"(d[20]), "+f"(d[21]), "+f"(d[22]),
        "+f"(d[23]), "+f"(d[24]), "+f"(d[25]), "+f"(d[26]), "+f"(d[27]), "+f"(d[28]), "+f"(d[29]), "+f"(d[30]), "+f"(d[31])
      : "r"(a0), "r"(a1), "r"(a2), "r"(a3), "l"(db), "r"(scaleD));
}
__device__ __forceinline__ void wgmma_pv(float (&d)[64], uint32_t a0, uint32_t a1, uint32_t a2, uint32_t a3, uint64_t db, int scaleD) {
  asm volatile("{\n.reg .pred p;\nsetp.ne.b32 p, %69, 0;\n"
      "wgmma.mma_async.sync.aligned.m64n128k16.f32.bf16.bf16 "
      "{%0, %1, %2, %3, %4, %5, %6, %7, %8, %9, %10, %11, %12, %13, %14, %15, %16, %17, %18, %19, %20, %21, %22, %23, %24, %25, %26, %27, %28, %29, %30, "
      "%31, %32, %33, %34, %35, %36, %37, %38, %39, %40, %41, %42, %43, %44, %45, %46, %47, %48, %49, %50, %51, %52, %53, %54, %55, %56, %57, %58, %59, %60, "
      "%61, %62, %63}, "
      "{%64, %65, %66, %67}, %68, p, 1, 1, 1;\n}\n"
      : "+f"(d[0]), "+f"(d[1]), "+f"(d[2]), "+f"(d[3]), "+f"(d[4]), "+f"(d[5]), "+f"(d[6]), "+f"(d[7]), "+f"(d[8]), "+f"(d[9]), "+f"(d[10]), "+f"(d[11]),
        "+f"(d[12]), "+f"(d[13]), "+f"(d[14]), "+f"(d[15]), "+f"(d[16]), "+f"(d[17]), "+f"(d[18]), "+f"(d[19]), "+f"(d[20]), "+f"(d[21]), "+f"(d[22]),
        "+f"(d[23]), "+f"(d[24]), "+f"(d[25]), "+f"(d[26]), "+f"(d[27]), "+f"(d[28]), "+f"(d[29]), "+f"(d[30]), "+f"(d[31]), "+f"(d[32]), "+f"(d[33]),
        "+f"(d[34]), "+f"(d[35]), "+f"(d[36]), "+f"(d[37]), "+f"(d[38]), "+f"(d[39]), "+f"(d[40]), "+f"(d[41]), "+f"(d[42]), "+f"(d[43]), "+f"(d[44]),
        "+f"(d[45]), "+f"(d[46]), "+f"(d[47]), "+f"(d[48]), "+f"(d[49]), "+f"(d[50]), "+f"(d[51]), "+f"(d[52]), "+f"(d[53]), "+f"(d[54]), "+f"(d[55]),
        "+f"(d[56]), "+f"(d[57]), "+f"(d[58]), "+f"(d[59]), "+f"(d[60]), "+f"(d[61]), "+f"(d[62]), "+f"(d[63])
      : "r"(a0), "r"(a1), "r"(a2), "r"(a3), "l"(db), "r"(scaleD));
}
__device__ __forceinline__ void wgmma_qk_sp(float (&d)[32], uint32_t a0, uint32_t a1, uint32_t a2, uint32_t a3, uint64_t db, int scaleD, uint32_t meta) {
  asm volatile("{\n.reg .pred p;\nsetp.ne.b32 p, %37, 0;\n"
      "wgmma.mma_async.sp.sync.aligned.m64n64k32.f32.bf16.bf16 "
      "{%0, %1, %2, %3, %4, %5, %6, %7, %8, %9, %10, %11, %12, %13, %14, %15, %16, %17, %18, %19, %20, %21, %22, %23, %24, %25, %26, %27, %28, %29, %30, "
      "%31}, "
      "{%32, %33, %34, %35}, %36, %38, 0, p, 1, 1, 0;\n}\n"
      : "+f"(d[0]), "+f"(d[1]), "+f"(d[2]), "+f"(d[3]), "+f"(d[4]), "+f"(d[5]), "+f"(d[6]), "+f"(d[7]), "+f"(d[8]), "+f"(d[9]), "+f"(d[10]), "+f"(d[11]),
        "+f"(d[12]), "+f"(d[13]), "+f"(d[14]), "+f"(d[15]), "+f"(d[16]), "+f"(d[17]), "+f"(d[18]), "+f"(d[19]), "+f"(d[20]), "+f"(d[21]), "+f"(d[22]),
        "+f"(d[23]), "+f"(d[24]), "+f"(d[25]), "+f"(d[26]), "+f"(d[27]), "+f"(d[28]), "+f"(d[29]), "+f"(d[30]), "+f"(d[31])
      : "r"(a0), "r"(a1), "r"(a2), "r"(a3), "l"(db), "r"(scaleD), "r"(meta));
}
__device__ __forceinline__ void wgmma_pv_sp(float (&d)[64], uint32_t a0, uint32_t a1, uint32_t a2, uint32_t a3, uint64_t db, int scaleD, uint32_t meta) {
  asm volatile("{\n.reg .pred p;\nsetp.ne.b32 p, %69, 0;\n"
      "wgmma.mma_async.sp.sync.aligned.m64n128k32.f32.bf16.bf16 "
      "{%0, %1, %2, %3, %4, %5, %6, %7, %8, %9, %10, %11, %12, %13, %14, %15, %16, %17, %18, %19, %20, %21, %22, %23, %24, %25, %26, %27, %28, %29, %30, "
      "%31, %32, %33, %34, %35, %36, %37, %38, %39, %40, %41, %42, %43, %44, %45, %46, %47, %48, %49, %50, %51, %52, %53, %54, %55, %56, %57, %58, %59, %60, "
      "%61, %62, %63}, "
      "{%64, %65, %66, %67}, %68, %70, 0, p, 1, 1, 1;\n}\n"
      : "+f"(d[0]), "+f"(d[1]), "+f"(d[2]), "+f"(d[3]), "+f"(d[4]), "+f"(d[5]), "+f"(d[6]), "+f"(d[7]), "+f"(d[8]), "+f"(d[9]), "+f"(d[10]), "+f"(d[11]),
        "+f"(d[12]), "+f"(d[13]), "+f"(d[14]), "+f"(d[15]), "+f"(d[16]), "+f"(d[17]), "+f"(d[18]), "+f"(d[19]), "+f"(d[20]), "+f"(d[21]), "+f"(d[22]),
        "+f"(d[23]), "+f"(d[24]), "+f"(d[25]), "+f"(d[26]), "+f"(d[27]), "+f"(d[28]), "+f"(d[29]), "+f"(d[30]), "+f"(d[31]), "+f"(d[32]), "+f"(d[33]),
        "+f"(d[34]), "+f"(d[35]), "+f"(d[36]), "+f"(d[37]), "+f"(d[38]), "+f"(d[39]), "+f"(d[40]), "+f"(d[41]), "+f"(d[42]), "+f"(d[43]), "+f"(d[44]),
        "+f"(d[45]), "+f"(d[46]), "+f"(d[47]), "+f"(d[48]), "+f"(d[49]), "+f"(d[50]), "+f"(d[51]), "+f"(d[52]), "+f"(d[53]), "+f"(d[54]), "+f"(d[55]),
        "+f"(d[56]), "+f"(d[57]), "+f"(d[58]), "+f"(d[59]), "+f"(d[60]), "+f"(d[61]), "+f"(d[62]), "+f"(d[63])
      : "r"(a0), "r"(a1), "r"(a2), "r"(a3), "l"(db), "r"(scaleD), "r"(meta));
}
__device__ __forceinline__ void wgmma_proj_init(float (&d)[64], uint64_t da, uint64_t db, int scaleD) {
  asm volatile("{\n.reg .pred p;\nsetp.ne.b32 p, %66, 0;\n"
      "wgmma.mma_async.sync.aligned.m64n128k16.f32.bf16.bf16 "
      "{%0, %1, %2, %3, %4, %5, %6, %7, %8, %9, %10, %11, %12, %13, %14, %15, %16, %17, %18, %19, %20, %21, %22, %23, %24, %25, %26, %27, %28, %29, %30, "
      "%31, %32, %33, %34, %35, %36, %37, %38, %39, %40, %41, %42, %43, %44, %45, %46, %47, %48, %49, %50, %51, %52, %53, %54, %55, %56, %57, %58, %59, %60, "
      "%61, %62, %63}, "
      "%64, %65, p, 1, 1, 0, 1;\n}\n"
      : "=f"(d[0]), "=f"(d[1]), "=f"(d[2]), "=f"(d[3]), "=f"(d[4]), "=f"(d[5]), "=f"(d[6]), "=f"(d[7]), "=f"(d[8]), "=f"(d[9]), "=f"(d[10]), "=f"(d[11]),
        "=f"(d[12]), "=f"(d[13]), "=f"(d[14]), "=f"(d[15]), "=f"(d[16]), "=f"(d[17]), "=f"(d[18]), "=f"(d[19]), "=f"(d[20]), "=f"(d[21]), "=f"(d[22]),
        "=f"(d[23]), "=f"(d[24]), "=f"(d[25]), "=f"(d[26]), "=f"(d[27]), "=f"(d[28]), "=f"(d[29]), "=f"(d[30]), "=f"(d[31]), "=f"(d[32]), "=f"(d[33]),
        "=f"(d[34]), "=f"(d[35]), "=f"(d[36]), "=f"(d[37]), "=f"(d[38]), "=f"(d[39]), "=f"(d[40]), "=f"(d[41]), "=f"(d[42]), "=f"(d[43]), "=f"(d[44]),
        "=f"(d[45]), "=f"(d[46]), "=f"(d[47]), "=f"(d[48]), "=f"(d[49]), "=f"(d[50]), "=f"(d[51]), "=f"(d[52]), "=f"(d[53]), "=f"(d[54]), "=f"(d[55]),
        "=f"(d[56]), "=f"(d[57]), "=f"(d[58]), "=f"(d[59]), "=f"(d[60]), "=f"(d[61]), "=f"(d[62]), "=f"(d[63])
      : "l"(da), "l"(db), "r"(scaleD));
}
__device__ __forceinline__ void wgmma_proj96_init(float (&d)[64], uint64_t da, uint64_t db, int scaleD) {
  asm volatile("{\n.reg .pred p;\nsetp.ne.b32 p, %50, 0;\n"
      "wgmma.mma_async.sync.aligned.m64n96k16.f32.bf16.bf16 "
      "{%0, %1, %2, %3, %4, %5, %6, %7, %8, %9, %10, %11, %12, %13, %14, %15, %16, %17, %18, %19, %20, %21, %22, %23, %24, %25, %26, %27, %28, %29, %30, "
      "%31, %32, %33, %34, %35, %36, %37, %38, %39, %40, %41, %42, %43, %44, %45, %46, %47}, "
      "%48, %49, p, 1, 1, 1, 0;\n}\n"
      : "=f"(d[0]), "=f"(d[1]), "=f"(d[2]), "=f"(d[3]), "=f"(d[4]), "=f"(d[5]), "=f"(d[6]), "=f"(d[7]), "=f"(d[8]), "=f"(d[9]), "=f"(d[10]), "=f"(d[11]),
        "=f"(d[12]), "=f"(d[13]), "=f"(d[14]), "=f"(d[15]), "=f"(d[16]), "=f"(d[17]), "=f"(d[18]), "=f"(d[19]), "=f"(d[20]), "=f"(d[21]), "=f"(d[22]),
        "=f"(d[23]), "=f"(d[24]), "=f"(d[25]), "=f"(d[26]), "=f"(d[27]), "=f"(d[28]), "=f"(d[29]), "=f"(d[30]), "=f"(d[31]), "=f"(d[32]), "=f"(d[33]),
        "=f"(d[34]), "=f"(d[35]), "=f"(d[36]), "=f"(d[37]), "=f"(d[38]), "=f"(d[39]), "=f"(d[40]), "=f"(d[41]), "=f"(d[42]), "=f"(d[43]), "=f"(d[44]),
        "=f"(d[45]), "=f"(d[46]), "=f"(d[47])
      : "l"(da), "l"(db), "r"(scaleD));
}
__device__ __forceinline__ void wgmma_qk_init(float (&d)[32], uint64_t da, uint64_t db, int scaleD) {
  asm volatile("{\n.reg .pred p;\nsetp.ne.b32 p, %34, 0;\n"
      "wgmma.mma_async.sync.aligned.m64n64k16.f32.bf16.bf16 "
      "{%0, %1, %2, %3, %4, %5, %6, %7, %8, %9, %10, %11, %12, %13, %14, %15, %16, %17, %18, %19, %20, %21, %22, %23, %24, %25, %26, %27, %28, %29, %30, "
      "%31}, "
      "%32, %33, p, 1, 1, 0, 0;\n}\n"
      : "=f"(d[0]), "=f"(d[1]), "=f"(d[2]), "=f"(d[3]), "=f"(d[4]), "=f"(d[5]), "=f"(d[6]), "=f"(d[7]), "=f"(d[8]), "=f"(d[9]), "=f"(d[10]), "=f"(d[11]),
        "=f"(d[12]), "=f"(d[13]), "=f"(d[14]), "=f"(d[15]), "=f"(d[16]), "=f"(d[17]), "=f"(d[18]), "=f"(d[19]), "=f"(d[20]), "=f"(d[21]), "=f"(d[22]),
        "=f"(d[23]), "=f"(d[24]), "=f"(d[25]), "=f"(d[26]), "=f"(d[27]), "=f"(d[28]), "=f"(d[29]), "=f"(d[30]), "=f"(d[31])
      : "l"(da), "l"(db), "r"(scaleD));
}
__device__ __forceinline__ void wgmma_qk_rs_init(float (&d)[32], uint32_t a0, uint32_t a1, uint32_t a2, uint32_t a3, uint64_t db, int scaleD) {
  asm volatile("{\n.reg .pred p;\nsetp.ne.b32 p, %37, 0;\n"
      "wgmma.mma_async.sync.aligned.m64n64k16.f32.bf16.bf16 "
      "{%0, %1, %2, %3, %4, %5, %6, %7, %8, %9, %10, %11, %12, %13, %14, %15, %16, %17, %18, %19, %20, %21, %22, %23, %24, %25, %26, %27, %28, %29, %30, "
      "%31}, "
      "{%32, %33, %34, %35}, %36, p, 1, 1, 0;\n}\n"
      : "=f"(d[0]), "=f"(d[1]), "=f"(d[2]), "=f"(d[3]), "=f"(d[4]), "=f"(d[5]), "=f"(d[6]), "=f"(d[7]), "=f"(d[8]), "=f"(d[9]), "=f"(d[10]), "=f"(d[11]),
        "=f"(d[12]), "=f"(d[13]), "=f"(d[14]), "=f"(d[15]), "=f"(d[16]), "=f"(d[17]), "=f"(d[18]), "=f"(d[19]), "=f"(d[20]), "=f"(d[21]), "=f"(d[22]),
        "=f"(d[23]), "=f"(d[24]), "=f"(d[25]), "=f"(d[26]), "=f"(d[27]), "=f"(d[28]), "=f"(d[29]), "=f"(d[30]), "=f"(d[31])
      : "r"(a0), "r"(a1), "r"(a2), "r"(a3), "l"(db), "r"(scaleD));
}
__device__ __forceinline__ void wgmma_pv_init(float (&d)[64], uint32_t a0, uint32_t a1, uint32_t a2, uint32_t a3, uint64_t db, int scaleD) {
  asm volatile("{\n.reg .pred p;\nsetp.ne.b32 p, %69, 0;\n"
      "wgmma.mma_async.sync.aligned.m64n128k16.f32.bf16.bf16 "
      "{%0, %1, %2, %3, %4, %5, %6, %7, %8, %9, %10, %11, %12, %13, %14, %15, %16, %17, %18, %19, %20, %21, %22, %23, %24, %25, %26, %27, %28, %29, %30, "
      "%31, %32, %33, %34, %35, %36, %37, %38, %39, %40, %41, %42, %43, %44, %45, %46, %47, %48, %49, %50, %51, %52, %53, %54, %55, %56, %57, %58, %59, %60, "
      "%61, %62, %63}, "
      "{%64, %65, %66, %67}, %68, p, 1, 1, 1;\n}\n"
      : "=f"(d[0]), "=f"(d[1]), "=f"(d[2]), "=f"(d[3]), "=f"(d[4]), "=f"(d[5]), "=f"(d[6]), "=f"(d[7]), "=f"(d[8]), "=f"(d[9]), "=f"(d[10]), "=f"(d[11]),
        "=f"(d[12]), "=f"(d[13]), "=f"(d[14]), "=f"(d[15]), "=f"(d[16]), "=f"(d[17]), "=f"(d[18]), "=f"(d[19]), "=f"(d[20]), "=f"(d[21]), "=f"(d[22]),
        "=f"(d[23]), "=f"(d[24]), "=f"(d[25]), "=f"(d[26]), "=f"(d[27]), "=f"(d[28]), "=f"(d[29]), "=f"(d[30]), "=f"(d[31]), "=f"(d[32]), "=f"(d[33]),
        "=f"(d[34]), "=f"(d[35]), "=f"(d[36]), "=f"(d[37]), "=f"(d[38]), "=f"(d[39]), "=f"(d[40]), "=f"(d[41]), "=f"(d[42]), "=f"(d[43]), "=f"(d[44]),
        "=f"(d[45]), "=f"(d[46]), "=f"(d[47]), "=f"(d[48]), "=f"(d[49]), "=f"(d[50]), "=f"(d[51]), "=f"(d[52]), "=f"(d[53]), "=f"(d[54]), "=f"(d[55]),
        "=f"(d[56]), "=f"(d[57]), "=f"(d[58]), "=f"(d[59]), "=f"(d[60]), "=f"(d[61]), "=f"(d[62]), "=f"(d[63])
      : "r"(a0), "r"(a1), "r"(a2), "r"(a3), "l"(db), "r"(scaleD));
}
__device__ __forceinline__ void wgmma_qk_sp_init(float (&d)[32], uint32_t a0, uint32_t a1, uint32_t a2, uint32_t a3, uint64_t db, int scaleD, uint32_t meta) {
  asm volatile("{\n.reg .pred p;\nsetp.ne.b32 p, %37, 0;\n"
      "wgmma.mma_async.sp.sync.aligned.m64n64k32.f32.bf16.bf16 "
      "{%0, %1, %2, %3, %4, %5, %6, %7, %8, %9, %10, %11, %12, %13, %14, %15, %16, %17, %18, %19, %20, %21, %22, %23, %24, %25, %26, %27, %28, %29, %30, "
      "%31}, "
      "{%32, %33, %34, %35}, %36, %38, 0, p, 1, 1, 0;\n}\n"
      : "=f"(d[0]), "=f"(d[1]), "=f"(d[2]), "=f"(d[3]), "=f"(d[4]), "=f"(d[5]), "=f"(d[6]), "=f"(d[7]), "=f"(d[8]), "=f"(d[9]), "=f"(d[10]), "=f"(d[11]),
        "=f"(d[12]), "=f"(d[13]), "=f"(d[14]), "=f"(d[15]), "=f"(d[16]), "=f"(d[17]), "=f"(d[18]), "=f"(d[19]), "=f"(d[20]), "=f"(d[21]), "=f"(d[22]),
        "=f"(d[23]), "=f"(d[24]), "=f"(d[25]), "=f"(d[26]), "=f"(d[27]), "=f"(d[28]), "=f"(d[29]), "=f"(d[30]), "=f"(d[31])
      : "r"(a0), "r"(a1), "r"(a2), "r"(a3), "l"(db), "r"(scaleD), "r"(meta));
}
__device__ __forceinline__ void wgmma_pv_sp_init(float (&d)[64], uint32_t a0, uint32_t a1, uint32_t a2, uint32_t a3, uint64_t db, int scaleD, uint32_t meta) {
  asm volatile("{\n.reg .pred p;\nsetp.ne.b32 p, %69, 0;\n"
      "wgmma.mma_async.sp.sync.aligned.m64n128k32.f32.bf16.bf16 "
      "{%0, %1, %2, %3, %4, %5, %6, %7, %8, %9, %10, %11, %12, %13, %14, %15, %16, %17, %18, %19, %20, %21, %22, %23, %24, %25, %26, %27, %28, %29, %30, "
      "%31, %32, %33, %34, %35, %36, %37, %38, %39, %40, %41, %42, %43, %44, %45, %46, %47, %48, %49, %50, %51, %52, %53, %54, %55, %56, %57, %58, %59, %60, "
      "%61, %62, %63}, "
      "{%64, %65, %66, %67}, %68, %70, 0, p, 1, 1, 1;\n}\n"
      : "=f"(d[0]), "=f"(d[1]), "=f"(d[2]), "=f"(d[3]), "=f"(d[4]), "=f"(d[5]), "=f"(d[6]), "=f"(d[7]), "=f"(d[8]), "=f"(d[9]), "=f"(d[10]), "=f"(d[11]),
        "=f"(d[12]), "=f"(d[13]), "=f"(d[14]), "=f"(d[15]), "=f"(d[16]), "=f"(d[17]), "=f"(d[18]), "=f"(d[19]), "=f"(d[20]), "=f"(d[21]), "=f"(d[22]),
        "=f"(d[23]), "=f"(d[24]), "=f"(d[25]), "=f"(d[26]), "=f"(d[27]), "=f"(d[28]), "=f"(d[29]), "=f"(d[30]), "=f"(d[31]), "=f"(d[32]), "=f"(d[33]),
        "=f"(d[34]), "=f"(d[35]), "=f"(d[36]), "=f"(d[37]), "=f"(d[38]), "=f"(d[39]), "=f"(d[40]), "=f"(d[41]), "=f"(d[42]), "=f"(d[43]), "=f"(d[44]),
        "=f"(d[45]), "=f"(d[46]), "=f"(d[47]), "=f"(d[48]), "=f"(d[49]), "=f"(d[50]), "=f"(d[51]), "=f"(d[52]), "=f"(d[53]), "=f"(d[54]), "=f"(d[55]),
        "=f"(d[56]), "=f"(d[57]), "=f"(d[58]), "=f"(d[59]), "=f"(d[60]), "=f"(d[61]), "=f"(d[62]), "=f"(d[63])
      : "r"(a0), "r"(a1), "r"(a2), "r"(a3), "l"(db), "r"(scaleD), "r"(meta));
}

constexpr int NB = 16, SQ = 224, DM = 640, NH = 32, SK = 1024, DH = 128;
constexpr int HD = NH * DH;
constexpr int NBETA = 2 * NB;
constexpr int NCTA = 132;
constexpr int NS = 10;
constexpr int SLOT = 16384;
constexpr int QBUF_OFF = NS * SLOT;
constexpr int NSX = NS + 4;
constexpr int BAR_OFF = NSX * SLOT;
constexpr int BAR_FULL = BAR_OFF;
constexpr int BAR_EMPTY = BAR_OFF + 8 * NSX;
constexpr int BAR_STG = BAR_OFF + 16 * NSX;
constexpr int BAR_OUT = BAR_STG + 32;
constexpr int BAR_DESC = BAR_OUT + 8;
constexpr int BAR_GO = BAR_DESC + 8;
constexpr int DESC_OFF = BAR_GO + 8;
constexpr int EPOCH_OFF = DESC_OFF + 16;
constexpr int TRACE_OFF = EPOCH_OFF + 8;
constexpr int SMEM_BYTES = TRACE_OFF;
constexpr float SM_C = 0.08838834764831845f * 1.4426950408889634f;
constexpr float SUM_HI = 1099511627776.f, SUM_LO = 1.f / 1099511627776.f;
constexpr uint32_t META_QK = 0xEEEE4444u;
constexpr uint32_t META_PV = 0x44EEEE44u;

#define QK_EARLY_MASK 3
#define ST_ORDER 0x2310
#define LAG_BAR 5
#define ST_NOW 8
#define PF_STEP 5
#define KV_WIN_UNITS 2
#define KV_WIN_D 4
#define SF 0xfe1f
#define O_STEPS 4
#define KV_WIN_RAMP 4
#define PDEPTH 0
#define KV_WIN_TILES -2
#define PR_KV 2
#define PR_X 2
#define PR_W 2
#define REG_C 232
#define REG_P 24
#define GO_P 4
#define P_POS 216
#define OR 6
#define OR0 2
#define EARLY_BEGIN 0
#define B_LATE 23
#define H_LATE 24
#define NQR 1
#define NQR1 5
#define NQR2 0
#define SKIP_ST 2
#define KG 5
#define PK 44
#define EARLY_MASK 0x7fffu
#define PIECE_TABLE 0x403f8812,0x80000000,0x403f301c,0x80000000,0x502fa015,0x6d0ba05f,0x50105019,0x652b5038,0x502f780f,0x6d4a7830,0x50348010,0x80000000,0x5019681a,0x685e6831,0x501d2013,0x69d82036,0x502ec817,0x80000000,0x50207011,0x6c0f702f,0x642f3834,0x80000000,0x501d981b,0x6c0f9835,0x50262816,0x80000000,0x65a9b83d,0x80000000,0x5015c01d,0x6bd0c037,0x66a5603a,0x80000000,0x545d4819,0x80000000,0x535d081e,0x80000000,0x500f4014,0x6bd04059,0x565aa81f,0x80000000,0x67a1903b,0x80000000,0x5018b01f,0x80000000,0x57951813,0x80000000,0x500c101e,0x6d0b1053,0x50135818,0x80000000,0x6ad4005e,0x80000000

struct Params {
  CUtensorMap x[2][2], wq[2], kv[2][2], wo[2];
  CUtensorMap o_ld[2], o_st[2], out_st[2];
  const __nv_bfloat16* kp[2];
  const __nv_bfloat16* vp[2];
};

constexpr int NPART = 32 * 5, O_BLOCKS = NBETA * 64 + 2 * NPART;
__device__ __align__(128) __nv_bfloat16 g_o[(size_t)O_BLOCKS * SQ * 64];
__device__ unsigned g_cnt[NBETA][8];
__device__ unsigned g_rd[NBETA][8];
__device__ unsigned g_epoch, g_next;
__device__ unsigned g_flag[NPART];

__device__ __forceinline__ uint32_t smem_u32(const void* p) { return (uint32_t)__cvta_generic_to_shared(p); }
__device__ __forceinline__ void mbar_arrive(uint32_t bar) {
  asm volatile("mbarrier.arrive.shared::cta.b64 _, [%0];" ::"r"(bar) : "memory");
}
__device__ __forceinline__ void mbar_arrive_warp(uint32_t bar) {
  asm volatile("{\n.reg .pred p;\nelect.sync _|p, 0xffffffff;\n@p mbarrier.arrive.shared::cta.b64 _, [%0];\n}" ::"r"(bar) : "memory");
}
__device__ __forceinline__ int lane_now() { int l; asm volatile("mov.u32 %0, %%laneid;" : "=r"(l)); return l; }
__device__ __forceinline__ bool mbar_try(uint32_t bar, uint32_t parity) {
  uint32_t ok;
  asm volatile("{\n.reg .pred p;\nmbarrier.try_wait.parity.shared::cta.b64 p, [%1], %2;\nselp.u32 %0, 1, 0, p;\n}"
               : "=r"(ok) : "r"(bar), "r"(parity) : "memory");
  return ok;
}
__device__ __forceinline__ bool mbar_test(uint32_t bar, uint32_t parity) {
  uint32_t ok;
  asm volatile("{\n.reg .pred p;\nmbarrier.test_wait.parity.shared::cta.b64 p, [%1], %2;\nselp.u32 %0, 1, 0, p;\n}"
               : "=r"(ok) : "r"(bar), "r"(parity) : "memory");
  return ok;
}
__device__ __forceinline__ void mbar_wait_w(uint32_t bar, uint32_t parity) {
  uint32_t n = 0;
  while (!__all_sync(0xffffffffu, mbar_try(bar, parity))) {
    if (++n > (1u << 22)) __trap();
  }
}
#define ELECT "{\n.reg .pred p;\nelect.sync _|p, 0xffffffff;\n@p "
__device__ __forceinline__ void tma_st3_hint_w(const CUtensorMap* m, uint32_t src, int c0, int c1, int c2, uint64_t pol) {
  asm volatile(ELECT "cp.async.bulk.tensor.3d.global.shared::cta.bulk_group.L2::cache_hint [%0, {%2, %3, %4}], [%1], %5;\n}"
               ::"l"(m), "r"(src), "r"(c0), "r"(c1), "r"(c2), "l"(pol) : "memory");
}
#define EXPECT(bar, bytes) "mbarrier.arrive.expect_tx.shared::cta.b64 _, [" bar "], " bytes ";\n@p "
__device__ __forceinline__ void tma_ld2_w(uint32_t dst, const CUtensorMap* m, int c0, int c1, uint32_t bar, uint32_t bytes) {
  asm volatile(ELECT EXPECT("%2", "%5") "cp.async.bulk.tensor.2d.shared::cluster.global.mbarrier::complete_tx::bytes [%0], [%1, {%3, %4}], [%2];\n}"
               ::"r"(dst), "l"(m), "r"(bar), "r"(c0), "r"(c1), "r"(bytes) : "memory");
}
__device__ __forceinline__ void tma_ld2_hint_w(uint32_t dst, const CUtensorMap* m, int c0, int c1, uint32_t bar, uint32_t bytes, uint64_t pol) {
  asm volatile(ELECT EXPECT("%2", "%6") "cp.async.bulk.tensor.2d.shared::cluster.global.mbarrier::complete_tx::bytes.L2::cache_hint"
               " [%0], [%1, {%3, %4}], [%2], %5;\n}"
               ::"r"(dst), "l"(m), "r"(bar), "r"(c0), "r"(c1), "l"(pol), "r"(bytes) : "memory");
}
__device__ __forceinline__ void tma_ld3_w(uint32_t dst, const CUtensorMap* m, int c0, int c1, int c2, uint32_t bar, uint32_t bytes) {
  asm volatile(ELECT EXPECT("%2", "%6") "cp.async.bulk.tensor.3d.shared::cluster.global.mbarrier::complete_tx::bytes [%0], [%1, {%3, %4, %5}], [%2];\n}"
               ::"r"(dst), "l"(m), "r"(bar), "r"(c0), "r"(c1), "r"(c2), "r"(bytes) : "memory");
}
__device__ __forceinline__ void tma_ld3_hint_w(uint32_t dst, const CUtensorMap* m, int c0, int c1, int c2, uint32_t bar, uint64_t pol) {
  asm volatile(ELECT EXPECT("%2", "16384") "cp.async.bulk.tensor.3d.shared::cluster.global.mbarrier::complete_tx::bytes.L2::cache_hint"
               " [%0], [%1, {%3, %4, %5}], [%2], %6;\n}"
               ::"r"(dst), "l"(m), "r"(bar), "r"(c0), "r"(c1), "r"(c2), "l"(pol) : "memory");
}
__device__ __forceinline__ void tma_ld_wo_w(uint32_t dst, const CUtensorMap* m, int col, int grp, uint32_t bar) {
  asm volatile(ELECT EXPECT("%2", "16384") "cp.async.bulk.tensor.5d.shared::cluster.global.mbarrier::complete_tx::bytes [%0], [%1, {%3, 0, 0, 0, %4}], [%2];\n"
               "@p cp.async.bulk.tensor.5d.shared::cluster.global.mbarrier::complete_tx::bytes [%5], [%1, {%6, 0, 0, 0, %4}], [%2];\n}"
               ::"r"(dst), "l"(m), "r"(bar), "r"(col), "r"(grp), "r"(dst + 8192), "r"(col + 64) : "memory");
}
__device__ __forceinline__ void mbar_arrive8_w(uint32_t bar) {
  asm volatile(ELECT "mbarrier.arrive.shared::cta.b64 _, [%0], 8;\n}" ::"r"(bar) : "memory");
}
__device__ __forceinline__ void bulk_commit() { asm volatile("cp.async.bulk.commit_group;" ::: "memory"); }
template <int N> __device__ __forceinline__ void bulk_wait_read() { asm volatile("cp.async.bulk.wait_group.read %0;" ::"n"(N) : "memory"); }
__device__ __forceinline__ void wg_fence() { asm volatile("wgmma.fence.sync.aligned;" ::: "memory"); }
__device__ __forceinline__ void wg_commit() { asm volatile("wgmma.commit_group.sync.aligned;" ::: "memory"); }
template <int N> __device__ __forceinline__ void wg_wait() { asm volatile("wgmma.wait_group.sync.aligned %0;" ::"n"(N) : "memory"); }
__device__ __forceinline__ void fence_async_smem() { asm volatile("fence.proxy.async.shared::cta;" ::: "memory"); }
__device__ __forceinline__ void bar_sync(int id, int n) { asm volatile("bar.sync %0, %1;" ::"r"(id), "r"(n) : "memory"); }
__device__ __forceinline__ void touch(float& a) { asm volatile("neg.f32 %0, %0;" : "+f"(a)); }
__device__ __forceinline__ void touch(uint32_t& a) { asm volatile("not.b32 %0, %0;" : "+r"(a)); }
template <typename T, int N> __device__ __forceinline__ void touch(T (&a)[N]) {
#pragma unroll
  for (int i = 0; i < N; i++) touch(a[i]);
}
template <int ID, typename... A> __device__ __forceinline__ void sched_fence(uint32_t x, A&... a) {
  if (!((SF >> ID) & 1)) return;
  asm volatile("" : "+r"(x)::"memory");
#pragma unroll 1
  for (; __builtin_expect(x >= 100 + ID, 0); x >>= 1) { (touch(a), ...); __nanosleep(x); }
}
template <int N> __device__ __forceinline__ void reg_fence(float (&a)[N]) {
#pragma unroll
  for (int i = 0; i < N; i++) asm volatile("" : "+f"(a[i])::"memory");
}
template <int N> __device__ __forceinline__ void reg_fence(uint32_t (&a)[N]) {
#pragma unroll
  for (int i = 0; i < N; i++) asm volatile("" : "+r"(a[i])::"memory");
}
__device__ __forceinline__ float ex2(float x) { float y; asm("ex2.approx.ftz.f32 %0, %1;" : "=f"(y) : "f"(x)); return y; }
__device__ __forceinline__ uint32_t pack_bf16(float lo, float hi) {
  uint32_t r; asm("cvt.rn.bf16x2.f32 %0, %1, %2;" : "=r"(r) : "f"(hi), "f"(lo)); return r;
}
__device__ __forceinline__ void stsm4(uint32_t a, uint32_t r0, uint32_t r1, uint32_t r2, uint32_t r3) {
  asm volatile("stmatrix.sync.aligned.m8n8.x4.shared.b16 [%0], {%1, %2, %3, %4};" ::"r"(a), "r"(r0), "r"(r1), "r"(r2), "r"(r3) : "memory");
}
__device__ __forceinline__ void stsm4t(uint32_t a, uint32_t r0, uint32_t r1, uint32_t r2, uint32_t r3) {
  asm volatile("stmatrix.sync.aligned.m8n8.x4.trans.shared.b16 [%0], {%1, %2, %3, %4};" ::"r"(a), "r"(r0), "r"(r1), "r"(r2), "r"(r3) : "memory");
}
__device__ __forceinline__ void ldsm4(uint32_t a, uint32_t& r0, uint32_t& r1, uint32_t& r2, uint32_t& r3) {
  asm volatile("ldmatrix.sync.aligned.m8n8.x4.shared.b16 {%0, %1, %2, %3}, [%4];" : "=r"(r0), "=r"(r1), "=r"(r2), "=r"(r3) : "r"(a) : "memory");
}
__device__ __forceinline__ void sts16(uint32_t a, uint32_t v) { asm volatile("st.shared.u16 [%0], %1;" ::"r"(a), "h"((uint16_t)v) : "memory"); }
__device__ __forceinline__ void mma16816(float& c0, float& c1, float& c2, float& c3, uint32_t a0, uint32_t a1, uint32_t a2, uint32_t a3,
                                         uint32_t b0, uint32_t b1) {
  asm volatile("mma.sync.aligned.m16n8k16.row.col.f32.bf16.bf16.f32 {%0, %1, %2, %3}, {%4, %5, %6, %7}, {%8, %9}, {%0, %1, %2, %3};"
               : "+f"(c0), "+f"(c1), "+f"(c2), "+f"(c3) : "r"(a0), "r"(a1), "r"(a2), "r"(a3), "r"(b0), "r"(b1));
}
__device__ __forceinline__ uint32_t sdesc(uint32_t addr, uint32_t lbo) { return (addr >> 4) + ((lbo >> 4) << 16); }
__device__ __forceinline__ uint64_t desc64(uint32_t lo, uint32_t hi) { uint64_t d; asm("mov.b64 %0, {%1, %2};" : "=l"(d) : "r"(lo), "r"(hi)); return d; }
__device__ __forceinline__ void dadd(uint64_t& d, uint32_t inc) {
  asm("{\n.reg .b32 l, h;\nmov.b64 {l, h}, %0;\nadd.u32 l, l, %1;\nmov.b64 %0, {l, h};\n}" : "+l"(d) : "r"(inc));
}

struct Ring {
  uint32_t slot, phase, xp;
  __device__ __forceinline__ void uniform() {
    slot = __shfl_sync(0xffffffffu, slot, 0); phase = __shfl_sync(0xffffffffu, phase, 0); xp = __shfl_sync(0xffffffffu, xp, 0);
  }
  __device__ __forceinline__ void next() { if (++slot == NS) { slot = 0; phase ^= 1; } }
  __device__ __forceinline__ void next_if(bool p) { slot += p; if (slot == NS) { slot = 0; phase ^= 1; } }
};
__device__ __forceinline__ uint32_t borrow(int ks, int n) {
  const int k = ks + 1;
  return k >= 4 && !(k & 2) && k < n ? k & 1 : 2;
}

constexpr uint32_t Q_RANGES = NBETA * NH + __builtin_popcount(EARLY_MASK) * 5, Q_ALL = NBETA * (NH + 5);
constexpr int NRANGE = NCTA / 5;
struct Work { int kind, mode, k0, nsteps, range, beta, sub; };
struct Sched { uint16_t queue[Q_ALL]; uint32_t piece[NRANGE + 1][4]; };
constexpr Sched make_sched() {
  Sched s{};
  int q = 0, a = 0;
  for (int t = 0, e = 0; a < NBETA * NH; t++) {
    for (; e < NBETA && 8 * e + PK <= t && a >= P_POS; e++)
      for (int col = 0; col < 5 && (EARLY_MASK >> e & 1); col++) s.queue[q++] = 0x8000 | col << 8 | e;
    for (int b = 0; b < NBETA; b++)
      for (int h = 0; h < NH; h++)
        if ((b >= B_LATE && h >= H_LATE ? 300 + b : 8 * b + KG * (h >> 2)) == t) { s.queue[q++] = b << 5 | h; a++; }
  }
  for (int b = 0; b < NBETA; b++)
    for (int col = 0; col < 5 && !(EARLY_MASK >> b & 1); col++) s.queue[q++] = 0x8000 | col << 8 | b;
  constexpr uint32_t T[NRANGE * 2] = {PIECE_TABLE};
  for (int g = 0; g <= NRANGE; g++)
    for (int n = 0; n < 4; n++) s.piece[g][n] = g < NRANGE && n < 2 ? T[2 * g + n] : 2u << 30;
  return s;
}
__constant__ Sched c_sched = make_sched();
constexpr int N_EARLY = __builtin_popcount(EARLY_MASK);
template <bool SIMPLE> __device__ __forceinline__ bool o_reuse(uint32_t b) { return !SIMPLE && b - (OR0 + OR) < N_EARLY - OR0; }
template <bool SIMPLE> __device__ __forceinline__ uint32_t o_slot(uint32_t b) { return o_reuse<SIMPLE>(b) ? OR0 + (b - OR0) % OR : b; }
__device__ __forceinline__ Work decode(uint32_t d) {
  Work w;
  w.kind = d >> 30; if (w.kind == 3) w.kind = 1;
  w.mode = (d >> 28) & 3; w.k0 = (d >> 22) & 63;
  if (w.kind == 0) { w.beta = (d >> 5) & 31; w.sub = d & 31; w.nsteps = DM / 64; }
  else { w.beta = d & 31; w.sub = (d >> 8) & 7; w.nsteps = ((d >> 16) & 63) + 1; }
  w.range = ((d >> 11) & 31) * 5 + w.sub;
  return w;
}

__device__ __forceinline__ bool reached(const unsigned* cnt, unsigned target) {
  unsigned v;
  asm volatile("ld.acquire.gpu.global.u32 %0, [%1];" : "=r"(v) : "l"(cnt) : "memory");
  return (int)(v - target) >= 0;
}
__device__ __forceinline__ void wait_count(const unsigned* cnt, unsigned target) {
  unsigned n = 0;
  while (!__all_sync(0xffffffffu, reached(cnt, target))) { if (++n > (1u << 24)) __trap(); }
}
__device__ __forceinline__ uint32_t lds(uint32_t a) { uint32_t v; asm volatile("ld.volatile.shared.u32 %0, [%1];" : "=r"(v) : "r"(a) : "memory"); return v; }

#define TRACE(u, e)
#define T3(u, e)
#define T2C(u, e)
#define T2P(u, r, e)
#define TTAIL(k)
#define TCLK(k)
#define TO -1
#define TRACE_O(k) if (TO == k) TRACE(i, 5)
#define TRACE_P(u, e)
#define TRACE_IN(u, e)

struct Ctx {
  uint32_t sb;
  int wg, warp;
  uint32_t mqk, mpv;
  bool lead;
  int lane0, lane;
  int src;
};
template <int N> __device__ __forceinline__ uint32_t dhi(uint32_t lo) { return 0x40000040u + (lo >> (26 + N)); }
__device__ __forceinline__ void release(const Ctx& c, uint32_t slot) {
  if (c.lead) mbar_arrive(c.sb + BAR_EMPTY + slot * 8);
}
__device__ __forceinline__ uint32_t acquire(const Ctx& c, Ring& r, bool have = false) {
  const uint32_t s = r.slot;
  if (!have) mbar_wait_w(c.sb + BAR_FULL + s * 8, r.phase);
  r.next();
  return s;
}
__device__ __forceinline__ void mbar_wait2_w(uint32_t b0, uint32_t p0, uint32_t b1, uint32_t p1) {
  uint32_t n = 0;
  while (!__all_sync(0xffffffffu, mbar_try(b0, p0) & mbar_try(b1, p1))) {
    if (++n > (1u << 22)) __trap();
  }
}
__device__ __forceinline__ void mbar_wait3_w(uint32_t b0, uint32_t p0, uint32_t b1, uint32_t p1, uint32_t b2, uint32_t p2) {
  uint32_t n = 0;
  while (!__all_sync(0xffffffffu, mbar_try(b0, p0) & mbar_try(b1, p1) & mbar_try(b2, p2))) {
    if (++n > (1u << 22)) __trap();
  }
}
__device__ __forceinline__ void acquire2(const Ctx& c, Ring& r, uint32_t& s0, uint32_t& s1, bool have = false) {
  const uint32_t p0 = r.phase;
  s0 = r.slot; r.next(); s1 = r.slot;
  if (!have) mbar_wait2_w(c.sb + BAR_FULL + s0 * 8, p0, c.sb + BAR_FULL + s1 * 8, r.phase);
  r.next();
}
template <int N>
__device__ __forceinline__ bool peek(const Ctx& c, Ring r) {
  bool ok = true;
#pragma unroll
  for (int k = 0; k < N; k++) { ok &= mbar_test(c.sb + BAR_FULL + r.slot * 8, r.phase); r.next(); }
  return ok;
}
__device__ __forceinline__ void staged(const Ctx& c, int part) {
  fence_async_smem();
  __syncwarp();
  mbar_arrive_warp(c.sb + BAR_STG + c.wg * 16 + part * 8);
}

template <int WG, bool FIRST, int H>
__device__ __forceinline__ void proj_half(const Ctx& c, float (&acc)[64], uint32_t w, uint32_t x, uint32_t sw) {
  uint64_t dx = desc64((c.sb + x * SLOT + (WG ? 0 : H * 8192)) >> 4, dhi<0>(x) + sw);
  uint64_t dw = desc64(WG ? (c.sb + w * SLOT + H * 8192) >> 4 : sdesc(c.sb + w * SLOT, 8192), dhi<1>(x));
  wg_fence();
  if (WG) { if (FIRST) wgmma_proj96_init(acc, dw, dx, 0); else wgmma_proj96(acc, dw, dx, 1); }
  else { if (FIRST) wgmma_proj_init(acc, dx, dw, 0); else wgmma_proj(acc, dx, dw, 1); }
#pragma unroll
  for (int k = 1; k < 4; k++) {
    dadd(dx, k == 2 ? 2 + (sw >> 30) * 28 : 2); dadd(dw, 128);
    if (WG) wgmma_proj96(acc, dw, dx, 1); else wgmma_proj(acc, dx, dw, 1);
  }
  wg_commit();
}

__device__ __forceinline__ void proj_store16(uint32_t a, const float* f, float sc) {
  stsm4t(a, pack_bf16(f[0] * sc, f[1] * sc), pack_bf16(f[2] * sc, f[3] * sc), pack_bf16(f[4] * sc, f[5] * sc), pack_bf16(f[6] * sc, f[7] * sc));
}

__device__ __forceinline__ uint32_t stage_off(const Ctx& c) {
  const int lane = c.lane, mi = lane >> 3, r8 = lane & 7;
  return ((mi >> 1) * 8 + r8) * 128 + (((2 * c.warp + (mi & 1)) ^ r8) << 4);
}
__device__ __forceinline__ uint32_t q3_swz(uint32_t r8) { return ((r8 & 3) << 1) | (r8 >> 2); }
template <int H>
__device__ __forceinline__ void stage_t2(const Ctx& c, const float (&a)[64], float sc) {
  const uint32_t base = c.sb + QBUF_OFF + 2 * 16384 + H * 8192 + stage_off(c);
#pragma unroll
  for (int jj = 0; jj < 4; jj++) proj_store16(base + jj * 2048, &a[jj * 8], sc);
}
template <int H, bool IS_Q>
__device__ __forceinline__ void stage_t3(const Ctx& c, const float (&a)[64], float sc) {
  const uint32_t off = stage_off(c), r8 = (off >> 7) & 7;
  const uint32_t t3 = c.sb + QBUF_OFF + 3 * 16384 + H * 4096 + (IS_Q ? off ^ ((r8 ^ q3_swz(r8)) << 4) : off);
  proj_store16(t3, &a[32], sc);
  proj_store16(t3 + 2048, &a[40], sc);
}

template <int WG, int h>
__device__ __forceinline__ void load_part(const Ctx& c, Ring r, uint32_t (&q)[32]) {
  uint32_t n = 0;
  while (!h && !__all_sync(0xffffffffu, peek<4>(c, r))) {
    if (++n > (1u << 26)) __trap();
  }
  const int lane = c.lane, mi = lane >> 3, r8 = lane & 7;
  if (WG) { r.next(); r.next(); }
  const uint32_t off = c.sb + (WG ? stage_off(c) : (16 * c.warp + (mi & 1) * 8 + r8) * 128), t0 = off + r.slot * SLOT;
  r.next();
  const uint32_t t1 = off + r.slot * SLOT;
#pragma unroll
    for (int jj = 0; jj < (WG ? 6 : 8); jj++) {
      uint32_t* p = &q[4 * jj];
      if (WG) asm volatile("ldmatrix.sync.aligned.m8n8.x4.trans.shared.b16 {%0, %1, %2, %3}, [%4];" : "=r"(p[0]), "=r"(p[1]), "=r"(p[2]), "=r"(p[3])
                           : "r"((jj < 4 ? t0 + h * 8192 : t1 + h * 4096) + (jj & 3) * 2048) : "memory");
      else ldsm4((h ? t1 : t0) + (jj >> 2) * 8192 + (((((2 * jj) & 7) + (mi >> 1)) ^ r8) << 4), p[0], p[1], p[2], p[3]);
    }
}
template <int WG>
__device__ __forceinline__ void add_part(const Ctx& c, const uint32_t (&q)[32], float (&a)[64]) {
  const uint32_t one = (c.lane >> 3) == (c.lane & 3) ? 0x3f80u << (c.lane & 4) * 4 : 0;
#pragma unroll
  for (int i = 0; i < (WG ? 12 : 16); i++)
    asm("mma.sync.aligned.m16n8k8.row.col.f32.bf16.bf16.f32 {%0, %1, %2, %3}, {%4, %5}, {%6}, {%0, %1, %2, %3};"
        : "+f"(a[4 * i]), "+f"(a[4 * i + 1]), "+f"(a[4 * i + 2]), "+f"(a[4 * i + 3]) : "r"(q[2 * i]), "r"(q[2 * i + 1]), "r"(one));
}

__device__ __forceinline__ void trace_dump(const Ctx& c) {
}
struct RowSum { float l0, l1; };
__device__ __forceinline__ const char* o_addr(uint32_t item, int row, int lane) {
  return reinterpret_cast<const char*>(g_o) + (((item >> 10) * (2 * SQ) + row) * 128 + (lane ^ (lane >> 3)) * 16);
}
__device__ __forceinline__ void o_stg(const char* p, int i, const uint32_t* q) {
  asm volatile("st.global.v4.b32 [%0], {%1, %2, %3, %4};"
               ::"l"(p + (i >> 1) * (SQ * 128) + (i & 1) * 512), "r"(q[0]), "r"(q[1]), "r"(q[2]), "r"(q[3]) : "memory");
}
template <int MODE, int I0 = 0, int NI = 4>
__device__ __forceinline__ void o_emit(const char* p, const float (&o)[64], float inv) {
#pragma unroll
  for (int i = I0; i < I0 + NI; i++) {
    uint32_t q[4];
#pragma unroll
    for (int j = 0; j < 4; j++) q[j] = pack_bf16(o[16 * i + 4 * j + 2 * MODE] * inv, o[16 * i + 4 * j + 2 * MODE + 1] * inv);
    o_stg(p, i, q);
  }
}
__device__ __forceinline__ void o_done(const Ctx& c) {
  __syncwarp();
  mbar_arrive_warp(c.sb + BAR_OUT);
  __syncwarp();
}
template <int WG>
__device__ __forceinline__ void o_first(const Ctx& c, uint32_t item, float (&o)[64], const RowSum& inv) {
  const char* p = o_addr(item, WG ? 192 + 8 * c.warp : 64 + 16 * c.warp, c.lane);
  reg_fence(o);
  if (WG) {
    uint32_t q[16];
#pragma unroll
    for (int j = 0; j < 16; j++) q[j] = pack_bf16((o[4 * j] + o[4 * j + 2]) * inv.l0, (o[4 * j + 1] + o[4 * j + 3]) * inv.l0);
#pragma unroll
    for (int i = 0; i < 4; i++) o_stg(p, i, q + 4 * i);
  } else { o_emit<0>(p, o, inv.l0); o_emit<1>(p + 1024, o, inv.l1); }
}
template <int K0, int K1>
__device__ __forceinline__ void o_piece(const Ctx& c, const char* p, int k, const float (&o)[64], const RowSum& inv) {
  constexpr int NI = 8 / O_STEPS, M = K0 * NI / 4;
  if constexpr (K1 - K0 == 1) {
    o_emit<M, K0 * NI % 4, NI>(p + M * 1024, o, M ? inv.l1 : inv.l0);
    if (K1 == O_STEPS) o_done(c);
  } else {
    if (k <= (K0 + K1) / 2) o_piece<K0, (K0 + K1) / 2>(c, p, k, o, inv); else o_piece<(K0 + K1) / 2, K1>(c, p, k, o, inv);
  }
}
template <int WG>
__device__ __forceinline__ void o_second(const Ctx& c, uint32_t item, int k, float (&o)[64], const RowSum& inv) {
  reg_fence(o);
  o_piece<0, O_STEPS>(c, o_addr(item, 128 * WG + 16 * c.warp, c.lane0 + (k >> 8)), k, o, inv);
}
template <int WG>
__device__ __forceinline__ void release_q(const Ctx& c) {
#pragma unroll
  for (int t = 0; t < 2; t++)
    if (c.lead) asm volatile("mbarrier.arrive.shared::cta.b64 _, [%0], 2;" ::"r"(c.sb + BAR_EMPTY + (NS + 2 * WG + t) * 8) : "memory");
  __syncwarp();
}
struct Slots { uint32_t w, x, o, po; };
template <int WG>
__device__ __forceinline__ void acc_fence(float (&a)[64]) {
#pragma unroll
  for (int i = 0; i < (WG ? 48 : 64); i++) asm volatile("" : "+f"(a[i])::"memory");
}
template <int WG>
__device__ __forceinline__ void begin_acquire(const Ctx& c, Ring& r, Slots& h, bool wait) {
  const uint32_t s0 = r.slot, p0 = r.phase, f = c.sb + BAR_FULL;
  r.next();
  const uint32_t p1 = r.phase;
  h.w = r.slot; r.next();
  h.x = WG ? r.slot : s0; h.o = WG ? s0 : r.slot; h.po = r.phase;
  if (wait) { if (WG) mbar_wait3_w(f + s0 * 8, p0, f + h.w * 8, p1, f + h.x * 8, r.phase); else mbar_wait2_w(f + s0 * 8, p0, f + h.w * 8, p1); }
  r.next();
}
template <int WG>
__device__ __forceinline__ void proj_begin(const Ctx& c, Ring& r, float (&a0)[64], Slots& h, bool wait, uint32_t sw) {
  begin_acquire<WG>(c, r, h, wait);
  proj_half<WG, true, 0>(c, a0, h.w, h.x, sw);
  if (WG) release(c, h.o);
}
template <int WG>
__device__ __forceinline__ void proj_main(Ctx& c, Ring& r, float (&a0)[64], float (&a1)[64], Slots& h, int n, uint32_t sw, int unit,
                                          uint32_t item, int nq, float (&o1)[64], const RowSum& inv) {
  constexpr bool DEEP = (PDEPTH >> WG) & 1;
  T2C(unit, 3);
  int ks = 1;
#pragma unroll 1
  do {
    const Slots p = h;
    const uint32_t b = borrow(ks, n), tile = NS + (WG ? 3 - b : b), f = c.sb + BAR_FULL;
    const uint32_t s0 = b != 2 ? tile : r.slot, p0 = b != 2 ? (r.xp >> b) & 1 : r.phase;
    r.next_if(b == 2);
    const uint32_t p1 = r.phase;
    h.w = r.slot; r.next();
    const uint32_t s2 = b != 2 ? tile : r.slot;
    h.po = b != 2 ? p0 : r.phase;
    r.next_if(b == 2);
    r.xp ^= 1 << b;
    h.x = WG ? s2 : s0; h.o = WG ? s0 : s2;
    mbar_wait3_w(f + s0 * 8, p0, f + h.w * 8, p1, f + (WG ? s2 : p.o) * 8, WG ? h.po : p.po);
    if (ks < 10) T2C(unit, ks * 4);
    if (DEEP) {
      proj_half<WG, false, 0>(c, a0, h.w, h.x, sw);
      release(c, WG ? h.o : p.o);
      if (ks < 10) T2C(unit, ks * 4 + 1);
      wg_wait<1>();
      if (ks < 10) T2C(unit, ks * 4 + 2);
      release(c, p.x); release(c, p.w);
    } else {
      release(c, WG ? h.o : p.o);
      wg_wait<0>();
      release(c, p.x); release(c, p.w);
      if (ks < 10) T2C(unit, ks * 4 + 1);
      proj_half<WG, false, 0>(c, a0, h.w, h.x, sw);
      if (ks < 10) T2C(unit, ks * 4 + 2);
    }
    proj_half<WG, false, 1>(c, a1, h.w, h.x, sw);
    if (ks < 10) T2C(unit, ks * 4 + 3);
    if (ks <= nq) o_second<WG>(c, item, ks, o1, inv);
  } while (++ks != n);
  {
    const uint32_t e0 = c.sb + BAR_EMPTY + (NS + 3 * WG) * 8, e1 = c.sb + BAR_EMPTY + (NS + 1 + WG) * 8;
    const uint32_t p0 = (r.xp ^ unit ^ 1) & 1, p1 = ((r.xp >> 1) ^ unit ^ 1) & 1;
    const uint32_t k0 = sw ? e0 : c.sb + BAR_FULL + r.slot * 8, pk = sw ? p0 : r.phase;
    uint32_t cnt = 0;
    while (!__all_sync(0xffffffffu, mbar_try(e0, p0) & mbar_try(e1, p1) & mbar_try(k0, pk) & (WG || mbar_try(c.sb + BAR_FULL + h.o * 8, h.po)))) {
      if (++cnt > (1u << 22)) __trap();
    }
  }
  c.lane = c.lane0 + (h.w >> 5);
  if (!WG) release(c, h.o);
}
template <int WG>
__device__ __forceinline__ void proj_end(const Ctx& c, float (&a1)[64], const Slots& h) {
  wg_wait<0>();
  acc_fence<WG>(a1);
  release(c, h.x); release(c, h.w);
}
__device__ __forceinline__ uint32_t get_desc(const Ctx& c, int i) {
  uint32_t d;
  mbar_wait_w(c.sb + BAR_DESC, (i - 1) & 1);
  asm volatile("ld.volatile.shared.u32 %0, [%1];" : "=r"(d) : "r"(c.sb + DESC_OFF + (i & 3) * 4) : "memory");
  return __shfl_sync(0xffffffffu, d, 0);
}

__device__ __forceinline__ float quad_max(float x) {
  x = fmaxf(x, __shfl_xor_sync(0xffffffffu, x, 1));
  return fmaxf(x, __shfl_xor_sync(0xffffffffu, x, 2));
}
__device__ __forceinline__ float quad_sum(float x) {
  x += __shfl_xor_sync(0xffffffffu, x, 1);
  return x + __shfl_xor_sync(0xffffffffu, x, 2);
}
template <bool SP, bool FIRST>
__device__ __forceinline__ void exps(const Ctx& c, const float (&s)[32], uint32_t (&p)[SP ? 8 : 16], RowSum& st) {
  if constexpr (SP) {
    uint32_t q[8];
    float t;
#pragma unroll
    for (int j = 0; j < 8; j++) {
      const float e0 = ex2(s[4 * j] + s[4 * j + 2]), e1 = ex2(s[4 * j + 1] + s[4 * j + 3]);
      if (j == 0) t = e0 + e1; else t += e0 + e1;
      q[j] = pack_bf16(e0, e1);
    }
    const bool odd = c.src & 2;
#pragma unroll
    for (int g = 0; g < 4; g++) {
      p[2 * g] = __shfl_sync(0xffffffffu, odd ? q[2 * g + 1] : q[2 * g], c.src);
      p[2 * g + 1] = __shfl_sync(0xffffffffu, odd ? q[2 * g] : q[2 * g + 1], c.src ^ 1);
    }
    st.l0 = FIRST ? t : st.l0 + t;
  } else {
    float t0, t1;
#pragma unroll
    for (int j = 0; j < 8; j++) {
      const float e0 = ex2(s[4 * j]), e1 = ex2(s[4 * j + 1]), e2 = ex2(s[4 * j + 2]), e3 = ex2(s[4 * j + 3]);
      if (j == 0) { t0 = e0 + e1; t1 = e2 + e3; } else { t0 += e0 + e1; t1 += e2 + e3; }
      p[2 * j] = pack_bf16(e0, e1);
      p[2 * j + 1] = pack_bf16(e2, e3);
    }
    st.l0 = FIRST ? t0 : st.l0 + t0;
    st.l1 = FIRST ? t1 : st.l1 + t1;
  }
}
template <bool SP>
__device__ __forceinline__ bool finish_sums(RowSum& st) {
  const float a = quad_sum(st.l0), b = SP ? a : quad_sum(st.l1);
  st.l0 = __fdividef(1.f, a); st.l1 = __fdividef(1.f, b);
  return !(a >= SUM_LO && a <= SUM_HI && b >= SUM_LO && b <= SUM_HI);
}
template <bool SP, bool INIT, int SITE, bool COMMIT = true, int NR = 0>
__device__ __forceinline__ void issue_qk(const Ctx& c, float (&s)[32], const uint32_t (&qs)[32], uint32_t dq, uint32_t dk) {
  uint64_t a = desc64(dq, dhi<SITE & 1>(dk)), b = desc64(dk, dhi<1 - (SITE & 1)>(dk));
  if (SP) {
    if (INIT) wgmma_qk_sp_init(s, qs[0], qs[1], qs[2], qs[3], b, 0, c.mqk); else wgmma_qk_sp(s, qs[0], qs[1], qs[2], qs[3], b, 0, c.mqk);
#pragma unroll
    for (int k = 1; k < 4; k++) { dadd(b, k == 2 ? 508 : 4); wgmma_qk_sp(s, qs[4 * k], qs[4 * k + 1], qs[4 * k + 2], qs[4 * k + 3], b, 1, c.mqk); }
  } else {
    if (NR) wgmma_qk_rs(s, qs[0], qs[1], qs[2], qs[3], b, 0); else if (INIT) wgmma_qk_init(s, a, b, 0); else wgmma_qk(s, a, b, 0);
#pragma unroll
    for (int k = 1; k < 8; k++) {
      if (k > NR) dadd(a, k == 4 ? 506 : 2);
      dadd(b, k == 4 ? 506 : 2);
      if (k < NR) wgmma_qk_rs(s, qs[4 * k], qs[4 * k + 1], qs[4 * k + 2], qs[4 * k + 3], b, 1); else wgmma_qk(s, a, b, 1);
    }
  }
  if (COMMIT) wg_commit();
}
template <bool SP, bool ACC, int SITE, bool SPLIT = false>
__device__ __forceinline__ void issue_pv(const Ctx& c, float (&o)[64], const uint32_t (&p)[SP ? 8 : 16], uint32_t dv) {
  uint64_t b = desc64(dv, dhi<SITE & 1>(dv));
  if constexpr (SP) {
    if (ACC) wgmma_pv_sp(o, p[0], p[1], p[2], p[3], b, 1, c.mpv); else wgmma_pv_sp_init(o, p[0], p[1], p[2], p[3], b, 0, c.mpv);
    if (SPLIT) wg_commit();
    dadd(b, 256);
    wgmma_pv_sp(o, p[4], p[5], p[6], p[7], b, 1, c.mpv);
  } else {
    if (ACC) wgmma_pv(o, p[0], p[1], p[2], p[3], b, 1); else wgmma_pv_init(o, p[0], p[1], p[2], p[3], b, 0);
#pragma unroll
    for (int k = 1; k < 4; k++) { dadd(b, 128); wgmma_pv(o, p[4 * k], p[4 * k + 1], p[4 * k + 2], p[4 * k + 3], b, 1); }
  }
  wg_commit();
}
__device__ __forceinline__ void pack_rows(const float (&o)[64], float sc, uint32_t (&q)[32]) {
#pragma unroll
  for (int j = 0; j < 32; j++) q[j] = pack_bf16(o[2 * j] * sc, o[2 * j + 1] * sc);
}
template <int J0 = 0, int J1 = 8>
__device__ __forceinline__ void stage_rows(const Ctx& c, uint32_t tile_addr, const uint32_t (&q)[32]) {
  const int lane = c.lane, mi = lane >> 3, r8 = lane & 7;
  const uint32_t row_addr = tile_addr + (16 * c.warp + (mi & 1) * 8 + r8) * 128;
#pragma unroll
  for (int jj = J0; jj < J1; jj++)
    stsm4(row_addr + (jj >> 2) * 8192 + (((((2 * jj) & 7) + (mi >> 1)) ^ r8) << 4), q[4 * jj], q[4 * jj + 1], q[4 * jj + 2], q[4 * jj + 3]);
}
__device__ __forceinline__ void stage_rows(const Ctx& c, uint32_t tile_addr, const float (&o)[64], float sc) {
  uint32_t q[32];
  pack_rows(o, sc, q);
  stage_rows(c, tile_addr, q);
}
template <int WG, int H>
__device__ __forceinline__ void stage_out(const Ctx& c, const float (&a)[64]) {
  if (WG) { stage_t3<H, false>(c, a, 1.f); if (H) staged(c, 0); stage_t2<H>(c, a, 1.f); }
  else stage_rows(c, c.sb + QBUF_OFF + H * 16384, a, 1.f);
  if (H || !WG) staged(c, H);
}
template <int SITE>
__device__ __forceinline__ void issue_qk_rs(float (&s)[32], uint32_t (&q)[32], uint32_t dk) {
  uint64_t b = desc64(dk, dhi<SITE>(dk));
  reg_fence(q);
  wg_fence();
  wgmma_qk_rs_init(s, q[0], q[1], q[2], q[3], b, 0);
#pragma unroll
  for (int k = 1; k < 8; k++) { dadd(b, k == 4 ? 506 : 2); wgmma_qk_rs(s, q[4 * k], q[4 * k + 1], q[4 * k + 2], q[4 * k + 3], b, 1); }
  wg_commit();
}

__device__ __forceinline__ void redo_tile(const Ctx& c, uint32_t q_addr, uint32_t half, const __nv_bfloat16* kp, const __nv_bfloat16* vp,
                                          uint32_t item, int row) {
  float o[64];
  const int lane = lane_now(), g = lane >> 2, cc = lane & 3, mi = lane >> 3, r8 = lane & 7;
  const uint32_t qa = q_addr + (half == 4096 ? 8 * c.warp + r8 : 16 * c.warp + (mi & 1) * 8 + r8) * 128, swz = half == 4096 ? q3_swz(r8) : r8;
  const uint32_t* kq = reinterpret_cast<const uint32_t*>(kp + g * DH) + cc;
  const unsigned short* vq = reinterpret_cast<const unsigned short*>(vp + 2 * cc * DH) + g;
  float m0 = -INFINITY, m1 = -INFINITY, l0 = 0.f, l1 = 0.f;
#pragma unroll
  for (int i = 0; i < 64; i++) o[i] = 0.f;
#pragma unroll 1
  for (int kb = 0; kb < SK / 16; kb++) {
    float z[8] = {0.f, 0.f, 0.f, 0.f, 0.f, 0.f, 0.f, 0.f};
#pragma unroll 2
    for (int kk = 0; kk < 8; kk++) {
      uint32_t a0, a1, a2, a3;
      ldsm4(qa + (kk >> 2) * half + ((((kk & 3) * 2 + (mi >> 1)) ^ swz) << 4), a0, a1, a2, a3);
      const uint32_t* kr = kq + kb * (16 * DH / 2) + kk * 8;
      mma16816(z[0], z[1], z[2], z[3], a0, a1, a2, a3, __ldg(kr), __ldg(kr + 4));
      mma16816(z[4], z[5], z[6], z[7], a0, a1, a2, a3, __ldg(kr + 8 * DH / 2), __ldg(kr + 8 * DH / 2 + 4));
    }
    const float n0 = fmaxf(m0, quad_max(fmaxf(fmaxf(z[0], z[1]), fmaxf(z[4], z[5]))));
    const float n1 = fmaxf(m1, quad_max(fmaxf(fmaxf(z[2], z[3]), fmaxf(z[6], z[7]))));
    const float al0 = ex2(m0 - n0), al1 = ex2(m1 - n1);
    m0 = n0; m1 = n1;
#pragma unroll
    for (int i = 0; i < 8; i++) z[i] = ex2(z[i] - ((i & 2) ? n1 : n0));
    l0 = l0 * al0 + (z[0] + z[1]) + (z[4] + z[5]);
    l1 = l1 * al1 + (z[2] + z[3]) + (z[6] + z[7]);
    const uint32_t a0 = pack_bf16(z[0], z[1]), a1 = pack_bf16(z[2], z[3]), a2 = pack_bf16(z[4], z[5]), a3 = pack_bf16(z[6], z[7]);
    const unsigned short* vr = vq + kb * (16 * DH);
#pragma unroll
    for (int nb = 0; nb < 16; nb++) {
      o[4 * nb] *= al0; o[4 * nb + 1] *= al0; o[4 * nb + 2] *= al1; o[4 * nb + 3] *= al1;
      const uint32_t b0 = __ldg(vr + nb * 8) | ((uint32_t)__ldg(vr + nb * 8 + DH) << 16);
      const uint32_t b1 = __ldg(vr + nb * 8 + 8 * DH) | ((uint32_t)__ldg(vr + nb * 8 + 9 * DH) << 16);
      mma16816(o[4 * nb], o[4 * nb + 1], o[4 * nb + 2], o[4 * nb + 3], a0, a1, a2, a3, b0, b1);
    }
  }
  const char* p = o_addr(item, row, lane);
  o_emit<0>(p, o, __fdividef(1.f, quad_sum(l0)));
  o_emit<1>(half == 4096 ? p : p + 1024, o, __fdividef(1.f, quad_sum(l1)));
}

template <bool SPA, bool SPB, int SITE, int ID>
__device__ __forceinline__ void batch(const Ctx& c, float (&s)[32], const uint32_t (&qs)[32], uint32_t dq, uint32_t dk, float (&ob)[64],
                                      uint32_t (&pb)[SPB ? 8 : 16], uint32_t dv) {
  if constexpr (SPA) {
    reg_fence(pb);
    wg_fence();
    issue_pv<SPB, true, ID>(c, ob, pb, dv);
    issue_qk<SPA, false, ID>(c, s, qs, dq, dk);
  } else {
    constexpr bool EARLY = ((QK_EARLY_MASK >> (SITE + (SPB ? 2 : 0))) & 1) != 0;
    if (!EARLY) reg_fence(pb);
    wg_fence();
    issue_qk<SPA, false, ID, !SPB, SITE ? NQR : SPB ? NQR2 : NQR1>(c, s, qs, dq, dk);
    if (EARLY) { reg_fence(pb); wg_fence(); }
    issue_pv<SPB, true, ID, SPB>(c, ob, pb, dv);
  }
}

template <bool SP0>
__device__ __forceinline__ bool attention(Ctx& c, Ring& r, int unit, uint32_t& d, const float (&a0)[64], float (&o0)[64], float (&o1)[64],
                                          RowSum& st0, RowSum& st1, const Slots& h) {
  constexpr bool SP1 = false;
  if (SP0) { c.mqk = META_QK + (d >> 28); c.mpv = META_PV + (d >> 28); asm volatile("" : "+r"(c.mqk), "+r"(c.mpv)); }
  if (SP0) c.src = (c.lane & 28) | ((c.lane & 1) << 1) | ((c.lane >> 1) & 1);
  float s[32];
  uint32_t p0[SP0 ? 8 : 16], p1[16];
  const uint32_t q0a = c.sb + QBUF_OFF + (SP0 ? 3 : 0) * 16384, q1a = c.sb + QBUF_OFF + (SP0 ? 2 : 1) * 16384;
  const uint32_t dq0 = sdesc(q0a + (NQR >> 2) * 8192 + (NQR & 3) * 32, 0), dq1 = sdesc(q1a + (SP0 ? NQR2 * 32 : (NQR1 >> 2) * 8192 + (NQR1 & 3) * 32), 0);
  uint32_t sk = acquire(c, r, true), sv, sn;
  uint32_t qs[32], q1[32];
  float s1[32];
  if (SP0) {
    stage_t3<0, true>(c, a0, SM_C);
    stage_t2<0>(c, a0, SM_C);
    proj_end<1>(c, o0, h);
    stage_t3<1, true>(c, o0, SM_C);
    stage_t2<1>(c, o0, SM_C);
    fence_async_smem();
    bar_sync(1, LAG_BAR & 30 ? 256 : 128);
    const int g = c.lane >> 2, cc = c.lane & 3;
    const uint32_t qa = q0a + (8 * c.warp + g) * 128 + (cc & 1) * 8;
#pragma unroll
    for (int k = 0; k < 8; k++)
      asm volatile("ld.shared.v2.u32 {%0, %1}, [%2];" : "=r"(qs[2 * k]), "=r"(qs[2 * k + 1])
                   : "r"(qa + (k >> 2) * 4096 + ((((k & 3) * 2 + (cc >> 1)) ^ q3_swz(g)) << 4)) : "memory");
    TRACE(unit, 2);
    wg_fence();
    issue_qk<SP1, true, 1>(c, s1, qs, dq1 - NQR2 * 2, sdesc(c.sb + sk * SLOT, 0));
#pragma unroll
    for (int k = 0; k < NQR2; k++)
      ldsm4(q1a + (16 * c.warp + (c.lane & 15)) * 128 + (((2 * k + (c.lane >> 4)) ^ (c.lane & 7)) << 4), q1[4 * k], q1[4 * k + 1], q1[4 * k + 2], q1[4 * k + 3]);
#pragma unroll
    for (int k = 0; k < 16; k++) asm volatile("" : "+r"(qs[k])::"memory");
    wg_fence();
    issue_qk<SP0, true, 0>(c, s, qs, dq0, sdesc(c.sb + sk * SLOT, 0));
    const bool have = peek<2>(c, r);
    wg_wait<1>();
    reg_fence(s1);
    exps<SP1, true>(c, s1, p1, st1);
    sched_fence<11>(sk, p1);
    acquire2(c, r, sv, sn, __all_sync(0xffffffffu, have));
    wg_wait<0>();
    wg_fence();
    issue_pv<SP1, false, 1>(c, o1, p1, sdesc(c.sb + sv * SLOT, 8192));
    if (LAG_BAR & 1) asm volatile("bar.arrive 4, 256;" ::: "memory");
    sched_fence<12>(sk, s);
    release(c, sk);
    sk = sn;
    exps<SP0, true>(c, s, p0, st0);
    reg_fence(p0);
    wg_fence();
    issue_pv<SP0, false, 0>(c, o0, p0, sdesc(c.sb + sv * SLOT, 8192));
    issue_qk<SP0, true, 2>(c, s, qs, dq0, sdesc(c.sb + sk * SLOT, 0));
    sn = acquire(c, r);
    wg_wait<0>();
    reg_fence(s);
  } else {
    pack_rows(a0, SM_C, qs);
    stage_rows<SKIP_ST & 1 ? NQR : 0>(c, q0a, qs);
    proj_end<0>(c, o1, h);
    TRACE(unit, 2);
    float sc = SM_C;
    issue_qk_rs<0>(s, qs, sdesc(c.sb + sk * SLOT, 0));
    sched_fence<0>(sk, sc);
    if (LAG_BAR & 8) asm volatile("bar.arrive 1, 256;" ::: "memory");
    pack_rows(o1, sc, q1);
    stage_rows<SKIP_ST & 2 ? NQR1 : 0>(c, q1a, q1);
    if (LAG_BAR & 4) asm volatile("bar.arrive 1, 256;" ::: "memory");
    issue_qk_rs<1>(s1, q1, sdesc(c.sb + sk * SLOT, 0));
    if (LAG_BAR & 2) asm volatile("bar.arrive 1, 256;" ::: "memory");
    bool have = peek<2>(c, r);
    wg_wait<1>();
    reg_fence(s);
    exps<SP0, true>(c, s, p0, st0);
    sched_fence<1>(sk, p0);
    if (LAG_BAR & 16) asm volatile("bar.arrive 1, 256;" ::: "memory");
    acquire2(c, r, sv, sn, __all_sync(0xffffffffu, have));
    wg_wait<0>();
    reg_fence(s1);
    fence_async_smem();
    __syncwarp();
    wg_fence();
    issue_qk<SP0, false, 2, true, NQR>(c, s, qs, dq0, sdesc(c.sb + sn * SLOT, 0));
    issue_pv<SP0, false, 0>(c, o0, p0, sdesc(c.sb + sv * SLOT, 8192));
    sched_fence<2>(sk, s1);
    release(c, sk);
    have = peek<1>(c, r);
    sk = sn;
    exps<SP1, true>(c, s1, p1, st1);
    reg_fence(p1);
    wg_fence();
    issue_pv<SP1, false, 1>(c, o1, p1, sdesc(c.sb + sv * SLOT, 8192));
    sn = acquire(c, r, __all_sync(0xffffffffu, have));
    if (LAG_BAR & 1) bar_sync(4, 256);
    wg_wait<1>();
    reg_fence(s);
  }
  TRACE_IN(unit, 4);
  T2C(unit, 51);
#pragma unroll 1
  for (int j = 1; j < 15; j++) {
    const uint32_t sv_prev = sv, sk_prev = sk;
    sv = sn;
    const uint32_t dv = sdesc(c.sb + sv * SLOT, 8192);
    reg_fence(p0);
    exps<SP0, false>(c, s, p0, st0);
    batch<SP1, SP0, 0, 3>(c, s, q1, dq1, sdesc(c.sb + sk * SLOT, 0), o0, p0, dv);
    sk = acquire(c, r);
    wg_wait<1>();
    reg_fence(s); reg_fence(p1);
    release(c, sv_prev); release(c, sk_prev);
    exps<SP1, false>(c, s, p1, st1);
    batch<SP0, SP1, 1, 4>(c, s, qs, dq0, sdesc(c.sb + sk * SLOT, 0), o1, p1, dv);
    sn = acquire(c, r);
    if (SP0) wg_wait<0>(); else wg_wait<1>();
    reg_fence(s);
  }
  TRACE_IN(unit, 5);
  T2C(unit + 1, 52);
  const uint32_t sv_prev = sv;
  sv = sn;
  const uint32_t dv = sdesc(c.sb + sv * SLOT, 8192);
  reg_fence(p0);
  exps<SP0, false>(c, s, p0, st0);
  batch<SP1, SP0, 0, 5>(c, s, q1, dq1, sdesc(c.sb + sk * SLOT, 0), o0, p0, dv);
  asm volatile("ld.volatile.shared.u32 %0, [%1];" : "=r"(d) : "r"(c.sb + DESC_OFF + ((unit + 1) & 3) * 4) : "memory");
  const bool have = peek<2 + SP0>(c, r);
  wg_wait<1>();
  reg_fence(s); reg_fence(p1);
  release(c, sv_prev); release(c, sk);
  exps<SP1, false>(c, s, p1, st1);
  reg_fence(p1);
  wg_fence();
  issue_pv<SP1, true, 2>(c, o1, p1, dv);
  if (SP0) sched_fence<6>(sk, st0.l0, st1.l0, st1.l1); else sched_fence<5>(sk, st0.l0, st0.l1, st1.l0, st1.l1);
  c.lane = c.lane0 + (sk >> 5);
  const bool bad = finish_sums<SP0>(st0) | finish_sums<SP1>(st1);
  uint32_t any;
  asm volatile("{\n.reg .pred p, q;\nsetp.ne.u32 p, %1, 0;\nbar.red.or.pred q, %2, 128, p;\nselp.u32 %0, 1, 0, q;\n}"
               : "=r"(any) : "r"((uint32_t)bad), "n"(2 + SP0) : "memory");
  any = __any_sync(0xffffffffu, any);
  d = __shfl_sync(0xffffffffu, d, 0);
  if (d < (2u << 30) && !__all_sync(0xffffffffu, have)) { Ring t = r; Slots u; begin_acquire<SP0>(c, t, u, true); }
  wg_wait<0>();
  reg_fence(o0); reg_fence(o1);
  release(c, sv);
  if (!SP0 && SKIP_ST && __builtin_expect(any, 0)) {
    stage_rows<0, SKIP_ST & 1 ? NQR : 0>(c, q0a, qs); stage_rows<0, SKIP_ST & 2 ? NQR1 : 0>(c, q1a, q1);
    __syncwarp();
  }
  return any;
}

template <int WG>
__device__ __forceinline__ void consumer(Ctx c, const __nv_bfloat16* const* kv) {
  asm volatile("setmaxnreg.inc.sync.aligned.u32 %0;" ::"n"(WG ? REG_C : 504 - REG_C - REG_P));
  c.wg = WG;
  Ring r{0, 0, 0};
  float a0[64], a1[64], o1[64];
  Slots h;
  RowSum inv0, inv1;
  uint32_t d = c_sched.queue[blockIdx.x] * 1025, dc = 0, sw;
  int i = 0, nq;
begin:
  sw = d & (1u << 30);
  proj_begin<WG>(c, r, a0, h, true, sw);
begin1:
  proj_half<WG, true, 1>(c, a1, h.w, h.x, sw);
  nq = 0;
#pragma unroll
  for (int k = 0; k < 64; k++) asm volatile("" : "=f"(o1[k]));
  asm volatile("" : "=f"(inv1.l0), "=f"(inv1.l1));
  while (true) {
    TRACE(i, 0); TRACE(i, 6);
    proj_main<WG>(c, r, a0, a1, h, d >> 30 ? ((d >> 16) & 63) + 1 : DM / 64, sw, i, dc, nq, o1, inv1);
    dc = d;
    TRACE(i, 1);
    if (d >> 30) goto out_tile;
    wg_wait<1>();
    acc_fence<WG>(a0);
    if (WG ? attention<WG>(c, r, i, d, a0, a1, o1, inv0, inv1, h) : attention<WG>(c, r, i, d, a0, o1, a1, inv1, inv0, h)) goto redo;
    if (d >= (2u << 30)) break;
    sw = d & (1u << 30);
    proj_begin<WG>(c, r, a0, h, false, sw);
    release_q<WG>(c);
    if (WG) sched_fence<8>(h.w, inv0.l0); else sched_fence<7>(h.w, inv0.l0, inv0.l1);
    o_first<WG>(c, dc, a1, inv0);
    sched_fence<9>(h.w, inv1.l0);
    proj_half<WG, true, 1>(c, a1, h.w, h.x, sw);
    nq = O_STEPS;
    TRACE(i, 3); TRACE(i, 7);
    i++;
  }
  release_q<WG>(c);
  o_first<WG>(c, dc, a1, inv0);
#pragma unroll
  for (int k = 1; k <= O_STEPS; k++) o_second<WG>(c, dc, k, o1, inv1);
next:
  TRACE(i, 3); TRACE(i, 7);
  if ((d >> 30) != 2) {
    i++;
    r.uniform();
    goto begin;
  }
  trace_dump(c);
  return;
out_tile:
  if (d & 96) goto finish;
  d = get_desc(c, i + 1);
  wg_wait<1>();
  acc_fence<WG>(a0);
  TRACE_O(0);
  stage_out<WG, 0>(c, a0);
  TRACE_O(1);
  proj_end<WG>(c, a1, h);
  TRACE_O(2);
  if (!EARLY_BEGIN || d >= (2u << 30)) { stage_out<WG, 1>(c, a1); TRACE(i, 2); goto next; }
  sw = d & (1u << 30);
  proj_begin<WG>(c, r, a0, h, true, sw);
  TRACE_O(3);
  stage_out<WG, 1>(c, a1);
  TRACE(i, 2); TRACE(i, 3); TRACE(i, 7);
  i++;
  goto begin1;
finish:
  {
    uint32_t q[32];
#pragma unroll 1
    for (int k = (d >> 5) & 3; k > 1; k--) {
      wg_wait<0>();
      acc_fence<WG>(a0); acc_fence<WG>(a1);
      if (k == ((d >> 5) & 3)) { release(c, h.x); release(c, h.w); }
      load_part<WG, 0>(c, r, q); add_part<WG>(c, q, a0);
      load_part<WG, 1>(c, r, q); add_part<WG>(c, q, a1);
#pragma unroll
      for (int t = 0; t < 4; t++) { release(c, r.slot); r.next(); }
    }
    load_part<WG, 0>(c, r, q);
    wg_wait<1>();
    acc_fence<WG>(a0);
    TRACE_O(0);
    add_part<WG>(c, q, a0);
    stage_out<WG, 0>(c, a0);
    TRACE_O(1);
    load_part<WG, 1>(c, r, q);
    wg_wait<0>();
    acc_fence<WG>(a1);
    TRACE_O(2);
    add_part<WG>(c, q, a1);
    stage_out<WG, 1>(c, a1);
    TRACE(i, 2); TRACE(i, 3); TRACE(i, 7);
    trace_dump(c);
    return;
  }
redo:
  {
    const size_t hoff = (size_t)(dc & 511) * (SK * DH);
    const int br = (dc >> 9) & 1;
#pragma unroll 1
    for (int part = 0; part < 2; part++) {
      const int t = WG ? 3 - part : part;
      redo_tile(c, c.sb + QBUF_OFF + t * 16384, t == 3 ? 4096 : 8192, kv[br] + hoff, kv[2 + br] + hoff, dc,
                t * 64 + (t == 3 ? 8 : 16) * c.warp);
    }
    o_done(c);
    release_q<WG>(c);
  }
  goto next;
}

template <bool SIMPLE>
__global__ void __launch_bounds__(384, 1) mha_fused_kernel(const __grid_constant__ Params P) {
  extern __shared__ __align__(1024) uint8_t smem_raw[];
  const uint32_t sbase = smem_u32(smem_raw);
  const int tid = threadIdx.x;
  const int wg = __shfl_sync(0xffffffffu, tid >> 7, 0);
  const int warp = __shfl_sync(0xffffffffu, (tid >> 5) & 3, 0);
  const int lane = tid & 31;
  const int cta = blockIdx.x;

  if (tid == 0) T3(15, 0);
  if ((sbase & 1023) || sbase + SMEM_BYTES > 0x40000) __trap();
  {
    const int wi = wg * 4 + warp;
    asm volatile(ELECT "prefetch.tensormap [%0];\n}" ::"l"(&P.x[0][0] + wi) : "memory");
#pragma unroll
    for (int k = 0; k < 3; k++) {
      const int b = min(BAR_OFF + (wi * 3 + k) * 8, BAR_GO);
      asm volatile(ELECT "mbarrier.init.shared::cta.b64 [%0], %1;\n}"
                   ::"r"(sbase + b), "r"(b < BAR_EMPTY || b >= BAR_DESC ? 1 : b >= BAR_STG && b < BAR_OUT ? 4 : 8) : "memory");
    }
    asm volatile("fence.mbarrier_init.release.cluster;" ::: "memory");
    if (wi < 6) asm volatile(ELECT "prefetch.tensormap [%0];\n}" ::"l"(&P.x[0][0] + 12 + wi) : "memory");
  }
  __syncthreads();

  if (wg == 2) {
    asm volatile("setmaxnreg.dec.sync.aligned.u32 %0;" ::"n"(REG_P));
    if (warp == 1) {
      const uint32_t qb = sbase + QBUF_OFF;
      const uint32_t ep = __shfl_sync(0xffffffffu, *(volatile unsigned*)&g_epoch + 1, 0);
      asm volatile("st.volatile.shared.u32 [%0], %1;" ::"r"(sbase + EPOCH_OFF), "r"(ep) : "memory");
      uint32_t dc = c_sched.queue[cta], qi = 0, piece = 0, na = 0;
      TTAIL(0);
      for (int i = 0; (dc >> 30) != 2; i++) {
        if (!(dc >> 30) && o_reuse<SIMPLE>((dc >> 5) & 31)) {
          const unsigned* rd = &g_rd[0][0] + ((dc & 1023) >> 2) - OR * 8;
          for (uint32_t n = 0; !__all_sync(0xffffffffu, reached(rd, ep * 5)); __nanosleep(300)) if (++n > (1u << 22)) __trap();
        }
        mbar_wait_w(sbase + BAR_GO, i & 1);
        if (piece == 0) {
          if (lane == 0) {
            qi = atomicAdd(&g_next, 1);
            if (qi == (SIMPLE ? Q_ALL : Q_RANGES) - 1) { g_next = 0; g_epoch = ep; }
          }
          qi = __shfl_sync(0xffffffffu, qi, 0) + (SIMPLE ? gridDim.x : NCTA);
        }
        uint32_t d;
        if (qi < (SIMPLE ? Q_ALL : Q_RANGES)) { d = c_sched.queue[qi]; if (d & 0x8000) d ^= (1u << 30) | (63u << 16) | 0x8000; else d |= o_slot<SIMPLE>(d >> 5) << 15 | (d & 31) << 10; }
        else if (SIMPLE) d = 2u << 30;
        else { const uint32_t e = qi - Q_RANGES, g = e / 5; d = c_sched.piece[g][piece++] | (e - g * 5) << 8; }
        if ((d >> 30) == 1) {
          const uint32_t k0 = (d >> 22) & 63;
          const uint32_t run = __ffs(__ballot_sync(0xffffffffu, !reached(&g_cnt[d & 31][lane & 7], ep * 4)) & (0xffu << (k0 >> 3))) - 1;
          if (run <= (k0 + ((d >> 16) & 63)) >> 3) d |= run <= (k0 + O_STEPS) >> 3 ? (2u << 30) | 128 : 128;
        }
        asm volatile("st.volatile.shared.u32 [%0], %1;" ::"r"(sbase + EPOCH_OFF + 4), "r"(qi) : "memory");
        asm volatile("st.volatile.shared.u32 [%0], %1;" ::"r"(sbase + DESC_OFF + ((i + 1) & 3) * 4), "r"(d) : "memory");
        __syncwarp();
        mbar_arrive_warp(sbase + BAR_DESC);
        const Work w = decode(dc);
        dc = d;
        if (w.kind == 0) {
          mbar_wait_w(sbase + BAR_OUT, na++ & 1);
          TTAIL(1);
          T3(i, 0); T3(i, 1);
          asm volatile(ELECT "red.release.gpu.global.add.u32 [%0], 1;\n}" ::"l"(&g_cnt[w.beta][w.sub >> 2]) : "memory");
          T3(i, 2);
          TTAIL(2);
          continue;
        }
        const bool fin = w.mode != 1;
        uint64_t pol, pol2;
        asm volatile("createpolicy.fractional.L2::evict_first.b64 %0, 1.0;" : "=l"(pol));
        asm volatile("createpolicy.fractional.L2::evict_normal.b64 %0, 1.0;" : "=l"(pol2));
        if (!fin) pol = pol2;
        const CUtensorMap* m = fin ? P.out_st : P.o_st;
        const int c1 = fin ? (w.beta & 15) * SQ : 0;
        const int c2 = fin ? (w.beta >> 4) * (DM / 64) + w.sub * 2 : NBETA * 64 + w.range * 2;
        uint32_t pend = 0;
#pragma unroll 1
        for (int e = 0; e < 4; e++) {
          const int t = (ST_ORDER >> (4 * e)) & 3;
          mbar_wait_w(sbase + BAR_STG + (t ^ (t >> 1)) * 8, (i - na) & 1);
          tma_st3_hint_w(m + (t == 3), qb + t * 16384, 0, c1 + t * 64, c2, pol);
          bulk_commit();
          T2P(i + 1, 5, 2 * e);
          if (pend) {
            bulk_wait_read<1>();
            mbar_arrive8_w(pend);
            T2P(i + 1, 5, 2 * e - 1);
          }
          pend = sbase + BAR_EMPTY + (NS + t) * 8;
          if ((ST_NOW >> e) & 1) {
            bulk_wait_read<0>();
            mbar_arrive8_w(pend);
            pend = 0;
            T2P(i + 1, 5, 2 * e + 1);
          }
        }
        if (w.beta < N_EARLY) asm volatile(ELECT "red.relaxed.gpu.global.add.u32 [%0], 1;\n}" ::"l"(&g_rd[w.beta][7]) : "memory");
        T3(i, 0);
        if (piece >= 2) TTAIL(piece * 2 - 1);
        asm volatile("cp.async.bulk.wait_group 0;" ::: "memory");
        T3(i, 1);
        if (w.mode == 1) asm volatile(ELECT "st.release.gpu.global.u32 [%0], %1;\n}" ::"l"(&g_flag[w.range]), "r"(ep) : "memory");
        T3(i, 2);
        if (piece >= 2) TTAIL(piece * 2);
      }
      T3(15, 1);
    } else
    if (warp == 0) {
      Ring r{0, 1, 3};
      uint32_t d = c_sched.queue[cta];
      for (int i = 0;; i++) {
        const Work w = decode(d);
        if (w.kind == 2) break;
        const CUtensorMap* m = w.kind == 0 ? &P.wq[w.beta >> 4] : &P.wo[w.beta >> 4];
        for (int ks = 0; ks < w.nsteps; ks++) {
          const uint32_t b = borrow(ks, w.nsteps);
          r.next_if(b == 2);
          const uint32_t bar = sbase + BAR_FULL + r.slot * 8;
          mbar_wait_w(bar + (BAR_EMPTY - BAR_FULL), r.phase);
          if (w.kind == 0) tma_ld3_w(sbase + r.slot * SLOT, m, 0, ks * 64, w.sub * 2, bar, 16384);
          else tma_ld_wo_w(sbase + r.slot * SLOT, m, w.sub * 128, (w.k0 + ks) * 2, bar);
          if (w.kind != 0 && w.beta < N_EARLY && (ks & 7) == 5 && ks > 5)
            asm volatile(ELECT "red.relaxed.gpu.global.add.u32 [%0], 1;\n}" ::"l"(&g_rd[w.beta][(ks >> 3) - 1]) : "memory");
          if (ks < 10) T2P(i, 2, ks);
          if (w.kind != 0 && ks == max(w.nsteps - GO_P, 4)) mbar_arrive_warp(sbase + BAR_GO);
          r.next(); r.next_if(b == 2);
        }
        if (w.kind == 0) {
          r.phase ^= 1; r.next(); r.next();
        } else if (w.mode == 2) {
          for (int k = 1; k <= ((d >> 5) & 3); k++) {
            if (k == 1) TTAIL(9);
            wait_count(&g_flag[w.range + 5 * k], lds(sbase + EPOCH_OFF));
            TTAIL(10);
            asm volatile("fence.proxy.async.global;" ::: "memory");
#pragma unroll 1
            for (int t = 0; t < 4; t++) {
              mbar_wait_w(sbase + BAR_EMPTY + r.slot * 8, r.phase);
              tma_ld3_w(sbase + r.slot * SLOT, &P.o_st[t == 3], 0, t * 64, NBETA * 64 + (w.range + 5 * k) * 2, sbase + BAR_FULL + r.slot * 8,
                        t == 3 ? 8192 : 16384);
              r.next();
            }
          }
        }
        mbar_wait_w(sbase + BAR_DESC, i & 1);
        d = __shfl_sync(0xffffffffu, lds(sbase + DESC_OFF + ((i + 1) & 3) * 4), 0);
      }
    } else {
      const int hi = warp - 2;
      uint64_t pol_stream;
      asm volatile("createpolicy.fractional.L2::evict_first.b64 %0, 1.0;" : "=l"(pol_stream));
      Ring r{0, 1, 3};
      uint32_t d = c_sched.queue[cta];
      for (int i = 0;; i++) {
        const Work w = decode(d);
        if (w.kind == 2) break;
        const CUtensorMap* m = w.kind == 0 ? &P.x[hi][w.beta >> 4] : &P.o_ld[hi];
        int c1 = (w.kind == 0 ? (w.beta & 15) : o_slot<SIMPLE>(w.beta) * 64 + w.k0) * SQ + hi * 128;
        int k_wait = -1;
        if (w.kind != 0) {
          if (d & 128) k_wait = d >= (3u << 30) ? 0 : 8 - (w.k0 & 7);
          asm volatile("fence.proxy.async.global;" ::: "memory");
        }
        const int rank = i == 0 ? cta : __shfl_sync(0xffffffffu, lds(sbase + EPOCH_OFF + 4), 0) - NCTA;
        for (int ks = 0; ks < w.nsteps; ks++) {
          if (ks == k_wait) {
            wait_count(&g_cnt[d & 31][(w.k0 + ks) >> 3], lds(sbase + EPOCH_OFF) * 4);
            asm volatile("fence.proxy.async.global;" ::: "memory");
            k_wait = ((w.k0 + ks) | 7) + 1 - w.k0;
          }
          const uint32_t b = borrow(ks, w.nsteps);
          const bool bo = b != 2;
          r.next_if(hi && !bo); r.next_if(hi && !bo);
          const uint32_t sl = bo ? NS + (b ^ (3 * hi)) : r.slot, bar = sbase + BAR_FULL + sl * 8;
          mbar_wait_w(bar + (BAR_EMPTY - BAR_FULL), bo ? (r.xp >> b) & 1 : r.phase);
          if (w.kind == 0) tma_ld2_w(sbase + sl * SLOT, m, ks * 64, c1, bar, (hi ? 96 * 128 : 128 * 128));
          else { tma_ld2_hint_w(sbase + sl * SLOT, m, 0, c1, bar, hi ? 96 * 128 : 128 * 128, pol_stream); c1 += SQ; }
          if (i == 0 && ks == PF_STEP)
            asm volatile(ELECT "cp.async.bulk.prefetch.tensor.3d.L2.global.L2::cache_hint [%0, {0, %1, 0}], %2;\n}"
                         ::"l"(&P.kv[hi][0]), "r"(d * SK), "l"(pol_stream) : "memory");
          if (ks < 10) T2P(i, 3 + hi, ks);
          if (!hi && w.kind != 0 && !(ks & 3)) TCLK(i * 16 + (ks >> 2));
          r.next(); r.next_if(!hi && !bo); r.next_if(!hi && !bo);
          r.xp ^= 1 << b;
        }
        r.xp ^= 3;
        if (w.kind == 0) {
          m = &P.kv[hi][w.beta >> 4];
          c1 = (d & 511) * SK;
          for (int j = 0; j < 16; j++) {
            if (hi) r.next();
            const uint32_t bar = sbase + BAR_FULL + r.slot * 8;
            const bool tight = i < KV_WIN_UNITS && j < KV_WIN_TILES + ((KV_WIN_RAMP * rank) >> 5);
            {
              const int s2 = (int)r.slot - (tight ? 2 : KV_WIN_D);
              mbar_wait_w(sbase + BAR_FULL + (s2 < 0 ? s2 + NS : s2) * 8, s2 < 0 ? r.phase : r.phase ^ 1);
            }
            if (j == 15 && hi) mbar_wait_w(sbase + BAR_DESC, i & 1);
            mbar_wait_w(sbase + BAR_EMPTY + r.slot * 8, r.phase);
            tma_ld3_hint_w(sbase + r.slot * SLOT, m, 0, c1, 0, bar, pol_stream);
            T2P(i, 3 + hi, 16 + j);
            if (!hi) TCLK(i * 16 + j);
            if (j == 14 && !hi) mbar_arrive_warp(sbase + BAR_GO);
            c1 += 64;
            r.next();
            if (!hi) r.next();
          }
        }
        mbar_wait_w(sbase + BAR_DESC, i & 1);
        d = __shfl_sync(0xffffffffu, lds(sbase + DESC_OFF + ((i + 1) & 3) * 4), 0);
      }
    }
  } else {
    Ctx c;
    c.sb = sbase; c.wg = wg; c.warp = warp; c.src = 0; c.mqk = 0; c.mpv = 0; c.lead = lane == 0; c.lane0 = c.lane = lane;
    if (wg == 0) consumer<0>(c, P.kp); else consumer<1>(c, P.kp);
  }
}

typedef CUresult (*EncodeFn)(CUtensorMap*, CUtensorMapDataType, cuuint32_t, void*, const cuuint64_t*, const cuuint64_t*,
                             const cuuint32_t*, const cuuint32_t*, CUtensorMapInterleave, CUtensorMapSwizzle,
                             CUtensorMapL2promotion, CUtensorMapFloatOOBfill);

void make_map(EncodeFn enc, CUtensorMap* m, const void* ptr, int rank, const cuuint64_t* dims, const cuuint64_t* strides,
              const cuuint32_t* box, int promo = 2, CUtensorMapSwizzle swz = CU_TENSOR_MAP_SWIZZLE_128B) {
  cuuint32_t es[5] = {1, 1, 1, 1, 1};
  enc(m, CU_TENSOR_MAP_DATA_TYPE_BFLOAT16, rank, const_cast<void*>(ptr), dims, strides, box, es,
      CU_TENSOR_MAP_INTERLEAVE_NONE, swz, promo == 2 ? CU_TENSOR_MAP_L2_PROMOTION_L2_256B : promo == 1 ? CU_TENSOR_MAP_L2_PROMOTION_L2_128B : CU_TENSOR_MAP_L2_PROMOTION_NONE,
      CU_TENSOR_MAP_FLOAT_OOB_FILL_NONE);
}

}

extern "C" void kernel_launch(void* const* d_in, const int* in_sizes, int n_in, void* d_out, int out_size) {
  (void)in_sizes; (void)n_in; (void)out_size;
  static EncodeFn enc = nullptr;
  static void* o_ptr = nullptr;
  static int n_sm = 0;
  if (!enc) {
    void* fn = nullptr;
    cudaDriverEntryPointQueryResult qr;
    cudaGetDriverEntryPoint("cuTensorMapEncodeTiled", &fn, cudaEnableDefault, &qr);
    enc = (EncodeFn)fn;
    cudaGetSymbolAddress(&o_ptr, g_o);
    cudaFuncSetAttribute(mha_fused_kernel<false>, cudaFuncAttributeMaxDynamicSharedMemorySize, SMEM_BYTES);
    cudaFuncSetAttribute(mha_fused_kernel<true>, cudaFuncAttributeMaxDynamicSharedMemorySize, SMEM_BYTES);
    int dev = 0;
    cudaGetDevice(&dev);
    cudaDeviceGetAttribute(&n_sm, cudaDevAttrMultiProcessorCount, dev);
  }
  Params P;
  for (int br = 0; br < 2; br++) {
    const void* x = d_in[br * 5 + 0]; const void* kc = d_in[br * 5 + 1]; const void* vc = d_in[br * 5 + 2];
    const void* wq = d_in[br * 5 + 3]; const void* wo = d_in[br * 5 + 4];
    { cuuint64_t d[2] = {DM, (cuuint64_t)NB * SQ}, s[1] = {DM * 2}; cuuint32_t b[2] = {64, 128}, b2[2] = {64, 96};
      make_map(enc, &P.x[0][br], x, 2, d, s, b, PR_X); make_map(enc, &P.x[1][br], x, 2, d, s, b2, PR_X); }
    { cuuint64_t d[3] = {64, DM, HD / 64}, s[2] = {HD * 2, 128}; cuuint32_t b[3] = {64, 64, 2}; make_map(enc, &P.wq[br], wq, 3, d, s, b, PR_W); }
    { cuuint64_t d[5] = {DM, 2, 4, 4, HD / 32}, s[4] = {DM * 2, 8 * DM * 2, 2 * DM * 2, 32 * DM * 2}; cuuint32_t b[5] = {64, 2, 4, 4, 2};
      make_map(enc, &P.wo[br], wo, 5, d, s, b, PR_W); }
    { cuuint64_t d[3] = {64, (cuuint64_t)NB * NH * SK, 2}, s[2] = {DH * 2, 128}; cuuint32_t b[3] = {64, 64, 2};
      make_map(enc, &P.kv[0][br], kc, 3, d, s, b, PR_KV); make_map(enc, &P.kv[1][br], vc, 3, d, s, b, PR_KV); }
    P.kp[br] = (const __nv_bfloat16*)kc; P.vp[br] = (const __nv_bfloat16*)vc;

  }
  { cuuint64_t d[2] = {64, (cuuint64_t)NBETA * 64 * SQ}, s[1] = {128}; cuuint32_t b[2] = {64, 128}, b2[2] = {64, 96};
    make_map(enc, &P.o_ld[0], o_ptr, 2, d, s, b, 2, CU_TENSOR_MAP_SWIZZLE_NONE); make_map(enc, &P.o_ld[1], o_ptr, 2, d, s, b2, 2, CU_TENSOR_MAP_SWIZZLE_NONE); }
  { cuuint64_t d[3] = {64, SQ, O_BLOCKS}, s[2] = {128, SQ * 128}; cuuint32_t b[3] = {64, 64, 2}, b2[3] = {64, 32, 2};
    make_map(enc, &P.o_st[0], o_ptr, 3, d, s, b); make_map(enc, &P.o_st[1], o_ptr, 3, d, s, b2); }
  { cuuint64_t d[3] = {64, (cuuint64_t)NB * SQ, 2 * DM / 64}, s[2] = {2 * DM * 2, 128}; cuuint32_t b[3] = {64, 64, 2}, b2[3] = {64, 32, 2};
    make_map(enc, &P.out_st[0], d_out, 3, d, s, b); make_map(enc, &P.out_st[1], d_out, 3, d, s, b2); }
  if (n_sm >= NCTA) mha_fused_kernel<false><<<NCTA, 384, SMEM_BYTES>>>(P);
  else mha_fused_kernel<true><<<n_sm, 384, SMEM_BYTES>>>(P);
}
```

```cpp
#include <cuda_runtime.h>
#include <cuda_bf16.h>
#include <cuda.h>
#include <stdint.h>
#include <stdlib.h>

namespace {

__device__ __forceinline__ void wgmma_proj(float (&d)[64], uint64_t da, uint64_t db, int scaleD) {
  asm volatile("{\n.reg .pred p;\nsetp.ne.b32 p, %66, 0;\n"
      "wgmma.mma_async.sync.aligned.m64n128k16.f32.bf16.bf16 "
      "{%0, %1, %2, %3, %4, %5, %6, %7, %8, %9, %10, %11, %12, %13, %14, %15, %16, %17, %18, %19, %20, %21, %22, %23, %24, %25, %26, %27, %28, %29, %30, "
      "%31, %32, %33, %34, %35, %36, %37, %38, %39, %40, %41, %42, %43, %44, %45, %46, %47, %48, %49, %50, %51, %52, %53, %54, %55, %56, %57, %58, %59, %60, "
      "%61, %62, %63}, "
      "%64, %65, p, 1, 1, 0, 1;\n}\n"
      : "+f"(d[0]), "+f"(d[1]), "+f"(d[2]), "+f"(d[3]), "+f"(d[4]), "+f"(d[5]), "+f"(d[6]), "+f"(d[7]), "+f"(d[8]), "+f"(d[9]), "+f"(d[10]), "+f"(d[11]),
        "+f"(d[12]), "+f"(d[13]), "+f"(d[14]), "+f"(d[15]), "+f"(d[16]), "+f"(d[17]), "+f"(d[18]), "+f"(d[19]), "+f"(d[20]), "+f"(d[21]), "+f"(d[22]),
        "+f"(d[23]), "+f"(d[24]), "+f"(d[25]), "+f"(d[26]), "+f"(d[27]), "+f"(d[28]), "+f"(d[29]), "+f"(d[30]), "+f"(d[31]), "+f"(d[32]), "+f"(d[33]),
        "+f"(d[34]), "+f"(d[35]), "+f"(d[36]), "+f"(d[37]), "+f"(d[38]), "+f"(d[39]), "+f"(d[40]), "+f"(d[41]), "+f"(d[42]), "+f"(d[43]), "+f"(d[44]),
        "+f"(d[45]), "+f"(d[46]), "+f"(d[47]), "+f"(d[48]), "+f"(d[49]), "+f"(d[50]), "+f"(d[51]), "+f"(d[52]), "+f"(d[53]), "+f"(d[54]), "+f"(d[55]),
        "+f"(d[56]), "+f"(d[57]), "+f"(d[58]), "+f"(d[59]), "+f"(d[60]), "+f"(d[61]), "+f"(d[62]), "+f"(d[63])
      : "l"(da), "l"(db), "r"(scaleD));
}
__device__ __forceinline__ void wgmma_proj96(float (&d)[64], uint64_t da, uint64_t db, int scaleD) {
  asm volatile("{\n.reg .pred p;\nsetp.ne.b32 p, %50, 0;\n"
      "wgmma.mma_async.sync.aligned.m64n96k16.f32.bf16.bf16 "
      "{%0, %1, %2, %3, %4, %5, %6, %7, %8, %9, %10, %11, %12, %13, %14, %15, %16, %17, %18, %19, %20, %21, %22, %23, %24, %25, %26, %27, %28, %29, %30, "
      "%31, %32, %33, %34, %35, %36, %37, %38, %39, %40, %41, %42, %43, %44, %45, %46, %47}, "
      "%48, %49, p, 1, 1, 1, 0;\n}\n"
      : "+f"(d[0]), "+f"(d[1]), "+f"(d[2]), "+f"(d[3]), "+f"(d[4]), "+f"(d[5]), "+f"(d[6]), "+f"(d[7]), "+f"(d[8]), "+f"(d[9]), "+f"(d[10]), "+f"(d[11]),
        "+f"(d[12]), "+f"(d[13]), "+f"(d[14]), "+f"(d[15]), "+f"(d[16]), "+f"(d[17]), "+f"(d[18]), "+f"(d[19]), "+f"(d[20]), "+f"(d[21]), "+f"(d[22]),
        "+f"(d[23]), "+f"(d[24]), "+f"(d[25]), "+f"(d[26]), "+f"(d[27]), "+f"(d[28]), "+f"(d[29]), "+f"(d[30]), "+f"(d[31]), "+f"(d[32]), "+f"(d[33]),
        "+f"(d[34]), "+f"(d[35]), "+f"(d[36]), "+f"(d[37]), "+f"(d[38]), "+f"(d[39]), "+f"(d[40]), "+f"(d[41]), "+f"(d[42]), "+f"(d[43]), "+f"(d[44]),
        "+f"(d[45]), "+f"(d[46]), "+f"(d[47])
      : "l"(da), "l"(db), "r"(scaleD));
}
__device__ __forceinline__ void wgmma_qk(float (&d)[32], uint64_t da, uint64_t db, int scaleD) {
  asm volatile("{\n.reg .pred p;\nsetp.ne.b32 p, %34, 0;\n"
      "wgmma.mma_async.sync.aligned.m64n64k16.f32.bf16.bf16 "
      "{%0, %1, %2, %3, %4, %5, %6, %7, %8, %9, %10, %11, %12, %13, %14, %15, %16, %17, %18, %19, %20, %21, %22, %23, %24, %25, %26, %27, %28, %29, %30, "
      "%31}, "
      "%32, %33, p, 1, 1, 0, 0;\n}\n"
      : "+f"(d[0]), "+f"(d[1]), "+f"(d[2]), "+f"(d[3]), "+f"(d[4]), "+f"(d[5]), "+f"(d[6]), "+f"(d[7]), "+f"(d[8]), "+f"(d[9]), "+f"(d[10]), "+f"(d[11]),
        "+f"(d[12]), "+f"(d[13]), "+f"(d[14]), "+f"(d[15]), "+f"(d[16]), "+f"(d[17]), "+f"(d[18]), "+f"(d[19]), "+f"(d[20]), "+f"(d[21]), "+f"(d[22]),
        "+f"(d[23]), "+f"(d[24]), "+f"(d[25]), "+f"(d[26]), "+f"(d[27]), "+f"(d[28]), "+f"(d[29]), "+f"(d[30]), "+f"(d[31])
      : "l"(da), "l"(db), "r"(scaleD));
}
__device__ __forceinline__ void wgmma_qk_rs(float (&d)[32], uint32_t a0, uint32_t a1, uint32_t a2, uint32_t a3, uint64_t db, int scaleD) {
  asm volatile("{\n.reg .pred p;\nsetp.ne.b32 p, %37, 0;\n"
      "wgmma.mma_async.sync.aligned.m64n64k16.f32.bf16.bf16 "
      "{%0, %1, %2, %3, %4, %5, %6, %7, %8, %9, %10, %11, %12, %13, %14, %15, %16, %17, %18, %19, %20, %21, %22, %23, %24, %25, %26, %27, %28, %29, %30, "
      "%31}, "
      "{%32, %33, %34, %35}, %36, p, 1, 1, 0;\n}\n"
      : "+f"(d[0]), "+f"(d[1]), "+f"(d[2]), "+f"(d[3]), "+f"(d[4]), "+f"(d[5]), "+f"(d[6]), "+f"(d[7]), "+f"(d[8]), "+f"(d[9]), "+f"(d[10]), "+f"(d[11]),
        "+f"(d[12]), "+f"(d[13]), "+f"(d[14]), "+f"(d[15]), "+f"(d[16]), "+f"(d[17]), "+f"(d[18]), "+f"(d[19]), "+f"(d[20]), "+f"(d[21]), "+f"(d[22]),
        "+f"(d[23]), "+f"(d[24]), "+f"(d[25]), "+f"(d[26]), "+f"(d[27]), "+f"(d[28]), "+f"(d[29]), "+f"(d[30]), "+f"(d[31])
      : "r"(a0), "r"(a1), "r"(a2), "r"(a3), "l"(db), "r"(scaleD));
}
__device__ __forceinline__ void wgmma_pv(float (&d)[64], uint32_t a0, uint32_t a1, uint32_t a2, uint32_t a3, uint64_t db, int scaleD) {
  asm volatile("{\n.reg .pred p;\nsetp.ne.b32 p, %69, 0;\n"
      "wgmma.mma_async.sync.aligned.m64n128k16.f32.bf16.bf16 "
      "{%0, %1, %2, %3, %4, %5, %6, %7, %8, %9, %10, %11, %12, %13, %14, %15, %16, %17, %18, %19, %20, %21, %22, %23, %24, %25, %26, %27, %28, %29, %30, "
      "%31, %32, %33, %34, %35, %36, %37, %38, %39, %40, %41, %42, %43, %44, %45, %46, %47, %48, %49, %50, %51, %52, %53, %54, %55, %56, %57, %58, %59, %60, "
      "%61, %62, %63}, "
      "{%64, %65, %66, %67}, %68, p, 1, 1, 1;\n}\n"
      : "+f"(d[0]), "+f"(d[1]), "+f"(d[2]), "+f"(d[3]), "+f"(d[4]), "+f"(d[5]), "+f"(d[6]), "+f"(d[7]), "+f"(d[8]), "+f"(d[9]), "+f"(d[10]), "+f"(d[11]),
        "+f"(d[12]), "+f"(d[13]), "+f"(d[14]), "+f"(d[15]), "+f"(d[16]), "+f"(d[17]), "+f"(d[18]), "+f"(d[19]), "+f"(d[20]), "+f"(d[21]), "+f"(d[22]),
        "+f"(d[23]), "+f"(d[24]), "+f"(d[25]), "+f"(d[26]), "+f"(d[27]), "+f"(d[28]), "+f"(d[29]), "+f"(d[30]), "+f"(d[31]), "+f"(d[32]), "+f"(d[33]),
        "+f"(d[34]), "+f"(d[35]), "+f"(d[36]), "+f"(d[37]), "+f"(d[38]), "+f"(d[39]), "+f"(d[40]), "+f"(d[41]), "+f"(d[42]), "+f"(d[43]), "+f"(d[44]),
        "+f"(d[45]), "+f"(d[46]), "+f"(d[47]), "+f"(d[48]), "+f"(d[49]), "+f"(d[50]), "+f"(d[51]), "+f"(d[52]), "+f"(d[53]), "+f"(d[54]), "+f"(d[55]),
        "+f"(d[56]), "+f"(d[57]), "+f"(d[58]), "+f"(d[59]), "+f"(d[60]), "+f"(d[61]), "+f"(d[62]), "+f"(d[63])
      : "r"(a0), "r"(a1), "r"(a2), "r"(a3), "l"(db), "r"(scaleD));
}
__device__ __forceinline__ void wgmma_qk_sp(float (&d)[32], uint32_t a0, uint32_t a1, uint32_t a2, uint32_t a3, uint64_t db, int scaleD, uint32_t meta) {
  asm volatile("{\n.reg .pred p;\nsetp.ne.b32 p, %37, 0;\n"
      "wgmma.mma_async.sp.sync.aligned.m64n64k32.f32.bf16.bf16 "
      "{%0, %1, %2, %3, %4, %5, %6, %7, %8, %9, %10, %11, %12, %13, %14, %15, %16, %17, %18, %19, %20, %21, %22, %23, %24, %25, %26, %27, %28, %29, %30, "
      "%31}, "
      "{%32, %33, %34, %35}, %36, %38, 0, p, 1, 1, 0;\n}\n"
      : "+f"(d[0]), "+f"(d[1]), "+f"(d[2]), "+f"(d[3]), "+f"(d[4]), "+f"(d[5]), "+f"(d[6]), "+f"(d[7]), "+f"(d[8]), "+f"(d[9]), "+f"(d[10]), "+f"(d[11]),
        "+f"(d[12]), "+f"(d[13]), "+f"(d[14]), "+f"(d[15]), "+f"(d[16]), "+f"(d[17]), "+f"(d[18]), "+f"(d[19]), "+f"(d[20]), "+f"(d[21]), "+f"(d[22]),
        "+f"(d[23]), "+f"(d[24]), "+f"(d[25]), "+f"(d[26]), "+f"(d[27]), "+f"(d[28]), "+f"(d[29]), "+f"(d[30]), "+f"(d[31])
      : "r"(a0), "r"(a1), "r"(a2), "r"(a3), "l"(db), "r"(scaleD), "r"(meta));
}
__device__ __forceinline__ void wgmma_pv_sp(float (&d)[64], uint32_t a0, uint32_t a1, uint32_t a2, uint32_t a3, uint64_t db, int scaleD, uint32_t meta) {
  asm volatile("{\n.reg .pred p;\nsetp.ne.b32 p, %69, 0;\n"
      "wgmma.mma_async.sp.sync.aligned.m64n128k32.f32.bf16.bf16 "
      "{%0, %1, %2, %3, %4, %5, %6, %7, %8, %9, %10, %11, %12, %13, %14, %15, %16, %17, %18, %19, %20, %21, %22, %23, %24, %25, %26, %27, %28, %29, %30, "
      "%31, %32, %33, %34, %35, %36, %37, %38, %39, %40, %41, %42, %43, %44, %45, %46, %47, %48, %49, %50, %51, %52, %53, %54, %55, %56, %57, %58, %59, %60, "
      "%61, %62, %63}, "
      "{%64, %65, %66, %67}, %68, %70, 0, p, 1, 1, 1;\n}\n"
      : "+f"(d[0]), "+f"(d[1]), "+f"(d[2]), "+f"(d[3]), "+f"(d[4]), "+f"(d[5]), "+f"(d[6]), "+f"(d[7]), "+f"(d[8]), "+f"(d[9]), "+f"(d[10]), "+f"(d[11]),
        "+f"(d[12]), "+f"(d[13]), "+f"(d[14]), "+f"(d[15]), "+f"(d[16]), "+f"(d[17]), "+f"(d[18]), "+f"(d[19]), "+f"(d[20]), "+f"(d[21]), "+f"(d[22]),
        "+f"(d[23]), "+f"(d[24]), "+f"(d[25]), "+f"(d[26]), "+f"(d[27]), "+f"(d[28]), "+f"(d[29]), "+f"(d[30]), "+f"(d[31]), "+f"(d[32]), "+f"(d[33]),
        "+f"(d[34]), "+f"(d[35]), "+f"(d[36]), "+f"(d[37]), "+f"(d[38]), "+f"(d[39]), "+f"(d[40]), "+f"(d[41]), "+f"(d[42]), "+f"(d[43]), "+f"(d[44]),
        "+f"(d[45]), "+f"(d[46]), "+f"(d[47]), "+f"(d[48]), "+f"(d[49]), "+f"(d[50]), "+f"(d[51]), "+f"(d[52]), "+f"(d[53]), "+f"(d[54]), "+f"(d[55]),
        "+f"(d[56]), "+f"(d[57]), "+f"(d[58]), "+f"(d[59]), "+f"(d[60]), "+f"(d[61]), "+f"(d[62]), "+f"(d[63])
      : "r"(a0), "r"(a1), "r"(a2), "r"(a3), "l"(db), "r"(scaleD), "r"(meta));
}
__device__ __forceinline__ void wgmma_proj_init(float (&d)[64], uint64_t da, uint64_t db, int scaleD) {
  asm volatile("{\n.reg .pred p;\nsetp.ne.b32 p, %66, 0;\n"
      "wgmma.mma_async.sync.aligned.m64n128k16.f32.bf16.bf16 "
      "{%0, %1, %2, %3, %4, %5, %6, %7, %8, %9, %10, %11, %12, %13, %14, %15, %16, %17, %18, %19, %20, %21, %22, %23, %24, %25, %26, %27, %28, %29, %30, "
      "%31, %32, %33, %34, %35, %36, %37, %38, %39, %40, %41, %42, %43, %44, %45, %46, %47, %48, %49, %50, %51, %52, %53, %54, %55, %56, %57, %58, %59, %60, "
      "%61, %62, %63}, "
      "%64, %65, p, 1, 1, 0, 1;\n}\n"
      : "=f"(d[0]), "=f"(d[1]), "=f"(d[2]), "=f"(d[3]), "=f"(d[4]), "=f"(d[5]), "=f"(d[6]), "=f"(d[7]), "=f"(d[8]), "=f"(d[9]), "=f"(d[10]), "=f"(d[11]),
        "=f"(d[12]), "=f"(d[13]), "=f"(d[14]), "=f"(d[15]), "=f"(d[16]), "=f"(d[17]), "=f"(d[18]), "=f"(d[19]), "=f"(d[20]), "=f"(d[21]), "=f"(d[22]),
        "=f"(d[23]), "=f"(d[24]), "=f"(d[25]), "=f"(d[26]), "=f"(d[27]), "=f"(d[28]), "=f"(d[29]), "=f"(d[30]), "=f"(d[31]), "=f"(d[32]), "=f"(d[33]),
        "=f"(d[34]), "=f"(d[35]), "=f"(d[36]), "=f"(d[37]), "=f"(d[38]), "=f"(d[39]), "=f"(d[40]), "=f"(d[41]), "=f"(d[42]), "=f"(d[43]), "=f"(d[44]),
        "=f"(d[45]), "=f"(d[46]), "=f"(d[47]), "=f"(d[48]), "=f"(d[49]), "=f"(d[50]), "=f"(d[51]), "=f"(d[52]), "=f"(d[53]), "=f"(d[54]), "=f"(d[55]),
        "=f"(d[56]), "=f"(d[57]), "=f"(d[58]), "=f"(d[59]), "=f"(d[60]), "=f"(d[61]), "=f"(d[62]), "=f"(d[63])
      : "l"(da), "l"(db), "r"(scaleD));
}
__device__ __forceinline__ void wgmma_proj96_init(float (&d)[64], uint64_t da, uint64_t db, int scaleD) {
  asm volatile("{\n.reg .pred p;\nsetp.ne.b32 p, %50, 0;\n"
      "wgmma.mma_async.sync.aligned.m64n96k16.f32.bf16.bf16 "
      "{%0, %1, %2, %3, %4, %5, %6, %7, %8, %9, %10, %11, %12, %13, %14, %15, %16, %17, %18, %19, %20, %21, %22, %23, %24, %25, %26, %27, %28, %29, %30, "
      "%31, %32, %33, %34, %35, %36, %37, %38, %39, %40, %41, %42, %43, %44, %45, %46, %47}, "
      "%48, %49, p, 1, 1, 1, 0;\n}\n"
      : "=f"(d[0]), "=f"(d[1]), "=f"(d[2]), "=f"(d[3]), "=f"(d[4]), "=f"(d[5]), "=f"(d[6]), "=f"(d[7]), "=f"(d[8]), "=f"(d[9]), "=f"(d[10]), "=f"(d[11]),
        "=f"(d[12]), "=f"(d[13]), "=f"(d[14]), "=f"(d[15]), "=f"(d[16]), "=f"(d[17]), "=f"(d[18]), "=f"(d[19]), "=f"(d[20]), "=f"(d[21]), "=f"(d[22]),
        "=f"(d[23]), "=f"(d[24]), "=f"(d[25]), "=f"(d[26]), "=f"(d[27]), "=f"(d[28]), "=f"(d[29]), "=f"(d[30]), "=f"(d[31]), "=f"(d[32]), "=f"(d[33]),
        "=f"(d[34]), "=f"(d[35]), "=f"(d[36]), "=f"(d[37]), "=f"(d[38]), "=f"(d[39]), "=f"(d[40]), "=f"(d[41]), "=f"(d[42]), "=f"(d[43]), "=f"(d[44]),
        "=f"(d[45]), "=f"(d[46]), "=f"(d[47])
      : "l"(da), "l"(db), "r"(scaleD));
}
__device__ __forceinline__ void wgmma_qk_init(float (&d)[32], uint64_t da, uint64_t db, int scaleD) {
  asm volatile("{\n.reg .pred p;\nsetp.ne.b32 p, %34, 0;\n"
      "wgmma.mma_async.sync.aligned.m64n64k16.f32.bf16.bf16 "
      "{%0, %1, %2, %3, %4, %5, %6, %7, %8, %9, %10, %11, %12, %13, %14, %15, %16, %17, %18, %19, %20, %21, %22, %23, %24, %25, %26, %27, %28, %29, %30, "
      "%31}, "
      "%32, %33, p, 1, 1, 0, 0;\n}\n"
      : "=f"(d[0]), "=f"(d[1]), "=f"(d[2]), "=f"(d[3]), "=f"(d[4]), "=f"(d[5]), "=f"(d[6]), "=f"(d[7]), "=f"(d[8]), "=f"(d[9]), "=f"(d[10]), "=f"(d[11]),
        "=f"(d[12]), "=f"(d[13]), "=f"(d[14]), "=f"(d[15]), "=f"(d[16]), "=f"(d[17]), "=f"(d[18]), "=f"(d[19]), "=f"(d[20]), "=f"(d[21]), "=f"(d[22]),
        "=f"(d[23]), "=f"(d[24]), "=f"(d[25]), "=f"(d[26]), "=f"(d[27]), "=f"(d[28]), "=f"(d[29]), "=f"(d[30]), "=f"(d[31])
      : "l"(da), "l"(db), "r"(scaleD));
}
__device__ __forceinline__ void wgmma_qk_rs_init(float (&d)[32], uint32_t a0, uint32_t a1, uint32_t a2, uint32_t a3, uint64_t db, int scaleD) {
  asm volatile("{\n.reg .pred p;\nsetp.ne.b32 p, %37, 0;\n"
      "wgmma.mma_async.sync.aligned.m64n64k16.f32.bf16.bf16 "
      "{%0, %1, %2, %3, %4, %5, %6, %7, %8, %9, %10, %11, %12, %13, %14, %15, %16, %17, %18, %19, %20, %21, %22, %23, %24, %25, %26, %27, %28, %29, %30, "
      "%31}, "
      "{%32, %33, %34, %35}, %36, p, 1, 1, 0;\n}\n"
      : "=f"(d[0]), "=f"(d[1]), "=f"(d[2]), "=f"(d[3]), "=f"(d[4]), "=f"(d[5]), "=f"(d[6]), "=f"(d[7]), "=f"(d[8]), "=f"(d[9]), "=f"(d[10]), "=f"(d[11]),
        "=f"(d[12]), "=f"(d[13]), "=f"(d[14]), "=f"(d[15]), "=f"(d[16]), "=f"(d[17]), "=f"(d[18]), "=f"(d[19]), "=f"(d[20]), "=f"(d[21]), "=f"(d[22]),
        "=f"(d[23]), "=f"(d[24]), "=f"(d[25]), "=f"(d[26]), "=f"(d[27]), "=f"(d[28]), "=f"(d[29]), "=f"(d[30]), "=f"(d[31])
      : "r"(a0), "r"(a1), "r"(a2), "r"(a3), "l"(db), "r"(scaleD));
}
__device__ __forceinline__ void wgmma_pv_init(float (&d)[64], uint32_t a0, uint32_t a1, uint32_t a2, uint32_t a3, uint64_t db, int scaleD) {
  asm volatile("{\n.reg .pred p;\nsetp.ne.b32 p, %69, 0;\n"
      "wgmma.mma_async.sync.aligned.m64n128k16.f32.bf16.bf16 "
      "{%0, %1, %2, %3, %4, %5, %6, %7, %8, %9, %10, %11, %12, %13, %14, %15, %16, %17, %18, %19, %20, %21, %22, %23, %24, %25, %26, %27, %28, %29, %30, "
      "%31, %32, %33, %34, %35, %36, %37, %38, %39, %40, %41, %42, %43, %44, %45, %46, %47, %48, %49, %50, %51, %52, %53, %54, %55, %56, %57, %58, %59, %60, "
      "%61, %62, %63}, "
      "{%64, %65, %66, %67}, %68, p, 1, 1, 1;\n}\n"
      : "=f"(d[0]), "=f"(d[1]), "=f"(d[2]), "=f"(d[3]), "=f"(d[4]), "=f"(d[5]), "=f"(d[6]), "=f"(d[7]), "=f"(d[8]), "=f"(d[9]), "=f"(d[10]), "=f"(d[11]),
        "=f"(d[12]), "=f"(d[13]), "=f"(d[14]), "=f"(d[15]), "=f"(d[16]), "=f"(d[17]), "=f"(d[18]), "=f"(d[19]), "=f"(d[20]), "=f"(d[21]), "=f"(d[22]),
        "=f"(d[23]), "=f"(d[24]), "=f"(d[25]), "=f"(d[26]), "=f"(d[27]), "=f"(d[28]), "=f"(d[29]), "=f"(d[30]), "=f"(d[31]), "=f"(d[32]), "=f"(d[33]),
        "=f"(d[34]), "=f"(d[35]), "=f"(d[36]), "=f"(d[37]), "=f"(d[38]), "=f"(d[39]), "=f"(d[40]), "=f"(d[41]), "=f"(d[42]), "=f"(d[43]), "=f"(d[44]),
        "=f"(d[45]), "=f"(d[46]), "=f"(d[47]), "=f"(d[48]), "=f"(d[49]), "=f"(d[50]), "=f"(d[51]), "=f"(d[52]), "=f"(d[53]), "=f"(d[54]), "=f"(d[55]),
        "=f"(d[56]), "=f"(d[57]), "=f"(d[58]), "=f"(d[59]), "=f"(d[60]), "=f"(d[61]), "=f"(d[62]), "=f"(d[63])
      : "r"(a0), "r"(a1), "r"(a2), "r"(a3), "l"(db), "r"(scaleD));
}
__device__ __forceinline__ void wgmma_qk_sp_init(float (&d)[32], uint32_t a0, uint32_t a1, uint32_t a2, uint32_t a3, uint64_t db, int scaleD, uint32_t meta) {
  asm volatile("{\n.reg .pred p;\nsetp.ne.b32 p, %37, 0;\n"
      "wgmma.mma_async.sp.sync.aligned.m64n64k32.f32.bf16.bf16 "
      "{%0, %1, %2, %3, %4, %5, %6, %7, %8, %9, %10, %11, %12, %13, %14, %15, %16, %17, %18, %19, %20, %21, %22, %23, %24, %25, %26, %27, %28, %29, %30, "
      "%31}, "
      "{%32, %33, %34, %35}, %36, %38, 0, p, 1, 1, 0;\n}\n"
      : "=f"(d[0]), "=f"(d[1]), "=f"(d[2]), "=f"(d[3]), "=f"(d[4]), "=f"(d[5]), "=f"(d[6]), "=f"(d[7]), "=f"(d[8]), "=f"(d[9]), "=f"(d[10]), "=f"(d[11]),
        "=f"(d[12]), "=f"(d[13]), "=f"(d[14]), "=f"(d[15]), "=f"(d[16]), "=f"(d[17]), "=f"(d[18]), "=f"(d[19]), "=f"(d[20]), "=f"(d[21]), "=f"(d[22]),
        "=f"(d[23]), "=f"(d[24]), "=f"(d[25]), "=f"(d[26]), "=f"(d[27]), "=f"(d[28]), "=f"(d[29]), "=f"(d[30]), "=f"(d[31])
      : "r"(a0), "r"(a1), "r"(a2), "r"(a3), "l"(db), "r"(scaleD), "r"(meta));
}
__device__ __forceinline__ void wgmma_pv_sp_init(float (&d)[64], uint32_t a0, uint32_t a1, uint32_t a2, uint32_t a3, uint64_t db, int scaleD, uint32_t meta) {
  asm volatile("{\n.reg .pred p;\nsetp.ne.b32 p, %69, 0;\n"
      "wgmma.mma_async.sp.sync.aligned.m64n128k32.f32.bf16.bf16 "
      "{%0, %1, %2, %3, %4, %5, %6, %7, %8, %9, %10, %11, %12, %13, %14, %15, %16, %17, %18, %19, %20, %21, %22, %23, %24, %25, %26, %27, %28, %29, %30, "
      "%31, %32, %33, %34, %35, %36, %37, %38, %39, %40, %41, %42, %43, %44, %45, %46, %47, %48, %49, %50, %51, %52, %53, %54, %55, %56, %57, %58, %59, %60, "
      "%61, %62, %63}, "
      "{%64, %65, %66, %67}, %68, %70, 0, p, 1, 1, 1;\n}\n"
      : "=f"(d[0]), "=f"(d[1]), "=f"(d[2]), "=f"(d[3]), "=f"(d[4]), "=f"(d[5]), "=f"(d[6]), "=f"(d[7]), "=f"(d[8]), "=f"(d[9]), "=f"(d[10]), "=f"(d[11]),
        "=f"(d[12]), "=f"(d[13]), "=f"(d[14]), "=f"(d[15]), "=f"(d[16]), "=f"(d[17]), "=f"(d[18]), "=f"(d[19]), "=f"(d[20]), "=f"(d[21]), "=f"(d[22]),
        "=f"(d[23]), "=f"(d[24]), "=f"(d[25]), "=f"(d[26]), "=f"(d[27]), "=f"(d[28]), "=f"(d[29]), "=f"(d[30]), "=f"(d[31]), "=f"(d[32]), "=f"(d[33]),
        "=f"(d[34]), "=f"(d[35]), "=f"(d[36]), "=f"(d[37]), "=f"(d[38]), "=f"(d[39]), "=f"(d[40]), "=f"(d[41]), "=f"(d[42]), "=f"(d[43]), "=f"(d[44]),
        "=f"(d[45]), "=f"(d[46]), "=f"(d[47]), "=f"(d[48]), "=f"(d[49]), "=f"(d[50]), "=f"(d[51]), "=f"(d[52]), "=f"(d[53]), "=f"(d[54]), "=f"(d[55]),
        "=f"(d[56]), "=f"(d[57]), "=f"(d[58]), "=f"(d[59]), "=f"(d[60]), "=f"(d[61]), "=f"(d[62]), "=f"(d[63])
      : "r"(a0), "r"(a1), "r"(a2), "r"(a3), "l"(db), "r"(scaleD), "r"(meta));
}

constexpr int NB = 16, SQ = 224, DM = 640, NH = 32, SK = 1024, DH = 128;
constexpr int HD = NH * DH;
constexpr int NBETA = 2 * NB;
constexpr int NCTA = 132;
constexpr uint32_t SB0 = 1024;
constexpr int NS = 10;
constexpr int SLOT = 16384;
constexpr int QBUF_OFF = NS * SLOT;
constexpr int NSX = NS + 4;
constexpr int BAR_OFF = NSX * SLOT;
constexpr int BAR_FULL = BAR_OFF;
constexpr int BAR_EMPTY = BAR_OFF + 8 * NSX;
constexpr int BAR_STG = BAR_OFF + 16 * NSX;
constexpr int BAR_OUT = BAR_STG + 32;
constexpr int BAR_DESC = BAR_OUT + 8;
constexpr int BAR_GO = BAR_DESC + 8;
constexpr int BAR_MAIL = BAR_GO + 8;
constexpr int BAR_RDY = BAR_MAIL + 8;
constexpr int DESC_OFF = BAR_RDY + 8 * NSX;
constexpr int EPOCH_OFF = DESC_OFF + 16;
constexpr int TRACE_OFF = EPOCH_OFF + 16;
constexpr int SMEM_BYTES = TRACE_OFF;
constexpr float SM_C = 0.08838834764831845f * 1.4426950408889634f;
constexpr float SUM_HI = 1099511627776.f, SUM_LO = 1.f / 1099511627776.f;
constexpr uint32_t META_QK = 0xEEEE4444u;
constexpr uint32_t META_PV = 0x44EEEE44u;

#define QK_EARLY_MASK 3
#define ST_ORDER 0x2310
#define LAG_BAR 3
#define ST_NOW 8
#define PF_STEP 5
#define KV_WIN_UNITS 2
#define KV_WIN_D 4
#define SF 0xfe3f
#define O_STEPS 4
#define KV_WIN_RAMP 4
#define PDEPTH 0
#define KV_WIN_TILES -2
#define PR_KV 2
#define PR_X 2
#define PR_W 2
#define REG_C 232
#define REG_P 24
#define GO_P 4
#define P_POS 216
#define OR 6
#define OR0 2
#define EARLY_BEGIN 0
#define B_LATE 23
#define H_LATE 24
#define NQR 1
#define NQR1 5
#define NQR2 0
#define SKIP_ST 2
#define CLUSTER 1
#define PAIRB 1
#define KG 5
#define PK 44
#define EARLY_MASK 0x3fffu
#define PIECE_TABLE 0x50188016,0x65e88038,0x50321819,0x6c8d1830,0x403f2812,0x80000000,0x50215014,0x695a503c,0x5029b813,0x6c4eb85e,0x501b4815,0x689d4834,0x502b1017,0x6ccc1039,0x50312010,0x80000000,0x500e681b,0x65e8683f,0x502ea011,0x80000000,0x63b1902e,0x80000000,0x63f0603b,0x80000000,0x64ad003d,0x80000000,0x64eca83a,0x80000000,0x5024581c,0x80000000,0x5012b01a,0x6a95b033,0x5011081d,0x6b130837,0x5016701f,0x6c8d7056,0x501ec81e,0x80000000,0x6723302f,0x80000000,0x501b380f,0x80000000,0x67234035,0x80000000,0x500d980e,0x6bd09831,0x56587816,0x80000000,0x50168818,0x80000000,0x57d1c01e,0x80000000

struct Params {
  CUtensorMap x[2][2], wq[2], kv[2][2], wo[2];
  CUtensorMap o_ld[2], o_st[2], out_st[2];
  const __nv_bfloat16* kp[2];
  const __nv_bfloat16* vp[2];
};

constexpr int NPART = 32 * 5, O_BLOCKS = NBETA * 64 + 2 * NPART;
__device__ __align__(128) __nv_bfloat16 g_o[(size_t)O_BLOCKS * SQ * 64];
__device__ unsigned g_cnt[NBETA][8];
__device__ unsigned g_rd[NBETA][8];
__device__ unsigned g_epoch, g_next;
__device__ unsigned g_flag[NPART];

__device__ __forceinline__ uint32_t smem_u32(const void* p) { return (uint32_t)__cvta_generic_to_shared(p); }
__device__ __forceinline__ void mbar_arrive(uint32_t bar) {
  asm volatile("mbarrier.arrive.shared::cta.b64 _, [%0];" ::"r"(bar) : "memory");
}
__device__ __forceinline__ void mbar_arrive_warp(uint32_t bar) {
  asm volatile("{\n.reg .pred p;\nelect.sync _|p, 0xffffffff;\n@p mbarrier.arrive.shared::cta.b64 _, [%0];\n}" ::"r"(bar) : "memory");
}
__device__ __forceinline__ int lane_now() { int l; asm volatile("mov.u32 %0, %%laneid;" : "=r"(l)); return l; }
__device__ __forceinline__ bool mbar_try(uint32_t bar, uint32_t parity) {
  uint32_t ok;
  asm volatile("{\n.reg .pred p;\nmbarrier.try_wait.parity.shared::cta.b64 p, [%1], %2;\nselp.u32 %0, 1, 0, p;\n}"
               : "=r"(ok) : "r"(bar), "r"(parity) : "memory");
  return ok;
}
__device__ __forceinline__ bool mbar_test(uint32_t bar, uint32_t parity) {
  uint32_t ok;
  asm volatile("{\n.reg .pred p;\nmbarrier.test_wait.parity.shared::cta.b64 p, [%1], %2;\nselp.u32 %0, 1, 0, p;\n}"
               : "=r"(ok) : "r"(bar), "r"(parity) : "memory");
  return ok;
}
__device__ __forceinline__ void mbar_wait_w(uint32_t bar, uint32_t parity) {
  uint32_t n = 0;
  while (!__all_sync(0xffffffffu, mbar_try(bar, parity))) {
    if (++n > (1u << 22)) __trap();
  }
}
#define ELECT "{\n.reg .pred p;\nelect.sync _|p, 0xffffffff;\n@p "
__device__ __forceinline__ void tma_st3_hint_w(const CUtensorMap* m, uint32_t src, int c0, int c1, int c2, uint64_t pol) {
  asm volatile(ELECT "cp.async.bulk.tensor.3d.global.shared::cta.bulk_group.L2::cache_hint [%0, {%2, %3, %4}], [%1], %5;\n}"
               ::"l"(m), "r"(src), "r"(c0), "r"(c1), "r"(c2), "l"(pol) : "memory");
}
#define EXPECT(bar, bytes) "mbarrier.arrive.expect_tx.shared::cta.b64 _, [" bar "], " bytes ";\n@p "
__device__ __forceinline__ void tma_ld2_w(uint32_t dst, const CUtensorMap* m, int c0, int c1, uint32_t bar, uint32_t bytes) {
  asm volatile(ELECT EXPECT("%2", "%5") "cp.async.bulk.tensor.2d.shared::cluster.global.mbarrier::complete_tx::bytes [%0], [%1, {%3, %4}], [%2];\n}"
               ::"r"(dst), "l"(m), "r"(bar), "r"(c0), "r"(c1), "r"(bytes) : "memory");
}
__device__ __forceinline__ void tma_ld2_hint_w(uint32_t dst, const CUtensorMap* m, int c0, int c1, uint32_t bar, uint32_t bytes, uint64_t pol) {
  asm volatile(ELECT EXPECT("%2", "%6") "cp.async.bulk.tensor.2d.shared::cluster.global.mbarrier::complete_tx::bytes.L2::cache_hint"
               " [%0], [%1, {%3, %4}], [%2], %5;\n}"
               ::"r"(dst), "l"(m), "r"(bar), "r"(c0), "r"(c1), "l"(pol), "r"(bytes) : "memory");
}
__device__ __forceinline__ void tma_ld3_w(uint32_t dst, const CUtensorMap* m, int c0, int c1, int c2, uint32_t bar, uint32_t bytes) {
  asm volatile(ELECT EXPECT("%2", "%6") "cp.async.bulk.tensor.3d.shared::cluster.global.mbarrier::complete_tx::bytes [%0], [%1, {%3, %4, %5}], [%2];\n}"
               ::"r"(dst), "l"(m), "r"(bar), "r"(c0), "r"(c1), "r"(c2), "r"(bytes) : "memory");
}
__device__ __forceinline__ void tma_ld3_hint_w(uint32_t dst, const CUtensorMap* m, int c0, int c1, int c2, uint32_t bar, uint64_t pol) {
  asm volatile(ELECT EXPECT("%2", "16384") "cp.async.bulk.tensor.3d.shared::cluster.global.mbarrier::complete_tx::bytes.L2::cache_hint"
               " [%0], [%1, {%3, %4, %5}], [%2], %6;\n}"
               ::"r"(dst), "l"(m), "r"(bar), "r"(c0), "r"(c1), "r"(c2), "l"(pol) : "memory");
}
__device__ __forceinline__ void tma_ld_wo_w(uint32_t dst, const CUtensorMap* m, int col, int grp, uint32_t bar) {
  asm volatile(ELECT EXPECT("%2", "16384") "cp.async.bulk.tensor.5d.shared::cluster.global.mbarrier::complete_tx::bytes [%0], [%1, {%3, 0, 0, 0, %4}], [%2];\n"
               "@p cp.async.bulk.tensor.5d.shared::cluster.global.mbarrier::complete_tx::bytes [%5], [%1, {%6, 0, 0, 0, %4}], [%2];\n}"
               ::"r"(dst), "l"(m), "r"(bar), "r"(col), "r"(grp), "r"(dst + 8192), "r"(col + 64) : "memory");
}
__device__ __forceinline__ void mbar_arrive8_w(uint32_t bar) {
  asm volatile(ELECT "mbarrier.arrive.shared::cta.b64 _, [%0], 8;\n}" ::"r"(bar) : "memory");
}
__device__ __forceinline__ uint32_t peer(uint32_t a) { uint32_t r; asm("mapa.shared::cluster.u32 %0, %1, %2;" : "=r"(r) : "r"(a), "r"(~blockIdx.x & 1)); return r; }
__device__ __forceinline__ void tma_ld2_both_w(uint32_t dst, const CUtensorMap* m, int c0, int c1, uint32_t bar, uint32_t bytes) {
  asm volatile(ELECT EXPECT("%2", "%5") "cp.async.bulk.tensor.2d.shared::cluster.global.mbarrier::complete_tx::bytes.multicast::cluster"
               " [%0], [%1, {%3, %4}], [%2], %6;\n}"
               ::"r"(dst), "l"(m), "r"(bar), "r"(c0), "r"(c1), "r"(bytes), "h"((uint16_t)3) : "memory");
}
__device__ __forceinline__ void tma_ld2_both_hint_w(uint32_t dst, const CUtensorMap* m, int c0, int c1, uint32_t bar, uint32_t bytes, uint64_t pol) {
  asm volatile(ELECT EXPECT("%2", "%6") "cp.async.bulk.tensor.2d.shared::cluster.global.mbarrier::complete_tx::bytes.multicast::cluster.L2::cache_hint"
               " [%0], [%1, {%3, %4}], [%2], %7, %5;\n}"
               ::"r"(dst), "l"(m), "r"(bar), "r"(c0), "r"(c1), "l"(pol), "r"(bytes), "h"((uint16_t)3) : "memory");
}
__device__ __forceinline__ void bulk_commit() { asm volatile("cp.async.bulk.commit_group;" ::: "memory"); }
template <int N> __device__ __forceinline__ void bulk_wait_read() { asm volatile("cp.async.bulk.wait_group.read %0;" ::"n"(N) : "memory"); }
__device__ __forceinline__ void wg_fence() { asm volatile("wgmma.fence.sync.aligned;" ::: "memory"); }
__device__ __forceinline__ void wg_commit() { asm volatile("wgmma.commit_group.sync.aligned;" ::: "memory"); }
template <int N> __device__ __forceinline__ void wg_wait() { asm volatile("wgmma.wait_group.sync.aligned %0;" ::"n"(N) : "memory"); }
__device__ __forceinline__ void fence_async_smem() { asm volatile("fence.proxy.async.shared::cta;" ::: "memory"); }
__device__ __forceinline__ void bar_sync(int id, int n) { asm volatile("bar.sync %0, %1;" ::"r"(id), "r"(n) : "memory"); }
__device__ __forceinline__ void touch(float& a) { asm volatile("neg.f32 %0, %0;" : "+f"(a)); }
__device__ __forceinline__ void touch(uint32_t& a) { asm volatile("not.b32 %0, %0;" : "+r"(a)); }
template <typename T, int N> __device__ __forceinline__ void touch(T (&a)[N]) {
#pragma unroll
  for (int i = 0; i < N; i++) touch(a[i]);
}
template <int ID, typename... A> __device__ __forceinline__ void sched_fence(uint32_t x, A&... a) {
  if (!((SF >> ID) & 1)) return;
  asm volatile("" : "+r"(x)::"memory");
#pragma unroll 1
  for (; __builtin_expect(x >= 100 + ID, 0); x >>= 1) { (touch(a), ...); __nanosleep(x); }
}
template <int N> __device__ __forceinline__ void reg_fence(float (&a)[N]) {
#pragma unroll
  for (int i = 0; i < N; i++) asm volatile("" : "+f"(a[i])::"memory");
}
template <int N> __device__ __forceinline__ void reg_fence(uint32_t (&a)[N]) {
#pragma unroll
  for (int i = 0; i < N; i++) asm volatile("" : "+r"(a[i])::"memory");
}
__device__ __forceinline__ float ex2(float x) { float y; asm("ex2.approx.ftz.f32 %0, %1;" : "=f"(y) : "f"(x)); return y; }
__device__ __forceinline__ uint32_t pack_bf16(float lo, float hi) {
  uint32_t r; asm("cvt.rn.bf16x2.f32 %0, %1, %2;" : "=r"(r) : "f"(hi), "f"(lo)); return r;
}
__device__ __forceinline__ void stsm4(uint32_t a, uint32_t r0, uint32_t r1, uint32_t r2, uint32_t r3) {
  asm volatile("stmatrix.sync.aligned.m8n8.x4.shared.b16 [%0], {%1, %2, %3, %4};" ::"r"(a), "r"(r0), "r"(r1), "r"(r2), "r"(r3) : "memory");
}
__device__ __forceinline__ void stsm4t(uint32_t a, uint32_t r0, uint32_t r1, uint32_t r2, uint32_t r3) {
  asm volatile("stmatrix.sync.aligned.m8n8.x4.trans.shared.b16 [%0], {%1, %2, %3, %4};" ::"r"(a), "r"(r0), "r"(r1), "r"(r2), "r"(r3) : "memory");
}
__device__ __forceinline__ void ldsm4(uint32_t a, uint32_t& r0, uint32_t& r1, uint32_t& r2, uint32_t& r3) {
  asm volatile("ldmatrix.sync.aligned.m8n8.x4.shared.b16 {%0, %1, %2, %3}, [%4];" : "=r"(r0), "=r"(r1), "=r"(r2), "=r"(r3) : "r"(a) : "memory");
}
__device__ __forceinline__ void sts16(uint32_t a, uint32_t v) { asm volatile("st.shared.u16 [%0], %1;" ::"r"(a), "h"((uint16_t)v) : "memory"); }
__device__ __forceinline__ void mma16816(float& c0, float& c1, float& c2, float& c3, uint32_t a0, uint32_t a1, uint32_t a2, uint32_t a3,
                                         uint32_t b0, uint32_t b1) {
  asm volatile("mma.sync.aligned.m16n8k16.row.col.f32.bf16.bf16.f32 {%0, %1, %2, %3}, {%4, %5, %6, %7}, {%8, %9}, {%0, %1, %2, %3};"
               : "+f"(c0), "+f"(c1), "+f"(c2), "+f"(c3) : "r"(a0), "r"(a1), "r"(a2), "r"(a3), "r"(b0), "r"(b1));
}
__device__ __forceinline__ uint32_t sdesc(uint32_t addr, uint32_t lbo) { return (addr >> 4) + ((lbo >> 4) << 16); }
__device__ __forceinline__ uint64_t desc64(uint32_t lo, uint32_t hi) { uint64_t d; asm("mov.b64 %0, {%1, %2};" : "=l"(d) : "r"(lo), "r"(hi)); return d; }
__device__ __forceinline__ void dadd(uint64_t& d, uint32_t inc) {
  asm("{\n.reg .b32 l, h;\nmov.b64 {l, h}, %0;\nadd.u32 l, l, %1;\nmov.b64 %0, {l, h};\n}" : "+l"(d) : "r"(inc));
}

struct Ring {
  uint32_t slot, phase, xp;
  __device__ __forceinline__ void uniform() {
    slot = __shfl_sync(0xffffffffu, slot, 0); phase = __shfl_sync(0xffffffffu, phase, 0); xp = __shfl_sync(0xffffffffu, xp, 0);
  }
  __device__ __forceinline__ void next() { if (++slot == NS) { slot = 0; phase ^= 1; } }
  __device__ __forceinline__ void next_if(bool p) { slot += p; if (slot == NS) { slot = 0; phase ^= 1; } }
};
__device__ __forceinline__ uint32_t borrow(int ks, int n) {
  const int k = ks + 1;
  return k >= 4 && !(k & 2) && k < n ? k & 1 : 2;
}

constexpr uint32_t Q_RANGES = NBETA * NH + __builtin_popcount(EARLY_MASK) * 5, Q_ALL = NBETA * (NH + 5);
constexpr int NRANGE = NCTA / 5;
struct Work { int kind, mode, k0, nsteps, range, beta, sub; };
struct Sched { uint16_t queue[Q_ALL]; uint32_t piece[NRANGE + 1][4]; };
constexpr Sched make_sched() {
  Sched s{};
  int q = 0, a = 0;
  for (int t = 0, e = 0; a < NBETA * NH; t++) {
    for (; e < NBETA && 8 * (e & ~PAIRB) + PK <= t && a >= P_POS; e++)
      for (int col = 0; col < 5 && (EARLY_MASK >> e & 1); col++) s.queue[q++] = 0x8000 | (e & 1 ? 4 - col : col) << 8 | e;
    for (int b = 0; b < NBETA; b++)
      for (int h = 0; h < NH; h++)
        if ((b >= B_LATE && h >= H_LATE ? 300 + b : 8 * (b & ~PAIRB) + KG * (h >> 2)) == t) { s.queue[q++] = b << 5 | h; a++; }
  }
  for (int b = 0; b < NBETA; b++)
    for (int col = 0; col < 5 && !(EARLY_MASK >> b & 1); col++) s.queue[q++] = 0x8000 | col << 8 | b;
  constexpr uint32_t T[NRANGE * 2] = {PIECE_TABLE};
  for (int g = 0; g <= NRANGE; g++)
    for (int n = 0; n < 4; n++) s.piece[g][n] = g < NRANGE && n < 2 ? T[2 * g + n] : 2u << 30;
  return s;
}
__constant__ Sched c_sched = make_sched();
constexpr int N_EARLY = __builtin_popcount(EARLY_MASK);
template <bool SIMPLE> __device__ __forceinline__ bool o_reuse(uint32_t b) { return !SIMPLE && b - (OR0 + OR) < N_EARLY - OR0; }
template <bool SIMPLE> __device__ __forceinline__ uint32_t o_slot(uint32_t b) { return o_reuse<SIMPLE>(b) ? OR0 + (b - OR0) % OR : b; }
__device__ __forceinline__ Work decode(uint32_t d) {
  Work w;
  w.kind = d >> 30; if (w.kind == 3) w.kind = 1;
  w.mode = (d >> 28) & 3; w.k0 = (d >> 22) & 63;
  if (w.kind == 0) { w.beta = (d >> 5) & 31; w.sub = d & 31; w.nsteps = DM / 64; }
  else { w.beta = d & 31; w.sub = (d >> 8) & 7; w.nsteps = ((d >> 16) & 63) + 1; }
  w.range = ((d >> 11) & 31) * 5 + w.sub;
  return w;
}

__device__ __forceinline__ bool reached(const unsigned* cnt, unsigned target) {
  unsigned v;
  asm volatile("ld.acquire.gpu.global.u32 %0, [%1];" : "=r"(v) : "l"(cnt) : "memory");
  return (int)(v - target) >= 0;
}
__device__ __forceinline__ void wait_count(const unsigned* cnt, unsigned target) {
  unsigned n = 0;
  while (!__all_sync(0xffffffffu, reached(cnt, target))) { if (++n > (1u << 24)) __trap(); }
}
__device__ __forceinline__ uint32_t lds(uint32_t a) { uint32_t v; asm volatile("ld.volatile.shared.u32 %0, [%1];" : "=r"(v) : "r"(a) : "memory"); return v; }

#define TRACE(u, e)
#define T3(u, e)
#define T2C(u, e)
#define T2P(u, r, e)
#define TTAIL(k)
#define TCLK(k)
#define TO -1
#define TRACE_O(k) if (TO == k) TRACE(i, 5)
#define TRACE_P(u, e)
#define TRACE_IN(u, e)

struct Ctx {
  uint32_t sb;
  int wg, warp;
  uint32_t mqk, mpv;
  bool lead;
  int lane0, lane;
  int src;
};
template <int N> __device__ __forceinline__ uint32_t dhi(uint32_t lo) { return 0x40000040u + (lo >> (26 + N)); }
__device__ __forceinline__ void release(const Ctx& c, uint32_t slot) {
  if (c.lead) mbar_arrive(c.sb + BAR_EMPTY + slot * 8);
}
__device__ __forceinline__ uint32_t acquire(const Ctx& c, Ring& r, bool have = false) {
  const uint32_t s = r.slot;
  if (!have) mbar_wait_w(c.sb + BAR_FULL + s * 8, r.phase);
  r.next();
  return s;
}
__device__ __forceinline__ void mbar_wait2_w(uint32_t b0, uint32_t p0, uint32_t b1, uint32_t p1) {
  uint32_t n = 0;
  while (!__all_sync(0xffffffffu, mbar_try(b0, p0) & mbar_try(b1, p1))) {
    if (++n > (1u << 22)) __trap();
  }
}
__device__ __forceinline__ void mbar_wait3_w(uint32_t b0, uint32_t p0, uint32_t b1, uint32_t p1, uint32_t b2, uint32_t p2) {
  uint32_t n = 0;
  while (!__all_sync(0xffffffffu, mbar_try(b0, p0) & mbar_try(b1, p1) & mbar_try(b2, p2))) {
    if (++n > (1u << 22)) __trap();
  }
}
__device__ __forceinline__ void acquire2(const Ctx& c, Ring& r, uint32_t& s0, uint32_t& s1, bool have = false) {
  const uint32_t p0 = r.phase;
  s0 = r.slot; r.next(); s1 = r.slot;
  if (!have) mbar_wait2_w(c.sb + BAR_FULL + s0 * 8, p0, c.sb + BAR_FULL + s1 * 8, r.phase);
  r.next();
}
template <int N>
__device__ __forceinline__ bool peek(const Ctx& c, Ring r) {
  bool ok = true;
#pragma unroll
  for (int k = 0; k < N; k++) { ok &= mbar_test(c.sb + BAR_FULL + r.slot * 8, r.phase); r.next(); }
  return ok;
}
__device__ __forceinline__ void staged(const Ctx& c, int part) {
  fence_async_smem();
  __syncwarp();
  mbar_arrive_warp(c.sb + BAR_STG + c.wg * 16 + part * 8);
}

template <int WG, bool FIRST, int H>
__device__ __forceinline__ void proj_half(const Ctx& c, float (&acc)[64], uint32_t w, uint32_t x, uint32_t sw) {
  uint64_t dx = desc64((SB0 + x * SLOT + (WG ? 0 : H * 8192)) >> 4, dhi<0>(x) + sw);
  uint64_t dw = desc64(WG ? (SB0 + w * SLOT + H * 8192) >> 4 : sdesc(SB0 + w * SLOT, 8192), dhi<1>(x));
  wg_fence();
  if (WG) { if (FIRST) wgmma_proj96_init(acc, dw, dx, 0); else wgmma_proj96(acc, dw, dx, 1); }
  else { if (FIRST) wgmma_proj_init(acc, dx, dw, 0); else wgmma_proj(acc, dx, dw, 1); }
#pragma unroll
  for (int k = 1; k < 4; k++) {
    dadd(dx, k == 2 ? 2 + (sw >> 30) * 28 : 2); dadd(dw, 128);
    if (WG) wgmma_proj96(acc, dw, dx, 1); else wgmma_proj(acc, dx, dw, 1);
  }
  wg_commit();
}

__device__ __forceinline__ void proj_store16(uint32_t a, const float* f, float sc) {
  stsm4t(a, pack_bf16(f[0] * sc, f[1] * sc), pack_bf16(f[2] * sc, f[3] * sc), pack_bf16(f[4] * sc, f[5] * sc), pack_bf16(f[6] * sc, f[7] * sc));
}

__device__ __forceinline__ uint32_t stage_off(const Ctx& c) {
  const int lane = c.lane, mi = lane >> 3, r8 = lane & 7;
  return ((mi >> 1) * 8 + r8) * 128 + (((2 * c.warp + (mi & 1)) ^ r8) << 4);
}
__device__ __forceinline__ uint32_t q3_swz(uint32_t r8) { return ((r8 & 3) << 1) | (r8 >> 2); }
template <int H>
__device__ __forceinline__ void stage_t2(const Ctx& c, const float (&a)[64], float sc) {
  const uint32_t base = c.sb + QBUF_OFF + 2 * 16384 + H * 8192 + stage_off(c);
#pragma unroll
  for (int jj = 0; jj < 4; jj++) proj_store16(base + jj * 2048, &a[jj * 8], sc);
}
template <int H, bool IS_Q>
__device__ __forceinline__ void stage_t3(const Ctx& c, const float (&a)[64], float sc) {
  const uint32_t off = stage_off(c), r8 = (off >> 7) & 7;
  const uint32_t t3 = c.sb + QBUF_OFF + 3 * 16384 + H * 4096 + (IS_Q ? off ^ ((r8 ^ q3_swz(r8)) << 4) : off);
  proj_store16(t3, &a[32], sc);
  proj_store16(t3 + 2048, &a[40], sc);
}

template <int WG, int h>
__device__ __forceinline__ void load_part(const Ctx& c, Ring r, uint32_t (&q)[32]) {
  uint32_t n = 0;
  while (!h && !__all_sync(0xffffffffu, peek<4>(c, r))) {
    if (++n > (1u << 26)) __trap();
  }
  const int lane = c.lane, mi = lane >> 3, r8 = lane & 7;
  if (WG) { r.next(); r.next(); }
  const uint32_t off = c.sb + (WG ? stage_off(c) : (16 * c.warp + (mi & 1) * 8 + r8) * 128), t0 = off + r.slot * SLOT;
  r.next();
  const uint32_t t1 = off + r.slot * SLOT;
#pragma unroll
    for (int jj = 0; jj < (WG ? 6 : 8); jj++) {
      uint32_t* p = &q[4 * jj];
      if (WG) asm volatile("ldmatrix.sync.aligned.m8n8.x4.trans.shared.b16 {%0, %1, %2, %3}, [%4];" : "=r"(p[0]), "=r"(p[1]), "=r"(p[2]), "=r"(p[3])
                           : "r"((jj < 4 ? t0 + h * 8192 : t1 + h * 4096) + (jj & 3) * 2048) : "memory");
      else ldsm4((h ? t1 : t0) + (jj >> 2) * 8192 + (((((2 * jj) & 7) + (mi >> 1)) ^ r8) << 4), p[0], p[1], p[2], p[3]);
    }
}
template <int WG>
__device__ __forceinline__ void add_part(const Ctx& c, const uint32_t (&q)[32], float (&a)[64]) {
  const uint32_t one = (c.lane >> 3) == (c.lane & 3) ? 0x3f80u << (c.lane & 4) * 4 : 0;
#pragma unroll
  for (int i = 0; i < (WG ? 12 : 16); i++)
    asm("mma.sync.aligned.m16n8k8.row.col.f32.bf16.bf16.f32 {%0, %1, %2, %3}, {%4, %5}, {%6}, {%0, %1, %2, %3};"
        : "+f"(a[4 * i]), "+f"(a[4 * i + 1]), "+f"(a[4 * i + 2]), "+f"(a[4 * i + 3]) : "r"(q[2 * i]), "r"(q[2 * i + 1]), "r"(one));
}

__device__ __forceinline__ void trace_dump(const Ctx& c) {
}
struct RowSum { float l0, l1; };
__device__ __forceinline__ const char* o_addr(uint32_t item, int row, int lane) {
  return reinterpret_cast<const char*>(g_o) + (((item >> 10) * (2 * SQ) + row) * 128 + (lane ^ (lane >> 3)) * 16);
}
__device__ __forceinline__ void o_stg(const char* p, int i, const uint32_t* q) {
  asm volatile("st.global.v4.b32 [%0], {%1, %2, %3, %4};"
               ::"l"(p + (i >> 1) * (SQ * 128) + (i & 1) * 512), "r"(q[0]), "r"(q[1]), "r"(q[2]), "r"(q[3]) : "memory");
}
template <int MODE, int I0 = 0, int NI = 4>
__device__ __forceinline__ void o_emit(const char* p, const float (&o)[64], float inv) {
#pragma unroll
  for (int i = I0; i < I0 + NI; i++) {
    uint32_t q[4];
#pragma unroll
    for (int j = 0; j < 4; j++) q[j] = pack_bf16(o[16 * i + 4 * j + 2 * MODE] * inv, o[16 * i + 4 * j + 2 * MODE + 1] * inv);
    o_stg(p, i, q);
  }
}
__device__ __forceinline__ void o_done(const Ctx& c) {
  __syncwarp();
  mbar_arrive_warp(c.sb + BAR_OUT);
  __syncwarp();
}
template <int WG>
__device__ __forceinline__ void o_first(const Ctx& c, uint32_t item, float (&o)[64], const RowSum& inv) {
  const char* p = o_addr(item, WG ? 192 + 8 * c.warp : 64 + 16 * c.warp, c.lane);
  reg_fence(o);
  if (WG) {
    uint32_t q[16];
#pragma unroll
    for (int j = 0; j < 16; j++) q[j] = pack_bf16((o[4 * j] + o[4 * j + 2]) * inv.l0, (o[4 * j + 1] + o[4 * j + 3]) * inv.l0);
#pragma unroll
    for (int i = 0; i < 4; i++) o_stg(p, i, q + 4 * i);
  } else { o_emit<0>(p, o, inv.l0); o_emit<1>(p + 1024, o, inv.l1); }
}
template <int K0, int K1>
__device__ __forceinline__ void o_piece(const Ctx& c, const char* p, int k, const float (&o)[64], const RowSum& inv) {
  constexpr int NI = 8 / O_STEPS, M = K0 * NI / 4;
  if constexpr (K1 - K0 == 1) {
    o_emit<M, K0 * NI % 4, NI>(p + M * 1024, o, M ? inv.l1 : inv.l0);
    if (K1 == O_STEPS) o_done(c);
  } else {
    if (k <= (K0 + K1) / 2) o_piece<K0, (K0 + K1) / 2>(c, p, k, o, inv); else o_piece<(K0 + K1) / 2, K1>(c, p, k, o, inv);
  }
}
template <int WG>
__device__ __forceinline__ void o_second(const Ctx& c, uint32_t item, int k, float (&o)[64], const RowSum& inv) {
  reg_fence(o);
  o_piece<0, O_STEPS>(c, o_addr(item, 128 * WG + 16 * c.warp, c.lane0 + (k >> 8)), k, o, inv);
}
template <int WG>
__device__ __forceinline__ void release_q(const Ctx& c) {
#pragma unroll
  for (int t = 0; t < 2; t++)
    if (c.lead) asm volatile("mbarrier.arrive.shared::cta.b64 _, [%0], 2;" ::"r"(c.sb + BAR_EMPTY + (NS + 2 * WG + t) * 8) : "memory");
  __syncwarp();
}
struct Slots { uint32_t w, x, o, po; };
template <int WG>
__device__ __forceinline__ void acc_fence(float (&a)[64]) {
#pragma unroll
  for (int i = 0; i < (WG ? 48 : 64); i++) asm volatile("" : "+f"(a[i])::"memory");
}
template <int WG>
__device__ __forceinline__ void begin_acquire(const Ctx& c, Ring& r, Slots& h, bool wait) {
  const uint32_t s0 = r.slot, p0 = r.phase, f = c.sb + BAR_FULL;
  r.next();
  const uint32_t p1 = r.phase;
  h.w = r.slot; r.next();
  h.x = WG ? r.slot : s0; h.o = WG ? s0 : r.slot; h.po = r.phase;
  if (wait) { if (WG) mbar_wait3_w(f + s0 * 8, p0, f + h.w * 8, p1, f + h.x * 8, r.phase); else mbar_wait2_w(f + s0 * 8, p0, f + h.w * 8, p1); }
  r.next();
}
template <int WG>
__device__ __forceinline__ void proj_begin(const Ctx& c, Ring& r, float (&a0)[64], Slots& h, bool wait, uint32_t sw) {
  begin_acquire<WG>(c, r, h, wait);
  proj_half<WG, true, 0>(c, a0, h.w, h.x, sw);
  if (WG) release(c, h.o);
}
template <int WG>
__device__ __forceinline__ void proj_main(Ctx& c, Ring& r, float (&a0)[64], float (&a1)[64], Slots& h, int n, uint32_t sw, int unit,
                                          uint32_t item, int nq, float (&o1)[64], const RowSum& inv) {
  constexpr bool DEEP = (PDEPTH >> WG) & 1;
  T2C(unit, 3);
  int ks = 1;
#pragma unroll 1
  do {
    const Slots p = h;
    const uint32_t b = borrow(ks, n), tile = NS + (WG ? 3 - b : b), f = c.sb + BAR_FULL;
    const uint32_t s0 = b != 2 ? tile : r.slot, p0 = b != 2 ? (r.xp >> b) & 1 : r.phase;
    r.next_if(b == 2);
    const uint32_t p1 = r.phase;
    h.w = r.slot; r.next();
    const uint32_t s2 = b != 2 ? tile : r.slot;
    h.po = b != 2 ? p0 : r.phase;
    r.next_if(b == 2);
    r.xp ^= 1 << b;
    h.x = WG ? s2 : s0; h.o = WG ? s0 : s2;
    mbar_wait3_w(f + s0 * 8, p0, f + h.w * 8, p1, f + (WG ? s2 : p.o) * 8, WG ? h.po : p.po);
    if (ks < 10) T2C(unit, ks * 4);
    if (DEEP) {
      proj_half<WG, false, 0>(c, a0, h.w, h.x, sw);
      release(c, WG ? h.o : p.o);
      if (ks < 10) T2C(unit, ks * 4 + 1);
      wg_wait<1>();
      if (ks < 10) T2C(unit, ks * 4 + 2);
      release(c, p.x); release(c, p.w);
    } else {
      release(c, WG ? h.o : p.o);
      wg_wait<0>();
      release(c, p.x); release(c, p.w);
      if (ks < 10) T2C(unit, ks * 4 + 1);
      proj_half<WG, false, 0>(c, a0, h.w, h.x, sw);
      if (ks < 10) T2C(unit, ks * 4 + 2);
    }
    proj_half<WG, false, 1>(c, a1, h.w, h.x, sw);
    if (ks < 10) T2C(unit, ks * 4 + 3);
    if (ks <= nq) o_second<WG>(c, item, ks, o1, inv);
  } while (++ks != n);
  {
    const uint32_t e0 = c.sb + BAR_EMPTY + (NS + 3 * WG) * 8, e1 = c.sb + BAR_EMPTY + (NS + 1 + WG) * 8;
    const uint32_t p0 = (r.xp ^ unit ^ 1) & 1, p1 = ((r.xp >> 1) ^ unit ^ 1) & 1;
    const uint32_t k0 = sw ? e0 : c.sb + BAR_FULL + r.slot * 8, pk = sw ? p0 : r.phase;
    uint32_t cnt = 0;
    while (!__all_sync(0xffffffffu, mbar_try(e0, p0) & mbar_try(e1, p1) & mbar_try(k0, pk) & (WG || mbar_try(c.sb + BAR_FULL + h.o * 8, h.po)))) {
      if (++cnt > (1u << 22)) __trap();
    }
  }
  c.lane = c.lane0 + (h.w >> 5);
  if (!WG) release(c, h.o);
}
template <int WG>
__device__ __forceinline__ void proj_end(const Ctx& c, float (&a1)[64], const Slots& h) {
  wg_wait<0>();
  acc_fence<WG>(a1);
  release(c, h.x); release(c, h.w);
}
__device__ __forceinline__ uint32_t get_desc(const Ctx& c, int i) {
  uint32_t d;
  mbar_wait_w(c.sb + BAR_DESC, (i - 1) & 1);
  asm volatile("ld.volatile.shared.u32 %0, [%1];" : "=r"(d) : "r"(c.sb + DESC_OFF + (i & 3) * 4) : "memory");
  return __shfl_sync(0xffffffffu, d, 0);
}

__device__ __forceinline__ float quad_max(float x) {
  x = fmaxf(x, __shfl_xor_sync(0xffffffffu, x, 1));
  return fmaxf(x, __shfl_xor_sync(0xffffffffu, x, 2));
}
__device__ __forceinline__ float quad_sum(float x) {
  x += __shfl_xor_sync(0xffffffffu, x, 1);
  return x + __shfl_xor_sync(0xffffffffu, x, 2);
}
template <bool SP, bool FIRST>
__device__ __forceinline__ void exps(const Ctx& c, const float (&s)[32], uint32_t (&p)[SP ? 8 : 16], RowSum& st) {
  if constexpr (SP) {
    uint32_t q[8];
    float t;
#pragma unroll
    for (int j = 0; j < 8; j++) {
      const float e0 = ex2(s[4 * j] + s[4 * j + 2]), e1 = ex2(s[4 * j + 1] + s[4 * j + 3]);
      if (j == 0) t = e0 + e1; else t += e0 + e1;
      q[j] = pack_bf16(e0, e1);
    }
    const bool odd = c.src & 2;
#pragma unroll
    for (int g = 0; g < 4; g++) {
      p[2 * g] = __shfl_sync(0xffffffffu, odd ? q[2 * g + 1] : q[2 * g], c.src);
      p[2 * g + 1] = __shfl_sync(0xffffffffu, odd ? q[2 * g] : q[2 * g + 1], c.src ^ 1);
    }
    st.l0 = FIRST ? t : st.l0 + t;
  } else {
    float t0, t1;
#pragma unroll
    for (int j = 0; j < 8; j++) {
      const float e0 = ex2(s[4 * j]), e1 = ex2(s[4 * j + 1]), e2 = ex2(s[4 * j + 2]), e3 = ex2(s[4 * j + 3]);
      if (j == 0) { t0 = e0 + e1; t1 = e2 + e3; } else { t0 += e0 + e1; t1 += e2 + e3; }
      p[2 * j] = pack_bf16(e0, e1);
      p[2 * j + 1] = pack_bf16(e2, e3);
    }
    st.l0 = FIRST ? t0 : st.l0 + t0;
    st.l1 = FIRST ? t1 : st.l1 + t1;
  }
}
template <bool SP>
__device__ __forceinline__ bool finish_sums(RowSum& st) {
  const float a = quad_sum(st.l0), b = SP ? a : quad_sum(st.l1);
  st.l0 = __fdividef(1.f, a); st.l1 = __fdividef(1.f, b);
  return !(a >= SUM_LO && a <= SUM_HI && b >= SUM_LO && b <= SUM_HI);
}
template <bool SP, bool INIT, int SITE, bool COMMIT = true, int NR = 0>
__device__ __forceinline__ void issue_qk(const Ctx& c, float (&s)[32], const uint32_t (&qs)[32], uint32_t dq, uint32_t dk) {
  uint64_t a = desc64(dq, dhi<SITE & 1>(dk)), b = desc64(dk, dhi<1 - (SITE & 1)>(dk));
  if (SP) {
    if (INIT) wgmma_qk_sp_init(s, qs[0], qs[1], qs[2], qs[3], b, 0, c.mqk); else wgmma_qk_sp(s, qs[0], qs[1], qs[2], qs[3], b, 0, c.mqk);
#pragma unroll
    for (int k = 1; k < 4; k++) { dadd(b, k == 2 ? 508 : 4); wgmma_qk_sp(s, qs[4 * k], qs[4 * k + 1], qs[4 * k + 2], qs[4 * k + 3], b, 1, c.mqk); }
  } else {
    if (NR) wgmma_qk_rs(s, qs[0], qs[1], qs[2], qs[3], b, 0); else if (INIT) wgmma_qk_init(s, a, b, 0); else wgmma_qk(s, a, b, 0);
#pragma unroll
    for (int k = 1; k < 8; k++) {
      if (k > NR) dadd(a, k == 4 ? 506 : 2);
      dadd(b, k == 4 ? 506 : 2);
      if (k < NR) wgmma_qk_rs(s, qs[4 * k], qs[4 * k + 1], qs[4 * k + 2], qs[4 * k + 3], b, 1); else wgmma_qk(s, a, b, 1);
    }
  }
  if (COMMIT) wg_commit();
}
template <bool SP, bool ACC, int SITE, bool SPLIT = false>
__device__ __forceinline__ void issue_pv(const Ctx& c, float (&o)[64], const uint32_t (&p)[SP ? 8 : 16], uint32_t dv) {
  uint64_t b = desc64(dv, dhi<SITE & 1>(dv));
  if constexpr (SP) {
    if (ACC) wgmma_pv_sp(o, p[0], p[1], p[2], p[3], b, 1, c.mpv); else wgmma_pv_sp_init(o, p[0], p[1], p[2], p[3], b, 0, c.mpv);
    if (SPLIT) wg_commit();
    dadd(b, 256);
    wgmma_pv_sp(o, p[4], p[5], p[6], p[7], b, 1, c.mpv);
  } else {
    if (ACC) wgmma_pv(o, p[0], p[1], p[2], p[3], b, 1); else wgmma_pv_init(o, p[0], p[1], p[2], p[3], b, 0);
#pragma unroll
    for (int k = 1; k < 4; k++) { dadd(b, 128); wgmma_pv(o, p[4 * k], p[4 * k + 1], p[4 * k + 2], p[4 * k + 3], b, 1); }
  }
  wg_commit();
}
__device__ __forceinline__ void pack_rows(const float (&o)[64], float sc, uint32_t (&q)[32]) {
#pragma unroll
  for (int j = 0; j < 32; j++) q[j] = pack_bf16(o[2 * j] * sc, o[2 * j + 1] * sc);
}
template <int J0 = 0, int J1 = 8>
__device__ __forceinline__ void stage_rows(const Ctx& c, uint32_t tile_addr, const uint32_t (&q)[32]) {
  const int lane = c.lane, mi = lane >> 3, r8 = lane & 7;
  const uint32_t row_addr = tile_addr + (16 * c.warp + (mi & 1) * 8 + r8) * 128;
#pragma unroll
  for (int jj = J0; jj < J1; jj++)
    stsm4(row_addr + (jj >> 2) * 8192 + (((((2 * jj) & 7) + (mi >> 1)) ^ r8) << 4), q[4 * jj], q[4 * jj + 1], q[4 * jj + 2], q[4 * jj + 3]);
}
__device__ __forceinline__ void stage_rows(const Ctx& c, uint32_t tile_addr, const float (&o)[64], float sc) {
  uint32_t q[32];
  pack_rows(o, sc, q);
  stage_rows(c, tile_addr, q);
}
template <int WG, int H>
__device__ __forceinline__ void stage_out(const Ctx& c, const float (&a)[64]) {
  if (WG) { stage_t3<H, false>(c, a, 1.f); if (H) staged(c, 0); stage_t2<H>(c, a, 1.f); }
  else stage_rows(c, c.sb + QBUF_OFF + H * 16384, a, 1.f);
  if (H || !WG) staged(c, H);
}
template <int SITE>
__device__ __forceinline__ void issue_qk_rs(float (&s)[32], uint32_t (&q)[32], uint32_t dk) {
  uint64_t b = desc64(dk, dhi<SITE>(dk));
  reg_fence(q);
  wg_fence();
  wgmma_qk_rs_init(s, q[0], q[1], q[2], q[3], b, 0);
#pragma unroll
  for (int k = 1; k < 8; k++) { dadd(b, k == 4 ? 506 : 2); wgmma_qk_rs(s, q[4 * k], q[4 * k + 1], q[4 * k + 2], q[4 * k + 3], b, 1); }
  wg_commit();
}

__device__ __forceinline__ void redo_tile(const Ctx& c, uint32_t q_addr, uint32_t half, const __nv_bfloat16* kp, const __nv_bfloat16* vp,
                                          uint32_t item, int row) {
  float o[64];
  const int lane = lane_now(), g = lane >> 2, cc = lane & 3, mi = lane >> 3, r8 = lane & 7;
  const uint32_t qa = q_addr + (half == 4096 ? 8 * c.warp + r8 : 16 * c.warp + (mi & 1) * 8 + r8) * 128, swz = half == 4096 ? q3_swz(r8) : r8;
  const uint32_t* kq = reinterpret_cast<const uint32_t*>(kp + g * DH) + cc;
  const unsigned short* vq = reinterpret_cast<const unsigned short*>(vp + 2 * cc * DH) + g;
  float m0 = -INFINITY, m1 = -INFINITY, l0 = 0.f, l1 = 0.f;
#pragma unroll
  for (int i = 0; i < 64; i++) o[i] = 0.f;
#pragma unroll 1
  for (int kb = 0; kb < SK / 16; kb++) {
    float z[8] = {0.f, 0.f, 0.f, 0.f, 0.f, 0.f, 0.f, 0.f};
#pragma unroll 2
    for (int kk = 0; kk < 8; kk++) {
      uint32_t a0, a1, a2, a3;
      ldsm4(qa + (kk >> 2) * half + ((((kk & 3) * 2 + (mi >> 1)) ^ swz) << 4), a0, a1, a2, a3);
      const uint32_t* kr = kq + kb * (16 * DH / 2) + kk * 8;
      mma16816(z[0], z[1], z[2], z[3], a0, a1, a2, a3, __ldg(kr), __ldg(kr + 4));
      mma16816(z[4], z[5], z[6], z[7], a0, a1, a2, a3, __ldg(kr + 8 * DH / 2), __ldg(kr + 8 * DH / 2 + 4));
    }
    const float n0 = fmaxf(m0, quad_max(fmaxf(fmaxf(z[0], z[1]), fmaxf(z[4], z[5]))));
    const float n1 = fmaxf(m1, quad_max(fmaxf(fmaxf(z[2], z[3]), fmaxf(z[6], z[7]))));
    const float al0 = ex2(m0 - n0), al1 = ex2(m1 - n1);
    m0 = n0; m1 = n1;
#pragma unroll
    for (int i = 0; i < 8; i++) z[i] = ex2(z[i] - ((i & 2) ? n1 : n0));
    l0 = l0 * al0 + (z[0] + z[1]) + (z[4] + z[5]);
    l1 = l1 * al1 + (z[2] + z[3]) + (z[6] + z[7]);
    const uint32_t a0 = pack_bf16(z[0], z[1]), a1 = pack_bf16(z[2], z[3]), a2 = pack_bf16(z[4], z[5]), a3 = pack_bf16(z[6], z[7]);
    const unsigned short* vr = vq + kb * (16 * DH);
#pragma unroll
    for (int nb = 0; nb < 16; nb++) {
      o[4 * nb] *= al0; o[4 * nb + 1] *= al0; o[4 * nb + 2] *= al1; o[4 * nb + 3] *= al1;
      const uint32_t b0 = __ldg(vr + nb * 8) | ((uint32_t)__ldg(vr + nb * 8 + DH) << 16);
      const uint32_t b1 = __ldg(vr + nb * 8 + 8 * DH) | ((uint32_t)__ldg(vr + nb * 8 + 9 * DH) << 16);
      mma16816(o[4 * nb], o[4 * nb + 1], o[4 * nb + 2], o[4 * nb + 3], a0, a1, a2, a3, b0, b1);
    }
  }
  const char* p = o_addr(item, row, lane);
  o_emit<0>(p, o, __fdividef(1.f, quad_sum(l0)));
  o_emit<1>(half == 4096 ? p : p + 1024, o, __fdividef(1.f, quad_sum(l1)));
}

template <bool SPA, bool SPB, int SITE, int ID>
__device__ __forceinline__ void batch(const Ctx& c, float (&s)[32], const uint32_t (&qs)[32], uint32_t dq, uint32_t dk, float (&ob)[64],
                                      uint32_t (&pb)[SPB ? 8 : 16], uint32_t dv) {
  if constexpr (SPA) {
    reg_fence(pb);
    wg_fence();
    issue_pv<SPB, true, ID>(c, ob, pb, dv);
    issue_qk<SPA, false, ID>(c, s, qs, dq, dk);
  } else {
    constexpr bool EARLY = ((QK_EARLY_MASK >> (SITE + (SPB ? 2 : 0))) & 1) != 0;
    if (!EARLY) reg_fence(pb);
    wg_fence();
    issue_qk<SPA, false, ID, !SPB, SITE ? NQR : SPB ? NQR2 : NQR1>(c, s, qs, dq, dk);
    if (EARLY) { reg_fence(pb); wg_fence(); }
    issue_pv<SPB, true, ID, SPB>(c, ob, pb, dv);
  }
}

template <bool SP0>
__device__ __forceinline__ bool attention(Ctx& c, Ring& r, int unit, uint32_t& d, const float (&a0)[64], float (&o0)[64], float (&o1)[64],
                                          RowSum& st0, RowSum& st1, const Slots& h) {
  constexpr bool SP1 = false;
  if (SP0) { c.mqk = META_QK + (d >> 28); c.mpv = META_PV + (d >> 28); asm volatile("" : "+r"(c.mqk), "+r"(c.mpv)); }
  if (SP0) c.src = (c.lane & 28) | ((c.lane & 1) << 1) | ((c.lane >> 1) & 1);
  float s[32];
  uint32_t p0[SP0 ? 8 : 16], p1[16];
  const uint32_t q0a = c.sb + QBUF_OFF + (SP0 ? 3 : 0) * 16384, q1a = c.sb + QBUF_OFF + (SP0 ? 2 : 1) * 16384;
  const uint32_t dq0 = sdesc(SB0 + QBUF_OFF + (NQR >> 2) * 8192 + (NQR & 3) * 32, 0), dq1 = sdesc(SB0 + QBUF_OFF + (SP0 ? 32768 + NQR2 * 32 : 16384 + (NQR1 >> 2) * 8192 + (NQR1 & 3) * 32), 0);
  uint32_t sk = acquire(c, r, true), sv, sn;
  uint32_t qs[32], q1[32];
  float s1[32];
  if (SP0) {
    stage_t3<0, true>(c, a0, SM_C);
    stage_t2<0>(c, a0, SM_C);
    proj_end<1>(c, o0, h);
    stage_t3<1, true>(c, o0, SM_C);
    stage_t2<1>(c, o0, SM_C);
    fence_async_smem();
    bar_sync(1, LAG_BAR & 30 ? 256 : 128);
    const int g = c.lane >> 2, cc = c.lane & 3;
    const uint32_t qa = q0a + (8 * c.warp + g) * 128 + (cc & 1) * 8;
#pragma unroll
    for (int k = 0; k < 8; k++)
      asm volatile("ld.shared.v2.u32 {%0, %1}, [%2];" : "=r"(qs[2 * k]), "=r"(qs[2 * k + 1])
                   : "r"(qa + (k >> 2) * 4096 + ((((k & 3) * 2 + (cc >> 1)) ^ q3_swz(g)) << 4)) : "memory");
    TRACE(unit, 2);
    wg_fence();
    issue_qk<SP1, true, 1>(c, s1, qs, dq1 - NQR2 * 2, sdesc(SB0 + sk * SLOT, 0));
#pragma unroll
    for (int k = 0; k < NQR2; k++)
      ldsm4(q1a + (16 * c.warp + (c.lane & 15)) * 128 + (((2 * k + (c.lane >> 4)) ^ (c.lane & 7)) << 4), q1[4 * k], q1[4 * k + 1], q1[4 * k + 2], q1[4 * k + 3]);
#pragma unroll
    for (int k = 0; k < 16; k++) asm volatile("" : "+r"(qs[k])::"memory");
    wg_fence();
    issue_qk<SP0, true, 0>(c, s, qs, dq0, sdesc(SB0 + sk * SLOT, 0));
    const bool have = peek<2>(c, r);
    wg_wait<1>();
    reg_fence(s1);
    exps<SP1, true>(c, s1, p1, st1);
    sched_fence<11>(sk, p1);
    acquire2(c, r, sv, sn, __all_sync(0xffffffffu, have));
    wg_wait<0>();
    wg_fence();
    issue_pv<SP1, false, 1>(c, o1, p1, sdesc(SB0 + sv * SLOT, 8192));
    if (LAG_BAR & 1) asm volatile("bar.arrive 4, 256;" ::: "memory");
    sched_fence<12>(sk, s);
    release(c, sk);
    sk = sn;
    exps<SP0, true>(c, s, p0, st0);
    reg_fence(p0);
    wg_fence();
    issue_pv<SP0, false, 0>(c, o0, p0, sdesc(SB0 + sv * SLOT, 8192));
    issue_qk<SP0, true, 2>(c, s, qs, dq0, sdesc(SB0 + sk * SLOT, 0));
    sn = acquire(c, r);
    wg_wait<0>();
    reg_fence(s);
  } else {
    pack_rows(a0, SM_C, qs);
    stage_rows<SKIP_ST & 1 ? NQR : 0>(c, q0a, qs);
    proj_end<0>(c, o1, h);
    TRACE(unit, 2);
    float sc = SM_C;
    issue_qk_rs<0>(s, qs, sdesc(SB0 + sk * SLOT, 0));
    sched_fence<0>(sk, sc);
    if (LAG_BAR & 8) asm volatile("bar.arrive 1, 256;" ::: "memory");
    pack_rows(o1, sc, q1);
    stage_rows<SKIP_ST & 2 ? NQR1 : 0>(c, q1a, q1);
    if (LAG_BAR & 4) asm volatile("bar.arrive 1, 256;" ::: "memory");
    issue_qk_rs<1>(s1, q1, sdesc(SB0 + sk * SLOT, 0));
    if (LAG_BAR & 2) asm volatile("bar.arrive 1, 256;" ::: "memory");
    bool have = peek<2>(c, r);
    wg_wait<1>();
    reg_fence(s);
    exps<SP0, true>(c, s, p0, st0);
    sched_fence<1>(sk, p0);
    if (LAG_BAR & 16) asm volatile("bar.arrive 1, 256;" ::: "memory");
    acquire2(c, r, sv, sn, __all_sync(0xffffffffu, have));
    wg_wait<0>();
    reg_fence(s1);
    fence_async_smem();
    __syncwarp();
    wg_fence();
    issue_qk<SP0, false, 2, true, NQR>(c, s, qs, dq0, sdesc(SB0 + sn * SLOT, 0));
    issue_pv<SP0, false, 0>(c, o0, p0, sdesc(SB0 + sv * SLOT, 8192));
    sched_fence<2>(sk, s1);
    release(c, sk);
    have = peek<1>(c, r);
    sk = sn;
    exps<SP1, true>(c, s1, p1, st1);
    reg_fence(p1);
    wg_fence();
    issue_pv<SP1, false, 1>(c, o1, p1, sdesc(SB0 + sv * SLOT, 8192));
    sn = acquire(c, r, __all_sync(0xffffffffu, have));
    if (LAG_BAR & 1) bar_sync(4, 256);
    wg_wait<1>();
    reg_fence(s);
  }
  TRACE_IN(unit, 4);
  T2C(unit, 51);
#pragma unroll 1
  for (int j = 1; j < 15; j++) {
    const uint32_t sv_prev = sv, sk_prev = sk;
    sv = sn;
    const uint32_t dv = sdesc(SB0 + sv * SLOT, 8192);
    reg_fence(p0);
    exps<SP0, false>(c, s, p0, st0);
    batch<SP1, SP0, 0, 3>(c, s, q1, dq1, sdesc(SB0 + sk * SLOT, 0), o0, p0, dv);
    sk = acquire(c, r);
    wg_wait<1>();
    reg_fence(s); reg_fence(p1);
    release(c, sv_prev); release(c, sk_prev);
    exps<SP1, false>(c, s, p1, st1);
    batch<SP0, SP1, 1, 4>(c, s, qs, dq0, sdesc(SB0 + sk * SLOT, 0), o1, p1, dv);
    sn = acquire(c, r);
    if (SP0) wg_wait<0>(); else wg_wait<1>();
    reg_fence(s);
  }
  TRACE_IN(unit, 5);
  T2C(unit + 1, 52);
  const uint32_t sv_prev = sv;
  sv = sn;
  const uint32_t dv = sdesc(SB0 + sv * SLOT, 8192);
  reg_fence(p0);
  exps<SP0, false>(c, s, p0, st0);
  batch<SP1, SP0, 0, 5>(c, s, q1, dq1, sdesc(SB0 + sk * SLOT, 0), o0, p0, dv);
  asm volatile("ld.volatile.shared.u32 %0, [%1];" : "=r"(d) : "r"(c.sb + DESC_OFF + ((unit + 1) & 3) * 4) : "memory");
  const bool have = peek<2 + SP0>(c, r);
  wg_wait<1>();
  reg_fence(s); reg_fence(p1);
  release(c, sv_prev); release(c, sk);
  exps<SP1, false>(c, s, p1, st1);
  reg_fence(p1);
  wg_fence();
  issue_pv<SP1, true, 2>(c, o1, p1, dv);
  if (SP0) sched_fence<6>(sk, st0.l0, st1.l0, st1.l1); else sched_fence<5>(sk, st0.l0, st0.l1, st1.l0, st1.l1);
  c.lane = c.lane0 + (sk >> 5);
  const bool bad = finish_sums<SP0>(st0) | finish_sums<SP1>(st1);
  uint32_t any;
  asm volatile("{\n.reg .pred p, q;\nsetp.ne.u32 p, %1, 0;\nbar.red.or.pred q, %2, 128, p;\nselp.u32 %0, 1, 0, q;\n}"
               : "=r"(any) : "r"((uint32_t)bad), "n"(2 + SP0) : "memory");
  any = __any_sync(0xffffffffu, any);
  d = __shfl_sync(0xffffffffu, d, 0);
  if (d < (2u << 30) && !__all_sync(0xffffffffu, have)) { Ring t = r; Slots u; begin_acquire<SP0>(c, t, u, true); }
  wg_wait<0>();
  reg_fence(o0); reg_fence(o1);
  release(c, sv);
  if (!SP0 && SKIP_ST && __builtin_expect(any, 0)) {
    stage_rows<0, SKIP_ST & 1 ? NQR : 0>(c, q0a, qs); stage_rows<0, SKIP_ST & 2 ? NQR1 : 0>(c, q1a, q1);
    __syncwarp();
  }
  return any;
}

template <int WG>
__device__ __forceinline__ void consumer(Ctx c, const __nv_bfloat16* const* kv) {
  asm volatile("setmaxnreg.inc.sync.aligned.u32 %0;" ::"n"(WG ? REG_C : 504 - REG_C - REG_P));
  c.wg = WG;
  Ring r{0, 0, 0};
  float a0[64], a1[64], o1[64];
  Slots h;
  RowSum inv0, inv1;
  uint32_t d = c_sched.queue[blockIdx.x] * 1025, dc = 0, sw;
  int i = 0, nq;
begin:
  sw = d & (1u << 30);
  proj_begin<WG>(c, r, a0, h, true, sw);
begin1:
  proj_half<WG, true, 1>(c, a1, h.w, h.x, sw);
  nq = 0;
#pragma unroll
  for (int k = 0; k < 64; k++) asm volatile("" : "=f"(o1[k]));
  asm volatile("" : "=f"(inv1.l0), "=f"(inv1.l1));
  while (true) {
    TRACE(i, 0); TRACE(i, 6);
    proj_main<WG>(c, r, a0, a1, h, d >> 30 ? ((d >> 16) & 63) + 1 : DM / 64, sw, i, dc, nq, o1, inv1);
    dc = d;
    TRACE(i, 1);
    if (d >> 30) goto out_tile;
    wg_wait<1>();
    acc_fence<WG>(a0);
    if (WG ? attention<WG>(c, r, i, d, a0, a1, o1, inv0, inv1, h) : attention<WG>(c, r, i, d, a0, o1, a1, inv1, inv0, h)) goto redo;
    if (d >= (2u << 30)) break;
    sw = d & (1u << 30);
    proj_begin<WG>(c, r, a0, h, false, sw);
    release_q<WG>(c);
    if (WG) sched_fence<8>(h.w, inv0.l0); else sched_fence<7>(h.w, inv0.l0, inv0.l1);
    o_first<WG>(c, dc, a1, inv0);
    sched_fence<9>(h.w, inv1.l0);
    proj_half<WG, true, 1>(c, a1, h.w, h.x, sw);
    nq = O_STEPS;
    TRACE(i, 3); TRACE(i, 7);
    i++;
  }
  release_q<WG>(c);
  o_first<WG>(c, dc, a1, inv0);
#pragma unroll
  for (int k = 1; k <= O_STEPS; k++) o_second<WG>(c, dc, k, o1, inv1);
next:
  TRACE(i, 3); TRACE(i, 7);
  if ((d >> 30) != 2) {
    i++;
    r.uniform();
    goto begin;
  }
  trace_dump(c);
  return;
out_tile:
  if (d & 96) goto finish;
  d = get_desc(c, i + 1);
  wg_wait<1>();
  acc_fence<WG>(a0);
  TRACE_O(0);
  stage_out<WG, 0>(c, a0);
  TRACE_O(1);
  proj_end<WG>(c, a1, h);
  TRACE_O(2);
  if (!EARLY_BEGIN || d >= (2u << 30)) { stage_out<WG, 1>(c, a1); TRACE(i, 2); goto next; }
  sw = d & (1u << 30);
  proj_begin<WG>(c, r, a0, h, true, sw);
  TRACE_O(3);
  stage_out<WG, 1>(c, a1);
  TRACE(i, 2); TRACE(i, 3); TRACE(i, 7);
  i++;
  goto begin1;
finish:
  {
    uint32_t q[32];
#pragma unroll 1
    for (int k = (d >> 5) & 3; k > 1; k--) {
      wg_wait<0>();
      acc_fence<WG>(a0); acc_fence<WG>(a1);
      if (k == ((d >> 5) & 3)) { release(c, h.x); release(c, h.w); }
      load_part<WG, 0>(c, r, q); add_part<WG>(c, q, a0);
      load_part<WG, 1>(c, r, q); add_part<WG>(c, q, a1);
#pragma unroll
      for (int t = 0; t < 4; t++) { release(c, r.slot); r.next(); }
    }
    load_part<WG, 0>(c, r, q);
    wg_wait<1>();
    acc_fence<WG>(a0);
    TRACE_O(0);
    add_part<WG>(c, q, a0);
    stage_out<WG, 0>(c, a0);
    TRACE_O(1);
    load_part<WG, 1>(c, r, q);
    wg_wait<0>();
    acc_fence<WG>(a1);
    TRACE_O(2);
    add_part<WG>(c, q, a1);
    stage_out<WG, 1>(c, a1);
    TRACE(i, 2); TRACE(i, 3); TRACE(i, 7);
    trace_dump(c);
    return;
  }
redo:
  {
    const size_t hoff = (size_t)(dc & 511) * (SK * DH);
    const int br = (dc >> 9) & 1;
#pragma unroll 1
    for (int part = 0; part < 2; part++) {
      const int t = WG ? 3 - part : part;
      redo_tile(c, c.sb + QBUF_OFF + t * 16384, t == 3 ? 4096 : 8192, kv[br] + hoff, kv[2 + br] + hoff, dc,
                t * 64 + (t == 3 ? 8 : 16) * c.warp);
    }
    o_done(c);
    release_q<WG>(c);
  }
  goto next;
}

template <bool SIMPLE>
__global__ void __launch_bounds__(384, 1) mha_fused_kernel(const __grid_constant__ Params P) {
  extern __shared__ __align__(1024) uint8_t smem_raw[];
  const uint32_t sbase = smem_u32(smem_raw);
  const int tid = threadIdx.x;
  const int wg = __shfl_sync(0xffffffffu, tid >> 7, 0);
  const int warp = __shfl_sync(0xffffffffu, (tid >> 5) & 3, 0);
  const int lane = tid & 31;
  const int cta = blockIdx.x;
  constexpr bool PAIR = !SIMPLE && CLUSTER;

  if (tid == 0) T3(15, 0);
  if ((sbase & 0xffffff) != SB0) __trap();
  {
    const int wi = wg * 4 + warp;
    asm volatile(ELECT "prefetch.tensormap [%0];\n}" ::"l"(&P.x[0][0] + wi) : "memory");
#pragma unroll
    for (int k = 0; k < 5; k++) {
      const int b = min(BAR_OFF + (wi * 5 + k) * 8, DESC_OFF - 8);
      asm volatile(ELECT "mbarrier.init.shared::cta.b64 [%0], %1;\n}"
                   ::"r"(sbase + b), "r"(b < BAR_EMPTY || b >= BAR_DESC ? 1 : b >= BAR_STG && b < BAR_OUT ? 4 : 8) : "memory");
    }
    asm volatile("fence.mbarrier_init.release.cluster;" ::: "memory");
    if (wi < 6) asm volatile(ELECT "prefetch.tensormap [%0];\n}" ::"l"(&P.x[0][0] + 12 + wi) : "memory");
  }
  if (PAIR) asm volatile("barrier.cluster.arrive.aligned;\nbarrier.cluster.wait.aligned;" ::: "memory"); else __syncthreads();

  if (wg == 2) {
    asm volatile("setmaxnreg.dec.sync.aligned.u32 %0;" ::"n"(REG_P));
    if (warp == 1) {
      const uint32_t qb = sbase + QBUF_OFF;
      const uint32_t ep = __shfl_sync(0xffffffffu, *(volatile unsigned*)&g_epoch + 1, 0);
      asm volatile("st.volatile.shared.u32 [%0], %1;" ::"r"(sbase + EPOCH_OFF), "r"(ep) : "memory");
      uint32_t dc = c_sched.queue[cta], qi = 0, piece = 0, na = 0;
      TTAIL(0);
      for (int i = 0; (dc >> 30) != 2; i++) {
        if (!(dc >> 30) && o_reuse<SIMPLE>((dc >> 5) & 31)) {
          const unsigned* rd = &g_rd[0][0] + ((dc & 1023) >> 2) - OR * 8;
          for (uint32_t n = 0; !__all_sync(0xffffffffu, reached(rd, ep * 5)); __nanosleep(300)) if (++n > (1u << 22)) __trap();
        }
        mbar_wait_w(sbase + BAR_GO, i & 1);
        if (piece == 0) {
          if (PAIR && (cta & 1)) {
            asm volatile(ELECT EXPECT("%0", "4") "mbarrier.arrive.shared::cluster.b64 _, [%1];\n}" ::"r"(sbase + BAR_MAIL), "r"(peer(sbase + BAR_MAIL)) : "memory");
            mbar_wait_w(sbase + BAR_MAIL, i & 1);
            qi = lds(sbase + EPOCH_OFF + 8);
          } else if (lane == 0) {
            qi = atomicAdd(&g_next, PAIR ? 2 : 1);
            if (qi == (SIMPLE ? Q_ALL : Q_RANGES) - (PAIR ? 2 : 1)) { g_next = 0; g_epoch = ep; }
          }
          qi = __shfl_sync(0xffffffffu, qi, 0);
          if (PAIR && !(cta & 1)) {
            mbar_wait_w(sbase + BAR_MAIL, i & 1);
            asm volatile(ELECT "st.async.shared::cluster.mbarrier::complete_tx::bytes.u32 [%0], %1, [%2];\n}"
                         ::"r"(peer(sbase + EPOCH_OFF + 8)), "r"(qi + 1), "r"(peer(sbase + BAR_MAIL)) : "memory");
          }
          qi += SIMPLE ? gridDim.x : NCTA;
        }
        uint32_t d;
        if (qi < (SIMPLE ? Q_ALL : Q_RANGES)) { d = c_sched.queue[qi]; if (d & 0x8000) d ^= (1u << 30) | (63u << 16) | 0x8000; else d |= o_slot<SIMPLE>(d >> 5) << 15 | (d & 31) << 10; }
        else if (SIMPLE) d = 2u << 30;
        else { const uint32_t e = qi - Q_RANGES, g = e / 5; d = c_sched.piece[g][piece++] | (g & 1 ? g * 5 + 4 - e : e - g * 5) << 8; }
        if ((d >> 30) == 1) {
          const uint32_t k0 = (d >> 22) & 63;
          const uint32_t run = __ffs(__ballot_sync(0xffffffffu, !reached(&g_cnt[d & 31][lane & 7], ep * 4)) & (0xffu << (k0 >> 3))) - 1;
          if (run <= (k0 + ((d >> 16) & 63)) >> 3) d |= run <= (k0 + O_STEPS) >> 3 ? (2u << 30) | 128 : 128;
        }
        asm volatile("st.volatile.shared.u32 [%0], %1;" ::"r"(sbase + EPOCH_OFF + 4), "r"(qi) : "memory");
        asm volatile("st.volatile.shared.u32 [%0], %1;" ::"r"(sbase + DESC_OFF + ((i + 1) & 3) * 4), "r"(d) : "memory");
        __syncwarp();
        mbar_arrive_warp(sbase + BAR_DESC);
        const Work w = decode(dc);
        dc = d;
        if (w.kind == 0) {
          mbar_wait_w(sbase + BAR_OUT, na++ & 1);
          TTAIL(1);
          T3(i, 0); T3(i, 1);
          asm volatile(ELECT "red.release.gpu.global.add.u32 [%0], 1;\n}" ::"l"(&g_cnt[w.beta][w.sub >> 2]) : "memory");
          T3(i, 2);
          TTAIL(2);
          continue;
        }
        const bool fin = w.mode != 1;
        uint64_t pol, pol2;
        asm volatile("createpolicy.fractional.L2::evict_first.b64 %0, 1.0;" : "=l"(pol));
        asm volatile("createpolicy.fractional.L2::evict_normal.b64 %0, 1.0;" : "=l"(pol2));
        if (!fin) pol = pol2;
        const CUtensorMap* m = fin ? P.out_st : P.o_st;
        const int c1 = fin ? (w.beta & 15) * SQ : 0;
        const int c2 = fin ? (w.beta >> 4) * (DM / 64) + w.sub * 2 : NBETA * 64 + w.range * 2;
        uint32_t pend = 0;
#pragma unroll 1
        for (int e = 0; e < 4; e++) {
          const int t = (ST_ORDER >> (4 * e)) & 3;
          mbar_wait_w(sbase + BAR_STG + (t ^ (t >> 1)) * 8, (i - na) & 1);
          tma_st3_hint_w(m + (t == 3), qb + t * 16384, 0, c1 + t * 64, c2, pol);
          bulk_commit();
          T2P(i + 1, 5, 2 * e);
          if (pend) {
            bulk_wait_read<1>();
            mbar_arrive8_w(pend);
            T2P(i + 1, 5, 2 * e - 1);
          }
          pend = sbase + BAR_EMPTY + (NS + t) * 8;
          if ((ST_NOW >> e) & 1) {
            bulk_wait_read<0>();
            mbar_arrive8_w(pend);
            pend = 0;
            T2P(i + 1, 5, 2 * e + 1);
          }
        }
        if (w.beta < N_EARLY) asm volatile(ELECT "red.relaxed.gpu.global.add.u32 [%0], 1;\n}" ::"l"(&g_rd[w.beta][7]) : "memory");
        T3(i, 0);
        if (piece >= 2) TTAIL(piece * 2 - 1);
        asm volatile("cp.async.bulk.wait_group 0;" ::: "memory");
        T3(i, 1);
        if (w.mode == 1) asm volatile(ELECT "st.release.gpu.global.u32 [%0], %1;\n}" ::"l"(&g_flag[w.range]), "r"(ep) : "memory");
        T3(i, 2);
        if (piece >= 2) TTAIL(piece * 2);
      }
      T3(15, 1);
    } else
    if (warp == 0) {
      Ring r{0, 1, 3};
      uint32_t d = c_sched.queue[cta];
      for (int i = 0;; i++) {
        const Work w = decode(d);
        if (w.kind == 2) break;
        const CUtensorMap* m = w.kind == 0 ? &P.wq[w.beta >> 4] : &P.wo[w.beta >> 4];
        for (int ks = 0; ks < w.nsteps; ks++) {
          const uint32_t b = borrow(ks, w.nsteps);
          r.next_if(b == 2);
          const uint32_t bar = sbase + BAR_FULL + r.slot * 8;
          mbar_wait_w(bar + (BAR_EMPTY - BAR_FULL), r.phase);
          if (w.kind == 0) tma_ld3_w(sbase + r.slot * SLOT, m, 0, ks * 64, w.sub * 2, bar, 16384);
          else tma_ld_wo_w(sbase + r.slot * SLOT, m, w.sub * 128, (w.k0 + ks) * 2, bar);
          if (w.kind != 0 && w.beta < N_EARLY && (ks & 7) == 5 && ks > 5)
            asm volatile(ELECT "red.relaxed.gpu.global.add.u32 [%0], 1;\n}" ::"l"(&g_rd[w.beta][(ks >> 3) - 1]) : "memory");
          if (ks < 10) T2P(i, 2, ks);
          if (w.kind != 0 && ks == max(w.nsteps - GO_P, 4)) mbar_arrive_warp(sbase + BAR_GO);
          r.next(); r.next_if(b == 2);
        }
        if (w.kind == 0) {
          r.phase ^= 1; r.next(); r.next();
        } else if (w.mode == 2) {
          for (int k = 1; k <= ((d >> 5) & 3); k++) {
            if (k == 1) TTAIL(9);
            wait_count(&g_flag[w.range + 5 * k], lds(sbase + EPOCH_OFF));
            TTAIL(10);
            asm volatile("fence.proxy.async.global;" ::: "memory");
#pragma unroll 1
            for (int t = 0; t < 4; t++) {
              mbar_wait_w(sbase + BAR_EMPTY + r.slot * 8, r.phase);
              tma_ld3_w(sbase + r.slot * SLOT, &P.o_st[t == 3], 0, t * 64, NBETA * 64 + (w.range + 5 * k) * 2, sbase + BAR_FULL + r.slot * 8,
                        t == 3 ? 8192 : 16384);
              r.next();
            }
          }
        }
        mbar_wait_w(sbase + BAR_DESC, i & 1);
        d = __shfl_sync(0xffffffffu, lds(sbase + DESC_OFF + ((i + 1) & 3) * 4), 0);
      }
    } else {
      const int hi = warp - 2;
      uint64_t pol_stream;
      uint32_t rdy = 0;
      asm volatile("createpolicy.fractional.L2::evict_first.b64 %0, 1.0;" : "=l"(pol_stream));
      Ring r{0, 1, 3};
      uint32_t d = c_sched.queue[cta];
      for (int i = 0;; i++) {
        const Work w = decode(d);
        if (w.kind == 2) break;
        const CUtensorMap* m = w.kind == 0 ? &P.x[hi][w.beta >> 4] : &P.o_ld[hi];
        int c1 = (w.kind == 0 ? (w.beta & 15) : o_slot<SIMPLE>(w.beta) * 64 + w.k0) * SQ + hi * 128;
        int k_wait = -1;
        const bool both = PAIR && (w.kind == 0 || w.sub != 4), mine = !both || hi == (cta & 1);
        if (w.kind != 0 && mine) {
          if (d & 128) k_wait = d >= (3u << 30) ? 0 : 8 - (w.k0 & 7);
          asm volatile("fence.proxy.async.global;" ::: "memory");
        }
        const int rank = i == 0 ? cta : __shfl_sync(0xffffffffu, lds(sbase + EPOCH_OFF + 4), 0) - NCTA;
        for (int ks = 0; ks < w.nsteps; ks++) {
          if (ks == k_wait) {
            wait_count(&g_cnt[d & 31][(w.k0 + ks) >> 3], lds(sbase + EPOCH_OFF) * 4);
            asm volatile("fence.proxy.async.global;" ::: "memory");
            k_wait = ((w.k0 + ks) | 7) + 1 - w.k0;
          }
          const uint32_t b = borrow(ks, w.nsteps);
          const bool bo = b != 2;
          r.next_if(hi && !bo); r.next_if(hi && !bo);
          const uint32_t sl = bo ? NS + (b ^ (3 * hi)) : r.slot, bar = sbase + BAR_FULL + sl * 8;
          mbar_wait_w(bar + (BAR_EMPTY - BAR_FULL), bo ? (r.xp >> b) & 1 : r.phase);
          const uint32_t bytes = hi ? 96 * 128 : 128 * 128;
          if (!mine) {
            asm volatile(ELECT EXPECT("%0", "%2") "mbarrier.arrive.shared::cluster.b64 _, [%1];\n}"
                         ::"r"(bar), "r"(peer(bar + (BAR_RDY - BAR_FULL))), "r"(bytes) : "memory");
          } else if (both) {
            mbar_wait_w(bar + (BAR_RDY - BAR_FULL), (rdy >> sl) & 1);
            rdy ^= 1 << sl;
            if (w.kind == 0) tma_ld2_both_w(sbase + sl * SLOT, m, ks * 64, c1, bar, bytes);
            else tma_ld2_both_hint_w(sbase + sl * SLOT, m, 0, c1, bar, bytes, pol_stream);
          } else if (!PAIR && w.kind == 0) tma_ld2_w(sbase + sl * SLOT, m, ks * 64, c1, bar, bytes);
          else tma_ld2_hint_w(sbase + sl * SLOT, m, 0, c1, bar, bytes, pol_stream);
          if (w.kind != 0) c1 += SQ;
          if (i == 0 && ks == PF_STEP)
            asm volatile(ELECT "cp.async.bulk.prefetch.tensor.3d.L2.global.L2::cache_hint [%0, {0, %1, 0}], %2;\n}"
                         ::"l"(&P.kv[hi][0]), "r"(d * SK), "l"(pol_stream) : "memory");
          if (ks < 10) T2P(i, 3 + hi, ks);
          if (!hi && w.kind != 0 && !(ks & 3)) TCLK(i * 16 + (ks >> 2));
          r.next(); r.next_if(!hi && !bo); r.next_if(!hi && !bo);
          r.xp ^= 1 << b;
        }
        r.xp ^= 3;
        if (w.kind == 0) {
          m = &P.kv[hi][w.beta >> 4];
          c1 = (d & 511) * SK;
          for (int j = 0; j < 16; j++) {
            if (hi) r.next();
            const uint32_t bar = sbase + BAR_FULL + r.slot * 8;
            const bool tight = i < KV_WIN_UNITS && j < KV_WIN_TILES + ((KV_WIN_RAMP * rank) >> 5);
            {
              const int s2 = (int)r.slot - (tight ? 2 : KV_WIN_D);
              mbar_wait_w(sbase + BAR_FULL + (s2 < 0 ? s2 + NS : s2) * 8, s2 < 0 ? r.phase : r.phase ^ 1);
            }
            if (j == 15 && hi) mbar_wait_w(sbase + BAR_DESC, i & 1);
            mbar_wait_w(sbase + BAR_EMPTY + r.slot * 8, r.phase);
            tma_ld3_hint_w(sbase + r.slot * SLOT, m, 0, c1, 0, bar, pol_stream);
            T2P(i, 3 + hi, 16 + j);
            if (!hi) TCLK(i * 16 + j);
            if (j == 14 && !hi) mbar_arrive_warp(sbase + BAR_GO);
            c1 += 64;
            r.next();
            if (!hi) r.next();
          }
        }
        mbar_wait_w(sbase + BAR_DESC, i & 1);
        d = __shfl_sync(0xffffffffu, lds(sbase + DESC_OFF + ((i + 1) & 3) * 4), 0);
      }
    }
  } else {
    Ctx c;
    c.sb = sbase; c.wg = wg; c.warp = warp; c.src = 0; c.mqk = 0; c.mpv = 0; c.lead = lane == 0; c.lane0 = c.lane = lane;
    if (wg == 0) consumer<0>(c, P.kp); else consumer<1>(c, P.kp);
  }
}

typedef CUresult (*EncodeFn)(CUtensorMap*, CUtensorMapDataType, cuuint32_t, void*, const cuuint64_t*, const cuuint64_t*,
                             const cuuint32_t*, const cuuint32_t*, CUtensorMapInterleave, CUtensorMapSwizzle,
                             CUtensorMapL2promotion, CUtensorMapFloatOOBfill);

void make_map(EncodeFn enc, CUtensorMap* m, const void* ptr, int rank, const cuuint64_t* dims, const cuuint64_t* strides,
              const cuuint32_t* box, int promo = 2, CUtensorMapSwizzle swz = CU_TENSOR_MAP_SWIZZLE_128B) {
  cuuint32_t es[5] = {1, 1, 1, 1, 1};
  enc(m, CU_TENSOR_MAP_DATA_TYPE_BFLOAT16, rank, const_cast<void*>(ptr), dims, strides, box, es,
      CU_TENSOR_MAP_INTERLEAVE_NONE, swz, promo == 2 ? CU_TENSOR_MAP_L2_PROMOTION_L2_256B : promo == 1 ? CU_TENSOR_MAP_L2_PROMOTION_L2_128B : CU_TENSOR_MAP_L2_PROMOTION_NONE,
      CU_TENSOR_MAP_FLOAT_OOB_FILL_NONE);
}

}

extern "C" void kernel_launch(void* const* d_in, const int* in_sizes, int n_in, void* d_out, int out_size) {
  (void)in_sizes; (void)n_in; (void)out_size;
  static EncodeFn enc = nullptr;
  static void* o_ptr = nullptr;
  static int n_sm = 0;
  cudaLaunchAttribute at;
  at.id = cudaLaunchAttributeClusterDimension;
  at.val.clusterDim.x = CLUSTER ? 2 : 1; at.val.clusterDim.y = 1; at.val.clusterDim.z = 1;
  cudaLaunchConfig_t cfg = {};
  cfg.gridDim = dim3(NCTA); cfg.blockDim = dim3(384); cfg.dynamicSmemBytes = SMEM_BYTES; cfg.attrs = &at; cfg.numAttrs = 1;
  if (!enc) {
    void* fn = nullptr;
    cudaDriverEntryPointQueryResult qr;
    cudaGetDriverEntryPoint("cuTensorMapEncodeTiled", &fn, cudaEnableDefault, &qr);
    enc = (EncodeFn)fn;
    cudaGetSymbolAddress(&o_ptr, g_o);
    cudaFuncSetAttribute(mha_fused_kernel<false>, cudaFuncAttributeMaxDynamicSharedMemorySize, SMEM_BYTES);
    cudaFuncSetAttribute(mha_fused_kernel<true>, cudaFuncAttributeMaxDynamicSharedMemorySize, SMEM_BYTES);
    int dev = 0;
    cudaGetDevice(&dev);
    cudaDeviceGetAttribute(&n_sm, cudaDevAttrMultiProcessorCount, dev);
    int n_cl = 0;
    cudaOccupancyMaxActiveClusters(&n_cl, mha_fused_kernel<false>, &cfg);
    if (n_cl * (CLUSTER ? 2 : 1) < NCTA && n_sm >= NCTA) n_sm = NCTA - 1;
  }
  Params P;
  for (int br = 0; br < 2; br++) {
    const void* x = d_in[br * 5 + 0]; const void* kc = d_in[br * 5 + 1]; const void* vc = d_in[br * 5 + 2];
    const void* wq = d_in[br * 5 + 3]; const void* wo = d_in[br * 5 + 4];
    { cuuint64_t d[2] = {DM, (cuuint64_t)NB * SQ}, s[1] = {DM * 2}; cuuint32_t b[2] = {64, 128}, b2[2] = {64, 96};
      make_map(enc, &P.x[0][br], x, 2, d, s, b, PR_X); make_map(enc, &P.x[1][br], x, 2, d, s, b2, PR_X); }
    { cuuint64_t d[3] = {64, DM, HD / 64}, s[2] = {HD * 2, 128}; cuuint32_t b[3] = {64, 64, 2}; make_map(enc, &P.wq[br], wq, 3, d, s, b, PR_W); }
    { cuuint64_t d[5] = {DM, 2, 4, 4, HD / 32}, s[4] = {DM * 2, 8 * DM * 2, 2 * DM * 2, 32 * DM * 2}; cuuint32_t b[5] = {64, 2, 4, 4, 2};
      make_map(enc, &P.wo[br], wo, 5, d, s, b, PR_W); }
    { cuuint64_t d[3] = {64, (cuuint64_t)NB * NH * SK, 2}, s[2] = {DH * 2, 128}; cuuint32_t b[3] = {64, 64, 2};
      make_map(enc, &P.kv[0][br], kc, 3, d, s, b, PR_KV); make_map(enc, &P.kv[1][br], vc, 3, d, s, b, PR_KV); }
    P.kp[br] = (const __nv_bfloat16*)kc; P.vp[br] = (const __nv_bfloat16*)vc;

  }
  { cuuint64_t d[2] = {64, (cuuint64_t)NBETA * 64 * SQ}, s[1] = {128}; cuuint32_t b[2] = {64, 128}, b2[2] = {64, 96};
    make_map(enc, &P.o_ld[0], o_ptr, 2, d, s, b, 2, CU_TENSOR_MAP_SWIZZLE_NONE); make_map(enc, &P.o_ld[1], o_ptr, 2, d, s, b2, 2, CU_TENSOR_MAP_SWIZZLE_NONE); }
  { cuuint64_t d[3] = {64, SQ, O_BLOCKS}, s[2] = {128, SQ * 128}; cuuint32_t b[3] = {64, 64, 2}, b2[3] = {64, 32, 2};
    make_map(enc, &P.o_st[0], o_ptr, 3, d, s, b); make_map(enc, &P.o_st[1], o_ptr, 3, d, s, b2); }
  { cuuint64_t d[3] = {64, (cuuint64_t)NB * SQ, 2 * DM / 64}, s[2] = {2 * DM * 2, 128}; cuuint32_t b[3] = {64, 64, 2}, b2[3] = {64, 32, 2};
    make_map(enc, &P.out_st[0], d_out, 3, d, s, b); make_map(enc, &P.out_st[1], d_out, 3, d, s, b2); }
  if (n_sm >= NCTA) cudaLaunchKernelEx(&cfg, mha_fused_kernel<false>, P);
  else mha_fused_kernel<true><<<n_sm, 384, SMEM_BYTES>>>(P);
}
```

```cpp
#include <cuda_runtime.h>
#include <cuda_bf16.h>
#include <cuda.h>
#include <stdint.h>
#include <stdlib.h>

namespace {

__device__ __forceinline__ void wgmma_proj(float (&d)[64], uint64_t da, uint64_t db, int scaleD) {
  asm volatile("{\n.reg .pred p;\nsetp.ne.b32 p, %66, 0;\n"
      "wgmma.mma_async.sync.aligned.m64n128k16.f32.bf16.bf16 "
      "{%0, %1, %2, %3, %4, %5, %6, %7, %8, %9, %10, %11, %12, %13, %14, %15, %16, %17, %18, %19, %20, %21, %22, %23, %24, %25, %26, %27, %28, %29, %30, "
      "%31, %32, %33, %34, %35, %36, %37, %38, %39, %40, %41, %42, %43, %44, %45, %46, %47, %48, %49, %50, %51, %52, %53, %54, %55, %56, %57, %58, %59, %60, "
      "%61, %62, %63}, "
      "%64, %65, p, 1, 1, 0, 1;\n}\n"
      : "+f"(d[0]), "+f"(d[1]), "+f"(d[2]), "+f"(d[3]), "+f"(d[4]), "+f"(d[5]), "+f"(d[6]), "+f"(d[7]), "+f"(d[8]), "+f"(d[9]), "+f"(d[10]), "+f"(d[11]),
        "+f"(d[12]), "+f"(d[13]), "+f"(d[14]), "+f"(d[15]), "+f"(d[16]), "+f"(d[17]), "+f"(d[18]), "+f"(d[19]), "+f"(d[20]), "+f"(d[21]), "+f"(d[22]),
        "+f"(d[23]), "+f"(d[24]), "+f"(d[25]), "+f"(d[26]), "+f"(d[27]), "+f"(d[28]), "+f"(d[29]), "+f"(d[30]), "+f"(d[31]), "+f"(d[32]), "+f"(d[33]),
        "+f"(d[34]), "+f"(d[35]), "+f"(d[36]), "+f"(d[37]), "+f"(d[38]), "+f"(d[39]), "+f"(d[40]), "+f"(d[41]), "+f"(d[42]), "+f"(d[43]), "+f"(d[44]),
        "+f"(d[45]), "+f"(d[46]), "+f"(d[47]), "+f"(d[48]), "+f"(d[49]), "+f"(d[50]), "+f"(d[51]), "+f"(d[52]), "+f"(d[53]), "+f"(d[54]), "+f"(d[55]),
        "+f"(d[56]), "+f"(d[57]), "+f"(d[58]), "+f"(d[59]), "+f"(d[60]), "+f"(d[61]), "+f"(d[62]), "+f"(d[63])
      : "l"(da), "l"(db), "r"(scaleD));
}
__device__ __forceinline__ void wgmma_proj96(float (&d)[64], uint64_t da, uint64_t db, int scaleD) {
  asm volatile("{\n.reg .pred p;\nsetp.ne.b32 p, %50, 0;\n"
      "wgmma.mma_async.sync.aligned.m64n96k16.f32.bf16.bf16 "
      "{%0, %1, %2, %3, %4, %5, %6, %7, %8, %9, %10, %11, %12, %13, %14, %15, %16, %17, %18, %19, %20, %21, %22, %23, %24, %25, %26, %27, %28, %29, %30, "
      "%31, %32, %33, %34, %35, %36, %37, %38, %39, %40, %41, %42, %43, %44, %45, %46, %47}, "
      "%48, %49, p, 1, 1, 1, 0;\n}\n"
      : "+f"(d[0]), "+f"(d[1]), "+f"(d[2]), "+f"(d[3]), "+f"(d[4]), "+f"(d[5]), "+f"(d[6]), "+f"(d[7]), "+f"(d[8]), "+f"(d[9]), "+f"(d[10]), "+f"(d[11]),
        "+f"(d[12]), "+f"(d[13]), "+f"(d[14]), "+f"(d[15]), "+f"(d[16]), "+f"(d[17]), "+f"(d[18]), "+f"(d[19]), "+f"(d[20]), "+f"(d[21]), "+f"(d[22]),
        "+f"(d[23]), "+f"(d[24]), "+f"(d[25]), "+f"(d[26]), "+f"(d[27]), "+f"(d[28]), "+f"(d[29]), "+f"(d[30]), "+f"(d[31]), "+f"(d[32]), "+f"(d[33]),
        "+f"(d[34]), "+f"(d[35]), "+f"(d[36]), "+f"(d[37]), "+f"(d[38]), "+f"(d[39]), "+f"(d[40]), "+f"(d[41]), "+f"(d[42]), "+f"(d[43]), "+f"(d[44]),
        "+f"(d[45]), "+f"(d[46]), "+f"(d[47])
      : "l"(da), "l"(db), "r"(scaleD));
}
__device__ __forceinline__ void wgmma_qk(float (&d)[32], uint64_t da, uint64_t db, int scaleD) {
  asm volatile("{\n.reg .pred p;\nsetp.ne.b32 p, %34, 0;\n"
      "wgmma.mma_async.sync.aligned.m64n64k16.f32.bf16.bf16 "
      "{%0, %1, %2, %3, %4, %5, %6, %7, %8, %9, %10, %11, %12, %13, %14, %15, %16, %17, %18, %19, %20, %21, %22, %23, %24, %25, %26, %27, %28, %29, %30, "
      "%31}, "
      "%32, %33, p, 1, 1, 0, 0;\n}\n"
      : "+f"(d[0]), "+f"(d[1]), "+f"(d[2]), "+f"(d[3]), "+f"(d[4]), "+f"(d[5]), "+f"(d[6]), "+f"(d[7]), "+f"(d[8]), "+f"(d[9]), "+f"(d[10]), "+f"(d[11]),
        "+f"(d[12]), "+f"(d[13]), "+f"(d[14]), "+f"(d[15]), "+f"(d[16]), "+f"(d[17]), "+f"(d[18]), "+f"(d[19]), "+f"(d[20]), "+f"(d[21]), "+f"(d[22]),
        "+f"(d[23]), "+f"(d[24]), "+f"(d[25]), "+f"(d[26]), "+f"(d[27]), "+f"(d[28]), "+f"(d[29]), "+f"(d[30]), "+f"(d[31])
      : "l"(da), "l"(db), "r"(scaleD));
}
__device__ __forceinline__ void wgmma_qk_rs(float (&d)[32], uint32_t a0, uint32_t a1, uint32_t a2, uint32_t a3, uint64_t db, int scaleD) {
  asm volatile("{\n.reg .pred p;\nsetp.ne.b32 p, %37, 0;\n"
      "wgmma.mma_async.sync.aligned.m64n64k16.f32.bf16.bf16 "
      "{%0, %1, %2, %3, %4, %5, %6, %7, %8, %9, %10, %11, %12, %13, %14, %15, %16, %17, %18, %19, %20, %21, %22, %23, %24, %25, %26, %27, %28, %29, %30, "
      "%31}, "
      "{%32, %33, %34, %35}, %36, p, 1, 1, 0;\n}\n"
      : "+f"(d[0]), "+f"(d[1]), "+f"(d[2]), "+f"(d[3]), "+f"(d[4]), "+f"(d[5]), "+f"(d[6]), "+f"(d[7]), "+f"(d[8]), "+f"(d[9]), "+f"(d[10]), "+f"(d[11]),
        "+f"(d[12]), "+f"(d[13]), "+f"(d[14]), "+f"(d[15]), "+f"(d[16]), "+f"(d[17]), "+f"(d[18]), "+f"(d[19]), "+f"(d[20]), "+f"(d[21]), "+f"(d[22]),
        "+f"(d[23]), "+f"(d[24]), "+f"(d[25]), "+f"(d[26]), "+f"(d[27]), "+f"(d[28]), "+f"(d[29]), "+f"(d[30]), "+f"(d[31])
      : "r"(a0), "r"(a1), "r"(a2), "r"(a3), "l"(db), "r"(scaleD));
}
__device__ __forceinline__ void wgmma_pv(float (&d)[64], uint32_t a0, uint32_t a1, uint32_t a2, uint32_t a3, uint64_t db, int scaleD) {
  asm volatile("{\n.reg .pred p;\nsetp.ne.b32 p, %69, 0;\n"
      "wgmma.mma_async.sync.aligned.m64n128k16.f32.bf16.bf16 "
      "{%0, %1, %2, %3, %4, %5, %6, %7, %8, %9, %10, %11, %12, %13, %14, %15, %16, %17, %18, %19, %20, %21, %22, %23, %24, %25, %26, %27, %28, %29, %30, "
      "%31, %32, %33, %34, %35, %36, %37, %38, %39, %40, %41, %42, %43, %44, %45, %46, %47, %48, %49, %50, %51, %52, %53, %54, %55, %56, %57, %58, %59, %60, "
      "%61, %62, %63}, "
      "{%64, %65, %66, %67}, %68, p, 1, 1, 1;\n}\n"
      : "+f"(d[0]), "+f"(d[1]), "+f"(d[2]), "+f"(d[3]), "+f"(d[4]), "+f"(d[5]), "+f"(d[6]), "+f"(d[7]), "+f"(d[8]), "+f"(d[9]), "+f"(d[10]), "+f"(d[11]),
        "+f"(d[12]), "+f"(d[13]), "+f"(d[14]), "+f"(d[15]), "+f"(d[16]), "+f"(d[17]), "+f"(d[18]), "+f"(d[19]), "+f"(d[20]), "+f"(d[21]), "+f"(d[22]),
        "+f"(d[23]), "+f"(d[24]), "+f"(d[25]), "+f"(d[26]), "+f"(d[27]), "+f"(d[28]), "+f"(d[29]), "+f"(d[30]), "+f"(d[31]), "+f"(d[32]), "+f"(d[33]),
        "+f"(d[34]), "+f"(d[35]), "+f"(d[36]), "+f"(d[37]), "+f"(d[38]), "+f"(d[39]), "+f"(d[40]), "+f"(d[41]), "+f"(d[42]), "+f"(d[43]), "+f"(d[44]),
        "+f"(d[45]), "+f"(d[46]), "+f"(d[47]), "+f"(d[48]), "+f"(d[49]), "+f"(d[50]), "+f"(d[51]), "+f"(d[52]), "+f"(d[53]), "+f"(d[54]), "+f"(d[55]),
        "+f"(d[56]), "+f"(d[57]), "+f"(d[58]), "+f"(d[59]), "+f"(d[60]), "+f"(d[61]), "+f"(d[62]), "+f"(d[63])
      : "r"(a0), "r"(a1), "r"(a2), "r"(a3), "l"(db), "r"(scaleD));
}
__device__ __forceinline__ void wgmma_qk_sp(float (&d)[32], uint32_t a0, uint32_t a1, uint32_t a2, uint32_t a3, uint64_t db, int scaleD, uint32_t meta) {
  asm volatile("{\n.reg .pred p;\nsetp.ne.b32 p, %37, 0;\n"
      "wgmma.mma_async.sp.sync.aligned.m64n64k32.f32.bf16.bf16 "
      "{%0, %1, %2, %3, %4, %5, %6, %7, %8, %9, %10, %11, %12, %13, %14, %15, %16, %17, %18, %19, %20, %21, %22, %23, %24, %25, %26, %27, %28, %29, %30, "
      "%31}, "
      "{%32, %33, %34, %35}, %36, %38, 0, p, 1, 1, 0;\n}\n"
      : "+f"(d[0]), "+f"(d[1]), "+f"(d[2]), "+f"(d[3]), "+f"(d[4]), "+f"(d[5]), "+f"(d[6]), "+f"(d[7]), "+f"(d[8]), "+f"(d[9]), "+f"(d[10]), "+f"(d[11]),
        "+f"(d[12]), "+f"(d[13]), "+f"(d[14]), "+f"(d[15]), "+f"(d[16]), "+f"(d[17]), "+f"(d[18]), "+f"(d[19]), "+f"(d[20]), "+f"(d[21]), "+f"(d[22]),
        "+f"(d[23]), "+f"(d[24]), "+f"(d[25]), "+f"(d[26]), "+f"(d[27]), "+f"(d[28]), "+f"(d[29]), "+f"(d[30]), "+f"(d[31])
      : "r"(a0), "r"(a1), "r"(a2), "r"(a3), "l"(db), "r"(scaleD), "r"(meta));
}
__device__ __forceinline__ void wgmma_pv_sp(float (&d)[64], uint32_t a0, uint32_t a1, uint32_t a2, uint32_t a3, uint64_t db, int scaleD, uint32_t meta) {
  asm volatile("{\n.reg .pred p;\nsetp.ne.b32 p, %69, 0;\n"
      "wgmma.mma_async.sp.sync.aligned.m64n128k32.f32.bf16.bf16 "
      "{%0, %1, %2, %3, %4, %5, %6, %7, %8, %9, %10, %11, %12, %13, %14, %15, %16, %17, %18, %19, %20, %21, %22, %23, %24, %25, %26, %27, %28, %29, %30, "
      "%31, %32, %33, %34, %35, %36, %37, %38, %39, %40, %41, %42, %43, %44, %45, %46, %47, %48, %49, %50, %51, %52, %53, %54, %55, %56, %57, %58, %59, %60, "
      "%61, %62, %63}, "
      "{%64, %65, %66, %67}, %68, %70, 0, p, 1, 1, 1;\n}\n"
      : "+f"(d[0]), "+f"(d[1]), "+f"(d[2]), "+f"(d[3]), "+f"(d[4]), "+f"(d[5]), "+f"(d[6]), "+f"(d[7]), "+f"(d[8]), "+f"(d[9]), "+f"(d[10]), "+f"(d[11]),
        "+f"(d[12]), "+f"(d[13]), "+f"(d[14]), "+f"(d[15]), "+f"(d[16]), "+f"(d[17]), "+f"(d[18]), "+f"(d[19]), "+f"(d[20]), "+f"(d[21]), "+f"(d[22]),
        "+f"(d[23]), "+f"(d[24]), "+f"(d[25]), "+f"(d[26]), "+f"(d[27]), "+f"(d[28]), "+f"(d[29]), "+f"(d[30]), "+f"(d[31]), "+f"(d[32]), "+f"(d[33]),
        "+f"(d[34]), "+f"(d[35]), "+f"(d[36]), "+f"(d[37]), "+f"(d[38]), "+f"(d[39]), "+f"(d[40]), "+f"(d[41]), "+f"(d[42]), "+f"(d[43]), "+f"(d[44]),
        "+f"(d[45]), "+f"(d[46]), "+f"(d[47]), "+f"(d[48]), "+f"(d[49]), "+f"(d[50]), "+f"(d[51]), "+f"(d[52]), "+f"(d[53]), "+f"(d[54]), "+f"(d[55]),
        "+f"(d[56]), "+f"(d[57]), "+f"(d[58]), "+f"(d[59]), "+f"(d[60]), "+f"(d[61]), "+f"(d[62]), "+f"(d[63])
      : "r"(a0), "r"(a1), "r"(a2), "r"(a3), "l"(db), "r"(scaleD), "r"(meta));
}
__device__ __forceinline__ void wgmma_proj_init(float (&d)[64], uint64_t da, uint64_t db, int scaleD) {
  asm volatile("{\n.reg .pred p;\nsetp.ne.b32 p, %66, 0;\n"
      "wgmma.mma_async.sync.aligned.m64n128k16.f32.bf16.bf16 "
      "{%0, %1, %2, %3, %4, %5, %6, %7, %8, %9, %10, %11, %12, %13, %14, %15, %16, %17, %18, %19, %20, %21, %22, %23, %24, %25, %26, %27, %28, %29, %30, "
      "%31, %32, %33, %34, %35, %36, %37, %38, %39, %40, %41, %42, %43, %44, %45, %46, %47, %48, %49, %50, %51, %52, %53, %54, %55, %56, %57, %58, %59, %60, "
      "%61, %62, %63}, "
      "%64, %65, p, 1, 1, 0, 1;\n}\n"
      : "=f"(d[0]), "=f"(d[1]), "=f"(d[2]), "=f"(d[3]), "=f"(d[4]), "=f"(d[5]), "=f"(d[6]), "=f"(d[7]), "=f"(d[8]), "=f"(d[9]), "=f"(d[10]), "=f"(d[11]),
        "=f"(d[12]), "=f"(d[13]), "=f"(d[14]), "=f"(d[15]), "=f"(d[16]), "=f"(d[17]), "=f"(d[18]), "=f"(d[19]), "=f"(d[20]), "=f"(d[21]), "=f"(d[22]),
        "=f"(d[23]), "=f"(d[24]), "=f"(d[25]), "=f"(d[26]), "=f"(d[27]), "=f"(d[28]), "=f"(d[29]), "=f"(d[30]), "=f"(d[31]), "=f"(d[32]), "=f"(d[33]),
        "=f"(d[34]), "=f"(d[35]), "=f"(d[36]), "=f"(d[37]), "=f"(d[38]), "=f"(d[39]), "=f"(d[40]), "=f"(d[41]), "=f"(d[42]), "=f"(d[43]), "=f"(d[44]),
        "=f"(d[45]), "=f"(d[46]), "=f"(d[47]), "=f"(d[48]), "=f"(d[49]), "=f"(d[50]), "=f"(d[51]), "=f"(d[52]), "=f"(d[53]), "=f"(d[54]), "=f"(d[55]),
        "=f"(d[56]), "=f"(d[57]), "=f"(d[58]), "=f"(d[59]), "=f"(d[60]), "=f"(d[61]), "=f"(d[62]), "=f"(d[63])
      : "l"(da), "l"(db), "r"(scaleD));
}
__device__ __forceinline__ void wgmma_proj96_init(float (&d)[64], uint64_t da, uint64_t db, int scaleD) {
  asm volatile("{\n.reg .pred p;\nsetp.ne.b32 p, %50, 0;\n"
      "wgmma.mma_async.sync.aligned.m64n96k16.f32.bf16.bf16 "
      "{%0, %1, %2, %3, %4, %5, %6, %7, %8, %9, %10, %11, %12, %13, %14, %15, %16, %17, %18, %19, %20, %21, %22, %23, %24, %25, %26, %27, %28, %29, %30, "
      "%31, %32, %33, %34, %35, %36, %37, %38, %39, %40, %41, %42, %43, %44, %45, %46, %47}, "
      "%48, %49, p, 1, 1, 1, 0;\n}\n"
      : "=f"(d[0]), "=f"(d[1]), "=f"(d[2]), "=f"(d[3]), "=f"(d[4]), "=f"(d[5]), "=f"(d[6]), "=f"(d[7]), "=f"(d[8]), "=f"(d[9]), "=f"(d[10]), "=f"(d[11]),
        "=f"(d[12]), "=f"(d[13]), "=f"(d[14]), "=f"(d[15]), "=f"(d[16]), "=f"(d[17]), "=f"(d[18]), "=f"(d[19]), "=f"(d[20]), "=f"(d[21]), "=f"(d[22]),
        "=f"(d[23]), "=f"(d[24]), "=f"(d[25]), "=f"(d[26]), "=f"(d[27]), "=f"(d[28]), "=f"(d[29]), "=f"(d[30]), "=f"(d[31]), "=f"(d[32]), "=f"(d[33]),
        "=f"(d[34]), "=f"(d[35]), "=f"(d[36]), "=f"(d[37]), "=f"(d[38]), "=f"(d[39]), "=f"(d[40]), "=f"(d[41]), "=f"(d[42]), "=f"(d[43]), "=f"(d[44]),
        "=f"(d[45]), "=f"(d[46]), "=f"(d[47])
      : "l"(da), "l"(db), "r"(scaleD));
}
__device__ __forceinline__ void wgmma_qk_init(float (&d)[32], uint64_t da, uint64_t db, int scaleD) {
  asm volatile("{\n.reg .pred p;\nsetp.ne.b32 p, %34, 0;\n"
      "wgmma.mma_async.sync.aligned.m64n64k16.f32.bf16.bf16 "
      "{%0, %1, %2, %3, %4, %5, %6, %7, %8, %9, %10, %11, %12, %13, %14, %15, %16, %17, %18, %19, %20, %21, %22, %23, %24, %25, %26, %27, %28, %29, %30, "
      "%31}, "
      "%32, %33, p, 1, 1, 0, 0;\n}\n"
      : "=f"(d[0]), "=f"(d[1]), "=f"(d[2]), "=f"(d[3]), "=f"(d[4]), "=f"(d[5]), "=f"(d[6]), "=f"(d[7]), "=f"(d[8]), "=f"(d[9]), "=f"(d[10]), "=f"(d[11]),
        "=f"(d[12]), "=f"(d[13]), "=f"(d[14]), "=f"(d[15]), "=f"(d[16]), "=f"(d[17]), "=f"(d[18]), "=f"(d[19]), "=f"(d[20]), "=f"(d[21]), "=f"(d[22]),
        "=f"(d[23]), "=f"(d[24]), "=f"(d[25]), "=f"(d[26]), "=f"(d[27]), "=f"(d[28]), "=f"(d[29]), "=f"(d[30]), "=f"(d[31])
      : "l"(da), "l"(db), "r"(scaleD));
}
__device__ __forceinline__ void wgmma_qk_rs_init(float (&d)[32], uint32_t a0, uint32_t a1, uint32_t a2, uint32_t a3, uint64_t db, int scaleD) {
  asm volatile("{\n.reg .pred p;\nsetp.ne.b32 p, %37, 0;\n"
      "wgmma.mma_async.sync.aligned.m64n64k16.f32.bf16.bf16 "
      "{%0, %1, %2, %3, %4, %5, %6, %7, %8, %9, %10, %11, %12, %13, %14, %15, %16, %17, %18, %19, %20, %21, %22, %23, %24, %25, %26, %27, %28, %29, %30, "
      "%31}, "
      "{%32, %33, %34, %35}, %36, p, 1, 1, 0;\n}\n"
      : "=f"(d[0]), "=f"(d[1]), "=f"(d[2]), "=f"(d[3]), "=f"(d[4]), "=f"(d[5]), "=f"(d[6]), "=f"(d[7]), "=f"(d[8]), "=f"(d[9]), "=f"(d[10]), "=f"(d[11]),
        "=f"(d[12]), "=f"(d[13]), "=f"(d[14]), "=f"(d[15]), "=f"(d[16]), "=f"(d[17]), "=f"(d[18]), "=f"(d[19]), "=f"(d[20]), "=f"(d[21]), "=f"(d[22]),
        "=f"(d[23]), "=f"(d[24]), "=f"(d[25]), "=f"(d[26]), "=f"(d[27]), "=f"(d[28]), "=f"(d[29]), "=f"(d[30]), "=f"(d[31])
      : "r"(a0), "r"(a1), "r"(a2), "r"(a3), "l"(db), "r"(scaleD));
}
__device__ __forceinline__ void wgmma_pv_init(float (&d)[64], uint32_t a0, uint32_t a1, uint32_t a2, uint32_t a3, uint64_t db, int scaleD) {
  asm volatile("{\n.reg .pred p;\nsetp.ne.b32 p, %69, 0;\n"
      "wgmma.mma_async.sync.aligned.m64n128k16.f32.bf16.bf16 "
      "{%0, %1, %2, %3, %4, %5, %6, %7, %8, %9, %10, %11, %12, %13, %14, %15, %16, %17, %18, %19, %20, %21, %22, %23, %24, %25, %26, %27, %28, %29, %30, "
      "%31, %32, %33, %34, %35, %36, %37, %38, %39, %40, %41, %42, %43, %44, %45, %46, %47, %48, %49, %50, %51, %52, %53, %54, %55, %56, %57, %58, %59, %60, "
      "%61, %62, %63}, "
      "{%64, %65, %66, %67}, %68, p, 1, 1, 1;\n}\n"
      : "=f"(d[0]), "=f"(d[1]), "=f"(d[2]), "=f"(d[3]), "=f"(d[4]), "=f"(d[5]), "=f"(d[6]), "=f"(d[7]), "=f"(d[8]), "=f"(d[9]), "=f"(d[10]), "=f"(d[11]),
        "=f"(d[12]), "=f"(d[13]), "=f"(d[14]), "=f"(d[15]), "=f"(d[16]), "=f"(d[17]), "=f"(d[18]), "=f"(d[19]), "=f"(d[20]), "=f"(d[21]), "=f"(d[22]),
        "=f"(d[23]), "=f"(d[24]), "=f"(d[25]), "=f"(d[26]), "=f"(d[27]), "=f"(d[28]), "=f"(d[29]), "=f"(d[30]), "=f"(d[31]), "=f"(d[32]), "=f"(d[33]),
        "=f"(d[34]), "=f"(d[35]), "=f"(d[36]), "=f"(d[37]), "=f"(d[38]), "=f"(d[39]), "=f"(d[40]), "=f"(d[41]), "=f"(d[42]), "=f"(d[43]), "=f"(d[44]),
        "=f"(d[45]), "=f"(d[46]), "=f"(d[47]), "=f"(d[48]), "=f"(d[49]), "=f"(d[50]), "=f"(d[51]), "=f"(d[52]), "=f"(d[53]), "=f"(d[54]), "=f"(d[55]),
        "=f"(d[56]), "=f"(d[57]), "=f"(d[58]), "=f"(d[59]), "=f"(d[60]), "=f"(d[61]), "=f"(d[62]), "=f"(d[63])
      : "r"(a0), "r"(a1), "r"(a2), "r"(a3), "l"(db), "r"(scaleD));
}
__device__ __forceinline__ void wgmma_qk_sp_init(float (&d)[32], uint32_t a0, uint32_t a1, uint32_t a2, uint32_t a3, uint64_t db, int scaleD, uint32_t meta) {
  asm volatile("{\n.reg .pred p;\nsetp.ne.b32 p, %37, 0;\n"
      "wgmma.mma_async.sp.sync.aligned.m64n64k32.f32.bf16.bf16 "
      "{%0, %1, %2, %3, %4, %5, %6, %7, %8, %9, %10, %11, %12, %13, %14, %15, %16, %17, %18, %19, %20, %21, %22, %23, %24, %25, %26, %27, %28, %29, %30, "
      "%31}, "
      "{%32, %33, %34, %35}, %36, %38, 0, p, 1, 1, 0;\n}\n"
      : "=f"(d[0]), "=f"(d[1]), "=f"(d[2]), "=f"(d[3]), "=f"(d[4]), "=f"(d[5]), "=f"(d[6]), "=f"(d[7]), "=f"(d[8]), "=f"(d[9]), "=f"(d[10]), "=f"(d[11]),
        "=f"(d[12]), "=f"(d[13]), "=f"(d[14]), "=f"(d[15]), "=f"(d[16]), "=f"(d[17]), "=f"(d[18]), "=f"(d[19]), "=f"(d[20]), "=f"(d[21]), "=f"(d[22]),
        "=f"(d[23]), "=f"(d[24]), "=f"(d[25]), "=f"(d[26]), "=f"(d[27]), "=f"(d[28]), "=f"(d[29]), "=f"(d[30]), "=f"(d[31])
      : "r"(a0), "r"(a1), "r"(a2), "r"(a3), "l"(db), "r"(scaleD), "r"(meta));
}
__device__ __forceinline__ void wgmma_pv_sp_init(float (&d)[64], uint32_t a0, uint32_t a1, uint32_t a2, uint32_t a3, uint64_t db, int scaleD, uint32_t meta) {
  asm volatile("{\n.reg .pred p;\nsetp.ne.b32 p, %69, 0;\n"
      "wgmma.mma_async.sp.sync.aligned.m64n128k32.f32.bf16.bf16 "
      "{%0, %1, %2, %3, %4, %5, %6, %7, %8, %9, %10, %11, %12, %13, %14, %15, %16, %17, %18, %19, %20, %21, %22, %23, %24, %25, %26, %27, %28, %29, %30, "
      "%31, %32, %33, %34, %35, %36, %37, %38, %39, %40, %41, %42, %43, %44, %45, %46, %47, %48, %49, %50, %51, %52, %53, %54, %55, %56, %57, %58, %59, %60, "
      "%61, %62, %63}, "
      "{%64, %65, %66, %67}, %68, %70, 0, p, 1, 1, 1;\n}\n"
      : "=f"(d[0]), "=f"(d[1]), "=f"(d[2]), "=f"(d[3]), "=f"(d[4]), "=f"(d[5]), "=f"(d[6]), "=f"(d[7]), "=f"(d[8]), "=f"(d[9]), "=f"(d[10]), "=f"(d[11]),
        "=f"(d[12]), "=f"(d[13]), "=f"(d[14]), "=f"(d[15]), "=f"(d[16]), "=f"(d[17]), "=f"(d[18]), "=f"(d[19]), "=f"(d[20]), "=f"(d[21]), "=f"(d[22]),
        "=f"(d[23]), "=f"(d[24]), "=f"(d[25]), "=f"(d[26]), "=f"(d[27]), "=f"(d[28]), "=f"(d[29]), "=f"(d[30]), "=f"(d[31]), "=f"(d[32]), "=f"(d[33]),
        "=f"(d[34]), "=f"(d[35]), "=f"(d[36]), "=f"(d[37]), "=f"(d[38]), "=f"(d[39]), "=f"(d[40]), "=f"(d[41]), "=f"(d[42]), "=f"(d[43]), "=f"(d[44]),
        "=f"(d[45]), "=f"(d[46]), "=f"(d[47]), "=f"(d[48]), "=f"(d[49]), "=f"(d[50]), "=f"(d[51]), "=f"(d[52]), "=f"(d[53]), "=f"(d[54]), "=f"(d[55]),
        "=f"(d[56]), "=f"(d[57]), "=f"(d[58]), "=f"(d[59]), "=f"(d[60]), "=f"(d[61]), "=f"(d[62]), "=f"(d[63])
      : "r"(a0), "r"(a1), "r"(a2), "r"(a3), "l"(db), "r"(scaleD), "r"(meta));
}

constexpr int NB = 16, SQ = 224, DM = 640, NH = 32, SK = 1024, DH = 128;
constexpr int HD = NH * DH;
constexpr int NBETA = 2 * NB;
constexpr int NCTA = 132;
constexpr uint32_t SB0 = 1024;
constexpr int NS = 10;
constexpr int SLOT = 16384;
constexpr int QBUF_OFF = NS * SLOT;
constexpr int NSX = NS + 4;
constexpr int BAR_OFF = NSX * SLOT;
constexpr int BAR_FULL = BAR_OFF;
constexpr int BAR_EMPTY = BAR_OFF + 8 * NSX;
constexpr int BAR_STG = BAR_OFF + 16 * NSX;
constexpr int BAR_OUT = BAR_STG + 32;
constexpr int BAR_DESC = BAR_OUT + 8;
constexpr int BAR_GO = BAR_DESC + 8;
constexpr int BAR_MAIL = BAR_GO + 8;
constexpr int BAR_RDY = BAR_MAIL + 8;
constexpr int DESC_OFF = BAR_RDY + 8 * NSX;
constexpr int EPOCH_OFF = DESC_OFF + 16;
constexpr int TRACE_OFF = EPOCH_OFF + 16;
constexpr int SMEM_BYTES = TRACE_OFF;
constexpr float SM_C = 0.08838834764831845f * 1.4426950408889634f;
constexpr float SUM_HI = 1099511627776.f, SUM_LO = 1.f / 1099511627776.f;
constexpr uint32_t META_QK = 0xEEEE4444u;
constexpr uint32_t META_PV = 0x44EEEE44u;

#define QK_EARLY_MASK 3
#define ST_ORDER 0x2310
#define LAG_BAR 3
#define ST_NOW 8
#define PF_STEP 5
#define KV_WIN_UNITS 2
#define KV_WIN_D 4
#define SF 0xfe3f
#define O_STEPS 4
#define KV_WIN_RAMP 4
#define PDEPTH 0
#define KV_WIN_TILES -2
#define PR_KV 2
#define PR_X 2
#define PR_W 2
#define REG_C 232
#define REG_P 24
#define GO_P 4
#define P_POS 216
#define OR 6
#define OR0 0
#define EARLY_BEGIN 0
#define B_LATE 23
#define H_LATE 24
#define NQR 1
#define NQR1 5
#define NQR2 0
#define SKIP_ST 2
#define CLUSTER 1
#define PAIRB 1
#define KG 5
#define PK 44
#define EARLY_MASK 0x3fffu
#define PIECE_TABLE 0x50188016,0x65e88038,0x50321819,0x6c8d1830,0x403f2812,0x80000000,0x50215014,0x695a503c,0x5029b813,0x6c4eb85e,0x501b4815,0x689d4834,0x502b1017,0x6ccc1039,0x50312010,0x80000000,0x500e681b,0x65e8683f,0x502ea011,0x80000000,0x63b1902e,0x80000000,0x63f0603b,0x80000000,0x64ad003d,0x80000000,0x64eca83a,0x80000000,0x5024581c,0x80000000,0x5012b01a,0x6a95b033,0x5011081d,0x6b130837,0x5016701f,0x6c8d7056,0x501ec81e,0x80000000,0x6723302f,0x80000000,0x501b380f,0x80000000,0x67234035,0x80000000,0x500d980e,0x6bd09831,0x56587816,0x80000000,0x50168818,0x80000000,0x57d1c01e,0x80000000

struct Params {
  CUtensorMap x[2][2], wq[2], kv[2][2], wo[2];
  CUtensorMap o_ld[2], o_st[2], out_st[2];
  const __nv_bfloat16* kp[2];
  const __nv_bfloat16* vp[2];
};

constexpr int NPART = 32 * 5, O_BLOCKS = NBETA * 64 + 2 * NPART;
__device__ __align__(128) __nv_bfloat16 g_o[(size_t)O_BLOCKS * SQ * 64];
__device__ unsigned g_cnt[NBETA][8];
__device__ unsigned g_rd[NBETA][8];
__device__ unsigned g_epoch, g_next;
__device__ unsigned g_flag[NPART];

__device__ __forceinline__ uint32_t smem_u32(const void* p) { return (uint32_t)__cvta_generic_to_shared(p); }
__device__ __forceinline__ void mbar_arrive(uint32_t bar) {
  asm volatile("mbarrier.arrive.shared::cta.b64 _, [%0];" ::"r"(bar) : "memory");
}
__device__ __forceinline__ void mbar_arrive_warp(uint32_t bar) {
  asm volatile("{\n.reg .pred p;\nelect.sync _|p, 0xffffffff;\n@p mbarrier.arrive.shared::cta.b64 _, [%0];\n}" ::"r"(bar) : "memory");
}
__device__ __forceinline__ int lane_now() { int l; asm volatile("mov.u32 %0, %%laneid;" : "=r"(l)); return l; }
__device__ __forceinline__ bool mbar_try(uint32_t bar, uint32_t parity) {
  uint32_t ok;
  asm volatile("{\n.reg .pred p;\nmbarrier.try_wait.parity.shared::cta.b64 p, [%1], %2;\nselp.u32 %0, 1, 0, p;\n}"
               : "=r"(ok) : "r"(bar), "r"(parity) : "memory");
  return ok;
}
__device__ __forceinline__ bool mbar_test(uint32_t bar, uint32_t parity) {
  uint32_t ok;
  asm volatile("{\n.reg .pred p;\nmbarrier.test_wait.parity.shared::cta.b64 p, [%1], %2;\nselp.u32 %0, 1, 0, p;\n}"
               : "=r"(ok) : "r"(bar), "r"(parity) : "memory");
  return ok;
}
__device__ __forceinline__ void mbar_wait_w(uint32_t bar, uint32_t parity) {
  uint32_t n = 0;
  while (!__all_sync(0xffffffffu, mbar_try(bar, parity))) {
    if (++n > (1u << 22)) __trap();
  }
}
#define ELECT "{\n.reg .pred p;\nelect.sync _|p, 0xffffffff;\n@p "
__device__ __forceinline__ void tma_st3_hint_w(const CUtensorMap* m, uint32_t src, int c0, int c1, int c2, uint64_t pol) {
  asm volatile(ELECT "cp.async.bulk.tensor.3d.global.shared::cta.bulk_group.L2::cache_hint [%0, {%2, %3, %4}], [%1], %5;\n}"
               ::"l"(m), "r"(src), "r"(c0), "r"(c1), "r"(c2), "l"(pol) : "memory");
}
#define EXPECT(bar, bytes) "mbarrier.arrive.expect_tx.shared::cta.b64 _, [" bar "], " bytes ";\n@p "
__device__ __forceinline__ void tma_ld2_w(uint32_t dst, const CUtensorMap* m, int c0, int c1, uint32_t bar, uint32_t bytes) {
  asm volatile(ELECT EXPECT("%2", "%5") "cp.async.bulk.tensor.2d.shared::cluster.global.mbarrier::complete_tx::bytes [%0], [%1, {%3, %4}], [%2];\n}"
               ::"r"(dst), "l"(m), "r"(bar), "r"(c0), "r"(c1), "r"(bytes) : "memory");
}
__device__ __forceinline__ void tma_ld2_hint_w(uint32_t dst, const CUtensorMap* m, int c0, int c1, uint32_t bar, uint32_t bytes, uint64_t pol) {
  asm volatile(ELECT EXPECT("%2", "%6") "cp.async.bulk.tensor.2d.shared::cluster.global.mbarrier::complete_tx::bytes.L2::cache_hint"
               " [%0], [%1, {%3, %4}], [%2], %5;\n}"
               ::"r"(dst), "l"(m), "r"(bar), "r"(c0), "r"(c1), "l"(pol), "r"(bytes) : "memory");
}
__device__ __forceinline__ void tma_ld3_w(uint32_t dst, const CUtensorMap* m, int c0, int c1, int c2, uint32_t bar, uint32_t bytes) {
  asm volatile(ELECT EXPECT("%2", "%6") "cp.async.bulk.tensor.3d.shared::cluster.global.mbarrier::complete_tx::bytes [%0], [%1, {%3, %4, %5}], [%2];\n}"
               ::"r"(dst), "l"(m), "r"(bar), "r"(c0), "r"(c1), "r"(c2), "r"(bytes) : "memory");
}
__device__ __forceinline__ void tma_ld3_hint_w(uint32_t dst, const CUtensorMap* m, int c0, int c1, int c2, uint32_t bar, uint64_t pol) {
  asm volatile(ELECT EXPECT("%2", "16384") "cp.async.bulk.tensor.3d.shared::cluster.global.mbarrier::complete_tx::bytes.L2::cache_hint"
               " [%0], [%1, {%3, %4, %5}], [%2], %6;\n}"
               ::"r"(dst), "l"(m), "r"(bar), "r"(c0), "r"(c1), "r"(c2), "l"(pol) : "memory");
}
__device__ __forceinline__ void tma_ld_wo_w(uint32_t dst, const CUtensorMap* m, int col, int grp, uint32_t bar) {
  asm volatile(ELECT EXPECT("%2", "16384") "cp.async.bulk.tensor.5d.shared::cluster.global.mbarrier::complete_tx::bytes [%0], [%1, {%3, 0, 0, 0, %4}], [%2];\n"
               "@p cp.async.bulk.tensor.5d.shared::cluster.global.mbarrier::complete_tx::bytes [%5], [%1, {%6, 0, 0, 0, %4}], [%2];\n}"
               ::"r"(dst), "l"(m), "r"(bar), "r"(col), "r"(grp), "r"(dst + 8192), "r"(col + 64) : "memory");
}
__device__ __forceinline__ void mbar_arrive8_w(uint32_t bar) {
  asm volatile(ELECT "mbarrier.arrive.shared::cta.b64 _, [%0], 8;\n}" ::"r"(bar) : "memory");
}
__device__ __forceinline__ uint32_t peer(uint32_t a) { uint32_t r; asm("mapa.shared::cluster.u32 %0, %1, %2;" : "=r"(r) : "r"(a), "r"(~blockIdx.x & 1)); return r; }
__device__ __forceinline__ void tma_ld2_both_w(uint32_t dst, const CUtensorMap* m, int c0, int c1, uint32_t bar, uint32_t bytes) {
  asm volatile(ELECT EXPECT("%2", "%5") "cp.async.bulk.tensor.2d.shared::cluster.global.mbarrier::complete_tx::bytes.multicast::cluster"
               " [%0], [%1, {%3, %4}], [%2], %6;\n}"
               ::"r"(dst), "l"(m), "r"(bar), "r"(c0), "r"(c1), "r"(bytes), "h"((uint16_t)3) : "memory");
}
__device__ __forceinline__ void tma_ld2_both_hint_w(uint32_t dst, const CUtensorMap* m, int c0, int c1, uint32_t bar, uint32_t bytes, uint64_t pol) {
  asm volatile(ELECT EXPECT("%2", "%6") "cp.async.bulk.tensor.2d.shared::cluster.global.mbarrier::complete_tx::bytes.multicast::cluster.L2::cache_hint"
               " [%0], [%1, {%3, %4}], [%2], %7, %5;\n}"
               ::"r"(dst), "l"(m), "r"(bar), "r"(c0), "r"(c1), "l"(pol), "r"(bytes), "h"((uint16_t)3) : "memory");
}
__device__ __forceinline__ void bulk_commit() { asm volatile("cp.async.bulk.commit_group;" ::: "memory"); }
template <int N> __device__ __forceinline__ void bulk_wait_read() { asm volatile("cp.async.bulk.wait_group.read %0;" ::"n"(N) : "memory"); }
__device__ __forceinline__ void wg_fence() { asm volatile("wgmma.fence.sync.aligned;" ::: "memory"); }
__device__ __forceinline__ void wg_commit() { asm volatile("wgmma.commit_group.sync.aligned;" ::: "memory"); }
template <int N> __device__ __forceinline__ void wg_wait() { asm volatile("wgmma.wait_group.sync.aligned %0;" ::"n"(N) : "memory"); }
__device__ __forceinline__ void fence_async_smem() { asm volatile("fence.proxy.async.shared::cta;" ::: "memory"); }
__device__ __forceinline__ void bar_sync(int id, int n) { asm volatile("bar.sync %0, %1;" ::"r"(id), "r"(n) : "memory"); }
__device__ __forceinline__ void touch(float& a) { asm volatile("neg.f32 %0, %0;" : "+f"(a)); }
__device__ __forceinline__ void touch(uint32_t& a) { asm volatile("not.b32 %0, %0;" : "+r"(a)); }
template <typename T, int N> __device__ __forceinline__ void touch(T (&a)[N]) {
#pragma unroll
  for (int i = 0; i < N; i++) touch(a[i]);
}
template <int ID, typename... A> __device__ __forceinline__ void sched_fence(uint32_t x, A&... a) {
  if (!((SF >> ID) & 1)) return;
  asm volatile("" : "+r"(x)::"memory");
#pragma unroll 1
  for (; __builtin_expect(x >= 100 + ID, 0); x >>= 1) { (touch(a), ...); __nanosleep(x); }
}
template <int N> __device__ __forceinline__ void reg_fence(float (&a)[N]) {
#pragma unroll
  for (int i = 0; i < N; i++) asm volatile("" : "+f"(a[i])::"memory");
}
template <int N> __device__ __forceinline__ void reg_fence(uint32_t (&a)[N]) {
#pragma unroll
  for (int i = 0; i < N; i++) asm volatile("" : "+r"(a[i])::"memory");
}
__device__ __forceinline__ float ex2(float x) { float y; asm("ex2.approx.ftz.f32 %0, %1;" : "=f"(y) : "f"(x)); return y; }
__device__ __forceinline__ uint32_t pack_bf16(float lo, float hi) {
  uint32_t r; asm("cvt.rn.bf16x2.f32 %0, %1, %2;" : "=r"(r) : "f"(hi), "f"(lo)); return r;
}
__device__ __forceinline__ void stsm4(uint32_t a, uint32_t r0, uint32_t r1, uint32_t r2, uint32_t r3) {
  asm volatile("stmatrix.sync.aligned.m8n8.x4.shared.b16 [%0], {%1, %2, %3, %4};" ::"r"(a), "r"(r0), "r"(r1), "r"(r2), "r"(r3) : "memory");
}
__device__ __forceinline__ void stsm4t(uint32_t a, uint32_t r0, uint32_t r1, uint32_t r2, uint32_t r3) {
  asm volatile("stmatrix.sync.aligned.m8n8.x4.trans.shared.b16 [%0], {%1, %2, %3, %4};" ::"r"(a), "r"(r0), "r"(r1), "r"(r2), "r"(r3) : "memory");
}
__device__ __forceinline__ void ldsm4(uint32_t a, uint32_t& r0, uint32_t& r1, uint32_t& r2, uint32_t& r3) {
  asm volatile("ldmatrix.sync.aligned.m8n8.x4.shared.b16 {%0, %1, %2, %3}, [%4];" : "=r"(r0), "=r"(r1), "=r"(r2), "=r"(r3) : "r"(a) : "memory");
}
__device__ __forceinline__ void sts16(uint32_t a, uint32_t v) { asm volatile("st.shared.u16 [%0], %1;" ::"r"(a), "h"((uint16_t)v) : "memory"); }
__device__ __forceinline__ void mma16816(float& c0, float& c1, float& c2, float& c3, uint32_t a0, uint32_t a1, uint32_t a2, uint32_t a3,
                                         uint32_t b0, uint32_t b1) {
  asm volatile("mma.sync.aligned.m16n8k16.row.col.f32.bf16.bf16.f32 {%0, %1, %2, %3}, {%4, %5, %6, %7}, {%8, %9}, {%0, %1, %2, %3};"
               : "+f"(c0), "+f"(c1), "+f"(c2), "+f"(c3) : "r"(a0), "r"(a1), "r"(a2), "r"(a3), "r"(b0), "r"(b1));
}
__device__ __forceinline__ uint32_t sdesc(uint32_t addr, uint32_t lbo) { return (addr >> 4) + ((lbo >> 4) << 16); }
__device__ __forceinline__ uint64_t desc64(uint32_t lo, uint32_t hi) { uint64_t d; asm("mov.b64 %0, {%1, %2};" : "=l"(d) : "r"(lo), "r"(hi)); return d; }
__device__ __forceinline__ void dadd(uint64_t& d, uint32_t inc) {
  asm("{\n.reg .b32 l, h;\nmov.b64 {l, h}, %0;\nadd.u32 l, l, %1;\nmov.b64 %0, {l, h};\n}" : "+l"(d) : "r"(inc));
}

struct Ring {
  uint32_t slot, phase, xp;
  __device__ __forceinline__ void uniform() {
    slot = __shfl_sync(0xffffffffu, slot, 0); phase = __shfl_sync(0xffffffffu, phase, 0); xp = __shfl_sync(0xffffffffu, xp, 0);
  }
  __device__ __forceinline__ void next() { if (++slot == NS) { slot = 0; phase ^= 1; } }
  __device__ __forceinline__ void next_if(bool p) { slot += p; if (slot == NS) { slot = 0; phase ^= 1; } }
};
__device__ __forceinline__ uint32_t borrow(int ks, int n) {
  const int k = ks + 1;
  return k >= 4 && !(k & 2) && k < n ? k & 1 : 2;
}

constexpr uint32_t Q_RANGES = NBETA * NH + __builtin_popcount(EARLY_MASK) * 5, Q_ALL = NBETA * (NH + 5);
constexpr int NRANGE = NCTA / 5;
struct Work { int kind, mode, k0, nsteps, range, beta, sub; };
struct Sched { uint16_t queue[Q_ALL]; uint32_t piece[NRANGE + 1][4]; };
constexpr Sched make_sched() {
  Sched s{};
  int q = 0, a = 0;
  for (int t = 0, e = 0; a < NBETA * NH; t++) {
    for (; e < NBETA && 8 * (e & ~PAIRB) + PK <= t && a >= P_POS; e++)
      for (int col = 0; col < 5 && (EARLY_MASK >> e & 1); col++) s.queue[q++] = 0x8000 | (e & 1 ? 4 - col : col) << 8 | e;
    for (int b = 0; b < NBETA; b++)
      for (int h = 0; h < NH; h++)
        if ((b >= B_LATE && h >= H_LATE ? 300 + b : 8 * (b & ~PAIRB) + KG * (h >> 2)) == t) { s.queue[q++] = b << 5 | h; a++; }
  }
  for (int b = 0; b < NBETA; b++)
    for (int col = 0; col < 5 && !(EARLY_MASK >> b & 1); col++) s.queue[q++] = 0x8000 | col << 8 | b;
  constexpr uint32_t T[NRANGE * 2] = {PIECE_TABLE};
  for (int g = 0; g <= NRANGE; g++)
    for (int n = 0; n < 4; n++) s.piece[g][n] = g < NRANGE && n < 2 ? T[2 * g + n] : 2u << 30;
  return s;
}
__constant__ Sched c_sched = make_sched();
constexpr int N_EARLY = __builtin_popcount(EARLY_MASK);
constexpr bool reuse_ok() {
  const Sched s = make_sched();
  int first[NBETA + OR] = {};
  for (int q = Q_RANGES - 1; q >= 0; q--) if (!(s.queue[q] & 0x8000)) first[s.queue[q] >> 5] = q;
  for (int q = 0; q < Q_RANGES; q++) if ((s.queue[q] & 0x8000) && (s.queue[q] & 31) >= OR0 && q - first[(s.queue[q] & 31) + OR] > NCTA - 32) return false;
  return true;
}
static_assert(reuse_ok());
template <bool SIMPLE> __device__ __forceinline__ bool o_reuse(uint32_t b) { return !SIMPLE && b - (OR0 + OR) < N_EARLY - OR0; }
template <bool SIMPLE> __device__ __forceinline__ uint32_t o_slot(uint32_t b) { return o_reuse<SIMPLE>(b) ? OR0 + (b - OR0) % OR : b; }
__device__ __forceinline__ Work decode(uint32_t d) {
  Work w;
  w.kind = d >> 30; if (w.kind == 3) w.kind = 1;
  w.mode = (d >> 28) & 3; w.k0 = (d >> 22) & 63;
  if (w.kind == 0) { w.beta = (d >> 5) & 31; w.sub = d & 31; w.nsteps = DM / 64; }
  else { w.beta = d & 31; w.sub = (d >> 8) & 7; w.nsteps = ((d >> 16) & 63) + 1; }
  w.range = ((d >> 11) & 31) * 5 + w.sub;
  return w;
}

__device__ __forceinline__ bool reached(const unsigned* cnt, unsigned target) {
  unsigned v;
  asm volatile("ld.acquire.gpu.global.u32 %0, [%1];" : "=r"(v) : "l"(cnt) : "memory");
  return (int)(v - target) >= 0;
}
__device__ __forceinline__ void wait_count(const unsigned* cnt, unsigned target) {
  unsigned n = 0;
  while (!__all_sync(0xffffffffu, reached(cnt, target))) { if (++n > (1u << 24)) __trap(); }
}
__device__ __forceinline__ uint32_t lds(uint32_t a) { uint32_t v; asm volatile("ld.volatile.shared.u32 %0, [%1];" : "=r"(v) : "r"(a) : "memory"); return v; }

#define TRACE(u, e)
#define T3(u, e)
#define T2C(u, e)
#define T2P(u, r, e)
#define TTAIL(k)
#define TCLK(k)
#define TO -1
#define TRACE_O(k) if (TO == k) TRACE(i, 5)
#define TRACE_P(u, e)
#define TRACE_IN(u, e)

struct Ctx {
  uint32_t sb;
  int wg, warp;
  uint32_t mqk, mpv;
  bool lead;
  int lane0, lane;
  int src;
};
template <int N> __device__ __forceinline__ uint32_t dhi(uint32_t lo) { return 0x40000040u + (lo >> (26 + N)); }
__device__ __forceinline__ void release(const Ctx& c, uint32_t slot) {
  if (c.lead) mbar_arrive(c.sb + BAR_EMPTY + slot * 8);
}
__device__ __forceinline__ uint32_t acquire(const Ctx& c, Ring& r, bool have = false) {
  const uint32_t s = r.slot;
  if (!have) mbar_wait_w(c.sb + BAR_FULL + s * 8, r.phase);
  r.next();
  return s;
}
__device__ __forceinline__ void mbar_wait2_w(uint32_t b0, uint32_t p0, uint32_t b1, uint32_t p1) {
  uint32_t n = 0;
  while (!__all_sync(0xffffffffu, mbar_try(b0, p0) & mbar_try(b1, p1))) {
    if (++n > (1u << 22)) __trap();
  }
}
__device__ __forceinline__ void mbar_wait3_w(uint32_t b0, uint32_t p0, uint32_t b1, uint32_t p1, uint32_t b2, uint32_t p2) {
  uint32_t n = 0;
  while (!__all_sync(0xffffffffu, mbar_try(b0, p0) & mbar_try(b1, p1) & mbar_try(b2, p2))) {
    if (++n > (1u << 22)) __trap();
  }
}
__device__ __forceinline__ void acquire2(const Ctx& c, Ring& r, uint32_t& s0, uint32_t& s1, bool have = false) {
  const uint32_t p0 = r.phase;
  s0 = r.slot; r.next(); s1 = r.slot;
  if (!have) mbar_wait2_w(c.sb + BAR_FULL + s0 * 8, p0, c.sb + BAR_FULL + s1 * 8, r.phase);
  r.next();
}
template <int N>
__device__ __forceinline__ bool peek(const Ctx& c, Ring r) {
  bool ok = true;
#pragma unroll
  for (int k = 0; k < N; k++) { ok &= mbar_test(c.sb + BAR_FULL + r.slot * 8, r.phase); r.next(); }
  return ok;
}
__device__ __forceinline__ void staged(const Ctx& c, int part) {
  fence_async_smem();
  __syncwarp();
  mbar_arrive_warp(c.sb + BAR_STG + c.wg * 16 + part * 8);
}

template <int WG, bool FIRST, int H>
__device__ __forceinline__ void proj_half(const Ctx& c, float (&acc)[64], uint32_t w, uint32_t x, uint32_t sw) {
  uint64_t dx = desc64((SB0 + x * SLOT + (WG ? 0 : H * 8192)) >> 4, dhi<0>(x) + sw);
  uint64_t dw = desc64(WG ? (SB0 + w * SLOT + H * 8192) >> 4 : sdesc(SB0 + w * SLOT, 8192), dhi<1>(x));
  wg_fence();
  if (WG) { if (FIRST) wgmma_proj96_init(acc, dw, dx, 0); else wgmma_proj96(acc, dw, dx, 1); }
  else { if (FIRST) wgmma_proj_init(acc, dx, dw, 0); else wgmma_proj(acc, dx, dw, 1); }
#pragma unroll
  for (int k = 1; k < 4; k++) {
    dadd(dx, k == 2 ? 2 + (sw >> 30) * 28 : 2); dadd(dw, 128);
    if (WG) wgmma_proj96(acc, dw, dx, 1); else wgmma_proj(acc, dx, dw, 1);
  }
  wg_commit();
}

__device__ __forceinline__ void proj_store16(uint32_t a, const float* f, float sc) {
  stsm4t(a, pack_bf16(f[0] * sc, f[1] * sc), pack_bf16(f[2] * sc, f[3] * sc), pack_bf16(f[4] * sc, f[5] * sc), pack_bf16(f[6] * sc, f[7] * sc));
}

__device__ __forceinline__ uint32_t stage_off(const Ctx& c) {
  const int lane = c.lane, mi = lane >> 3, r8 = lane & 7;
  return ((mi >> 1) * 8 + r8) * 128 + (((2 * c.warp + (mi & 1)) ^ r8) << 4);
}
__device__ __forceinline__ uint32_t q3_swz(uint32_t r8) { return ((r8 & 3) << 1) | (r8 >> 2); }
template <int H>
__device__ __forceinline__ void stage_t2(const Ctx& c, const float (&a)[64], float sc) {
  const uint32_t base = c.sb + QBUF_OFF + 2 * 16384 + H * 8192 + stage_off(c);
#pragma unroll
  for (int jj = 0; jj < 4; jj++) proj_store16(base + jj * 2048, &a[jj * 8], sc);
}
template <int H, bool IS_Q>
__device__ __forceinline__ void stage_t3(const Ctx& c, const float (&a)[64], float sc) {
  const uint32_t off = stage_off(c), r8 = (off >> 7) & 7;
  const uint32_t t3 = c.sb + QBUF_OFF + 3 * 16384 + H * 4096 + (IS_Q ? off ^ ((r8 ^ q3_swz(r8)) << 4) : off);
  proj_store16(t3, &a[32], sc);
  proj_store16(t3 + 2048, &a[40], sc);
}

template <int WG, int h>
__device__ __forceinline__ void load_part(const Ctx& c, Ring r, uint32_t (&q)[32]) {
  uint32_t n = 0;
  while (!h && !__all_sync(0xffffffffu, peek<4>(c, r))) {
    if (++n > (1u << 26)) __trap();
  }
  const int lane = c.lane, mi = lane >> 3, r8 = lane & 7;
  if (WG) { r.next(); r.next(); }
  const uint32_t off = c.sb + (WG ? stage_off(c) : (16 * c.warp + (mi & 1) * 8 + r8) * 128), t0 = off + r.slot * SLOT;
  r.next();
  const uint32_t t1 = off + r.slot * SLOT;
#pragma unroll
    for (int jj = 0; jj < (WG ? 6 : 8); jj++) {
      uint32_t* p = &q[4 * jj];
      if (WG) asm volatile("ldmatrix.sync.aligned.m8n8.x4.trans.shared.b16 {%0, %1, %2, %3}, [%4];" : "=r"(p[0]), "=r"(p[1]), "=r"(p[2]), "=r"(p[3])
                           : "r"((jj < 4 ? t0 + h * 8192 : t1 + h * 4096) + (jj & 3) * 2048) : "memory");
      else ldsm4((h ? t1 : t0) + (jj >> 2) * 8192 + (((((2 * jj) & 7) + (mi >> 1)) ^ r8) << 4), p[0], p[1], p[2], p[3]);
    }
}
template <int WG>
__device__ __forceinline__ void add_part(const Ctx& c, const uint32_t (&q)[32], float (&a)[64]) {
  const uint32_t one = (c.lane >> 3) == (c.lane & 3) ? 0x3f80u << (c.lane & 4) * 4 : 0;
#pragma unroll
  for (int i = 0; i < (WG ? 12 : 16); i++)
    asm("mma.sync.aligned.m16n8k8.row.col.f32.bf16.bf16.f32 {%0, %1, %2, %3}, {%4, %5}, {%6}, {%0, %1, %2, %3};"
        : "+f"(a[4 * i]), "+f"(a[4 * i + 1]), "+f"(a[4 * i + 2]), "+f"(a[4 * i + 3]) : "r"(q[2 * i]), "r"(q[2 * i + 1]), "r"(one));
}

__device__ __forceinline__ void trace_dump(const Ctx& c) {
}
struct RowSum { float l0, l1; };
__device__ __forceinline__ const char* o_addr(uint32_t item, int row, int lane) {
  return reinterpret_cast<const char*>(g_o) + (((item >> 10) * (2 * SQ) + row) * 128 + (lane ^ (lane >> 3)) * 16);
}
__device__ __forceinline__ void o_stg(const char* p, int i, const uint32_t* q) {
  asm volatile("st.global.v4.b32 [%0], {%1, %2, %3, %4};"
               ::"l"(p + (i >> 1) * (SQ * 128) + (i & 1) * 512), "r"(q[0]), "r"(q[1]), "r"(q[2]), "r"(q[3]) : "memory");
}
template <int MODE, int I0 = 0, int NI = 4>
__device__ __forceinline__ void o_emit(const char* p, const float (&o)[64], float inv) {
#pragma unroll
  for (int i = I0; i < I0 + NI; i++) {
    uint32_t q[4];
#pragma unroll
    for (int j = 0; j < 4; j++) q[j] = pack_bf16(o[16 * i + 4 * j + 2 * MODE] * inv, o[16 * i + 4 * j + 2 * MODE + 1] * inv);
    o_stg(p, i, q);
  }
}
__device__ __forceinline__ void o_done(const Ctx& c) {
  __syncwarp();
  mbar_arrive_warp(c.sb + BAR_OUT);
  __syncwarp();
}
template <int WG>
__device__ __forceinline__ void o_first(const Ctx& c, uint32_t item, float (&o)[64], const RowSum& inv) {
  const char* p = o_addr(item, WG ? 192 + 8 * c.warp : 64 + 16 * c.warp, c.lane);
  reg_fence(o);
  if (WG) {
    uint32_t q[16];
#pragma unroll
    for (int j = 0; j < 16; j++) q[j] = pack_bf16((o[4 * j] + o[4 * j + 2]) * inv.l0, (o[4 * j + 1] + o[4 * j + 3]) * inv.l0);
#pragma unroll
    for (int i = 0; i < 4; i++) o_stg(p, i, q + 4 * i);
  } else { o_emit<0>(p, o, inv.l0); o_emit<1>(p + 1024, o, inv.l1); }
}
template <int K0, int K1>
__device__ __forceinline__ void o_piece(const Ctx& c, const char* p, int k, const float (&o)[64], const RowSum& inv) {
  constexpr int NI = 8 / O_STEPS, M = K0 * NI / 4;
  if constexpr (K1 - K0 == 1) {
    o_emit<M, K0 * NI % 4, NI>(p + M * 1024, o, M ? inv.l1 : inv.l0);
    if (K1 == O_STEPS) o_done(c);
  } else {
    if (k <= (K0 + K1) / 2) o_piece<K0, (K0 + K1) / 2>(c, p, k, o, inv); else o_piece<(K0 + K1) / 2, K1>(c, p, k, o, inv);
  }
}
template <int WG>
__device__ __forceinline__ void o_second(const Ctx& c, uint32_t item, int k, float (&o)[64], const RowSum& inv) {
  reg_fence(o);
  o_piece<0, O_STEPS>(c, o_addr(item, 128 * WG + 16 * c.warp, c.lane0 + (k >> 8)), k, o, inv);
}
template <int WG>
__device__ __forceinline__ void release_q(const Ctx& c) {
#pragma unroll
  for (int t = 0; t < 2; t++)
    if (c.lead) asm volatile("mbarrier.arrive.shared::cta.b64 _, [%0], 2;" ::"r"(c.sb + BAR_EMPTY + (NS + 2 * WG + t) * 8) : "memory");
  __syncwarp();
}
struct Slots { uint32_t w, x, o, po; };
template <int WG>
__device__ __forceinline__ void acc_fence(float (&a)[64]) {
#pragma unroll
  for (int i = 0; i < (WG ? 48 : 64); i++) asm volatile("" : "+f"(a[i])::"memory");
}
template <int WG>
__device__ __forceinline__ void begin_acquire(const Ctx& c, Ring& r, Slots& h, bool wait) {
  const uint32_t s0 = r.slot, p0 = r.phase, f = c.sb + BAR_FULL;
  r.next();
  const uint32_t p1 = r.phase;
  h.w = r.slot; r.next();
  h.x = WG ? r.slot : s0; h.o = WG ? s0 : r.slot; h.po = r.phase;
  if (wait) { if (WG) mbar_wait3_w(f + s0 * 8, p0, f + h.w * 8, p1, f + h.x * 8, r.phase); else mbar_wait2_w(f + s0 * 8, p0, f + h.w * 8, p1); }
  r.next();
}
template <int WG>
__device__ __forceinline__ void proj_begin(const Ctx& c, Ring& r, float (&a0)[64], Slots& h, bool wait, uint32_t sw) {
  begin_acquire<WG>(c, r, h, wait);
  proj_half<WG, true, 0>(c, a0, h.w, h.x, sw);
  if (WG) release(c, h.o);
}
template <int WG>
__device__ __forceinline__ void proj_main(Ctx& c, Ring& r, float (&a0)[64], float (&a1)[64], Slots& h, int n, uint32_t sw, int unit,
                                          uint32_t item, int nq, float (&o1)[64], const RowSum& inv) {
  constexpr bool DEEP = (PDEPTH >> WG) & 1;
  T2C(unit, 3);
  int ks = 1;
#pragma unroll 1
  do {
    const Slots p = h;
    const uint32_t b = borrow(ks, n), tile = NS + (WG ? 3 - b : b), f = c.sb + BAR_FULL;
    const uint32_t s0 = b != 2 ? tile : r.slot, p0 = b != 2 ? (r.xp >> b) & 1 : r.phase;
    r.next_if(b == 2);
    const uint32_t p1 = r.phase;
    h.w = r.slot; r.next();
    const uint32_t s2 = b != 2 ? tile : r.slot;
    h.po = b != 2 ? p0 : r.phase;
    r.next_if(b == 2);
    r.xp ^= 1 << b;
    h.x = WG ? s2 : s0; h.o = WG ? s0 : s2;
    mbar_wait3_w(f + s0 * 8, p0, f + h.w * 8, p1, f + (WG ? s2 : p.o) * 8, WG ? h.po : p.po);
    if (ks < 10) T2C(unit, ks * 4);
    if (DEEP) {
      proj_half<WG, false, 0>(c, a0, h.w, h.x, sw);
      release(c, WG ? h.o : p.o);
      if (ks < 10) T2C(unit, ks * 4 + 1);
      wg_wait<1>();
      if (ks < 10) T2C(unit, ks * 4 + 2);
      release(c, p.x); release(c, p.w);
    } else {
      release(c, WG ? h.o : p.o);
      wg_wait<0>();
      release(c, p.x); release(c, p.w);
      if (ks < 10) T2C(unit, ks * 4 + 1);
      proj_half<WG, false, 0>(c, a0, h.w, h.x, sw);
      if (ks < 10) T2C(unit, ks * 4 + 2);
    }
    proj_half<WG, false, 1>(c, a1, h.w, h.x, sw);
    if (ks < 10) T2C(unit, ks * 4 + 3);
    if (ks <= nq) o_second<WG>(c, item, ks, o1, inv);
  } while (++ks != n);
  {
    const uint32_t e0 = c.sb + BAR_EMPTY + (NS + 3 * WG) * 8, e1 = c.sb + BAR_EMPTY + (NS + 1 + WG) * 8;
    const uint32_t p0 = (r.xp ^ unit ^ 1) & 1, p1 = ((r.xp >> 1) ^ unit ^ 1) & 1;
    const uint32_t k0 = sw ? e0 : c.sb + BAR_FULL + r.slot * 8, pk = sw ? p0 : r.phase;
    uint32_t cnt = 0;
    while (!__all_sync(0xffffffffu, mbar_try(e0, p0) & mbar_try(e1, p1) & mbar_try(k0, pk) & (WG || mbar_try(c.sb + BAR_FULL + h.o * 8, h.po)))) {
      if (++cnt > (1u << 22)) __trap();
    }
  }
  c.lane = c.lane0 + (h.w >> 5);
  if (!WG) release(c, h.o);
}
template <int WG>
__device__ __forceinline__ void proj_end(const Ctx& c, float (&a1)[64], const Slots& h) {
  wg_wait<0>();
  acc_fence<WG>(a1);
  release(c, h.x); release(c, h.w);
}
__device__ __forceinline__ uint32_t get_desc(const Ctx& c, int i) {
  uint32_t d;
  mbar_wait_w(c.sb + BAR_DESC, (i - 1) & 1);
  asm volatile("ld.volatile.shared.u32 %0, [%1];" : "=r"(d) : "r"(c.sb + DESC_OFF + (i & 3) * 4) : "memory");
  return __shfl_sync(0xffffffffu, d, 0);
}

__device__ __forceinline__ float quad_max(float x) {
  x = fmaxf(x, __shfl_xor_sync(0xffffffffu, x, 1));
  return fmaxf(x, __shfl_xor_sync(0xffffffffu, x, 2));
}
__device__ __forceinline__ float quad_sum(float x) {
  x += __shfl_xor_sync(0xffffffffu, x, 1);
  return x + __shfl_xor_sync(0xffffffffu, x, 2);
}
template <bool SP, bool FIRST>
__device__ __forceinline__ void exps(const Ctx& c, const float (&s)[32], uint32_t (&p)[SP ? 8 : 16], RowSum& st) {
  if constexpr (SP) {
    uint32_t q[8];
    float t;
#pragma unroll
    for (int j = 0; j < 8; j++) {
      const float e0 = ex2(s[4 * j] + s[4 * j + 2]), e1 = ex2(s[4 * j + 1] + s[4 * j + 3]);
      if (j == 0) t = e0 + e1; else t += e0 + e1;
      q[j] = pack_bf16(e0, e1);
    }
    const bool odd = c.src & 2;
#pragma unroll
    for (int g = 0; g < 4; g++) {
      p[2 * g] = __shfl_sync(0xffffffffu, odd ? q[2 * g + 1] : q[2 * g], c.src);
      p[2 * g + 1] = __shfl_sync(0xffffffffu, odd ? q[2 * g] : q[2 * g + 1], c.src ^ 1);
    }
    st.l0 = FIRST ? t : st.l0 + t;
  } else {
    float t0, t1;
#pragma unroll
    for (int j = 0; j < 8; j++) {
      const float e0 = ex2(s[4 * j]), e1 = ex2(s[4 * j + 1]), e2 = ex2(s[4 * j + 2]), e3 = ex2(s[4 * j + 3]);
      if (j == 0) { t0 = e0 + e1; t1 = e2 + e3; } else { t0 += e0 + e1; t1 += e2 + e3; }
      p[2 * j] = pack_bf16(e0, e1);
      p[2 * j + 1] = pack_bf16(e2, e3);
    }
    st.l0 = FIRST ? t0 : st.l0 + t0;
    st.l1 = FIRST ? t1 : st.l1 + t1;
  }
}
template <bool SP>
__device__ __forceinline__ bool finish_sums(RowSum& st) {
  const float a = quad_sum(st.l0), b = SP ? a : quad_sum(st.l1);
  st.l0 = __fdividef(1.f, a); st.l1 = __fdividef(1.f, b);
  return !(a >= SUM_LO && a <= SUM_HI && b >= SUM_LO && b <= SUM_HI);
}
template <bool SP, bool INIT, int SITE, bool COMMIT = true, int NR = 0>
__device__ __forceinline__ void issue_qk(const Ctx& c, float (&s)[32], const uint32_t (&qs)[32], uint32_t dq, uint32_t dk) {
  uint64_t a = desc64(dq, dhi<SITE & 1>(dk)), b = desc64(dk, dhi<1 - (SITE & 1)>(dk));
  if (SP) {
    if (INIT) wgmma_qk_sp_init(s, qs[0], qs[1], qs[2], qs[3], b, 0, c.mqk); else wgmma_qk_sp(s, qs[0], qs[1], qs[2], qs[3], b, 0, c.mqk);
#pragma unroll
    for (int k = 1; k < 4; k++) { dadd(b, k == 2 ? 508 : 4); wgmma_qk_sp(s, qs[4 * k], qs[4 * k + 1], qs[4 * k + 2], qs[4 * k + 3], b, 1, c.mqk); }
  } else {
    if (NR) wgmma_qk_rs(s, qs[0], qs[1], qs[2], qs[3], b, 0); else if (INIT) wgmma_qk_init(s, a, b, 0); else wgmma_qk(s, a, b, 0);
#pragma unroll
    for (int k = 1; k < 8; k++) {
      if (k > NR) dadd(a, k == 4 ? 506 : 2);
      dadd(b, k == 4 ? 506 : 2);
      if (k < NR) wgmma_qk_rs(s, qs[4 * k], qs[4 * k + 1], qs[4 * k + 2], qs[4 * k + 3], b, 1); else wgmma_qk(s, a, b, 1);
    }
  }
  if (COMMIT) wg_commit();
}
template <bool SP, bool ACC, int SITE, bool SPLIT = false>
__device__ __forceinline__ void issue_pv(const Ctx& c, float (&o)[64], const uint32_t (&p)[SP ? 8 : 16], uint32_t dv) {
  uint64_t b = desc64(dv, dhi<SITE & 1>(dv));
  if constexpr (SP) {
    if (ACC) wgmma_pv_sp(o, p[0], p[1], p[2], p[3], b, 1, c.mpv); else wgmma_pv_sp_init(o, p[0], p[1], p[2], p[3], b, 0, c.mpv);
    if (SPLIT) wg_commit();
    dadd(b, 256);
    wgmma_pv_sp(o, p[4], p[5], p[6], p[7], b, 1, c.mpv);
  } else {
    if (ACC) wgmma_pv(o, p[0], p[1], p[2], p[3], b, 1); else wgmma_pv_init(o, p[0], p[1], p[2], p[3], b, 0);
#pragma unroll
    for (int k = 1; k < 4; k++) { dadd(b, 128); wgmma_pv(o, p[4 * k], p[4 * k + 1], p[4 * k + 2], p[4 * k + 3], b, 1); }
  }
  wg_commit();
}
__device__ __forceinline__ void pack_rows(const float (&o)[64], float sc, uint32_t (&q)[32]) {
#pragma unroll
  for (int j = 0; j < 32; j++) q[j] = pack_bf16(o[2 * j] * sc, o[2 * j + 1] * sc);
}
template <int J0 = 0, int J1 = 8>
__device__ __forceinline__ void stage_rows(const Ctx& c, uint32_t tile_addr, const uint32_t (&q)[32]) {
  const int lane = c.lane, mi = lane >> 3, r8 = lane & 7;
  const uint32_t row_addr = tile_addr + (16 * c.warp + (mi & 1) * 8 + r8) * 128;
#pragma unroll
  for (int jj = J0; jj < J1; jj++)
    stsm4(row_addr + (jj >> 2) * 8192 + (((((2 * jj) & 7) + (mi >> 1)) ^ r8) << 4), q[4 * jj], q[4 * jj + 1], q[4 * jj + 2], q[4 * jj + 3]);
}
__device__ __forceinline__ void stage_rows(const Ctx& c, uint32_t tile_addr, const float (&o)[64], float sc) {
  uint32_t q[32];
  pack_rows(o, sc, q);
  stage_rows(c, tile_addr, q);
}
template <int WG, int H>
__device__ __forceinline__ void stage_out(const Ctx& c, const float (&a)[64]) {
  if (WG) { stage_t3<H, false>(c, a, 1.f); if (H) staged(c, 0); stage_t2<H>(c, a, 1.f); }
  else stage_rows(c, c.sb + QBUF_OFF + H * 16384, a, 1.f);
  if (H || !WG) staged(c, H);
}
template <int SITE>
__device__ __forceinline__ void issue_qk_rs(float (&s)[32], uint32_t (&q)[32], uint32_t dk) {
  uint64_t b = desc64(dk, dhi<SITE>(dk));
  reg_fence(q);
  wg_fence();
  wgmma_qk_rs_init(s, q[0], q[1], q[2], q[3], b, 0);
#pragma unroll
  for (int k = 1; k < 8; k++) { dadd(b, k == 4 ? 506 : 2); wgmma_qk_rs(s, q[4 * k], q[4 * k + 1], q[4 * k + 2], q[4 * k + 3], b, 1); }
  wg_commit();
}

__device__ __forceinline__ void redo_tile(const Ctx& c, uint32_t q_addr, uint32_t half, const __nv_bfloat16* kp, const __nv_bfloat16* vp,
                                          uint32_t item, int row) {
  float o[64];
  const int lane = lane_now(), g = lane >> 2, cc = lane & 3, mi = lane >> 3, r8 = lane & 7;
  const uint32_t qa = q_addr + (half == 4096 ? 8 * c.warp + r8 : 16 * c.warp + (mi & 1) * 8 + r8) * 128, swz = half == 4096 ? q3_swz(r8) : r8;
  const uint32_t* kq = reinterpret_cast<const uint32_t*>(kp + g * DH) + cc;
  const unsigned short* vq = reinterpret_cast<const unsigned short*>(vp + 2 * cc * DH) + g;
  float m0 = -INFINITY, m1 = -INFINITY, l0 = 0.f, l1 = 0.f;
#pragma unroll
  for (int i = 0; i < 64; i++) o[i] = 0.f;
#pragma unroll 1
  for (int kb = 0; kb < SK / 16; kb++) {
    float z[8] = {0.f, 0.f, 0.f, 0.f, 0.f, 0.f, 0.f, 0.f};
#pragma unroll 2
    for (int kk = 0; kk < 8; kk++) {
      uint32_t a0, a1, a2, a3;
      ldsm4(qa + (kk >> 2) * half + ((((kk & 3) * 2 + (mi >> 1)) ^ swz) << 4), a0, a1, a2, a3);
      const uint32_t* kr = kq + kb * (16 * DH / 2) + kk * 8;
      mma16816(z[0], z[1], z[2], z[3], a0, a1, a2, a3, __ldg(kr), __ldg(kr + 4));
      mma16816(z[4], z[5], z[6], z[7], a0, a1, a2, a3, __ldg(kr + 8 * DH / 2), __ldg(kr + 8 * DH / 2 + 4));
    }
    const float n0 = fmaxf(m0, quad_max(fmaxf(fmaxf(z[0], z[1]), fmaxf(z[4], z[5]))));
    const float n1 = fmaxf(m1, quad_max(fmaxf(fmaxf(z[2], z[3]), fmaxf(z[6], z[7]))));
    const float al0 = ex2(m0 - n0), al1 = ex2(m1 - n1);
    m0 = n0; m1 = n1;
#pragma unroll
    for (int i = 0; i < 8; i++) z[i] = ex2(z[i] - ((i & 2) ? n1 : n0));
    l0 = l0 * al0 + (z[0] + z[1]) + (z[4] + z[5]);
    l1 = l1 * al1 + (z[2] + z[3]) + (z[6] + z[7]);
    const uint32_t a0 = pack_bf16(z[0], z[1]), a1 = pack_bf16(z[2], z[3]), a2 = pack_bf16(z[4], z[5]), a3 = pack_bf16(z[6], z[7]);
    const unsigned short* vr = vq + kb * (16 * DH);
#pragma unroll
    for (int nb = 0; nb < 16; nb++) {
      o[4 * nb] *= al0; o[4 * nb + 1] *= al0; o[4 * nb + 2] *= al1; o[4 * nb + 3] *= al1;
      const uint32_t b0 = __ldg(vr + nb * 8) | ((uint32_t)__ldg(vr + nb * 8 + DH) << 16);
      const uint32_t b1 = __ldg(vr + nb * 8 + 8 * DH) | ((uint32_t)__ldg(vr + nb * 8 + 9 * DH) << 16);
      mma16816(o[4 * nb], o[4 * nb + 1], o[4 * nb + 2], o[4 * nb + 3], a0, a1, a2, a3, b0, b1);
    }
  }
  const char* p = o_addr(item, row, lane);
  o_emit<0>(p, o, __fdividef(1.f, quad_sum(l0)));
  o_emit<1>(half == 4096 ? p : p + 1024, o, __fdividef(1.f, quad_sum(l1)));
}

template <bool SPA, bool SPB, int SITE, int ID>
__device__ __forceinline__ void batch(const Ctx& c, float (&s)[32], const uint32_t (&qs)[32], uint32_t dq, uint32_t dk, float (&ob)[64],
                                      uint32_t (&pb)[SPB ? 8 : 16], uint32_t dv) {
  if constexpr (SPA) {
    reg_fence(pb);
    wg_fence();
    issue_pv<SPB, true, ID>(c, ob, pb, dv);
    issue_qk<SPA, false, ID>(c, s, qs, dq, dk);
  } else {
    constexpr bool EARLY = ((QK_EARLY_MASK >> (SITE + (SPB ? 2 : 0))) & 1) != 0;
    if (!EARLY) reg_fence(pb);
    wg_fence();
    issue_qk<SPA, false, ID, !SPB, SITE ? NQR : SPB ? NQR2 : NQR1>(c, s, qs, dq, dk);
    if (EARLY) { reg_fence(pb); wg_fence(); }
    issue_pv<SPB, true, ID, SPB>(c, ob, pb, dv);
  }
}

template <bool SP0>
__device__ __forceinline__ bool attention(Ctx& c, Ring& r, int unit, uint32_t& d, const float (&a0)[64], float (&o0)[64], float (&o1)[64],
                                          RowSum& st0, RowSum& st1, const Slots& h) {
  constexpr bool SP1 = false;
  if (SP0) { c.mqk = META_QK + (d >> 28); c.mpv = META_PV + (d >> 28); asm volatile("" : "+r"(c.mqk), "+r"(c.mpv)); }
  if (SP0) c.src = (c.lane & 28) | ((c.lane & 1) << 1) | ((c.lane >> 1) & 1);
  float s[32];
  uint32_t p0[SP0 ? 8 : 16], p1[16];
  const uint32_t q0a = c.sb + QBUF_OFF + (SP0 ? 3 : 0) * 16384, q1a = c.sb + QBUF_OFF + (SP0 ? 2 : 1) * 16384;
  const uint32_t dq0 = sdesc(SB0 + QBUF_OFF + (NQR >> 2) * 8192 + (NQR & 3) * 32, 0), dq1 = sdesc(SB0 + QBUF_OFF + (SP0 ? 32768 + NQR2 * 32 : 16384 + (NQR1 >> 2) * 8192 + (NQR1 & 3) * 32), 0);
  uint32_t sk = acquire(c, r, true), sv, sn;
  uint32_t qs[32], q1[32];
  float s1[32];
  if (SP0) {
    stage_t3<0, true>(c, a0, SM_C);
    stage_t2<0>(c, a0, SM_C);
    proj_end<1>(c, o0, h);
    stage_t3<1, true>(c, o0, SM_C);
    stage_t2<1>(c, o0, SM_C);
    fence_async_smem();
    bar_sync(1, LAG_BAR & 30 ? 256 : 128);
    const int g = c.lane >> 2, cc = c.lane & 3;
    const uint32_t qa = q0a + (8 * c.warp + g) * 128 + (cc & 1) * 8;
#pragma unroll
    for (int k = 0; k < 8; k++)
      asm volatile("ld.shared.v2.u32 {%0, %1}, [%2];" : "=r"(qs[2 * k]), "=r"(qs[2 * k + 1])
                   : "r"(qa + (k >> 2) * 4096 + ((((k & 3) * 2 + (cc >> 1)) ^ q3_swz(g)) << 4)) : "memory");
    TRACE(unit, 2);
    wg_fence();
    issue_qk<SP1, true, 1>(c, s1, qs, dq1 - NQR2 * 2, sdesc(SB0 + sk * SLOT, 0));
#pragma unroll
    for (int k = 0; k < NQR2; k++)
      ldsm4(q1a + (16 * c.warp + (c.lane & 15)) * 128 + (((2 * k + (c.lane >> 4)) ^ (c.lane & 7)) << 4), q1[4 * k], q1[4 * k + 1], q1[4 * k + 2], q1[4 * k + 3]);
#pragma unroll
    for (int k = 0; k < 16; k++) asm volatile("" : "+r"(qs[k])::"memory");
    wg_fence();
    issue_qk<SP0, true, 0>(c, s, qs, dq0, sdesc(SB0 + sk * SLOT, 0));
    const bool have = peek<2>(c, r);
    wg_wait<1>();
    reg_fence(s1);
    exps<SP1, true>(c, s1, p1, st1);
    sched_fence<11>(sk, p1);
    acquire2(c, r, sv, sn, __all_sync(0xffffffffu, have));
    wg_wait<0>();
    wg_fence();
    issue_pv<SP1, false, 1>(c, o1, p1, sdesc(SB0 + sv * SLOT, 8192));
    if (LAG_BAR & 1) asm volatile("bar.arrive 4, 256;" ::: "memory");
    sched_fence<12>(sk, s);
    release(c, sk);
    sk = sn;
    exps<SP0, true>(c, s, p0, st0);
    reg_fence(p0);
    wg_fence();
    issue_pv<SP0, false, 0>(c, o0, p0, sdesc(SB0 + sv * SLOT, 8192));
    issue_qk<SP0, true, 2>(c, s, qs, dq0, sdesc(SB0 + sk * SLOT, 0));
    sn = acquire(c, r);
    wg_wait<0>();
    reg_fence(s);
  } else {
    pack_rows(a0, SM_C, qs);
    stage_rows<SKIP_ST & 1 ? NQR : 0>(c, q0a, qs);
    proj_end<0>(c, o1, h);
    TRACE(unit, 2);
    float sc = SM_C;
    issue_qk_rs<0>(s, qs, sdesc(SB0 + sk * SLOT, 0));
    sched_fence<0>(sk, sc);
    if (LAG_BAR & 8) asm volatile("bar.arrive 1, 256;" ::: "memory");
    pack_rows(o1, sc, q1);
    stage_rows<SKIP_ST & 2 ? NQR1 : 0>(c, q1a, q1);
    if (LAG_BAR & 4) asm volatile("bar.arrive 1, 256;" ::: "memory");
    issue_qk_rs<1>(s1, q1, sdesc(SB0 + sk * SLOT, 0));
    if (LAG_BAR & 2) asm volatile("bar.arrive 1, 256;" ::: "memory");
    bool have = peek<2>(c, r);
    wg_wait<1>();
    reg_fence(s);
    exps<SP0, true>(c, s, p0, st0);
    sched_fence<1>(sk, p0);
    if (LAG_BAR & 16) asm volatile("bar.arrive 1, 256;" ::: "memory");
    acquire2(c, r, sv, sn, __all_sync(0xffffffffu, have));
    wg_wait<0>();
    reg_fence(s1);
    fence_async_smem();
    __syncwarp();
    wg_fence();
    issue_qk<SP0, false, 2, true, NQR>(c, s, qs, dq0, sdesc(SB0 + sn * SLOT, 0));
    issue_pv<SP0, false, 0>(c, o0, p0, sdesc(SB0 + sv * SLOT, 8192));
    sched_fence<2>(sk, s1);
    release(c, sk);
    have = peek<1>(c, r);
    sk = sn;
    exps<SP1, true>(c, s1, p1, st1);
    reg_fence(p1);
    wg_fence();
    issue_pv<SP1, false, 1>(c, o1, p1, sdesc(SB0 + sv * SLOT, 8192));
    sn = acquire(c, r, __all_sync(0xffffffffu, have));
    if (LAG_BAR & 1) bar_sync(4, 256);
    wg_wait<1>();
    reg_fence(s);
  }
  TRACE_IN(unit, 4);
  T2C(unit, 51);
#pragma unroll 1
  for (int j = 1; j < 15; j++) {
    const uint32_t sv_prev = sv, sk_prev = sk;
    sv = sn;
    const uint32_t dv = sdesc(SB0 + sv * SLOT, 8192);
    reg_fence(p0);
    exps<SP0, false>(c, s, p0, st0);
    batch<SP1, SP0, 0, 3>(c, s, q1, dq1, sdesc(SB0 + sk * SLOT, 0), o0, p0, dv);
    sk = acquire(c, r);
    wg_wait<1>();
    reg_fence(s); reg_fence(p1);
    release(c, sv_prev); release(c, sk_prev);
    exps<SP1, false>(c, s, p1, st1);
    batch<SP0, SP1, 1, 4>(c, s, qs, dq0, sdesc(SB0 + sk * SLOT, 0), o1, p1, dv);
    sn = acquire(c, r);
    if (SP0) wg_wait<0>(); else wg_wait<1>();
    reg_fence(s);
  }
  TRACE_IN(unit, 5);
  T2C(unit + 1, 52);
  const uint32_t sv_prev = sv;
  sv = sn;
  const uint32_t dv = sdesc(SB0 + sv * SLOT, 8192);
  reg_fence(p0);
  exps<SP0, false>(c, s, p0, st0);
  batch<SP1, SP0, 0, 5>(c, s, q1, dq1, sdesc(SB0 + sk * SLOT, 0), o0, p0, dv);
  asm volatile("ld.volatile.shared.u32 %0, [%1];" : "=r"(d) : "r"(c.sb + DESC_OFF + ((unit + 1) & 3) * 4) : "memory");
  const bool have = peek<2 + SP0>(c, r);
  wg_wait<1>();
  reg_fence(s); reg_fence(p1);
  release(c, sv_prev); release(c, sk);
  exps<SP1, false>(c, s, p1, st1);
  reg_fence(p1);
  wg_fence();
  issue_pv<SP1, true, 2>(c, o1, p1, dv);
  if (SP0) sched_fence<6>(sk, st0.l0, st1.l0, st1.l1); else sched_fence<5>(sk, st0.l0, st0.l1, st1.l0, st1.l1);
  c.lane = c.lane0 + (sk >> 5);
  const bool bad = finish_sums<SP0>(st0) | finish_sums<SP1>(st1);
  uint32_t any;
  asm volatile("{\n.reg .pred p, q;\nsetp.ne.u32 p, %1, 0;\nbar.red.or.pred q, %2, 128, p;\nselp.u32 %0, 1, 0, q;\n}"
               : "=r"(any) : "r"((uint32_t)bad), "n"(2 + SP0) : "memory");
  any = __any_sync(0xffffffffu, any);
  d = __shfl_sync(0xffffffffu, d, 0);
  if (d < (2u << 30) && !__all_sync(0xffffffffu, have)) { Ring t = r; Slots u; begin_acquire<SP0>(c, t, u, true); }
  wg_wait<0>();
  reg_fence(o0); reg_fence(o1);
  release(c, sv);
  if (!SP0 && SKIP_ST && __builtin_expect(any, 0)) {
    stage_rows<0, SKIP_ST & 1 ? NQR : 0>(c, q0a, qs); stage_rows<0, SKIP_ST & 2 ? NQR1 : 0>(c, q1a, q1);
    __syncwarp();
  }
  return any;
}

template <int WG>
__device__ __forceinline__ void consumer(Ctx c, const __nv_bfloat16* const* kv) {
  asm volatile("setmaxnreg.inc.sync.aligned.u32 %0;" ::"n"(WG ? REG_C : 504 - REG_C - REG_P));
  c.wg = WG;
  Ring r{0, 0, 0};
  float a0[64], a1[64], o1[64];
  Slots h;
  RowSum inv0, inv1;
  uint32_t d = c_sched.queue[blockIdx.x] * 1025, dc = 0, sw;
  int i = 0, nq;
begin:
  sw = d & (1u << 30);
  proj_begin<WG>(c, r, a0, h, true, sw);
begin1:
  proj_half<WG, true, 1>(c, a1, h.w, h.x, sw);
  nq = 0;
#pragma unroll
  for (int k = 0; k < 64; k++) asm volatile("" : "=f"(o1[k]));
  asm volatile("" : "=f"(inv1.l0), "=f"(inv1.l1));
  while (true) {
    TRACE(i, 0); TRACE(i, 6);
    proj_main<WG>(c, r, a0, a1, h, d >> 30 ? ((d >> 16) & 63) + 1 : DM / 64, sw, i, dc, nq, o1, inv1);
    dc = d;
    TRACE(i, 1);
    if (d >> 30) goto out_tile;
    wg_wait<1>();
    acc_fence<WG>(a0);
    if (WG ? attention<WG>(c, r, i, d, a0, a1, o1, inv0, inv1, h) : attention<WG>(c, r, i, d, a0, o1, a1, inv1, inv0, h)) goto redo;
    if (d >= (2u << 30)) break;
    sw = d & (1u << 30);
    proj_begin<WG>(c, r, a0, h, false, sw);
    release_q<WG>(c);
    if (WG) sched_fence<8>(h.w, inv0.l0); else sched_fence<7>(h.w, inv0.l0, inv0.l1);
    o_first<WG>(c, dc, a1, inv0);
    sched_fence<9>(h.w, inv1.l0);
    proj_half<WG, true, 1>(c, a1, h.w, h.x, sw);
    nq = O_STEPS;
    TRACE(i, 3); TRACE(i, 7);
    i++;
  }
  release_q<WG>(c);
  o_first<WG>(c, dc, a1, inv0);
#pragma unroll
  for (int k = 1; k <= O_STEPS; k++) o_second<WG>(c, dc, k, o1, inv1);
next:
  TRACE(i, 3); TRACE(i, 7);
  if ((d >> 30) != 2) {
    i++;
    r.uniform();
    goto begin;
  }
  trace_dump(c);
  return;
out_tile:
  if (d & 96) goto finish;
  d = get_desc(c, i + 1);
  wg_wait<1>();
  acc_fence<WG>(a0);
  TRACE_O(0);
  stage_out<WG, 0>(c, a0);
  TRACE_O(1);
  proj_end<WG>(c, a1, h);
  TRACE_O(2);
  if (!EARLY_BEGIN || d >= (2u << 30)) { stage_out<WG, 1>(c, a1); TRACE(i, 2); goto next; }
  sw = d & (1u << 30);
  proj_begin<WG>(c, r, a0, h, true, sw);
  TRACE_O(3);
  stage_out<WG, 1>(c, a1);
  TRACE(i, 2); TRACE(i, 3); TRACE(i, 7);
  i++;
  goto begin1;
finish:
  {
    uint32_t q[32];
#pragma unroll 1
    for (int k = (d >> 5) & 3; k > 1; k--) {
      wg_wait<0>();
      acc_fence<WG>(a0); acc_fence<WG>(a1);
      if (k == ((d >> 5) & 3)) { release(c, h.x); release(c, h.w); }
      load_part<WG, 0>(c, r, q); add_part<WG>(c, q, a0);
      load_part<WG, 1>(c, r, q); add_part<WG>(c, q, a1);
#pragma unroll
      for (int t = 0; t < 4; t++) { release(c, r.slot); r.next(); }
    }
    load_part<WG, 0>(c, r, q);
    wg_wait<1>();
    acc_fence<WG>(a0);
    TRACE_O(0);
    add_part<WG>(c, q, a0);
    stage_out<WG, 0>(c, a0);
    TRACE_O(1);
    load_part<WG, 1>(c, r, q);
    wg_wait<0>();
    acc_fence<WG>(a1);
    TRACE_O(2);
    add_part<WG>(c, q, a1);
    stage_out<WG, 1>(c, a1);
    TRACE(i, 2); TRACE(i, 3); TRACE(i, 7);
    trace_dump(c);
    return;
  }
redo:
  {
    const size_t hoff = (size_t)(dc & 511) * (SK * DH);
    const int br = (dc >> 9) & 1;
#pragma unroll 1
    for (int part = 0; part < 2; part++) {
      const int t = WG ? 3 - part : part;
      redo_tile(c, c.sb + QBUF_OFF + t * 16384, t == 3 ? 4096 : 8192, kv[br] + hoff, kv[2 + br] + hoff, dc,
                t * 64 + (t == 3 ? 8 : 16) * c.warp);
    }
    o_done(c);
    release_q<WG>(c);
  }
  goto next;
}

template <bool SIMPLE>
__global__ void __launch_bounds__(384, 1) mha_fused_kernel(const __grid_constant__ Params P) {
  extern __shared__ __align__(1024) uint8_t smem_raw[];
  const uint32_t sbase = smem_u32(smem_raw);
  const int tid = threadIdx.x;
  const int wg = __shfl_sync(0xffffffffu, tid >> 7, 0);
  const int warp = __shfl_sync(0xffffffffu, (tid >> 5) & 3, 0);
  const int lane = tid & 31;
  const int cta = blockIdx.x;
  constexpr bool PAIR = !SIMPLE && CLUSTER;

  if (tid == 0) T3(15, 0);
  if ((sbase & 0xffffff) != SB0) __trap();
  {
    const int wi = wg * 4 + warp;
    asm volatile(ELECT "prefetch.tensormap [%0];\n}" ::"l"(&P.x[0][0] + wi) : "memory");
#pragma unroll
    for (int k = 0; k < 5; k++) {
      const int b = min(BAR_OFF + (wi * 5 + k) * 8, DESC_OFF - 8);
      asm volatile(ELECT "mbarrier.init.shared::cta.b64 [%0], %1;\n}"
                   ::"r"(sbase + b), "r"(b < BAR_EMPTY || b >= BAR_DESC ? 1 : b >= BAR_STG && b < BAR_OUT ? 4 : 8) : "memory");
    }
    asm volatile("fence.mbarrier_init.release.cluster;" ::: "memory");
    if (wi < 6) asm volatile(ELECT "prefetch.tensormap [%0];\n}" ::"l"(&P.x[0][0] + 12 + wi) : "memory");
  }
  if (PAIR) asm volatile("barrier.cluster.arrive.aligned;\nbarrier.cluster.wait.aligned;" ::: "memory"); else __syncthreads();

  if (wg == 2) {
    asm volatile("setmaxnreg.dec.sync.aligned.u32 %0;" ::"n"(REG_P));
    if (warp == 1) {
      const uint32_t qb = sbase + QBUF_OFF;
      const uint32_t ep = __shfl_sync(0xffffffffu, *(volatile unsigned*)&g_epoch + 1, 0);
      asm volatile("st.volatile.shared.u32 [%0], %1;" ::"r"(sbase + EPOCH_OFF), "r"(ep) : "memory");
      uint32_t dc = c_sched.queue[cta], qi = 0, piece = 0, na = 0;
      TTAIL(0);
      for (int i = 0; (dc >> 30) != 2; i++) {
        if (!(dc >> 30) && o_reuse<SIMPLE>((dc >> 5) & 31)) {
          const unsigned* rd = &g_rd[0][0] + ((dc & 1023) >> 2) - OR * 8;
          for (uint32_t n = 0; !__all_sync(0xffffffffu, reached(rd, ep * 5)); __nanosleep(300)) if (++n > (1u << 22)) __trap();
        }
        mbar_wait_w(sbase + BAR_GO, i & 1);
        if (piece == 0) {
          if (PAIR && (cta & 1)) {
            asm volatile(ELECT EXPECT("%0", "4") "mbarrier.arrive.shared::cluster.b64 _, [%1];\n}" ::"r"(sbase + BAR_MAIL), "r"(peer(sbase + BAR_MAIL)) : "memory");
            mbar_wait_w(sbase + BAR_MAIL, i & 1);
            qi = lds(sbase + EPOCH_OFF + 8);
          } else if (lane == 0) {
            qi = atomicAdd(&g_next, PAIR ? 2 : 1);
            if (qi == (SIMPLE ? Q_ALL : Q_RANGES) - (PAIR ? 2 : 1)) { g_next = 0; g_epoch = ep; }
          }
          qi = __shfl_sync(0xffffffffu, qi, 0);
          if (PAIR && !(cta & 1)) {
            mbar_wait_w(sbase + BAR_MAIL, i & 1);
            asm volatile(ELECT "st.async.shared::cluster.mbarrier::complete_tx::bytes.u32 [%0], %1, [%2];\n}"
                         ::"r"(peer(sbase + EPOCH_OFF + 8)), "r"(qi + 1), "r"(peer(sbase + BAR_MAIL)) : "memory");
          }
          qi += SIMPLE ? gridDim.x : NCTA;
        }
        uint32_t d;
        if (qi < (SIMPLE ? Q_ALL : Q_RANGES)) { d = c_sched.queue[qi]; if (d & 0x8000) d ^= (1u << 30) | (63u << 16) | 0x8000; else d |= o_slot<SIMPLE>(d >> 5) << 15 | (d & 31) << 10; }
        else if (SIMPLE) d = 2u << 30;
        else { const uint32_t e = qi - Q_RANGES, g = e / 5; d = c_sched.piece[g][piece++] | (g & 1 ? g * 5 + 4 - e : e - g * 5) << 8; }
        if ((d >> 30) == 1) {
          const uint32_t k0 = (d >> 22) & 63;
          const uint32_t run = __ffs(__ballot_sync(0xffffffffu, !reached(&g_cnt[d & 31][lane & 7], ep * 4)) & (0xffu << (k0 >> 3))) - 1;
          if (run <= (k0 + ((d >> 16) & 63)) >> 3) d |= run <= (k0 + O_STEPS) >> 3 ? (2u << 30) | 128 : 128;
        }
        asm volatile("st.volatile.shared.u32 [%0], %1;" ::"r"(sbase + EPOCH_OFF + 4), "r"(qi) : "memory");
        asm volatile("st.volatile.shared.u32 [%0], %1;" ::"r"(sbase + DESC_OFF + ((i + 1) & 3) * 4), "r"(d) : "memory");
        __syncwarp();
        mbar_arrive_warp(sbase + BAR_DESC);
        const Work w = decode(dc);
        dc = d;
        if (w.kind == 0) {
          mbar_wait_w(sbase + BAR_OUT, na++ & 1);
          TTAIL(1);
          T3(i, 0); T3(i, 1);
          asm volatile(ELECT "red.release.gpu.global.add.u32 [%0], 1;\n}" ::"l"(&g_cnt[w.beta][w.sub >> 2]) : "memory");
          T3(i, 2);
          TTAIL(2);
          continue;
        }
        const bool fin = w.mode != 1;
        uint64_t pol, pol2;
        asm volatile("createpolicy.fractional.L2::evict_first.b64 %0, 1.0;" : "=l"(pol));
        asm volatile("createpolicy.fractional.L2::evict_normal.b64 %0, 1.0;" : "=l"(pol2));
        if (!fin) pol = pol2;
        const CUtensorMap* m = fin ? P.out_st : P.o_st;
        const int c1 = fin ? (w.beta & 15) * SQ : 0;
        const int c2 = fin ? (w.beta >> 4) * (DM / 64) + w.sub * 2 : NBETA * 64 + w.range * 2;
        uint32_t pend = 0;
#pragma unroll 1
        for (int e = 0; e < 4; e++) {
          const int t = (ST_ORDER >> (4 * e)) & 3;
          mbar_wait_w(sbase + BAR_STG + (t ^ (t >> 1)) * 8, (i - na) & 1);
          tma_st3_hint_w(m + (t == 3), qb + t * 16384, 0, c1 + t * 64, c2, pol);
          bulk_commit();
          T2P(i + 1, 5, 2 * e);
          if (pend) {
            bulk_wait_read<1>();
            mbar_arrive8_w(pend);
            T2P(i + 1, 5, 2 * e - 1);
          }
          pend = sbase + BAR_EMPTY + (NS + t) * 8;
          if ((ST_NOW >> e) & 1) {
            bulk_wait_read<0>();
            mbar_arrive8_w(pend);
            pend = 0;
            T2P(i + 1, 5, 2 * e + 1);
          }
        }
        if (w.beta < N_EARLY) asm volatile(ELECT "red.relaxed.gpu.global.add.u32 [%0], 1;\n}" ::"l"(&g_rd[w.beta][7]) : "memory");
        T3(i, 0);
        if (piece >= 2) TTAIL(piece * 2 - 1);
        asm volatile("cp.async.bulk.wait_group 0;" ::: "memory");
        T3(i, 1);
        if (w.mode == 1) asm volatile(ELECT "st.release.gpu.global.u32 [%0], %1;\n}" ::"l"(&g_flag[w.range]), "r"(ep) : "memory");
        T3(i, 2);
        if (piece >= 2) TTAIL(piece * 2);
      }
      T3(15, 1);
    } else
    if (warp == 0) {
      Ring r{0, 1, 3};
      uint32_t d = c_sched.queue[cta];
      for (int i = 0;; i++) {
        const Work w = decode(d);
        if (w.kind == 2) break;
        const CUtensorMap* m = w.kind == 0 ? &P.wq[w.beta >> 4] : &P.wo[w.beta >> 4];
        for (int ks = 0; ks < w.nsteps; ks++) {
          const uint32_t b = borrow(ks, w.nsteps);
          r.next_if(b == 2);
          const uint32_t bar = sbase + BAR_FULL + r.slot * 8;
          mbar_wait_w(bar + (BAR_EMPTY - BAR_FULL), r.phase);
          if (w.kind == 0) tma_ld3_w(sbase + r.slot * SLOT, m, 0, ks * 64, w.sub * 2, bar, 16384);
          else tma_ld_wo_w(sbase + r.slot * SLOT, m, w.sub * 128, (w.k0 + ks) * 2, bar);
          if (w.kind != 0 && w.beta < N_EARLY && (ks & 7) == 5 && ks > 5)
            asm volatile(ELECT "red.relaxed.gpu.global.add.u32 [%0], 1;\n}" ::"l"(&g_rd[w.beta][(ks >> 3) - 1]) : "memory");
          if (ks < 10) T2P(i, 2, ks);
          if (w.kind != 0 && ks == max(w.nsteps - GO_P, 4)) mbar_arrive_warp(sbase + BAR_GO);
          r.next(); r.next_if(b == 2);
        }
        if (w.kind == 0) {
          r.phase ^= 1; r.next(); r.next();
        } else if (w.mode == 2) {
          for (int k = 1; k <= ((d >> 5) & 3); k++) {
            if (k == 1) TTAIL(9);
            wait_count(&g_flag[w.range + 5 * k], lds(sbase + EPOCH_OFF));
            TTAIL(10);
            asm volatile("fence.proxy.async.global;" ::: "memory");
#pragma unroll 1
            for (int t = 0; t < 4; t++) {
              mbar_wait_w(sbase + BAR_EMPTY + r.slot * 8, r.phase);
              tma_ld3_w(sbase + r.slot * SLOT, &P.o_st[t == 3], 0, t * 64, NBETA * 64 + (w.range + 5 * k) * 2, sbase + BAR_FULL + r.slot * 8,
                        t == 3 ? 8192 : 16384);
              r.next();
            }
          }
        }
        mbar_wait_w(sbase + BAR_DESC, i & 1);
        d = __shfl_sync(0xffffffffu, lds(sbase + DESC_OFF + ((i + 1) & 3) * 4), 0);
      }
    } else {
      const int hi = warp - 2;
      uint64_t pol_stream;
      uint32_t rdy = 0;
      asm volatile("createpolicy.fractional.L2::evict_first.b64 %0, 1.0;" : "=l"(pol_stream));
      Ring r{0, 1, 3};
      uint32_t d = c_sched.queue[cta];
      for (int i = 0;; i++) {
        const Work w = decode(d);
        if (w.kind == 2) break;
        const CUtensorMap* m = w.kind == 0 ? &P.x[hi][w.beta >> 4] : &P.o_ld[hi];
        int c1 = (w.kind == 0 ? (w.beta & 15) : o_slot<SIMPLE>(w.beta) * 64 + w.k0) * SQ + hi * 128;
        int k_wait = -1;
        const bool both = PAIR && (w.kind == 0 || w.sub != 4), mine = !both || hi == (cta & 1);
        if (w.kind != 0 && mine) {
          if (d & 128) k_wait = d >= (3u << 30) ? 0 : 8 - (w.k0 & 7);
          asm volatile("fence.proxy.async.global;" ::: "memory");
        }
        const int rank = i == 0 ? cta : __shfl_sync(0xffffffffu, lds(sbase + EPOCH_OFF + 4), 0) - NCTA;
        for (int ks = 0; ks < w.nsteps; ks++) {
          if (ks == k_wait) {
            wait_count(&g_cnt[d & 31][(w.k0 + ks) >> 3], lds(sbase + EPOCH_OFF) * 4);
            asm volatile("fence.proxy.async.global;" ::: "memory");
            k_wait = ((w.k0 + ks) | 7) + 1 - w.k0;
          }
          const uint32_t b = borrow(ks, w.nsteps);
          const bool bo = b != 2;
          r.next_if(hi && !bo); r.next_if(hi && !bo);
          const uint32_t sl = bo ? NS + (b ^ (3 * hi)) : r.slot, bar = sbase + BAR_FULL + sl * 8;
          mbar_wait_w(bar + (BAR_EMPTY - BAR_FULL), bo ? (r.xp >> b) & 1 : r.phase);
          const uint32_t bytes = hi ? 96 * 128 : 128 * 128;
          if (!mine) {
            asm volatile(ELECT EXPECT("%0", "%2") "mbarrier.arrive.shared::cluster.b64 _, [%1];\n}"
                         ::"r"(bar), "r"(peer(bar + (BAR_RDY - BAR_FULL))), "r"(bytes) : "memory");
          } else if (both) {
            mbar_wait_w(bar + (BAR_RDY - BAR_FULL), (rdy >> sl) & 1);
            rdy ^= 1 << sl;
            if (w.kind == 0) tma_ld2_both_w(sbase + sl * SLOT, m, ks * 64, c1, bar, bytes);
            else tma_ld2_both_hint_w(sbase + sl * SLOT, m, 0, c1, bar, bytes, pol_stream);
          } else if (!PAIR && w.kind == 0) tma_ld2_w(sbase + sl * SLOT, m, ks * 64, c1, bar, bytes);
          else tma_ld2_hint_w(sbase + sl * SLOT, m, 0, c1, bar, bytes, pol_stream);
          if (w.kind != 0) c1 += SQ;
          if (i == 0 && ks == PF_STEP)
            asm volatile(ELECT "cp.async.bulk.prefetch.tensor.3d.L2.global.L2::cache_hint [%0, {0, %1, 0}], %2;\n}"
                         ::"l"(&P.kv[hi][0]), "r"(d * SK), "l"(pol_stream) : "memory");
          if (ks < 10) T2P(i, 3 + hi, ks);
          if (!hi && w.kind != 0 && !(ks & 3)) TCLK(i * 16 + (ks >> 2));
          r.next(); r.next_if(!hi && !bo); r.next_if(!hi && !bo);
          r.xp ^= 1 << b;
        }
        r.xp ^= 3;
        if (w.kind == 0) {
          m = &P.kv[hi][w.beta >> 4];
          c1 = (d & 511) * SK;
          for (int j = 0; j < 16; j++) {
            if (hi) r.next();
            const uint32_t bar = sbase + BAR_FULL + r.slot * 8;
            const bool tight = i < KV_WIN_UNITS && j < KV_WIN_TILES + ((KV_WIN_RAMP * rank) >> 5);
            {
              const int s2 = (int)r.slot - (tight ? 2 : KV_WIN_D);
              mbar_wait_w(sbase + BAR_FULL + (s2 < 0 ? s2 + NS : s2) * 8, s2 < 0 ? r.phase : r.phase ^ 1);
            }
            if (j == 15 && hi) mbar_wait_w(sbase + BAR_DESC, i & 1);
            mbar_wait_w(sbase + BAR_EMPTY + r.slot * 8, r.phase);
            tma_ld3_hint_w(sbase + r.slot * SLOT, m, 0, c1, 0, bar, pol_stream);
            T2P(i, 3 + hi, 16 + j);
            if (!hi) TCLK(i * 16 + j);
            if (j == 14 && !hi) mbar_arrive_warp(sbase + BAR_GO);
            c1 += 64;
            r.next();
            if (!hi) r.next();
          }
        }
        mbar_wait_w(sbase + BAR_DESC, i & 1);
        d = __shfl_sync(0xffffffffu, lds(sbase + DESC_OFF + ((i + 1) & 3) * 4), 0);
      }
    }
  } else {
    Ctx c;
    c.sb = sbase; c.wg = wg; c.warp = warp; c.src = 0; c.mqk = 0; c.mpv = 0; c.lead = lane == 0; c.lane0 = c.lane = lane;
    if (wg == 0) consumer<0>(c, P.kp); else consumer<1>(c, P.kp);
  }
}

typedef CUresult (*EncodeFn)(CUtensorMap*, CUtensorMapDataType, cuuint32_t, void*, const cuuint64_t*, const cuuint64_t*,
                             const cuuint32_t*, const cuuint32_t*, CUtensorMapInterleave, CUtensorMapSwizzle,
                             CUtensorMapL2promotion, CUtensorMapFloatOOBfill);

void make_map(EncodeFn enc, CUtensorMap* m, const void* ptr, int rank, const cuuint64_t* dims, const cuuint64_t* strides,
              const cuuint32_t* box, int promo = 2, CUtensorMapSwizzle swz = CU_TENSOR_MAP_SWIZZLE_128B) {
  cuuint32_t es[5] = {1, 1, 1, 1, 1};
  enc(m, CU_TENSOR_MAP_DATA_TYPE_BFLOAT16, rank, const_cast<void*>(ptr), dims, strides, box, es,
      CU_TENSOR_MAP_INTERLEAVE_NONE, swz, promo == 2 ? CU_TENSOR_MAP_L2_PROMOTION_L2_256B : promo == 1 ? CU_TENSOR_MAP_L2_PROMOTION_L2_128B : CU_TENSOR_MAP_L2_PROMOTION_NONE,
      CU_TENSOR_MAP_FLOAT_OOB_FILL_NONE);
}

}

extern "C" void kernel_launch(void* const* d_in, const int* in_sizes, int n_in, void* d_out, int out_size) {
  (void)in_sizes; (void)n_in; (void)out_size;
  static EncodeFn enc = nullptr;
  static void* o_ptr = nullptr;
  static int n_sm = 0;
  cudaLaunchAttribute at;
  at.id = cudaLaunchAttributeClusterDimension;
  at.val.clusterDim.x = CLUSTER ? 2 : 1; at.val.clusterDim.y = 1; at.val.clusterDim.z = 1;
  cudaLaunchConfig_t cfg = {};
  cfg.gridDim = dim3(NCTA); cfg.blockDim = dim3(384); cfg.dynamicSmemBytes = SMEM_BYTES; cfg.attrs = &at; cfg.numAttrs = 1;
  if (!enc) {
    void* fn = nullptr;
    cudaDriverEntryPointQueryResult qr;
    cudaGetDriverEntryPoint("cuTensorMapEncodeTiled", &fn, cudaEnableDefault, &qr);
    enc = (EncodeFn)fn;
    cudaGetSymbolAddress(&o_ptr, g_o);
    cudaFuncSetAttribute(mha_fused_kernel<false>, cudaFuncAttributeMaxDynamicSharedMemorySize, SMEM_BYTES);
    cudaFuncSetAttribute(mha_fused_kernel<true>, cudaFuncAttributeMaxDynamicSharedMemorySize, SMEM_BYTES);
    int dev = 0;
    cudaGetDevice(&dev);
    cudaDeviceGetAttribute(&n_sm, cudaDevAttrMultiProcessorCount, dev);
    int n_cl = 0;
    cudaOccupancyMaxActiveClusters(&n_cl, mha_fused_kernel<false>, &cfg);
    if (n_cl * (CLUSTER ? 2 : 1) < NCTA && n_sm >= NCTA) n_sm = NCTA - 1;
  }
  Params P;
  for (int br = 0; br < 2; br++) {
    const void* x = d_in[br * 5 + 0]; const void* kc = d_in[br * 5 + 1]; const void* vc = d_in[br * 5 + 2];
    const void* wq = d_in[br * 5 + 3]; const void* wo = d_in[br * 5 + 4];
    { cuuint64_t d[2] = {DM, (cuuint64_t)NB * SQ}, s[1] = {DM * 2}; cuuint32_t b[2] = {64, 128}, b2[2] = {64, 96};
      make_map(enc, &P.x[0][br], x, 2, d, s, b, PR_X); make_map(enc, &P.x[1][br], x, 2, d, s, b2, PR_X); }
    { cuuint64_t d[3] = {64, DM, HD / 64}, s[2] = {HD * 2, 128}; cuuint32_t b[3] = {64, 64, 2}; make_map(enc, &P.wq[br], wq, 3, d, s, b, PR_W); }
    { cuuint64_t d[5] = {DM, 2, 4, 4, HD / 32}, s[4] = {DM * 2, 8 * DM * 2, 2 * DM * 2, 32 * DM * 2}; cuuint32_t b[5] = {64, 2, 4, 4, 2};
      make_map(enc, &P.wo[br], wo, 5, d, s, b, PR_W); }
    { cuuint64_t d[3] = {64, (cuuint64_t)NB * NH * SK, 2}, s[2] = {DH * 2, 128}; cuuint32_t b[3] = {64, 64, 2};
      make_map(enc, &P.kv[0][br], kc, 3, d, s, b, PR_KV); make_map(enc, &P.kv[1][br], vc, 3, d, s, b, PR_KV); }
    P.kp[br] = (const __nv_bfloat16*)kc; P.vp[br] = (const __nv_bfloat16*)vc;

  }
  { cuuint64_t d[2] = {64, (cuuint64_t)NBETA * 64 * SQ}, s[1] = {128}; cuuint32_t b[2] = {64, 128}, b2[2] = {64, 96};
    make_map(enc, &P.o_ld[0], o_ptr, 2, d, s, b, 2, CU_TENSOR_MAP_SWIZZLE_NONE); make_map(enc, &P.o_ld[1], o_ptr, 2, d, s, b2, 2, CU_TENSOR_MAP_SWIZZLE_NONE); }
  { cuuint64_t d[3] = {64, SQ, O_BLOCKS}, s[2] = {128, SQ * 128}; cuuint32_t b[3] = {64, 64, 2}, b2[3] = {64, 32, 2};
    make_map(enc, &P.o_st[0], o_ptr, 3, d, s, b); make_map(enc, &P.o_st[1], o_ptr, 3, d, s, b2); }
  { cuuint64_t d[3] = {64, (cuuint64_t)NB * SQ, 2 * DM / 64}, s[2] = {2 * DM * 2, 128}; cuuint32_t b[3] = {64, 64, 2}, b2[3] = {64, 32, 2};
    make_map(enc, &P.out_st[0], d_out, 3, d, s, b); make_map(enc, &P.out_st[1], d_out, 3, d, s, b2); }
  if (n_sm >= NCTA) cudaLaunchKernelEx(&cfg, mha_fused_kernel<false>, P);
  else mha_fused_kernel<true><<<n_sm, 384, SMEM_BYTES>>>(P);
}
```

```cpp
#include <cuda_runtime.h>
#include <cuda_bf16.h>
#include <cuda.h>
#include <stdint.h>
#include <stdlib.h>

namespace {

__device__ __forceinline__ void wgmma_proj(float (&d)[64], uint64_t da, uint64_t db, int scaleD) {
  asm volatile("{\n.reg .pred p;\nsetp.ne.b32 p, %66, 0;\n"
      "wgmma.mma_async.sync.aligned.m64n128k16.f32.bf16.bf16 "
      "{%0, %1, %2, %3, %4, %5, %6, %7, %8, %9, %10, %11, %12, %13, %14, %15, %16, %17, %18, %19, %20, %21, %22, %23, %24, %25, %26, %27, %28, %29, %30, "
      "%31, %32, %33, %34, %35, %36, %37, %38, %39, %40, %41, %42, %43, %44, %45, %46, %47, %48, %49, %50, %51, %52, %53, %54, %55, %56, %57, %58, %59, %60, "
      "%61, %62, %63}, "
      "%64, %65, p, 1, 1, 0, 1;\n}\n"
      : "+f"(d[0]), "+f"(d[1]), "+f"(d[2]), "+f"(d[3]), "+f"(d[4]), "+f"(d[5]), "+f"(d[6]), "+f"(d[7]), "+f"(d[8]), "+f"(d[9]), "+f"(d[10]), "+f"(d[11]),
        "+f"(d[12]), "+f"(d[13]), "+f"(d[14]), "+f"(d[15]), "+f"(d[16]), "+f"(d[17]), "+f"(d[18]), "+f"(d[19]), "+f"(d[20]), "+f"(d[21]), "+f"(d[22]),
        "+f"(d[23]), "+f"(d[24]), "+f"(d[25]), "+f"(d[26]), "+f"(d[27]), "+f"(d[28]), "+f"(d[29]), "+f"(d[30]), "+f"(d[31]), "+f"(d[32]), "+f"(d[33]),
        "+f"(d[34]), "+f"(d[35]), "+f"(d[36]), "+f"(d[37]), "+f"(d[38]), "+f"(d[39]), "+f"(d[40]), "+f"(d[41]), "+f"(d[42]), "+f"(d[43]), "+f"(d[44]),
        "+f"(d[45]), "+f"(d[46]), "+f"(d[47]), "+f"(d[48]), "+f"(d[49]), "+f"(d[50]), "+f"(d[51]), "+f"(d[52]), "+f"(d[53]), "+f"(d[54]), "+f"(d[55]),
        "+f"(d[56]), "+f"(d[57]), "+f"(d[58]), "+f"(d[59]), "+f"(d[60]), "+f"(d[61]), "+f"(d[62]), "+f"(d[63])
      : "l"(da), "l"(db), "r"(scaleD));
}
__device__ __forceinline__ void wgmma_proj96(float (&d)[64], uint64_t da, uint64_t db, int scaleD) {
  asm volatile("{\n.reg .pred p;\nsetp.ne.b32 p, %50, 0;\n"
      "wgmma.mma_async.sync.aligned.m64n96k16.f32.bf16.bf16 "
      "{%0, %1, %2, %3, %4, %5, %6, %7, %8, %9, %10, %11, %12, %13, %14, %15, %16, %17, %18, %19, %20, %21, %22, %23, %24, %25, %26, %27, %28, %29, %30, "
      "%31, %32, %33, %34, %35, %36, %37, %38, %39, %40, %41, %42, %43, %44, %45, %46, %47}, "
      "%48, %49, p, 1, 1, 1, 0;\n}\n"
      : "+f"(d[0]), "+f"(d[1]), "+f"(d[2]), "+f"(d[3]), "+f"(d[4]), "+f"(d[5]), "+f"(d[6]), "+f"(d[7]), "+f"(d[8]), "+f"(d[9]), "+f"(d[10]), "+f"(d[11]),
        "+f"(d[12]), "+f"(d[13]), "+f"(d[14]), "+f"(d[15]), "+f"(d[16]), "+f"(d[17]), "+f"(d[18]), "+f"(d[19]), "+f"(d[20]), "+f"(d[21]), "+f"(d[22]),
        "+f"(d[23]), "+f"(d[24]), "+f"(d[25]), "+f"(d[26]), "+f"(d[27]), "+f"(d[28]), "+f"(d[29]), "+f"(d[30]), "+f"(d[31]), "+f"(d[32]), "+f"(d[33]),
        "+f"(d[34]), "+f"(d[35]), "+f"(d[36]), "+f"(d[37]), "+f"(d[38]), "+f"(d[39]), "+f"(d[40]), "+f"(d[41]), "+f"(d[42]), "+f"(d[43]), "+f"(d[44]),
        "+f"(d[45]), "+f"(d[46]), "+f"(d[47])
      : "l"(da), "l"(db), "r"(scaleD));
}
__device__ __forceinline__ void wgmma_qk(float (&d)[32], uint64_t da, uint64_t db, int scaleD) {
  asm volatile("{\n.reg .pred p;\nsetp.ne.b32 p, %34, 0;\n"
      "wgmma.mma_async.sync.aligned.m64n64k16.f32.bf16.bf16 "
      "{%0, %1, %2, %3, %4, %5, %6, %7, %8, %9, %10, %11, %12, %13, %14, %15, %16, %17, %18, %19, %20, %21, %22, %23, %24, %25, %26, %27, %28, %29, %30, "
      "%31}, "
      "%32, %33, p, 1, 1, 0, 0;\n}\n"
      : "+f"(d[0]), "+f"(d[1]), "+f"(d[2]), "+f"(d[3]), "+f"(d[4]), "+f"(d[5]), "+f"(d[6]), "+f"(d[7]), "+f"(d[8]), "+f"(d[9]), "+f"(d[10]), "+f"(d[11]),
        "+f"(d[12]), "+f"(d[13]), "+f"(d[14]), "+f"(d[15]), "+f"(d[16]), "+f"(d[17]), "+f"(d[18]), "+f"(d[19]), "+f"(d[20]), "+f"(d[21]), "+f"(d[22]),
        "+f"(d[23]), "+f"(d[24]), "+f"(d[25]), "+f"(d[26]), "+f"(d[27]), "+f"(d[28]), "+f"(d[29]), "+f"(d[30]), "+f"(d[31])
      : "l"(da), "l"(db), "r"(scaleD));
}
__device__ __forceinline__ void wgmma_qk_rs(float (&d)[32], uint32_t a0, uint32_t a1, uint32_t a2, uint32_t a3, uint64_t db, int scaleD) {
  asm volatile("{\n.reg .pred p;\nsetp.ne.b32 p, %37, 0;\n"
      "wgmma.mma_async.sync.aligned.m64n64k16.f32.bf16.bf16 "
      "{%0, %1, %2, %3, %4, %5, %6, %7, %8, %9, %10, %11, %12, %13, %14, %15, %16, %17, %18, %19, %20, %21, %22, %23, %24, %25, %26, %27, %28, %29, %30, "
      "%31}, "
      "{%32, %33, %34, %35}, %36, p, 1, 1, 0;\n}\n"
      : "+f"(d[0]), "+f"(d[1]), "+f"(d[2]), "+f"(d[3]), "+f"(d[4]), "+f"(d[5]), "+f"(d[6]), "+f"(d[7]), "+f"(d[8]), "+f"(d[9]), "+f"(d[10]), "+f"(d[11]),
        "+f"(d[12]), "+f"(d[13]), "+f"(d[14]), "+f"(d[15]), "+f"(d[16]), "+f"(d[17]), "+f"(d[18]), "+f"(d[19]), "+f"(d[20]), "+f"(d[21]), "+f"(d[22]),
        "+f"(d[23]), "+f"(d[24]), "+f"(d[25]), "+f"(d[26]), "+f"(d[27]), "+f"(d[28]), "+f"(d[29]), "+f"(d[30]), "+f"(d[31])
      : "r"(a0), "r"(a1), "r"(a2), "r"(a3), "l"(db), "r"(scaleD));
}
__device__ __forceinline__ void wgmma_pv(float (&d)[64], uint32_t a0, uint32_t a1, uint32_t a2, uint32_t a3, uint64_t db, int scaleD) {
  asm volatile("{\n.reg .pred p;\nsetp.ne.b32 p, %69, 0;\n"
      "wgmma.mma_async.sync.aligned.m64n128k16.f32.bf16.bf16 "
      "{%0, %1, %2, %3, %4, %5, %6, %7, %8, %9, %10, %11, %12, %13, %14, %15, %16, %17, %18, %19, %20, %21, %22, %23, %24, %25, %26, %27, %28, %29, %30, "
      "%31, %32, %33, %34, %35, %36, %37, %38, %39, %40, %41, %42, %43, %44, %45, %46, %47, %48, %49, %50, %51, %52, %53, %54, %55, %56, %57, %58, %59, %60, "
      "%61, %62, %63}, "
      "{%64, %65, %66, %67}, %68, p, 1, 1, 1;\n}\n"
      : "+f"(d[0]), "+f"(d[1]), "+f"(d[2]), "+f"(d[3]), "+f"(d[4]), "+f"(d[5]), "+f"(d[6]), "+f"(d[7]), "+f"(d[8]), "+f"(d[9]), "+f"(d[10]), "+f"(d[11]),
        "+f"(d[12]), "+f"(d[13]), "+f"(d[14]), "+f"(d[15]), "+f"(d[16]), "+f"(d[17]), "+f"(d[18]), "+f"(d[19]), "+f"(d[20]), "+f"(d[21]), "+f"(d[22]),
        "+f"(d[23]), "+f"(d[24]), "+f"(d[25]), "+f"(d[26]), "+f"(d[27]), "+f"(d[28]), "+f"(d[29]), "+f"(d[30]), "+f"(d[31]), "+f"(d[32]), "+f"(d[33]),
        "+f"(d[34]), "+f"(d[35]), "+f"(d[36]), "+f"(d[37]), "+f"(d[38]), "+f"(d[39]), "+f"(d[40]), "+f"(d[41]), "+f"(d[42]), "+f"(d[43]), "+f"(d[44]),
        "+f"(d[45]), "+f"(d[46]), "+f"(d[47]), "+f"(d[48]), "+f"(d[49]), "+f"(d[50]), "+f"(d[51]), "+f"(d[52]), "+f"(d[53]), "+f"(d[54]), "+f"(d[55]),
        "+f"(d[56]), "+f"(d[57]), "+f"(d[58]), "+f"(d[59]), "+f"(d[60]), "+f"(d[61]), "+f"(d[62]), "+f"(d[63])
      : "r"(a0), "r"(a1), "r"(a2), "r"(a3), "l"(db), "r"(scaleD));
}
__device__ __forceinline__ void wgmma_qk_sp(float (&d)[32], uint32_t a0, uint32_t a1, uint32_t a2, uint32_t a3, uint64_t db, int scaleD, uint32_t meta) {
  asm volatile("{\n.reg .pred p;\nsetp.ne.b32 p, %37, 0;\n"
      "wgmma.mma_async.sp.sync.aligned.m64n64k32.f32.bf16.bf16 "
      "{%0, %1, %2, %3, %4, %5, %6, %7, %8, %9, %10, %11, %12, %13, %14, %15, %16, %17, %18, %19, %20, %21, %22, %23, %24, %25, %26, %27, %28, %29, %30, "
      "%31}, "
      "{%32, %33, %34, %35}, %36, %38, 0, p, 1, 1, 0;\n}\n"
      : "+f"(d[0]), "+f"(d[1]), "+f"(d[2]), "+f"(d[3]), "+f"(d[4]), "+f"(d[5]), "+f"(d[6]), "+f"(d[7]), "+f"(d[8]), "+f"(d[9]), "+f"(d[10]), "+f"(d[11]),
        "+f"(d[12]), "+f"(d[13]), "+f"(d[14]), "+f"(d[15]), "+f"(d[16]), "+f"(d[17]), "+f"(d[18]), "+f"(d[19]), "+f"(d[20]), "+f"(d[21]), "+f"(d[22]),
        "+f"(d[23]), "+f"(d[24]), "+f"(d[25]), "+f"(d[26]), "+f"(d[27]), "+f"(d[28]), "+f"(d[29]), "+f"(d[30]), "+f"(d[31])
      : "r"(a0), "r"(a1), "r"(a2), "r"(a3), "l"(db), "r"(scaleD), "r"(meta));
}
__device__ __forceinline__ void wgmma_pv_sp(float (&d)[64], uint32_t a0, uint32_t a1, uint32_t a2, uint32_t a3, uint64_t db, int scaleD, uint32_t meta) {
  asm volatile("{\n.reg .pred p;\nsetp.ne.b32 p, %69, 0;\n"
      "wgmma.mma_async.sp.sync.aligned.m64n128k32.f32.bf16.bf16 "
      "{%0, %1, %2, %3, %4, %5, %6, %7, %8, %9, %10, %11, %12, %13, %14, %15, %16, %17, %18, %19, %20, %21, %22, %23, %24, %25, %26, %27, %28, %29, %30, "
      "%31, %32, %33, %34, %35, %36, %37, %38, %39, %40, %41, %42, %43, %44, %45, %46, %47, %48, %49, %50, %51, %52, %53, %54, %55, %56, %57, %58, %59, %60, "
      "%61, %62, %63}, "
      "{%64, %65, %66, %67}, %68, %70, 0, p, 1, 1, 1;\n}\n"
      : "+f"(d[0]), "+f"(d[1]), "+f"(d[2]), "+f"(d[3]), "+f"(d[4]), "+f"(d[5]), "+f"(d[6]), "+f"(d[7]), "+f"(d[8]), "+f"(d[9]), "+f"(d[10]), "+f"(d[11]),
        "+f"(d[12]), "+f"(d[13]), "+f"(d[14]), "+f"(d[15]), "+f"(d[16]), "+f"(d[17]), "+f"(d[18]), "+f"(d[19]), "+f"(d[20]), "+f"(d[21]), "+f"(d[22]),
        "+f"(d[23]), "+f"(d[24]), "+f"(d[25]), "+f"(d[26]), "+f"(d[27]), "+f"(d[28]), "+f"(d[29]), "+f"(d[30]), "+f"(d[31]), "+f"(d[32]), "+f"(d[33]),
        "+f"(d[34]), "+f"(d[35]), "+f"(d[36]), "+f"(d[37]), "+f"(d[38]), "+f"(d[39]), "+f"(d[40]), "+f"(d[41]), "+f"(d[42]), "+f"(d[43]), "+f"(d[44]),
        "+f"(d[45]), "+f"(d[46]), "+f"(d[47]), "+f"(d[48]), "+f"(d[49]), "+f"(d[50]), "+f"(d[51]), "+f"(d[52]), "+f"(d[53]), "+f"(d[54]), "+f"(d[55]),
        "+f"(d[56]), "+f"(d[57]), "+f"(d[58]), "+f"(d[59]), "+f"(d[60]), "+f"(d[61]), "+f"(d[62]), "+f"(d[63])
      : "r"(a0), "r"(a1), "r"(a2), "r"(a3), "l"(db), "r"(scaleD), "r"(meta));
}
__device__ __forceinline__ void wgmma_proj_init(float (&d)[64], uint64_t da, uint64_t db, int scaleD) {
  asm volatile("{\n.reg .pred p;\nsetp.ne.b32 p, %66, 0;\n"
      "wgmma.mma_async.sync.aligned.m64n128k16.f32.bf16.bf16 "
      "{%0, %1, %2, %3, %4, %5, %6, %7, %8, %9, %10, %11, %12, %13, %14, %15, %16, %17, %18, %19, %20, %21, %22, %23, %24, %25, %26, %27, %28, %29, %30, "
      "%31, %32, %33, %34, %35, %36, %37, %38, %39, %40, %41, %42, %43, %44, %45, %46, %47, %48, %49, %50, %51, %52, %53, %54, %55, %56, %57, %58, %59, %60, "
      "%61, %62, %63}, "
      "%64, %65, p, 1, 1, 0, 1;\n}\n"
      : "=f"(d[0]), "=f"(d[1]), "=f"(d[2]), "=f"(d[3]), "=f"(d[4]), "=f"(d[5]), "=f"(d[6]), "=f"(d[7]), "=f"(d[8]), "=f"(d[9]), "=f"(d[10]), "=f"(d[11]),
        "=f"(d[12]), "=f"(d[13]), "=f"(d[14]), "=f"(d[15]), "=f"(d[16]), "=f"(d[17]), "=f"(d[18]), "=f"(d[19]), "=f"(d[20]), "=f"(d[21]), "=f"(d[22]),
        "=f"(d[23]), "=f"(d[24]), "=f"(d[25]), "=f"(d[26]), "=f"(d[27]), "=f"(d[28]), "=f"(d[29]), "=f"(d[30]), "=f"(d[31]), "=f"(d[32]), "=f"(d[33]),
        "=f"(d[34]), "=f"(d[35]), "=f"(d[36]), "=f"(d[37]), "=f"(d[38]), "=f"(d[39]), "=f"(d[40]), "=f"(d[41]), "=f"(d[42]), "=f"(d[43]), "=f"(d[44]),
        "=f"(d[45]), "=f"(d[46]), "=f"(d[47]), "=f"(d[48]), "=f"(d[49]), "=f"(d[50]), "=f"(d[51]), "=f"(d[52]), "=f"(d[53]), "=f"(d[54]), "=f"(d[55]),
        "=f"(d[56]), "=f"(d[57]), "=f"(d[58]), "=f"(d[59]), "=f"(d[60]), "=f"(d[61]), "=f"(d[62]), "=f"(d[63])
      : "l"(da), "l"(db), "r"(scaleD));
}
__device__ __forceinline__ void wgmma_proj96_init(float (&d)[64], uint64_t da, uint64_t db, int scaleD) {
  asm volatile("{\n.reg .pred p;\nsetp.ne.b32 p, %50, 0;\n"
      "wgmma.mma_async.sync.aligned.m64n96k16.f32.bf16.bf16 "
      "{%0, %1, %2, %3, %4, %5, %6, %7, %8, %9, %10, %11, %12, %13, %14, %15, %16, %17, %18, %19, %20, %21, %22, %23, %24, %25, %26, %27, %28, %29, %30, "
      "%31, %32, %33, %34, %35, %36, %37, %38, %39, %40, %41, %42, %43, %44, %45, %46, %47}, "
      "%48, %49, p, 1, 1, 1, 0;\n}\n"
      : "=f"(d[0]), "=f"(d[1]), "=f"(d[2]), "=f"(d[3]), "=f"(d[4]), "=f"(d[5]), "=f"(d[6]), "=f"(d[7]), "=f"(d[8]), "=f"(d[9]), "=f"(d[10]), "=f"(d[11]),
        "=f"(d[12]), "=f"(d[13]), "=f"(d[14]), "=f"(d[15]), "=f"(d[16]), "=f"(d[17]), "=f"(d[18]), "=f"(d[19]), "=f"(d[20]), "=f"(d[21]), "=f"(d[22]),
        "=f"(d[23]), "=f"(d[24]), "=f"(d[25]), "=f"(d[26]), "=f"(d[27]), "=f"(d[28]), "=f"(d[29]), "=f"(d[30]), "=f"(d[31]), "=f"(d[32]), "=f"(d[33]),
        "=f"(d[34]), "=f"(d[35]), "=f"(d[36]), "=f"(d[37]), "=f"(d[38]), "=f"(d[39]), "=f"(d[40]), "=f"(d[41]), "=f"(d[42]), "=f"(d[43]), "=f"(d[44]),
        "=f"(d[45]), "=f"(d[46]), "=f"(d[47])
      : "l"(da), "l"(db), "r"(scaleD));
}
__device__ __forceinline__ void wgmma_qk_init(float (&d)[32], uint64_t da, uint64_t db, int scaleD) {
  asm volatile("{\n.reg .pred p;\nsetp.ne.b32 p, %34, 0;\n"
      "wgmma.mma_async.sync.aligned.m64n64k16.f32.bf16.bf16 "
      "{%0, %1, %2, %3, %4, %5, %6, %7, %8, %9, %10, %11, %12, %13, %14, %15, %16, %17, %18, %19, %20, %21, %22, %23, %24, %25, %26, %27, %28, %29, %30, "
      "%31}, "
      "%32, %33, p, 1, 1, 0, 0;\n}\n"
      : "=f"(d[0]), "=f"(d[1]), "=f"(d[2]), "=f"(d[3]), "=f"(d[4]), "=f"(d[5]), "=f"(d[6]), "=f"(d[7]), "=f"(d[8]), "=f"(d[9]), "=f"(d[10]), "=f"(d[11]),
        "=f"(d[12]), "=f"(d[13]), "=f"(d[14]), "=f"(d[15]), "=f"(d[16]), "=f"(d[17]), "=f"(d[18]), "=f"(d[19]), "=f"(d[20]), "=f"(d[21]), "=f"(d[22]),
        "=f"(d[23]), "=f"(d[24]), "=f"(d[25]), "=f"(d[26]), "=f"(d[27]), "=f"(d[28]), "=f"(d[29]), "=f"(d[30]), "=f"(d[31])
      : "l"(da), "l"(db), "r"(scaleD));
}
__device__ __forceinline__ void wgmma_qk_rs_init(float (&d)[32], uint32_t a0, uint32_t a1, uint32_t a2, uint32_t a3, uint64_t db, int scaleD) {
  asm volatile("{\n.reg .pred p;\nsetp.ne.b32 p, %37, 0;\n"
      "wgmma.mma_async.sync.aligned.m64n64k16.f32.bf16.bf16 "
      "{%0, %1, %2, %3, %4, %5, %6, %7, %8, %9, %10, %11, %12, %13, %14, %15, %16, %17, %18, %19, %20, %21, %22, %23, %24, %25, %26, %27, %28, %29, %30, "
      "%31}, "
      "{%32, %33, %34, %35}, %36, p, 1, 1, 0;\n}\n"
      : "=f"(d[0]), "=f"(d[1]), "=f"(d[2]), "=f"(d[3]), "=f"(d[4]), "=f"(d[5]), "=f"(d[6]), "=f"(d[7]), "=f"(d[8]), "=f"(d[9]), "=f"(d[10]), "=f"(d[11]),
        "=f"(d[12]), "=f"(d[13]), "=f"(d[14]), "=f"(d[15]), "=f"(d[16]), "=f"(d[17]), "=f"(d[18]), "=f"(d[19]), "=f"(d[20]), "=f"(d[21]), "=f"(d[22]),
        "=f"(d[23]), "=f"(d[24]), "=f"(d[25]), "=f"(d[26]), "=f"(d[27]), "=f"(d[28]), "=f"(d[29]), "=f"(d[30]), "=f"(d[31])
      : "r"(a0), "r"(a1), "r"(a2), "r"(a3), "l"(db), "r"(scaleD));
}
__device__ __forceinline__ void wgmma_pv_init(float (&d)[64], uint32_t a0, uint32_t a1, uint32_t a2, uint32_t a3, uint64_t db, int scaleD) {
  asm volatile("{\n.reg .pred p;\nsetp.ne.b32 p, %69, 0;\n"
      "wgmma.mma_async.sync.aligned.m64n128k16.f32.bf16.bf16 "
      "{%0, %1, %2, %3, %4, %5, %6, %7, %8, %9, %10, %11, %12, %13, %14, %15, %16, %17, %18, %19, %20, %21, %22, %23, %24, %25, %26, %27, %28, %29, %30, "
      "%31, %32, %33, %34, %35, %36, %37, %38, %39, %40, %41, %42, %43, %44, %45, %46, %47, %48, %49, %50, %51, %52, %53, %54, %55, %56, %57, %58, %59, %60, "
      "%61, %62, %63}, "
      "{%64, %65, %66, %67}, %68, p, 1, 1, 1;\n}\n"
      : "=f"(d[0]), "=f"(d[1]), "=f"(d[2]), "=f"(d[3]), "=f"(d[4]), "=f"(d[5]), "=f"(d[6]), "=f"(d[7]), "=f"(d[8]), "=f"(d[9]), "=f"(d[10]), "=f"(d[11]),
        "=f"(d[12]), "=f"(d[13]), "=f"(d[14]), "=f"(d[15]), "=f"(d[16]), "=f"(d[17]), "=f"(d[18]), "=f"(d[19]), "=f"(d[20]), "=f"(d[21]), "=f"(d[22]),
        "=f"(d[23]), "=f"(d[24]), "=f"(d[25]), "=f"(d[26]), "=f"(d[27]), "=f"(d[28]), "=f"(d[29]), "=f"(d[30]), "=f"(d[31]), "=f"(d[32]), "=f"(d[33]),
        "=f"(d[34]), "=f"(d[35]), "=f"(d[36]), "=f"(d[37]), "=f"(d[38]), "=f"(d[39]), "=f"(d[40]), "=f"(d[41]), "=f"(d[42]), "=f"(d[43]), "=f"(d[44]),
        "=f"(d[45]), "=f"(d[46]), "=f"(d[47]), "=f"(d[48]), "=f"(d[49]), "=f"(d[50]), "=f"(d[51]), "=f"(d[52]), "=f"(d[53]), "=f"(d[54]), "=f"(d[55]),
        "=f"(d[56]), "=f"(d[57]), "=f"(d[58]), "=f"(d[59]), "=f"(d[60]), "=f"(d[61]), "=f"(d[62]), "=f"(d[63])
      : "r"(a0), "r"(a1), "r"(a2), "r"(a3), "l"(db), "r"(scaleD));
}
__device__ __forceinline__ void wgmma_qk_sp_init(float (&d)[32], uint32_t a0, uint32_t a1, uint32_t a2, uint32_t a3, uint64_t db, int scaleD, uint32_t meta) {
  asm volatile("{\n.reg .pred p;\nsetp.ne.b32 p, %37, 0;\n"
      "wgmma.mma_async.sp.sync.aligned.m64n64k32.f32.bf16.bf16 "
      "{%0, %1, %2, %3, %4, %5, %6, %7, %8, %9, %10, %11, %12, %13, %14, %15, %16, %17, %18, %19, %20, %21, %22, %23, %24, %25, %26, %27, %28, %29, %30, "
      "%31}, "
      "{%32, %33, %34, %35}, %36, %38, 0, p, 1, 1, 0;\n}\n"
      : "=f"(d[0]), "=f"(d[1]), "=f"(d[2]), "=f"(d[3]), "=f"(d[4]), "=f"(d[5]), "=f"(d[6]), "=f"(d[7]), "=f"(d[8]), "=f"(d[9]), "=f"(d[10]), "=f"(d[11]),
        "=f"(d[12]), "=f"(d[13]), "=f"(d[14]), "=f"(d[15]), "=f"(d[16]), "=f"(d[17]), "=f"(d[18]), "=f"(d[19]), "=f"(d[20]), "=f"(d[21]), "=f"(d[22]),
        "=f"(d[23]), "=f"(d[24]), "=f"(d[25]), "=f"(d[26]), "=f"(d[27]), "=f"(d[28]), "=f"(d[29]), "=f"(d[30]), "=f"(d[31])
      : "r"(a0), "r"(a1), "r"(a2), "r"(a3), "l"(db), "r"(scaleD), "r"(meta));
}
__device__ __forceinline__ void wgmma_pv_sp_init(float (&d)[64], uint32_t a0, uint32_t a1, uint32_t a2, uint32_t a3, uint64_t db, int scaleD, uint32_t meta) {
  asm volatile("{\n.reg .pred p;\nsetp.ne.b32 p, %69, 0;\n"
      "wgmma.mma_async.sp.sync.aligned.m64n128k32.f32.bf16.bf16 "
      "{%0, %1, %2, %3, %4, %5, %6, %7, %8, %9, %10, %11, %12, %13, %14, %15, %16, %17, %18, %19, %20, %21, %22, %23, %24, %25, %26, %27, %28, %29, %30, "
      "%31, %32, %33, %34, %35, %36, %37, %38, %39, %40, %41, %42, %43, %44, %45, %46, %47, %48, %49, %50, %51, %52, %53, %54, %55, %56, %57, %58, %59, %60, "
      "%61, %62, %63}, "
      "{%64, %65, %66, %67}, %68, %70, 0, p, 1, 1, 1;\n}\n"
      : "=f"(d[0]), "=f"(d[1]), "=f"(d[2]), "=f"(d[3]), "=f"(d[4]), "=f"(d[5]), "=f"(d[6]), "=f"(d[7]), "=f"(d[8]), "=f"(d[9]), "=f"(d[10]), "=f"(d[11]),
        "=f"(d[12]), "=f"(d[13]), "=f"(d[14]), "=f"(d[15]), "=f"(d[16]), "=f"(d[17]), "=f"(d[18]), "=f"(d[19]), "=f"(d[20]), "=f"(d[21]), "=f"(d[22]),
        "=f"(d[23]), "=f"(d[24]), "=f"(d[25]), "=f"(d[26]), "=f"(d[27]), "=f"(d[28]), "=f"(d[29]), "=f"(d[30]), "=f"(d[31]), "=f"(d[32]), "=f"(d[33]),
        "=f"(d[34]), "=f"(d[35]), "=f"(d[36]), "=f"(d[37]), "=f"(d[38]), "=f"(d[39]), "=f"(d[40]), "=f"(d[41]), "=f"(d[42]), "=f"(d[43]), "=f"(d[44]),
        "=f"(d[45]), "=f"(d[46]), "=f"(d[47]), "=f"(d[48]), "=f"(d[49]), "=f"(d[50]), "=f"(d[51]), "=f"(d[52]), "=f"(d[53]), "=f"(d[54]), "=f"(d[55]),
        "=f"(d[56]), "=f"(d[57]), "=f"(d[58]), "=f"(d[59]), "=f"(d[60]), "=f"(d[61]), "=f"(d[62]), "=f"(d[63])
      : "r"(a0), "r"(a1), "r"(a2), "r"(a3), "l"(db), "r"(scaleD), "r"(meta));
}

constexpr int NB = 16, SQ = 224, DM = 640, NH = 32, SK = 1024, DH = 128;
constexpr int HD = NH * DH;
constexpr int NBETA = 2 * NB;
constexpr int NCTA = 132;
constexpr uint32_t SB0 = 1024;
constexpr int NS = 10;
constexpr int SLOT = 16384;
constexpr int QBUF_OFF = NS * SLOT;
constexpr int NSX = NS + 4;
constexpr int BAR_OFF = NSX * SLOT;
constexpr int BAR_FULL = BAR_OFF;
constexpr int BAR_EMPTY = BAR_OFF + 8 * NSX;
constexpr int BAR_STG = BAR_OFF + 16 * NSX;
constexpr int BAR_OUT = BAR_STG + 32;
constexpr int BAR_DESC = BAR_OUT + 8;
constexpr int BAR_GO = BAR_DESC + 8;
constexpr int BAR_MAIL = BAR_GO + 8;
constexpr int BAR_RDY = BAR_MAIL + 8;
constexpr int DESC_OFF = BAR_RDY + 8 * NSX;
constexpr int EPOCH_OFF = DESC_OFF + 16;
constexpr int TRACE_OFF = EPOCH_OFF + 16;
constexpr int SMEM_BYTES = TRACE_OFF;
constexpr float SM_C = 0.08838834764831845f * 1.4426950408889634f;
constexpr float SUM_HI = 1099511627776.f, SUM_LO = 1.f / 1099511627776.f;
constexpr uint32_t META_QK = 0xEEEE4444u;
constexpr uint32_t META_PV = 0x44EEEE44u;

#define QK_EARLY_MASK 3
#define ST_ORDER 0x2310
#define LAG_BAR 3
#define ST_NOW 8
#define PF_STEP 5
#define KV_WIN_UNITS 2
#define KV_WIN_D 4
#define SF 0xfe3f
#define O_STEPS 4
#define KV_WIN_RAMP 4
#define PDEPTH 0
#define KV_WIN_TILES -2
#define PR_KV 2
#define PR_X 2
#define PR_W 2
#define REG_C 232
#define REG_P 24
#define GO_P 4
#define P_POS 216
#define OR 6
#define OR0 0
#define B_LATE 23
#define H_LATE 24
#define RM0 1
#define RM1 31
#define RM2 0
#define CLUSTER 1
#define PAIRB 1
#define KG 5
#define PK 44
#define EARLY_MASK 0x3fffu
#define PIECE_TABLE 0x50188016,0x65e88038,0x50321819,0x6c8d1830,0x403f2812,0x80000000,0x50215014,0x695a503c,0x5029b813,0x6c4eb85e,0x501b4815,0x689d4834,0x502b1017,0x6ccc1039,0x50312010,0x80000000,0x500e681b,0x65e8683f,0x502ea011,0x80000000,0x63b1902e,0x80000000,0x63f0603b,0x80000000,0x64ad003d,0x80000000,0x64eca83a,0x80000000,0x5024581c,0x80000000,0x5012b01a,0x6a95b033,0x5011081d,0x6b130837,0x5016701f,0x6c8d7056,0x501ec81e,0x80000000,0x6723302f,0x80000000,0x501b380f,0x80000000,0x67234035,0x80000000,0x500d980e,0x6bd09831,0x56587816,0x80000000,0x50168818,0x80000000,0x57d1c01e,0x80000000

struct Params {
  CUtensorMap x[2][2], wq[2], kv[2][2], wo[2];
  CUtensorMap o_ld[2], o_st[2], out_st[2];
  const __nv_bfloat16* kp[2];
  const __nv_bfloat16* vp[2];
};

constexpr int NPART = 32 * 5, O_BLOCKS = NBETA * 64 + 2 * NPART;
__device__ __align__(128) __nv_bfloat16 g_o[(size_t)O_BLOCKS * SQ * 64];
__device__ unsigned g_cnt[NBETA][8];
__device__ unsigned g_rd[NBETA][8];
__device__ unsigned g_epoch, g_next;
__device__ unsigned g_flag[NPART];

__device__ __forceinline__ uint32_t smem_u32(const void* p) { return (uint32_t)__cvta_generic_to_shared(p); }
__device__ __forceinline__ void mbar_arrive(uint32_t bar) {
  asm volatile("mbarrier.arrive.shared::cta.b64 _, [%0];" ::"r"(bar) : "memory");
}
__device__ __forceinline__ void mbar_arrive_warp(uint32_t bar) {
  asm volatile("{\n.reg .pred p;\nelect.sync _|p, 0xffffffff;\n@p mbarrier.arrive.shared::cta.b64 _, [%0];\n}" ::"r"(bar) : "memory");
}
__device__ __forceinline__ int lane_now() { int l; asm volatile("mov.u32 %0, %%laneid;" : "=r"(l)); return l; }
__device__ __forceinline__ bool mbar_try(uint32_t bar, uint32_t parity) {
  uint32_t ok;
  asm volatile("{\n.reg .pred p;\nmbarrier.try_wait.parity.shared::cta.b64 p, [%1], %2;\nselp.u32 %0, 1, 0, p;\n}"
               : "=r"(ok) : "r"(bar), "r"(parity) : "memory");
  return ok;
}
__device__ __forceinline__ bool mbar_test(uint32_t bar, uint32_t parity) {
  uint32_t ok;
  asm volatile("{\n.reg .pred p;\nmbarrier.test_wait.parity.shared::cta.b64 p, [%1], %2;\nselp.u32 %0, 1, 0, p;\n}"
               : "=r"(ok) : "r"(bar), "r"(parity) : "memory");
  return ok;
}
__device__ __forceinline__ void mbar_wait_w(uint32_t bar, uint32_t parity) {
  uint32_t n = 0;
  while (!__all_sync(0xffffffffu, mbar_try(bar, parity))) {
    if (++n > (1u << 22)) __trap();
  }
}
#define ELECT "{\n.reg .pred p;\nelect.sync _|p, 0xffffffff;\n@p "
__device__ __forceinline__ void tma_st3_hint_w(const CUtensorMap* m, uint32_t src, int c0, int c1, int c2, uint64_t pol) {
  asm volatile(ELECT "cp.async.bulk.tensor.3d.global.shared::cta.bulk_group.L2::cache_hint [%0, {%2, %3, %4}], [%1], %5;\n}"
               ::"l"(m), "r"(src), "r"(c0), "r"(c1), "r"(c2), "l"(pol) : "memory");
}
#define EXPECT(bar, bytes) "mbarrier.arrive.expect_tx.shared::cta.b64 _, [" bar "], " bytes ";\n@p "
__device__ __forceinline__ void tma_ld2_w(uint32_t dst, const CUtensorMap* m, int c0, int c1, uint32_t bar, uint32_t bytes) {
  asm volatile(ELECT EXPECT("%2", "%5") "cp.async.bulk.tensor.2d.shared::cluster.global.mbarrier::complete_tx::bytes [%0], [%1, {%3, %4}], [%2];\n}"
               ::"r"(dst), "l"(m), "r"(bar), "r"(c0), "r"(c1), "r"(bytes) : "memory");
}
__device__ __forceinline__ void tma_ld2_hint_w(uint32_t dst, const CUtensorMap* m, int c0, int c1, uint32_t bar, uint32_t bytes, uint64_t pol) {
  asm volatile(ELECT EXPECT("%2", "%6") "cp.async.bulk.tensor.2d.shared::cluster.global.mbarrier::complete_tx::bytes.L2::cache_hint"
               " [%0], [%1, {%3, %4}], [%2], %5;\n}"
               ::"r"(dst), "l"(m), "r"(bar), "r"(c0), "r"(c1), "l"(pol), "r"(bytes) : "memory");
}
__device__ __forceinline__ void tma_ld3_w(uint32_t dst, const CUtensorMap* m, int c0, int c1, int c2, uint32_t bar, uint32_t bytes) {
  asm volatile(ELECT EXPECT("%2", "%6") "cp.async.bulk.tensor.3d.shared::cluster.global.mbarrier::complete_tx::bytes [%0], [%1, {%3, %4, %5}], [%2];\n}"
               ::"r"(dst), "l"(m), "r"(bar), "r"(c0), "r"(c1), "r"(c2), "r"(bytes) : "memory");
}
__device__ __forceinline__ void tma_ld3_hint_w(uint32_t dst, const CUtensorMap* m, int c0, int c1, int c2, uint32_t bar, uint64_t pol) {
  asm volatile(ELECT EXPECT("%2", "16384") "cp.async.bulk.tensor.3d.shared::cluster.global.mbarrier::complete_tx::bytes.L2::cache_hint"
               " [%0], [%1, {%3, %4, %5}], [%2], %6;\n}"
               ::"r"(dst), "l"(m), "r"(bar), "r"(c0), "r"(c1), "r"(c2), "l"(pol) : "memory");
}
__device__ __forceinline__ void tma_ld_wo_w(uint32_t dst, const CUtensorMap* m, int col, int grp, uint32_t bar) {
  asm volatile(ELECT EXPECT("%2", "16384") "cp.async.bulk.tensor.5d.shared::cluster.global.mbarrier::complete_tx::bytes [%0], [%1, {%3, 0, 0, 0, %4}], [%2];\n"
               "@p cp.async.bulk.tensor.5d.shared::cluster.global.mbarrier::complete_tx::bytes [%5], [%1, {%6, 0, 0, 0, %4}], [%2];\n}"
               ::"r"(dst), "l"(m), "r"(bar), "r"(col), "r"(grp), "r"(dst + 8192), "r"(col + 64) : "memory");
}
__device__ __forceinline__ void mbar_arrive8_w(uint32_t bar) {
  asm volatile(ELECT "mbarrier.arrive.shared::cta.b64 _, [%0], 8;\n}" ::"r"(bar) : "memory");
}
__device__ __forceinline__ uint32_t peer(uint32_t a) { uint32_t r; asm("mapa.shared::cluster.u32 %0, %1, %2;" : "=r"(r) : "r"(a), "r"(~blockIdx.x & 1)); return r; }
__device__ __forceinline__ void tma_ld2_both_w(uint32_t dst, const CUtensorMap* m, int c0, int c1, uint32_t bar, uint32_t bytes) {
  asm volatile(ELECT EXPECT("%2", "%5") "cp.async.bulk.tensor.2d.shared::cluster.global.mbarrier::complete_tx::bytes.multicast::cluster"
               " [%0], [%1, {%3, %4}], [%2], %6;\n}"
               ::"r"(dst), "l"(m), "r"(bar), "r"(c0), "r"(c1), "r"(bytes), "h"((uint16_t)3) : "memory");
}
__device__ __forceinline__ void tma_ld2_both_hint_w(uint32_t dst, const CUtensorMap* m, int c0, int c1, uint32_t bar, uint32_t bytes, uint64_t pol) {
  asm volatile(ELECT EXPECT("%2", "%6") "cp.async.bulk.tensor.2d.shared::cluster.global.mbarrier::complete_tx::bytes.multicast::cluster.L2::cache_hint"
               " [%0], [%1, {%3, %4}], [%2], %7, %5;\n}"
               ::"r"(dst), "l"(m), "r"(bar), "r"(c0), "r"(c1), "l"(pol), "r"(bytes), "h"((uint16_t)3) : "memory");
}
__device__ __forceinline__ void bulk_commit() { asm volatile("cp.async.bulk.commit_group;" ::: "memory"); }
template <int N> __device__ __forceinline__ void bulk_wait_read() { asm volatile("cp.async.bulk.wait_group.read %0;" ::"n"(N) : "memory"); }
__device__ __forceinline__ void wg_fence() { asm volatile("wgmma.fence.sync.aligned;" ::: "memory"); }
__device__ __forceinline__ void wg_commit() { asm volatile("wgmma.commit_group.sync.aligned;" ::: "memory"); }
template <int N> __device__ __forceinline__ void wg_wait() { asm volatile("wgmma.wait_group.sync.aligned %0;" ::"n"(N) : "memory"); }
__device__ __forceinline__ void fence_async_smem() { asm volatile("fence.proxy.async.shared::cta;" ::: "memory"); }
__device__ __forceinline__ void bar_sync(int id, int n) { asm volatile("bar.sync %0, %1;" ::"r"(id), "r"(n) : "memory"); }
__device__ __forceinline__ void touch(float& a) { asm volatile("neg.f32 %0, %0;" : "+f"(a)); }
__device__ __forceinline__ void touch(uint32_t& a) { asm volatile("not.b32 %0, %0;" : "+r"(a)); }
template <typename T, int N> __device__ __forceinline__ void touch(T (&a)[N]) {
#pragma unroll
  for (int i = 0; i < N; i++) touch(a[i]);
}
template <int ID, typename... A> __device__ __forceinline__ void sched_fence(uint32_t x, A&... a) {
  if (!((SF >> ID) & 1)) return;
  asm volatile("" : "+r"(x)::"memory");
#pragma unroll 1
  for (; __builtin_expect(x >= 100 + ID, 0); x >>= 1) { (touch(a), ...); __nanosleep(x); }
}
template <int N> __device__ __forceinline__ void reg_fence(float (&a)[N]) {
#pragma unroll
  for (int i = 0; i < N; i++) asm volatile("" : "+f"(a[i])::"memory");
}
template <int N> __device__ __forceinline__ void reg_fence(uint32_t (&a)[N]) {
#pragma unroll
  for (int i = 0; i < N; i++) asm volatile("" : "+r"(a[i])::"memory");
}
__device__ __forceinline__ float ex2(float x) { float y; asm("ex2.approx.ftz.f32 %0, %1;" : "=f"(y) : "f"(x)); return y; }
__device__ __forceinline__ uint32_t pack_bf16(float lo, float hi) {
  uint32_t r; asm("cvt.rn.bf16x2.f32 %0, %1, %2;" : "=r"(r) : "f"(hi), "f"(lo)); return r;
}
__device__ __forceinline__ void stsm4(uint32_t a, uint32_t r0, uint32_t r1, uint32_t r2, uint32_t r3) {
  asm volatile("stmatrix.sync.aligned.m8n8.x4.shared.b16 [%0], {%1, %2, %3, %4};" ::"r"(a), "r"(r0), "r"(r1), "r"(r2), "r"(r3) : "memory");
}
__device__ __forceinline__ void stsm4t(uint32_t a, uint32_t r0, uint32_t r1, uint32_t r2, uint32_t r3) {
  asm volatile("stmatrix.sync.aligned.m8n8.x4.trans.shared.b16 [%0], {%1, %2, %3, %4};" ::"r"(a), "r"(r0), "r"(r1), "r"(r2), "r"(r3) : "memory");
}
__device__ __forceinline__ void ldsm4(uint32_t a, uint32_t& r0, uint32_t& r1, uint32_t& r2, uint32_t& r3) {
  asm volatile("ldmatrix.sync.aligned.m8n8.x4.shared.b16 {%0, %1, %2, %3}, [%4];" : "=r"(r0), "=r"(r1), "=r"(r2), "=r"(r3) : "r"(a) : "memory");
}
__device__ __forceinline__ void sts16(uint32_t a, uint32_t v) { asm volatile("st.shared.u16 [%0], %1;" ::"r"(a), "h"((uint16_t)v) : "memory"); }
__device__ __forceinline__ void mma16816(float& c0, float& c1, float& c2, float& c3, uint32_t a0, uint32_t a1, uint32_t a2, uint32_t a3,
                                         uint32_t b0, uint32_t b1) {
  asm volatile("mma.sync.aligned.m16n8k16.row.col.f32.bf16.bf16.f32 {%0, %1, %2, %3}, {%4, %5, %6, %7}, {%8, %9}, {%0, %1, %2, %3};"
               : "+f"(c0), "+f"(c1), "+f"(c2), "+f"(c3) : "r"(a0), "r"(a1), "r"(a2), "r"(a3), "r"(b0), "r"(b1));
}
__device__ __forceinline__ uint32_t sdesc(uint32_t addr, uint32_t lbo) { return (addr >> 4) + ((lbo >> 4) << 16); }
__device__ __forceinline__ uint64_t desc64(uint32_t lo, uint32_t hi) { uint64_t d; asm("mov.b64 %0, {%1, %2};" : "=l"(d) : "r"(lo), "r"(hi)); return d; }
__device__ __forceinline__ void dadd(uint64_t& d, uint32_t inc) {
  asm("{\n.reg .b32 l, h;\nmov.b64 {l, h}, %0;\nadd.u32 l, l, %1;\nmov.b64 %0, {l, h};\n}" : "+l"(d) : "r"(inc));
}

struct Ring {
  uint32_t slot, phase, xp;
  __device__ __forceinline__ void uniform() {
    slot = __shfl_sync(0xffffffffu, slot, 0); phase = __shfl_sync(0xffffffffu, phase, 0); xp = __shfl_sync(0xffffffffu, xp, 0);
  }
  __device__ __forceinline__ void next() { if (++slot == NS) { slot = 0; phase ^= 1; } }
  __device__ __forceinline__ void next_if(bool p) { slot += p; if (slot == NS) { slot = 0; phase ^= 1; } }
};
__device__ __forceinline__ uint32_t borrow(int ks, int n) {
  const int k = ks + 1;
  return k >= 4 && !(k & 2) && k < n ? k & 1 : 2;
}

constexpr uint32_t Q_RANGES = NBETA * NH + __builtin_popcount(EARLY_MASK) * 5, Q_ALL = NBETA * (NH + 5);
constexpr int NRANGE = NCTA / 5;
struct Work { int kind, mode, k0, nsteps, range, beta, sub; };
struct Sched { uint16_t queue[Q_ALL]; uint32_t piece[NRANGE + 1][4]; };
constexpr Sched make_sched() {
  Sched s{};
  int q = 0, a = 0;
  for (int t = 0, e = 0; a < NBETA * NH; t++) {
    for (; e < NBETA && 8 * (e & ~PAIRB) + PK <= t && a >= P_POS; e++)
      for (int col = 0; col < 5 && (EARLY_MASK >> e & 1); col++) s.queue[q++] = 0x8000 | (e & 1 ? 4 - col : col) << 8 | e;
    for (int b = 0; b < NBETA; b++)
      for (int h = 0; h < NH; h++)
        if ((b >= B_LATE && h >= H_LATE ? 300 + b : 8 * (b & ~PAIRB) + KG * (h >> 2)) == t) { s.queue[q++] = b << 5 | h; a++; }
  }
  for (int b = 0; b < NBETA; b++)
    for (int col = 0; col < 5 && !(EARLY_MASK >> b & 1); col++) s.queue[q++] = 0x8000 | col << 8 | b;
  constexpr uint32_t T[NRANGE * 2] = {PIECE_TABLE};
  for (int g = 0; g <= NRANGE; g++)
    for (int n = 0; n < 4; n++) s.piece[g][n] = g < NRANGE && n < 2 ? T[2 * g + n] : 2u << 30;
  return s;
}
__constant__ Sched c_sched = make_sched();
constexpr int N_EARLY = __builtin_popcount(EARLY_MASK);
constexpr bool reuse_ok() {
  const Sched s = make_sched();
  int first[NBETA + OR] = {};
  for (int q = Q_RANGES - 1; q >= 0; q--) if (!(s.queue[q] & 0x8000)) first[s.queue[q] >> 5] = q;
  for (int q = 0; q < Q_RANGES; q++) if ((s.queue[q] & 0x8000) && (s.queue[q] & 31) >= OR0 && q - first[(s.queue[q] & 31) + OR] > NCTA - 32) return false;
  return true;
}
static_assert(reuse_ok());
template <bool SIMPLE> __device__ __forceinline__ bool o_reuse(uint32_t b) { return !SIMPLE && b - (OR0 + OR) < N_EARLY - OR0; }
template <bool SIMPLE> __device__ __forceinline__ uint32_t o_slot(uint32_t b) { return o_reuse<SIMPLE>(b) ? OR0 + (b - OR0) % OR : b; }
__device__ __forceinline__ Work decode(uint32_t d) {
  Work w;
  w.kind = d >> 30; if (w.kind == 3) w.kind = 1;
  w.mode = (d >> 28) & 3; w.k0 = (d >> 22) & 63;
  if (w.kind == 0) { w.beta = (d >> 5) & 31; w.sub = d & 31; w.nsteps = DM / 64; }
  else { w.beta = d & 31; w.sub = (d >> 8) & 7; w.nsteps = ((d >> 16) & 63) + 1; }
  w.range = ((d >> 11) & 31) * 5 + w.sub;
  return w;
}

__device__ __forceinline__ bool reached(const unsigned* cnt, unsigned target) {
  unsigned v;
  asm volatile("ld.acquire.gpu.global.u32 %0, [%1];" : "=r"(v) : "l"(cnt) : "memory");
  return (int)(v - target) >= 0;
}
__device__ __forceinline__ void wait_count(const unsigned* cnt, unsigned target) {
  unsigned n = 0;
  while (!__all_sync(0xffffffffu, reached(cnt, target))) { if (++n > (1u << 24)) __trap(); }
}
__device__ __forceinline__ uint32_t lds(uint32_t a) { uint32_t v; asm volatile("ld.volatile.shared.u32 %0, [%1];" : "=r"(v) : "r"(a) : "memory"); return v; }

#define TRACE(u, e)
#define T3(u, e)
#define T2C(u, e)
#define T2P(u, r, e)
#define TTAIL(k)
#define TCLK(k)
#define TO -1
#define TRACE_O(k) if (TO == k) TRACE(i, 5)
#define TRACE_P(u, e)
#define TRACE_IN(u, e)

struct Ctx {
  uint32_t sb;
  int wg, warp;
  uint32_t mqk, mpv;
  bool lead;
  int lane0, lane;
  int src;
};
template <int N> __device__ __forceinline__ uint32_t dhi(uint32_t lo) { return 0x40000040u + (lo >> (26 + N)); }
__device__ __forceinline__ void release(const Ctx& c, uint32_t slot) {
  if (c.lead) mbar_arrive(c.sb + BAR_EMPTY + slot * 8);
}
__device__ __forceinline__ uint32_t acquire(const Ctx& c, Ring& r, bool have = false) {
  const uint32_t s = r.slot;
  if (!have) mbar_wait_w(c.sb + BAR_FULL + s * 8, r.phase);
  r.next();
  return s;
}
__device__ __forceinline__ void mbar_wait2_w(uint32_t b0, uint32_t p0, uint32_t b1, uint32_t p1) {
  uint32_t n = 0;
  while (!__all_sync(0xffffffffu, mbar_try(b0, p0) & mbar_try(b1, p1))) {
    if (++n > (1u << 22)) __trap();
  }
}
__device__ __forceinline__ void mbar_wait3_w(uint32_t b0, uint32_t p0, uint32_t b1, uint32_t p1, uint32_t b2, uint32_t p2) {
  uint32_t n = 0;
  while (!__all_sync(0xffffffffu, mbar_try(b0, p0) & mbar_try(b1, p1) & mbar_try(b2, p2))) {
    if (++n > (1u << 22)) __trap();
  }
}
__device__ __forceinline__ void acquire2(const Ctx& c, Ring& r, uint32_t& s0, uint32_t& s1, bool have = false) {
  const uint32_t p0 = r.phase;
  s0 = r.slot; r.next(); s1 = r.slot;
  if (!have) mbar_wait2_w(c.sb + BAR_FULL + s0 * 8, p0, c.sb + BAR_FULL + s1 * 8, r.phase);
  r.next();
}
template <int N>
__device__ __forceinline__ bool peek(const Ctx& c, Ring r) {
  bool ok = true;
#pragma unroll
  for (int k = 0; k < N; k++) { ok &= mbar_test(c.sb + BAR_FULL + r.slot * 8, r.phase); r.next(); }
  return ok;
}
__device__ __forceinline__ void staged(const Ctx& c, int part) {
  fence_async_smem();
  __syncwarp();
  mbar_arrive_warp(c.sb + BAR_STG + c.wg * 16 + part * 8);
}

template <int WG, bool FIRST, int H>
__device__ __forceinline__ void proj_half(const Ctx& c, float (&acc)[64], uint32_t w, uint32_t x, uint32_t sw) {
  uint64_t dx = desc64((SB0 + x * SLOT + (WG ? 0 : H * 8192)) >> 4, dhi<0>(x) + sw);
  uint64_t dw = desc64(WG ? (SB0 + w * SLOT + H * 8192) >> 4 : sdesc(SB0 + w * SLOT, 8192), dhi<1>(x));
  wg_fence();
  if (WG) { if (FIRST) wgmma_proj96_init(acc, dw, dx, 0); else wgmma_proj96(acc, dw, dx, 1); }
  else { if (FIRST) wgmma_proj_init(acc, dx, dw, 0); else wgmma_proj(acc, dx, dw, 1); }
#pragma unroll
  for (int k = 1; k < 4; k++) {
    dadd(dx, k == 2 ? 2 + (sw >> 30) * 28 : 2); dadd(dw, 128);
    if (WG) wgmma_proj96(acc, dw, dx, 1); else wgmma_proj(acc, dx, dw, 1);
  }
  wg_commit();
}

__device__ __forceinline__ void proj_store16(uint32_t a, const float* f, float sc) {
  stsm4t(a, pack_bf16(f[0] * sc, f[1] * sc), pack_bf16(f[2] * sc, f[3] * sc), pack_bf16(f[4] * sc, f[5] * sc), pack_bf16(f[6] * sc, f[7] * sc));
}

__device__ __forceinline__ uint32_t stage_off(const Ctx& c) {
  const int lane = c.lane, mi = lane >> 3, r8 = lane & 7;
  return ((mi >> 1) * 8 + r8) * 128 + (((2 * c.warp + (mi & 1)) ^ r8) << 4);
}
__device__ __forceinline__ uint32_t q3_swz(uint32_t r8) { return ((r8 & 3) << 1) | (r8 >> 2); }
template <int H>
__device__ __forceinline__ void stage_t2(const Ctx& c, const float (&a)[64], float sc) {
  const uint32_t base = c.sb + QBUF_OFF + 2 * 16384 + H * 8192 + stage_off(c);
#pragma unroll
  for (int jj = 0; jj < 4; jj++) proj_store16(base + jj * 2048, &a[jj * 8], sc);
}
template <int H, bool IS_Q>
__device__ __forceinline__ void stage_t3(const Ctx& c, const float (&a)[64], float sc) {
  const uint32_t off = stage_off(c), r8 = (off >> 7) & 7;
  const uint32_t t3 = c.sb + QBUF_OFF + 3 * 16384 + H * 4096 + (IS_Q ? off ^ ((r8 ^ q3_swz(r8)) << 4) : off);
  proj_store16(t3, &a[32], sc);
  proj_store16(t3 + 2048, &a[40], sc);
}

template <int WG, int h>
__device__ __forceinline__ void load_part(const Ctx& c, Ring r, uint32_t (&q)[32]) {
  uint32_t n = 0;
  while (!h && !__all_sync(0xffffffffu, peek<4>(c, r))) {
    if (++n > (1u << 26)) __trap();
  }
  const int lane = c.lane, mi = lane >> 3, r8 = lane & 7;
  if (WG) { r.next(); r.next(); }
  const uint32_t off = c.sb + (WG ? stage_off(c) : (16 * c.warp + (mi & 1) * 8 + r8) * 128), t0 = off + r.slot * SLOT;
  r.next();
  const uint32_t t1 = off + r.slot * SLOT;
#pragma unroll
    for (int jj = 0; jj < (WG ? 6 : 8); jj++) {
      uint32_t* p = &q[4 * jj];
      if (WG) asm volatile("ldmatrix.sync.aligned.m8n8.x4.trans.shared.b16 {%0, %1, %2, %3}, [%4];" : "=r"(p[0]), "=r"(p[1]), "=r"(p[2]), "=r"(p[3])
                           : "r"((jj < 4 ? t0 + h * 8192 : t1 + h * 4096) + (jj & 3) * 2048) : "memory");
      else ldsm4((h ? t1 : t0) + (jj >> 2) * 8192 + (((((2 * jj) & 7) + (mi >> 1)) ^ r8) << 4), p[0], p[1], p[2], p[3]);
    }
}
template <int WG>
__device__ __forceinline__ void add_part(const Ctx& c, const uint32_t (&q)[32], float (&a)[64]) {
  const uint32_t one = (c.lane >> 3) == (c.lane & 3) ? 0x3f80u << (c.lane & 4) * 4 : 0;
#pragma unroll
  for (int i = 0; i < (WG ? 12 : 16); i++)
    asm("mma.sync.aligned.m16n8k8.row.col.f32.bf16.bf16.f32 {%0, %1, %2, %3}, {%4, %5}, {%6}, {%0, %1, %2, %3};"
        : "+f"(a[4 * i]), "+f"(a[4 * i + 1]), "+f"(a[4 * i + 2]), "+f"(a[4 * i + 3]) : "r"(q[2 * i]), "r"(q[2 * i + 1]), "r"(one));
}

__device__ __forceinline__ void trace_dump(const Ctx& c) {
}
struct RowSum { float l0, l1; };
__device__ __forceinline__ const char* o_addr(uint32_t item, int row, int lane) {
  return reinterpret_cast<const char*>(g_o) + (((item >> 10) * (2 * SQ) + row) * 128 + (lane ^ (lane >> 3)) * 16);
}
__device__ __forceinline__ void o_stg(const char* p, int i, const uint32_t* q) {
  asm volatile("st.global.v4.b32 [%0], {%1, %2, %3, %4};"
               ::"l"(p + (i >> 1) * (SQ * 128) + (i & 1) * 512), "r"(q[0]), "r"(q[1]), "r"(q[2]), "r"(q[3]) : "memory");
}
template <int MODE, int I0 = 0, int NI = 4>
__device__ __forceinline__ void o_emit(const char* p, const float (&o)[64], float inv) {
#pragma unroll
  for (int i = I0; i < I0 + NI; i++) {
    uint32_t q[4];
#pragma unroll
    for (int j = 0; j < 4; j++) q[j] = pack_bf16(o[16 * i + 4 * j + 2 * MODE] * inv, o[16 * i + 4 * j + 2 * MODE + 1] * inv);
    o_stg(p, i, q);
  }
}
__device__ __forceinline__ void o_done(const Ctx& c) {
  __syncwarp();
  mbar_arrive_warp(c.sb + BAR_OUT);
  __syncwarp();
}
template <int WG>
__device__ __forceinline__ void o_first(const Ctx& c, uint32_t item, float (&o)[64], const RowSum& inv) {
  const char* p = o_addr(item, WG ? 192 + 8 * c.warp : 64 + 16 * c.warp, c.lane);
  reg_fence(o);
  if (WG) {
    uint32_t q[16];
#pragma unroll
    for (int j = 0; j < 16; j++) q[j] = pack_bf16((o[4 * j] + o[4 * j + 2]) * inv.l0, (o[4 * j + 1] + o[4 * j + 3]) * inv.l0);
#pragma unroll
    for (int i = 0; i < 4; i++) o_stg(p, i, q + 4 * i);
  } else { o_emit<0>(p, o, inv.l0); o_emit<1>(p + 1024, o, inv.l1); }
}
template <int K0, int K1>
__device__ __forceinline__ void o_piece(const Ctx& c, const char* p, int k, const float (&o)[64], const RowSum& inv) {
  constexpr int NI = 8 / O_STEPS, M = K0 * NI / 4;
  if constexpr (K1 - K0 == 1) {
    o_emit<M, K0 * NI % 4, NI>(p + M * 1024, o, M ? inv.l1 : inv.l0);
    if (K1 == O_STEPS) o_done(c);
  } else {
    if (k <= (K0 + K1) / 2) o_piece<K0, (K0 + K1) / 2>(c, p, k, o, inv); else o_piece<(K0 + K1) / 2, K1>(c, p, k, o, inv);
  }
}
template <int WG>
__device__ __forceinline__ void o_second(const Ctx& c, uint32_t item, int k, float (&o)[64], const RowSum& inv) {
  reg_fence(o);
  o_piece<0, O_STEPS>(c, o_addr(item, 128 * WG + 16 * c.warp, c.lane0 + (k >> 8)), k, o, inv);
}
template <int WG>
__device__ __forceinline__ void release_q(const Ctx& c) {
#pragma unroll
  for (int t = 0; t < 2; t++)
    if (c.lead) asm volatile("mbarrier.arrive.shared::cta.b64 _, [%0], 2;" ::"r"(c.sb + BAR_EMPTY + (NS + 2 * WG + t) * 8) : "memory");
  __syncwarp();
}
struct Slots { uint32_t w, x, o, po; };
template <int WG>
__device__ __forceinline__ void acc_fence(float (&a)[64]) {
#pragma unroll
  for (int i = 0; i < (WG ? 48 : 64); i++) asm volatile("" : "+f"(a[i])::"memory");
}
template <int WG>
__device__ __forceinline__ void begin_acquire(const Ctx& c, Ring& r, Slots& h, bool wait) {
  const uint32_t s0 = r.slot, p0 = r.phase, f = c.sb + BAR_FULL;
  r.next();
  const uint32_t p1 = r.phase;
  h.w = r.slot; r.next();
  h.x = WG ? r.slot : s0; h.o = WG ? s0 : r.slot; h.po = r.phase;
  if (wait) { if (WG) mbar_wait3_w(f + s0 * 8, p0, f + h.w * 8, p1, f + h.x * 8, r.phase); else mbar_wait2_w(f + s0 * 8, p0, f + h.w * 8, p1); }
  r.next();
}
template <int WG>
__device__ __forceinline__ void proj_begin(const Ctx& c, Ring& r, float (&a0)[64], Slots& h, bool wait, uint32_t sw) {
  begin_acquire<WG>(c, r, h, wait);
  proj_half<WG, true, 0>(c, a0, h.w, h.x, sw);
  if (WG) release(c, h.o);
}
template <int WG>
__device__ __forceinline__ void proj_main(Ctx& c, Ring& r, float (&a0)[64], float (&a1)[64], Slots& h, int n, uint32_t sw, int unit,
                                          uint32_t item, int nq, float (&o1)[64], const RowSum& inv) {
  constexpr bool DEEP = (PDEPTH >> WG) & 1;
  T2C(unit, 3);
  int ks = 1;
#pragma unroll 1
  do {
    const Slots p = h;
    const uint32_t b = borrow(ks, n), tile = NS + (WG ? 3 - b : b), f = c.sb + BAR_FULL;
    const uint32_t s0 = b != 2 ? tile : r.slot, p0 = b != 2 ? (r.xp >> b) & 1 : r.phase;
    r.next_if(b == 2);
    const uint32_t p1 = r.phase;
    h.w = r.slot; r.next();
    const uint32_t s2 = b != 2 ? tile : r.slot;
    h.po = b != 2 ? p0 : r.phase;
    r.next_if(b == 2);
    r.xp ^= 1 << b;
    h.x = WG ? s2 : s0; h.o = WG ? s0 : s2;
    mbar_wait3_w(f + s0 * 8, p0, f + h.w * 8, p1, f + (WG ? s2 : p.o) * 8, WG ? h.po : p.po);
    if (ks < 10) T2C(unit, ks * 4);
    if (DEEP) {
      proj_half<WG, false, 0>(c, a0, h.w, h.x, sw);
      release(c, WG ? h.o : p.o);
      if (ks < 10) T2C(unit, ks * 4 + 1);
      wg_wait<1>();
      if (ks < 10) T2C(unit, ks * 4 + 2);
      release(c, p.x); release(c, p.w);
    } else {
      release(c, WG ? h.o : p.o);
      wg_wait<0>();
      release(c, p.x); release(c, p.w);
      if (ks < 10) T2C(unit, ks * 4 + 1);
      proj_half<WG, false, 0>(c, a0, h.w, h.x, sw);
      if (ks < 10) T2C(unit, ks * 4 + 2);
    }
    proj_half<WG, false, 1>(c, a1, h.w, h.x, sw);
    if (ks < 10) T2C(unit, ks * 4 + 3);
    if (ks <= nq) o_second<WG>(c, item, ks, o1, inv);
  } while (++ks != n);
  {
    const uint32_t e0 = c.sb + BAR_EMPTY + (NS + 3 * WG) * 8, e1 = c.sb + BAR_EMPTY + (NS + 1 + WG) * 8;
    const uint32_t p0 = (r.xp ^ unit ^ 1) & 1, p1 = ((r.xp >> 1) ^ unit ^ 1) & 1;
    const uint32_t k0 = sw ? e0 : c.sb + BAR_FULL + r.slot * 8, pk = sw ? p0 : r.phase;
    uint32_t cnt = 0;
    while (!__all_sync(0xffffffffu, mbar_try(e0, p0) & mbar_try(e1, p1) & mbar_try(k0, pk) & (WG || mbar_try(c.sb + BAR_FULL + h.o * 8, h.po)))) {
      if (++cnt > (1u << 22)) __trap();
    }
  }
  c.lane = c.lane0 + (h.w >> 5);
  if (!WG) release(c, h.o);
}
template <int WG>
__device__ __forceinline__ void proj_end(const Ctx& c, float (&a1)[64], const Slots& h) {
  wg_wait<0>();
  acc_fence<WG>(a1);
  release(c, h.x); release(c, h.w);
}
__device__ __forceinline__ uint32_t get_desc(const Ctx& c, int i) {
  uint32_t d;
  mbar_wait_w(c.sb + BAR_DESC, (i - 1) & 1);
  asm volatile("ld.volatile.shared.u32 %0, [%1];" : "=r"(d) : "r"(c.sb + DESC_OFF + (i & 3) * 4) : "memory");
  return __shfl_sync(0xffffffffu, d, 0);
}

__device__ __forceinline__ float quad_max(float x) {
  x = fmaxf(x, __shfl_xor_sync(0xffffffffu, x, 1));
  return fmaxf(x, __shfl_xor_sync(0xffffffffu, x, 2));
}
__device__ __forceinline__ float quad_sum(float x) {
  x += __shfl_xor_sync(0xffffffffu, x, 1);
  return x + __shfl_xor_sync(0xffffffffu, x, 2);
}
template <bool SP, bool FIRST>
__device__ __forceinline__ void exps(const Ctx& c, const float (&s)[32], uint32_t (&p)[SP ? 8 : 16], RowSum& st) {
  if constexpr (SP) {
    uint32_t q[8];
    float t;
#pragma unroll
    for (int j = 0; j < 8; j++) {
      const float e0 = ex2(s[4 * j] + s[4 * j + 2]), e1 = ex2(s[4 * j + 1] + s[4 * j + 3]);
      if (j == 0) t = e0 + e1; else t += e0 + e1;
      q[j] = pack_bf16(e0, e1);
    }
    const bool odd = c.src & 2;
#pragma unroll
    for (int g = 0; g < 4; g++) {
      p[2 * g] = __shfl_sync(0xffffffffu, odd ? q[2 * g + 1] : q[2 * g], c.src);
      p[2 * g + 1] = __shfl_sync(0xffffffffu, odd ? q[2 * g] : q[2 * g + 1], c.src ^ 1);
    }
    st.l0 = FIRST ? t : st.l0 + t;
  } else {
    float t0, t1;
#pragma unroll
    for (int j = 0; j < 8; j++) {
      const float e0 = ex2(s[4 * j]), e1 = ex2(s[4 * j + 1]), e2 = ex2(s[4 * j + 2]), e3 = ex2(s[4 * j + 3]);
      if (j == 0) { t0 = e0 + e1; t1 = e2 + e3; } else { t0 += e0 + e1; t1 += e2 + e3; }
      p[2 * j] = pack_bf16(e0, e1);
      p[2 * j + 1] = pack_bf16(e2, e3);
    }
    st.l0 = FIRST ? t0 : st.l0 + t0;
    st.l1 = FIRST ? t1 : st.l1 + t1;
  }
}
template <bool SP>
__device__ __forceinline__ bool finish_sums(RowSum& st) {
  const float a = quad_sum(st.l0), b = SP ? a : quad_sum(st.l1);
  st.l0 = __fdividef(1.f, a); st.l1 = __fdividef(1.f, b);
  return !(a >= SUM_LO && a <= SUM_HI && b >= SUM_LO && b <= SUM_HI);
}
template <bool SP, bool INIT, int SITE, bool COMMIT = true, int RM = 0>
__device__ __forceinline__ void issue_qk(const Ctx& c, float (&s)[32], const uint32_t (&qs)[32], uint32_t dq, uint32_t dk) {
  uint64_t a = desc64(dq, dhi<SITE & 1>(dk)), b = desc64(dk, dhi<1 - (SITE & 1)>(dk));
  if (SP) {
    if (INIT) wgmma_qk_sp_init(s, qs[0], qs[1], qs[2], qs[3], b, 0, c.mqk); else wgmma_qk_sp(s, qs[0], qs[1], qs[2], qs[3], b, 0, c.mqk);
#pragma unroll
    for (int k = 1; k < 4; k++) { dadd(b, k == 2 ? 508 : 4); wgmma_qk_sp(s, qs[4 * k], qs[4 * k + 1], qs[4 * k + 2], qs[4 * k + 3], b, 1, c.mqk); }
  } else {
    if (RM & 1) wgmma_qk_rs(s, qs[0], qs[1], qs[2], qs[3], b, 0); else if (INIT) wgmma_qk_init(s, a, b, 0); else wgmma_qk(s, a, b, 0);
#pragma unroll
    for (int k = 1; k < 8; k++) {
      dadd(a, k == 4 ? 506 : 2); dadd(b, k == 4 ? 506 : 2);
      if (RM >> k & 1) wgmma_qk_rs(s, qs[4 * k], qs[4 * k + 1], qs[4 * k + 2], qs[4 * k + 3], b, 1); else wgmma_qk(s, a, b, 1);
    }
  }
  if (COMMIT) wg_commit();
}
template <bool SP, bool ACC, int SITE, bool SPLIT = false>
__device__ __forceinline__ void issue_pv(const Ctx& c, float (&o)[64], const uint32_t (&p)[SP ? 8 : 16], uint32_t dv) {
  uint64_t b = desc64(dv, dhi<SITE & 1>(dv));
  if constexpr (SP) {
    if (ACC) wgmma_pv_sp(o, p[0], p[1], p[2], p[3], b, 1, c.mpv); else wgmma_pv_sp_init(o, p[0], p[1], p[2], p[3], b, 0, c.mpv);
    if (SPLIT) wg_commit();
    dadd(b, 256);
    wgmma_pv_sp(o, p[4], p[5], p[6], p[7], b, 1, c.mpv);
  } else {
    if (ACC) wgmma_pv(o, p[0], p[1], p[2], p[3], b, 1); else wgmma_pv_init(o, p[0], p[1], p[2], p[3], b, 0);
#pragma unroll
    for (int k = 1; k < 4; k++) { dadd(b, 128); wgmma_pv(o, p[4 * k], p[4 * k + 1], p[4 * k + 2], p[4 * k + 3], b, 1); }
  }
  wg_commit();
}
__device__ __forceinline__ void pack_rows(const float (&o)[64], float sc, uint32_t (&q)[32]) {
#pragma unroll
  for (int j = 0; j < 32; j++) q[j] = pack_bf16(o[2 * j] * sc, o[2 * j + 1] * sc);
}
template <int MASK = 255>
__device__ __forceinline__ void stage_rows(const Ctx& c, uint32_t tile_addr, const uint32_t (&q)[32]) {
  const int lane = c.lane, mi = lane >> 3, r8 = lane & 7;
  const uint32_t row_addr = tile_addr + (16 * c.warp + (mi & 1) * 8 + r8) * 128;
#pragma unroll
  for (int jj = 0; jj < 8; jj++)
    if (MASK >> jj & 1) stsm4(row_addr + (jj >> 2) * 8192 + (((((2 * jj) & 7) + (mi >> 1)) ^ r8) << 4), q[4 * jj], q[4 * jj + 1], q[4 * jj + 2], q[4 * jj + 3]);
}
__device__ __forceinline__ void stage_rows(const Ctx& c, uint32_t tile_addr, const float (&o)[64], float sc) {
  uint32_t q[32];
  pack_rows(o, sc, q);
  stage_rows(c, tile_addr, q);
}
template <int WG, int H>
__device__ __forceinline__ void stage_out(const Ctx& c, const float (&a)[64]) {
  if (WG) { stage_t3<H, false>(c, a, 1.f); if (H) staged(c, 0); stage_t2<H>(c, a, 1.f); }
  else stage_rows(c, c.sb + QBUF_OFF + H * 16384, a, 1.f);
  if (H || !WG) staged(c, H);
}
template <int SITE>
__device__ __forceinline__ void issue_qk_rs(float (&s)[32], uint32_t (&q)[32], uint32_t dk) {
  uint64_t b = desc64(dk, dhi<SITE>(dk));
  reg_fence(q);
  wg_fence();
  wgmma_qk_rs_init(s, q[0], q[1], q[2], q[3], b, 0);
#pragma unroll
  for (int k = 1; k < 8; k++) { dadd(b, k == 4 ? 506 : 2); wgmma_qk_rs(s, q[4 * k], q[4 * k + 1], q[4 * k + 2], q[4 * k + 3], b, 1); }
  wg_commit();
}

__device__ __forceinline__ void redo_tile(const Ctx& c, uint32_t q_addr, uint32_t half, const __nv_bfloat16* kp, const __nv_bfloat16* vp,
                                          uint32_t item, int row) {
  float o[64];
  const int lane = lane_now(), g = lane >> 2, cc = lane & 3, mi = lane >> 3, r8 = lane & 7;
  const uint32_t qa = q_addr + (half == 4096 ? 8 * c.warp + r8 : 16 * c.warp + (mi & 1) * 8 + r8) * 128, swz = half == 4096 ? q3_swz(r8) : r8;
  const uint32_t* kq = reinterpret_cast<const uint32_t*>(kp + g * DH) + cc;
  const unsigned short* vq = reinterpret_cast<const unsigned short*>(vp + 2 * cc * DH) + g;
  float m0 = -INFINITY, m1 = -INFINITY, l0 = 0.f, l1 = 0.f;
#pragma unroll
  for (int i = 0; i < 64; i++) o[i] = 0.f;
#pragma unroll 1
  for (int kb = 0; kb < SK / 16; kb++) {
    float z[8] = {0.f, 0.f, 0.f, 0.f, 0.f, 0.f, 0.f, 0.f};
#pragma unroll 2
    for (int kk = 0; kk < 8; kk++) {
      uint32_t a0, a1, a2, a3;
      ldsm4(qa + (kk >> 2) * half + ((((kk & 3) * 2 + (mi >> 1)) ^ swz) << 4), a0, a1, a2, a3);
      const uint32_t* kr = kq + kb * (16 * DH / 2) + kk * 8;
      mma16816(z[0], z[1], z[2], z[3], a0, a1, a2, a3, __ldg(kr), __ldg(kr + 4));
      mma16816(z[4], z[5], z[6], z[7], a0, a1, a2, a3, __ldg(kr + 8 * DH / 2), __ldg(kr + 8 * DH / 2 + 4));
    }
    const float n0 = fmaxf(m0, quad_max(fmaxf(fmaxf(z[0], z[1]), fmaxf(z[4], z[5]))));
    const float n1 = fmaxf(m1, quad_max(fmaxf(fmaxf(z[2], z[3]), fmaxf(z[6], z[7]))));
    const float al0 = ex2(m0 - n0), al1 = ex2(m1 - n1);
    m0 = n0; m1 = n1;
#pragma unroll
    for (int i = 0; i < 8; i++) z[i] = ex2(z[i] - ((i & 2) ? n1 : n0));
    l0 = l0 * al0 + (z[0] + z[1]) + (z[4] + z[5]);
    l1 = l1 * al1 + (z[2] + z[3]) + (z[6] + z[7]);
    const uint32_t a0 = pack_bf16(z[0], z[1]), a1 = pack_bf16(z[2], z[3]), a2 = pack_bf16(z[4], z[5]), a3 = pack_bf16(z[6], z[7]);
    const unsigned short* vr = vq + kb * (16 * DH);
#pragma unroll
    for (int nb = 0; nb < 16; nb++) {
      o[4 * nb] *= al0; o[4 * nb + 1] *= al0; o[4 * nb + 2] *= al1; o[4 * nb + 3] *= al1;
      const uint32_t b0 = __ldg(vr + nb * 8) | ((uint32_t)__ldg(vr + nb * 8 + DH) << 16);
      const uint32_t b1 = __ldg(vr + nb * 8 + 8 * DH) | ((uint32_t)__ldg(vr + nb * 8 + 9 * DH) << 16);
      mma16816(o[4 * nb], o[4 * nb + 1], o[4 * nb + 2], o[4 * nb + 3], a0, a1, a2, a3, b0, b1);
    }
  }
  const char* p = o_addr(item, row, lane);
  o_emit<0>(p, o, __fdividef(1.f, quad_sum(l0)));
  o_emit<1>(half == 4096 ? p : p + 1024, o, __fdividef(1.f, quad_sum(l1)));
}

template <bool SPA, bool SPB, int SITE, int ID>
__device__ __forceinline__ void batch(const Ctx& c, float (&s)[32], const uint32_t (&qs)[32], uint32_t dq, uint32_t dk, float (&ob)[64],
                                      uint32_t (&pb)[SPB ? 8 : 16], uint32_t dv) {
  if constexpr (SPA) {
    reg_fence(pb);
    wg_fence();
    issue_pv<SPB, true, ID>(c, ob, pb, dv);
    issue_qk<SPA, false, ID>(c, s, qs, dq, dk);
  } else {
    constexpr bool EARLY = ((QK_EARLY_MASK >> (SITE + (SPB ? 2 : 0))) & 1) != 0;
    if (!EARLY) reg_fence(pb);
    wg_fence();
    issue_qk<SPA, false, ID, !SPB, SITE ? RM0 : SPB ? RM2 : RM1>(c, s, qs, dq, dk);
    if (EARLY) { reg_fence(pb); wg_fence(); }
    issue_pv<SPB, true, ID, SPB>(c, ob, pb, dv);
  }
}

template <bool SP0>
__device__ __forceinline__ bool attention(Ctx& c, Ring& r, int unit, uint32_t& d, const float (&a0)[64], float (&o0)[64], float (&o1)[64],
                                          RowSum& st0, RowSum& st1, const Slots& h) {
  constexpr bool SP1 = false;
  if (SP0) { c.mqk = META_QK + (d >> 28); c.mpv = META_PV + (d >> 28); asm volatile("" : "+r"(c.mqk), "+r"(c.mpv)); }
  if (SP0) c.src = (c.lane & 28) | ((c.lane & 1) << 1) | ((c.lane >> 1) & 1);
  float s[32];
  uint32_t p0[SP0 ? 8 : 16], p1[16];
  const uint32_t q0a = c.sb + QBUF_OFF + (SP0 ? 3 : 0) * 16384, q1a = c.sb + QBUF_OFF + (SP0 ? 2 : 1) * 16384;
  const uint32_t dq0 = sdesc(SB0 + QBUF_OFF, 0), dq1 = sdesc(SB0 + QBUF_OFF + (SP0 ? 2 : 1) * 16384, 0);
  uint32_t sk = acquire(c, r, true), sv, sn;
  uint32_t qs[32], q1[32];
  float s1[32];
  if (SP0) {
    stage_t3<0, true>(c, a0, SM_C);
    stage_t2<0>(c, a0, SM_C);
    proj_end<1>(c, o0, h);
    stage_t3<1, true>(c, o0, SM_C);
    stage_t2<1>(c, o0, SM_C);
    fence_async_smem();
    bar_sync(1, LAG_BAR & 30 ? 256 : 128);
    const int g = c.lane >> 2, cc = c.lane & 3;
    const uint32_t qa = q0a + (8 * c.warp + g) * 128 + (cc & 1) * 8;
#pragma unroll
    for (int k = 0; k < 8; k++)
      asm volatile("ld.shared.v2.u32 {%0, %1}, [%2];" : "=r"(qs[2 * k]), "=r"(qs[2 * k + 1])
                   : "r"(qa + (k >> 2) * 4096 + ((((k & 3) * 2 + (cc >> 1)) ^ q3_swz(g)) << 4)) : "memory");
    TRACE(unit, 2);
    wg_fence();
    issue_qk<SP1, true, 1>(c, s1, qs, dq1, sdesc(SB0 + sk * SLOT, 0));
#pragma unroll
    for (int k = 0; k < 8; k++)
      if (RM2 >> k & 1) ldsm4(q1a + (k >> 2) * 8192 + (16 * c.warp + (c.lane & 15)) * 128 + (((2 * (k & 3) + (c.lane >> 4)) ^ (c.lane & 7)) << 4),
                              q1[4 * k], q1[4 * k + 1], q1[4 * k + 2], q1[4 * k + 3]);
#pragma unroll
    for (int k = 0; k < 16; k++) asm volatile("" : "+r"(qs[k])::"memory");
    wg_fence();
    issue_qk<SP0, true, 0>(c, s, qs, dq0, sdesc(SB0 + sk * SLOT, 0));
    const bool have = peek<2>(c, r);
    wg_wait<1>();
    reg_fence(s1);
    exps<SP1, true>(c, s1, p1, st1);
    sched_fence<11>(sk, p1);
    acquire2(c, r, sv, sn, __all_sync(0xffffffffu, have));
    wg_wait<0>();
    wg_fence();
    issue_pv<SP1, false, 1>(c, o1, p1, sdesc(SB0 + sv * SLOT, 8192));
    if (LAG_BAR & 1) asm volatile("bar.arrive 4, 256;" ::: "memory");
    sched_fence<12>(sk, s);
    release(c, sk);
    sk = sn;
    exps<SP0, true>(c, s, p0, st0);
    reg_fence(p0);
    wg_fence();
    issue_pv<SP0, false, 0>(c, o0, p0, sdesc(SB0 + sv * SLOT, 8192));
    issue_qk<SP0, true, 2>(c, s, qs, dq0, sdesc(SB0 + sk * SLOT, 0));
    sn = acquire(c, r);
    wg_wait<0>();
    reg_fence(s);
  } else {
    pack_rows(a0, SM_C, qs);
    stage_rows(c, q0a, qs);
    proj_end<0>(c, o1, h);
    TRACE(unit, 2);
    float sc = SM_C;
    issue_qk_rs<0>(s, qs, sdesc(SB0 + sk * SLOT, 0));
    sched_fence<0>(sk, sc);
    if (LAG_BAR & 8) asm volatile("bar.arrive 1, 256;" ::: "memory");
    pack_rows(o1, sc, q1);
    stage_rows<~RM1>(c, q1a, q1);
    if (LAG_BAR & 4) asm volatile("bar.arrive 1, 256;" ::: "memory");
    issue_qk_rs<1>(s1, q1, sdesc(SB0 + sk * SLOT, 0));
    if (LAG_BAR & 2) asm volatile("bar.arrive 1, 256;" ::: "memory");
    bool have = peek<2>(c, r);
    wg_wait<1>();
    reg_fence(s);
    exps<SP0, true>(c, s, p0, st0);
    sched_fence<1>(sk, p0);
    if (LAG_BAR & 16) asm volatile("bar.arrive 1, 256;" ::: "memory");
    acquire2(c, r, sv, sn, __all_sync(0xffffffffu, have));
    wg_wait<0>();
    reg_fence(s1);
    fence_async_smem();
    __syncwarp();
    wg_fence();
    issue_qk<SP0, false, 2, true, RM0>(c, s, qs, dq0, sdesc(SB0 + sn * SLOT, 0));
    issue_pv<SP0, false, 0>(c, o0, p0, sdesc(SB0 + sv * SLOT, 8192));
    sched_fence<2>(sk, s1);
    release(c, sk);
    have = peek<1>(c, r);
    sk = sn;
    exps<SP1, true>(c, s1, p1, st1);
    reg_fence(p1);
    wg_fence();
    issue_pv<SP1, false, 1>(c, o1, p1, sdesc(SB0 + sv * SLOT, 8192));
    sn = acquire(c, r, __all_sync(0xffffffffu, have));
    if (LAG_BAR & 1) bar_sync(4, 256);
    wg_wait<1>();
    reg_fence(s);
  }
  TRACE_IN(unit, 4);
  T2C(unit, 51);
#pragma unroll 1
  for (int j = 1; j < 15; j++) {
    const uint32_t sv_prev = sv, sk_prev = sk;
    sv = sn;
    const uint32_t dv = sdesc(SB0 + sv * SLOT, 8192);
    reg_fence(p0);
    exps<SP0, false>(c, s, p0, st0);
    batch<SP1, SP0, 0, 3>(c, s, q1, dq1, sdesc(SB0 + sk * SLOT, 0), o0, p0, dv);
    sk = acquire(c, r);
    wg_wait<1>();
    reg_fence(s); reg_fence(p1);
    release(c, sv_prev); release(c, sk_prev);
    exps<SP1, false>(c, s, p1, st1);
    batch<SP0, SP1, 1, 4>(c, s, qs, dq0, sdesc(SB0 + sk * SLOT, 0), o1, p1, dv);
    sn = acquire(c, r);
    if (SP0) wg_wait<0>(); else wg_wait<1>();
    reg_fence(s);
  }
  TRACE_IN(unit, 5);
  T2C(unit + 1, 52);
  const uint32_t sv_prev = sv;
  sv = sn;
  const uint32_t dv = sdesc(SB0 + sv * SLOT, 8192);
  reg_fence(p0);
  exps<SP0, false>(c, s, p0, st0);
  batch<SP1, SP0, 0, 5>(c, s, q1, dq1, sdesc(SB0 + sk * SLOT, 0), o0, p0, dv);
  asm volatile("ld.volatile.shared.u32 %0, [%1];" : "=r"(d) : "r"(c.sb + DESC_OFF + ((unit + 1) & 3) * 4) : "memory");
  const bool have = peek<2 + SP0>(c, r);
  wg_wait<1>();
  reg_fence(s); reg_fence(p1);
  release(c, sv_prev); release(c, sk);
  exps<SP1, false>(c, s, p1, st1);
  reg_fence(p1);
  wg_fence();
  issue_pv<SP1, true, 2>(c, o1, p1, dv);
  if (SP0) sched_fence<6>(sk, st0.l0, st1.l0, st1.l1); else sched_fence<5>(sk, st0.l0, st0.l1, st1.l0, st1.l1);
  c.lane = c.lane0 + (sk >> 5);
  const bool bad = finish_sums<SP0>(st0) | finish_sums<SP1>(st1);
  uint32_t any;
  asm volatile("{\n.reg .pred p, q;\nsetp.ne.u32 p, %1, 0;\nbar.red.or.pred q, %2, 128, p;\nselp.u32 %0, 1, 0, q;\n}"
               : "=r"(any) : "r"((uint32_t)bad), "n"(2 + SP0) : "memory");
  any = __any_sync(0xffffffffu, any);
  d = __shfl_sync(0xffffffffu, d, 0);
  if (d < (2u << 30) && !__all_sync(0xffffffffu, have)) { Ring t = r; Slots u; begin_acquire<SP0>(c, t, u, true); }
  wg_wait<0>();
  reg_fence(o0); reg_fence(o1);
  release(c, sv);
  if (!SP0 && __builtin_expect(any, 0)) { stage_rows<RM1>(c, q1a, q1); __syncwarp(); }
  return any;
}

template <int WG>
__device__ __forceinline__ void consumer(Ctx c, const __nv_bfloat16* const* kv) {
  asm volatile("setmaxnreg.inc.sync.aligned.u32 %0;" ::"n"(WG ? REG_C : 504 - REG_C - REG_P));
  c.wg = WG;
  Ring r{0, 0, 0};
  float a0[64], a1[64], o1[64];
  Slots h;
  RowSum inv0, inv1;
  uint32_t d = c_sched.queue[blockIdx.x] * 1025, dc = 0, sw;
  int i = 0, nq;
begin:
  sw = d & (1u << 30);
  proj_begin<WG>(c, r, a0, h, true, sw);
  proj_half<WG, true, 1>(c, a1, h.w, h.x, sw);
  nq = 0;
#pragma unroll
  for (int k = 0; k < 64; k++) asm volatile("" : "=f"(o1[k]));
  asm volatile("" : "=f"(inv1.l0), "=f"(inv1.l1));
  while (true) {
    TRACE(i, 0); TRACE(i, 6);
    proj_main<WG>(c, r, a0, a1, h, d >> 30 ? ((d >> 16) & 63) + 1 : DM / 64, sw, i, dc, nq, o1, inv1);
    dc = d;
    TRACE(i, 1);
    if (d >> 30) goto out_tile;
    wg_wait<1>();
    acc_fence<WG>(a0);
    if (WG ? attention<WG>(c, r, i, d, a0, a1, o1, inv0, inv1, h) : attention<WG>(c, r, i, d, a0, o1, a1, inv1, inv0, h)) goto redo;
    if (d >= (2u << 30)) break;
    sw = d & (1u << 30);
    proj_begin<WG>(c, r, a0, h, false, sw);
    release_q<WG>(c);
    if (WG) sched_fence<8>(h.w, inv0.l0); else sched_fence<7>(h.w, inv0.l0, inv0.l1);
    o_first<WG>(c, dc, a1, inv0);
    sched_fence<9>(h.w, inv1.l0);
    proj_half<WG, true, 1>(c, a1, h.w, h.x, sw);
    nq = O_STEPS;
    TRACE(i, 3); TRACE(i, 7);
    i++;
  }
  release_q<WG>(c);
  o_first<WG>(c, dc, a1, inv0);
#pragma unroll
  for (int k = 1; k <= O_STEPS; k++) o_second<WG>(c, dc, k, o1, inv1);
next:
  TRACE(i, 3); TRACE(i, 7);
  if ((d >> 30) != 2) {
    i++;
    r.uniform();
    goto begin;
  }
  trace_dump(c);
  return;
out_tile:
  if (d & 96) goto finish;
  d = get_desc(c, i + 1);
  wg_wait<1>();
  acc_fence<WG>(a0);
  TRACE_O(0);
  stage_out<WG, 0>(c, a0);
  TRACE_O(1);
  proj_end<WG>(c, a1, h);
  TRACE_O(2);
  stage_out<WG, 1>(c, a1);
  TRACE(i, 2);
  goto next;
finish:
  {
    uint32_t q[32];
#pragma unroll 1
    for (int k = (d >> 5) & 3; k > 1; k--) {
      wg_wait<0>();
      acc_fence<WG>(a0); acc_fence<WG>(a1);
      if (k == ((d >> 5) & 3)) { release(c, h.x); release(c, h.w); }
      load_part<WG, 0>(c, r, q); add_part<WG>(c, q, a0);
      load_part<WG, 1>(c, r, q); add_part<WG>(c, q, a1);
#pragma unroll
      for (int t = 0; t < 4; t++) { release(c, r.slot); r.next(); }
    }
    load_part<WG, 0>(c, r, q);
    wg_wait<1>();
    acc_fence<WG>(a0);
    TRACE_O(0);
    add_part<WG>(c, q, a0);
    stage_out<WG, 0>(c, a0);
    TRACE_O(1);
    load_part<WG, 1>(c, r, q);
    wg_wait<0>();
    acc_fence<WG>(a1);
    TRACE_O(2);
    add_part<WG>(c, q, a1);
    stage_out<WG, 1>(c, a1);
    TRACE(i, 2); TRACE(i, 3); TRACE(i, 7);
    trace_dump(c);
    return;
  }
redo:
  {
    const size_t hoff = (size_t)(dc & 511) * (SK * DH);
    const int br = (dc >> 9) & 1;
#pragma unroll 1
    for (int part = 0; part < 2; part++) {
      const int t = WG ? 3 - part : part;
      redo_tile(c, c.sb + QBUF_OFF + t * 16384, t == 3 ? 4096 : 8192, kv[br] + hoff, kv[2 + br] + hoff, dc,
                t * 64 + (t == 3 ? 8 : 16) * c.warp);
    }
    o_done(c);
    release_q<WG>(c);
  }
  goto next;
}

template <bool SIMPLE>
__global__ void __launch_bounds__(384, 1) mha_fused_kernel(const __grid_constant__ Params P) {
  extern __shared__ __align__(1024) uint8_t smem_raw[];
  const uint32_t sbase = smem_u32(smem_raw);
  const int tid = threadIdx.x;
  const int wg = __shfl_sync(0xffffffffu, tid >> 7, 0);
  const int warp = __shfl_sync(0xffffffffu, (tid >> 5) & 3, 0);
  const int lane = tid & 31;
  const int cta = blockIdx.x;
  constexpr bool PAIR = !SIMPLE && CLUSTER;

  if (tid == 0) T3(15, 0);
  if ((sbase & 0xffffff) != SB0) __trap();
  {
    const int wi = wg * 4 + warp;
    asm volatile(ELECT "prefetch.tensormap [%0];\n}" ::"l"(&P.x[0][0] + wi) : "memory");
#pragma unroll
    for (int k = 0; k < 5; k++) {
      const int b = min(BAR_OFF + (wi * 5 + k) * 8, DESC_OFF - 8);
      asm volatile(ELECT "mbarrier.init.shared::cta.b64 [%0], %1;\n}"
                   ::"r"(sbase + b), "r"(b < BAR_EMPTY || b >= BAR_DESC ? 1 : b >= BAR_STG && b < BAR_OUT ? 4 : 8) : "memory");
    }
    asm volatile("fence.mbarrier_init.release.cluster;" ::: "memory");
    if (wi < 6) asm volatile(ELECT "prefetch.tensormap [%0];\n}" ::"l"(&P.x[0][0] + 12 + wi) : "memory");
  }
  if (PAIR) asm volatile("barrier.cluster.arrive.aligned;\nbarrier.cluster.wait.aligned;" ::: "memory"); else __syncthreads();

  if (wg == 2) {
    asm volatile("setmaxnreg.dec.sync.aligned.u32 %0;" ::"n"(REG_P));
    if (warp == 1) {
      const uint32_t qb = sbase + QBUF_OFF;
      const uint32_t ep = __shfl_sync(0xffffffffu, *(volatile unsigned*)&g_epoch + 1, 0);
      asm volatile("st.volatile.shared.u32 [%0], %1;" ::"r"(sbase + EPOCH_OFF), "r"(ep) : "memory");
      uint32_t dc = c_sched.queue[cta], qi = 0, piece = 0, na = 0;
      TTAIL(0);
      for (int i = 0; (dc >> 30) != 2; i++) {
        if (!(dc >> 30) && o_reuse<SIMPLE>((dc >> 5) & 31)) {
          const unsigned* rd = &g_rd[0][0] + ((dc & 1023) >> 2) - OR * 8;
          for (uint32_t n = 0; !__all_sync(0xffffffffu, reached(rd, ep * 5)); __nanosleep(300)) if (++n > (1u << 22)) __trap();
        }
        mbar_wait_w(sbase + BAR_GO, i & 1);
        if (piece == 0) {
          if (PAIR && (cta & 1)) {
            asm volatile(ELECT EXPECT("%0", "4") "mbarrier.arrive.shared::cluster.b64 _, [%1];\n}" ::"r"(sbase + BAR_MAIL), "r"(peer(sbase + BAR_MAIL)) : "memory");
            mbar_wait_w(sbase + BAR_MAIL, i & 1);
            qi = lds(sbase + EPOCH_OFF + 8);
          } else if (lane == 0) {
            qi = atomicAdd(&g_next, PAIR ? 2 : 1);
            if (qi == (SIMPLE ? Q_ALL : Q_RANGES) - (PAIR ? 2 : 1)) { g_next = 0; g_epoch = ep; }
          }
          qi = __shfl_sync(0xffffffffu, qi, 0);
          if (PAIR && !(cta & 1)) {
            mbar_wait_w(sbase + BAR_MAIL, i & 1);
            asm volatile(ELECT "st.async.shared::cluster.mbarrier::complete_tx::bytes.u32 [%0], %1, [%2];\n}"
                         ::"r"(peer(sbase + EPOCH_OFF + 8)), "r"(qi + 1), "r"(peer(sbase + BAR_MAIL)) : "memory");
          }
          qi += SIMPLE ? gridDim.x : NCTA;
        }
        uint32_t d;
        if (qi < (SIMPLE ? Q_ALL : Q_RANGES)) { d = c_sched.queue[qi]; if (d & 0x8000) d ^= (1u << 30) | (63u << 16) | 0x8000; else d |= o_slot<SIMPLE>(d >> 5) << 15 | (d & 31) << 10; }
        else if (SIMPLE) d = 2u << 30;
        else { const uint32_t e = qi - Q_RANGES, g = e / 5; d = c_sched.piece[g][piece++] | (g & 1 ? g * 5 + 4 - e : e - g * 5) << 8; }
        if ((d >> 30) == 1) {
          const uint32_t k0 = (d >> 22) & 63;
          const uint32_t run = __ffs(__ballot_sync(0xffffffffu, !reached(&g_cnt[d & 31][lane & 7], ep * 4)) & (0xffu << (k0 >> 3))) - 1;
          if (run <= (k0 + ((d >> 16) & 63)) >> 3) d |= run <= (k0 + O_STEPS) >> 3 ? (2u << 30) | 128 : 128;
        }
        asm volatile("st.volatile.shared.u32 [%0], %1;" ::"r"(sbase + EPOCH_OFF + 4), "r"(qi) : "memory");
        asm volatile("st.volatile.shared.u32 [%0], %1;" ::"r"(sbase + DESC_OFF + ((i + 1) & 3) * 4), "r"(d) : "memory");
        __syncwarp();
        mbar_arrive_warp(sbase + BAR_DESC);
        const Work w = decode(dc);
        dc = d;
        if (w.kind == 0) {
          mbar_wait_w(sbase + BAR_OUT, na++ & 1);
          TTAIL(1);
          T3(i, 0); T3(i, 1);
          asm volatile(ELECT "red.release.gpu.global.add.u32 [%0], 1;\n}" ::"l"(&g_cnt[w.beta][w.sub >> 2]) : "memory");
          T3(i, 2);
          TTAIL(2);
          continue;
        }
        const bool fin = w.mode != 1;
        uint64_t pol, pol2;
        asm volatile("createpolicy.fractional.L2::evict_first.b64 %0, 1.0;" : "=l"(pol));
        asm volatile("createpolicy.fractional.L2::evict_normal.b64 %0, 1.0;" : "=l"(pol2));
        if (!fin) pol = pol2;
        const CUtensorMap* m = fin ? P.out_st : P.o_st;
        const int c1 = fin ? (w.beta & 15) * SQ : 0;
        const int c2 = fin ? (w.beta >> 4) * (DM / 64) + w.sub * 2 : NBETA * 64 + w.range * 2;
        uint32_t pend = 0;
#pragma unroll 1
        for (int e = 0; e < 4; e++) {
          const int t = (ST_ORDER >> (4 * e)) & 3;
          mbar_wait_w(sbase + BAR_STG + (t ^ (t >> 1)) * 8, (i - na) & 1);
          tma_st3_hint_w(m + (t == 3), qb + t * 16384, 0, c1 + t * 64, c2, pol);
          bulk_commit();
          T2P(i + 1, 5, 2 * e);
          if (pend) {
            bulk_wait_read<1>();
            mbar_arrive8_w(pend);
            T2P(i + 1, 5, 2 * e - 1);
          }
          pend = sbase + BAR_EMPTY + (NS + t) * 8;
          if ((ST_NOW >> e) & 1) {
            bulk_wait_read<0>();
            mbar_arrive8_w(pend);
            pend = 0;
            T2P(i + 1, 5, 2 * e + 1);
          }
        }
        if (w.beta < N_EARLY) asm volatile(ELECT "red.relaxed.gpu.global.add.u32 [%0], 1;\n}" ::"l"(&g_rd[w.beta][7]) : "memory");
        T3(i, 0);
        if (piece >= 2) TTAIL(piece * 2 - 1);
        asm volatile("cp.async.bulk.wait_group 0;" ::: "memory");
        T3(i, 1);
        if (w.mode == 1) asm volatile(ELECT "st.release.gpu.global.u32 [%0], %1;\n}" ::"l"(&g_flag[w.range]), "r"(ep) : "memory");
        T3(i, 2);
        if (piece >= 2) TTAIL(piece * 2);
      }
      T3(15, 1);
    } else
    if (warp == 0) {
      Ring r{0, 1, 3};
      uint32_t d = c_sched.queue[cta];
      for (int i = 0;; i++) {
        const Work w = decode(d);
        if (w.kind == 2) break;
        const CUtensorMap* m = w.kind == 0 ? &P.wq[w.beta >> 4] : &P.wo[w.beta >> 4];
        for (int ks = 0; ks < w.nsteps; ks++) {
          const uint32_t b = borrow(ks, w.nsteps);
          r.next_if(b == 2);
          const uint32_t bar = sbase + BAR_FULL + r.slot * 8;
          mbar_wait_w(bar + (BAR_EMPTY - BAR_FULL), r.phase);
          if (w.kind == 0) tma_ld3_w(sbase + r.slot * SLOT, m, 0, ks * 64, w.sub * 2, bar, 16384);
          else tma_ld_wo_w(sbase + r.slot * SLOT, m, w.sub * 128, (w.k0 + ks) * 2, bar);
          if (w.kind != 0 && w.beta < N_EARLY && (ks & 7) == 5 && ks > 5)
            asm volatile(ELECT "red.relaxed.gpu.global.add.u32 [%0], 1;\n}" ::"l"(&g_rd[w.beta][(ks >> 3) - 1]) : "memory");
          if (ks < 10) T2P(i, 2, ks);
          if (w.kind != 0 && ks == max(w.nsteps - GO_P, 4)) mbar_arrive_warp(sbase + BAR_GO);
          r.next(); r.next_if(b == 2);
        }
        if (w.kind == 0) {
          r.phase ^= 1; r.next(); r.next();
        } else if (w.mode == 2) {
          for (int k = 1; k <= ((d >> 5) & 3); k++) {
            if (k == 1) TTAIL(9);
            wait_count(&g_flag[w.range + 5 * k], lds(sbase + EPOCH_OFF));
            TTAIL(10);
            asm volatile("fence.proxy.async.global;" ::: "memory");
#pragma unroll 1
            for (int t = 0; t < 4; t++) {
              mbar_wait_w(sbase + BAR_EMPTY + r.slot * 8, r.phase);
              tma_ld3_w(sbase + r.slot * SLOT, &P.o_st[t == 3], 0, t * 64, NBETA * 64 + (w.range + 5 * k) * 2, sbase + BAR_FULL + r.slot * 8,
                        t == 3 ? 8192 : 16384);
              r.next();
            }
          }
        }
        mbar_wait_w(sbase + BAR_DESC, i & 1);
        d = __shfl_sync(0xffffffffu, lds(sbase + DESC_OFF + ((i + 1) & 3) * 4), 0);
      }
    } else {
      const int hi = warp - 2;
      uint64_t pol_stream;
      uint32_t rdy = 0;
      asm volatile("createpolicy.fractional.L2::evict_first.b64 %0, 1.0;" : "=l"(pol_stream));
      Ring r{0, 1, 3};
      uint32_t d = c_sched.queue[cta];
      for (int i = 0;; i++) {
        const Work w = decode(d);
        if (w.kind == 2) break;
        const CUtensorMap* m = w.kind == 0 ? &P.x[hi][w.beta >> 4] : &P.o_ld[hi];
        int c1 = (w.kind == 0 ? (w.beta & 15) : o_slot<SIMPLE>(w.beta) * 64 + w.k0) * SQ + hi * 128;
        int k_wait = -1;
        const bool both = PAIR && (w.kind == 0 || w.sub != 4), mine = !both || hi == (cta & 1);
        if (w.kind != 0 && mine) {
          if (d & 128) k_wait = d >= (3u << 30) ? 0 : 8 - (w.k0 & 7);
          asm volatile("fence.proxy.async.global;" ::: "memory");
        }
        const int rank = i == 0 ? cta : __shfl_sync(0xffffffffu, lds(sbase + EPOCH_OFF + 4), 0) - NCTA;
        for (int ks = 0; ks < w.nsteps; ks++) {
          if (ks == k_wait) {
            wait_count(&g_cnt[d & 31][(w.k0 + ks) >> 3], lds(sbase + EPOCH_OFF) * 4);
            asm volatile("fence.proxy.async.global;" ::: "memory");
            k_wait = ((w.k0 + ks) | 7) + 1 - w.k0;
          }
          const uint32_t b = borrow(ks, w.nsteps);
          const bool bo = b != 2;
          r.next_if(hi && !bo); r.next_if(hi && !bo);
          const uint32_t sl = bo ? NS + (b ^ (3 * hi)) : r.slot, bar = sbase + BAR_FULL + sl * 8;
          mbar_wait_w(bar + (BAR_EMPTY - BAR_FULL), bo ? (r.xp >> b) & 1 : r.phase);
          const uint32_t bytes = hi ? 96 * 128 : 128 * 128;
          if (!mine) {
            asm volatile(ELECT EXPECT("%0", "%2") "mbarrier.arrive.shared::cluster.b64 _, [%1];\n}"
                         ::"r"(bar), "r"(peer(bar + (BAR_RDY - BAR_FULL))), "r"(bytes) : "memory");
          } else if (both) {
            mbar_wait_w(bar + (BAR_RDY - BAR_FULL), (rdy >> sl) & 1);
            rdy ^= 1 << sl;
            if (w.kind == 0) tma_ld2_both_w(sbase + sl * SLOT, m, ks * 64, c1, bar, bytes);
            else tma_ld2_both_hint_w(sbase + sl * SLOT, m, 0, c1, bar, bytes, pol_stream);
          } else if (!PAIR && w.kind == 0) tma_ld2_w(sbase + sl * SLOT, m, ks * 64, c1, bar, bytes);
          else tma_ld2_hint_w(sbase + sl * SLOT, m, 0, c1, bar, bytes, pol_stream);
          if (w.kind != 0) c1 += SQ;
          if (i == 0 && ks == PF_STEP)
            asm volatile(ELECT "cp.async.bulk.prefetch.tensor.3d.L2.global.L2::cache_hint [%0, {0, %1, 0}], %2;\n}"
                         ::"l"(&P.kv[hi][0]), "r"(d * SK), "l"(pol_stream) : "memory");
          if (ks < 10) T2P(i, 3 + hi, ks);
          if (!hi && w.kind != 0 && !(ks & 3)) TCLK(i * 16 + (ks >> 2));
          r.next(); r.next_if(!hi && !bo); r.next_if(!hi && !bo);
          r.xp ^= 1 << b;
        }
        r.xp ^= 3;
        if (w.kind == 0) {
          m = &P.kv[hi][w.beta >> 4];
          c1 = (d & 511) * SK;
          for (int j = 0; j < 16; j++) {
            if (hi) r.next();
            const uint32_t bar = sbase + BAR_FULL + r.slot * 8;
            const bool tight = i < KV_WIN_UNITS && j < KV_WIN_TILES + ((KV_WIN_RAMP * rank) >> 5);
            {
              const int s2 = (int)r.slot - (tight ? 2 : KV_WIN_D);
              mbar_wait_w(sbase + BAR_FULL + (s2 < 0 ? s2 + NS : s2) * 8, s2 < 0 ? r.phase : r.phase ^ 1);
            }
            if (j == 15 && hi) mbar_wait_w(sbase + BAR_DESC, i & 1);
            mbar_wait_w(sbase + BAR_EMPTY + r.slot * 8, r.phase);
            tma_ld3_hint_w(sbase + r.slot * SLOT, m, 0, c1, 0, bar, pol_stream);
            T2P(i, 3 + hi, 16 + j);
            if (!hi) TCLK(i * 16 + j);
            if (j == 14 && !hi) mbar_arrive_warp(sbase + BAR_GO);
            c1 += 64;
            r.next();
            if (!hi) r.next();
          }
        }
        mbar_wait_w(sbase + BAR_DESC, i & 1);
        d = __shfl_sync(0xffffffffu, lds(sbase + DESC_OFF + ((i + 1) & 3) * 4), 0);
      }
    }
  } else {
    Ctx c;
    c.sb = sbase; c.wg = wg; c.warp = warp; c.src = 0; c.mqk = 0; c.mpv = 0; c.lead = lane == 0; c.lane0 = c.lane = lane;
    if (wg == 0) consumer<0>(c, P.kp); else consumer<1>(c, P.kp);
  }
}

typedef CUresult (*EncodeFn)(CUtensorMap*, CUtensorMapDataType, cuuint32_t, void*, const cuuint64_t*, const cuuint64_t*,
                             const cuuint32_t*, const cuuint32_t*, CUtensorMapInterleave, CUtensorMapSwizzle,
                             CUtensorMapL2promotion, CUtensorMapFloatOOBfill);

void make_map(EncodeFn enc, CUtensorMap* m, const void* ptr, int rank, const cuuint64_t* dims, const cuuint64_t* strides,
              const cuuint32_t* box, int promo = 2, CUtensorMapSwizzle swz = CU_TENSOR_MAP_SWIZZLE_128B) {
  cuuint32_t es[5] = {1, 1, 1, 1, 1};
  enc(m, CU_TENSOR_MAP_DATA_TYPE_BFLOAT16, rank, const_cast<void*>(ptr), dims, strides, box, es,
      CU_TENSOR_MAP_INTERLEAVE_NONE, swz, promo == 2 ? CU_TENSOR_MAP_L2_PROMOTION_L2_256B : promo == 1 ? CU_TENSOR_MAP_L2_PROMOTION_L2_128B : CU_TENSOR_MAP_L2_PROMOTION_NONE,
      CU_TENSOR_MAP_FLOAT_OOB_FILL_NONE);
}

}

extern "C" void kernel_launch(void* const* d_in, const int* in_sizes, int n_in, void* d_out, int out_size) {
  (void)in_sizes; (void)n_in; (void)out_size;
  static EncodeFn enc = nullptr;
  static void* o_ptr = nullptr;
  static int n_sm = 0;
  cudaLaunchAttribute at;
  at.id = cudaLaunchAttributeClusterDimension;
  at.val.clusterDim.x = CLUSTER ? 2 : 1; at.val.clusterDim.y = 1; at.val.clusterDim.z = 1;
  cudaLaunchConfig_t cfg = {};
  cfg.gridDim = dim3(NCTA); cfg.blockDim = dim3(384); cfg.dynamicSmemBytes = SMEM_BYTES; cfg.attrs = &at; cfg.numAttrs = 1;
  if (!enc) {
    void* fn = nullptr;
    cudaDriverEntryPointQueryResult qr;
    cudaGetDriverEntryPoint("cuTensorMapEncodeTiled", &fn, cudaEnableDefault, &qr);
    enc = (EncodeFn)fn;
    cudaGetSymbolAddress(&o_ptr, g_o);
    cudaFuncSetAttribute(mha_fused_kernel<false>, cudaFuncAttributeMaxDynamicSharedMemorySize, SMEM_BYTES);
    cudaFuncSetAttribute(mha_fused_kernel<true>, cudaFuncAttributeMaxDynamicSharedMemorySize, SMEM_BYTES);
    int dev = 0;
    cudaGetDevice(&dev);
    cudaDeviceGetAttribute(&n_sm, cudaDevAttrMultiProcessorCount, dev);
    int n_cl = 0;
    cudaOccupancyMaxActiveClusters(&n_cl, mha_fused_kernel<false>, &cfg);
    if (n_cl * (CLUSTER ? 2 : 1) < NCTA && n_sm >= NCTA) n_sm = NCTA - 1;
  }
  Params P;
  for (int br = 0; br < 2; br++) {
    const void* x = d_in[br * 5 + 0]; const void* kc = d_in[br * 5 + 1]; const void* vc = d_in[br * 5 + 2];
    const void* wq = d_in[br * 5 + 3]; const void* wo = d_in[br * 5 + 4];
    { cuuint64_t d[2] = {DM, (cuuint64_t)NB * SQ}, s[1] = {DM * 2}; cuuint32_t b[2] = {64, 128}, b2[2] = {64, 96};
      make_map(enc, &P.x[0][br], x, 2, d, s, b, PR_X); make_map(enc, &P.x[1][br], x, 2, d, s, b2, PR_X); }
    { cuuint64_t d[3] = {64, DM, HD / 64}, s[2] = {HD * 2, 128}; cuuint32_t b[3] = {64, 64, 2}; make_map(enc, &P.wq[br], wq, 3, d, s, b, PR_W); }
    { cuuint64_t d[5] = {DM, 2, 4, 4, HD / 32}, s[4] = {DM * 2, 8 * DM * 2, 2 * DM * 2, 32 * DM * 2}; cuuint32_t b[5] = {64, 2, 4, 4, 2};
      make_map(enc, &P.wo[br], wo, 5, d, s, b, PR_W); }
    { cuuint64_t d[3] = {64, (cuuint64_t)NB * NH * SK, 2}, s[2] = {DH * 2, 128}; cuuint32_t b[3] = {64, 64, 2};
      make_map(enc, &P.kv[0][br], kc, 3, d, s, b, PR_KV); make_map(enc, &P.kv[1][br], vc, 3, d, s, b, PR_KV); }
    P.kp[br] = (const __nv_bfloat16*)kc; P.vp[br] = (const __nv_bfloat16*)vc;

  }
  { cuuint64_t d[2] = {64, (cuuint64_t)NBETA * 64 * SQ}, s[1] = {128}; cuuint32_t b[2] = {64, 128}, b2[2] = {64, 96};
    make_map(enc, &P.o_ld[0], o_ptr, 2, d, s, b, 2, CU_TENSOR_MAP_SWIZZLE_NONE); make_map(enc, &P.o_ld[1], o_ptr, 2, d, s, b2, 2, CU_TENSOR_MAP_SWIZZLE_NONE); }
  { cuuint64_t d[3] = {64, SQ, O_BLOCKS}, s[2] = {128, SQ * 128}; cuuint32_t b[3] = {64, 64, 2}, b2[3] = {64, 32, 2};
    make_map(enc, &P.o_st[0], o_ptr, 3, d, s, b); make_map(enc, &P.o_st[1], o_ptr, 3, d, s, b2); }
  { cuuint64_t d[3] = {64, (cuuint64_t)NB * SQ, 2 * DM / 64}, s[2] = {2 * DM * 2, 128}; cuuint32_t b[3] = {64, 64, 2}, b2[3] = {64, 32, 2};
    make_map(enc, &P.out_st[0], d_out, 3, d, s, b); make_map(enc, &P.out_st[1], d_out, 3, d, s, b2); }
  if (n_sm >= NCTA) cudaLaunchKernelEx(&cfg, mha_fused_kernel<false>, P);
  else mha_fused_kernel<true><<<n_sm, 384, SMEM_BYTES>>>(P);
}
```

```cpp
#include <cuda_runtime.h>
#include <cuda_bf16.h>
#include <cuda.h>
#include <stdint.h>
#include <stdlib.h>

namespace {

__device__ __forceinline__ void wgmma_proj(float (&d)[64], uint64_t da, uint64_t db, int scaleD) {
  asm volatile("{\n.reg .pred p;\nsetp.ne.b32 p, %66, 0;\n"
      "wgmma.mma_async.sync.aligned.m64n128k16.f32.bf16.bf16 "
      "{%0, %1, %2, %3, %4, %5, %6, %7, %8, %9, %10, %11, %12, %13, %14, %15, %16, %17, %18, %19, %20, %21, %22, %23, %24, %25, %26, %27, %28, %29, %30, "
      "%31, %32, %33, %34, %35, %36, %37, %38, %39, %40, %41, %42, %43, %44, %45, %46, %47, %48, %49, %50, %51, %52, %53, %54, %55, %56, %57, %58, %59, %60, "
      "%61, %62, %63}, "
      "%64, %65, p, 1, 1, 0, 1;\n}\n"
      : "+f"(d[0]), "+f"(d[1]), "+f"(d[2]), "+f"(d[3]), "+f"(d[4]), "+f"(d[5]), "+f"(d[6]), "+f"(d[7]), "+f"(d[8]), "+f"(d[9]), "+f"(d[10]), "+f"(d[11]),
        "+f"(d[12]), "+f"(d[13]), "+f"(d[14]), "+f"(d[15]), "+f"(d[16]), "+f"(d[17]), "+f"(d[18]), "+f"(d[19]), "+f"(d[20]), "+f"(d[21]), "+f"(d[22]),
        "+f"(d[23]), "+f"(d[24]), "+f"(d[25]), "+f"(d[26]), "+f"(d[27]), "+f"(d[28]), "+f"(d[29]), "+f"(d[30]), "+f"(d[31]), "+f"(d[32]), "+f"(d[33]),
        "+f"(d[34]), "+f"(d[35]), "+f"(d[36]), "+f"(d[37]), "+f"(d[38]), "+f"(d[39]), "+f"(d[40]), "+f"(d[41]), "+f"(d[42]), "+f"(d[43]), "+f"(d[44]),
        "+f"(d[45]), "+f"(d[46]), "+f"(d[47]), "+f"(d[48]), "+f"(d[49]), "+f"(d[50]), "+f"(d[51]), "+f"(d[52]), "+f"(d[53]), "+f"(d[54]), "+f"(d[55]),
        "+f"(d[56]), "+f"(d[57]), "+f"(d[58]), "+f"(d[59]), "+f"(d[60]), "+f"(d[61]), "+f"(d[62]), "+f"(d[63])
      : "l"(da), "l"(db), "r"(scaleD));
}
__device__ __forceinline__ void wgmma_proj96(float (&d)[64], uint64_t da, uint64_t db, int scaleD) {
  asm volatile("{\n.reg .pred p;\nsetp.ne.b32 p, %50, 0;\n"
      "wgmma.mma_async.sync.aligned.m64n96k16.f32.bf16.bf16 "
      "{%0, %1, %2, %3, %4, %5, %6, %7, %8, %9, %10, %11, %12, %13, %14, %15, %16, %17, %18, %19, %20, %21, %22, %23, %24, %25, %26, %27, %28, %29, %30, "
      "%31, %32, %33, %34, %35, %36, %37, %38, %39, %40, %41, %42, %43, %44, %45, %46, %47}, "
      "%48, %49, p, 1, 1, 1, 0;\n}\n"
      : "+f"(d[0]), "+f"(d[1]), "+f"(d[2]), "+f"(d[3]), "+f"(d[4]), "+f"(d[5]), "+f"(d[6]), "+f"(d[7]), "+f"(d[8]), "+f"(d[9]), "+f"(d[10]), "+f"(d[11]),
        "+f"(d[12]), "+f"(d[13]), "+f"(d[14]), "+f"(d[15]), "+f"(d[16]), "+f"(d[17]), "+f"(d[18]), "+f"(d[19]), "+f"(d[20]), "+f"(d[21]), "+f"(d[22]),
        "+f"(d[23]), "+f"(d[24]), "+f"(d[25]), "+f"(d[26]), "+f"(d[27]), "+f"(d[28]), "+f"(d[29]), "+f"(d[30]), "+f"(d[31]), "+f"(d[32]), "+f"(d[33]),
        "+f"(d[34]), "+f"(d[35]), "+f"(d[36]), "+f"(d[37]), "+f"(d[38]), "+f"(d[39]), "+f"(d[40]), "+f"(d[41]), "+f"(d[42]), "+f"(d[43]), "+f"(d[44]),
        "+f"(d[45]), "+f"(d[46]), "+f"(d[47])
      : "l"(da), "l"(db), "r"(scaleD));
}
__device__ __forceinline__ void wgmma_qk(float (&d)[32], uint64_t da, uint64_t db, int scaleD) {
  asm volatile("{\n.reg .pred p;\nsetp.ne.b32 p, %34, 0;\n"
      "wgmma.mma_async.sync.aligned.m64n64k16.f32.bf16.bf16 "
      "{%0, %1, %2, %3, %4, %5, %6, %7, %8, %9, %10, %11, %12, %13, %14, %15, %16, %17, %18, %19, %20, %21, %22, %23, %24, %25, %26, %27, %28, %29, %30, "
      "%31}, "
      "%32, %33, p, 1, 1, 0, 0;\n}\n"
      : "+f"(d[0]), "+f"(d[1]), "+f"(d[2]), "+f"(d[3]), "+f"(d[4]), "+f"(d[5]), "+f"(d[6]), "+f"(d[7]), "+f"(d[8]), "+f"(d[9]), "+f"(d[10]), "+f"(d[11]),
        "+f"(d[12]), "+f"(d[13]), "+f"(d[14]), "+f"(d[15]), "+f"(d[16]), "+f"(d[17]), "+f"(d[18]), "+f"(d[19]), "+f"(d[20]), "+f"(d[21]), "+f"(d[22]),
        "+f"(d[23]), "+f"(d[24]), "+f"(d[25]), "+f"(d[26]), "+f"(d[27]), "+f"(d[28]), "+f"(d[29]), "+f"(d[30]), "+f"(d[31])
      : "l"(da), "l"(db), "r"(scaleD));
}
__device__ __forceinline__ void wgmma_qk_rs(float (&d)[32], uint32_t a0, uint32_t a1, uint32_t a2, uint32_t a3, uint64_t db, int scaleD) {
  asm volatile("{\n.reg .pred p;\nsetp.ne.b32 p, %37, 0;\n"
      "wgmma.mma_async.sync.aligned.m64n64k16.f32.bf16.bf16 "
      "{%0, %1, %2, %3, %4, %5, %6, %7, %8, %9, %10, %11, %12, %13, %14, %15, %16, %17, %18, %19, %20, %21, %22, %23, %24, %25, %26, %27, %28, %29, %30, "
      "%31}, "
      "{%32, %33, %34, %35}, %36, p, 1, 1, 0;\n}\n"
      : "+f"(d[0]), "+f"(d[1]), "+f"(d[2]), "+f"(d[3]), "+f"(d[4]), "+f"(d[5]), "+f"(d[6]), "+f"(d[7]), "+f"(d[8]), "+f"(d[9]), "+f"(d[10]), "+f"(d[11]),
        "+f"(d[12]), "+f"(d[13]), "+f"(d[14]), "+f"(d[15]), "+f"(d[16]), "+f"(d[17]), "+f"(d[18]), "+f"(d[19]), "+f"(d[20]), "+f"(d[21]), "+f"(d[22]),
        "+f"(d[23]), "+f"(d[24]), "+f"(d[25]), "+f"(d[26]), "+f"(d[27]), "+f"(d[28]), "+f"(d[29]), "+f"(d[30]), "+f"(d[31])
      : "r"(a0), "r"(a1), "r"(a2), "r"(a3), "l"(db), "r"(scaleD));
}
__device__ __forceinline__ void wgmma_pv(float (&d)[64], uint32_t a0, uint32_t a1, uint32_t a2, uint32_t a3, uint64_t db, int scaleD) {
  asm volatile("{\n.reg .pred p;\nsetp.ne.b32 p, %69, 0;\n"
      "wgmma.mma_async.sync.aligned.m64n128k16.f32.bf16.bf16 "
      "{%0, %1, %2, %3, %4, %5, %6, %7, %8, %9, %10, %11, %12, %13, %14, %15, %16, %17, %18, %19, %20, %21, %22, %23, %24, %25, %26, %27, %28, %29, %30, "
      "%31, %32, %33, %34, %35, %36, %37, %38, %39, %40, %41, %42, %43, %44, %45, %46, %47, %48, %49, %50, %51, %52, %53, %54, %55, %56, %57, %58, %59, %60, "
      "%61, %62, %63}, "
      "{%64, %65, %66, %67}, %68, p, 1, 1, 1;\n}\n"
      : "+f"(d[0]), "+f"(d[1]), "+f"(d[2]), "+f"(d[3]), "+f"(d[4]), "+f"(d[5]), "+f"(d[6]), "+f"(d[7]), "+f"(d[8]), "+f"(d[9]), "+f"(d[10]), "+f"(d[11]),
        "+f"(d[12]), "+f"(d[13]), "+f"(d[14]), "+f"(d[15]), "+f"(d[16]), "+f"(d[17]), "+f"(d[18]), "+f"(d[19]), "+f"(d[20]), "+f"(d[21]), "+f"(d[22]),
        "+f"(d[23]), "+f"(d[24]), "+f"(d[25]), "+f"(d[26]), "+f"(d[27]), "+f"(d[28]), "+f"(d[29]), "+f"(d[30]), "+f"(d[31]), "+f"(d[32]), "+f"(d[33]),
        "+f"(d[34]), "+f"(d[35]), "+f"(d[36]), "+f"(d[37]), "+f"(d[38]), "+f"(d[39]), "+f"(d[40]), "+f"(d[41]), "+f"(d[42]), "+f"(d[43]), "+f"(d[44]),
        "+f"(d[45]), "+f"(d[46]), "+f"(d[47]), "+f"(d[48]), "+f"(d[49]), "+f"(d[50]), "+f"(d[51]), "+f"(d[52]), "+f"(d[53]), "+f"(d[54]), "+f"(d[55]),
        "+f"(d[56]), "+f"(d[57]), "+f"(d[58]), "+f"(d[59]), "+f"(d[60]), "+f"(d[61]), "+f"(d[62]), "+f"(d[63])
      : "r"(a0), "r"(a1), "r"(a2), "r"(a3), "l"(db), "r"(scaleD));
}
__device__ __forceinline__ void wgmma_qk_sp(float (&d)[32], uint32_t a0, uint32_t a1, uint32_t a2, uint32_t a3, uint64_t db, int scaleD, uint32_t meta) {
  asm volatile("{\n.reg .pred p;\nsetp.ne.b32 p, %37, 0;\n"
      "wgmma.mma_async.sp.sync.aligned.m64n64k32.f32.bf16.bf16 "
      "{%0, %1, %2, %3, %4, %5, %6, %7, %8, %9, %10, %11, %12, %13, %14, %15, %16, %17, %18, %19, %20, %21, %22, %23, %24, %25, %26, %27, %28, %29, %30, "
      "%31}, "
      "{%32, %33, %34, %35}, %36, %38, 0, p, 1, 1, 0;\n}\n"
      : "+f"(d[0]), "+f"(d[1]), "+f"(d[2]), "+f"(d[3]), "+f"(d[4]), "+f"(d[5]), "+f"(d[6]), "+f"(d[7]), "+f"(d[8]), "+f"(d[9]), "+f"(d[10]), "+f"(d[11]),
        "+f"(d[12]), "+f"(d[13]), "+f"(d[14]), "+f"(d[15]), "+f"(d[16]), "+f"(d[17]), "+f"(d[18]), "+f"(d[19]), "+f"(d[20]), "+f"(d[21]), "+f"(d[22]),
        "+f"(d[23]), "+f"(d[24]), "+f"(d[25]), "+f"(d[26]), "+f"(d[27]), "+f"(d[28]), "+f"(d[29]), "+f"(d[30]), "+f"(d[31])
      : "r"(a0), "r"(a1), "r"(a2), "r"(a3), "l"(db), "r"(scaleD), "r"(meta));
}
__device__ __forceinline__ void wgmma_pv_sp(float (&d)[64], uint32_t a0, uint32_t a1, uint32_t a2, uint32_t a3, uint64_t db, int scaleD, uint32_t meta) {
  asm volatile("{\n.reg .pred p;\nsetp.ne.b32 p, %69, 0;\n"
      "wgmma.mma_async.sp.sync.aligned.m64n128k32.f32.bf16.bf16 "
      "{%0, %1, %2, %3, %4, %5, %6, %7, %8, %9, %10, %11, %12, %13, %14, %15, %16, %17, %18, %19, %20, %21, %22, %23, %24, %25, %26, %27, %28, %29, %30, "
      "%31, %32, %33, %34, %35, %36, %37, %38, %39, %40, %41, %42, %43, %44, %45, %46, %47, %48, %49, %50, %51, %52, %53, %54, %55, %56, %57, %58, %59, %60, "
      "%61, %62, %63}, "
      "{%64, %65, %66, %67}, %68, %70, 0, p, 1, 1, 1;\n}\n"
      : "+f"(d[0]), "+f"(d[1]), "+f"(d[2]), "+f"(d[3]), "+f"(d[4]), "+f"(d[5]), "+f"(d[6]), "+f"(d[7]), "+f"(d[8]), "+f"(d[9]), "+f"(d[10]), "+f"(d[11]),
        "+f"(d[12]), "+f"(d[13]), "+f"(d[14]), "+f"(d[15]), "+f"(d[16]), "+f"(d[17]), "+f"(d[18]), "+f"(d[19]), "+f"(d[20]), "+f"(d[21]), "+f"(d[22]),
        "+f"(d[23]), "+f"(d[24]), "+f"(d[25]), "+f"(d[26]), "+f"(d[27]), "+f"(d[28]), "+f"(d[29]), "+f"(d[30]), "+f"(d[31]), "+f"(d[32]), "+f"(d[33]),
        "+f"(d[34]), "+f"(d[35]), "+f"(d[36]), "+f"(d[37]), "+f"(d[38]), "+f"(d[39]), "+f"(d[40]), "+f"(d[41]), "+f"(d[42]), "+f"(d[43]), "+f"(d[44]),
        "+f"(d[45]), "+f"(d[46]), "+f"(d[47]), "+f"(d[48]), "+f"(d[49]), "+f"(d[50]), "+f"(d[51]), "+f"(d[52]), "+f"(d[53]), "+f"(d[54]), "+f"(d[55]),
        "+f"(d[56]), "+f"(d[57]), "+f"(d[58]), "+f"(d[59]), "+f"(d[60]), "+f"(d[61]), "+f"(d[62]), "+f"(d[63])
      : "r"(a0), "r"(a1), "r"(a2), "r"(a3), "l"(db), "r"(scaleD), "r"(meta));
}
__device__ __forceinline__ void wgmma_proj_init(float (&d)[64], uint64_t da, uint64_t db, int scaleD) {
  asm volatile("{\n.reg .pred p;\nsetp.ne.b32 p, %66, 0;\n"
      "wgmma.mma_async.sync.aligned.m64n128k16.f32.bf16.bf16 "
      "{%0, %1, %2, %3, %4, %5, %6, %7, %8, %9, %10, %11, %12, %13, %14, %15, %16, %17, %18, %19, %20, %21, %22, %23, %24, %25, %26, %27, %28, %29, %30, "
      "%31, %32, %33, %34, %35, %36, %37, %38, %39, %40, %41, %42, %43, %44, %45, %46, %47, %48, %49, %50, %51, %52, %53, %54, %55, %56, %57, %58, %59, %60, "
      "%61, %62, %63}, "
      "%64, %65, p, 1, 1, 0, 1;\n}\n"
      : "=f"(d[0]), "=f"(d[1]), "=f"(d[2]), "=f"(d[3]), "=f"(d[4]), "=f"(d[5]), "=f"(d[6]), "=f"(d[7]), "=f"(d[8]), "=f"(d[9]), "=f"(d[10]), "=f"(d[11]),
        "=f"(d[12]), "=f"(d[13]), "=f"(d[14]), "=f"(d[15]), "=f"(d[16]), "=f"(d[17]), "=f"(d[18]), "=f"(d[19]), "=f"(d[20]), "=f"(d[21]), "=f"(d[22]),
        "=f"(d[23]), "=f"(d[24]), "=f"(d[25]), "=f"(d[26]), "=f"(d[27]), "=f"(d[28]), "=f"(d[29]), "=f"(d[30]), "=f"(d[31]), "=f"(d[32]), "=f"(d[33]),
        "=f"(d[34]), "=f"(d[35]), "=f"(d[36]), "=f"(d[37]), "=f"(d[38]), "=f"(d[39]), "=f"(d[40]), "=f"(d[41]), "=f"(d[42]), "=f"(d[43]), "=f"(d[44]),
        "=f"(d[45]), "=f"(d[46]), "=f"(d[47]), "=f"(d[48]), "=f"(d[49]), "=f"(d[50]), "=f"(d[51]), "=f"(d[52]), "=f"(d[53]), "=f"(d[54]), "=f"(d[55]),
        "=f"(d[56]), "=f"(d[57]), "=f"(d[58]), "=f"(d[59]), "=f"(d[60]), "=f"(d[61]), "=f"(d[62]), "=f"(d[63])
      : "l"(da), "l"(db), "r"(scaleD));
}
__device__ __forceinline__ void wgmma_proj96_init(float (&d)[64], uint64_t da, uint64_t db, int scaleD) {
  asm volatile("{\n.reg .pred p;\nsetp.ne.b32 p, %50, 0;\n"
      "wgmma.mma_async.sync.aligned.m64n96k16.f32.bf16.bf16 "
      "{%0, %1, %2, %3, %4, %5, %6, %7, %8, %9, %10, %11, %12, %13, %14, %15, %16, %17, %18, %19, %20, %21, %22, %23, %24, %25, %26, %27, %28, %29, %30, "
      "%31, %32, %33, %34, %35, %36, %37, %38, %39, %40, %41, %42, %43, %44, %45, %46, %47}, "
      "%48, %49, p, 1, 1, 1, 0;\n}\n"
      : "=f"(d[0]), "=f"(d[1]), "=f"(d[2]), "=f"(d[3]), "=f"(d[4]), "=f"(d[5]), "=f"(d[6]), "=f"(d[7]), "=f"(d[8]), "=f"(d[9]), "=f"(d[10]), "=f"(d[11]),
        "=f"(d[12]), "=f"(d[13]), "=f"(d[14]), "=f"(d[15]), "=f"(d[16]), "=f"(d[17]), "=f"(d[18]), "=f"(d[19]), "=f"(d[20]), "=f"(d[21]), "=f"(d[22]),
        "=f"(d[23]), "=f"(d[24]), "=f"(d[25]), "=f"(d[26]), "=f"(d[27]), "=f"(d[28]), "=f"(d[29]), "=f"(d[30]), "=f"(d[31]), "=f"(d[32]), "=f"(d[33]),
        "=f"(d[34]), "=f"(d[35]), "=f"(d[36]), "=f"(d[37]), "=f"(d[38]), "=f"(d[39]), "=f"(d[40]), "=f"(d[41]), "=f"(d[42]), "=f"(d[43]), "=f"(d[44]),
        "=f"(d[45]), "=f"(d[46]), "=f"(d[47])
      : "l"(da), "l"(db), "r"(scaleD));
}
__device__ __forceinline__ void wgmma_qk_init(float (&d)[32], uint64_t da, uint64_t db, int scaleD) {
  asm volatile("{\n.reg .pred p;\nsetp.ne.b32 p, %34, 0;\n"
      "wgmma.mma_async.sync.aligned.m64n64k16.f32.bf16.bf16 "
      "{%0, %1, %2, %3, %4, %5, %6, %7, %8, %9, %10, %11, %12, %13, %14, %15, %16, %17, %18, %19, %20, %21, %22, %23, %24, %25, %26, %27, %28, %29, %30, "
      "%31}, "
      "%32, %33, p, 1, 1, 0, 0;\n}\n"
      : "=f"(d[0]), "=f"(d[1]), "=f"(d[2]), "=f"(d[3]), "=f"(d[4]), "=f"(d[5]), "=f"(d[6]), "=f"(d[7]), "=f"(d[8]), "=f"(d[9]), "=f"(d[10]), "=f"(d[11]),
        "=f"(d[12]), "=f"(d[13]), "=f"(d[14]), "=f"(d[15]), "=f"(d[16]), "=f"(d[17]), "=f"(d[18]), "=f"(d[19]), "=f"(d[20]), "=f"(d[21]), "=f"(d[22]),
        "=f"(d[23]), "=f"(d[24]), "=f"(d[25]), "=f"(d[26]), "=f"(d[27]), "=f"(d[28]), "=f"(d[29]), "=f"(d[30]), "=f"(d[31])
      : "l"(da), "l"(db), "r"(scaleD));
}
__device__ __forceinline__ void wgmma_qk_rs_init(float (&d)[32], uint32_t a0, uint32_t a1, uint32_t a2, uint32_t a3, uint64_t db, int scaleD) {
  asm volatile("{\n.reg .pred p;\nsetp.ne.b32 p, %37, 0;\n"
      "wgmma.mma_async.sync.aligned.m64n64k16.f32.bf16.bf16 "
      "{%0, %1, %2, %3, %4, %5, %6, %7, %8, %9, %10, %11, %12, %13, %14, %15, %16, %17, %18, %19, %20, %21, %22, %23, %24, %25, %26, %27, %28, %29, %30, "
      "%31}, "
      "{%32, %33, %34, %35}, %36, p, 1, 1, 0;\n}\n"
      : "=f"(d[0]), "=f"(d[1]), "=f"(d[2]), "=f"(d[3]), "=f"(d[4]), "=f"(d[5]), "=f"(d[6]), "=f"(d[7]), "=f"(d[8]), "=f"(d[9]), "=f"(d[10]), "=f"(d[11]),
        "=f"(d[12]), "=f"(d[13]), "=f"(d[14]), "=f"(d[15]), "=f"(d[16]), "=f"(d[17]), "=f"(d[18]), "=f"(d[19]), "=f"(d[20]), "=f"(d[21]), "=f"(d[22]),
        "=f"(d[23]), "=f"(d[24]), "=f"(d[25]), "=f"(d[26]), "=f"(d[27]), "=f"(d[28]), "=f"(d[29]), "=f"(d[30]), "=f"(d[31])
      : "r"(a0), "r"(a1), "r"(a2), "r"(a3), "l"(db), "r"(scaleD));
}
__device__ __forceinline__ void wgmma_pv_init(float (&d)[64], uint32_t a0, uint32_t a1, uint32_t a2, uint32_t a3, uint64_t db, int scaleD) {
  asm volatile("{\n.reg .pred p;\nsetp.ne.b32 p, %69, 0;\n"
      "wgmma.mma_async.sync.aligned.m64n128k16.f32.bf16.bf16 "
      "{%0, %1, %2, %3, %4, %5, %6, %7, %8, %9, %10, %11, %12, %13, %14, %15, %16, %17, %18, %19, %20, %21, %22, %23, %24, %25, %26, %27, %28, %29, %30, "
      "%31, %32, %33, %34, %35, %36, %37, %38, %39, %40, %41, %42, %43, %44, %45, %46, %47, %48, %49, %50, %51, %52, %53, %54, %55, %56, %57, %58, %59, %60, "
      "%61, %62, %63}, "
      "{%64, %65, %66, %67}, %68, p, 1, 1, 1;\n}\n"
      : "=f"(d[0]), "=f"(d[1]), "=f"(d[2]), "=f"(d[3]), "=f"(d[4]), "=f"(d[5]), "=f"(d[6]), "=f"(d[7]), "=f"(d[8]), "=f"(d[9]), "=f"(d[10]), "=f"(d[11]),
        "=f"(d[12]), "=f"(d[13]), "=f"(d[14]), "=f"(d[15]), "=f"(d[16]), "=f"(d[17]), "=f"(d[18]), "=f"(d[19]), "=f"(d[20]), "=f"(d[21]), "=f"(d[22]),
        "=f"(d[23]), "=f"(d[24]), "=f"(d[25]), "=f"(d[26]), "=f"(d[27]), "=f"(d[28]), "=f"(d[29]), "=f"(d[30]), "=f"(d[31]), "=f"(d[32]), "=f"(d[33]),
        "=f"(d[34]), "=f"(d[35]), "=f"(d[36]), "=f"(d[37]), "=f"(d[38]), "=f"(d[39]), "=f"(d[40]), "=f"(d[41]), "=f"(d[42]), "=f"(d[43]), "=f"(d[44]),
        "=f"(d[45]), "=f"(d[46]), "=f"(d[47]), "=f"(d[48]), "=f"(d[49]), "=f"(d[50]), "=f"(d[51]), "=f"(d[52]), "=f"(d[53]), "=f"(d[54]), "=f"(d[55]),
        "=f"(d[56]), "=f"(d[57]), "=f"(d[58]), "=f"(d[59]), "=f"(d[60]), "=f"(d[61]), "=f"(d[62]), "=f"(d[63])
      : "r"(a0), "r"(a1), "r"(a2), "r"(a3), "l"(db), "r"(scaleD));
}
__device__ __forceinline__ void wgmma_qk_sp_init(float (&d)[32], uint32_t a0, uint32_t a1, uint32_t a2, uint32_t a3, uint64_t db, int scaleD, uint32_t meta) {
  asm volatile("{\n.reg .pred p;\nsetp.ne.b32 p, %37, 0;\n"
      "wgmma.mma_async.sp.sync.aligned.m64n64k32.f32.bf16.bf16 "
      "{%0, %1, %2, %3, %4, %5, %6, %7, %8, %9, %10, %11, %12, %13, %14, %15, %16, %17, %18, %19, %20, %21, %22, %23, %24, %25, %26, %27, %28, %29, %30, "
      "%31}, "
      "{%32, %33, %34, %35}, %36, %38, 0, p, 1, 1, 0;\n}\n"
      : "=f"(d[0]), "=f"(d[1]), "=f"(d[2]), "=f"(d[3]), "=f"(d[4]), "=f"(d[5]), "=f"(d[6]), "=f"(d[7]), "=f"(d[8]), "=f"(d[9]), "=f"(d[10]), "=f"(d[11]),
        "=f"(d[12]), "=f"(d[13]), "=f"(d[14]), "=f"(d[15]), "=f"(d[16]), "=f"(d[17]), "=f"(d[18]), "=f"(d[19]), "=f"(d[20]), "=f"(d[21]), "=f"(d[22]),
        "=f"(d[23]), "=f"(d[24]), "=f"(d[25]), "=f"(d[26]), "=f"(d[27]), "=f"(d[28]), "=f"(d[29]), "=f"(d[30]), "=f"(d[31])
      : "r"(a0), "r"(a1), "r"(a2), "r"(a3), "l"(db), "r"(scaleD), "r"(meta));
}
__device__ __forceinline__ void wgmma_pv_sp_init(float (&d)[64], uint32_t a0, uint32_t a1, uint32_t a2, uint32_t a3, uint64_t db, int scaleD, uint32_t meta) {
  asm volatile("{\n.reg .pred p;\nsetp.ne.b32 p, %69, 0;\n"
      "wgmma.mma_async.sp.sync.aligned.m64n128k32.f32.bf16.bf16 "
      "{%0, %1, %2, %3, %4, %5, %6, %7, %8, %9, %10, %11, %12, %13, %14, %15, %16, %17, %18, %19, %20, %21, %22, %23, %24, %25, %26, %27, %28, %29, %30, "
      "%31, %32, %33, %34, %35, %36, %37, %38, %39, %40, %41, %42, %43, %44, %45, %46, %47, %48, %49, %50, %51, %52, %53, %54, %55, %56, %57, %58, %59, %60, "
      "%61, %62, %63}, "
      "{%64, %65, %66, %67}, %68, %70, 0, p, 1, 1, 1;\n}\n"
      : "=f"(d[0]), "=f"(d[1]), "=f"(d[2]), "=f"(d[3]), "=f"(d[4]), "=f"(d[5]), "=f"(d[6]), "=f"(d[7]), "=f"(d[8]), "=f"(d[9]), "=f"(d[10]), "=f"(d[11]),
        "=f"(d[12]), "=f"(d[13]), "=f"(d[14]), "=f"(d[15]), "=f"(d[16]), "=f"(d[17]), "=f"(d[18]), "=f"(d[19]), "=f"(d[20]), "=f"(d[21]), "=f"(d[22]),
        "=f"(d[23]), "=f"(d[24]), "=f"(d[25]), "=f"(d[26]), "=f"(d[27]), "=f"(d[28]), "=f"(d[29]), "=f"(d[30]), "=f"(d[31]), "=f"(d[32]), "=f"(d[33]),
        "=f"(d[34]), "=f"(d[35]), "=f"(d[36]), "=f"(d[37]), "=f"(d[38]), "=f"(d[39]), "=f"(d[40]), "=f"(d[41]), "=f"(d[42]), "=f"(d[43]), "=f"(d[44]),
        "=f"(d[45]), "=f"(d[46]), "=f"(d[47]), "=f"(d[48]), "=f"(d[49]), "=f"(d[50]), "=f"(d[51]), "=f"(d[52]), "=f"(d[53]), "=f"(d[54]), "=f"(d[55]),
        "=f"(d[56]), "=f"(d[57]), "=f"(d[58]), "=f"(d[59]), "=f"(d[60]), "=f"(d[61]), "=f"(d[62]), "=f"(d[63])
      : "r"(a0), "r"(a1), "r"(a2), "r"(a3), "l"(db), "r"(scaleD), "r"(meta));
}

constexpr int NB = 16, SQ = 224, DM = 640, NH = 32, SK = 1024, DH = 128;
constexpr int HD = NH * DH;
constexpr int NBETA = 2 * NB;
constexpr int NCTA = 132;
constexpr uint32_t SB0 = 1024;
constexpr int NS = 10;
constexpr int SLOT = 16384;
constexpr int QBUF_OFF = NS * SLOT;
constexpr int NSX = NS + 4;
constexpr int BAR_OFF = NSX * SLOT;
constexpr int BAR_FULL = BAR_OFF;
constexpr int BAR_EMPTY = BAR_OFF + 8 * NSX;
constexpr int BAR_STG = BAR_OFF + 16 * NSX;
constexpr int BAR_OUT = BAR_STG + 32;
constexpr int BAR_DESC = BAR_OUT + 8;
constexpr int BAR_GO = BAR_DESC + 8;
constexpr int BAR_MAIL = BAR_GO + 8;
constexpr int BAR_RDY = BAR_MAIL + 8;
constexpr int DESC_OFF = BAR_RDY + 8 * NSX;
constexpr int EPOCH_OFF = DESC_OFF + 16;
constexpr int TRACE_OFF = EPOCH_OFF + 16;
constexpr int SMEM_BYTES = TRACE_OFF;
constexpr float SM_C = 0.08838834764831845f * 1.4426950408889634f;
constexpr float SUM_HI = 1099511627776.f, SUM_LO = 1.f / 1099511627776.f;
constexpr uint32_t META_QK = 0xEEEE4444u;
constexpr uint32_t META_PV = 0x44EEEE44u;

#define QK_EARLY_MASK 3
#define ST_ORDER 0x2310
#define LAG_BAR 3
#define ST_NOW 8
#define PF_STEP 5
#define KV_WIN_UNITS 2
#define KV_WIN_D 4
#define SF 0xfe3f
#define O_STEPS 4
#define KV_WIN_RAMP 4
#define PDEPTH 0
#define KV_WIN_TILES -2
#define PR_KV 2
#define PR_X 2
#define PR_W 2
#define REG_C 232
#define REG_P 24
#define GO_P 4
#define P_POS 216
#define OR 6
#define OR0 0
#define B_LATE 23
#define H_LATE 24
#define RM0 1
#define RM1 0xd5
#define RM2 0
#define CLUSTER 1
#define PAIRB 1
#define LATE0 0
#define LATE1 0
#define KG 5
#define PK 44
#define EARLY_MASK 0x3fffu
#define PIECE_TABLE 0x50188016,0x65e88038,0x50321819,0x6c8d1830,0x403f2812,0x80000000,0x50215014,0x695a503c,0x5029b813,0x6c4eb85e,0x501b4815,0x689d4834,0x502b1017,0x6ccc1039,0x50312010,0x80000000,0x500e681b,0x65e8683f,0x502ea011,0x80000000,0x63b1902e,0x80000000,0x63f0603b,0x80000000,0x64ad003d,0x80000000,0x64eca83a,0x80000000,0x5024581c,0x80000000,0x5012b01a,0x6a95b033,0x5011081d,0x6b130837,0x5016701f,0x6c8d7056,0x501ec81e,0x80000000,0x6723302f,0x80000000,0x501b380f,0x80000000,0x67234035,0x80000000,0x500d980e,0x6bd09831,0x56587816,0x80000000,0x50168818,0x80000000,0x57d1c01e,0x80000000

struct Params {
  CUtensorMap x[2][2], wq[2], kv[2][2], wo[2];
  CUtensorMap o_ld[2], o_st[2], out_st[2];
  const __nv_bfloat16* kp[2];
  const __nv_bfloat16* vp[2];
};

constexpr int NPART = 32 * 5, O_BLOCKS = NBETA * 64 + 2 * NPART;
__device__ __align__(128) __nv_bfloat16 g_o[(size_t)O_BLOCKS * SQ * 64];
__device__ unsigned g_cnt[NBETA][8];
__device__ unsigned g_rd[NBETA][8];
__device__ unsigned g_epoch, g_next;
__device__ unsigned g_flag[NPART];

__device__ __forceinline__ uint32_t smem_u32(const void* p) { return (uint32_t)__cvta_generic_to_shared(p); }
__device__ __forceinline__ void mbar_arrive(uint32_t bar) {
  asm volatile("mbarrier.arrive.shared::cta.b64 _, [%0];" ::"r"(bar) : "memory");
}
__device__ __forceinline__ void mbar_arrive_warp(uint32_t bar) {
  asm volatile("{\n.reg .pred p;\nelect.sync _|p, 0xffffffff;\n@p mbarrier.arrive.shared::cta.b64 _, [%0];\n}" ::"r"(bar) : "memory");
}
__device__ __forceinline__ int lane_now() { int l; asm volatile("mov.u32 %0, %%laneid;" : "=r"(l)); return l; }
__device__ __forceinline__ bool mbar_try(uint32_t bar, uint32_t parity) {
  uint32_t ok;
  asm volatile("{\n.reg .pred p;\nmbarrier.try_wait.parity.shared::cta.b64 p, [%1], %2;\nselp.u32 %0, 1, 0, p;\n}"
               : "=r"(ok) : "r"(bar), "r"(parity) : "memory");
  return ok;
}
__device__ __forceinline__ bool mbar_test(uint32_t bar, uint32_t parity) {
  uint32_t ok;
  asm volatile("{\n.reg .pred p;\nmbarrier.test_wait.parity.shared::cta.b64 p, [%1], %2;\nselp.u32 %0, 1, 0, p;\n}"
               : "=r"(ok) : "r"(bar), "r"(parity) : "memory");
  return ok;
}
__device__ __forceinline__ void mbar_wait_w(uint32_t bar, uint32_t parity) {
  uint32_t n = 0;
  while (!__all_sync(0xffffffffu, mbar_try(bar, parity))) {
    if (++n > (1u << 22)) __trap();
  }
}
#define ELECT "{\n.reg .pred p;\nelect.sync _|p, 0xffffffff;\n@p "
__device__ __forceinline__ void tma_st3_hint_w(const CUtensorMap* m, uint32_t src, int c0, int c1, int c2, uint64_t pol) {
  asm volatile(ELECT "cp.async.bulk.tensor.3d.global.shared::cta.bulk_group.L2::cache_hint [%0, {%2, %3, %4}], [%1], %5;\n}"
               ::"l"(m), "r"(src), "r"(c0), "r"(c1), "r"(c2), "l"(pol) : "memory");
}
#define EXPECT(bar, bytes) "mbarrier.arrive.expect_tx.shared::cta.b64 _, [" bar "], " bytes ";\n@p "
__device__ __forceinline__ void tma_ld2_w(uint32_t dst, const CUtensorMap* m, int c0, int c1, uint32_t bar, uint32_t bytes) {
  asm volatile(ELECT EXPECT("%2", "%5") "cp.async.bulk.tensor.2d.shared::cluster.global.mbarrier::complete_tx::bytes [%0], [%1, {%3, %4}], [%2];\n}"
               ::"r"(dst), "l"(m), "r"(bar), "r"(c0), "r"(c1), "r"(bytes) : "memory");
}
__device__ __forceinline__ void tma_ld2_hint_w(uint32_t dst, const CUtensorMap* m, int c0, int c1, uint32_t bar, uint32_t bytes, uint64_t pol) {
  asm volatile(ELECT EXPECT("%2", "%6") "cp.async.bulk.tensor.2d.shared::cluster.global.mbarrier::complete_tx::bytes.L2::cache_hint"
               " [%0], [%1, {%3, %4}], [%2], %5;\n}"
               ::"r"(dst), "l"(m), "r"(bar), "r"(c0), "r"(c1), "l"(pol), "r"(bytes) : "memory");
}
__device__ __forceinline__ void tma_ld3_w(uint32_t dst, const CUtensorMap* m, int c0, int c1, int c2, uint32_t bar, uint32_t bytes) {
  asm volatile(ELECT EXPECT("%2", "%6") "cp.async.bulk.tensor.3d.shared::cluster.global.mbarrier::complete_tx::bytes [%0], [%1, {%3, %4, %5}], [%2];\n}"
               ::"r"(dst), "l"(m), "r"(bar), "r"(c0), "r"(c1), "r"(c2), "r"(bytes) : "memory");
}
__device__ __forceinline__ void tma_ld3_hint_w(uint32_t dst, const CUtensorMap* m, int c0, int c1, int c2, uint32_t bar, uint64_t pol) {
  asm volatile(ELECT EXPECT("%2", "16384") "cp.async.bulk.tensor.3d.shared::cluster.global.mbarrier::complete_tx::bytes.L2::cache_hint"
               " [%0], [%1, {%3, %4, %5}], [%2], %6;\n}"
               ::"r"(dst), "l"(m), "r"(bar), "r"(c0), "r"(c1), "r"(c2), "l"(pol) : "memory");
}
__device__ __forceinline__ void tma_ld_wo_w(uint32_t dst, const CUtensorMap* m, int col, int grp, uint32_t bar) {
  asm volatile(ELECT EXPECT("%2", "16384") "cp.async.bulk.tensor.5d.shared::cluster.global.mbarrier::complete_tx::bytes [%0], [%1, {%3, 0, 0, 0, %4}], [%2];\n"
               "@p cp.async.bulk.tensor.5d.shared::cluster.global.mbarrier::complete_tx::bytes [%5], [%1, {%6, 0, 0, 0, %4}], [%2];\n}"
               ::"r"(dst), "l"(m), "r"(bar), "r"(col), "r"(grp), "r"(dst + 8192), "r"(col + 64) : "memory");
}
__device__ __forceinline__ void mbar_arrive8_w(uint32_t bar) {
  asm volatile(ELECT "mbarrier.arrive.shared::cta.b64 _, [%0], 8;\n}" ::"r"(bar) : "memory");
}
__device__ __forceinline__ uint32_t peer(uint32_t a) { uint32_t r; asm("mapa.shared::cluster.u32 %0, %1, %2;" : "=r"(r) : "r"(a), "r"(~blockIdx.x & 1)); return r; }
__device__ __forceinline__ void tma_ld2_both_w(uint32_t dst, const CUtensorMap* m, int c0, int c1, uint32_t bar, uint32_t bytes) {
  asm volatile(ELECT EXPECT("%2", "%5") "cp.async.bulk.tensor.2d.shared::cluster.global.mbarrier::complete_tx::bytes.multicast::cluster"
               " [%0], [%1, {%3, %4}], [%2], %6;\n}"
               ::"r"(dst), "l"(m), "r"(bar), "r"(c0), "r"(c1), "r"(bytes), "h"((uint16_t)3) : "memory");
}
__device__ __forceinline__ void tma_ld2_both_hint_w(uint32_t dst, const CUtensorMap* m, int c0, int c1, uint32_t bar, uint32_t bytes, uint64_t pol) {
  asm volatile(ELECT EXPECT("%2", "%6") "cp.async.bulk.tensor.2d.shared::cluster.global.mbarrier::complete_tx::bytes.multicast::cluster.L2::cache_hint"
               " [%0], [%1, {%3, %4}], [%2], %7, %5;\n}"
               ::"r"(dst), "l"(m), "r"(bar), "r"(c0), "r"(c1), "l"(pol), "r"(bytes), "h"((uint16_t)3) : "memory");
}
__device__ __forceinline__ void bulk_commit() { asm volatile("cp.async.bulk.commit_group;" ::: "memory"); }
template <int N> __device__ __forceinline__ void bulk_wait_read() { asm volatile("cp.async.bulk.wait_group.read %0;" ::"n"(N) : "memory"); }
__device__ __forceinline__ void wg_fence() { asm volatile("wgmma.fence.sync.aligned;" ::: "memory"); }
__device__ __forceinline__ void wg_commit() { asm volatile("wgmma.commit_group.sync.aligned;" ::: "memory"); }
template <int N> __device__ __forceinline__ void wg_wait() { asm volatile("wgmma.wait_group.sync.aligned %0;" ::"n"(N) : "memory"); }
__device__ __forceinline__ void fence_async_smem() { asm volatile("fence.proxy.async.shared::cta;" ::: "memory"); }
__device__ __forceinline__ void bar_sync(int id, int n) { asm volatile("bar.sync %0, %1;" ::"r"(id), "r"(n) : "memory"); }
__device__ __forceinline__ void touch(float& a) { asm volatile("neg.f32 %0, %0;" : "+f"(a)); }
__device__ __forceinline__ void touch(uint32_t& a) { asm volatile("not.b32 %0, %0;" : "+r"(a)); }
template <typename T, int N> __device__ __forceinline__ void touch(T (&a)[N]) {
#pragma unroll
  for (int i = 0; i < N; i++) touch(a[i]);
}
template <int ID, typename... A> __device__ __forceinline__ void sched_fence(uint32_t x, A&... a) {
  if (!((SF >> ID) & 1)) return;
  asm volatile("" : "+r"(x)::"memory");
#pragma unroll 1
  for (; __builtin_expect(x >= 100 + ID, 0); x >>= 1) { (touch(a), ...); __nanosleep(x); }
}
template <int N> __device__ __forceinline__ void reg_fence(float (&a)[N]) {
#pragma unroll
  for (int i = 0; i < N; i++) asm volatile("" : "+f"(a[i])::"memory");
}
template <int N> __device__ __forceinline__ void reg_fence(uint32_t (&a)[N]) {
#pragma unroll
  for (int i = 0; i < N; i++) asm volatile("" : "+r"(a[i])::"memory");
}
__device__ __forceinline__ float ex2(float x) { float y; asm("ex2.approx.ftz.f32 %0, %1;" : "=f"(y) : "f"(x)); return y; }
__device__ __forceinline__ uint32_t pack_bf16(float lo, float hi) {
  uint32_t r; asm("cvt.rn.bf16x2.f32 %0, %1, %2;" : "=r"(r) : "f"(hi), "f"(lo)); return r;
}
__device__ __forceinline__ void stsm4(uint32_t a, uint32_t r0, uint32_t r1, uint32_t r2, uint32_t r3) {
  asm volatile("stmatrix.sync.aligned.m8n8.x4.shared.b16 [%0], {%1, %2, %3, %4};" ::"r"(a), "r"(r0), "r"(r1), "r"(r2), "r"(r3) : "memory");
}
__device__ __forceinline__ void stsm4t(uint32_t a, uint32_t r0, uint32_t r1, uint32_t r2, uint32_t r3) {
  asm volatile("stmatrix.sync.aligned.m8n8.x4.trans.shared.b16 [%0], {%1, %2, %3, %4};" ::"r"(a), "r"(r0), "r"(r1), "r"(r2), "r"(r3) : "memory");
}
__device__ __forceinline__ void ldsm4(uint32_t a, uint32_t& r0, uint32_t& r1, uint32_t& r2, uint32_t& r3) {
  asm volatile("ldmatrix.sync.aligned.m8n8.x4.shared.b16 {%0, %1, %2, %3}, [%4];" : "=r"(r0), "=r"(r1), "=r"(r2), "=r"(r3) : "r"(a) : "memory");
}
__device__ __forceinline__ void sts16(uint32_t a, uint32_t v) { asm volatile("st.shared.u16 [%0], %1;" ::"r"(a), "h"((uint16_t)v) : "memory"); }
__device__ __forceinline__ void mma16816(float& c0, float& c1, float& c2, float& c3, uint32_t a0, uint32_t a1, uint32_t a2, uint32_t a3,
                                         uint32_t b0, uint32_t b1) {
  asm volatile("mma.sync.aligned.m16n8k16.row.col.f32.bf16.bf16.f32 {%0, %1, %2, %3}, {%4, %5, %6, %7}, {%8, %9}, {%0, %1, %2, %3};"
               : "+f"(c0), "+f"(c1), "+f"(c2), "+f"(c3) : "r"(a0), "r"(a1), "r"(a2), "r"(a3), "r"(b0), "r"(b1));
}
__device__ __forceinline__ uint32_t sdesc(uint32_t addr, uint32_t lbo) { return (addr >> 4) + ((lbo >> 4) << 16); }
__device__ __forceinline__ uint64_t desc64(uint32_t lo, uint32_t hi) { uint64_t d; asm("mov.b64 %0, {%1, %2};" : "=l"(d) : "r"(lo), "r"(hi)); return d; }
__device__ __forceinline__ void dadd(uint64_t& d, uint32_t inc) {
  asm("{\n.reg .b32 l, h;\nmov.b64 {l, h}, %0;\nadd.u32 l, l, %1;\nmov.b64 %0, {l, h};\n}" : "+l"(d) : "r"(inc));
}

struct Ring {
  uint32_t slot, phase, xp;
  __device__ __forceinline__ void uniform() {
    slot = __shfl_sync(0xffffffffu, slot, 0); phase = __shfl_sync(0xffffffffu, phase, 0); xp = __shfl_sync(0xffffffffu, xp, 0);
  }
  __device__ __forceinline__ void next() { if (++slot == NS) { slot = 0; phase ^= 1; } }
  __device__ __forceinline__ void next_if(bool p) { slot += p; if (slot == NS) { slot = 0; phase ^= 1; } }
};
__device__ __forceinline__ uint32_t borrow(int ks, int n) {
  const int k = ks + 1;
  return k >= 4 && !(k & 2) && k < n ? k & 1 : 2;
}

constexpr uint32_t Q_RANGES = NBETA * NH + __builtin_popcount(EARLY_MASK) * 5, Q_ALL = NBETA * (NH + 5);
constexpr int NRANGE = NCTA / 5;
struct Work { int kind, mode, k0, nsteps, range, beta, sub; };
struct Sched { uint16_t queue[Q_ALL]; uint32_t piece[NRANGE + 1][4]; };
constexpr Sched make_sched() {
  Sched s{};
  int q = 0, a = 0;
  for (int t = 0, e = 0; a < NBETA * NH; t++) {
    for (; e < NBETA && 8 * (e & ~PAIRB) + PK <= t && a >= P_POS; e++)
      for (int col = 0; col < 5 && (EARLY_MASK >> e & 1); col++) s.queue[q++] = 0x8000 | (e & 1 ? 4 - col : col) << 8 | e;
    for (int b = 0; b < NBETA; b++)
      for (int h = 0; h < NH; h++)
        if ((b >= B_LATE && h >= H_LATE ? 300 + b : 8 * (b & ~PAIRB) + KG * (h >> 2)) == t) { s.queue[q++] = b << 5 | h; a++; }
  }
  for (int b = 0; b < NBETA; b++)
    for (int col = 0; col < 5 && !(EARLY_MASK >> b & 1); col++) s.queue[q++] = 0x8000 | col << 8 | b;
  constexpr uint32_t T[NRANGE * 2] = {PIECE_TABLE};
  for (int g = 0; g <= NRANGE; g++)
    for (int n = 0; n < 4; n++) s.piece[g][n] = g < NRANGE && n < 2 ? T[2 * g + n] : 2u << 30;
  return s;
}
__constant__ Sched c_sched = make_sched();
constexpr int N_EARLY = __builtin_popcount(EARLY_MASK);
constexpr bool reuse_ok() {
  const Sched s = make_sched();
  int first[NBETA + OR] = {};
  for (int q = Q_RANGES - 1; q >= 0; q--) if (!(s.queue[q] & 0x8000)) first[s.queue[q] >> 5] = q;
  for (int q = 0; q < Q_RANGES; q++) if ((s.queue[q] & 0x8000) && (s.queue[q] & 31) >= OR0 && q - first[(s.queue[q] & 31) + OR] > NCTA - 32) return false;
  return true;
}
static_assert(reuse_ok());
template <bool SIMPLE> __device__ __forceinline__ bool o_reuse(uint32_t b) { return !SIMPLE && b - (OR0 + OR) < N_EARLY - OR0; }
template <bool SIMPLE> __device__ __forceinline__ uint32_t o_slot(uint32_t b) { return o_reuse<SIMPLE>(b) ? OR0 + (b - OR0) % OR : b; }
__device__ __forceinline__ Work decode(uint32_t d) {
  Work w;
  w.kind = d >> 30; if (w.kind == 3) w.kind = 1;
  w.mode = (d >> 28) & 3; w.k0 = (d >> 22) & 63;
  if (w.kind == 0) { w.beta = (d >> 5) & 31; w.sub = d & 31; w.nsteps = DM / 64; }
  else { w.beta = d & 31; w.sub = (d >> 8) & 7; w.nsteps = ((d >> 16) & 63) + 1; }
  w.range = ((d >> 11) & 31) * 5 + w.sub;
  return w;
}

__device__ __forceinline__ bool reached(const unsigned* cnt, unsigned target) {
  unsigned v;
  asm volatile("ld.acquire.gpu.global.u32 %0, [%1];" : "=r"(v) : "l"(cnt) : "memory");
  return (int)(v - target) >= 0;
}
__device__ __forceinline__ void wait_count(const unsigned* cnt, unsigned target) {
  unsigned n = 0;
  while (!__all_sync(0xffffffffu, reached(cnt, target))) { if (++n > (1u << 24)) __trap(); }
}
__device__ __forceinline__ uint32_t lds(uint32_t a) { uint32_t v; asm volatile("ld.volatile.shared.u32 %0, [%1];" : "=r"(v) : "r"(a) : "memory"); return v; }

#define TRACE(u, e)
#define T3(u, e)
#define T2C(u, e)
#define T2P(u, r, e)
#define TTAIL(k)
#define TCLK(k)
#define TO -1
#define TRACE_O(k) if (TO == k) TRACE(i, 5)
#define TRACE_P(u, e)
#define TRACE_IN(u, e)

struct Ctx {
  uint32_t sb;
  int wg, warp;
  uint32_t mqk, mpv;
  bool lead;
  int lane0, lane;
  int src;
};
template <int N> __device__ __forceinline__ uint32_t dhi(uint32_t lo) { return 0x40000040u + (lo >> (26 + N)); }
__device__ __forceinline__ void release(const Ctx& c, uint32_t slot) {
  if (c.lead) mbar_arrive(c.sb + BAR_EMPTY + slot * 8);
}
__device__ __forceinline__ uint32_t acquire(const Ctx& c, Ring& r, bool have = false) {
  const uint32_t s = r.slot;
  if (!have) mbar_wait_w(c.sb + BAR_FULL + s * 8, r.phase);
  r.next();
  return s;
}
__device__ __forceinline__ void mbar_wait2_w(uint32_t b0, uint32_t p0, uint32_t b1, uint32_t p1) {
  uint32_t n = 0;
  while (!__all_sync(0xffffffffu, mbar_try(b0, p0) & mbar_try(b1, p1))) {
    if (++n > (1u << 22)) __trap();
  }
}
__device__ __forceinline__ void mbar_wait3_w(uint32_t b0, uint32_t p0, uint32_t b1, uint32_t p1, uint32_t b2, uint32_t p2) {
  uint32_t n = 0;
  while (!__all_sync(0xffffffffu, mbar_try(b0, p0) & mbar_try(b1, p1) & mbar_try(b2, p2))) {
    if (++n > (1u << 22)) __trap();
  }
}
__device__ __forceinline__ void acquire2(const Ctx& c, Ring& r, uint32_t& s0, uint32_t& s1, bool have = false) {
  const uint32_t p0 = r.phase;
  s0 = r.slot; r.next(); s1 = r.slot;
  if (!have) mbar_wait2_w(c.sb + BAR_FULL + s0 * 8, p0, c.sb + BAR_FULL + s1 * 8, r.phase);
  r.next();
}
template <int N>
__device__ __forceinline__ bool peek(const Ctx& c, Ring r) {
  bool ok = true;
#pragma unroll
  for (int k = 0; k < N; k++) { ok &= mbar_test(c.sb + BAR_FULL + r.slot * 8, r.phase); r.next(); }
  return ok;
}
__device__ __forceinline__ void staged(const Ctx& c, int part) {
  fence_async_smem();
  __syncwarp();
  mbar_arrive_warp(c.sb + BAR_STG + c.wg * 16 + part * 8);
}

template <int WG, bool FIRST, int H>
__device__ __forceinline__ void proj_half(const Ctx& c, float (&acc)[64], uint32_t w, uint32_t x, uint32_t sw) {
  uint64_t dx = desc64((SB0 + x * SLOT + (WG ? 0 : H * 8192)) >> 4, dhi<0>(x) + sw);
  uint64_t dw = desc64(WG ? (SB0 + w * SLOT + H * 8192) >> 4 : sdesc(SB0 + w * SLOT, 8192), dhi<1>(x));
  wg_fence();
  if (WG) { if (FIRST) wgmma_proj96_init(acc, dw, dx, 0); else wgmma_proj96(acc, dw, dx, 1); }
  else { if (FIRST) wgmma_proj_init(acc, dx, dw, 0); else wgmma_proj(acc, dx, dw, 1); }
#pragma unroll
  for (int k = 1; k < 4; k++) {
    dadd(dx, k == 2 ? 2 + (sw >> 30) * 28 : 2); dadd(dw, 128);
    if (WG) wgmma_proj96(acc, dw, dx, 1); else wgmma_proj(acc, dx, dw, 1);
  }
  wg_commit();
}

__device__ __forceinline__ void proj_store16(uint32_t a, const float* f, float sc) {
  stsm4t(a, pack_bf16(f[0] * sc, f[1] * sc), pack_bf16(f[2] * sc, f[3] * sc), pack_bf16(f[4] * sc, f[5] * sc), pack_bf16(f[6] * sc, f[7] * sc));
}

__device__ __forceinline__ uint32_t stage_off(const Ctx& c) {
  const int lane = c.lane, mi = lane >> 3, r8 = lane & 7;
  return ((mi >> 1) * 8 + r8) * 128 + (((2 * c.warp + (mi & 1)) ^ r8) << 4);
}
__device__ __forceinline__ uint32_t q3_swz(uint32_t r8) { return ((r8 & 3) << 1) | (r8 >> 2); }
template <int H>
__device__ __forceinline__ void stage_t2(const Ctx& c, const float (&a)[64], float sc) {
  const uint32_t base = c.sb + QBUF_OFF + 2 * 16384 + H * 8192 + stage_off(c);
#pragma unroll
  for (int jj = 0; jj < 4; jj++) proj_store16(base + jj * 2048, &a[jj * 8], sc);
}
template <int H, bool IS_Q>
__device__ __forceinline__ void stage_t3(const Ctx& c, const float (&a)[64], float sc) {
  const uint32_t off = stage_off(c), r8 = (off >> 7) & 7;
  const uint32_t t3 = c.sb + QBUF_OFF + 3 * 16384 + H * 4096 + (IS_Q ? off ^ ((r8 ^ q3_swz(r8)) << 4) : off);
  proj_store16(t3, &a[32], sc);
  proj_store16(t3 + 2048, &a[40], sc);
}

template <int WG, int h>
__device__ __forceinline__ void load_part(const Ctx& c, Ring r, uint32_t (&q)[32]) {
  uint32_t n = 0;
  while (!h && !__all_sync(0xffffffffu, peek<4>(c, r))) {
    if (++n > (1u << 26)) __trap();
  }
  const int lane = c.lane, mi = lane >> 3, r8 = lane & 7;
  if (WG) { r.next(); r.next(); }
  const uint32_t off = c.sb + (WG ? stage_off(c) : (16 * c.warp + (mi & 1) * 8 + r8) * 128), t0 = off + r.slot * SLOT;
  r.next();
  const uint32_t t1 = off + r.slot * SLOT;
#pragma unroll
    for (int jj = 0; jj < (WG ? 6 : 8); jj++) {
      uint32_t* p = &q[4 * jj];
      if (WG) asm volatile("ldmatrix.sync.aligned.m8n8.x4.trans.shared.b16 {%0, %1, %2, %3}, [%4];" : "=r"(p[0]), "=r"(p[1]), "=r"(p[2]), "=r"(p[3])
                           : "r"((jj < 4 ? t0 + h * 8192 : t1 + h * 4096) + (jj & 3) * 2048) : "memory");
      else ldsm4((h ? t1 : t0) + (jj >> 2) * 8192 + (((((2 * jj) & 7) + (mi >> 1)) ^ r8) << 4), p[0], p[1], p[2], p[3]);
    }
}
template <int WG>
__device__ __forceinline__ void add_part(const Ctx& c, const uint32_t (&q)[32], float (&a)[64]) {
  const uint32_t one = (c.lane >> 3) == (c.lane & 3) ? 0x3f80u << (c.lane & 4) * 4 : 0;
#pragma unroll
  for (int i = 0; i < (WG ? 12 : 16); i++)
    asm("mma.sync.aligned.m16n8k8.row.col.f32.bf16.bf16.f32 {%0, %1, %2, %3}, {%4, %5}, {%6}, {%0, %1, %2, %3};"
        : "+f"(a[4 * i]), "+f"(a[4 * i + 1]), "+f"(a[4 * i + 2]), "+f"(a[4 * i + 3]) : "r"(q[2 * i]), "r"(q[2 * i + 1]), "r"(one));
}

__device__ __forceinline__ void trace_dump(const Ctx& c) {
}
struct RowSum { float l0, l1; };
__device__ __forceinline__ const char* o_addr(uint32_t item, int row, int lane) {
  return reinterpret_cast<const char*>(g_o) + (((item >> 10) * (2 * SQ) + row) * 128 + (lane ^ (lane >> 3)) * 16);
}
__device__ __forceinline__ void o_stg(const char* p, int i, const uint32_t* q) {
  asm volatile("st.global.v4.b32 [%0], {%1, %2, %3, %4};"
               ::"l"(p + (i >> 1) * (SQ * 128) + (i & 1) * 512), "r"(q[0]), "r"(q[1]), "r"(q[2]), "r"(q[3]) : "memory");
}
template <int MODE, int I0 = 0, int NI = 4>
__device__ __forceinline__ void o_emit(const char* p, const float (&o)[64], float inv) {
#pragma unroll
  for (int i = I0; i < I0 + NI; i++) {
    uint32_t q[4];
#pragma unroll
    for (int j = 0; j < 4; j++) q[j] = pack_bf16(o[16 * i + 4 * j + 2 * MODE] * inv, o[16 * i + 4 * j + 2 * MODE + 1] * inv);
    o_stg(p, i, q);
  }
}
__device__ __forceinline__ void o_done(const Ctx& c) {
  __syncwarp();
  mbar_arrive_warp(c.sb + BAR_OUT);
  __syncwarp();
}
template <int WG>
__device__ __forceinline__ void o_first(const Ctx& c, uint32_t item, float (&o)[64], const RowSum& inv, uint32_t (&q)[32]) {
  const char* p = o_addr(item, WG ? 192 + 8 * c.warp : 64 + 16 * c.warp, c.lane);
  reg_fence(o);
#pragma unroll
  for (int j = 0; j < 16; j++) {
    if (WG) q[j] = pack_bf16((o[4 * j] + o[4 * j + 2]) * inv.l0, (o[4 * j + 1] + o[4 * j + 3]) * inv.l0);
    else q[j] = pack_bf16(o[4 * j] * inv.l0, o[4 * j + 1] * inv.l0);
    if (!WG && (j & 3) == 3 && (j >> 2) < 8 - LATE0) o_stg(p, j >> 2, q + j - 3);
  }
#pragma unroll
  for (int j = 0; j < 16; j++) {
    if (!WG) q[16 + j] = pack_bf16(o[4 * j + 2] * inv.l1, o[4 * j + 3] * inv.l1);
    if ((j & 3) == 3 && (j >> 2) < 4 - (WG ? LATE1 : LATE0)) o_stg(WG ? p : p + 1024, j >> 2, q + (WG ? 0 : 16) + j - 3);
  }
}
template <int WG>
__device__ __forceinline__ void o_rest(const Ctx& c, uint32_t item, uint32_t (&q)[32]) {
  const char* p = o_addr(item, WG ? 192 + 8 * c.warp : 64 + 16 * c.warp, c.lane);
#pragma unroll
  for (int i = WG ? 4 - LATE1 : 8 - LATE0; i < (WG ? 4 : 8); i++) o_stg(p + (i >> 2) * 1024, i & 3, q + 4 * i);
}
template <int K0, int K1>
__device__ __forceinline__ void o_piece(const Ctx& c, const char* p, int k, const float (&o)[64], const RowSum& inv) {
  constexpr int NI = 8 / O_STEPS, M = K0 * NI / 4;
  if constexpr (K1 - K0 == 1) {
    o_emit<M, K0 * NI % 4, NI>(p + M * 1024, o, M ? inv.l1 : inv.l0);
    if (K1 == O_STEPS) o_done(c);
  } else {
    if (k <= (K0 + K1) / 2) o_piece<K0, (K0 + K1) / 2>(c, p, k, o, inv); else o_piece<(K0 + K1) / 2, K1>(c, p, k, o, inv);
  }
}
template <int WG>
__device__ __forceinline__ void o_second(const Ctx& c, uint32_t item, int k, float (&o)[64], const RowSum& inv) {
  reg_fence(o);
  o_piece<0, O_STEPS>(c, o_addr(item, 128 * WG + 16 * c.warp, c.lane0 + (k >> 8)), k, o, inv);
}
template <int WG>
__device__ __forceinline__ void release_q(const Ctx& c) {
#pragma unroll
  for (int t = 0; t < 2; t++)
    if (c.lead) asm volatile("mbarrier.arrive.shared::cta.b64 _, [%0], 2;" ::"r"(c.sb + BAR_EMPTY + (NS + 2 * WG + t) * 8) : "memory");
  __syncwarp();
}
struct Slots { uint32_t w, x, o, po; };
template <int WG>
__device__ __forceinline__ void acc_fence(float (&a)[64]) {
#pragma unroll
  for (int i = 0; i < (WG ? 48 : 64); i++) asm volatile("" : "+f"(a[i])::"memory");
}
template <int WG>
__device__ __forceinline__ void begin_acquire(const Ctx& c, Ring& r, Slots& h, bool wait) {
  const uint32_t s0 = r.slot, p0 = r.phase, f = c.sb + BAR_FULL;
  r.next();
  const uint32_t p1 = r.phase;
  h.w = r.slot; r.next();
  h.x = WG ? r.slot : s0; h.o = WG ? s0 : r.slot; h.po = r.phase;
  if (wait) { if (WG) mbar_wait3_w(f + s0 * 8, p0, f + h.w * 8, p1, f + h.x * 8, r.phase); else mbar_wait2_w(f + s0 * 8, p0, f + h.w * 8, p1); }
  r.next();
}
template <int WG>
__device__ __forceinline__ void proj_begin(const Ctx& c, Ring& r, float (&a0)[64], Slots& h, bool wait, uint32_t sw) {
  begin_acquire<WG>(c, r, h, wait);
  proj_half<WG, true, 0>(c, a0, h.w, h.x, sw);
  if (WG) release(c, h.o);
}
template <int WG>
__device__ __forceinline__ void proj_main(Ctx& c, Ring& r, float (&a0)[64], float (&a1)[64], Slots& h, int n, uint32_t sw, int unit,
                                          uint32_t item, int nq, float (&o1)[64], const RowSum& inv) {
  constexpr bool DEEP = (PDEPTH >> WG) & 1;
  T2C(unit, 3);
  int ks = 1;
#pragma unroll 1
  do {
    const Slots p = h;
    const uint32_t b = borrow(ks, n), tile = NS + (WG ? 3 - b : b), f = c.sb + BAR_FULL;
    const uint32_t s0 = b != 2 ? tile : r.slot, p0 = b != 2 ? (r.xp >> b) & 1 : r.phase;
    r.next_if(b == 2);
    const uint32_t p1 = r.phase;
    h.w = r.slot; r.next();
    const uint32_t s2 = b != 2 ? tile : r.slot;
    h.po = b != 2 ? p0 : r.phase;
    r.next_if(b == 2);
    r.xp ^= 1 << b;
    h.x = WG ? s2 : s0; h.o = WG ? s0 : s2;
    mbar_wait3_w(f + s0 * 8, p0, f + h.w * 8, p1, f + (WG ? s2 : p.o) * 8, WG ? h.po : p.po);
    if (ks < 10) T2C(unit, ks * 4);
    if (DEEP) {
      proj_half<WG, false, 0>(c, a0, h.w, h.x, sw);
      release(c, WG ? h.o : p.o);
      if (ks < 10) T2C(unit, ks * 4 + 1);
      wg_wait<1>();
      if (ks < 10) T2C(unit, ks * 4 + 2);
      release(c, p.x); release(c, p.w);
    } else {
      release(c, WG ? h.o : p.o);
      wg_wait<0>();
      release(c, p.x); release(c, p.w);
      if (ks < 10) T2C(unit, ks * 4 + 1);
      proj_half<WG, false, 0>(c, a0, h.w, h.x, sw);
      if (ks < 10) T2C(unit, ks * 4 + 2);
    }
    proj_half<WG, false, 1>(c, a1, h.w, h.x, sw);
    if (ks < 10) T2C(unit, ks * 4 + 3);
    if (ks <= nq) o_second<WG>(c, item, ks, o1, inv);
  } while (++ks != n);
  {
    const uint32_t e0 = c.sb + BAR_EMPTY + (NS + 3 * WG) * 8, e1 = c.sb + BAR_EMPTY + (NS + 1 + WG) * 8;
    const uint32_t p0 = (r.xp ^ unit ^ 1) & 1, p1 = ((r.xp >> 1) ^ unit ^ 1) & 1;
    const uint32_t k0 = sw ? e0 : c.sb + BAR_FULL + r.slot * 8, pk = sw ? p0 : r.phase;
    uint32_t cnt = 0;
    while (!__all_sync(0xffffffffu, mbar_try(e0, p0) & mbar_try(e1, p1) & mbar_try(k0, pk) & (WG || mbar_try(c.sb + BAR_FULL + h.o * 8, h.po)))) {
      if (++cnt > (1u << 22)) __trap();
    }
  }
  c.lane = c.lane0 + (h.w >> 5);
  if (!WG) release(c, h.o);
}
template <int WG>
__device__ __forceinline__ void proj_end(const Ctx& c, float (&a1)[64], const Slots& h) {
  wg_wait<0>();
  acc_fence<WG>(a1);
  release(c, h.x); release(c, h.w);
}
__device__ __forceinline__ uint32_t get_desc(const Ctx& c, int i) {
  uint32_t d;
  mbar_wait_w(c.sb + BAR_DESC, (i - 1) & 1);
  asm volatile("ld.volatile.shared.u32 %0, [%1];" : "=r"(d) : "r"(c.sb + DESC_OFF + (i & 3) * 4) : "memory");
  return __shfl_sync(0xffffffffu, d, 0);
}

__device__ __forceinline__ float quad_max(float x) {
  x = fmaxf(x, __shfl_xor_sync(0xffffffffu, x, 1));
  return fmaxf(x, __shfl_xor_sync(0xffffffffu, x, 2));
}
__device__ __forceinline__ float quad_sum(float x) {
  x += __shfl_xor_sync(0xffffffffu, x, 1);
  return x + __shfl_xor_sync(0xffffffffu, x, 2);
}
template <bool SP, bool FIRST>
__device__ __forceinline__ void exps(const Ctx& c, const float (&s)[32], uint32_t (&p)[SP ? 8 : 16], RowSum& st) {
  if constexpr (SP) {
    uint32_t q[8];
    float t;
#pragma unroll
    for (int j = 0; j < 8; j++) {
      const float e0 = ex2(s[4 * j] + s[4 * j + 2]), e1 = ex2(s[4 * j + 1] + s[4 * j + 3]);
      if (j == 0) t = e0 + e1; else t += e0 + e1;
      q[j] = pack_bf16(e0, e1);
    }
    const bool odd = c.src & 2;
#pragma unroll
    for (int g = 0; g < 4; g++) {
      p[2 * g] = __shfl_sync(0xffffffffu, odd ? q[2 * g + 1] : q[2 * g], c.src);
      p[2 * g + 1] = __shfl_sync(0xffffffffu, odd ? q[2 * g] : q[2 * g + 1], c.src ^ 1);
    }
    st.l0 = FIRST ? t : st.l0 + t;
  } else {
    float t0, t1;
#pragma unroll
    for (int j = 0; j < 8; j++) {
      const float e0 = ex2(s[4 * j]), e1 = ex2(s[4 * j + 1]), e2 = ex2(s[4 * j + 2]), e3 = ex2(s[4 * j + 3]);
      if (j == 0) { t0 = e0 + e1; t1 = e2 + e3; } else { t0 += e0 + e1; t1 += e2 + e3; }
      p[2 * j] = pack_bf16(e0, e1);
      p[2 * j + 1] = pack_bf16(e2, e3);
    }
    st.l0 = FIRST ? t0 : st.l0 + t0;
    st.l1 = FIRST ? t1 : st.l1 + t1;
  }
}
template <bool SP>
__device__ __forceinline__ bool finish_sums(RowSum& st) {
  const float a = quad_sum(st.l0), b = SP ? a : quad_sum(st.l1);
  st.l0 = __fdividef(1.f, a); st.l1 = __fdividef(1.f, b);
  return !(a >= SUM_LO && a <= SUM_HI && b >= SUM_LO && b <= SUM_HI);
}
template <bool SP, bool INIT, int SITE, bool COMMIT = true, int RM = 0>
__device__ __forceinline__ void issue_qk(const Ctx& c, float (&s)[32], const uint32_t (&qs)[32], uint32_t dq, uint32_t dk) {
  uint64_t a = desc64(dq, dhi<SITE & 1>(dk)), b = desc64(dk, dhi<1 - (SITE & 1)>(dk));
  if (SP) {
    if (INIT) wgmma_qk_sp_init(s, qs[0], qs[1], qs[2], qs[3], b, 0, c.mqk); else wgmma_qk_sp(s, qs[0], qs[1], qs[2], qs[3], b, 0, c.mqk);
#pragma unroll
    for (int k = 1; k < 4; k++) { dadd(b, k == 2 ? 508 : 4); wgmma_qk_sp(s, qs[4 * k], qs[4 * k + 1], qs[4 * k + 2], qs[4 * k + 3], b, 1, c.mqk); }
  } else {
    if (RM & 1) wgmma_qk_rs(s, qs[0], qs[1], qs[2], qs[3], b, 0); else if (INIT) wgmma_qk_init(s, a, b, 0); else wgmma_qk(s, a, b, 0);
#pragma unroll
    for (int k = 1; k < 8; k++) {
      dadd(a, k == 4 ? 506 : 2); dadd(b, k == 4 ? 506 : 2);
      if (RM >> k & 1) wgmma_qk_rs(s, qs[4 * k], qs[4 * k + 1], qs[4 * k + 2], qs[4 * k + 3], b, 1); else wgmma_qk(s, a, b, 1);
    }
  }
  if (COMMIT) wg_commit();
}
template <bool SP, bool ACC, int SITE, bool SPLIT = false>
__device__ __forceinline__ void issue_pv(const Ctx& c, float (&o)[64], const uint32_t (&p)[SP ? 8 : 16], uint32_t dv) {
  uint64_t b = desc64(dv, dhi<SITE & 1>(dv));
  if constexpr (SP) {
    if (ACC) wgmma_pv_sp(o, p[0], p[1], p[2], p[3], b, 1, c.mpv); else wgmma_pv_sp_init(o, p[0], p[1], p[2], p[3], b, 0, c.mpv);
    if (SPLIT) wg_commit();
    dadd(b, 256);
    wgmma_pv_sp(o, p[4], p[5], p[6], p[7], b, 1, c.mpv);
  } else {
    if (ACC) wgmma_pv(o, p[0], p[1], p[2], p[3], b, 1); else wgmma_pv_init(o, p[0], p[1], p[2], p[3], b, 0);
#pragma unroll
    for (int k = 1; k < 4; k++) { dadd(b, 128); wgmma_pv(o, p[4 * k], p[4 * k + 1], p[4 * k + 2], p[4 * k + 3], b, 1); }
  }
  wg_commit();
}
__device__ __forceinline__ void pack_rows(const float (&o)[64], float sc, uint32_t (&q)[32]) {
#pragma unroll
  for (int j = 0; j < 32; j++) q[j] = pack_bf16(o[2 * j] * sc, o[2 * j + 1] * sc);
}
template <int MASK = 255>
__device__ __forceinline__ void stage_rows(const Ctx& c, uint32_t tile_addr, const uint32_t (&q)[32]) {
  const int lane = c.lane, mi = lane >> 3, r8 = lane & 7;
  const uint32_t row_addr = tile_addr + (16 * c.warp + (mi & 1) * 8 + r8) * 128;
#pragma unroll
  for (int jj = 0; jj < 8; jj++)
    if (MASK >> jj & 1) stsm4(row_addr + (jj >> 2) * 8192 + (((((2 * jj) & 7) + (mi >> 1)) ^ r8) << 4), q[4 * jj], q[4 * jj + 1], q[4 * jj + 2], q[4 * jj + 3]);
}
__device__ __forceinline__ void stage_rows(const Ctx& c, uint32_t tile_addr, const float (&o)[64], float sc) {
  uint32_t q[32];
  pack_rows(o, sc, q);
  stage_rows(c, tile_addr, q);
}
template <int WG, int H>
__device__ __forceinline__ void stage_out(const Ctx& c, const float (&a)[64]) {
  if (WG) { stage_t3<H, false>(c, a, 1.f); if (H) staged(c, 0); stage_t2<H>(c, a, 1.f); }
  else stage_rows(c, c.sb + QBUF_OFF + H * 16384, a, 1.f);
  if (H || !WG) staged(c, H);
}
template <int SITE>
__device__ __forceinline__ void issue_qk_rs(float (&s)[32], uint32_t (&q)[32], uint32_t dk) {
  uint64_t b = desc64(dk, dhi<SITE>(dk));
  reg_fence(q);
  wg_fence();
  wgmma_qk_rs_init(s, q[0], q[1], q[2], q[3], b, 0);
#pragma unroll
  for (int k = 1; k < 8; k++) { dadd(b, k == 4 ? 506 : 2); wgmma_qk_rs(s, q[4 * k], q[4 * k + 1], q[4 * k + 2], q[4 * k + 3], b, 1); }
  wg_commit();
}

__device__ __forceinline__ void redo_tile(const Ctx& c, uint32_t q_addr, uint32_t half, const __nv_bfloat16* kp, const __nv_bfloat16* vp,
                                          uint32_t item, int row) {
  float o[64];
  const int lane = lane_now(), g = lane >> 2, cc = lane & 3, mi = lane >> 3, r8 = lane & 7;
  const uint32_t qa = q_addr + (half == 4096 ? 8 * c.warp + r8 : 16 * c.warp + (mi & 1) * 8 + r8) * 128, swz = half == 4096 ? q3_swz(r8) : r8;
  const uint32_t* kq = reinterpret_cast<const uint32_t*>(kp + g * DH) + cc;
  const unsigned short* vq = reinterpret_cast<const unsigned short*>(vp + 2 * cc * DH) + g;
  float m0 = -INFINITY, m1 = -INFINITY, l0 = 0.f, l1 = 0.f;
#pragma unroll
  for (int i = 0; i < 64; i++) o[i] = 0.f;
#pragma unroll 1
  for (int kb = 0; kb < SK / 16; kb++) {
    float z[8] = {0.f, 0.f, 0.f, 0.f, 0.f, 0.f, 0.f, 0.f};
#pragma unroll 2
    for (int kk = 0; kk < 8; kk++) {
      uint32_t a0, a1, a2, a3;
      ldsm4(qa + (kk >> 2) * half + ((((kk & 3) * 2 + (mi >> 1)) ^ swz) << 4), a0, a1, a2, a3);
      const uint32_t* kr = kq + kb * (16 * DH / 2) + kk * 8;
      mma16816(z[0], z[1], z[2], z[3], a0, a1, a2, a3, __ldg(kr), __ldg(kr + 4));
      mma16816(z[4], z[5], z[6], z[7], a0, a1, a2, a3, __ldg(kr + 8 * DH / 2), __ldg(kr + 8 * DH / 2 + 4));
    }
    const float n0 = fmaxf(m0, quad_max(fmaxf(fmaxf(z[0], z[1]), fmaxf(z[4], z[5]))));
    const float n1 = fmaxf(m1, quad_max(fmaxf(fmaxf(z[2], z[3]), fmaxf(z[6], z[7]))));
    const float al0 = ex2(m0 - n0), al1 = ex2(m1 - n1);
    m0 = n0; m1 = n1;
#pragma unroll
    for (int i = 0; i < 8; i++) z[i] = ex2(z[i] - ((i & 2) ? n1 : n0));
    l0 = l0 * al0 + (z[0] + z[1]) + (z[4] + z[5]);
    l1 = l1 * al1 + (z[2] + z[3]) + (z[6] + z[7]);
    const uint32_t a0 = pack_bf16(z[0], z[1]), a1 = pack_bf16(z[2], z[3]), a2 = pack_bf16(z[4], z[5]), a3 = pack_bf16(z[6], z[7]);
    const unsigned short* vr = vq + kb * (16 * DH);
#pragma unroll
    for (int nb = 0; nb < 16; nb++) {
      o[4 * nb] *= al0; o[4 * nb + 1] *= al0; o[4 * nb + 2] *= al1; o[4 * nb + 3] *= al1;
      const uint32_t b0 = __ldg(vr + nb * 8) | ((uint32_t)__ldg(vr + nb * 8 + DH) << 16);
      const uint32_t b1 = __ldg(vr + nb * 8 + 8 * DH) | ((uint32_t)__ldg(vr + nb * 8 + 9 * DH) << 16);
      mma16816(o[4 * nb], o[4 * nb + 1], o[4 * nb + 2], o[4 * nb + 3], a0, a1, a2, a3, b0, b1);
    }
  }
  const char* p = o_addr(item, row, lane);
  o_emit<0>(p, o, __fdividef(1.f, quad_sum(l0)));
  o_emit<1>(half == 4096 ? p : p + 1024, o, __fdividef(1.f, quad_sum(l1)));
}

template <bool SPA, bool SPB, int SITE, int ID>
__device__ __forceinline__ void batch(const Ctx& c, float (&s)[32], const uint32_t (&qs)[32], uint32_t dq, uint32_t dk, float (&ob)[64],
                                      uint32_t (&pb)[SPB ? 8 : 16], uint32_t dv) {
  if constexpr (SPA) {
    reg_fence(pb);
    wg_fence();
    issue_pv<SPB, true, ID>(c, ob, pb, dv);
    issue_qk<SPA, false, ID>(c, s, qs, dq, dk);
  } else {
    constexpr bool EARLY = ((QK_EARLY_MASK >> (SITE + (SPB ? 2 : 0))) & 1) != 0;
    if (!EARLY) reg_fence(pb);
    wg_fence();
    issue_qk<SPA, false, ID, !SPB, SITE ? RM0 : SPB ? RM2 : RM1>(c, s, qs, dq, dk);
    if (EARLY) { reg_fence(pb); wg_fence(); }
    issue_pv<SPB, true, ID, SPB>(c, ob, pb, dv);
  }
}

template <bool SP0>
__device__ __forceinline__ bool attention(Ctx& c, Ring& r, int unit, uint32_t& d, const float (&a0)[64], float (&o0)[64], float (&o1)[64],
                                          RowSum& st0, RowSum& st1, const Slots& h) {
  constexpr bool SP1 = false;
  if (SP0) { c.mqk = META_QK + (d >> 28); c.mpv = META_PV + (d >> 28); asm volatile("" : "+r"(c.mqk), "+r"(c.mpv)); }
  if (SP0) c.src = (c.lane & 28) | ((c.lane & 1) << 1) | ((c.lane >> 1) & 1);
  float s[32];
  uint32_t p0[SP0 ? 8 : 16], p1[16];
  const uint32_t q0a = c.sb + QBUF_OFF + (SP0 ? 3 : 0) * 16384, q1a = c.sb + QBUF_OFF + (SP0 ? 2 : 1) * 16384;
  const uint32_t dq0 = sdesc(SB0 + QBUF_OFF, 0), dq1 = sdesc(SB0 + QBUF_OFF + (SP0 ? 2 : 1) * 16384, 0);
  uint32_t sk = acquire(c, r, true), sv, sn;
  uint32_t qs[32], q1[32];
  float s1[32];
  if (SP0) {
    stage_t3<0, true>(c, a0, SM_C);
    stage_t2<0>(c, a0, SM_C);
    proj_end<1>(c, o0, h);
    stage_t3<1, true>(c, o0, SM_C);
    stage_t2<1>(c, o0, SM_C);
    fence_async_smem();
    bar_sync(1, LAG_BAR & 30 ? 256 : 128);
    const int g = c.lane >> 2, cc = c.lane & 3;
    const uint32_t qa = q0a + (8 * c.warp + g) * 128 + (cc & 1) * 8;
#pragma unroll
    for (int k = 0; k < 8; k++)
      asm volatile("ld.shared.v2.u32 {%0, %1}, [%2];" : "=r"(qs[2 * k]), "=r"(qs[2 * k + 1])
                   : "r"(qa + (k >> 2) * 4096 + ((((k & 3) * 2 + (cc >> 1)) ^ q3_swz(g)) << 4)) : "memory");
    TRACE(unit, 2);
    wg_fence();
    issue_qk<SP1, true, 1>(c, s1, qs, dq1, sdesc(SB0 + sk * SLOT, 0));
#pragma unroll
    for (int k = 0; k < 8; k++)
      if (RM2 >> k & 1) ldsm4(q1a + (k >> 2) * 8192 + (16 * c.warp + (c.lane & 15)) * 128 + (((2 * (k & 3) + (c.lane >> 4)) ^ (c.lane & 7)) << 4),
                              q1[4 * k], q1[4 * k + 1], q1[4 * k + 2], q1[4 * k + 3]);
#pragma unroll
    for (int k = 0; k < 16; k++) asm volatile("" : "+r"(qs[k])::"memory");
    wg_fence();
    issue_qk<SP0, true, 0>(c, s, qs, dq0, sdesc(SB0 + sk * SLOT, 0));
    const bool have = peek<2>(c, r);
    wg_wait<1>();
    reg_fence(s1);
    exps<SP1, true>(c, s1, p1, st1);
    sched_fence<11>(sk, p1);
    acquire2(c, r, sv, sn, __all_sync(0xffffffffu, have));
    wg_wait<0>();
    wg_fence();
    issue_pv<SP1, false, 1>(c, o1, p1, sdesc(SB0 + sv * SLOT, 8192));
    if (LAG_BAR & 1) asm volatile("bar.arrive 4, 256;" ::: "memory");
    sched_fence<12>(sk, s);
    release(c, sk);
    sk = sn;
    exps<SP0, true>(c, s, p0, st0);
    reg_fence(p0);
    wg_fence();
    issue_pv<SP0, false, 0>(c, o0, p0, sdesc(SB0 + sv * SLOT, 8192));
    issue_qk<SP0, true, 2>(c, s, qs, dq0, sdesc(SB0 + sk * SLOT, 0));
    sn = acquire(c, r);
    wg_wait<0>();
    reg_fence(s);
  } else {
    pack_rows(a0, SM_C, qs);
    stage_rows(c, q0a, qs);
    proj_end<0>(c, o1, h);
    TRACE(unit, 2);
    float sc = SM_C;
    issue_qk_rs<0>(s, qs, sdesc(SB0 + sk * SLOT, 0));
    sched_fence<0>(sk, sc);
    if (LAG_BAR & 8) asm volatile("bar.arrive 1, 256;" ::: "memory");
    pack_rows(o1, sc, q1);
    stage_rows<~RM1>(c, q1a, q1);
    if (LAG_BAR & 4) asm volatile("bar.arrive 1, 256;" ::: "memory");
    issue_qk_rs<1>(s1, q1, sdesc(SB0 + sk * SLOT, 0));
    if (LAG_BAR & 2) asm volatile("bar.arrive 1, 256;" ::: "memory");
    bool have = peek<2>(c, r);
    wg_wait<1>();
    reg_fence(s);
    exps<SP0, true>(c, s, p0, st0);
    sched_fence<1>(sk, p0);
    if (LAG_BAR & 16) asm volatile("bar.arrive 1, 256;" ::: "memory");
    acquire2(c, r, sv, sn, __all_sync(0xffffffffu, have));
    wg_wait<0>();
    reg_fence(s1);
    fence_async_smem();
    __syncwarp();
    wg_fence();
    issue_qk<SP0, false, 2, true, RM0>(c, s, qs, dq0, sdesc(SB0 + sn * SLOT, 0));
    issue_pv<SP0, false, 0>(c, o0, p0, sdesc(SB0 + sv * SLOT, 8192));
    sched_fence<2>(sk, s1);
    release(c, sk);
    have = peek<1>(c, r);
    sk = sn;
    exps<SP1, true>(c, s1, p1, st1);
    reg_fence(p1);
    wg_fence();
    issue_pv<SP1, false, 1>(c, o1, p1, sdesc(SB0 + sv * SLOT, 8192));
    sn = acquire(c, r, __all_sync(0xffffffffu, have));
    if (LAG_BAR & 1) bar_sync(4, 256);
    wg_wait<1>();
    reg_fence(s);
  }
  TRACE_IN(unit, 4);
  T2C(unit, 51);
#pragma unroll 1
  for (int j = 1; j < 15; j++) {
    const uint32_t sv_prev = sv, sk_prev = sk;
    sv = sn;
    const uint32_t dv = sdesc(SB0 + sv * SLOT, 8192);
    reg_fence(p0);
    exps<SP0, false>(c, s, p0, st0);
    batch<SP1, SP0, 0, 3>(c, s, q1, dq1, sdesc(SB0 + sk * SLOT, 0), o0, p0, dv);
    sk = acquire(c, r);
    wg_wait<1>();
    reg_fence(s); reg_fence(p1);
    release(c, sv_prev); release(c, sk_prev);
    exps<SP1, false>(c, s, p1, st1);
    batch<SP0, SP1, 1, 4>(c, s, qs, dq0, sdesc(SB0 + sk * SLOT, 0), o1, p1, dv);
    sn = acquire(c, r);
    if (SP0) wg_wait<0>(); else wg_wait<1>();
    reg_fence(s);
  }
  TRACE_IN(unit, 5);
  T2C(unit + 1, 52);
  const uint32_t sv_prev = sv;
  sv = sn;
  const uint32_t dv = sdesc(SB0 + sv * SLOT, 8192);
  reg_fence(p0);
  exps<SP0, false>(c, s, p0, st0);
  batch<SP1, SP0, 0, 5>(c, s, q1, dq1, sdesc(SB0 + sk * SLOT, 0), o0, p0, dv);
  asm volatile("ld.volatile.shared.u32 %0, [%1];" : "=r"(d) : "r"(c.sb + DESC_OFF + ((unit + 1) & 3) * 4) : "memory");
  const bool have = peek<2 + SP0>(c, r);
  wg_wait<1>();
  reg_fence(s); reg_fence(p1);
  release(c, sv_prev); release(c, sk);
  exps<SP1, false>(c, s, p1, st1);
  reg_fence(p1);
  wg_fence();
  issue_pv<SP1, true, 2>(c, o1, p1, dv);
  if (SP0) sched_fence<6>(sk, st0.l0, st1.l0, st1.l1); else sched_fence<5>(sk, st0.l0, st0.l1, st1.l0, st1.l1);
  c.lane = c.lane0 + (sk >> 5);
  const bool bad = finish_sums<SP0>(st0) | finish_sums<SP1>(st1);
  uint32_t any;
  asm volatile("{\n.reg .pred p, q;\nsetp.ne.u32 p, %1, 0;\nbar.red.or.pred q, %2, 128, p;\nselp.u32 %0, 1, 0, q;\n}"
               : "=r"(any) : "r"((uint32_t)bad), "n"(2 + SP0) : "memory");
  any = __any_sync(0xffffffffu, any);
  d = __shfl_sync(0xffffffffu, d, 0);
  if (d < (2u << 30) && !__all_sync(0xffffffffu, have)) { Ring t = r; Slots u; begin_acquire<SP0>(c, t, u, true); }
  wg_wait<0>();
  reg_fence(o0); reg_fence(o1);
  release(c, sv);
  if (!SP0 && __builtin_expect(any, 0)) { stage_rows<RM1>(c, q1a, q1); __syncwarp(); }
  return any;
}

template <int WG>
__device__ __forceinline__ void consumer(Ctx c, const __nv_bfloat16* const* kv) {
  asm volatile("setmaxnreg.inc.sync.aligned.u32 %0;" ::"n"(WG ? REG_C : 504 - REG_C - REG_P));
  c.wg = WG;
  Ring r{0, 0, 0};
  float a0[64], a1[64], o1[64];
  Slots h;
  RowSum inv0, inv1;
  uint32_t oq[32];
  uint32_t d = c_sched.queue[blockIdx.x] * 1025, dc = 0, sw;
  int i = 0, nq;
begin:
  sw = d & (1u << 30);
  proj_begin<WG>(c, r, a0, h, true, sw);
  proj_half<WG, true, 1>(c, a1, h.w, h.x, sw);
  nq = 0;
#pragma unroll
  for (int k = 0; k < 64; k++) asm volatile("" : "=f"(o1[k]));
  asm volatile("" : "=f"(inv1.l0), "=f"(inv1.l1));
  while (true) {
    TRACE(i, 0); TRACE(i, 6);
    proj_main<WG>(c, r, a0, a1, h, d >> 30 ? ((d >> 16) & 63) + 1 : DM / 64, sw, i, dc, nq, o1, inv1);
    dc = d;
    TRACE(i, 1);
    if (d >> 30) goto out_tile;
    wg_wait<1>();
    acc_fence<WG>(a0);
    if (WG ? attention<WG>(c, r, i, d, a0, a1, o1, inv0, inv1, h) : attention<WG>(c, r, i, d, a0, o1, a1, inv1, inv0, h)) goto redo;
    if (d >= (2u << 30)) break;
    sw = d & (1u << 30);
    proj_begin<WG>(c, r, a0, h, false, sw);
    release_q<WG>(c);
    if (WG) sched_fence<8>(h.w, inv0.l0); else sched_fence<7>(h.w, inv0.l0, inv0.l1);
    o_first<WG>(c, dc, a1, inv0, oq);
    sched_fence<9>(h.w, inv1.l0);
    proj_half<WG, true, 1>(c, a1, h.w, h.x, sw);
    o_rest<WG>(c, dc, oq);
    nq = O_STEPS;
    TRACE(i, 3); TRACE(i, 7);
    i++;
  }
  release_q<WG>(c);
  o_first<WG>(c, dc, a1, inv0, oq);
  o_rest<WG>(c, dc, oq);
#pragma unroll
  for (int k = 1; k <= O_STEPS; k++) o_second<WG>(c, dc, k, o1, inv1);
next:
  TRACE(i, 3); TRACE(i, 7);
  if ((d >> 30) != 2) {
    i++;
    r.uniform();
    goto begin;
  }
  trace_dump(c);
  return;
out_tile:
  if (d & 96) goto finish;
  d = get_desc(c, i + 1);
  wg_wait<1>();
  acc_fence<WG>(a0);
  TRACE_O(0);
  stage_out<WG, 0>(c, a0);
  TRACE_O(1);
  proj_end<WG>(c, a1, h);
  TRACE_O(2);
  stage_out<WG, 1>(c, a1);
  TRACE(i, 2);
  goto next;
finish:
  {
    uint32_t q[32];
#pragma unroll 1
    for (int k = (d >> 5) & 3; k > 1; k--) {
      wg_wait<0>();
      acc_fence<WG>(a0); acc_fence<WG>(a1);
      if (k == ((d >> 5) & 3)) { release(c, h.x); release(c, h.w); }
      load_part<WG, 0>(c, r, q); add_part<WG>(c, q, a0);
      load_part<WG, 1>(c, r, q); add_part<WG>(c, q, a1);
#pragma unroll
      for (int t = 0; t < 4; t++) { release(c, r.slot); r.next(); }
    }
    load_part<WG, 0>(c, r, q);
    wg_wait<1>();
    acc_fence<WG>(a0);
    TRACE_O(0);
    add_part<WG>(c, q, a0);
    stage_out<WG, 0>(c, a0);
    TRACE_O(1);
    load_part<WG, 1>(c, r, q);
    wg_wait<0>();
    acc_fence<WG>(a1);
    TRACE_O(2);
    add_part<WG>(c, q, a1);
    stage_out<WG, 1>(c, a1);
    TRACE(i, 2); TRACE(i, 3); TRACE(i, 7);
    trace_dump(c);
    return;
  }
redo:
  {
    const size_t hoff = (size_t)(dc & 511) * (SK * DH);
    const int br = (dc >> 9) & 1;
#pragma unroll 1
    for (int part = 0; part < 2; part++) {
      const int t = WG ? 3 - part : part;
      redo_tile(c, c.sb + QBUF_OFF + t * 16384, t == 3 ? 4096 : 8192, kv[br] + hoff, kv[2 + br] + hoff, dc,
                t * 64 + (t == 3 ? 8 : 16) * c.warp);
    }
    o_done(c);
    release_q<WG>(c);
  }
  goto next;
}

template <bool SIMPLE>
__global__ void __launch_bounds__(384, 1) mha_fused_kernel(const __grid_constant__ Params P) {
  extern __shared__ __align__(1024) uint8_t smem_raw[];
  const uint32_t sbase = smem_u32(smem_raw);
  const int tid = threadIdx.x;
  const int wg = __shfl_sync(0xffffffffu, tid >> 7, 0);
  const int warp = __shfl_sync(0xffffffffu, (tid >> 5) & 3, 0);
  const int lane = tid & 31;
  const int cta = blockIdx.x;
  constexpr bool PAIR = !SIMPLE && CLUSTER;

  if (tid == 0) T3(15, 0);
  if ((sbase & 0xffffff) != SB0) __trap();
  {
    const int wi = wg * 4 + warp;
    asm volatile(ELECT "prefetch.tensormap [%0];\n}" ::"l"(&P.x[0][0] + wi) : "memory");
#pragma unroll
    for (int k = 0; k < 5; k++) {
      const int b = min(BAR_OFF + (wi * 5 + k) * 8, DESC_OFF - 8);
      asm volatile(ELECT "mbarrier.init.shared::cta.b64 [%0], %1;\n}"
                   ::"r"(sbase + b), "r"(b < BAR_EMPTY || b >= BAR_DESC ? 1 : b >= BAR_STG && b < BAR_OUT ? 4 : 8) : "memory");
    }
    asm volatile("fence.mbarrier_init.release.cluster;" ::: "memory");
    if (wi < 6) asm volatile(ELECT "prefetch.tensormap [%0];\n}" ::"l"(&P.x[0][0] + 12 + wi) : "memory");
  }
  if (PAIR) asm volatile("barrier.cluster.arrive.aligned;\nbarrier.cluster.wait.aligned;" ::: "memory"); else __syncthreads();

  if (wg == 2) {
    asm volatile("setmaxnreg.dec.sync.aligned.u32 %0;" ::"n"(REG_P));
    if (warp == 1) {
      const uint32_t qb = sbase + QBUF_OFF;
      const uint32_t ep = __shfl_sync(0xffffffffu, *(volatile unsigned*)&g_epoch + 1, 0);
      asm volatile("st.volatile.shared.u32 [%0], %1;" ::"r"(sbase + EPOCH_OFF), "r"(ep) : "memory");
      uint32_t dc = c_sched.queue[cta], qi = 0, piece = 0, na = 0;
      TTAIL(0);
      for (int i = 0; (dc >> 30) != 2; i++) {
        if (!(dc >> 30) && o_reuse<SIMPLE>((dc >> 5) & 31)) {
          const unsigned* rd = &g_rd[0][0] + ((dc & 1023) >> 2) - OR * 8;
          for (uint32_t n = 0; !__all_sync(0xffffffffu, reached(rd, ep * 5)); __nanosleep(300)) if (++n > (1u << 22)) __trap();
        }
        mbar_wait_w(sbase + BAR_GO, i & 1);
        if (piece == 0) {
          if (PAIR && (cta & 1)) {
            asm volatile(ELECT EXPECT("%0", "4") "mbarrier.arrive.shared::cluster.b64 _, [%1];\n}" ::"r"(sbase + BAR_MAIL), "r"(peer(sbase + BAR_MAIL)) : "memory");
            mbar_wait_w(sbase + BAR_MAIL, i & 1);
            qi = lds(sbase + EPOCH_OFF + 8);
          } else if (lane == 0) {
            qi = atomicAdd(&g_next, PAIR ? 2 : 1);
            if (qi == (SIMPLE ? Q_ALL : Q_RANGES) - (PAIR ? 2 : 1)) { g_next = 0; g_epoch = ep; }
          }
          qi = __shfl_sync(0xffffffffu, qi, 0);
          if (PAIR && !(cta & 1)) {
            mbar_wait_w(sbase + BAR_MAIL, i & 1);
            asm volatile(ELECT "st.async.shared::cluster.mbarrier::complete_tx::bytes.u32 [%0], %1, [%2];\n}"
                         ::"r"(peer(sbase + EPOCH_OFF + 8)), "r"(qi + 1), "r"(peer(sbase + BAR_MAIL)) : "memory");
          }
          qi += SIMPLE ? gridDim.x : NCTA;
        }
        uint32_t d;
        if (qi < (SIMPLE ? Q_ALL : Q_RANGES)) { d = c_sched.queue[qi]; if (d & 0x8000) d ^= (1u << 30) | (63u << 16) | 0x8000; else d |= o_slot<SIMPLE>(d >> 5) << 15 | (d & 31) << 10; }
        else if (SIMPLE) d = 2u << 30;
        else { const uint32_t e = qi - Q_RANGES, g = e / 5; d = c_sched.piece[g][piece++] | (g & 1 ? g * 5 + 4 - e : e - g * 5) << 8; }
        if ((d >> 30) == 1) {
          const uint32_t k0 = (d >> 22) & 63;
          const uint32_t run = __ffs(__ballot_sync(0xffffffffu, !reached(&g_cnt[d & 31][lane & 7], ep * 4)) & (0xffu << (k0 >> 3))) - 1;
          if (run <= (k0 + ((d >> 16) & 63)) >> 3) d |= run <= (k0 + O_STEPS) >> 3 ? (2u << 30) | 128 : 128;
        }
        asm volatile("st.volatile.shared.u32 [%0], %1;" ::"r"(sbase + EPOCH_OFF + 4), "r"(qi) : "memory");
        asm volatile("st.volatile.shared.u32 [%0], %1;" ::"r"(sbase + DESC_OFF + ((i + 1) & 3) * 4), "r"(d) : "memory");
        __syncwarp();
        mbar_arrive_warp(sbase + BAR_DESC);
        const Work w = decode(dc);
        dc = d;
        if (w.kind == 0) {
          mbar_wait_w(sbase + BAR_OUT, na++ & 1);
          TTAIL(1);
          T3(i, 0); T3(i, 1);
          asm volatile(ELECT "red.release.gpu.global.add.u32 [%0], 1;\n}" ::"l"(&g_cnt[w.beta][w.sub >> 2]) : "memory");
          T3(i, 2);
          TTAIL(2);
          continue;
        }
        const bool fin = w.mode != 1;
        uint64_t pol, pol2;
        asm volatile("createpolicy.fractional.L2::evict_first.b64 %0, 1.0;" : "=l"(pol));
        asm volatile("createpolicy.fractional.L2::evict_normal.b64 %0, 1.0;" : "=l"(pol2));
        if (!fin) pol = pol2;
        const CUtensorMap* m = fin ? P.out_st : P.o_st;
        const int c1 = fin ? (w.beta & 15) * SQ : 0;
        const int c2 = fin ? (w.beta >> 4) * (DM / 64) + w.sub * 2 : NBETA * 64 + w.range * 2;
        uint32_t pend = 0;
#pragma unroll 1
        for (int e = 0; e < 4; e++) {
          const int t = (ST_ORDER >> (4 * e)) & 3;
          mbar_wait_w(sbase + BAR_STG + (t ^ (t >> 1)) * 8, (i - na) & 1);
          tma_st3_hint_w(m + (t == 3), qb + t * 16384, 0, c1 + t * 64, c2, pol);
          bulk_commit();
          T2P(i + 1, 5, 2 * e);
          if (pend) {
            bulk_wait_read<1>();
            mbar_arrive8_w(pend);
            T2P(i + 1, 5, 2 * e - 1);
          }
          pend = sbase + BAR_EMPTY + (NS + t) * 8;
          if ((ST_NOW >> e) & 1) {
            bulk_wait_read<0>();
            mbar_arrive8_w(pend);
            pend = 0;
            T2P(i + 1, 5, 2 * e + 1);
          }
        }
        if (w.beta < N_EARLY) asm volatile(ELECT "red.relaxed.gpu.global.add.u32 [%0], 1;\n}" ::"l"(&g_rd[w.beta][7]) : "memory");
        T3(i, 0);
        if (piece >= 2) TTAIL(piece * 2 - 1);
        asm volatile("cp.async.bulk.wait_group 0;" ::: "memory");
        T3(i, 1);
        if (w.mode == 1) asm volatile(ELECT "st.release.gpu.global.u32 [%0], %1;\n}" ::"l"(&g_flag[w.range]), "r"(ep) : "memory");
        T3(i, 2);
        if (piece >= 2) TTAIL(piece * 2);
      }
      T3(15, 1);
    } else
    if (warp == 0) {
      Ring r{0, 1, 3};
      uint32_t d = c_sched.queue[cta];
      for (int i = 0;; i++) {
        const Work w = decode(d);
        if (w.kind == 2) break;
        const CUtensorMap* m = w.kind == 0 ? &P.wq[w.beta >> 4] : &P.wo[w.beta >> 4];
        for (int ks = 0; ks < w.nsteps; ks++) {
          const uint32_t b = borrow(ks, w.nsteps);
          r.next_if(b == 2);
          const uint32_t bar = sbase + BAR_FULL + r.slot * 8;
          mbar_wait_w(bar + (BAR_EMPTY - BAR_FULL), r.phase);
          if (w.kind == 0) tma_ld3_w(sbase + r.slot * SLOT, m, 0, ks * 64, w.sub * 2, bar, 16384);
          else tma_ld_wo_w(sbase + r.slot * SLOT, m, w.sub * 128, (w.k0 + ks) * 2, bar);
          if (w.kind != 0 && w.beta < N_EARLY && (ks & 7) == 5 && ks > 5)
            asm volatile(ELECT "red.relaxed.gpu.global.add.u32 [%0], 1;\n}" ::"l"(&g_rd[w.beta][(ks >> 3) - 1]) : "memory");
          if (ks < 10) T2P(i, 2, ks);
          if (w.kind != 0 && ks == max(w.nsteps - GO_P, 4)) mbar_arrive_warp(sbase + BAR_GO);
          r.next(); r.next_if(b == 2);
        }
        if (w.kind == 0) {
          r.phase ^= 1; r.next(); r.next();
        } else if (w.mode == 2) {
          for (int k = 1; k <= ((d >> 5) & 3); k++) {
            if (k == 1) TTAIL(9);
            wait_count(&g_flag[w.range + 5 * k], lds(sbase + EPOCH_OFF));
            TTAIL(10);
            asm volatile("fence.proxy.async.global;" ::: "memory");
#pragma unroll 1
            for (int t = 0; t < 4; t++) {
              mbar_wait_w(sbase + BAR_EMPTY + r.slot * 8, r.phase);
              tma_ld3_w(sbase + r.slot * SLOT, &P.o_st[t == 3], 0, t * 64, NBETA * 64 + (w.range + 5 * k) * 2, sbase + BAR_FULL + r.slot * 8,
                        t == 3 ? 8192 : 16384);
              r.next();
            }
          }
        }
        mbar_wait_w(sbase + BAR_DESC, i & 1);
        d = __shfl_sync(0xffffffffu, lds(sbase + DESC_OFF + ((i + 1) & 3) * 4), 0);
      }
    } else {
      const int hi = warp - 2;
      uint64_t pol_stream;
      uint32_t rdy = 0;
      asm volatile("createpolicy.fractional.L2::evict_first.b64 %0, 1.0;" : "=l"(pol_stream));
      Ring r{0, 1, 3};
      uint32_t d = c_sched.queue[cta];
      for (int i = 0;; i++) {
        const Work w = decode(d);
        if (w.kind == 2) break;
        const CUtensorMap* m = w.kind == 0 ? &P.x[hi][w.beta >> 4] : &P.o_ld[hi];
        int c1 = (w.kind == 0 ? (w.beta & 15) : o_slot<SIMPLE>(w.beta) * 64 + w.k0) * SQ + hi * 128;
        int k_wait = -1;
        const bool both = PAIR && (w.kind == 0 || w.sub != 4), mine = !both || hi == (cta & 1);
        if (w.kind != 0 && mine) {
          if (d & 128) k_wait = d >= (3u << 30) ? 0 : 8 - (w.k0 & 7);
          asm volatile("fence.proxy.async.global;" ::: "memory");
        }
        const int rank = i == 0 ? cta : __shfl_sync(0xffffffffu, lds(sbase + EPOCH_OFF + 4), 0) - NCTA;
        for (int ks = 0; ks < w.nsteps; ks++) {
          if (ks == k_wait) {
            wait_count(&g_cnt[d & 31][(w.k0 + ks) >> 3], lds(sbase + EPOCH_OFF) * 4);
            asm volatile("fence.proxy.async.global;" ::: "memory");
            k_wait = ((w.k0 + ks) | 7) + 1 - w.k0;
          }
          const uint32_t b = borrow(ks, w.nsteps);
          const bool bo = b != 2;
          r.next_if(hi && !bo); r.next_if(hi && !bo);
          const uint32_t sl = bo ? NS + (b ^ (3 * hi)) : r.slot, bar = sbase + BAR_FULL + sl * 8;
          mbar_wait_w(bar + (BAR_EMPTY - BAR_FULL), bo ? (r.xp >> b) & 1 : r.phase);
          const uint32_t bytes = hi ? 96 * 128 : 128 * 128;
          if (!mine) {
            asm volatile(ELECT EXPECT("%0", "%2") "mbarrier.arrive.shared::cluster.b64 _, [%1];\n}"
                         ::"r"(bar), "r"(peer(bar + (BAR_RDY - BAR_FULL))), "r"(bytes) : "memory");
          } else if (both) {
            mbar_wait_w(bar + (BAR_RDY - BAR_FULL), (rdy >> sl) & 1);
            rdy ^= 1 << sl;
            if (w.kind == 0) tma_ld2_both_w(sbase + sl * SLOT, m, ks * 64, c1, bar, bytes);
            else tma_ld2_both_hint_w(sbase + sl * SLOT, m, 0, c1, bar, bytes, pol_stream);
          } else if (!PAIR && w.kind == 0) tma_ld2_w(sbase + sl * SLOT, m, ks * 64, c1, bar, bytes);
          else tma_ld2_hint_w(sbase + sl * SLOT, m, 0, c1, bar, bytes, pol_stream);
          if (w.kind != 0) c1 += SQ;
          if (i == 0 && ks == PF_STEP)
            asm volatile(ELECT "cp.async.bulk.prefetch.tensor.3d.L2.global.L2::cache_hint [%0, {0, %1, 0}], %2;\n}"
                         ::"l"(&P.kv[hi][0]), "r"(d * SK), "l"(pol_stream) : "memory");
          if (ks < 10) T2P(i, 3 + hi, ks);
          if (!hi && w.kind != 0 && !(ks & 3)) TCLK(i * 16 + (ks >> 2));
          r.next(); r.next_if(!hi && !bo); r.next_if(!hi && !bo);
          r.xp ^= 1 << b;
        }
        r.xp ^= 3;
        if (w.kind == 0) {
          m = &P.kv[hi][w.beta >> 4];
          c1 = (d & 511) * SK;
          for (int j = 0; j < 16; j++) {
            if (hi) r.next();
            const uint32_t bar = sbase + BAR_FULL + r.slot * 8;
            const bool tight = i < KV_WIN_UNITS && j < KV_WIN_TILES + ((KV_WIN_RAMP * rank) >> 5);
            {
              const int s2 = (int)r.slot - (tight ? 2 : KV_WIN_D);
              mbar_wait_w(sbase + BAR_FULL + (s2 < 0 ? s2 + NS : s2) * 8, s2 < 0 ? r.phase : r.phase ^ 1);
            }
            if (j == 15 && hi) mbar_wait_w(sbase + BAR_DESC, i & 1);
            mbar_wait_w(sbase + BAR_EMPTY + r.slot * 8, r.phase);
            tma_ld3_hint_w(sbase + r.slot * SLOT, m, 0, c1, 0, bar, pol_stream);
            T2P(i, 3 + hi, 16 + j);
            if (!hi) TCLK(i * 16 + j);
            if (j == 14 && !hi) mbar_arrive_warp(sbase + BAR_GO);
            c1 += 64;
            r.next();
            if (!hi) r.next();
          }
        }
        mbar_wait_w(sbase + BAR_DESC, i & 1);
        d = __shfl_sync(0xffffffffu, lds(sbase + DESC_OFF + ((i + 1) & 3) * 4), 0);
      }
    }
  } else {
    Ctx c;
    c.sb = sbase; c.wg = wg; c.warp = warp; c.src = 0; c.mqk = 0; c.mpv = 0; c.lead = lane == 0; c.lane0 = c.lane = lane;
    if (wg == 0) consumer<0>(c, P.kp); else consumer<1>(c, P.kp);
  }
}

typedef CUresult (*EncodeFn)(CUtensorMap*, CUtensorMapDataType, cuuint32_t, void*, const cuuint64_t*, const cuuint64_t*,
                             const cuuint32_t*, const cuuint32_t*, CUtensorMapInterleave, CUtensorMapSwizzle,
                             CUtensorMapL2promotion, CUtensorMapFloatOOBfill);

void make_map(EncodeFn enc, CUtensorMap* m, const void* ptr, int rank, const cuuint64_t* dims, const cuuint64_t* strides,
              const cuuint32_t* box, int promo = 2, CUtensorMapSwizzle swz = CU_TENSOR_MAP_SWIZZLE_128B) {
  cuuint32_t es[5] = {1, 1, 1, 1, 1};
  enc(m, CU_TENSOR_MAP_DATA_TYPE_BFLOAT16, rank, const_cast<void*>(ptr), dims, strides, box, es,
      CU_TENSOR_MAP_INTERLEAVE_NONE, swz, promo == 2 ? CU_TENSOR_MAP_L2_PROMOTION_L2_256B : promo == 1 ? CU_TENSOR_MAP_L2_PROMOTION_L2_128B : CU_TENSOR_MAP_L2_PROMOTION_NONE,
      CU_TENSOR_MAP_FLOAT_OOB_FILL_NONE);
}

}

extern "C" void kernel_launch(void* const* d_in, const int* in_sizes, int n_in, void* d_out, int out_size) {
  (void)in_sizes; (void)n_in; (void)out_size;
  static EncodeFn enc = nullptr;
  static void* o_ptr = nullptr;
  static int n_sm = 0;
  cudaLaunchAttribute at;
  at.id = cudaLaunchAttributeClusterDimension;
  at.val.clusterDim.x = CLUSTER ? 2 : 1; at.val.clusterDim.y = 1; at.val.clusterDim.z = 1;
  cudaLaunchConfig_t cfg = {};
  cfg.gridDim = dim3(NCTA); cfg.blockDim = dim3(384); cfg.dynamicSmemBytes = SMEM_BYTES; cfg.attrs = &at; cfg.numAttrs = 1;
  if (!enc) {
    void* fn = nullptr;
    cudaDriverEntryPointQueryResult qr;
    cudaGetDriverEntryPoint("cuTensorMapEncodeTiled", &fn, cudaEnableDefault, &qr);
    enc = (EncodeFn)fn;
    cudaGetSymbolAddress(&o_ptr, g_o);
    cudaFuncSetAttribute(mha_fused_kernel<false>, cudaFuncAttributeMaxDynamicSharedMemorySize, SMEM_BYTES);
    cudaFuncSetAttribute(mha_fused_kernel<true>, cudaFuncAttributeMaxDynamicSharedMemorySize, SMEM_BYTES);
    int dev = 0;
    cudaGetDevice(&dev);
    cudaDeviceGetAttribute(&n_sm, cudaDevAttrMultiProcessorCount, dev);
    int n_cl = 0;
    cudaOccupancyMaxActiveClusters(&n_cl, mha_fused_kernel<false>, &cfg);
    if (n_cl * (CLUSTER ? 2 : 1) < NCTA && n_sm >= NCTA) n_sm = NCTA - 1;
  }
  Params P;
  for (int br = 0; br < 2; br++) {
    const void* x = d_in[br * 5 + 0]; const void* kc = d_in[br * 5 + 1]; const void* vc = d_in[br * 5 + 2];
    const void* wq = d_in[br * 5 + 3]; const void* wo = d_in[br * 5 + 4];
    { cuuint64_t d[2] = {DM, (cuuint64_t)NB * SQ}, s[1] = {DM * 2}; cuuint32_t b[2] = {64, 128}, b2[2] = {64, 96};
      make_map(enc, &P.x[0][br], x, 2, d, s, b, PR_X); make_map(enc, &P.x[1][br], x, 2, d, s, b2, PR_X); }
    { cuuint64_t d[3] = {64, DM, HD / 64}, s[2] = {HD * 2, 128}; cuuint32_t b[3] = {64, 64, 2}; make_map(enc, &P.wq[br], wq, 3, d, s, b, PR_W); }
    { cuuint64_t d[5] = {DM, 2, 4, 4, HD / 32}, s[4] = {DM * 2, 8 * DM * 2, 2 * DM * 2, 32 * DM * 2}; cuuint32_t b[5] = {64, 2, 4, 4, 2};
      make_map(enc, &P.wo[br], wo, 5, d, s, b, PR_W); }
    { cuuint64_t d[3] = {64, (cuuint64_t)NB * NH * SK, 2}, s[2] = {DH * 2, 128}; cuuint32_t b[3] = {64, 64, 2};
      make_map(enc, &P.kv[0][br], kc, 3, d, s, b, PR_KV); make_map(enc, &P.kv[1][br], vc, 3, d, s, b, PR_KV); }
    P.kp[br] = (const __nv_bfloat16*)kc; P.vp[br] = (const __nv_bfloat16*)vc;

  }
  { cuuint64_t d[2] = {64, (cuuint64_t)NBETA * 64 * SQ}, s[1] = {128}; cuuint32_t b[2] = {64, 128}, b2[2] = {64, 96};
    make_map(enc, &P.o_ld[0], o_ptr, 2, d, s, b, 2, CU_TENSOR_MAP_SWIZZLE_NONE); make_map(enc, &P.o_ld[1], o_ptr, 2, d, s, b2, 2, CU_TENSOR_MAP_SWIZZLE_NONE); }
  { cuuint64_t d[3] = {64, SQ, O_BLOCKS}, s[2] = {128, SQ * 128}; cuuint32_t b[3] = {64, 64, 2}, b2[3] = {64, 32, 2};
    make_map(enc, &P.o_st[0], o_ptr, 3, d, s, b); make_map(enc, &P.o_st[1], o_ptr, 3, d, s, b2); }
  { cuuint64_t d[3] = {64, (cuuint64_t)NB * SQ, 2 * DM / 64}, s[2] = {2 * DM * 2, 128}; cuuint32_t b[3] = {64, 64, 2}, b2[3] = {64, 32, 2};
    make_map(enc, &P.out_st[0], d_out, 3, d, s, b); make_map(enc, &P.out_st[1], d_out, 3, d, s, b2); }
  if (n_sm >= NCTA) cudaLaunchKernelEx(&cfg, mha_fused_kernel<false>, P);
  else mha_fused_kernel<true><<<n_sm, 384, SMEM_BYTES>>>(P);
}
```

```cpp
#include <cuda_runtime.h>
#include <cuda_bf16.h>
#include <cuda.h>
#include <stdint.h>
#include <stdlib.h>

namespace {

__device__ __forceinline__ void wgmma_proj(float (&d)[64], uint64_t da, uint64_t db, int scaleD) {
  asm volatile("{\n.reg .pred p;\nsetp.ne.b32 p, %66, 0;\n"
      "wgmma.mma_async.sync.aligned.m64n128k16.f32.bf16.bf16 "
      "{%0, %1, %2, %3, %4, %5, %6, %7, %8, %9, %10, %11, %12, %13, %14, %15, %16, %17, %18, %19, %20, %21, %22, %23, %24, %25, %26, %27, %28, %29, %30, "
      "%31, %32, %33, %34, %35, %36, %37, %38, %39, %40, %41, %42, %43, %44, %45, %46, %47, %48, %49, %50, %51, %52, %53, %54, %55, %56, %57, %58, %59, %60, "
      "%61, %62, %63}, "
      "%64, %65, p, 1, 1, 0, 1;\n}\n"
      : "+f"(d[0]), "+f"(d[1]), "+f"(d[2]), "+f"(d[3]), "+f"(d[4]), "+f"(d[5]), "+f"(d[6]), "+f"(d[7]), "+f"(d[8]), "+f"(d[9]), "+f"(d[10]), "+f"(d[11]),
        "+f"(d[12]), "+f"(d[13]), "+f"(d[14]), "+f"(d[15]), "+f"(d[16]), "+f"(d[17]), "+f"(d[18]), "+f"(d[19]), "+f"(d[20]), "+f"(d[21]), "+f"(d[22]),
        "+f"(d[23]), "+f"(d[24]), "+f"(d[25]), "+f"(d[26]), "+f"(d[27]), "+f"(d[28]), "+f"(d[29]), "+f"(d[30]), "+f"(d[31]), "+f"(d[32]), "+f"(d[33]),
        "+f"(d[34]), "+f"(d[35]), "+f"(d[36]), "+f"(d[37]), "+f"(d[38]), "+f"(d[39]), "+f"(d[40]), "+f"(d[41]), "+f"(d[42]), "+f"(d[43]), "+f"(d[44]),
        "+f"(d[45]), "+f"(d[46]), "+f"(d[47]), "+f"(d[48]), "+f"(d[49]), "+f"(d[50]), "+f"(d[51]), "+f"(d[52]), "+f"(d[53]), "+f"(d[54]), "+f"(d[55]),
        "+f"(d[56]), "+f"(d[57]), "+f"(d[58]), "+f"(d[59]), "+f"(d[60]), "+f"(d[61]), "+f"(d[62]), "+f"(d[63])
      : "l"(da), "l"(db), "r"(scaleD));
}
__device__ __forceinline__ void wgmma_proj96(float (&d)[64], uint64_t da, uint64_t db, int scaleD) {
  asm volatile("{\n.reg .pred p;\nsetp.ne.b32 p, %50, 0;\n"
      "wgmma.mma_async.sync.aligned.m64n96k16.f32.bf16.bf16 "
      "{%0, %1, %2, %3, %4, %5, %6, %7, %8, %9, %10, %11, %12, %13, %14, %15, %16, %17, %18, %19, %20, %21, %22, %23, %24, %25, %26, %27, %28, %29, %30, "
      "%31, %32, %33, %34, %35, %36, %37, %38, %39, %40, %41, %42, %43, %44, %45, %46, %47}, "
      "%48, %49, p, 1, 1, 1, 0;\n}\n"
      : "+f"(d[0]), "+f"(d[1]), "+f"(d[2]), "+f"(d[3]), "+f"(d[4]), "+f"(d[5]), "+f"(d[6]), "+f"(d[7]), "+f"(d[8]), "+f"(d[9]), "+f"(d[10]), "+f"(d[11]),
        "+f"(d[12]), "+f"(d[13]), "+f"(d[14]), "+f"(d[15]), "+f"(d[16]), "+f"(d[17]), "+f"(d[18]), "+f"(d[19]), "+f"(d[20]), "+f"(d[21]), "+f"(d[22]),
        "+f"(d[23]), "+f"(d[24]), "+f"(d[25]), "+f"(d[26]), "+f"(d[27]), "+f"(d[28]), "+f"(d[29]), "+f"(d[30]), "+f"(d[31]), "+f"(d[32]), "+f"(d[33]),
        "+f"(d[34]), "+f"(d[35]), "+f"(d[36]), "+f"(d[37]), "+f"(d[38]), "+f"(d[39]), "+f"(d[40]), "+f"(d[41]), "+f"(d[42]), "+f"(d[43]), "+f"(d[44]),
        "+f"(d[45]), "+f"(d[46]), "+f"(d[47])
      : "l"(da), "l"(db), "r"(scaleD));
}
__device__ __forceinline__ void wgmma_qk(float (&d)[32], uint64_t da, uint64_t db, int scaleD) {
  asm volatile("{\n.reg .pred p;\nsetp.ne.b32 p, %34, 0;\n"
      "wgmma.mma_async.sync.aligned.m64n64k16.f32.bf16.bf16 "
      "{%0, %1, %2, %3, %4, %5, %6, %7, %8, %9, %10, %11, %12, %13, %14, %15, %16, %17, %18, %19, %20, %21, %22, %23, %24, %25, %26, %27, %28, %29, %30, "
      "%31}, "
      "%32, %33, p, 1, 1, 0, 0;\n}\n"
      : "+f"(d[0]), "+f"(d[1]), "+f"(d[2]), "+f"(d[3]), "+f"(d[4]), "+f"(d[5]), "+f"(d[6]), "+f"(d[7]), "+f"(d[8]), "+f"(d[9]), "+f"(d[10]), "+f"(d[11]),
        "+f"(d[12]), "+f"(d[13]), "+f"(d[14]), "+f"(d[15]), "+f"(d[16]), "+f"(d[17]), "+f"(d[18]), "+f"(d[19]), "+f"(d[20]), "+f"(d[21]), "+f"(d[22]),
        "+f"(d[23]), "+f"(d[24]), "+f"(d[25]), "+f"(d[26]), "+f"(d[27]), "+f"(d[28]), "+f"(d[29]), "+f"(d[30]), "+f"(d[31])
      : "l"(da), "l"(db), "r"(scaleD));
}
__device__ __forceinline__ void wgmma_qk_rs(float (&d)[32], uint32_t a0, uint32_t a1, uint32_t a2, uint32_t a3, uint64_t db, int scaleD) {
  asm volatile("{\n.reg .pred p;\nsetp.ne.b32 p, %37, 0;\n"
      "wgmma.mma_async.sync.aligned.m64n64k16.f32.bf16.bf16 "
      "{%0, %1, %2, %3, %4, %5, %6, %7, %8, %9, %10, %11, %12, %13, %14, %15, %16, %17, %18, %19, %20, %21, %22, %23, %24, %25, %26, %27, %28, %29, %30, "
      "%31}, "
      "{%32, %33, %34, %35}, %36, p, 1, 1, 0;\n}\n"
      : "+f"(d[0]), "+f"(d[1]), "+f"(d[2]), "+f"(d[3]), "+f"(d[4]), "+f"(d[5]), "+f"(d[6]), "+f"(d[7]), "+f"(d[8]), "+f"(d[9]), "+f"(d[10]), "+f"(d[11]),
        "+f"(d[12]), "+f"(d[13]), "+f"(d[14]), "+f"(d[15]), "+f"(d[16]), "+f"(d[17]), "+f"(d[18]), "+f"(d[19]), "+f"(d[20]), "+f"(d[21]), "+f"(d[22]),
        "+f"(d[23]), "+f"(d[24]), "+f"(d[25]), "+f"(d[26]), "+f"(d[27]), "+f"(d[28]), "+f"(d[29]), "+f"(d[30]), "+f"(d[31])
      : "r"(a0), "r"(a1), "r"(a2), "r"(a3), "l"(db), "r"(scaleD));
}
__device__ __forceinline__ void wgmma_pv(float (&d)[64], uint32_t a0, uint32_t a1, uint32_t a2, uint32_t a3, uint64_t db, int scaleD) {
  asm volatile("{\n.reg .pred p;\nsetp.ne.b32 p, %69, 0;\n"
      "wgmma.mma_async.sync.aligned.m64n128k16.f32.bf16.bf16 "
      "{%0, %1, %2, %3, %4, %5, %6, %7, %8, %9, %10, %11, %12, %13, %14, %15, %16, %17, %18, %19, %20, %21, %22, %23, %24, %25, %26, %27, %28, %29, %30, "
      "%31, %32, %33, %34, %35, %36, %37, %38, %39, %40, %41, %42, %43, %44, %45, %46, %47, %48, %49, %50, %51, %52, %53, %54, %55, %56, %57, %58, %59, %60, "
      "%61, %62, %63}, "
      "{%64, %65, %66, %67}, %68, p, 1, 1, 1;\n}\n"
      : "+f"(d[0]), "+f"(d[1]), "+f"(d[2]), "+f"(d[3]), "+f"(d[4]), "+f"(d[5]), "+f"(d[6]), "+f"(d[7]), "+f"(d[8]), "+f"(d[9]), "+f"(d[10]), "+f"(d[11]),
        "+f"(d[12]), "+f"(d[13]), "+f"(d[14]), "+f"(d[15]), "+f"(d[16]), "+f"(d[17]), "+f"(d[18]), "+f"(d[19]), "+f"(d[20]), "+f"(d[21]), "+f"(d[22]),
        "+f"(d[23]), "+f"(d[24]), "+f"(d[25]), "+f"(d[26]), "+f"(d[27]), "+f"(d[28]), "+f"(d[29]), "+f"(d[30]), "+f"(d[31]), "+f"(d[32]), "+f"(d[33]),
        "+f"(d[34]), "+f"(d[35]), "+f"(d[36]), "+f"(d[37]), "+f"(d[38]), "+f"(d[39]), "+f"(d[40]), "+f"(d[41]), "+f"(d[42]), "+f"(d[43]), "+f"(d[44]),
        "+f"(d[45]), "+f"(d[46]), "+f"(d[47]), "+f"(d[48]), "+f"(d[49]), "+f"(d[50]), "+f"(d[51]), "+f"(d[52]), "+f"(d[53]), "+f"(d[54]), "+f"(d[55]),
        "+f"(d[56]), "+f"(d[57]), "+f"(d[58]), "+f"(d[59]), "+f"(d[60]), "+f"(d[61]), "+f"(d[62]), "+f"(d[63])
      : "r"(a0), "r"(a1), "r"(a2), "r"(a3), "l"(db), "r"(scaleD));
}
__device__ __forceinline__ void wgmma_qk_sp(float (&d)[32], uint32_t a0, uint32_t a1, uint32_t a2, uint32_t a3, uint64_t db, int scaleD, uint32_t meta) {
  asm volatile("{\n.reg .pred p;\nsetp.ne.b32 p, %37, 0;\n"
      "wgmma.mma_async.sp.sync.aligned.m64n64k32.f32.bf16.bf16 "
      "{%0, %1, %2, %3, %4, %5, %6, %7, %8, %9, %10, %11, %12, %13, %14, %15, %16, %17, %18, %19, %20, %21, %22, %23, %24, %25, %26, %27, %28, %29, %30, "
      "%31}, "
      "{%32, %33, %34, %35}, %36, %38, 0, p, 1, 1, 0;\n}\n"
      : "+f"(d[0]), "+f"(d[1]), "+f"(d[2]), "+f"(d[3]), "+f"(d[4]), "+f"(d[5]), "+f"(d[6]), "+f"(d[7]), "+f"(d[8]), "+f"(d[9]), "+f"(d[10]), "+f"(d[11]),
        "+f"(d[12]), "+f"(d[13]), "+f"(d[14]), "+f"(d[15]), "+f"(d[16]), "+f"(d[17]), "+f"(d[18]), "+f"(d[19]), "+f"(d[20]), "+f"(d[21]), "+f"(d[22]),
        "+f"(d[23]), "+f"(d[24]), "+f"(d[25]), "+f"(d[26]), "+f"(d[27]), "+f"(d[28]), "+f"(d[29]), "+f"(d[30]), "+f"(d[31])
      : "r"(a0), "r"(a1), "r"(a2), "r"(a3), "l"(db), "r"(scaleD), "r"(meta));
}
__device__ __forceinline__ void wgmma_pv_sp(float (&d)[64], uint32_t a0, uint32_t a1, uint32_t a2, uint32_t a3, uint64_t db, int scaleD, uint32_t meta) {
  asm volatile("{\n.reg .pred p;\nsetp.ne.b32 p, %69, 0;\n"
      "wgmma.mma_async.sp.sync.aligned.m64n128k32.f32.bf16.bf16 "
      "{%0, %1, %2, %3, %4, %5, %6, %7, %8, %9, %10, %11, %12, %13, %14, %15, %16, %17, %18, %19, %20, %21, %22, %23, %24, %25, %26, %27, %28, %29, %30, "
      "%31, %32, %33, %34, %35, %36, %37, %38, %39, %40, %41, %42, %43, %44, %45, %46, %47, %48, %49, %50, %51, %52, %53, %54, %55, %56, %57, %58, %59, %60, "
      "%61, %62, %63}, "
      "{%64, %65, %66, %67}, %68, %70, 0, p, 1, 1, 1;\n}\n"
      : "+f"(d[0]), "+f"(d[1]), "+f"(d[2]), "+f"(d[3]), "+f"(d[4]), "+f"(d[5]), "+f"(d[6]), "+f"(d[7]), "+f"(d[8]), "+f"(d[9]), "+f"(d[10]), "+f"(d[11]),
        "+f"(d[12]), "+f"(d[13]), "+f"(d[14]), "+f"(d[15]), "+f"(d[16]), "+f"(d[17]), "+f"(d[18]), "+f"(d[19]), "+f"(d[20]), "+f"(d[21]), "+f"(d[22]),
        "+f"(d[23]), "+f"(d[24]), "+f"(d[25]), "+f"(d[26]), "+f"(d[27]), "+f"(d[28]), "+f"(d[29]), "+f"(d[30]), "+f"(d[31]), "+f"(d[32]), "+f"(d[33]),
        "+f"(d[34]), "+f"(d[35]), "+f"(d[36]), "+f"(d[37]), "+f"(d[38]), "+f"(d[39]), "+f"(d[40]), "+f"(d[41]), "+f"(d[42]), "+f"(d[43]), "+f"(d[44]),
        "+f"(d[45]), "+f"(d[46]), "+f"(d[47]), "+f"(d[48]), "+f"(d[49]), "+f"(d[50]), "+f"(d[51]), "+f"(d[52]), "+f"(d[53]), "+f"(d[54]), "+f"(d[55]),
        "+f"(d[56]), "+f"(d[57]), "+f"(d[58]), "+f"(d[59]), "+f"(d[60]), "+f"(d[61]), "+f"(d[62]), "+f"(d[63])
      : "r"(a0), "r"(a1), "r"(a2), "r"(a3), "l"(db), "r"(scaleD), "r"(meta));
}
__device__ __forceinline__ void wgmma_proj_init(float (&d)[64], uint64_t da, uint64_t db, int scaleD) {
  asm volatile("{\n.reg .pred p;\nsetp.ne.b32 p, %66, 0;\n"
      "wgmma.mma_async.sync.aligned.m64n128k16.f32.bf16.bf16 "
      "{%0, %1, %2, %3, %4, %5, %6, %7, %8, %9, %10, %11, %12, %13, %14, %15, %16, %17, %18, %19, %20, %21, %22, %23, %24, %25, %26, %27, %28, %29, %30, "
      "%31, %32, %33, %34, %35, %36, %37, %38, %39, %40, %41, %42, %43, %44, %45, %46, %47, %48, %49, %50, %51, %52, %53, %54, %55, %56, %57, %58, %59, %60, "
      "%61, %62, %63}, "
      "%64, %65, p, 1, 1, 0, 1;\n}\n"
      : "=f"(d[0]), "=f"(d[1]), "=f"(d[2]), "=f"(d[3]), "=f"(d[4]), "=f"(d[5]), "=f"(d[6]), "=f"(d[7]), "=f"(d[8]), "=f"(d[9]), "=f"(d[10]), "=f"(d[11]),
        "=f"(d[12]), "=f"(d[13]), "=f"(d[14]), "=f"(d[15]), "=f"(d[16]), "=f"(d[17]), "=f"(d[18]), "=f"(d[19]), "=f"(d[20]), "=f"(d[21]), "=f"(d[22]),
        "=f"(d[23]), "=f"(d[24]), "=f"(d[25]), "=f"(d[26]), "=f"(d[27]), "=f"(d[28]), "=f"(d[29]), "=f"(d[30]), "=f"(d[31]), "=f"(d[32]), "=f"(d[33]),
        "=f"(d[34]), "=f"(d[35]), "=f"(d[36]), "=f"(d[37]), "=f"(d[38]), "=f"(d[39]), "=f"(d[40]), "=f"(d[41]), "=f"(d[42]), "=f"(d[43]), "=f"(d[44]),
        "=f"(d[45]), "=f"(d[46]), "=f"(d[47]), "=f"(d[48]), "=f"(d[49]), "=f"(d[50]), "=f"(d[51]), "=f"(d[52]), "=f"(d[53]), "=f"(d[54]), "=f"(d[55]),
        "=f"(d[56]), "=f"(d[57]), "=f"(d[58]), "=f"(d[59]), "=f"(d[60]), "=f"(d[61]), "=f"(d[62]), "=f"(d[63])
      : "l"(da), "l"(db), "r"(scaleD));
}
__device__ __forceinline__ void wgmma_proj96_init(float (&d)[64], uint64_t da, uint64_t db, int scaleD) {
  asm volatile("{\n.reg .pred p;\nsetp.ne.b32 p, %50, 0;\n"
      "wgmma.mma_async.sync.aligned.m64n96k16.f32.bf16.bf16 "
      "{%0, %1, %2, %3, %4, %5, %6, %7, %8, %9, %10, %11, %12, %13, %14, %15, %16, %17, %18, %19, %20, %21, %22, %23, %24, %25, %26, %27, %28, %29, %30, "
      "%31, %32, %33, %34, %35, %36, %37, %38, %39, %40, %41, %42, %43, %44, %45, %46, %47}, "
      "%48, %49, p, 1, 1, 1, 0;\n}\n"
      : "=f"(d[0]), "=f"(d[1]), "=f"(d[2]), "=f"(d[3]), "=f"(d[4]), "=f"(d[5]), "=f"(d[6]), "=f"(d[7]), "=f"(d[8]), "=f"(d[9]), "=f"(d[10]), "=f"(d[11]),
        "=f"(d[12]), "=f"(d[13]), "=f"(d[14]), "=f"(d[15]), "=f"(d[16]), "=f"(d[17]), "=f"(d[18]), "=f"(d[19]), "=f"(d[20]), "=f"(d[21]), "=f"(d[22]),
        "=f"(d[23]), "=f"(d[24]), "=f"(d[25]), "=f"(d[26]), "=f"(d[27]), "=f"(d[28]), "=f"(d[29]), "=f"(d[30]), "=f"(d[31]), "=f"(d[32]), "=f"(d[33]),
        "=f"(d[34]), "=f"(d[35]), "=f"(d[36]), "=f"(d[37]), "=f"(d[38]), "=f"(d[39]), "=f"(d[40]), "=f"(d[41]), "=f"(d[42]), "=f"(d[43]), "=f"(d[44]),
        "=f"(d[45]), "=f"(d[46]), "=f"(d[47])
      : "l"(da), "l"(db), "r"(scaleD));
}
__device__ __forceinline__ void wgmma_qk_init(float (&d)[32], uint64_t da, uint64_t db, int scaleD) {
  asm volatile("{\n.reg .pred p;\nsetp.ne.b32 p, %34, 0;\n"
      "wgmma.mma_async.sync.aligned.m64n64k16.f32.bf16.bf16 "
      "{%0, %1, %2, %3, %4, %5, %6, %7, %8, %9, %10, %11, %12, %13, %14, %15, %16, %17, %18, %19, %20, %21, %22, %23, %24, %25, %26, %27, %28, %29, %30, "
      "%31}, "
      "%32, %33, p, 1, 1, 0, 0;\n}\n"
      : "=f"(d[0]), "=f"(d[1]), "=f"(d[2]), "=f"(d[3]), "=f"(d[4]), "=f"(d[5]), "=f"(d[6]), "=f"(d[7]), "=f"(d[8]), "=f"(d[9]), "=f"(d[10]), "=f"(d[11]),
        "=f"(d[12]), "=f"(d[13]), "=f"(d[14]), "=f"(d[15]), "=f"(d[16]), "=f"(d[17]), "=f"(d[18]), "=f"(d[19]), "=f"(d[20]), "=f"(d[21]), "=f"(d[22]),
        "=f"(d[23]), "=f"(d[24]), "=f"(d[25]), "=f"(d[26]), "=f"(d[27]), "=f"(d[28]), "=f"(d[29]), "=f"(d[30]), "=f"(d[31])
      : "l"(da), "l"(db), "r"(scaleD));
}
__device__ __forceinline__ void wgmma_qk_rs_init(float (&d)[32], uint32_t a0, uint32_t a1, uint32_t a2, uint32_t a3, uint64_t db, int scaleD) {
  asm volatile("{\n.reg .pred p;\nsetp.ne.b32 p, %37, 0;\n"
      "wgmma.mma_async.sync.aligned.m64n64k16.f32.bf16.bf16 "
      "{%0, %1, %2, %3, %4, %5, %6, %7, %8, %9, %10, %11, %12, %13, %14, %15, %16, %17, %18, %19, %20, %21, %22, %23, %24, %25, %26, %27, %28, %29, %30, "
      "%31}, "
      "{%32, %33, %34, %35}, %36, p, 1, 1, 0;\n}\n"
      : "=f"(d[0]), "=f"(d[1]), "=f"(d[2]), "=f"(d[3]), "=f"(d[4]), "=f"(d[5]), "=f"(d[6]), "=f"(d[7]), "=f"(d[8]), "=f"(d[9]), "=f"(d[10]), "=f"(d[11]),
        "=f"(d[12]), "=f"(d[13]), "=f"(d[14]), "=f"(d[15]), "=f"(d[16]), "=f"(d[17]), "=f"(d[18]), "=f"(d[19]), "=f"(d[20]), "=f"(d[21]), "=f"(d[22]),
        "=f"(d[23]), "=f"(d[24]), "=f"(d[25]), "=f"(d[26]), "=f"(d[27]), "=f"(d[28]), "=f"(d[29]), "=f"(d[30]), "=f"(d[31])
      : "r"(a0), "r"(a1), "r"(a2), "r"(a3), "l"(db), "r"(scaleD));
}
__device__ __forceinline__ void wgmma_pv_init(float (&d)[64], uint32_t a0, uint32_t a1, uint32_t a2, uint32_t a3, uint64_t db, int scaleD) {
  asm volatile("{\n.reg .pred p;\nsetp.ne.b32 p, %69, 0;\n"
      "wgmma.mma_async.sync.aligned.m64n128k16.f32.bf16.bf16 "
      "{%0, %1, %2, %3, %4, %5, %6, %7, %8, %9, %10, %11, %12, %13, %14, %15, %16, %17, %18, %19, %20, %21, %22, %23, %24, %25, %26, %27, %28, %29, %30, "
      "%31, %32, %33, %34, %35, %36, %37, %38, %39, %40, %41, %42, %43, %44, %45, %46, %47, %48, %49, %50, %51, %52, %53, %54, %55, %56, %57, %58, %59, %60, "
      "%61, %62, %63}, "
      "{%64, %65, %66, %67}, %68, p, 1, 1, 1;\n}\n"
      : "=f"(d[0]), "=f"(d[1]), "=f"(d[2]), "=f"(d[3]), "=f"(d[4]), "=f"(d[5]), "=f"(d[6]), "=f"(d[7]), "=f"(d[8]), "=f"(d[9]), "=f"(d[10]), "=f"(d[11]),
        "=f"(d[12]), "=f"(d[13]), "=f"(d[14]), "=f"(d[15]), "=f"(d[16]), "=f"(d[17]), "=f"(d[18]), "=f"(d[19]), "=f"(d[20]), "=f"(d[21]), "=f"(d[22]),
        "=f"(d[23]), "=f"(d[24]), "=f"(d[25]), "=f"(d[26]), "=f"(d[27]), "=f"(d[28]), "=f"(d[29]), "=f"(d[30]), "=f"(d[31]), "=f"(d[32]), "=f"(d[33]),
        "=f"(d[34]), "=f"(d[35]), "=f"(d[36]), "=f"(d[37]), "=f"(d[38]), "=f"(d[39]), "=f"(d[40]), "=f"(d[41]), "=f"(d[42]), "=f"(d[43]), "=f"(d[44]),
        "=f"(d[45]), "=f"(d[46]), "=f"(d[47]), "=f"(d[48]), "=f"(d[49]), "=f"(d[50]), "=f"(d[51]), "=f"(d[52]), "=f"(d[53]), "=f"(d[54]), "=f"(d[55]),
        "=f"(d[56]), "=f"(d[57]), "=f"(d[58]), "=f"(d[59]), "=f"(d[60]), "=f"(d[61]), "=f"(d[62]), "=f"(d[63])
      : "r"(a0), "r"(a1), "r"(a2), "r"(a3), "l"(db), "r"(scaleD));
}
__device__ __forceinline__ void wgmma_qk_sp_init(float (&d)[32], uint32_t a0, uint32_t a1, uint32_t a2, uint32_t a3, uint64_t db, int scaleD, uint32_t meta) {
  asm volatile("{\n.reg .pred p;\nsetp.ne.b32 p, %37, 0;\n"
      "wgmma.mma_async.sp.sync.aligned.m64n64k32.f32.bf16.bf16 "
      "{%0, %1, %2, %3, %4, %5, %6, %7, %8, %9, %10, %11, %12, %13, %14, %15, %16, %17, %18, %19, %20, %21, %22, %23, %24, %25, %26, %27, %28, %29, %30, "
      "%31}, "
      "{%32, %33, %34, %35}, %36, %38, 0, p, 1, 1, 0;\n}\n"
      : "=f"(d[0]), "=f"(d[1]), "=f"(d[2]), "=f"(d[3]), "=f"(d[4]), "=f"(d[5]), "=f"(d[6]), "=f"(d[7]), "=f"(d[8]), "=f"(d[9]), "=f"(d[10]), "=f"(d[11]),
        "=f"(d[12]), "=f"(d[13]), "=f"(d[14]), "=f"(d[15]), "=f"(d[16]), "=f"(d[17]), "=f"(d[18]), "=f"(d[19]), "=f"(d[20]), "=f"(d[21]), "=f"(d[22]),
        "=f"(d[23]), "=f"(d[24]), "=f"(d[25]), "=f"(d[26]), "=f"(d[27]), "=f"(d[28]), "=f"(d[29]), "=f"(d[30]), "=f"(d[31])
      : "r"(a0), "r"(a1), "r"(a2), "r"(a3), "l"(db), "r"(scaleD), "r"(meta));
}
__device__ __forceinline__ void wgmma_pv_sp_init(float (&d)[64], uint32_t a0, uint32_t a1, uint32_t a2, uint32_t a3, uint64_t db, int scaleD, uint32_t meta) {
  asm volatile("{\n.reg .pred p;\nsetp.ne.b32 p, %69, 0;\n"
      "wgmma.mma_async.sp.sync.aligned.m64n128k32.f32.bf16.bf16 "
      "{%0, %1, %2, %3, %4, %5, %6, %7, %8, %9, %10, %11, %12, %13, %14, %15, %16, %17, %18, %19, %20, %21, %22, %23, %24, %25, %26, %27, %28, %29, %30, "
      "%31, %32, %33, %34, %35, %36, %37, %38, %39, %40, %41, %42, %43, %44, %45, %46, %47, %48, %49, %50, %51, %52, %53, %54, %55, %56, %57, %58, %59, %60, "
      "%61, %62, %63}, "
      "{%64, %65, %66, %67}, %68, %70, 0, p, 1, 1, 1;\n}\n"
      : "=f"(d[0]), "=f"(d[1]), "=f"(d[2]), "=f"(d[3]), "=f"(d[4]), "=f"(d[5]), "=f"(d[6]), "=f"(d[7]), "=f"(d[8]), "=f"(d[9]), "=f"(d[10]), "=f"(d[11]),
        "=f"(d[12]), "=f"(d[13]), "=f"(d[14]), "=f"(d[15]), "=f"(d[16]), "=f"(d[17]), "=f"(d[18]), "=f"(d[19]), "=f"(d[20]), "=f"(d[21]), "=f"(d[22]),
        "=f"(d[23]), "=f"(d[24]), "=f"(d[25]), "=f"(d[26]), "=f"(d[27]), "=f"(d[28]), "=f"(d[29]), "=f"(d[30]), "=f"(d[31]), "=f"(d[32]), "=f"(d[33]),
        "=f"(d[34]), "=f"(d[35]), "=f"(d[36]), "=f"(d[37]), "=f"(d[38]), "=f"(d[39]), "=f"(d[40]), "=f"(d[41]), "=f"(d[42]), "=f"(d[43]), "=f"(d[44]),
        "=f"(d[45]), "=f"(d[46]), "=f"(d[47]), "=f"(d[48]), "=f"(d[49]), "=f"(d[50]), "=f"(d[51]), "=f"(d[52]), "=f"(d[53]), "=f"(d[54]), "=f"(d[55]),
        "=f"(d[56]), "=f"(d[57]), "=f"(d[58]), "=f"(d[59]), "=f"(d[60]), "=f"(d[61]), "=f"(d[62]), "=f"(d[63])
      : "r"(a0), "r"(a1), "r"(a2), "r"(a3), "l"(db), "r"(scaleD), "r"(meta));
}

constexpr int NB = 16, SQ = 224, DM = 640, NH = 32, SK = 1024, DH = 128;
constexpr int HD = NH * DH;
constexpr int NBETA = 2 * NB;
constexpr int NCTA = 132;
constexpr uint32_t SB0 = 1024;
constexpr int NS = 10;
constexpr int SLOT = 16384;
constexpr int QBUF_OFF = NS * SLOT;
constexpr int NSX = NS + 4;
constexpr int BAR_OFF = NSX * SLOT;
constexpr int BAR_FULL = BAR_OFF;
constexpr int BAR_EMPTY = BAR_OFF + 8 * NSX;
constexpr int BAR_STG = BAR_OFF + 16 * NSX;
constexpr int BAR_OUT = BAR_STG + 32;
constexpr int BAR_DESC = BAR_OUT + 8;
constexpr int BAR_GO = BAR_DESC + 8;
constexpr int BAR_MAIL = BAR_GO + 8;
constexpr int BAR_RDY = BAR_MAIL + 8;
constexpr int DESC_OFF = BAR_RDY + 8 * NSX;
constexpr int EPOCH_OFF = DESC_OFF + 16;
constexpr int TRACE_OFF = EPOCH_OFF + 16;
constexpr int SMEM_BYTES = TRACE_OFF;
constexpr float SM_C = 0.08838834764831845f * 1.4426950408889634f;
constexpr float SUM_HI = 1099511627776.f, SUM_LO = 1.f / 1099511627776.f;
constexpr uint32_t META_QK = 0xEEEE4444u;
constexpr uint32_t META_PV = 0x44EEEE44u;

#define QK_EARLY_MASK 3
#define ST_ORDER 0x2310
#define LAG_BAR 3
#define ST_NOW 8
#define PF_STEP 5
#define KV_WIN_UNITS 2
#define KV_WIN_D 4
#define SF 0xfebf
#define O_STEPS 4
#define KV_WIN_RAMP 4
#define PDEPTH 0
#define KV_WIN_TILES -2
#define PR_KV 2
#define PR_X 2
#define PR_W 2
#define REG_C 232
#define REG_P 24
#define GO_P 4
#define P_POS 216
#define OR 6
#define OR0 0
#define B_LATE 23
#define H_LATE 24
#define RM0 1
#define RM1 0xb5
#define RM2 0
#define CLUSTER 1
#define PAIRB 1
#define LATE0 1
#define LATE1 2
#define PAD0 0
#define PAD1 0
#define KG 5
#define PK 44
#define EARLY_MASK 0x3fffu
#define PIECE_TABLE 0x50188016,0x65e88038,0x50321819,0x6c8d1830,0x403f2812,0x80000000,0x50215014,0x695a503c,0x5029b813,0x6c4eb85e,0x501b4815,0x689d4834,0x502b1017,0x6ccc1039,0x50312010,0x80000000,0x500e681b,0x65e8683f,0x502ea011,0x80000000,0x63b1902e,0x80000000,0x63f0603b,0x80000000,0x64ad003d,0x80000000,0x64eca83a,0x80000000,0x5024581c,0x80000000,0x5012b01a,0x6a95b033,0x5011081d,0x6b130837,0x5016701f,0x6c8d7056,0x501ec81e,0x80000000,0x6723302f,0x80000000,0x501b380f,0x80000000,0x67234035,0x80000000,0x500d980e,0x6bd09831,0x56587816,0x80000000,0x50168818,0x80000000,0x57d1c01e,0x80000000

struct Params {
  CUtensorMap x[2][2], wq[2], kv[2][2], wo[2];
  CUtensorMap o_ld[2], o_st[2], out_st[2];
  const __nv_bfloat16* kp[2];
  const __nv_bfloat16* vp[2];
};

constexpr int NPART = 32 * 5, O_BLOCKS = NBETA * 64 + 2 * NPART;
__device__ __align__(128) __nv_bfloat16 g_o[(size_t)O_BLOCKS * SQ * 64];
__device__ unsigned g_cnt[NBETA][8];
__device__ unsigned g_rd[NBETA][8];
__device__ unsigned g_epoch, g_next;
__device__ unsigned g_flag[NPART];

__device__ __forceinline__ uint32_t smem_u32(const void* p) { return (uint32_t)__cvta_generic_to_shared(p); }
__device__ __forceinline__ void mbar_arrive(uint32_t bar) {
  asm volatile("mbarrier.arrive.shared::cta.b64 _, [%0];" ::"r"(bar) : "memory");
}
__device__ __forceinline__ void mbar_arrive_warp(uint32_t bar) {
  asm volatile("{\n.reg .pred p;\nelect.sync _|p, 0xffffffff;\n@p mbarrier.arrive.shared::cta.b64 _, [%0];\n}" ::"r"(bar) : "memory");
}
__device__ __forceinline__ int lane_now() { int l; asm volatile("mov.u32 %0, %%laneid;" : "=r"(l)); return l; }
__device__ __forceinline__ bool mbar_try(uint32_t bar, uint32_t parity) {
  uint32_t ok;
  asm volatile("{\n.reg .pred p;\nmbarrier.try_wait.parity.shared::cta.b64 p, [%1], %2;\nselp.u32 %0, 1, 0, p;\n}"
               : "=r"(ok) : "r"(bar), "r"(parity) : "memory");
  return ok;
}
__device__ __forceinline__ bool mbar_test(uint32_t bar, uint32_t parity) {
  uint32_t ok;
  asm volatile("{\n.reg .pred p;\nmbarrier.test_wait.parity.shared::cta.b64 p, [%1], %2;\nselp.u32 %0, 1, 0, p;\n}"
               : "=r"(ok) : "r"(bar), "r"(parity) : "memory");
  return ok;
}
__device__ __forceinline__ void mbar_wait_w(uint32_t bar, uint32_t parity) {
  uint32_t n = 0;
  while (!__all_sync(0xffffffffu, mbar_try(bar, parity))) {
    if (++n > (1u << 22)) __trap();
  }
}
#define ELECT "{\n.reg .pred p;\nelect.sync _|p, 0xffffffff;\n@p "
__device__ __forceinline__ void tma_st3_hint_w(const CUtensorMap* m, uint32_t src, int c0, int c1, int c2, uint64_t pol) {
  asm volatile(ELECT "cp.async.bulk.tensor.3d.global.shared::cta.bulk_group.L2::cache_hint [%0, {%2, %3, %4}], [%1], %5;\n}"
               ::"l"(m), "r"(src), "r"(c0), "r"(c1), "r"(c2), "l"(pol) : "memory");
}
#define EXPECT(bar, bytes) "mbarrier.arrive.expect_tx.shared::cta.b64 _, [" bar "], " bytes ";\n@p "
__device__ __forceinline__ void tma_ld2_w(uint32_t dst, const CUtensorMap* m, int c0, int c1, uint32_t bar, uint32_t bytes) {
  asm volatile(ELECT EXPECT("%2", "%5") "cp.async.bulk.tensor.2d.shared::cluster.global.mbarrier::complete_tx::bytes [%0], [%1, {%3, %4}], [%2];\n}"
               ::"r"(dst), "l"(m), "r"(bar), "r"(c0), "r"(c1), "r"(bytes) : "memory");
}
__device__ __forceinline__ void tma_ld2_hint_w(uint32_t dst, const CUtensorMap* m, int c0, int c1, uint32_t bar, uint32_t bytes, uint64_t pol) {
  asm volatile(ELECT EXPECT("%2", "%6") "cp.async.bulk.tensor.2d.shared::cluster.global.mbarrier::complete_tx::bytes.L2::cache_hint"
               " [%0], [%1, {%3, %4}], [%2], %5;\n}"
               ::"r"(dst), "l"(m), "r"(bar), "r"(c0), "r"(c1), "l"(pol), "r"(bytes) : "memory");
}
__device__ __forceinline__ void tma_ld3_w(uint32_t dst, const CUtensorMap* m, int c0, int c1, int c2, uint32_t bar, uint32_t bytes) {
  asm volatile(ELECT EXPECT("%2", "%6") "cp.async.bulk.tensor.3d.shared::cluster.global.mbarrier::complete_tx::bytes [%0], [%1, {%3, %4, %5}], [%2];\n}"
               ::"r"(dst), "l"(m), "r"(bar), "r"(c0), "r"(c1), "r"(c2), "r"(bytes) : "memory");
}
__device__ __forceinline__ void tma_ld3_hint_w(uint32_t dst, const CUtensorMap* m, int c0, int c1, int c2, uint32_t bar, uint64_t pol) {
  asm volatile(ELECT EXPECT("%2", "16384") "cp.async.bulk.tensor.3d.shared::cluster.global.mbarrier::complete_tx::bytes.L2::cache_hint"
               " [%0], [%1, {%3, %4, %5}], [%2], %6;\n}"
               ::"r"(dst), "l"(m), "r"(bar), "r"(c0), "r"(c1), "r"(c2), "l"(pol) : "memory");
}
__device__ __forceinline__ void tma_ld_wo_w(uint32_t dst, const CUtensorMap* m, int col, int grp, uint32_t bar) {
  asm volatile(ELECT EXPECT("%2", "16384") "cp.async.bulk.tensor.5d.shared::cluster.global.mbarrier::complete_tx::bytes [%0], [%1, {%3, 0, 0, 0, %4}], [%2];\n"
               "@p cp.async.bulk.tensor.5d.shared::cluster.global.mbarrier::complete_tx::bytes [%5], [%1, {%6, 0, 0, 0, %4}], [%2];\n}"
               ::"r"(dst), "l"(m), "r"(bar), "r"(col), "r"(grp), "r"(dst + 8192), "r"(col + 64) : "memory");
}
__device__ __forceinline__ void mbar_arrive8_w(uint32_t bar) {
  asm volatile(ELECT "mbarrier.arrive.shared::cta.b64 _, [%0], 8;\n}" ::"r"(bar) : "memory");
}
__device__ __forceinline__ uint32_t peer(uint32_t a) { uint32_t r; asm("mapa.shared::cluster.u32 %0, %1, %2;" : "=r"(r) : "r"(a), "r"(~blockIdx.x & 1)); return r; }
__device__ __forceinline__ void tma_ld2_both_w(uint32_t dst, const CUtensorMap* m, int c0, int c1, uint32_t bar, uint32_t bytes) {
  asm volatile(ELECT EXPECT("%2", "%5") "cp.async.bulk.tensor.2d.shared::cluster.global.mbarrier::complete_tx::bytes.multicast::cluster"
               " [%0], [%1, {%3, %4}], [%2], %6;\n}"
               ::"r"(dst), "l"(m), "r"(bar), "r"(c0), "r"(c1), "r"(bytes), "h"((uint16_t)3) : "memory");
}
__device__ __forceinline__ void tma_ld2_both_hint_w(uint32_t dst, const CUtensorMap* m, int c0, int c1, uint32_t bar, uint32_t bytes, uint64_t pol) {
  asm volatile(ELECT EXPECT("%2", "%6") "cp.async.bulk.tensor.2d.shared::cluster.global.mbarrier::complete_tx::bytes.multicast::cluster.L2::cache_hint"
               " [%0], [%1, {%3, %4}], [%2], %7, %5;\n}"
               ::"r"(dst), "l"(m), "r"(bar), "r"(c0), "r"(c1), "l"(pol), "r"(bytes), "h"((uint16_t)3) : "memory");
}
__device__ __forceinline__ void bulk_commit() { asm volatile("cp.async.bulk.commit_group;" ::: "memory"); }
template <int N> __device__ __forceinline__ void bulk_wait_read() { asm volatile("cp.async.bulk.wait_group.read %0;" ::"n"(N) : "memory"); }
__device__ __forceinline__ void wg_fence() { asm volatile("wgmma.fence.sync.aligned;" ::: "memory"); }
__device__ __forceinline__ void wg_commit() { asm volatile("wgmma.commit_group.sync.aligned;" ::: "memory"); }
template <int N> __device__ __forceinline__ void wg_wait() { asm volatile("wgmma.wait_group.sync.aligned %0;" ::"n"(N) : "memory"); }
__device__ __forceinline__ void fence_async_smem() { asm volatile("fence.proxy.async.shared::cta;" ::: "memory"); }
__device__ __forceinline__ void bar_sync(int id, int n) { asm volatile("bar.sync %0, %1;" ::"r"(id), "r"(n) : "memory"); }
__device__ __forceinline__ void touch(float& a) { asm volatile("neg.f32 %0, %0;" : "+f"(a)); }
__device__ __forceinline__ void touch(uint32_t& a) { asm volatile("not.b32 %0, %0;" : "+r"(a)); }
template <typename T, int N> __device__ __forceinline__ void touch(T (&a)[N]) {
#pragma unroll
  for (int i = 0; i < N; i++) touch(a[i]);
}
template <int ID, typename... A> __device__ __forceinline__ void sched_fence(uint32_t x, A&... a) {
  if (!((SF >> ID) & 1)) return;
  asm volatile("" : "+r"(x)::"memory");
#pragma unroll 1
  for (; __builtin_expect(x >= 100 + ID, 0); x >>= 1) { (touch(a), ...); __nanosleep(x); }
}
template <int N> __device__ __forceinline__ void reg_fence(float (&a)[N]) {
#pragma unroll
  for (int i = 0; i < N; i++) asm volatile("" : "+f"(a[i])::"memory");
}
template <int N> __device__ __forceinline__ void reg_fence(uint32_t (&a)[N]) {
#pragma unroll
  for (int i = 0; i < N; i++) asm volatile("" : "+r"(a[i])::"memory");
}
__device__ __forceinline__ float ex2(float x) { float y; asm("ex2.approx.ftz.f32 %0, %1;" : "=f"(y) : "f"(x)); return y; }
__device__ __forceinline__ uint32_t pack_bf16(float lo, float hi) {
  uint32_t r; asm("cvt.rn.bf16x2.f32 %0, %1, %2;" : "=r"(r) : "f"(hi), "f"(lo)); return r;
}
__device__ __forceinline__ void stsm4(uint32_t a, uint32_t r0, uint32_t r1, uint32_t r2, uint32_t r3) {
  asm volatile("stmatrix.sync.aligned.m8n8.x4.shared.b16 [%0], {%1, %2, %3, %4};" ::"r"(a), "r"(r0), "r"(r1), "r"(r2), "r"(r3) : "memory");
}
__device__ __forceinline__ void stsm4t(uint32_t a, uint32_t r0, uint32_t r1, uint32_t r2, uint32_t r3) {
  asm volatile("stmatrix.sync.aligned.m8n8.x4.trans.shared.b16 [%0], {%1, %2, %3, %4};" ::"r"(a), "r"(r0), "r"(r1), "r"(r2), "r"(r3) : "memory");
}
__device__ __forceinline__ void ldsm4(uint32_t a, uint32_t& r0, uint32_t& r1, uint32_t& r2, uint32_t& r3) {
  asm volatile("ldmatrix.sync.aligned.m8n8.x4.shared.b16 {%0, %1, %2, %3}, [%4];" : "=r"(r0), "=r"(r1), "=r"(r2), "=r"(r3) : "r"(a) : "memory");
}
__device__ __forceinline__ void sts16(uint32_t a, uint32_t v) { asm volatile("st.shared.u16 [%0], %1;" ::"r"(a), "h"((uint16_t)v) : "memory"); }
__device__ __forceinline__ void mma16816(float& c0, float& c1, float& c2, float& c3, uint32_t a0, uint32_t a1, uint32_t a2, uint32_t a3,
                                         uint32_t b0, uint32_t b1) {
  asm volatile("mma.sync.aligned.m16n8k16.row.col.f32.bf16.bf16.f32 {%0, %1, %2, %3}, {%4, %5, %6, %7}, {%8, %9}, {%0, %1, %2, %3};"
               : "+f"(c0), "+f"(c1), "+f"(c2), "+f"(c3) : "r"(a0), "r"(a1), "r"(a2), "r"(a3), "r"(b0), "r"(b1));
}
__device__ __forceinline__ uint32_t sdesc(uint32_t addr, uint32_t lbo) { return (addr >> 4) + ((lbo >> 4) << 16); }
__device__ __forceinline__ uint64_t desc64(uint32_t lo, uint32_t hi) { uint64_t d; asm("mov.b64 %0, {%1, %2};" : "=l"(d) : "r"(lo), "r"(hi)); return d; }
__device__ __forceinline__ void dadd(uint64_t& d, uint32_t inc) {
  asm("{\n.reg .b32 l, h;\nmov.b64 {l, h}, %0;\nadd.u32 l, l, %1;\nmov.b64 %0, {l, h};\n}" : "+l"(d) : "r"(inc));
}

struct Ring {
  uint32_t slot, phase, xp;
  __device__ __forceinline__ void uniform() {
    slot = __shfl_sync(0xffffffffu, slot, 0); phase = __shfl_sync(0xffffffffu, phase, 0); xp = __shfl_sync(0xffffffffu, xp, 0);
  }
  __device__ __forceinline__ void next() { if (++slot == NS) { slot = 0; phase ^= 1; } }
  __device__ __forceinline__ void next_if(bool p) { slot += p; if (slot == NS) { slot = 0; phase ^= 1; } }
};
__device__ __forceinline__ uint32_t borrow(int ks, int n) {
  const int k = ks + 1;
  return k >= 4 && !(k & 2) && k < n ? k & 1 : 2;
}

constexpr uint32_t Q_RANGES = NBETA * NH + __builtin_popcount(EARLY_MASK) * 5, Q_ALL = NBETA * (NH + 5);
constexpr int NRANGE = NCTA / 5;
struct Work { int kind, mode, k0, nsteps, range, beta, sub; };
struct Sched { uint16_t queue[Q_ALL]; uint32_t piece[NRANGE + 1][4]; };
constexpr Sched make_sched() {
  Sched s{};
  int q = 0, a = 0;
  for (int t = 0, e = 0; a < NBETA * NH; t++) {
    for (; e < NBETA && 8 * (e & ~PAIRB) + PK <= t && a >= P_POS; e++)
      for (int col = 0; col < 5 && (EARLY_MASK >> e & 1); col++) s.queue[q++] = 0x8000 | (e & 1 ? 4 - col : col) << 8 | e;
    for (int b = 0; b < NBETA; b++)
      for (int h = 0; h < NH; h++)
        if ((b >= B_LATE && h >= H_LATE ? 300 + b : 8 * (b & ~PAIRB) + KG * (h >> 2)) == t) { s.queue[q++] = b << 5 | h; a++; }
  }
  for (int b = 0; b < NBETA; b++)
    for (int col = 0; col < 5 && !(EARLY_MASK >> b & 1); col++) s.queue[q++] = 0x8000 | col << 8 | b;
  constexpr uint32_t T[NRANGE * 2] = {PIECE_TABLE};
  for (int g = 0; g <= NRANGE; g++)
    for (int n = 0; n < 4; n++) s.piece[g][n] = g < NRANGE && n < 2 ? T[2 * g + n] : 2u << 30;
  return s;
}
__constant__ Sched c_sched = make_sched();
constexpr int N_EARLY = __builtin_popcount(EARLY_MASK);
constexpr bool reuse_ok() {
  const Sched s = make_sched();
  int first[NBETA + OR] = {};
  for (int q = Q_RANGES - 1; q >= 0; q--) if (!(s.queue[q] & 0x8000)) first[s.queue[q] >> 5] = q;
  for (int q = 0; q < Q_RANGES; q++) if ((s.queue[q] & 0x8000) && (s.queue[q] & 31) >= OR0 && q - first[(s.queue[q] & 31) + OR] > NCTA - 32) return false;
  return true;
}
static_assert(reuse_ok());
template <bool SIMPLE> __device__ __forceinline__ bool o_reuse(uint32_t b) { return !SIMPLE && b - (OR0 + OR) < N_EARLY - OR0; }
template <bool SIMPLE> __device__ __forceinline__ uint32_t o_slot(uint32_t b) { return o_reuse<SIMPLE>(b) ? OR0 + (b - OR0) % OR : b; }
__device__ __forceinline__ Work decode(uint32_t d) {
  Work w;
  w.kind = d >> 30; if (w.kind == 3) w.kind = 1;
  w.mode = (d >> 28) & 3; w.k0 = (d >> 22) & 63;
  if (w.kind == 0) { w.beta = (d >> 5) & 31; w.sub = d & 31; w.nsteps = DM / 64; }
  else { w.beta = d & 31; w.sub = (d >> 8) & 7; w.nsteps = ((d >> 16) & 63) + 1; }
  w.range = ((d >> 11) & 31) * 5 + w.sub;
  return w;
}

__device__ __forceinline__ bool reached(const unsigned* cnt, unsigned target) {
  unsigned v;
  asm volatile("ld.acquire.gpu.global.u32 %0, [%1];" : "=r"(v) : "l"(cnt) : "memory");
  return (int)(v - target) >= 0;
}
__device__ __forceinline__ void wait_count(const unsigned* cnt, unsigned target) {
  unsigned n = 0;
  while (!__all_sync(0xffffffffu, reached(cnt, target))) { if (++n > (1u << 24)) __trap(); }
}
__device__ __forceinline__ uint32_t lds(uint32_t a) { uint32_t v; asm volatile("ld.volatile.shared.u32 %0, [%1];" : "=r"(v) : "r"(a) : "memory"); return v; }

#define TRACE(u, e)
#define T3(u, e)
#define T2C(u, e)
#define T2P(u, r, e)
#define TTAIL(k)
#define TCLK(k)
#define TO -1
#define TRACE_O(k) if (TO == k) TRACE(i, 5)
#define TRACE_P(u, e)
#define TRACE_IN(u, e)

struct Ctx {
  uint32_t sb;
  int wg, warp;
  uint32_t mqk, mpv;
  bool lead;
  int lane0, lane;
  int src;
};
template <int N> __device__ __forceinline__ uint32_t dhi(uint32_t lo) { return 0x40000040u + (lo >> (26 + N)); }
__device__ __forceinline__ void release(const Ctx& c, uint32_t slot) {
  if (c.lead) mbar_arrive(c.sb + BAR_EMPTY + slot * 8);
}
__device__ __forceinline__ uint32_t acquire(const Ctx& c, Ring& r, bool have = false) {
  const uint32_t s = r.slot;
  if (!have) mbar_wait_w(c.sb + BAR_FULL + s * 8, r.phase);
  r.next();
  return s;
}
__device__ __forceinline__ void mbar_wait2_w(uint32_t b0, uint32_t p0, uint32_t b1, uint32_t p1) {
  uint32_t n = 0;
  while (!__all_sync(0xffffffffu, mbar_try(b0, p0) & mbar_try(b1, p1))) {
    if (++n > (1u << 22)) __trap();
  }
}
__device__ __forceinline__ void mbar_wait3_w(uint32_t b0, uint32_t p0, uint32_t b1, uint32_t p1, uint32_t b2, uint32_t p2) {
  uint32_t n = 0;
  while (!__all_sync(0xffffffffu, mbar_try(b0, p0) & mbar_try(b1, p1) & mbar_try(b2, p2))) {
    if (++n > (1u << 22)) __trap();
  }
}
__device__ __forceinline__ void acquire2(const Ctx& c, Ring& r, uint32_t& s0, uint32_t& s1, bool have = false) {
  const uint32_t p0 = r.phase;
  s0 = r.slot; r.next(); s1 = r.slot;
  if (!have) mbar_wait2_w(c.sb + BAR_FULL + s0 * 8, p0, c.sb + BAR_FULL + s1 * 8, r.phase);
  r.next();
}
template <int N>
__device__ __forceinline__ bool peek(const Ctx& c, Ring r) {
  bool ok = true;
#pragma unroll
  for (int k = 0; k < N; k++) { ok &= mbar_test(c.sb + BAR_FULL + r.slot * 8, r.phase); r.next(); }
  return ok;
}
__device__ __forceinline__ void staged(const Ctx& c, int part) {
  fence_async_smem();
  __syncwarp();
  mbar_arrive_warp(c.sb + BAR_STG + c.wg * 16 + part * 8);
}

template <int WG, bool FIRST, int H>
__device__ __forceinline__ void proj_half(const Ctx& c, float (&acc)[64], uint32_t w, uint32_t x, uint32_t sw) {
  uint64_t dx = desc64((SB0 + x * SLOT + (WG ? 0 : H * 8192)) >> 4, dhi<0>(x) + sw);
  uint64_t dw = desc64(WG ? (SB0 + w * SLOT + H * 8192) >> 4 : sdesc(SB0 + w * SLOT, 8192), dhi<1>(x));
  wg_fence();
  if (WG) { if (FIRST) wgmma_proj96_init(acc, dw, dx, 0); else wgmma_proj96(acc, dw, dx, 1); }
  else { if (FIRST) wgmma_proj_init(acc, dx, dw, 0); else wgmma_proj(acc, dx, dw, 1); }
#pragma unroll
  for (int k = 1; k < 4; k++) {
    dadd(dx, k == 2 ? 2 + (sw >> 30) * 28 : 2); dadd(dw, 128);
    if (WG) wgmma_proj96(acc, dw, dx, 1); else wgmma_proj(acc, dx, dw, 1);
  }
  wg_commit();
}

__device__ __forceinline__ void proj_store16(uint32_t a, const float* f, float sc) {
  stsm4t(a, pack_bf16(f[0] * sc, f[1] * sc), pack_bf16(f[2] * sc, f[3] * sc), pack_bf16(f[4] * sc, f[5] * sc), pack_bf16(f[6] * sc, f[7] * sc));
}

__device__ __forceinline__ uint32_t stage_off(const Ctx& c) {
  const int lane = c.lane, mi = lane >> 3, r8 = lane & 7;
  return ((mi >> 1) * 8 + r8) * 128 + (((2 * c.warp + (mi & 1)) ^ r8) << 4);
}
__device__ __forceinline__ uint32_t q3_swz(uint32_t r8) { return ((r8 & 3) << 1) | (r8 >> 2); }
template <int H>
__device__ __forceinline__ void stage_t2(const Ctx& c, const float (&a)[64], float sc) {
  const uint32_t base = c.sb + QBUF_OFF + 2 * 16384 + H * 8192 + stage_off(c);
#pragma unroll
  for (int jj = 0; jj < 4; jj++) proj_store16(base + jj * 2048, &a[jj * 8], sc);
}
template <int H, bool IS_Q>
__device__ __forceinline__ void stage_t3(const Ctx& c, const float (&a)[64], float sc) {
  const uint32_t off = stage_off(c), r8 = (off >> 7) & 7;
  const uint32_t t3 = c.sb + QBUF_OFF + 3 * 16384 + H * 4096 + (IS_Q ? off ^ ((r8 ^ q3_swz(r8)) << 4) : off);
  proj_store16(t3, &a[32], sc);
  proj_store16(t3 + 2048, &a[40], sc);
}

template <int WG, int h>
__device__ __forceinline__ void load_part(const Ctx& c, Ring r, uint32_t (&q)[32]) {
  uint32_t n = 0;
  while (!h && !__all_sync(0xffffffffu, peek<4>(c, r))) {
    if (++n > (1u << 26)) __trap();
  }
  const int lane = c.lane, mi = lane >> 3, r8 = lane & 7;
  if (WG) { r.next(); r.next(); }
  const uint32_t off = c.sb + (WG ? stage_off(c) : (16 * c.warp + (mi & 1) * 8 + r8) * 128), t0 = off + r.slot * SLOT;
  r.next();
  const uint32_t t1 = off + r.slot * SLOT;
#pragma unroll
    for (int jj = 0; jj < (WG ? 6 : 8); jj++) {
      uint32_t* p = &q[4 * jj];
      if (WG) asm volatile("ldmatrix.sync.aligned.m8n8.x4.trans.shared.b16 {%0, %1, %2, %3}, [%4];" : "=r"(p[0]), "=r"(p[1]), "=r"(p[2]), "=r"(p[3])
                           : "r"((jj < 4 ? t0 + h * 8192 : t1 + h * 4096) + (jj & 3) * 2048) : "memory");
      else ldsm4((h ? t1 : t0) + (jj >> 2) * 8192 + (((((2 * jj) & 7) + (mi >> 1)) ^ r8) << 4), p[0], p[1], p[2], p[3]);
    }
}
template <int WG>
__device__ __forceinline__ void add_part(const Ctx& c, const uint32_t (&q)[32], float (&a)[64]) {
  const uint32_t one = (c.lane >> 3) == (c.lane & 3) ? 0x3f80u << (c.lane & 4) * 4 : 0;
#pragma unroll
  for (int i = 0; i < (WG ? 12 : 16); i++)
    asm("mma.sync.aligned.m16n8k8.row.col.f32.bf16.bf16.f32 {%0, %1, %2, %3}, {%4, %5}, {%6}, {%0, %1, %2, %3};"
        : "+f"(a[4 * i]), "+f"(a[4 * i + 1]), "+f"(a[4 * i + 2]), "+f"(a[4 * i + 3]) : "r"(q[2 * i]), "r"(q[2 * i + 1]), "r"(one));
}

__device__ __forceinline__ void trace_dump(const Ctx& c) {
}
struct RowSum { float l0, l1; };
__device__ __forceinline__ const char* o_addr(uint32_t item, int row, int lane) {
  return reinterpret_cast<const char*>(g_o) + (((item >> 10) * (2 * SQ) + row) * 128 + (lane ^ (lane >> 3)) * 16);
}
__device__ __forceinline__ void o_stg(const char* p, int i, const uint32_t* q) {
  asm volatile("st.global.v4.b32 [%0], {%1, %2, %3, %4};"
               ::"l"(p + (i >> 1) * (SQ * 128) + (i & 1) * 512), "r"(q[0]), "r"(q[1]), "r"(q[2]), "r"(q[3]) : "memory");
}
template <int MODE, int I0 = 0, int NI = 4>
__device__ __forceinline__ void o_emit(const char* p, const float (&o)[64], float inv) {
#pragma unroll
  for (int i = I0; i < I0 + NI; i++) {
    uint32_t q[4];
#pragma unroll
    for (int j = 0; j < 4; j++) q[j] = pack_bf16(o[16 * i + 4 * j + 2 * MODE] * inv, o[16 * i + 4 * j + 2 * MODE + 1] * inv);
    o_stg(p, i, q);
  }
}
__device__ __forceinline__ void o_done(const Ctx& c) {
  __syncwarp();
  mbar_arrive_warp(c.sb + BAR_OUT);
  __syncwarp();
}
template <int WG>
__device__ __forceinline__ void o_first(const Ctx& c, uint32_t item, float (&o)[64], const RowSum& inv, uint32_t (&q)[32]) {
  const char* p = o_addr(item, WG ? 192 + 8 * c.warp : 64 + 16 * c.warp, c.lane);
  reg_fence(o);
#pragma unroll
  for (int j = 0; j < 16; j++) {
    if (WG) q[j] = pack_bf16((o[4 * j] + o[4 * j + 2]) * inv.l0, (o[4 * j + 1] + o[4 * j + 3]) * inv.l0);
    else q[j] = pack_bf16(o[4 * j] * inv.l0, o[4 * j + 1] * inv.l0);
    if (!WG && (j & 3) == 3 && (j >> 2) < 8 - LATE0) o_stg(p, j >> 2, q + j - 3);
  }
#pragma unroll
  for (int j = 0; j < 16; j++) {
    if (!WG) q[16 + j] = pack_bf16(o[4 * j + 2] * inv.l1, o[4 * j + 3] * inv.l1);
    if ((j & 3) == 3 && (j >> 2) < 4 - (WG ? LATE1 : LATE0)) o_stg(WG ? p : p + 1024, j >> 2, q + (WG ? 0 : 16) + j - 3);
  }
}
template <int WG>
__device__ __forceinline__ void o_rest(const Ctx& c, uint32_t item, uint32_t (&q)[32]) {
  const char* p = o_addr(item, WG ? 192 + 8 * c.warp : 64 + 16 * c.warp, c.lane);
#pragma unroll
  for (int i = WG ? 4 - LATE1 : 8 - LATE0; i < (WG ? 4 : 8); i++) o_stg(p + (i >> 2) * 1024, i & 3, q + 4 * i);
}
template <int K0, int K1>
__device__ __forceinline__ void o_piece(const Ctx& c, const char* p, int k, const float (&o)[64], const RowSum& inv) {
  constexpr int NI = 8 / O_STEPS, M = K0 * NI / 4;
  if constexpr (K1 - K0 == 1) {
    o_emit<M, K0 * NI % 4, NI>(p + M * 1024, o, M ? inv.l1 : inv.l0);
    if (K1 == O_STEPS) o_done(c);
  } else {
    if (k <= (K0 + K1) / 2) o_piece<K0, (K0 + K1) / 2>(c, p, k, o, inv); else o_piece<(K0 + K1) / 2, K1>(c, p, k, o, inv);
  }
}
template <int WG>
__device__ __forceinline__ void o_second(const Ctx& c, uint32_t item, int k, float (&o)[64], const RowSum& inv) {
  reg_fence(o);
  o_piece<0, O_STEPS>(c, o_addr(item, 128 * WG + 16 * c.warp, c.lane0 + (k >> 8)), k, o, inv);
}
template <int WG>
__device__ __forceinline__ void release_q(const Ctx& c) {
#pragma unroll
  for (int t = 0; t < 2; t++)
    if (c.lead) asm volatile("mbarrier.arrive.shared::cta.b64 _, [%0], 2;" ::"r"(c.sb + BAR_EMPTY + (NS + 2 * WG + t) * 8) : "memory");
  __syncwarp();
}
struct Slots { uint32_t w, x, o, po; };
template <int WG>
__device__ __forceinline__ void acc_fence(float (&a)[64]) {
#pragma unroll
  for (int i = 0; i < (WG ? 48 : 64); i++) asm volatile("" : "+f"(a[i])::"memory");
}
template <int WG>
__device__ __forceinline__ void begin_acquire(const Ctx& c, Ring& r, Slots& h, bool wait) {
  const uint32_t s0 = r.slot, p0 = r.phase, f = c.sb + BAR_FULL;
  r.next();
  const uint32_t p1 = r.phase;
  h.w = r.slot; r.next();
  h.x = WG ? r.slot : s0; h.o = WG ? s0 : r.slot; h.po = r.phase;
  if (wait) { if (WG) mbar_wait3_w(f + s0 * 8, p0, f + h.w * 8, p1, f + h.x * 8, r.phase); else mbar_wait2_w(f + s0 * 8, p0, f + h.w * 8, p1); }
  r.next();
}
template <int WG>
__device__ __forceinline__ void proj_begin(const Ctx& c, Ring& r, float (&a0)[64], Slots& h, bool wait, uint32_t sw) {
  begin_acquire<WG>(c, r, h, wait);
  proj_half<WG, true, 0>(c, a0, h.w, h.x, sw);
  if (WG) release(c, h.o);
}
template <int WG>
__device__ __forceinline__ void proj_main(Ctx& c, Ring& r, float (&a0)[64], float (&a1)[64], Slots& h, int n, uint32_t sw, int unit,
                                          uint32_t item, int nq, float (&o1)[64], const RowSum& inv) {
  constexpr bool DEEP = (PDEPTH >> WG) & 1;
  T2C(unit, 3);
  int ks = 1;
#pragma unroll 1
  do {
    const Slots p = h;
    const uint32_t b = borrow(ks, n), tile = NS + (WG ? 3 - b : b), f = c.sb + BAR_FULL;
    const uint32_t s0 = b != 2 ? tile : r.slot, p0 = b != 2 ? (r.xp >> b) & 1 : r.phase;
    r.next_if(b == 2);
    const uint32_t p1 = r.phase;
    h.w = r.slot; r.next();
    const uint32_t s2 = b != 2 ? tile : r.slot;
    h.po = b != 2 ? p0 : r.phase;
    r.next_if(b == 2);
    r.xp ^= 1 << b;
    h.x = WG ? s2 : s0; h.o = WG ? s0 : s2;
    mbar_wait3_w(f + s0 * 8, p0, f + h.w * 8, p1, f + (WG ? s2 : p.o) * 8, WG ? h.po : p.po);
    if (ks < 10) T2C(unit, ks * 4);
    if (DEEP) {
      proj_half<WG, false, 0>(c, a0, h.w, h.x, sw);
      release(c, WG ? h.o : p.o);
      if (ks < 10) T2C(unit, ks * 4 + 1);
      wg_wait<1>();
      if (ks < 10) T2C(unit, ks * 4 + 2);
      release(c, p.x); release(c, p.w);
    } else {
      release(c, WG ? h.o : p.o);
      wg_wait<0>();
      release(c, p.x); release(c, p.w);
      if (ks < 10) T2C(unit, ks * 4 + 1);
      proj_half<WG, false, 0>(c, a0, h.w, h.x, sw);
      if (ks < 10) T2C(unit, ks * 4 + 2);
    }
    proj_half<WG, false, 1>(c, a1, h.w, h.x, sw);
    if (ks < 10) T2C(unit, ks * 4 + 3);
    if (ks <= nq) o_second<WG>(c, item, ks, o1, inv);
  } while (++ks != n);
  {
    const uint32_t e0 = c.sb + BAR_EMPTY + (NS + 3 * WG) * 8, e1 = c.sb + BAR_EMPTY + (NS + 1 + WG) * 8;
    const uint32_t p0 = (r.xp ^ unit ^ 1) & 1, p1 = ((r.xp >> 1) ^ unit ^ 1) & 1;
    const uint32_t k0 = sw ? e0 : c.sb + BAR_FULL + r.slot * 8, pk = sw ? p0 : r.phase;
    uint32_t cnt = 0;
    while (!__all_sync(0xffffffffu, mbar_try(e0, p0) & mbar_try(e1, p1) & mbar_try(k0, pk) & (WG || mbar_try(c.sb + BAR_FULL + h.o * 8, h.po)))) {
      if (++cnt > (1u << 22)) __trap();
    }
  }
  c.lane = c.lane0 + (h.w >> 5);
  if (!WG) release(c, h.o);
}
template <int WG>
__device__ __forceinline__ void proj_end(const Ctx& c, float (&a1)[64], const Slots& h) {
  wg_wait<0>();
  acc_fence<WG>(a1);
  release(c, h.x); release(c, h.w);
}
__device__ __forceinline__ uint32_t get_desc(const Ctx& c, int i) {
  uint32_t d;
  mbar_wait_w(c.sb + BAR_DESC, (i - 1) & 1);
  asm volatile("ld.volatile.shared.u32 %0, [%1];" : "=r"(d) : "r"(c.sb + DESC_OFF + (i & 3) * 4) : "memory");
  return __shfl_sync(0xffffffffu, d, 0);
}

__device__ __forceinline__ float quad_max(float x) {
  x = fmaxf(x, __shfl_xor_sync(0xffffffffu, x, 1));
  return fmaxf(x, __shfl_xor_sync(0xffffffffu, x, 2));
}
__device__ __forceinline__ float quad_sum(float x) {
  x += __shfl_xor_sync(0xffffffffu, x, 1);
  return x + __shfl_xor_sync(0xffffffffu, x, 2);
}
template <bool SP, bool FIRST>
__device__ __forceinline__ void exps(const Ctx& c, const float (&s)[32], uint32_t (&p)[SP ? 8 : 16], RowSum& st) {
  if constexpr (SP) {
    uint32_t q[8];
    float t;
#pragma unroll
    for (int j = 0; j < 8; j++) {
      const float e0 = ex2(s[4 * j] + s[4 * j + 2]), e1 = ex2(s[4 * j + 1] + s[4 * j + 3]);
      if (j == 0) t = e0 + e1; else t += e0 + e1;
      q[j] = pack_bf16(e0, e1);
    }
    const bool odd = c.src & 2;
#pragma unroll
    for (int g = 0; g < 4; g++) {
      p[2 * g] = __shfl_sync(0xffffffffu, odd ? q[2 * g + 1] : q[2 * g], c.src);
      p[2 * g + 1] = __shfl_sync(0xffffffffu, odd ? q[2 * g] : q[2 * g + 1], c.src ^ 1);
    }
    st.l0 = FIRST ? t : st.l0 + t;
  } else {
    float t0, t1;
#pragma unroll
    for (int j = 0; j < 8; j++) {
      const float e0 = ex2(s[4 * j]), e1 = ex2(s[4 * j + 1]), e2 = ex2(s[4 * j + 2]), e3 = ex2(s[4 * j + 3]);
      if (j == 0) { t0 = e0 + e1; t1 = e2 + e3; } else { t0 += e0 + e1; t1 += e2 + e3; }
      p[2 * j] = pack_bf16(e0, e1);
      p[2 * j + 1] = pack_bf16(e2, e3);
    }
    st.l0 = FIRST ? t0 : st.l0 + t0;
    st.l1 = FIRST ? t1 : st.l1 + t1;
  }
}
template <bool SP>
__device__ __forceinline__ bool finish_sums(RowSum& st) {
  const float a = quad_sum(st.l0), b = SP ? a : quad_sum(st.l1);
  st.l0 = __fdividef(1.f, a); st.l1 = __fdividef(1.f, b);
  return !(a >= SUM_LO && a <= SUM_HI && b >= SUM_LO && b <= SUM_HI);
}
template <bool SP, bool INIT, int SITE, bool COMMIT = true, int RM = 0>
__device__ __forceinline__ void issue_qk(const Ctx& c, float (&s)[32], const uint32_t (&qs)[32], uint32_t dq, uint32_t dk) {
  uint64_t a = desc64(dq, dhi<SITE & 1>(dk)), b = desc64(dk, dhi<1 - (SITE & 1)>(dk));
  if (SP) {
    if (INIT) wgmma_qk_sp_init(s, qs[0], qs[1], qs[2], qs[3], b, 0, c.mqk); else wgmma_qk_sp(s, qs[0], qs[1], qs[2], qs[3], b, 0, c.mqk);
#pragma unroll
    for (int k = 1; k < 4; k++) { dadd(b, k == 2 ? 508 : 4); wgmma_qk_sp(s, qs[4 * k], qs[4 * k + 1], qs[4 * k + 2], qs[4 * k + 3], b, 1, c.mqk); }
  } else {
    if (RM & 1) wgmma_qk_rs(s, qs[0], qs[1], qs[2], qs[3], b, 0); else if (INIT) wgmma_qk_init(s, a, b, 0); else wgmma_qk(s, a, b, 0);
#pragma unroll
    for (int k = 1; k < 8; k++) {
      dadd(a, k == 4 ? 506 : 2); dadd(b, k == 4 ? 506 : 2);
      if (RM >> k & 1) wgmma_qk_rs(s, qs[4 * k], qs[4 * k + 1], qs[4 * k + 2], qs[4 * k + 3], b, 1); else wgmma_qk(s, a, b, 1);
    }
  }
  if (COMMIT) wg_commit();
}
template <bool SP, bool ACC, int SITE, bool SPLIT = false>
__device__ __forceinline__ void issue_pv(const Ctx& c, float (&o)[64], const uint32_t (&p)[SP ? 8 : 16], uint32_t dv) {
  uint64_t b = desc64(dv, dhi<SITE & 1>(dv));
  if constexpr (SP) {
    if (ACC) wgmma_pv_sp(o, p[0], p[1], p[2], p[3], b, 1, c.mpv); else wgmma_pv_sp_init(o, p[0], p[1], p[2], p[3], b, 0, c.mpv);
    if (SPLIT) wg_commit();
    dadd(b, 256);
    wgmma_pv_sp(o, p[4], p[5], p[6], p[7], b, 1, c.mpv);
  } else {
    if (ACC) wgmma_pv(o, p[0], p[1], p[2], p[3], b, 1); else wgmma_pv_init(o, p[0], p[1], p[2], p[3], b, 0);
#pragma unroll
    for (int k = 1; k < 4; k++) { dadd(b, 128); wgmma_pv(o, p[4 * k], p[4 * k + 1], p[4 * k + 2], p[4 * k + 3], b, 1); }
  }
  wg_commit();
}
__device__ __forceinline__ void pack_rows(const float (&o)[64], float sc, uint32_t (&q)[32]) {
#pragma unroll
  for (int j = 0; j < 32; j++) q[j] = pack_bf16(o[2 * j] * sc, o[2 * j + 1] * sc);
}
template <int MASK = 255>
__device__ __forceinline__ void stage_rows(const Ctx& c, uint32_t tile_addr, const uint32_t (&q)[32]) {
  const int lane = c.lane, mi = lane >> 3, r8 = lane & 7;
  const uint32_t row_addr = tile_addr + (16 * c.warp + (mi & 1) * 8 + r8) * 128;
#pragma unroll
  for (int jj = 0; jj < 8; jj++)
    if (MASK >> jj & 1) stsm4(row_addr + (jj >> 2) * 8192 + (((((2 * jj) & 7) + (mi >> 1)) ^ r8) << 4), q[4 * jj], q[4 * jj + 1], q[4 * jj + 2], q[4 * jj + 3]);
}
__device__ __forceinline__ void stage_rows(const Ctx& c, uint32_t tile_addr, const float (&o)[64], float sc) {
  uint32_t q[32];
  pack_rows(o, sc, q);
  stage_rows(c, tile_addr, q);
}
template <int WG, int H>
__device__ __forceinline__ void stage_out(const Ctx& c, const float (&a)[64]) {
  if (WG) { stage_t3<H, false>(c, a, 1.f); if (H) staged(c, 0); stage_t2<H>(c, a, 1.f); }
  else stage_rows(c, c.sb + QBUF_OFF + H * 16384, a, 1.f);
  if (H || !WG) staged(c, H);
}
template <int SITE>
__device__ __forceinline__ void issue_qk_rs(float (&s)[32], uint32_t (&q)[32], uint32_t dk) {
  uint64_t b = desc64(dk, dhi<SITE>(dk));
  reg_fence(q);
  wg_fence();
  wgmma_qk_rs_init(s, q[0], q[1], q[2], q[3], b, 0);
#pragma unroll
  for (int k = 1; k < 8; k++) { dadd(b, k == 4 ? 506 : 2); wgmma_qk_rs(s, q[4 * k], q[4 * k + 1], q[4 * k + 2], q[4 * k + 3], b, 1); }
  wg_commit();
}

__device__ __forceinline__ void redo_tile(const Ctx& c, uint32_t q_addr, uint32_t half, const __nv_bfloat16* kp, const __nv_bfloat16* vp,
                                          uint32_t item, int row) {
  float o[64];
  const int lane = lane_now(), g = lane >> 2, cc = lane & 3, mi = lane >> 3, r8 = lane & 7;
  const uint32_t qa = q_addr + (half == 4096 ? 8 * c.warp + r8 : 16 * c.warp + (mi & 1) * 8 + r8) * 128, swz = half == 4096 ? q3_swz(r8) : r8;
  const uint32_t* kq = reinterpret_cast<const uint32_t*>(kp + g * DH) + cc;
  const unsigned short* vq = reinterpret_cast<const unsigned short*>(vp + 2 * cc * DH) + g;
  float m0 = -INFINITY, m1 = -INFINITY, l0 = 0.f, l1 = 0.f;
#pragma unroll
  for (int i = 0; i < 64; i++) o[i] = 0.f;
#pragma unroll 1
  for (int kb = 0; kb < SK / 16; kb++) {
    float z[8] = {0.f, 0.f, 0.f, 0.f, 0.f, 0.f, 0.f, 0.f};
#pragma unroll 2
    for (int kk = 0; kk < 8; kk++) {
      uint32_t a0, a1, a2, a3;
      ldsm4(qa + (kk >> 2) * half + ((((kk & 3) * 2 + (mi >> 1)) ^ swz) << 4), a0, a1, a2, a3);
      const uint32_t* kr = kq + kb * (16 * DH / 2) + kk * 8;
      mma16816(z[0], z[1], z[2], z[3], a0, a1, a2, a3, __ldg(kr), __ldg(kr + 4));
      mma16816(z[4], z[5], z[6], z[7], a0, a1, a2, a3, __ldg(kr + 8 * DH / 2), __ldg(kr + 8 * DH / 2 + 4));
    }
    const float n0 = fmaxf(m0, quad_max(fmaxf(fmaxf(z[0], z[1]), fmaxf(z[4], z[5]))));
    const float n1 = fmaxf(m1, quad_max(fmaxf(fmaxf(z[2], z[3]), fmaxf(z[6], z[7]))));
    const float al0 = ex2(m0 - n0), al1 = ex2(m1 - n1);
    m0 = n0; m1 = n1;
#pragma unroll
    for (int i = 0; i < 8; i++) z[i] = ex2(z[i] - ((i & 2) ? n1 : n0));
    l0 = l0 * al0 + (z[0] + z[1]) + (z[4] + z[5]);
    l1 = l1 * al1 + (z[2] + z[3]) + (z[6] + z[7]);
    const uint32_t a0 = pack_bf16(z[0], z[1]), a1 = pack_bf16(z[2], z[3]), a2 = pack_bf16(z[4], z[5]), a3 = pack_bf16(z[6], z[7]);
    const unsigned short* vr = vq + kb * (16 * DH);
#pragma unroll
    for (int nb = 0; nb < 16; nb++) {
      o[4 * nb] *= al0; o[4 * nb + 1] *= al0; o[4 * nb + 2] *= al1; o[4 * nb + 3] *= al1;
      const uint32_t b0 = __ldg(vr + nb * 8) | ((uint32_t)__ldg(vr + nb * 8 + DH) << 16);
      const uint32_t b1 = __ldg(vr + nb * 8 + 8 * DH) | ((uint32_t)__ldg(vr + nb * 8 + 9 * DH) << 16);
      mma16816(o[4 * nb], o[4 * nb + 1], o[4 * nb + 2], o[4 * nb + 3], a0, a1, a2, a3, b0, b1);
    }
  }
  const char* p = o_addr(item, row, lane);
  o_emit<0>(p, o, __fdividef(1.f, quad_sum(l0)));
  o_emit<1>(half == 4096 ? p : p + 1024, o, __fdividef(1.f, quad_sum(l1)));
}

template <bool SPA, bool SPB, int SITE, int ID>
__device__ __forceinline__ void batch(const Ctx& c, float (&s)[32], const uint32_t (&qs)[32], uint32_t dq, uint32_t dk, float (&ob)[64],
                                      uint32_t (&pb)[SPB ? 8 : 16], uint32_t dv) {
  if constexpr (SPA) {
    reg_fence(pb);
    wg_fence();
    issue_pv<SPB, true, ID>(c, ob, pb, dv);
    issue_qk<SPA, false, ID>(c, s, qs, dq, dk);
  } else {
    constexpr bool EARLY = ((QK_EARLY_MASK >> (SITE + (SPB ? 2 : 0))) & 1) != 0;
    if (!EARLY) reg_fence(pb);
    wg_fence();
    issue_qk<SPA, false, ID, !SPB, SITE ? RM0 : SPB ? RM2 : RM1>(c, s, qs, dq, dk);
    if (EARLY) { reg_fence(pb); wg_fence(); }
    issue_pv<SPB, true, ID, SPB>(c, ob, pb, dv);
  }
}

template <bool SP0>
__device__ __forceinline__ bool attention(Ctx& c, Ring& r, int unit, uint32_t& d, const float (&a0)[64], float (&o0)[64], float (&o1)[64],
                                          RowSum& st0, RowSum& st1, const Slots& h, uint32_t (&q1)[32]) {
  constexpr bool SP1 = false;
  if (SP0) { c.mqk = META_QK + (d >> 28); c.mpv = META_PV + (d >> 28); asm volatile("" : "+r"(c.mqk), "+r"(c.mpv)); }
  if (SP0) c.src = (c.lane & 28) | ((c.lane & 1) << 1) | ((c.lane >> 1) & 1);
  float s[32];
  uint32_t p0[SP0 ? 8 : 16], p1[16];
  const uint32_t q0a = c.sb + QBUF_OFF + (SP0 ? 3 : 0) * 16384, q1a = c.sb + QBUF_OFF + (SP0 ? 2 : 1) * 16384;
  const uint32_t dq0 = sdesc(SB0 + QBUF_OFF, 0), dq1 = sdesc(SB0 + QBUF_OFF + (SP0 ? 2 : 1) * 16384, 0);
  uint32_t sk = acquire(c, r, true), sv, sn;
  uint32_t qs[32];
  float s1[32];
  if (SP0) {
    stage_t3<0, true>(c, a0, SM_C);
    stage_t2<0>(c, a0, SM_C);
    proj_end<1>(c, o0, h);
    stage_t3<1, true>(c, o0, SM_C);
    stage_t2<1>(c, o0, SM_C);
    fence_async_smem();
    bar_sync(1, LAG_BAR & 30 ? 256 : 128);
    const int g = c.lane >> 2, cc = c.lane & 3;
    const uint32_t qa = q0a + (8 * c.warp + g) * 128 + (cc & 1) * 8;
#pragma unroll
    for (int k = 0; k < 8; k++)
      asm volatile("ld.shared.v2.u32 {%0, %1}, [%2];" : "=r"(qs[2 * k]), "=r"(qs[2 * k + 1])
                   : "r"(qa + (k >> 2) * 4096 + ((((k & 3) * 2 + (cc >> 1)) ^ q3_swz(g)) << 4)) : "memory");
    TRACE(unit, 2);
    wg_fence();
    issue_qk<SP1, true, 1>(c, s1, qs, dq1, sdesc(SB0 + sk * SLOT, 0));
#pragma unroll
    for (int k = 0; k < 8; k++)
      if (RM2 >> k & 1) ldsm4(q1a + (k >> 2) * 8192 + (16 * c.warp + (c.lane & 15)) * 128 + (((2 * (k & 3) + (c.lane >> 4)) ^ (c.lane & 7)) << 4),
                              q1[4 * k], q1[4 * k + 1], q1[4 * k + 2], q1[4 * k + 3]);
#pragma unroll
    for (int k = 0; k < 16; k++) asm volatile("" : "+r"(qs[k])::"memory");
    wg_fence();
    issue_qk<SP0, true, 0>(c, s, qs, dq0, sdesc(SB0 + sk * SLOT, 0));
    const bool have = peek<2>(c, r);
    wg_wait<1>();
    reg_fence(s1);
    exps<SP1, true>(c, s1, p1, st1);
    sched_fence<11>(sk, p1);
    acquire2(c, r, sv, sn, __all_sync(0xffffffffu, have));
    wg_wait<0>();
    wg_fence();
    issue_pv<SP1, false, 1>(c, o1, p1, sdesc(SB0 + sv * SLOT, 8192));
    if (LAG_BAR & 1) asm volatile("bar.arrive 4, 256;" ::: "memory");
    sched_fence<12>(sk, s);
    release(c, sk);
    sk = sn;
    exps<SP0, true>(c, s, p0, st0);
    reg_fence(p0);
    wg_fence();
    issue_pv<SP0, false, 0>(c, o0, p0, sdesc(SB0 + sv * SLOT, 8192));
    issue_qk<SP0, true, 2>(c, s, qs, dq0, sdesc(SB0 + sk * SLOT, 0));
    sn = acquire(c, r);
    wg_wait<0>();
    reg_fence(s);
  } else {
    pack_rows(a0, SM_C, qs);
    stage_rows(c, q0a, qs);
    proj_end<0>(c, o1, h);
    TRACE(unit, 2);
    float sc = SM_C;
    issue_qk_rs<0>(s, qs, sdesc(SB0 + sk * SLOT, 0));
    sched_fence<0>(sk, sc);
    if (LAG_BAR & 8) asm volatile("bar.arrive 1, 256;" ::: "memory");
    pack_rows(o1, sc, q1);
    stage_rows<~RM1>(c, q1a, q1);
    if (LAG_BAR & 4) asm volatile("bar.arrive 1, 256;" ::: "memory");
    issue_qk_rs<1>(s1, q1, sdesc(SB0 + sk * SLOT, 0));
    if (LAG_BAR & 2) asm volatile("bar.arrive 1, 256;" ::: "memory");
    bool have = peek<2>(c, r);
    wg_wait<1>();
    reg_fence(s);
    exps<SP0, true>(c, s, p0, st0);
    sched_fence<1>(sk, p0);
    if (LAG_BAR & 16) asm volatile("bar.arrive 1, 256;" ::: "memory");
    acquire2(c, r, sv, sn, __all_sync(0xffffffffu, have));
    wg_wait<0>();
    reg_fence(s1);
    fence_async_smem();
    __syncwarp();
    wg_fence();
    issue_qk<SP0, false, 2, true, RM0>(c, s, qs, dq0, sdesc(SB0 + sn * SLOT, 0));
    issue_pv<SP0, false, 0>(c, o0, p0, sdesc(SB0 + sv * SLOT, 8192));
    sched_fence<2>(sk, s1);
    release(c, sk);
    have = peek<1>(c, r);
    sk = sn;
    exps<SP1, true>(c, s1, p1, st1);
    reg_fence(p1);
    wg_fence();
    issue_pv<SP1, false, 1>(c, o1, p1, sdesc(SB0 + sv * SLOT, 8192));
    sn = acquire(c, r, __all_sync(0xffffffffu, have));
    if (LAG_BAR & 1) bar_sync(4, 256);
    wg_wait<1>();
    reg_fence(s);
  }
  TRACE_IN(unit, 4);
  T2C(unit, 51);
#pragma unroll 1
  for (int j = 1; j < 15; j++) {
    const uint32_t sv_prev = sv, sk_prev = sk;
    sv = sn;
    const uint32_t dv = sdesc(SB0 + sv * SLOT, 8192);
    reg_fence(p0);
    exps<SP0, false>(c, s, p0, st0);
    batch<SP1, SP0, 0, 3>(c, s, q1, dq1, sdesc(SB0 + sk * SLOT, 0), o0, p0, dv);
    sk = acquire(c, r);
    wg_wait<1>();
    reg_fence(s); reg_fence(p1);
    release(c, sv_prev); release(c, sk_prev);
    exps<SP1, false>(c, s, p1, st1);
    batch<SP0, SP1, 1, 4>(c, s, qs, dq0, sdesc(SB0 + sk * SLOT, 0), o1, p1, dv);
    sn = acquire(c, r);
    if (SP0) wg_wait<0>(); else wg_wait<1>();
    reg_fence(s);
  }
  TRACE_IN(unit, 5);
  T2C(unit + 1, 52);
  const uint32_t sv_prev = sv;
  sv = sn;
  const uint32_t dv = sdesc(SB0 + sv * SLOT, 8192);
  reg_fence(p0);
  exps<SP0, false>(c, s, p0, st0);
  batch<SP1, SP0, 0, 5>(c, s, q1, dq1, sdesc(SB0 + sk * SLOT, 0), o0, p0, dv);
  asm volatile("ld.volatile.shared.u32 %0, [%1];" : "=r"(d) : "r"(c.sb + DESC_OFF + ((unit + 1) & 3) * 4) : "memory");
  const bool have = peek<2 + SP0>(c, r);
  wg_wait<1>();
  reg_fence(s); reg_fence(p1);
  release(c, sv_prev); release(c, sk);
  exps<SP1, false>(c, s, p1, st1);
  reg_fence(p1);
  wg_fence();
  issue_pv<SP1, true, 2>(c, o1, p1, dv);
  if (SP0) sched_fence<6>(sk, st0.l0, st1.l0, st1.l1); else sched_fence<5>(sk, st0.l0, st0.l1, st1.l0, st1.l1);
  c.lane = c.lane0 + (sk >> 5);
  const bool bad = finish_sums<SP0>(st0) | finish_sums<SP1>(st1);
  uint32_t any;
  asm volatile("{\n.reg .pred p, q;\nsetp.ne.u32 p, %1, 0;\nbar.red.or.pred q, %2, 128, p;\nselp.u32 %0, 1, 0, q;\n}"
               : "=r"(any) : "r"((uint32_t)bad), "n"(2 + SP0) : "memory");
  any = __any_sync(0xffffffffu, any);
  d = __shfl_sync(0xffffffffu, d, 0);
  if (d < (2u << 30) && !__all_sync(0xffffffffu, have)) { Ring t = r; Slots u; begin_acquire<SP0>(c, t, u, true); }
  wg_wait<0>();
  reg_fence(o0); reg_fence(o1);
  release(c, sv);
  return any;
}

template <int WG>
__device__ __forceinline__ void consumer(Ctx c, const __nv_bfloat16* const* kv) {
  asm volatile("setmaxnreg.inc.sync.aligned.u32 %0;" ::"n"(WG ? REG_C : 504 - REG_C - REG_P));
  c.wg = WG;
#pragma unroll
  for (int k = 0; k < (WG ? PAD1 : PAD0); k++) asm volatile("pmevent 0;");
  Ring r{0, 0, 0};
  float a0[64], a1[64], o1[64];
  Slots h;
  RowSum inv0, inv1;
  uint32_t oq[32];
  uint32_t d = c_sched.queue[blockIdx.x] * 1025, dc = 0, sw;
  int i = 0, nq;
begin:
  sw = d & (1u << 30);
  proj_begin<WG>(c, r, a0, h, true, sw);
  proj_half<WG, true, 1>(c, a1, h.w, h.x, sw);
  nq = 0;
#pragma unroll
  for (int k = 0; k < 64; k++) asm volatile("" : "=f"(o1[k]));
  asm volatile("" : "=f"(inv1.l0), "=f"(inv1.l1));
  while (true) {
    TRACE(i, 0); TRACE(i, 6);
    proj_main<WG>(c, r, a0, a1, h, d >> 30 ? ((d >> 16) & 63) + 1 : DM / 64, sw, i, dc, nq, o1, inv1);
    dc = d;
    TRACE(i, 1);
    if (d >> 30) goto out_tile;
    wg_wait<1>();
    acc_fence<WG>(a0);
    if (WG ? attention<WG>(c, r, i, d, a0, a1, o1, inv0, inv1, h, oq) : attention<WG>(c, r, i, d, a0, o1, a1, inv1, inv0, h, oq)) goto redo;
    if (d >= (2u << 30)) break;
    sw = d & (1u << 30);
    proj_begin<WG>(c, r, a0, h, false, sw);
    release_q<WG>(c);
    if (WG) sched_fence<8>(h.w, inv0.l0); else sched_fence<7>(h.w, inv0.l0, inv0.l1);
    o_first<WG>(c, dc, a1, inv0, oq);
    sched_fence<9>(h.w, inv1.l0);
    proj_half<WG, true, 1>(c, a1, h.w, h.x, sw);
    o_rest<WG>(c, dc, oq);
    nq = O_STEPS;
    TRACE(i, 3); TRACE(i, 7);
    i++;
  }
  release_q<WG>(c);
  o_first<WG>(c, dc, a1, inv0, oq);
  o_rest<WG>(c, dc, oq);
#pragma unroll
  for (int k = 1; k <= O_STEPS; k++) o_second<WG>(c, dc, k, o1, inv1);
next:
  TRACE(i, 3); TRACE(i, 7);
  if ((d >> 30) != 2) {
    i++;
    r.uniform();
    goto begin;
  }
  trace_dump(c);
  return;
out_tile:
  if (d & 96) goto finish;
  d = get_desc(c, i + 1);
  wg_wait<1>();
  acc_fence<WG>(a0);
  TRACE_O(0);
  stage_out<WG, 0>(c, a0);
  TRACE_O(1);
  proj_end<WG>(c, a1, h);
  TRACE_O(2);
  stage_out<WG, 1>(c, a1);
  TRACE(i, 2);
  goto next;
finish:
  {
    uint32_t q[32];
#pragma unroll 1
    for (int k = (d >> 5) & 3; k > 1; k--) {
      wg_wait<0>();
      acc_fence<WG>(a0); acc_fence<WG>(a1);
      if (k == ((d >> 5) & 3)) { release(c, h.x); release(c, h.w); }
      load_part<WG, 0>(c, r, q); add_part<WG>(c, q, a0);
      load_part<WG, 1>(c, r, q); add_part<WG>(c, q, a1);
#pragma unroll
      for (int t = 0; t < 4; t++) { release(c, r.slot); r.next(); }
    }
    load_part<WG, 0>(c, r, q);
    wg_wait<1>();
    acc_fence<WG>(a0);
    TRACE_O(0);
    add_part<WG>(c, q, a0);
    stage_out<WG, 0>(c, a0);
    TRACE_O(1);
    load_part<WG, 1>(c, r, q);
    wg_wait<0>();
    acc_fence<WG>(a1);
    TRACE_O(2);
    add_part<WG>(c, q, a1);
    stage_out<WG, 1>(c, a1);
    TRACE(i, 2); TRACE(i, 3); TRACE(i, 7);
    trace_dump(c);
    return;
  }
redo:
  {
    if (!WG) { stage_rows<RM1>(c, c.sb + QBUF_OFF + 16384, oq); __syncwarp(); }
    const size_t hoff = (size_t)(dc & 511) * (SK * DH);
    const int br = (dc >> 9) & 1;
#pragma unroll 1
    for (int part = 0; part < 2; part++) {
      const int t = WG ? 3 - part : part;
      redo_tile(c, c.sb + QBUF_OFF + t * 16384, t == 3 ? 4096 : 8192, kv[br] + hoff, kv[2 + br] + hoff, dc,
                t * 64 + (t == 3 ? 8 : 16) * c.warp);
    }
    o_done(c);
    release_q<WG>(c);
  }
  goto next;
}

template <bool SIMPLE>
__global__ void __launch_bounds__(384, 1) mha_fused_kernel(const __grid_constant__ Params P) {
  extern __shared__ __align__(1024) uint8_t smem_raw[];
  const uint32_t sbase = smem_u32(smem_raw);
  const int tid = threadIdx.x;
  const int wg = __shfl_sync(0xffffffffu, tid >> 7, 0);
  const int warp = __shfl_sync(0xffffffffu, (tid >> 5) & 3, 0);
  const int lane = tid & 31;
  const int cta = blockIdx.x;
  constexpr bool PAIR = !SIMPLE && CLUSTER;

  if (tid == 0) T3(15, 0);
  if ((sbase & 0xffffff) != SB0) __trap();
  {
    const int wi = wg * 4 + warp;
    asm volatile(ELECT "prefetch.tensormap [%0];\n}" ::"l"(&P.x[0][0] + wi) : "memory");
#pragma unroll
    for (int k = 0; k < 5; k++) {
      const int b = min(BAR_OFF + (wi * 5 + k) * 8, DESC_OFF - 8);
      asm volatile(ELECT "mbarrier.init.shared::cta.b64 [%0], %1;\n}"
                   ::"r"(sbase + b), "r"(b < BAR_EMPTY || b >= BAR_DESC ? 1 : b >= BAR_STG && b < BAR_OUT ? 4 : 8) : "memory");
    }
    asm volatile("fence.mbarrier_init.release.cluster;" ::: "memory");
    if (wi < 6) asm volatile(ELECT "prefetch.tensormap [%0];\n}" ::"l"(&P.x[0][0] + 12 + wi) : "memory");
  }
  if (PAIR) asm volatile("barrier.cluster.arrive.aligned;\nbarrier.cluster.wait.aligned;" ::: "memory"); else __syncthreads();

  if (wg == 2) {
    asm volatile("setmaxnreg.dec.sync.aligned.u32 %0;" ::"n"(REG_P));
    if (warp == 1) {
      const uint32_t qb = sbase + QBUF_OFF;
      const uint32_t ep = __shfl_sync(0xffffffffu, *(volatile unsigned*)&g_epoch + 1, 0);
      asm volatile("st.volatile.shared.u32 [%0], %1;" ::"r"(sbase + EPOCH_OFF), "r"(ep) : "memory");
      uint32_t dc = c_sched.queue[cta], qi = 0, piece = 0, na = 0;
      TTAIL(0);
      for (int i = 0; (dc >> 30) != 2; i++) {
        if (!(dc >> 30) && o_reuse<SIMPLE>((dc >> 5) & 31)) {
          const unsigned* rd = &g_rd[0][0] + ((dc & 1023) >> 2) - OR * 8;
          for (uint32_t n = 0; !__all_sync(0xffffffffu, reached(rd, ep * 5)); __nanosleep(300)) if (++n > (1u << 22)) __trap();
        }
        mbar_wait_w(sbase + BAR_GO, i & 1);
        if (piece == 0) {
          if (PAIR && (cta & 1)) {
            asm volatile(ELECT EXPECT("%0", "4") "mbarrier.arrive.shared::cluster.b64 _, [%1];\n}" ::"r"(sbase + BAR_MAIL), "r"(peer(sbase + BAR_MAIL)) : "memory");
            mbar_wait_w(sbase + BAR_MAIL, i & 1);
            qi = lds(sbase + EPOCH_OFF + 8);
          } else if (lane == 0) {
            qi = atomicAdd(&g_next, PAIR ? 2 : 1);
            if (qi == (SIMPLE ? Q_ALL : Q_RANGES) - (PAIR ? 2 : 1)) { g_next = 0; g_epoch = ep; }
          }
          qi = __shfl_sync(0xffffffffu, qi, 0);
          if (PAIR && !(cta & 1)) {
            mbar_wait_w(sbase + BAR_MAIL, i & 1);
            asm volatile(ELECT "st.async.shared::cluster.mbarrier::complete_tx::bytes.u32 [%0], %1, [%2];\n}"
                         ::"r"(peer(sbase + EPOCH_OFF + 8)), "r"(qi + 1), "r"(peer(sbase + BAR_MAIL)) : "memory");
          }
          qi += SIMPLE ? gridDim.x : NCTA;
        }
        uint32_t d;
        if (qi < (SIMPLE ? Q_ALL : Q_RANGES)) { d = c_sched.queue[qi]; if (d & 0x8000) d ^= (1u << 30) | (63u << 16) | 0x8000; else d |= o_slot<SIMPLE>(d >> 5) << 15 | (d & 31) << 10; }
        else if (SIMPLE) d = 2u << 30;
        else { const uint32_t e = qi - Q_RANGES, g = e / 5; d = c_sched.piece[g][piece++] | (g & 1 ? g * 5 + 4 - e : e - g * 5) << 8; }
        if ((d >> 30) == 1) {
          const uint32_t k0 = (d >> 22) & 63;
          const uint32_t run = __ffs(__ballot_sync(0xffffffffu, !reached(&g_cnt[d & 31][lane & 7], ep * 4)) & (0xffu << (k0 >> 3))) - 1;
          if (run <= (k0 + ((d >> 16) & 63)) >> 3) d |= run <= (k0 + O_STEPS) >> 3 ? (2u << 30) | 128 : 128;
        }
        asm volatile("st.volatile.shared.u32 [%0], %1;" ::"r"(sbase + EPOCH_OFF + 4), "r"(qi) : "memory");
        asm volatile("st.volatile.shared.u32 [%0], %1;" ::"r"(sbase + DESC_OFF + ((i + 1) & 3) * 4), "r"(d) : "memory");
        __syncwarp();
        mbar_arrive_warp(sbase + BAR_DESC);
        const Work w = decode(dc);
        dc = d;
        if (w.kind == 0) {
          mbar_wait_w(sbase + BAR_OUT, na++ & 1);
          TTAIL(1);
          T3(i, 0); T3(i, 1);
          asm volatile(ELECT "red.release.gpu.global.add.u32 [%0], 1;\n}" ::"l"(&g_cnt[w.beta][w.sub >> 2]) : "memory");
          T3(i, 2);
          TTAIL(2);
          continue;
        }
        const bool fin = w.mode != 1;
        uint64_t pol, pol2;
        asm volatile("createpolicy.fractional.L2::evict_first.b64 %0, 1.0;" : "=l"(pol));
        asm volatile("createpolicy.fractional.L2::evict_normal.b64 %0, 1.0;" : "=l"(pol2));
        if (!fin) pol = pol2;
        const CUtensorMap* m = fin ? P.out_st : P.o_st;
        const int c1 = fin ? (w.beta & 15) * SQ : 0;
        const int c2 = fin ? (w.beta >> 4) * (DM / 64) + w.sub * 2 : NBETA * 64 + w.range * 2;
        uint32_t pend = 0;
#pragma unroll 1
        for (int e = 0; e < 4; e++) {
          const int t = (ST_ORDER >> (4 * e)) & 3;
          mbar_wait_w(sbase + BAR_STG + (t ^ (t >> 1)) * 8, (i - na) & 1);
          tma_st3_hint_w(m + (t == 3), qb + t * 16384, 0, c1 + t * 64, c2, pol);
          bulk_commit();
          T2P(i + 1, 5, 2 * e);
          if (pend) {
            bulk_wait_read<1>();
            mbar_arrive8_w(pend);
            T2P(i + 1, 5, 2 * e - 1);
          }
          pend = sbase + BAR_EMPTY + (NS + t) * 8;
          if ((ST_NOW >> e) & 1) {
            bulk_wait_read<0>();
            mbar_arrive8_w(pend);
            pend = 0;
            T2P(i + 1, 5, 2 * e + 1);
          }
        }
        if (w.beta < N_EARLY) asm volatile(ELECT "red.relaxed.gpu.global.add.u32 [%0], 1;\n}" ::"l"(&g_rd[w.beta][7]) : "memory");
        T3(i, 0);
        if (piece >= 2) TTAIL(piece * 2 - 1);
        asm volatile("cp.async.bulk.wait_group 0;" ::: "memory");
        T3(i, 1);
        if (w.mode == 1) asm volatile(ELECT "st.release.gpu.global.u32 [%0], %1;\n}" ::"l"(&g_flag[w.range]), "r"(ep) : "memory");
        T3(i, 2);
        if (piece >= 2) TTAIL(piece * 2);
      }
      T3(15, 1);
    } else
    if (warp == 0) {
      Ring r{0, 1, 3};
      uint32_t d = c_sched.queue[cta];
      for (int i = 0;; i++) {
        const Work w = decode(d);
        if (w.kind == 2) break;
        const CUtensorMap* m = w.kind == 0 ? &P.wq[w.beta >> 4] : &P.wo[w.beta >> 4];
        for (int ks = 0; ks < w.nsteps; ks++) {
          const uint32_t b = borrow(ks, w.nsteps);
          r.next_if(b == 2);
          const uint32_t bar = sbase + BAR_FULL + r.slot * 8;
          mbar_wait_w(bar + (BAR_EMPTY - BAR_FULL), r.phase);
          if (w.kind == 0) tma_ld3_w(sbase + r.slot * SLOT, m, 0, ks * 64, w.sub * 2, bar, 16384);
          else tma_ld_wo_w(sbase + r.slot * SLOT, m, w.sub * 128, (w.k0 + ks) * 2, bar);
          if (w.kind != 0 && w.beta < N_EARLY && (ks & 7) == 5 && ks > 5)
            asm volatile(ELECT "red.relaxed.gpu.global.add.u32 [%0], 1;\n}" ::"l"(&g_rd[w.beta][(ks >> 3) - 1]) : "memory");
          if (ks < 10) T2P(i, 2, ks);
          if (w.kind != 0 && ks == max(w.nsteps - GO_P, 4)) mbar_arrive_warp(sbase + BAR_GO);
          r.next(); r.next_if(b == 2);
        }
        if (w.kind == 0) {
          r.phase ^= 1; r.next(); r.next();
        } else if (w.mode == 2) {
          for (int k = 1; k <= ((d >> 5) & 3); k++) {
            if (k == 1) TTAIL(9);
            wait_count(&g_flag[w.range + 5 * k], lds(sbase + EPOCH_OFF));
            TTAIL(10);
            asm volatile("fence.proxy.async.global;" ::: "memory");
#pragma unroll 1
            for (int t = 0; t < 4; t++) {
              mbar_wait_w(sbase + BAR_EMPTY + r.slot * 8, r.phase);
              tma_ld3_w(sbase + r.slot * SLOT, &P.o_st[t == 3], 0, t * 64, NBETA * 64 + (w.range + 5 * k) * 2, sbase + BAR_FULL + r.slot * 8,
                        t == 3 ? 8192 : 16384);
              r.next();
            }
          }
        }
        mbar_wait_w(sbase + BAR_DESC, i & 1);
        d = __shfl_sync(0xffffffffu, lds(sbase + DESC_OFF + ((i + 1) & 3) * 4), 0);
      }
    } else {
      const int hi = warp - 2;
      uint64_t pol_stream;
      uint32_t rdy = 0;
      asm volatile("createpolicy.fractional.L2::evict_first.b64 %0, 1.0;" : "=l"(pol_stream));
      Ring r{0, 1, 3};
      uint32_t d = c_sched.queue[cta];
      for (int i = 0;; i++) {
        const Work w = decode(d);
        if (w.kind == 2) break;
        const CUtensorMap* m = w.kind == 0 ? &P.x[hi][w.beta >> 4] : &P.o_ld[hi];
        int c1 = (w.kind == 0 ? (w.beta & 15) : o_slot<SIMPLE>(w.beta) * 64 + w.k0) * SQ + hi * 128;
        int k_wait = -1;
        const bool both = PAIR && (w.kind == 0 || w.sub != 4), mine = !both || hi == (cta & 1);
        if (w.kind != 0 && mine) {
          if (d & 128) k_wait = d >= (3u << 30) ? 0 : 8 - (w.k0 & 7);
          asm volatile("fence.proxy.async.global;" ::: "memory");
        }
        const int rank = i == 0 ? cta : __shfl_sync(0xffffffffu, lds(sbase + EPOCH_OFF + 4), 0) - NCTA;
        for (int ks = 0; ks < w.nsteps; ks++) {
          if (ks == k_wait) {
            wait_count(&g_cnt[d & 31][(w.k0 + ks) >> 3], lds(sbase + EPOCH_OFF) * 4);
            asm volatile("fence.proxy.async.global;" ::: "memory");
            k_wait = ((w.k0 + ks) | 7) + 1 - w.k0;
          }
          const uint32_t b = borrow(ks, w.nsteps);
          const bool bo = b != 2;
          r.next_if(hi && !bo); r.next_if(hi && !bo);
          const uint32_t sl = bo ? NS + (b ^ (3 * hi)) : r.slot, bar = sbase + BAR_FULL + sl * 8;
          mbar_wait_w(bar + (BAR_EMPTY - BAR_FULL), bo ? (r.xp >> b) & 1 : r.phase);
          const uint32_t bytes = hi ? 96 * 128 : 128 * 128;
          if (!mine) {
            asm volatile(ELECT EXPECT("%0", "%2") "mbarrier.arrive.shared::cluster.b64 _, [%1];\n}"
                         ::"r"(bar), "r"(peer(bar + (BAR_RDY - BAR_FULL))), "r"(bytes) : "memory");
          } else if (both) {
            mbar_wait_w(bar + (BAR_RDY - BAR_FULL), (rdy >> sl) & 1);
            rdy ^= 1 << sl;
            if (w.kind == 0) tma_ld2_both_w(sbase + sl * SLOT, m, ks * 64, c1, bar, bytes);
            else tma_ld2_both_hint_w(sbase + sl * SLOT, m, 0, c1, bar, bytes, pol_stream);
          } else if (!PAIR && w.kind == 0) tma_ld2_w(sbase + sl * SLOT, m, ks * 64, c1, bar, bytes);
          else tma_ld2_hint_w(sbase + sl * SLOT, m, 0, c1, bar, bytes, pol_stream);
          if (w.kind != 0) c1 += SQ;
          if (i == 0 && ks == PF_STEP)
            asm volatile(ELECT "cp.async.bulk.prefetch.tensor.3d.L2.global.L2::cache_hint [%0, {0, %1, 0}], %2;\n}"
                         ::"l"(&P.kv[hi][0]), "r"(d * SK), "l"(pol_stream) : "memory");
          if (ks < 10) T2P(i, 3 + hi, ks);
          if (!hi && w.kind != 0 && !(ks & 3)) TCLK(i * 16 + (ks >> 2));
          r.next(); r.next_if(!hi && !bo); r.next_if(!hi && !bo);
          r.xp ^= 1 << b;
        }
        r.xp ^= 3;
        if (w.kind == 0) {
          m = &P.kv[hi][w.beta >> 4];
          c1 = (d & 511) * SK;
          for (int j = 0; j < 16; j++) {
            if (hi) r.next();
            const uint32_t bar = sbase + BAR_FULL + r.slot * 8;
            const bool tight = i < KV_WIN_UNITS && j < KV_WIN_TILES + ((KV_WIN_RAMP * rank) >> 5);
            {
              const int s2 = (int)r.slot - (tight ? 2 : KV_WIN_D);
              mbar_wait_w(sbase + BAR_FULL + (s2 < 0 ? s2 + NS : s2) * 8, s2 < 0 ? r.phase : r.phase ^ 1);
            }
            if (j == 15 && hi) mbar_wait_w(sbase + BAR_DESC, i & 1);
            mbar_wait_w(sbase + BAR_EMPTY + r.slot * 8, r.phase);
            tma_ld3_hint_w(sbase + r.slot * SLOT, m, 0, c1, 0, bar, pol_stream);
            T2P(i, 3 + hi, 16 + j);
            if (!hi) TCLK(i * 16 + j);
            if (j == 14 && !hi) mbar_arrive_warp(sbase + BAR_GO);
            c1 += 64;
            r.next();
            if (!hi) r.next();
          }
        }
        mbar_wait_w(sbase + BAR_DESC, i & 1);
        d = __shfl_sync(0xffffffffu, lds(sbase + DESC_OFF + ((i + 1) & 3) * 4), 0);
      }
    }
  } else {
    Ctx c;
    c.sb = sbase; c.wg = wg; c.warp = warp; c.src = 0; c.mqk = 0; c.mpv = 0; c.lead = lane == 0; c.lane0 = c.lane = lane;
    if (wg == 0) consumer<0>(c, P.kp); else consumer<1>(c, P.kp);
  }
}

typedef CUresult (*EncodeFn)(CUtensorMap*, CUtensorMapDataType, cuuint32_t, void*, const cuuint64_t*, const cuuint64_t*,
                             const cuuint32_t*, const cuuint32_t*, CUtensorMapInterleave, CUtensorMapSwizzle,
                             CUtensorMapL2promotion, CUtensorMapFloatOOBfill);

void make_map(EncodeFn enc, CUtensorMap* m, const void* ptr, int rank, const cuuint64_t* dims, const cuuint64_t* strides,
              const cuuint32_t* box, int promo = 2, CUtensorMapSwizzle swz = CU_TENSOR_MAP_SWIZZLE_128B) {
  cuuint32_t es[5] = {1, 1, 1, 1, 1};
  enc(m, CU_TENSOR_MAP_DATA_TYPE_BFLOAT16, rank, const_cast<void*>(ptr), dims, strides, box, es,
      CU_TENSOR_MAP_INTERLEAVE_NONE, swz, promo == 2 ? CU_TENSOR_MAP_L2_PROMOTION_L2_256B : promo == 1 ? CU_TENSOR_MAP_L2_PROMOTION_L2_128B : CU_TENSOR_MAP_L2_PROMOTION_NONE,
      CU_TENSOR_MAP_FLOAT_OOB_FILL_NONE);
}

}

extern "C" void kernel_launch(void* const* d_in, const int* in_sizes, int n_in, void* d_out, int out_size) {
  (void)in_sizes; (void)n_in; (void)out_size;
  static EncodeFn enc = nullptr;
  static void* o_ptr = nullptr;
  static int n_sm = 0;
  cudaLaunchAttribute at;
  at.id = cudaLaunchAttributeClusterDimension;
  at.val.clusterDim.x = CLUSTER ? 2 : 1; at.val.clusterDim.y = 1; at.val.clusterDim.z = 1;
  cudaLaunchConfig_t cfg = {};
  cfg.gridDim = dim3(NCTA); cfg.blockDim = dim3(384); cfg.dynamicSmemBytes = SMEM_BYTES; cfg.attrs = &at; cfg.numAttrs = 1;
  if (!enc) {
    void* fn = nullptr;
    cudaDriverEntryPointQueryResult qr;
    cudaGetDriverEntryPoint("cuTensorMapEncodeTiled", &fn, cudaEnableDefault, &qr);
    enc = (EncodeFn)fn;
    cudaGetSymbolAddress(&o_ptr, g_o);
    cudaFuncSetAttribute(mha_fused_kernel<false>, cudaFuncAttributeMaxDynamicSharedMemorySize, SMEM_BYTES);
    cudaFuncSetAttribute(mha_fused_kernel<true>, cudaFuncAttributeMaxDynamicSharedMemorySize, SMEM_BYTES);
    int dev = 0;
    cudaGetDevice(&dev);
    cudaDeviceGetAttribute(&n_sm, cudaDevAttrMultiProcessorCount, dev);
    int n_cl = 0;
    cudaOccupancyMaxActiveClusters(&n_cl, mha_fused_kernel<false>, &cfg);
    if (n_cl * (CLUSTER ? 2 : 1) < NCTA && n_sm >= NCTA) n_sm = NCTA - 1;
  }
  Params P;
  for (int br = 0; br < 2; br++) {
    const void* x = d_in[br * 5 + 0]; const void* kc = d_in[br * 5 + 1]; const void* vc = d_in[br * 5 + 2];
    const void* wq = d_in[br * 5 + 3]; const void* wo = d_in[br * 5 + 4];
    { cuuint64_t d[2] = {DM, (cuuint64_t)NB * SQ}, s[1] = {DM * 2}; cuuint32_t b[2] = {64, 128}, b2[2] = {64, 96};
      make_map(enc, &P.x[0][br], x, 2, d, s, b, PR_X); make_map(enc, &P.x[1][br], x, 2, d, s, b2, PR_X); }
    { cuuint64_t d[3] = {64, DM, HD / 64}, s[2] = {HD * 2, 128}; cuuint32_t b[3] = {64, 64, 2}; make_map(enc, &P.wq[br], wq, 3, d, s, b, PR_W); }
    { cuuint64_t d[5] = {DM, 2, 4, 4, HD / 32}, s[4] = {DM * 2, 8 * DM * 2, 2 * DM * 2, 32 * DM * 2}; cuuint32_t b[5] = {64, 2, 4, 4, 2};
      make_map(enc, &P.wo[br], wo, 5, d, s, b, PR_W); }
    { cuuint64_t d[3] = {64, (cuuint64_t)NB * NH * SK, 2}, s[2] = {DH * 2, 128}; cuuint32_t b[3] = {64, 64, 2};
      make_map(enc, &P.kv[0][br], kc, 3, d, s, b, PR_KV); make_map(enc, &P.kv[1][br], vc, 3, d, s, b, PR_KV); }
    P.kp[br] = (const __nv_bfloat16*)kc; P.vp[br] = (const __nv_bfloat16*)vc;

  }
  { cuuint64_t d[2] = {64, (cuuint64_t)NBETA * 64 * SQ}, s[1] = {128}; cuuint32_t b[2] = {64, 128}, b2[2] = {64, 96};
    make_map(enc, &P.o_ld[0], o_ptr, 2, d, s, b, 2, CU_TENSOR_MAP_SWIZZLE_NONE); make_map(enc, &P.o_ld[1], o_ptr, 2, d, s, b2, 2, CU_TENSOR_MAP_SWIZZLE_NONE); }
  { cuuint64_t d[3] = {64, SQ, O_BLOCKS}, s[2] = {128, SQ * 128}; cuuint32_t b[3] = {64, 64, 2}, b2[3] = {64, 32, 2};
    make_map(enc, &P.o_st[0], o_ptr, 3, d, s, b); make_map(enc, &P.o_st[1], o_ptr, 3, d, s, b2); }
  { cuuint64_t d[3] = {64, (cuuint64_t)NB * SQ, 2 * DM / 64}, s[2] = {2 * DM * 2, 128}; cuuint32_t b[3] = {64, 64, 2}, b2[3] = {64, 32, 2};
    make_map(enc, &P.out_st[0], d_out, 3, d, s, b); make_map(enc, &P.out_st[1], d_out, 3, d, s, b2); }
  if (n_sm >= NCTA) cudaLaunchKernelEx(&cfg, mha_fused_kernel<false>, P);
  else mha_fused_kernel<true><<<n_sm, 384, SMEM_BYTES>>>(P);
}
```

```cpp
#include <cuda_runtime.h>
#include <cuda_bf16.h>
#include <cuda.h>
#include <stdint.h>
#include <stdlib.h>

namespace {

__device__ __forceinline__ void wgmma_proj(float (&d)[64], uint64_t da, uint64_t db, int scaleD) {
  asm volatile("{\n.reg .pred p;\nsetp.ne.b32 p, %66, 0;\n"
      "wgmma.mma_async.sync.aligned.m64n128k16.f32.bf16.bf16 "
      "{%0, %1, %2, %3, %4, %5, %6, %7, %8, %9, %10, %11, %12, %13, %14, %15, %16, %17, %18, %19, %20, %21, %22, %23, %24, %25, %26, %27, %28, %29, %30, "
      "%31, %32, %33, %34, %35, %36, %37, %38, %39, %40, %41, %42, %43, %44, %45, %46, %47, %48, %49, %50, %51, %52, %53, %54, %55, %56, %57, %58, %59, %60, "
      "%61, %62, %63}, "
      "%64, %65, p, 1, 1, 0, 1;\n}\n"
      : "+f"(d[0]), "+f"(d[1]), "+f"(d[2]), "+f"(d[3]), "+f"(d[4]), "+f"(d[5]), "+f"(d[6]), "+f"(d[7]), "+f"(d[8]), "+f"(d[9]), "+f"(d[10]), "+f"(d[11]),
        "+f"(d[12]), "+f"(d[13]), "+f"(d[14]), "+f"(d[15]), "+f"(d[16]), "+f"(d[17]), "+f"(d[18]), "+f"(d[19]), "+f"(d[20]), "+f"(d[21]), "+f"(d[22]),
        "+f"(d[23]), "+f"(d[24]), "+f"(d[25]), "+f"(d[26]), "+f"(d[27]), "+f"(d[28]), "+f"(d[29]), "+f"(d[30]), "+f"(d[31]), "+f"(d[32]), "+f"(d[33]),
        "+f"(d[34]), "+f"(d[35]), "+f"(d[36]), "+f"(d[37]), "+f"(d[38]), "+f"(d[39]), "+f"(d[40]), "+f"(d[41]), "+f"(d[42]), "+f"(d[43]), "+f"(d[44]),
        "+f"(d[45]), "+f"(d[46]), "+f"(d[47]), "+f"(d[48]), "+f"(d[49]), "+f"(d[50]), "+f"(d[51]), "+f"(d[52]), "+f"(d[53]), "+f"(d[54]), "+f"(d[55]),
        "+f"(d[56]), "+f"(d[57]), "+f"(d[58]), "+f"(d[59]), "+f"(d[60]), "+f"(d[61]), "+f"(d[62]), "+f"(d[63])
      : "l"(da), "l"(db), "r"(scaleD));
}
__device__ __forceinline__ void wgmma_proj96(float (&d)[64], uint64_t da, uint64_t db, int scaleD) {
  asm volatile("{\n.reg .pred p;\nsetp.ne.b32 p, %50, 0;\n"
      "wgmma.mma_async.sync.aligned.m64n96k16.f32.bf16.bf16 "
      "{%0, %1, %2, %3, %4, %5, %6, %7, %8, %9, %10, %11, %12, %13, %14, %15, %16, %17, %18, %19, %20, %21, %22, %23, %24, %25, %26, %27, %28, %29, %30, "
      "%31, %32, %33, %34, %35, %36, %37, %38, %39, %40, %41, %42, %43, %44, %45, %46, %47}, "
      "%48, %49, p, 1, 1, 1, 0;\n}\n"
      : "+f"(d[0]), "+f"(d[1]), "+f"(d[2]), "+f"(d[3]), "+f"(d[4]), "+f"(d[5]), "+f"(d[6]), "+f"(d[7]), "+f"(d[8]), "+f"(d[9]), "+f"(d[10]), "+f"(d[11]),
        "+f"(d[12]), "+f"(d[13]), "+f"(d[14]), "+f"(d[15]), "+f"(d[16]), "+f"(d[17]), "+f"(d[18]), "+f"(d[19]), "+f"(d[20]), "+f"(d[21]), "+f"(d[22]),
        "+f"(d[23]), "+f"(d[24]), "+f"(d[25]), "+f"(d[26]), "+f"(d[27]), "+f"(d[28]), "+f"(d[29]), "+f"(d[30]), "+f"(d[31]), "+f"(d[32]), "+f"(d[33]),
        "+f"(d[34]), "+f"(d[35]), "+f"(d[36]), "+f"(d[37]), "+f"(d[38]), "+f"(d[39]), "+f"(d[40]), "+f"(d[41]), "+f"(d[42]), "+f"(d[43]), "+f"(d[44]),
        "+f"(d[45]), "+f"(d[46]), "+f"(d[47])
      : "l"(da), "l"(db), "r"(scaleD));
}
__device__ __forceinline__ void wgmma_qk(float (&d)[32], uint64_t da, uint64_t db, int scaleD) {
  asm volatile("{\n.reg .pred p;\nsetp.ne.b32 p, %34, 0;\n"
      "wgmma.mma_async.sync.aligned.m64n64k16.f32.bf16.bf16 "
      "{%0, %1, %2, %3, %4, %5, %6, %7, %8, %9, %10, %11, %12, %13, %14, %15, %16, %17, %18, %19, %20, %21, %22, %23, %24, %25, %26, %27, %28, %29, %30, "
      "%31}, "
      "%32, %33, p, 1, 1, 0, 0;\n}\n"
      : "+f"(d[0]), "+f"(d[1]), "+f"(d[2]), "+f"(d[3]), "+f"(d[4]), "+f"(d[5]), "+f"(d[6]), "+f"(d[7]), "+f"(d[8]), "+f"(d[9]), "+f"(d[10]), "+f"(d[11]),
        "+f"(d[12]), "+f"(d[13]), "+f"(d[14]), "+f"(d[15]), "+f"(d[16]), "+f"(d[17]), "+f"(d[18]), "+f"(d[19]), "+f"(d[20]), "+f"(d[21]), "+f"(d[22]),
        "+f"(d[23]), "+f"(d[24]), "+f"(d[25]), "+f"(d[26]), "+f"(d[27]), "+f"(d[28]), "+f"(d[29]), "+f"(d[30]), "+f"(d[31])
      : "l"(da), "l"(db), "r"(scaleD));
}
__device__ __forceinline__ void wgmma_qk_rs(float (&d)[32], uint32_t a0, uint32_t a1, uint32_t a2, uint32_t a3, uint64_t db, int scaleD) {
  asm volatile("{\n.reg .pred p;\nsetp.ne.b32 p, %37, 0;\n"
      "wgmma.mma_async.sync.aligned.m64n64k16.f32.bf16.bf16 "
      "{%0, %1, %2, %3, %4, %5, %6, %7, %8, %9, %10, %11, %12, %13, %14, %15, %16, %17, %18, %19, %20, %21, %22, %23, %24, %25, %26, %27, %28, %29, %30, "
      "%31}, "
      "{%32, %33, %34, %35}, %36, p, 1, 1, 0;\n}\n"
      : "+f"(d[0]), "+f"(d[1]), "+f"(d[2]), "+f"(d[3]), "+f"(d[4]), "+f"(d[5]), "+f"(d[6]), "+f"(d[7]), "+f"(d[8]), "+f"(d[9]), "+f"(d[10]), "+f"(d[11]),
        "+f"(d[12]), "+f"(d[13]), "+f"(d[14]), "+f"(d[15]), "+f"(d[16]), "+f"(d[17]), "+f"(d[18]), "+f"(d[19]), "+f"(d[20]), "+f"(d[21]), "+f"(d[22]),
        "+f"(d[23]), "+f"(d[24]), "+f"(d[25]), "+f"(d[26]), "+f"(d[27]), "+f"(d[28]), "+f"(d[29]), "+f"(d[30]), "+f"(d[31])
      : "r"(a0), "r"(a1), "r"(a2), "r"(a3), "l"(db), "r"(scaleD));
}
__device__ __forceinline__ void wgmma_pv(float (&d)[64], uint32_t a0, uint32_t a1, uint32_t a2, uint32_t a3, uint64_t db, int scaleD) {
  asm volatile("{\n.reg .pred p;\nsetp.ne.b32 p, %69, 0;\n"
      "wgmma.mma_async.sync.aligned.m64n128k16.f32.bf16.bf16 "
      "{%0, %1, %2, %3, %4, %5, %6, %7, %8, %9, %10, %11, %12, %13, %14, %15, %16, %17, %18, %19, %20, %21, %22, %23, %24, %25, %26, %27, %28, %29, %30, "
      "%31, %32, %33, %34, %35, %36, %37, %38, %39, %40, %41, %42, %43, %44, %45, %46, %47, %48, %49, %50, %51, %52, %53, %54, %55, %56, %57, %58, %59, %60, "
      "%61, %62, %63}, "
      "{%64, %65, %66, %67}, %68, p, 1, 1, 1;\n}\n"
      : "+f"(d[0]), "+f"(d[1]), "+f"(d[2]), "+f"(d[3]), "+f"(d[4]), "+f"(d[5]), "+f"(d[6]), "+f"(d[7]), "+f"(d[8]), "+f"(d[9]), "+f"(d[10]), "+f"(d[11]),
        "+f"(d[12]), "+f"(d[13]), "+f"(d[14]), "+f"(d[15]), "+f"(d[16]), "+f"(d[17]), "+f"(d[18]), "+f"(d[19]), "+f"(d[20]), "+f"(d[21]), "+f"(d[22]),
        "+f"(d[23]), "+f"(d[24]), "+f"(d[25]), "+f"(d[26]), "+f"(d[27]), "+f"(d[28]), "+f"(d[29]), "+f"(d[30]), "+f"(d[31]), "+f"(d[32]), "+f"(d[33]),
        "+f"(d[34]), "+f"(d[35]), "+f"(d[36]), "+f"(d[37]), "+f"(d[38]), "+f"(d[39]), "+f"(d[40]), "+f"(d[41]), "+f"(d[42]), "+f"(d[43]), "+f"(d[44]),
        "+f"(d[45]), "+f"(d[46]), "+f"(d[47]), "+f"(d[48]), "+f"(d[49]), "+f"(d[50]), "+f"(d[51]), "+f"(d[52]), "+f"(d[53]), "+f"(d[54]), "+f"(d[55]),
        "+f"(d[56]), "+f"(d[57]), "+f"(d[58]), "+f"(d[59]), "+f"(d[60]), "+f"(d[61]), "+f"(d[62]), "+f"(d[63])
      : "r"(a0), "r"(a1), "r"(a2), "r"(a3), "l"(db), "r"(scaleD));
}
__device__ __forceinline__ void wgmma_qk_sp(float (&d)[32], uint32_t a0, uint32_t a1, uint32_t a2, uint32_t a3, uint64_t db, int scaleD, uint32_t meta) {
  asm volatile("{\n.reg .pred p;\nsetp.ne.b32 p, %37, 0;\n"
      "wgmma.mma_async.sp.sync.aligned.m64n64k32.f32.bf16.bf16 "
      "{%0, %1, %2, %3, %4, %5, %6, %7, %8, %9, %10, %11, %12, %13, %14, %15, %16, %17, %18, %19, %20, %21, %22, %23, %24, %25, %26, %27, %28, %29, %30, "
      "%31}, "
      "{%32, %33, %34, %35}, %36, %38, 0, p, 1, 1, 0;\n}\n"
      : "+f"(d[0]), "+f"(d[1]), "+f"(d[2]), "+f"(d[3]), "+f"(d[4]), "+f"(d[5]), "+f"(d[6]), "+f"(d[7]), "+f"(d[8]), "+f"(d[9]), "+f"(d[10]), "+f"(d[11]),
        "+f"(d[12]), "+f"(d[13]), "+f"(d[14]), "+f"(d[15]), "+f"(d[16]), "+f"(d[17]), "+f"(d[18]), "+f"(d[19]), "+f"(d[20]), "+f"(d[21]), "+f"(d[22]),
        "+f"(d[23]), "+f"(d[24]), "+f"(d[25]), "+f"(d[26]), "+f"(d[27]), "+f"(d[28]), "+f"(d[29]), "+f"(d[30]), "+f"(d[31])
      : "r"(a0), "r"(a1), "r"(a2), "r"(a3), "l"(db), "r"(scaleD), "r"(meta));
}
__device__ __forceinline__ void wgmma_pv_sp(float (&d)[64], uint32_t a0, uint32_t a1, uint32_t a2, uint32_t a3, uint64_t db, int scaleD, uint32_t meta) {
  asm volatile("{\n.reg .pred p;\nsetp.ne.b32 p, %69, 0;\n"
      "wgmma.mma_async.sp.sync.aligned.m64n128k32.f32.bf16.bf16 "
      "{%0, %1, %2, %3, %4, %5, %6, %7, %8, %9, %10, %11, %12, %13, %14, %15, %16, %17, %18, %19, %20, %21, %22, %23, %24, %25, %26, %27, %28, %29, %30, "
      "%31, %32, %33, %34, %35, %36, %37, %38, %39, %40, %41, %42, %43, %44, %45, %46, %47, %48, %49, %50, %51, %52, %53, %54, %55, %56, %57, %58, %59, %60, "
      "%61, %62, %63}, "
      "{%64, %65, %66, %67}, %68, %70, 0, p, 1, 1, 1;\n}\n"
      : "+f"(d[0]), "+f"(d[1]), "+f"(d[2]), "+f"(d[3]), "+f"(d[4]), "+f"(d[5]), "+f"(d[6]), "+f"(d[7]), "+f"(d[8]), "+f"(d[9]), "+f"(d[10]), "+f"(d[11]),
        "+f"(d[12]), "+f"(d[13]), "+f"(d[14]), "+f"(d[15]), "+f"(d[16]), "+f"(d[17]), "+f"(d[18]), "+f"(d[19]), "+f"(d[20]), "+f"(d[21]), "+f"(d[22]),
        "+f"(d[23]), "+f"(d[24]), "+f"(d[25]), "+f"(d[26]), "+f"(d[27]), "+f"(d[28]), "+f"(d[29]), "+f"(d[30]), "+f"(d[31]), "+f"(d[32]), "+f"(d[33]),
        "+f"(d[34]), "+f"(d[35]), "+f"(d[36]), "+f"(d[37]), "+f"(d[38]), "+f"(d[39]), "+f"(d[40]), "+f"(d[41]), "+f"(d[42]), "+f"(d[43]), "+f"(d[44]),
        "+f"(d[45]), "+f"(d[46]), "+f"(d[47]), "+f"(d[48]), "+f"(d[49]), "+f"(d[50]), "+f"(d[51]), "+f"(d[52]), "+f"(d[53]), "+f"(d[54]), "+f"(d[55]),
        "+f"(d[56]), "+f"(d[57]), "+f"(d[58]), "+f"(d[59]), "+f"(d[60]), "+f"(d[61]), "+f"(d[62]), "+f"(d[63])
      : "r"(a0), "r"(a1), "r"(a2), "r"(a3), "l"(db), "r"(scaleD), "r"(meta));
}
__device__ __forceinline__ void wgmma_proj_init(float (&d)[64], uint64_t da, uint64_t db, int scaleD) {
  asm volatile("{\n.reg .pred p;\nsetp.ne.b32 p, %66, 0;\n"
      "wgmma.mma_async.sync.aligned.m64n128k16.f32.bf16.bf16 "
      "{%0, %1, %2, %3, %4, %5, %6, %7, %8, %9, %10, %11, %12, %13, %14, %15, %16, %17, %18, %19, %20, %21, %22, %23, %24, %25, %26, %27, %28, %29, %30, "
      "%31, %32, %33, %34, %35, %36, %37, %38, %39, %40, %41, %42, %43, %44, %45, %46, %47, %48, %49, %50, %51, %52, %53, %54, %55, %56, %57, %58, %59, %60, "
      "%61, %62, %63}, "
      "%64, %65, p, 1, 1, 0, 1;\n}\n"
      : "=f"(d[0]), "=f"(d[1]), "=f"(d[2]), "=f"(d[3]), "=f"(d[4]), "=f"(d[5]), "=f"(d[6]), "=f"(d[7]), "=f"(d[8]), "=f"(d[9]), "=f"(d[10]), "=f"(d[11]),
        "=f"(d[12]), "=f"(d[13]), "=f"(d[14]), "=f"(d[15]), "=f"(d[16]), "=f"(d[17]), "=f"(d[18]), "=f"(d[19]), "=f"(d[20]), "=f"(d[21]), "=f"(d[22]),
        "=f"(d[23]), "=f"(d[24]), "=f"(d[25]), "=f"(d[26]), "=f"(d[27]), "=f"(d[28]), "=f"(d[29]), "=f"(d[30]), "=f"(d[31]), "=f"(d[32]), "=f"(d[33]),
        "=f"(d[34]), "=f"(d[35]), "=f"(d[36]), "=f"(d[37]), "=f"(d[38]), "=f"(d[39]), "=f"(d[40]), "=f"(d[41]), "=f"(d[42]), "=f"(d[43]), "=f"(d[44]),
        "=f"(d[45]), "=f"(d[46]), "=f"(d[47]), "=f"(d[48]), "=f"(d[49]), "=f"(d[50]), "=f"(d[51]), "=f"(d[52]), "=f"(d[53]), "=f"(d[54]), "=f"(d[55]),
        "=f"(d[56]), "=f"(d[57]), "=f"(d[58]), "=f"(d[59]), "=f"(d[60]), "=f"(d[61]), "=f"(d[62]), "=f"(d[63])
      : "l"(da), "l"(db), "r"(scaleD));
}
__device__ __forceinline__ void wgmma_proj96_init(float (&d)[64], uint64_t da, uint64_t db, int scaleD) {
  asm volatile("{\n.reg .pred p;\nsetp.ne.b32 p, %50, 0;\n"
      "wgmma.mma_async.sync.aligned.m64n96k16.f32.bf16.bf16 "
      "{%0, %1, %2, %3, %4, %5, %6, %7, %8, %9, %10, %11, %12, %13, %14, %15, %16, %17, %18, %19, %20, %21, %22, %23, %24, %25, %26, %27, %28, %29, %30, "
      "%31, %32, %33, %34, %35, %36, %37, %38, %39, %40, %41, %42, %43, %44, %45, %46, %47}, "
      "%48, %49, p, 1, 1, 1, 0;\n}\n"
      : "=f"(d[0]), "=f"(d[1]), "=f"(d[2]), "=f"(d[3]), "=f"(d[4]), "=f"(d[5]), "=f"(d[6]), "=f"(d[7]), "=f"(d[8]), "=f"(d[9]), "=f"(d[10]), "=f"(d[11]),
        "=f"(d[12]), "=f"(d[13]), "=f"(d[14]), "=f"(d[15]), "=f"(d[16]), "=f"(d[17]), "=f"(d[18]), "=f"(d[19]), "=f"(d[20]), "=f"(d[21]), "=f"(d[22]),
        "=f"(d[23]), "=f"(d[24]), "=f"(d[25]), "=f"(d[26]), "=f"(d[27]), "=f"(d[28]), "=f"(d[29]), "=f"(d[30]), "=f"(d[31]), "=f"(d[32]), "=f"(d[33]),
        "=f"(d[34]), "=f"(d[35]), "=f"(d[36]), "=f"(d[37]), "=f"(d[38]), "=f"(d[39]), "=f"(d[40]), "=f"(d[41]), "=f"(d[42]), "=f"(d[43]), "=f"(d[44]),
        "=f"(d[45]), "=f"(d[46]), "=f"(d[47])
      : "l"(da), "l"(db), "r"(scaleD));
}
__device__ __forceinline__ void wgmma_qk_init(float (&d)[32], uint64_t da, uint64_t db, int scaleD) {
  asm volatile("{\n.reg .pred p;\nsetp.ne.b32 p, %34, 0;\n"
      "wgmma.mma_async.sync.aligned.m64n64k16.f32.bf16.bf16 "
      "{%0, %1, %2, %3, %4, %5, %6, %7, %8, %9, %10, %11, %12, %13, %14, %15, %16, %17, %18, %19, %20, %21, %22, %23, %24, %25, %26, %27, %28, %29, %30, "
      "%31}, "
      "%32, %33, p, 1, 1, 0, 0;\n}\n"
      : "=f"(d[0]), "=f"(d[1]), "=f"(d[2]), "=f"(d[3]), "=f"(d[4]), "=f"(d[5]), "=f"(d[6]), "=f"(d[7]), "=f"(d[8]), "=f"(d[9]), "=f"(d[10]), "=f"(d[11]),
        "=f"(d[12]), "=f"(d[13]), "=f"(d[14]), "=f"(d[15]), "=f"(d[16]), "=f"(d[17]), "=f"(d[18]), "=f"(d[19]), "=f"(d[20]), "=f"(d[21]), "=f"(d[22]),
        "=f"(d[23]), "=f"(d[24]), "=f"(d[25]), "=f"(d[26]), "=f"(d[27]), "=f"(d[28]), "=f"(d[29]), "=f"(d[30]), "=f"(d[31])
      : "l"(da), "l"(db), "r"(scaleD));
}
__device__ __forceinline__ void wgmma_qk_rs_init(float (&d)[32], uint32_t a0, uint32_t a1, uint32_t a2, uint32_t a3, uint64_t db, int scaleD) {
  asm volatile("{\n.reg .pred p;\nsetp.ne.b32 p, %37, 0;\n"
      "wgmma.mma_async.sync.aligned.m64n64k16.f32.bf16.bf16 "
      "{%0, %1, %2, %3, %4, %5, %6, %7, %8, %9, %10, %11, %12, %13, %14, %15, %16, %17, %18, %19, %20, %21, %22, %23, %24, %25, %26, %27, %28, %29, %30, "
      "%31}, "
      "{%32, %33, %34, %35}, %36, p, 1, 1, 0;\n}\n"
      : "=f"(d[0]), "=f"(d[1]), "=f"(d[2]), "=f"(d[3]), "=f"(d[4]), "=f"(d[5]), "=f"(d[6]), "=f"(d[7]), "=f"(d[8]), "=f"(d[9]), "=f"(d[10]), "=f"(d[11]),
        "=f"(d[12]), "=f"(d[13]), "=f"(d[14]), "=f"(d[15]), "=f"(d[16]), "=f"(d[17]), "=f"(d[18]), "=f"(d[19]), "=f"(d[20]), "=f"(d[21]), "=f"(d[22]),
        "=f"(d[23]), "=f"(d[24]), "=f"(d[25]), "=f"(d[26]), "=f"(d[27]), "=f"(d[28]), "=f"(d[29]), "=f"(d[30]), "=f"(d[31])
      : "r"(a0), "r"(a1), "r"(a2), "r"(a3), "l"(db), "r"(scaleD));
}
__device__ __forceinline__ void wgmma_pv_init(float (&d)[64], uint32_t a0, uint32_t a1, uint32_t a2, uint32_t a3, uint64_t db, int scaleD) {
  asm volatile("{\n.reg .pred p;\nsetp.ne.b32 p, %69, 0;\n"
      "wgmma.mma_async.sync.aligned.m64n128k16.f32.bf16.bf16 "
      "{%0, %1, %2, %3, %4, %5, %6, %7, %8, %9, %10, %11, %12, %13, %14, %15, %16, %17, %18, %19, %20, %21, %22, %23, %24, %25, %26, %27, %28, %29, %30, "
      "%31, %32, %33, %34, %35, %36, %37, %38, %39, %40, %41, %42, %43, %44, %45, %46, %47, %48, %49, %50, %51, %52, %53, %54, %55, %56, %57, %58, %59, %60, "
      "%61, %62, %63}, "
      "{%64, %65, %66, %67}, %68, p, 1, 1, 1;\n}\n"
      : "=f"(d[0]), "=f"(d[1]), "=f"(d[2]), "=f"(d[3]), "=f"(d[4]), "=f"(d[5]), "=f"(d[6]), "=f"(d[7]), "=f"(d[8]), "=f"(d[9]), "=f"(d[10]), "=f"(d[11]),
        "=f"(d[12]), "=f"(d[13]), "=f"(d[14]), "=f"(d[15]), "=f"(d[16]), "=f"(d[17]), "=f"(d[18]), "=f"(d[19]), "=f"(d[20]), "=f"(d[21]), "=f"(d[22]),
        "=f"(d[23]), "=f"(d[24]), "=f"(d[25]), "=f"(d[26]), "=f"(d[27]), "=f"(d[28]), "=f"(d[29]), "=f"(d[30]), "=f"(d[31]), "=f"(d[32]), "=f"(d[33]),
        "=f"(d[34]), "=f"(d[35]), "=f"(d[36]), "=f"(d[37]), "=f"(d[38]), "=f"(d[39]), "=f"(d[40]), "=f"(d[41]), "=f"(d[42]), "=f"(d[43]), "=f"(d[44]),
        "=f"(d[45]), "=f"(d[46]), "=f"(d[47]), "=f"(d[48]), "=f"(d[49]), "=f"(d[50]), "=f"(d[51]), "=f"(d[52]), "=f"(d[53]), "=f"(d[54]), "=f"(d[55]),
        "=f"(d[56]), "=f"(d[57]), "=f"(d[58]), "=f"(d[59]), "=f"(d[60]), "=f"(d[61]), "=f"(d[62]), "=f"(d[63])
      : "r"(a0), "r"(a1), "r"(a2), "r"(a3), "l"(db), "r"(scaleD));
}
__device__ __forceinline__ void wgmma_qk_sp_init(float (&d)[32], uint32_t a0, uint32_t a1, uint32_t a2, uint32_t a3, uint64_t db, int scaleD, uint32_t meta) {
  asm volatile("{\n.reg .pred p;\nsetp.ne.b32 p, %37, 0;\n"
      "wgmma.mma_async.sp.sync.aligned.m64n64k32.f32.bf16.bf16 "
      "{%0, %1, %2, %3, %4, %5, %6, %7, %8, %9, %10, %11, %12, %13, %14, %15, %16, %17, %18, %19, %20, %21, %22, %23, %24, %25, %26, %27, %28, %29, %30, "
      "%31}, "
      "{%32, %33, %34, %35}, %36, %38, 0, p, 1, 1, 0;\n}\n"
      : "=f"(d[0]), "=f"(d[1]), "=f"(d[2]), "=f"(d[3]), "=f"(d[4]), "=f"(d[5]), "=f"(d[6]), "=f"(d[7]), "=f"(d[8]), "=f"(d[9]), "=f"(d[10]), "=f"(d[11]),
        "=f"(d[12]), "=f"(d[13]), "=f"(d[14]), "=f"(d[15]), "=f"(d[16]), "=f"(d[17]), "=f"(d[18]), "=f"(d[19]), "=f"(d[20]), "=f"(d[21]), "=f"(d[22]),
        "=f"(d[23]), "=f"(d[24]), "=f"(d[25]), "=f"(d[26]), "=f"(d[27]), "=f"(d[28]), "=f"(d[29]), "=f"(d[30]), "=f"(d[31])
      : "r"(a0), "r"(a1), "r"(a2), "r"(a3), "l"(db), "r"(scaleD), "r"(meta));
}
__device__ __forceinline__ void wgmma_pv_sp_init(float (&d)[64], uint32_t a0, uint32_t a1, uint32_t a2, uint32_t a3, uint64_t db, int scaleD, uint32_t meta) {
  asm volatile("{\n.reg .pred p;\nsetp.ne.b32 p, %69, 0;\n"
      "wgmma.mma_async.sp.sync.aligned.m64n128k32.f32.bf16.bf16 "
      "{%0, %1, %2, %3, %4, %5, %6, %7, %8, %9, %10, %11, %12, %13, %14, %15, %16, %17, %18, %19, %20, %21, %22, %23, %24, %25, %26, %27, %28, %29, %30, "
      "%31, %32, %33, %34, %35, %36, %37, %38, %39, %40, %41, %42, %43, %44, %45, %46, %47, %48, %49, %50, %51, %52, %53, %54, %55, %56, %57, %58, %59, %60, "
      "%61, %62, %63}, "
      "{%64, %65, %66, %67}, %68, %70, 0, p, 1, 1, 1;\n}\n"
      : "=f"(d[0]), "=f"(d[1]), "=f"(d[2]), "=f"(d[3]), "=f"(d[4]), "=f"(d[5]), "=f"(d[6]), "=f"(d[7]), "=f"(d[8]), "=f"(d[9]), "=f"(d[10]), "=f"(d[11]),
        "=f"(d[12]), "=f"(d[13]), "=f"(d[14]), "=f"(d[15]), "=f"(d[16]), "=f"(d[17]), "=f"(d[18]), "=f"(d[19]), "=f"(d[20]), "=f"(d[21]), "=f"(d[22]),
        "=f"(d[23]), "=f"(d[24]), "=f"(d[25]), "=f"(d[26]), "=f"(d[27]), "=f"(d[28]), "=f"(d[29]), "=f"(d[30]), "=f"(d[31]), "=f"(d[32]), "=f"(d[33]),
        "=f"(d[34]), "=f"(d[35]), "=f"(d[36]), "=f"(d[37]), "=f"(d[38]), "=f"(d[39]), "=f"(d[40]), "=f"(d[41]), "=f"(d[42]), "=f"(d[43]), "=f"(d[44]),
        "=f"(d[45]), "=f"(d[46]), "=f"(d[47]), "=f"(d[48]), "=f"(d[49]), "=f"(d[50]), "=f"(d[51]), "=f"(d[52]), "=f"(d[53]), "=f"(d[54]), "=f"(d[55]),
        "=f"(d[56]), "=f"(d[57]), "=f"(d[58]), "=f"(d[59]), "=f"(d[60]), "=f"(d[61]), "=f"(d[62]), "=f"(d[63])
      : "r"(a0), "r"(a1), "r"(a2), "r"(a3), "l"(db), "r"(scaleD), "r"(meta));
}

constexpr int NB = 16, SQ = 224, DM = 640, NH = 32, SK = 1024, DH = 128;
constexpr int HD = NH * DH;
constexpr int NBETA = 2 * NB;
constexpr int NCTA = 132;
constexpr uint32_t SB0 = 1024;
constexpr int NS = 10;
constexpr int SLOT = 16384;
constexpr int QBUF_OFF = NS * SLOT;
constexpr int NSX = NS + 4;
constexpr int BAR_OFF = NSX * SLOT;
constexpr int BAR_FULL = BAR_OFF;
constexpr int BAR_EMPTY = BAR_OFF + 8 * NSX;
constexpr int BAR_STG = BAR_OFF + 16 * NSX;
constexpr int BAR_OUT = BAR_STG + 32;
constexpr int BAR_DESC = BAR_OUT + 8;
constexpr int BAR_GO = BAR_DESC + 8;
constexpr int BAR_MAIL = BAR_GO + 8;
constexpr int BAR_RDY = BAR_MAIL + 8;
constexpr int DESC_OFF = BAR_RDY + 8 * NSX;
constexpr int EPOCH_OFF = DESC_OFF + 16;
constexpr int TRACE_OFF = EPOCH_OFF + 16;
constexpr int SMEM_BYTES = TRACE_OFF;
constexpr float SM_C = 0.08838834764831845f * 1.4426950408889634f;
constexpr float SUM_HI = 1099511627776.f, SUM_LO = 1.f / 1099511627776.f;
constexpr uint32_t META_QK = 0xEEEE4444u;
constexpr uint32_t META_PV = 0x44EEEE44u;

#define QK_EARLY_MASK 3
#define ST_ORDER 0x2310
#define LAG_BAR 2
#define ST_NOW 8
#define PF_STEP 5
#define KV_WIN_UNITS 2
#define KV_WIN_D 4
#define SF 0xeebf
#define O_STEPS 4
#define KV_WIN_RAMP 4
#define PDEPTH 0
#define KV_WIN_TILES -2
#define PR_KV 2
#define PR_X 2
#define PR_W 2
#define REG_C 232
#define REG_P 24
#define GO_P 4
#define P_POS 216
#define OR 6
#define OR0 0
#define B_LATE 23
#define H_LATE 24
#define RM0 1
#define RM1 0xab
#define RM2 0
#define CLUSTER 1
#define PAIRB 1
#define LATE0 1
#define LATE1 2
#define PACK1 0
#define LAGK 8
#define KG 5
#define PK 44
#define EARLY_MASK 0x3fffu
#define PIECE_TABLE 0x50188016,0x65e88038,0x50321819,0x6c8d1830,0x403f2812,0x80000000,0x50215014,0x695a503c,0x5029b813,0x6c4eb85e,0x501b4815,0x689d4834,0x502b1017,0x6ccc1039,0x50312010,0x80000000,0x500e681b,0x65e8683f,0x502ea011,0x80000000,0x63b1902e,0x80000000,0x63f0603b,0x80000000,0x64ad003d,0x80000000,0x64eca83a,0x80000000,0x5024581c,0x80000000,0x5012b01a,0x6a95b033,0x5011081d,0x6b130837,0x5016701f,0x6c8d7056,0x501ec81e,0x80000000,0x6723302f,0x80000000,0x501b380f,0x80000000,0x67234035,0x80000000,0x500d980e,0x6bd09831,0x56587816,0x80000000,0x50168818,0x80000000,0x57d1c01e,0x80000000

struct Params {
  CUtensorMap x[2][2], wq[2], kv[2][2], wo[2];
  CUtensorMap o_ld[2], o_st[2], out_st[2];
  const __nv_bfloat16* kp[2];
  const __nv_bfloat16* vp[2];
};

constexpr int NPART = 32 * 5, O_BLOCKS = NBETA * 64 + 2 * NPART;
__device__ __align__(128) __nv_bfloat16 g_o[(size_t)O_BLOCKS * SQ * 64];
__device__ unsigned g_cnt[NBETA][8];
__device__ unsigned g_rd[NBETA][8];
__device__ unsigned g_epoch, g_next;
__device__ unsigned g_flag[NPART];

__device__ __forceinline__ uint32_t smem_u32(const void* p) { return (uint32_t)__cvta_generic_to_shared(p); }
__device__ __forceinline__ void mbar_arrive(uint32_t bar) {
  asm volatile("mbarrier.arrive.shared::cta.b64 _, [%0];" ::"r"(bar) : "memory");
}
__device__ __forceinline__ void mbar_arrive_warp(uint32_t bar) {
  asm volatile("{\n.reg .pred p;\nelect.sync _|p, 0xffffffff;\n@p mbarrier.arrive.shared::cta.b64 _, [%0];\n}" ::"r"(bar) : "memory");
}
__device__ __forceinline__ int lane_now() { int l; asm volatile("mov.u32 %0, %%laneid;" : "=r"(l)); return l; }
__device__ __forceinline__ bool mbar_try(uint32_t bar, uint32_t parity) {
  uint32_t ok;
  asm volatile("{\n.reg .pred p;\nmbarrier.try_wait.parity.shared::cta.b64 p, [%1], %2;\nselp.u32 %0, 1, 0, p;\n}"
               : "=r"(ok) : "r"(bar), "r"(parity) : "memory");
  return ok;
}
__device__ __forceinline__ bool mbar_test(uint32_t bar, uint32_t parity) {
  uint32_t ok;
  asm volatile("{\n.reg .pred p;\nmbarrier.test_wait.parity.shared::cta.b64 p, [%1], %2;\nselp.u32 %0, 1, 0, p;\n}"
               : "=r"(ok) : "r"(bar), "r"(parity) : "memory");
  return ok;
}
__device__ __forceinline__ void mbar_wait_w(uint32_t bar, uint32_t parity) {
  uint32_t n = 0;
  while (!__all_sync(0xffffffffu, mbar_try(bar, parity))) {
    if (++n > (1u << 22)) __trap();
  }
}
#define ELECT "{\n.reg .pred p;\nelect.sync _|p, 0xffffffff;\n@p "
__device__ __forceinline__ void tma_st3_hint_w(const CUtensorMap* m, uint32_t src, int c0, int c1, int c2, uint64_t pol) {
  asm volatile(ELECT "cp.async.bulk.tensor.3d.global.shared::cta.bulk_group.L2::cache_hint [%0, {%2, %3, %4}], [%1], %5;\n}"
               ::"l"(m), "r"(src), "r"(c0), "r"(c1), "r"(c2), "l"(pol) : "memory");
}
#define EXPECT(bar, bytes) "mbarrier.arrive.expect_tx.shared::cta.b64 _, [" bar "], " bytes ";\n@p "
__device__ __forceinline__ void tma_ld2_w(uint32_t dst, const CUtensorMap* m, int c0, int c1, uint32_t bar, uint32_t bytes) {
  asm volatile(ELECT EXPECT("%2", "%5") "cp.async.bulk.tensor.2d.shared::cluster.global.mbarrier::complete_tx::bytes [%0], [%1, {%3, %4}], [%2];\n}"
               ::"r"(dst), "l"(m), "r"(bar), "r"(c0), "r"(c1), "r"(bytes) : "memory");
}
__device__ __forceinline__ void tma_ld2_hint_w(uint32_t dst, const CUtensorMap* m, int c0, int c1, uint32_t bar, uint32_t bytes, uint64_t pol) {
  asm volatile(ELECT EXPECT("%2", "%6") "cp.async.bulk.tensor.2d.shared::cluster.global.mbarrier::complete_tx::bytes.L2::cache_hint"
               " [%0], [%1, {%3, %4}], [%2], %5;\n}"
               ::"r"(dst), "l"(m), "r"(bar), "r"(c0), "r"(c1), "l"(pol), "r"(bytes) : "memory");
}
__device__ __forceinline__ void tma_ld3_w(uint32_t dst, const CUtensorMap* m, int c0, int c1, int c2, uint32_t bar, uint32_t bytes) {
  asm volatile(ELECT EXPECT("%2", "%6") "cp.async.bulk.tensor.3d.shared::cluster.global.mbarrier::complete_tx::bytes [%0], [%1, {%3, %4, %5}], [%2];\n}"
               ::"r"(dst), "l"(m), "r"(bar), "r"(c0), "r"(c1), "r"(c2), "r"(bytes) : "memory");
}
__device__ __forceinline__ void tma_ld3_hint_w(uint32_t dst, const CUtensorMap* m, int c0, int c1, int c2, uint32_t bar, uint64_t pol) {
  asm volatile(ELECT EXPECT("%2", "16384") "cp.async.bulk.tensor.3d.shared::cluster.global.mbarrier::complete_tx::bytes.L2::cache_hint"
               " [%0], [%1, {%3, %4, %5}], [%2], %6;\n}"
               ::"r"(dst), "l"(m), "r"(bar), "r"(c0), "r"(c1), "r"(c2), "l"(pol) : "memory");
}
__device__ __forceinline__ void tma_ld_wo_w(uint32_t dst, const CUtensorMap* m, int col, int grp, uint32_t bar) {
  asm volatile(ELECT EXPECT("%2", "16384") "cp.async.bulk.tensor.5d.shared::cluster.global.mbarrier::complete_tx::bytes [%0], [%1, {%3, 0, 0, 0, %4}], [%2];\n"
               "@p cp.async.bulk.tensor.5d.shared::cluster.global.mbarrier::complete_tx::bytes [%5], [%1, {%6, 0, 0, 0, %4}], [%2];\n}"
               ::"r"(dst), "l"(m), "r"(bar), "r"(col), "r"(grp), "r"(dst + 8192), "r"(col + 64) : "memory");
}
__device__ __forceinline__ void mbar_arrive8_w(uint32_t bar) {
  asm volatile(ELECT "mbarrier.arrive.shared::cta.b64 _, [%0], 8;\n}" ::"r"(bar) : "memory");
}
__device__ __forceinline__ uint32_t peer(uint32_t a) { uint32_t r; asm("mapa.shared::cluster.u32 %0, %1, %2;" : "=r"(r) : "r"(a), "r"(~blockIdx.x & 1)); return r; }
__device__ __forceinline__ void tma_ld2_both_w(uint32_t dst, const CUtensorMap* m, int c0, int c1, uint32_t bar, uint32_t bytes) {
  asm volatile(ELECT EXPECT("%2", "%5") "cp.async.bulk.tensor.2d.shared::cluster.global.mbarrier::complete_tx::bytes.multicast::cluster"
               " [%0], [%1, {%3, %4}], [%2], %6;\n}"
               ::"r"(dst), "l"(m), "r"(bar), "r"(c0), "r"(c1), "r"(bytes), "h"((uint16_t)3) : "memory");
}
__device__ __forceinline__ void tma_ld2_both_hint_w(uint32_t dst, const CUtensorMap* m, int c0, int c1, uint32_t bar, uint32_t bytes, uint64_t pol) {
  asm volatile(ELECT EXPECT("%2", "%6") "cp.async.bulk.tensor.2d.shared::cluster.global.mbarrier::complete_tx::bytes.multicast::cluster.L2::cache_hint"
               " [%0], [%1, {%3, %4}], [%2], %7, %5;\n}"
               ::"r"(dst), "l"(m), "r"(bar), "r"(c0), "r"(c1), "l"(pol), "r"(bytes), "h"((uint16_t)3) : "memory");
}
__device__ __forceinline__ void bulk_commit() { asm volatile("cp.async.bulk.commit_group;" ::: "memory"); }
template <int N> __device__ __forceinline__ void bulk_wait_read() { asm volatile("cp.async.bulk.wait_group.read %0;" ::"n"(N) : "memory"); }
__device__ __forceinline__ void wg_fence() { asm volatile("wgmma.fence.sync.aligned;" ::: "memory"); }
__device__ __forceinline__ void wg_commit() { asm volatile("wgmma.commit_group.sync.aligned;" ::: "memory"); }
template <int N> __device__ __forceinline__ void wg_wait() { asm volatile("wgmma.wait_group.sync.aligned %0;" ::"n"(N) : "memory"); }
__device__ __forceinline__ void fence_async_smem() { asm volatile("fence.proxy.async.shared::cta;" ::: "memory"); }
__device__ __forceinline__ void bar_sync(int id, int n) { asm volatile("bar.sync %0, %1;" ::"r"(id), "r"(n) : "memory"); }
__device__ __forceinline__ void touch(float& a) { asm volatile("neg.f32 %0, %0;" : "+f"(a)); }
__device__ __forceinline__ void touch(uint32_t& a) { asm volatile("not.b32 %0, %0;" : "+r"(a)); }
template <typename T, int N> __device__ __forceinline__ void touch(T (&a)[N]) {
#pragma unroll
  for (int i = 0; i < N; i++) touch(a[i]);
}
template <int ID, typename... A> __device__ __forceinline__ void sched_fence(uint32_t x, A&... a) {
  if (!((SF >> ID) & 1)) return;
  asm volatile("" : "+r"(x)::"memory");
#pragma unroll 1
  for (; __builtin_expect(x >= 100 + ID, 0); x >>= 1) { (touch(a), ...); __nanosleep(x); }
}
template <int N> __device__ __forceinline__ void reg_fence(float (&a)[N]) {
#pragma unroll
  for (int i = 0; i < N; i++) asm volatile("" : "+f"(a[i])::"memory");
}
template <int N> __device__ __forceinline__ void reg_fence(uint32_t (&a)[N]) {
#pragma unroll
  for (int i = 0; i < N; i++) asm volatile("" : "+r"(a[i])::"memory");
}
__device__ __forceinline__ float ex2(float x) { float y; asm("ex2.approx.ftz.f32 %0, %1;" : "=f"(y) : "f"(x)); return y; }
__device__ __forceinline__ uint32_t pack_bf16(float lo, float hi) {
  uint32_t r; asm("cvt.rn.bf16x2.f32 %0, %1, %2;" : "=r"(r) : "f"(hi), "f"(lo)); return r;
}
__device__ __forceinline__ void stsm4(uint32_t a, uint32_t r0, uint32_t r1, uint32_t r2, uint32_t r3) {
  asm volatile("stmatrix.sync.aligned.m8n8.x4.shared.b16 [%0], {%1, %2, %3, %4};" ::"r"(a), "r"(r0), "r"(r1), "r"(r2), "r"(r3) : "memory");
}
__device__ __forceinline__ void stsm4t(uint32_t a, uint32_t r0, uint32_t r1, uint32_t r2, uint32_t r3) {
  asm volatile("stmatrix.sync.aligned.m8n8.x4.trans.shared.b16 [%0], {%1, %2, %3, %4};" ::"r"(a), "r"(r0), "r"(r1), "r"(r2), "r"(r3) : "memory");
}
__device__ __forceinline__ void ldsm4(uint32_t a, uint32_t& r0, uint32_t& r1, uint32_t& r2, uint32_t& r3) {
  asm volatile("ldmatrix.sync.aligned.m8n8.x4.shared.b16 {%0, %1, %2, %3}, [%4];" : "=r"(r0), "=r"(r1), "=r"(r2), "=r"(r3) : "r"(a) : "memory");
}
__device__ __forceinline__ void sts16(uint32_t a, uint32_t v) { asm volatile("st.shared.u16 [%0], %1;" ::"r"(a), "h"((uint16_t)v) : "memory"); }
__device__ __forceinline__ void mma16816(float& c0, float& c1, float& c2, float& c3, uint32_t a0, uint32_t a1, uint32_t a2, uint32_t a3,
                                         uint32_t b0, uint32_t b1) {
  asm volatile("mma.sync.aligned.m16n8k16.row.col.f32.bf16.bf16.f32 {%0, %1, %2, %3}, {%4, %5, %6, %7}, {%8, %9}, {%0, %1, %2, %3};"
               : "+f"(c0), "+f"(c1), "+f"(c2), "+f"(c3) : "r"(a0), "r"(a1), "r"(a2), "r"(a3), "r"(b0), "r"(b1));
}
__device__ __forceinline__ uint32_t sdesc(uint32_t addr, uint32_t lbo) { return (addr >> 4) + ((lbo >> 4) << 16); }
__device__ __forceinline__ uint64_t desc64(uint32_t lo, uint32_t hi) { uint64_t d; asm("mov.b64 %0, {%1, %2};" : "=l"(d) : "r"(lo), "r"(hi)); return d; }
__device__ __forceinline__ void dadd(uint64_t& d, uint32_t inc) {
  asm("{\n.reg .b32 l, h;\nmov.b64 {l, h}, %0;\nadd.u32 l, l, %1;\nmov.b64 %0, {l, h};\n}" : "+l"(d) : "r"(inc));
}

struct Ring {
  uint32_t slot, phase, xp;
  __device__ __forceinline__ void uniform() {
    slot = __shfl_sync(0xffffffffu, slot, 0); phase = __shfl_sync(0xffffffffu, phase, 0); xp = __shfl_sync(0xffffffffu, xp, 0);
  }
  __device__ __forceinline__ void next() { if (++slot == NS) { slot = 0; phase ^= 1; } }
  __device__ __forceinline__ void next_if(bool p) { slot += p; if (slot == NS) { slot = 0; phase ^= 1; } }
};
__device__ __forceinline__ uint32_t borrow(int ks, int n) {
  const int k = ks + 1;
  return k >= 4 && !(k & 2) && k < n ? k & 1 : 2;
}

constexpr uint32_t Q_RANGES = NBETA * NH + __builtin_popcount(EARLY_MASK) * 5, Q_ALL = NBETA * (NH + 5);
constexpr int NRANGE = NCTA / 5;
struct Work { int kind, mode, k0, nsteps, range, beta, sub; };
struct Sched { uint16_t queue[Q_ALL]; uint32_t piece[NRANGE + 1][4]; };
constexpr Sched make_sched() {
  Sched s{};
  int q = 0, a = 0;
  for (int t = 0, e = 0; a < NBETA * NH; t++) {
    for (; e < NBETA && 8 * (e & ~PAIRB) + PK <= t && a >= P_POS; e++)
      for (int col = 0; col < 5 && (EARLY_MASK >> e & 1); col++) s.queue[q++] = 0x8000 | (e & 1 ? 4 - col : col) << 8 | e;
    for (int b = 0; b < NBETA; b++)
      for (int h = 0; h < NH; h++)
        if ((b >= B_LATE && h >= H_LATE ? 300 + b : 8 * (b & ~PAIRB) + KG * (h >> 2)) == t) { s.queue[q++] = b << 5 | h; a++; }
  }
  for (int b = 0; b < NBETA; b++)
    for (int col = 0; col < 5 && !(EARLY_MASK >> b & 1); col++) s.queue[q++] = 0x8000 | col << 8 | b;
  constexpr uint32_t T[NRANGE * 2] = {PIECE_TABLE};
  for (int g = 0; g <= NRANGE; g++)
    for (int n = 0; n < 4; n++) s.piece[g][n] = g < NRANGE && n < 2 ? T[2 * g + n] : 2u << 30;
  return s;
}
__constant__ Sched c_sched = make_sched();
constexpr int N_EARLY = __builtin_popcount(EARLY_MASK);
constexpr bool reuse_ok() {
  const Sched s = make_sched();
  int first[NBETA + OR] = {};
  for (int q = Q_RANGES - 1; q >= 0; q--) if (!(s.queue[q] & 0x8000)) first[s.queue[q] >> 5] = q;
  for (int q = 0; q < Q_RANGES; q++) if ((s.queue[q] & 0x8000) && (s.queue[q] & 31) >= OR0 && q - first[(s.queue[q] & 31) + OR] > NCTA - 32) return false;
  return true;
}
static_assert(reuse_ok());
template <bool SIMPLE> __device__ __forceinline__ bool o_reuse(uint32_t b) { return !SIMPLE && b - (OR0 + OR) < N_EARLY - OR0; }
template <bool SIMPLE> __device__ __forceinline__ uint32_t o_slot(uint32_t b) { return o_reuse<SIMPLE>(b) ? OR0 + (b - OR0) % OR : b; }
__device__ __forceinline__ Work decode(uint32_t d) {
  Work w;
  w.kind = d >> 30; if (w.kind == 3) w.kind = 1;
  w.mode = (d >> 28) & 3; w.k0 = (d >> 22) & 63;
  if (w.kind == 0) { w.beta = (d >> 5) & 31; w.sub = d & 31; w.nsteps = DM / 64; }
  else { w.beta = d & 31; w.sub = (d >> 8) & 7; w.nsteps = ((d >> 16) & 63) + 1; }
  w.range = ((d >> 11) & 31) * 5 + w.sub;
  return w;
}

__device__ __forceinline__ bool reached(const unsigned* cnt, unsigned target) {
  unsigned v;
  asm volatile("ld.acquire.gpu.global.u32 %0, [%1];" : "=r"(v) : "l"(cnt) : "memory");
  return (int)(v - target) >= 0;
}
__device__ __forceinline__ void wait_count(const unsigned* cnt, unsigned target) {
  unsigned n = 0;
  while (!__all_sync(0xffffffffu, reached(cnt, target))) { if (++n > (1u << 24)) __trap(); }
}
__device__ __forceinline__ uint32_t lds(uint32_t a) { uint32_t v; asm volatile("ld.volatile.shared.u32 %0, [%1];" : "=r"(v) : "r"(a) : "memory"); return v; }

#define TRACE(u, e)
#define T3(u, e)
#define T2C(u, e)
#define T2P(u, r, e)
#define TTAIL(k)
#define TCLK(k)
#define TO -1
#define TRACE_O(k) if (TO == k) TRACE(i, 5)
#define TRACE_P(u, e)
#define TRACE_IN(u, e)

struct Ctx {
  uint32_t sb;
  int wg, warp;
  uint32_t mqk, mpv;
  bool lead;
  int lane0, lane;
  int src;
};
template <int N> __device__ __forceinline__ uint32_t dhi(uint32_t lo) { return 0x40000040u + (lo >> (26 + N)); }
__device__ __forceinline__ void release(const Ctx& c, uint32_t slot) {
  if (c.lead) mbar_arrive(c.sb + BAR_EMPTY + slot * 8);
}
__device__ __forceinline__ uint32_t acquire(const Ctx& c, Ring& r, bool have = false) {
  const uint32_t s = r.slot;
  if (!have) mbar_wait_w(c.sb + BAR_FULL + s * 8, r.phase);
  r.next();
  return s;
}
__device__ __forceinline__ void mbar_wait2_w(uint32_t b0, uint32_t p0, uint32_t b1, uint32_t p1) {
  uint32_t n = 0;
  while (!__all_sync(0xffffffffu, mbar_try(b0, p0) & mbar_try(b1, p1))) {
    if (++n > (1u << 22)) __trap();
  }
}
__device__ __forceinline__ void mbar_wait3_w(uint32_t b0, uint32_t p0, uint32_t b1, uint32_t p1, uint32_t b2, uint32_t p2) {
  uint32_t n = 0;
  while (!__all_sync(0xffffffffu, mbar_try(b0, p0) & mbar_try(b1, p1) & mbar_try(b2, p2))) {
    if (++n > (1u << 22)) __trap();
  }
}
__device__ __forceinline__ void acquire2(const Ctx& c, Ring& r, uint32_t& s0, uint32_t& s1, bool have = false) {
  const uint32_t p0 = r.phase;
  s0 = r.slot; r.next(); s1 = r.slot;
  if (!have) mbar_wait2_w(c.sb + BAR_FULL + s0 * 8, p0, c.sb + BAR_FULL + s1 * 8, r.phase);
  r.next();
}
template <int N>
__device__ __forceinline__ bool peek(const Ctx& c, Ring r) {
  bool ok = true;
#pragma unroll
  for (int k = 0; k < N; k++) { ok &= mbar_test(c.sb + BAR_FULL + r.slot * 8, r.phase); r.next(); }
  return ok;
}
__device__ __forceinline__ void staged(const Ctx& c, int part) {
  fence_async_smem();
  __syncwarp();
  mbar_arrive_warp(c.sb + BAR_STG + c.wg * 16 + part * 8);
}

template <int WG, bool FIRST, int H>
__device__ __forceinline__ void proj_half(const Ctx& c, float (&acc)[64], uint32_t w, uint32_t x, uint32_t sw) {
  uint64_t dx = desc64((SB0 + x * SLOT + (WG ? 0 : H * 8192)) >> 4, dhi<0>(x) + sw);
  uint64_t dw = desc64(WG ? (SB0 + w * SLOT + H * 8192) >> 4 : sdesc(SB0 + w * SLOT, 8192), dhi<1>(x));
  wg_fence();
  if (WG) { if (FIRST) wgmma_proj96_init(acc, dw, dx, 0); else wgmma_proj96(acc, dw, dx, 1); }
  else { if (FIRST) wgmma_proj_init(acc, dx, dw, 0); else wgmma_proj(acc, dx, dw, 1); }
#pragma unroll
  for (int k = 1; k < 4; k++) {
    dadd(dx, k == 2 ? 2 + (sw >> 30) * 28 : 2); dadd(dw, 128);
    if (WG) wgmma_proj96(acc, dw, dx, 1); else wgmma_proj(acc, dx, dw, 1);
  }
  wg_commit();
}

__device__ __forceinline__ void proj_store16(uint32_t a, const float* f, float sc) {
  stsm4t(a, pack_bf16(f[0] * sc, f[1] * sc), pack_bf16(f[2] * sc, f[3] * sc), pack_bf16(f[4] * sc, f[5] * sc), pack_bf16(f[6] * sc, f[7] * sc));
}

__device__ __forceinline__ uint32_t stage_off(const Ctx& c) {
  const int lane = c.lane, mi = lane >> 3, r8 = lane & 7;
  return ((mi >> 1) * 8 + r8) * 128 + (((2 * c.warp + (mi & 1)) ^ r8) << 4);
}
__device__ __forceinline__ uint32_t q3_swz(uint32_t r8) { return ((r8 & 3) << 1) | (r8 >> 2); }
template <int H>
__device__ __forceinline__ void stage_t2(const Ctx& c, const float (&a)[64], float sc) {
  const uint32_t base = c.sb + QBUF_OFF + 2 * 16384 + H * 8192 + stage_off(c);
#pragma unroll
  for (int jj = 0; jj < 4; jj++) proj_store16(base + jj * 2048, &a[jj * 8], sc);
}
template <int H, bool IS_Q>
__device__ __forceinline__ void stage_t3(const Ctx& c, const float (&a)[64], float sc) {
  const uint32_t off = stage_off(c), r8 = (off >> 7) & 7;
  const uint32_t t3 = c.sb + QBUF_OFF + 3 * 16384 + H * 4096 + (IS_Q ? off ^ ((r8 ^ q3_swz(r8)) << 4) : off);
  proj_store16(t3, &a[32], sc);
  proj_store16(t3 + 2048, &a[40], sc);
}

template <int WG, int h>
__device__ __forceinline__ void load_part(const Ctx& c, Ring r, uint32_t (&q)[32]) {
  uint32_t n = 0;
  while (!h && !__all_sync(0xffffffffu, peek<4>(c, r))) {
    if (++n > (1u << 26)) __trap();
  }
  const int lane = c.lane, mi = lane >> 3, r8 = lane & 7;
  if (WG) { r.next(); r.next(); }
  const uint32_t off = c.sb + (WG ? stage_off(c) : (16 * c.warp + (mi & 1) * 8 + r8) * 128), t0 = off + r.slot * SLOT;
  r.next();
  const uint32_t t1 = off + r.slot * SLOT;
#pragma unroll
    for (int jj = 0; jj < (WG ? 6 : 8); jj++) {
      uint32_t* p = &q[4 * jj];
      if (WG) asm volatile("ldmatrix.sync.aligned.m8n8.x4.trans.shared.b16 {%0, %1, %2, %3}, [%4];" : "=r"(p[0]), "=r"(p[1]), "=r"(p[2]), "=r"(p[3])
                           : "r"((jj < 4 ? t0 + h * 8192 : t1 + h * 4096) + (jj & 3) * 2048) : "memory");
      else ldsm4((h ? t1 : t0) + (jj >> 2) * 8192 + (((((2 * jj) & 7) + (mi >> 1)) ^ r8) << 4), p[0], p[1], p[2], p[3]);
    }
}
template <int WG>
__device__ __forceinline__ void add_part(const Ctx& c, const uint32_t (&q)[32], float (&a)[64]) {
  const uint32_t one = (c.lane >> 3) == (c.lane & 3) ? 0x3f80u << (c.lane & 4) * 4 : 0;
#pragma unroll
  for (int i = 0; i < (WG ? 12 : 16); i++)
    asm("mma.sync.aligned.m16n8k8.row.col.f32.bf16.bf16.f32 {%0, %1, %2, %3}, {%4, %5}, {%6}, {%0, %1, %2, %3};"
        : "+f"(a[4 * i]), "+f"(a[4 * i + 1]), "+f"(a[4 * i + 2]), "+f"(a[4 * i + 3]) : "r"(q[2 * i]), "r"(q[2 * i + 1]), "r"(one));
}

__device__ __forceinline__ void trace_dump(const Ctx& c) {
}
struct RowSum { float l0, l1; };
__device__ __forceinline__ const char* o_addr(uint32_t item, int row, int lane) {
  return reinterpret_cast<const char*>(g_o) + (((item >> 10) * (2 * SQ) + row) * 128 + (lane ^ (lane >> 3)) * 16);
}
__device__ __forceinline__ void o_stg(const char* p, int i, const uint32_t* q) {
  asm volatile("st.global.v4.b32 [%0], {%1, %2, %3, %4};"
               ::"l"(p + (i >> 1) * (SQ * 128) + (i & 1) * 512), "r"(q[0]), "r"(q[1]), "r"(q[2]), "r"(q[3]) : "memory");
}
template <int MODE, int I0 = 0, int NI = 4>
__device__ __forceinline__ void o_emit(const char* p, const float (&o)[64], float inv) {
#pragma unroll
  for (int i = I0; i < I0 + NI; i++) {
    uint32_t q[4];
#pragma unroll
    for (int j = 0; j < 4; j++) q[j] = pack_bf16(o[16 * i + 4 * j + 2 * MODE] * inv, o[16 * i + 4 * j + 2 * MODE + 1] * inv);
    o_stg(p, i, q);
  }
}
__device__ __forceinline__ void o_done(const Ctx& c) {
  __syncwarp();
  mbar_arrive_warp(c.sb + BAR_OUT);
  __syncwarp();
}
template <int WG>
__device__ __forceinline__ void o_first(const Ctx& c, uint32_t item, float (&o)[64], const RowSum& inv, uint32_t (&q)[32]) {
  const char* p = o_addr(item, WG ? 192 + 8 * c.warp : 64 + 16 * c.warp, c.lane);
  reg_fence(o);
#pragma unroll
  for (int j = 0; j < 16; j++) {
    if (WG) q[j] = pack_bf16((o[4 * j] + o[4 * j + 2]) * inv.l0, (o[4 * j + 1] + o[4 * j + 3]) * inv.l0);
    else q[j] = pack_bf16(o[4 * j] * inv.l0, o[4 * j + 1] * inv.l0);
    if (!WG && (j & 3) == 3 && (j >> 2) < 8 - LATE0) o_stg(p, j >> 2, q + j - 3);
  }
#pragma unroll
  for (int j = 0; j < 16; j++) {
    if (!WG) q[16 + j] = pack_bf16(o[4 * j + 2] * inv.l1, o[4 * j + 3] * inv.l1);
    if ((j & 3) == 3 && (j >> 2) < 4 - (WG ? LATE1 : LATE0)) o_stg(WG ? p : p + 1024, j >> 2, q + (WG ? 0 : 16) + j - 3);
  }
}
template <int WG>
__device__ __forceinline__ void o_rest(const Ctx& c, uint32_t item, uint32_t (&q)[32]) {
  const char* p = o_addr(item, WG ? 192 + 8 * c.warp : 64 + 16 * c.warp, c.lane);
#pragma unroll
  for (int i = WG ? 4 - LATE1 : 8 - LATE0; i < (WG ? 4 : 8); i++) o_stg(p + (i >> 2) * 1024, i & 3, q + 4 * i);
}
template <int K0, int K1>
__device__ __forceinline__ void o_piece(const Ctx& c, const char* p, int k, const float (&o)[64], const RowSum& inv) {
  constexpr int NI = 8 / O_STEPS, M = K0 * NI / 4;
  if constexpr (K1 - K0 == 1) {
    o_emit<M, K0 * NI % 4, NI>(p + M * 1024, o, M ? inv.l1 : inv.l0);
    if (K1 == O_STEPS) o_done(c);
  } else {
    if (k <= (K0 + K1) / 2) o_piece<K0, (K0 + K1) / 2>(c, p, k, o, inv); else o_piece<(K0 + K1) / 2, K1>(c, p, k, o, inv);
  }
}
template <int WG>
__device__ __forceinline__ void o_second(const Ctx& c, uint32_t item, int k, float (&o)[64], const RowSum& inv) {
  reg_fence(o);
  o_piece<0, O_STEPS>(c, o_addr(item, 128 * WG + 16 * c.warp, c.lane0 + (k >> 8)), k, o, inv);
}
template <int WG>
__device__ __forceinline__ void release_q(const Ctx& c) {
#pragma unroll
  for (int t = 0; t < 2; t++)
    if (c.lead) asm volatile("mbarrier.arrive.shared::cta.b64 _, [%0], 2;" ::"r"(c.sb + BAR_EMPTY + (NS + 2 * WG + t) * 8) : "memory");
  __syncwarp();
}
struct Slots { uint32_t w, x, o, po; };
template <int WG>
__device__ __forceinline__ void acc_fence(float (&a)[64]) {
#pragma unroll
  for (int i = 0; i < (WG ? 48 : 64); i++) asm volatile("" : "+f"(a[i])::"memory");
}
template <int WG>
__device__ __forceinline__ void begin_acquire(const Ctx& c, Ring& r, Slots& h, bool wait) {
  const uint32_t s0 = r.slot, p0 = r.phase, f = c.sb + BAR_FULL;
  r.next();
  const uint32_t p1 = r.phase;
  h.w = r.slot; r.next();
  h.x = WG ? r.slot : s0; h.o = WG ? s0 : r.slot; h.po = r.phase;
  if (wait) { if (WG) mbar_wait3_w(f + s0 * 8, p0, f + h.w * 8, p1, f + h.x * 8, r.phase); else mbar_wait2_w(f + s0 * 8, p0, f + h.w * 8, p1); }
  r.next();
}
template <int WG>
__device__ __forceinline__ void proj_begin(const Ctx& c, Ring& r, float (&a0)[64], Slots& h, bool wait, uint32_t sw) {
  begin_acquire<WG>(c, r, h, wait);
  proj_half<WG, true, 0>(c, a0, h.w, h.x, sw);
  if (WG) release(c, h.o);
}
template <int WG>
__device__ __forceinline__ void proj_main(Ctx& c, Ring& r, float (&a0)[64], float (&a1)[64], Slots& h, int n, uint32_t sw, int unit,
                                          uint32_t item, int nq, float (&o1)[64], const RowSum& inv) {
  constexpr bool DEEP = (PDEPTH >> WG) & 1;
  T2C(unit, 3);
  int ks = 1;
#pragma unroll 1
  do {
    const Slots p = h;
    const uint32_t b = borrow(ks, n), tile = NS + (WG ? 3 - b : b), f = c.sb + BAR_FULL;
    const uint32_t s0 = b != 2 ? tile : r.slot, p0 = b != 2 ? (r.xp >> b) & 1 : r.phase;
    r.next_if(b == 2);
    const uint32_t p1 = r.phase;
    h.w = r.slot; r.next();
    const uint32_t s2 = b != 2 ? tile : r.slot;
    h.po = b != 2 ? p0 : r.phase;
    r.next_if(b == 2);
    r.xp ^= 1 << b;
    h.x = WG ? s2 : s0; h.o = WG ? s0 : s2;
    mbar_wait3_w(f + s0 * 8, p0, f + h.w * 8, p1, f + (WG ? s2 : p.o) * 8, WG ? h.po : p.po);
    if (ks < 10) T2C(unit, ks * 4);
    if (DEEP) {
      proj_half<WG, false, 0>(c, a0, h.w, h.x, sw);
      release(c, WG ? h.o : p.o);
      if (ks < 10) T2C(unit, ks * 4 + 1);
      wg_wait<1>();
      if (ks < 10) T2C(unit, ks * 4 + 2);
      release(c, p.x); release(c, p.w);
    } else {
      release(c, WG ? h.o : p.o);
      wg_wait<0>();
      release(c, p.x); release(c, p.w);
      if (ks < 10) T2C(unit, ks * 4 + 1);
      proj_half<WG, false, 0>(c, a0, h.w, h.x, sw);
      if (ks < 10) T2C(unit, ks * 4 + 2);
    }
    proj_half<WG, false, 1>(c, a1, h.w, h.x, sw);
    if (ks < 10) T2C(unit, ks * 4 + 3);
    if (ks <= nq) o_second<WG>(c, item, ks, o1, inv);
  } while (++ks != n);
  {
    const uint32_t e0 = c.sb + BAR_EMPTY + (NS + 3 * WG) * 8, e1 = c.sb + BAR_EMPTY + (NS + 1 + WG) * 8;
    const uint32_t p0 = (r.xp ^ unit ^ 1) & 1, p1 = ((r.xp >> 1) ^ unit ^ 1) & 1;
    const uint32_t k0 = sw ? e0 : c.sb + BAR_FULL + r.slot * 8, pk = sw ? p0 : r.phase;
    uint32_t cnt = 0;
    while (!__all_sync(0xffffffffu, mbar_try(e0, p0) & mbar_try(e1, p1) & mbar_try(k0, pk) & (WG || mbar_try(c.sb + BAR_FULL + h.o * 8, h.po)))) {
      if (++cnt > (1u << 22)) __trap();
    }
  }
  c.lane = c.lane0 + (h.w >> 5);
  if (!WG) release(c, h.o);
}
template <int WG>
__device__ __forceinline__ void proj_end(const Ctx& c, float (&a1)[64], const Slots& h) {
  wg_wait<0>();
  acc_fence<WG>(a1);
  release(c, h.x); release(c, h.w);
}
__device__ __forceinline__ uint32_t get_desc(const Ctx& c, int i) {
  uint32_t d;
  mbar_wait_w(c.sb + BAR_DESC, (i - 1) & 1);
  asm volatile("ld.volatile.shared.u32 %0, [%1];" : "=r"(d) : "r"(c.sb + DESC_OFF + (i & 3) * 4) : "memory");
  return __shfl_sync(0xffffffffu, d, 0);
}

__device__ __forceinline__ float quad_max(float x) {
  x = fmaxf(x, __shfl_xor_sync(0xffffffffu, x, 1));
  return fmaxf(x, __shfl_xor_sync(0xffffffffu, x, 2));
}
__device__ __forceinline__ float quad_sum(float x) {
  x += __shfl_xor_sync(0xffffffffu, x, 1);
  return x + __shfl_xor_sync(0xffffffffu, x, 2);
}
template <bool SP, bool FIRST>
__device__ __forceinline__ void exps(const Ctx& c, const float (&s)[32], uint32_t (&p)[SP ? 8 : 16], RowSum& st) {
  if constexpr (SP) {
    uint32_t q[8];
    float t;
#pragma unroll
    for (int j = 0; j < 8; j++) {
      const float e0 = ex2(s[4 * j] + s[4 * j + 2]), e1 = ex2(s[4 * j + 1] + s[4 * j + 3]);
      if (j == 0) t = e0 + e1; else t += e0 + e1;
      q[j] = pack_bf16(e0, e1);
    }
    const bool odd = c.src & 2;
#pragma unroll
    for (int g = 0; g < 4; g++) {
      p[2 * g] = __shfl_sync(0xffffffffu, odd ? q[2 * g + 1] : q[2 * g], c.src);
      p[2 * g + 1] = __shfl_sync(0xffffffffu, odd ? q[2 * g] : q[2 * g + 1], c.src ^ 1);
    }
    st.l0 = FIRST ? t : st.l0 + t;
  } else {
    float t0, t1;
#pragma unroll
    for (int j = 0; j < 8; j++) {
      const float e0 = ex2(s[4 * j]), e1 = ex2(s[4 * j + 1]), e2 = ex2(s[4 * j + 2]), e3 = ex2(s[4 * j + 3]);
      if (j == 0) { t0 = e0 + e1; t1 = e2 + e3; } else { t0 += e0 + e1; t1 += e2 + e3; }
      p[2 * j] = pack_bf16(e0, e1);
      p[2 * j + 1] = pack_bf16(e2, e3);
    }
    st.l0 = FIRST ? t0 : st.l0 + t0;
    st.l1 = FIRST ? t1 : st.l1 + t1;
  }
}
template <bool SP>
__device__ __forceinline__ bool finish_sums(RowSum& st) {
  const float a = quad_sum(st.l0), b = SP ? a : quad_sum(st.l1);
  st.l0 = __fdividef(1.f, a); st.l1 = __fdividef(1.f, b);
  return !(a >= SUM_LO && a <= SUM_HI && b >= SUM_LO && b <= SUM_HI);
}
template <bool SP, bool INIT, int SITE, bool COMMIT = true, int RM = 0>
__device__ __forceinline__ void issue_qk(const Ctx& c, float (&s)[32], const uint32_t (&qs)[32], uint32_t dq, uint32_t dk) {
  uint64_t a = desc64(dq, dhi<SITE & 1>(dk)), b = desc64(dk, dhi<1 - (SITE & 1)>(dk));
  if (SP) {
    if (INIT) wgmma_qk_sp_init(s, qs[0], qs[1], qs[2], qs[3], b, 0, c.mqk); else wgmma_qk_sp(s, qs[0], qs[1], qs[2], qs[3], b, 0, c.mqk);
#pragma unroll
    for (int k = 1; k < 4; k++) { dadd(b, k == 2 ? 508 : 4); wgmma_qk_sp(s, qs[4 * k], qs[4 * k + 1], qs[4 * k + 2], qs[4 * k + 3], b, 1, c.mqk); }
  } else {
    if (RM & 1) wgmma_qk_rs(s, qs[0], qs[1], qs[2], qs[3], b, 0); else if (INIT) wgmma_qk_init(s, a, b, 0); else wgmma_qk(s, a, b, 0);
#pragma unroll
    for (int k = 1; k < 8; k++) {
      dadd(a, k == 4 ? 506 : 2); dadd(b, k == 4 ? 506 : 2);
      if (RM >> k & 1) wgmma_qk_rs(s, qs[4 * k], qs[4 * k + 1], qs[4 * k + 2], qs[4 * k + 3], b, 1); else wgmma_qk(s, a, b, 1);
    }
  }
  if (COMMIT) wg_commit();
}
template <bool SP, bool ACC, int SITE, bool SPLIT = false>
__device__ __forceinline__ void issue_pv(const Ctx& c, float (&o)[64], const uint32_t (&p)[SP ? 8 : 16], uint32_t dv) {
  uint64_t b = desc64(dv, dhi<SITE & 1>(dv));
  if constexpr (SP) {
    if (ACC) wgmma_pv_sp(o, p[0], p[1], p[2], p[3], b, 1, c.mpv); else wgmma_pv_sp_init(o, p[0], p[1], p[2], p[3], b, 0, c.mpv);
    if (SPLIT) wg_commit();
    dadd(b, 256);
    wgmma_pv_sp(o, p[4], p[5], p[6], p[7], b, 1, c.mpv);
  } else {
    if (ACC) wgmma_pv(o, p[0], p[1], p[2], p[3], b, 1); else wgmma_pv_init(o, p[0], p[1], p[2], p[3], b, 0);
#pragma unroll
    for (int k = 1; k < 4; k++) { dadd(b, 128); wgmma_pv(o, p[4 * k], p[4 * k + 1], p[4 * k + 2], p[4 * k + 3], b, 1); }
  }
  wg_commit();
}
__device__ __forceinline__ void pack_rows(const float (&o)[64], float sc, uint32_t (&q)[32]) {
#pragma unroll
  for (int j = 0; j < 32; j++) q[j] = pack_bf16(o[2 * j] * sc, o[2 * j + 1] * sc);
}
template <int MASK = 255>
__device__ __forceinline__ void stage_rows(const Ctx& c, uint32_t tile_addr, const uint32_t (&q)[32]) {
  const int lane = c.lane, mi = lane >> 3, r8 = lane & 7;
  const uint32_t row_addr = tile_addr + (16 * c.warp + (mi & 1) * 8 + r8) * 128;
#pragma unroll
  for (int jj = 0; jj < 8; jj++)
    if (MASK >> jj & 1) stsm4(row_addr + (jj >> 2) * 8192 + (((((2 * jj) & 7) + (mi >> 1)) ^ r8) << 4), q[4 * jj], q[4 * jj + 1], q[4 * jj + 2], q[4 * jj + 3]);
}
__device__ __forceinline__ void stage_rows(const Ctx& c, uint32_t tile_addr, const float (&o)[64], float sc) {
  uint32_t q[32];
  pack_rows(o, sc, q);
  stage_rows(c, tile_addr, q);
}
template <int WG, int H>
__device__ __forceinline__ void stage_out(const Ctx& c, const float (&a)[64]) {
  if (WG) { stage_t3<H, false>(c, a, 1.f); if (H) staged(c, 0); stage_t2<H>(c, a, 1.f); }
  else stage_rows(c, c.sb + QBUF_OFF + H * 16384, a, 1.f);
  if (H || !WG) staged(c, H);
}
template <int SITE>
__device__ __forceinline__ void issue_qk_rs(float (&s)[32], uint32_t (&q)[32], uint32_t dk) {
  uint64_t b = desc64(dk, dhi<SITE>(dk));
  reg_fence(q);
  wg_fence();
  wgmma_qk_rs_init(s, q[0], q[1], q[2], q[3], b, 0);
#pragma unroll
  for (int k = 1; k < 8; k++) {
    if (SITE && k == LAGK) asm volatile("bar.arrive 1, 256;" ::: "memory");
    dadd(b, k == 4 ? 506 : 2); wgmma_qk_rs(s, q[4 * k], q[4 * k + 1], q[4 * k + 2], q[4 * k + 3], b, 1);
  }
  wg_commit();
  if (SITE && LAGK == 8) asm volatile("bar.arrive 1, 256;" ::: "memory");
}

__device__ __forceinline__ void redo_tile(const Ctx& c, uint32_t q_addr, uint32_t half, const __nv_bfloat16* kp, const __nv_bfloat16* vp,
                                          uint32_t item, int row) {
  float o[64];
  const int lane = lane_now(), g = lane >> 2, cc = lane & 3, mi = lane >> 3, r8 = lane & 7;
  const uint32_t qa = q_addr + (half == 4096 ? 8 * c.warp + r8 : 16 * c.warp + (mi & 1) * 8 + r8) * 128, swz = half == 4096 ? q3_swz(r8) : r8;
  const uint32_t* kq = reinterpret_cast<const uint32_t*>(kp + g * DH) + cc;
  const unsigned short* vq = reinterpret_cast<const unsigned short*>(vp + 2 * cc * DH) + g;
  float m0 = -INFINITY, m1 = -INFINITY, l0 = 0.f, l1 = 0.f;
#pragma unroll
  for (int i = 0; i < 64; i++) o[i] = 0.f;
#pragma unroll 1
  for (int kb = 0; kb < SK / 16; kb++) {
    float z[8] = {0.f, 0.f, 0.f, 0.f, 0.f, 0.f, 0.f, 0.f};
#pragma unroll 2
    for (int kk = 0; kk < 8; kk++) {
      uint32_t a0, a1, a2, a3;
      ldsm4(qa + (kk >> 2) * half + ((((kk & 3) * 2 + (mi >> 1)) ^ swz) << 4), a0, a1, a2, a3);
      const uint32_t* kr = kq + kb * (16 * DH / 2) + kk * 8;
      mma16816(z[0], z[1], z[2], z[3], a0, a1, a2, a3, __ldg(kr), __ldg(kr + 4));
      mma16816(z[4], z[5], z[6], z[7], a0, a1, a2, a3, __ldg(kr + 8 * DH / 2), __ldg(kr + 8 * DH / 2 + 4));
    }
    const float n0 = fmaxf(m0, quad_max(fmaxf(fmaxf(z[0], z[1]), fmaxf(z[4], z[5]))));
    const float n1 = fmaxf(m1, quad_max(fmaxf(fmaxf(z[2], z[3]), fmaxf(z[6], z[7]))));
    const float al0 = ex2(m0 - n0), al1 = ex2(m1 - n1);
    m0 = n0; m1 = n1;
#pragma unroll
    for (int i = 0; i < 8; i++) z[i] = ex2(z[i] - ((i & 2) ? n1 : n0));
    l0 = l0 * al0 + (z[0] + z[1]) + (z[4] + z[5]);
    l1 = l1 * al1 + (z[2] + z[3]) + (z[6] + z[7]);
    const uint32_t a0 = pack_bf16(z[0], z[1]), a1 = pack_bf16(z[2], z[3]), a2 = pack_bf16(z[4], z[5]), a3 = pack_bf16(z[6], z[7]);
    const unsigned short* vr = vq + kb * (16 * DH);
#pragma unroll
    for (int nb = 0; nb < 16; nb++) {
      o[4 * nb] *= al0; o[4 * nb + 1] *= al0; o[4 * nb + 2] *= al1; o[4 * nb + 3] *= al1;
      const uint32_t b0 = __ldg(vr + nb * 8) | ((uint32_t)__ldg(vr + nb * 8 + DH) << 16);
      const uint32_t b1 = __ldg(vr + nb * 8 + 8 * DH) | ((uint32_t)__ldg(vr + nb * 8 + 9 * DH) << 16);
      mma16816(o[4 * nb], o[4 * nb + 1], o[4 * nb + 2], o[4 * nb + 3], a0, a1, a2, a3, b0, b1);
    }
  }
  const char* p = o_addr(item, row, lane);
  o_emit<0>(p, o, __fdividef(1.f, quad_sum(l0)));
  o_emit<1>(half == 4096 ? p : p + 1024, o, __fdividef(1.f, quad_sum(l1)));
}

template <bool SPA, bool SPB, int SITE, int ID>
__device__ __forceinline__ void batch(const Ctx& c, float (&s)[32], const uint32_t (&qs)[32], uint32_t dq, uint32_t dk, float (&ob)[64],
                                      uint32_t (&pb)[SPB ? 8 : 16], uint32_t dv) {
  if constexpr (SPA) {
    reg_fence(pb);
    wg_fence();
    issue_pv<SPB, true, ID>(c, ob, pb, dv);
    issue_qk<SPA, false, ID>(c, s, qs, dq, dk);
  } else {
    constexpr bool EARLY = ((QK_EARLY_MASK >> (SITE + (SPB ? 2 : 0))) & 1) != 0;
    if (!EARLY) reg_fence(pb);
    wg_fence();
    issue_qk<SPA, false, ID, !SPB, SITE ? RM0 : SPB ? RM2 : RM1>(c, s, qs, dq, dk);
    if (EARLY) { reg_fence(pb); wg_fence(); }
    issue_pv<SPB, true, ID, SPB>(c, ob, pb, dv);
  }
}

template <bool SP0>
__device__ __forceinline__ bool attention(Ctx& c, Ring& r, int unit, uint32_t& d, const float (&a0)[64], float (&o0)[64], float (&o1)[64],
                                          RowSum& st0, RowSum& st1, const Slots& h, uint32_t (&q1)[32]) {
  constexpr bool SP1 = false;
  if (SP0) { c.mqk = META_QK + (d >> 28); c.mpv = META_PV + (d >> 28); asm volatile("" : "+r"(c.mqk), "+r"(c.mpv)); }
  if (SP0) c.src = (c.lane & 28) | ((c.lane & 1) << 1) | ((c.lane >> 1) & 1);
  float s[32];
  uint32_t p0[SP0 ? 8 : 16], p1[16];
  const uint32_t q0a = c.sb + QBUF_OFF + (SP0 ? 3 : 0) * 16384, q1a = c.sb + QBUF_OFF + (SP0 ? 2 : 1) * 16384;
  const uint32_t dq0 = sdesc(SB0 + QBUF_OFF, 0), dq1 = sdesc(SB0 + QBUF_OFF + (SP0 ? 2 : 1) * 16384, 0);
  uint32_t sk = acquire(c, r, true), sv, sn;
  uint32_t qs[32];
  float s1[32];
  if (SP0) {
    stage_t3<0, true>(c, a0, SM_C);
    stage_t2<0>(c, a0, SM_C);
    proj_end<1>(c, o0, h);
    stage_t3<1, true>(c, o0, SM_C);
    stage_t2<1>(c, o0, SM_C);
    bar_sync(5, 128);
    const int g = c.lane >> 2, cc = c.lane & 3;
    const uint32_t qa = q0a + (8 * c.warp + g) * 128 + (cc & 1) * 8;
#pragma unroll
    for (int k = 0; k < 8; k++)
      asm volatile("ld.shared.v2.u32 {%0, %1}, [%2];" : "=r"(qs[2 * k]), "=r"(qs[2 * k + 1])
                   : "r"(qa + (k >> 2) * 4096 + ((((k & 3) * 2 + (cc >> 1)) ^ q3_swz(g)) << 4)) : "memory");
    fence_async_smem();
    bar_sync(1, 256);
    TRACE(unit, 2);
    wg_fence();
    issue_qk<SP1, true, 1>(c, s1, qs, dq1, sdesc(SB0 + sk * SLOT, 0));
#pragma unroll
    for (int k = 0; k < 8; k++)
      if (RM2 >> k & 1) ldsm4(q1a + (k >> 2) * 8192 + (16 * c.warp + (c.lane & 15)) * 128 + (((2 * (k & 3) + (c.lane >> 4)) ^ (c.lane & 7)) << 4),
                              q1[4 * k], q1[4 * k + 1], q1[4 * k + 2], q1[4 * k + 3]);
#pragma unroll
    for (int k = 0; k < 16; k++) asm volatile("" : "+r"(qs[k])::"memory");
    wg_fence();
    issue_qk<SP0, true, 0>(c, s, qs, dq0, sdesc(SB0 + sk * SLOT, 0));
    const bool have = peek<2>(c, r);
    wg_wait<1>();
    reg_fence(s1);
    exps<SP1, true>(c, s1, p1, st1);
    sched_fence<11>(sk, p1);
    acquire2(c, r, sv, sn, __all_sync(0xffffffffu, have));
    wg_wait<0>();
    wg_fence();
    issue_pv<SP1, false, 1>(c, o1, p1, sdesc(SB0 + sv * SLOT, 8192));
    if (LAG_BAR & 1) asm volatile("bar.arrive 4, 256;" ::: "memory");
    sched_fence<12>(sk, s);
    release(c, sk);
    sk = sn;
    exps<SP0, true>(c, s, p0, st0);
    reg_fence(p0);
    wg_fence();
    issue_pv<SP0, false, 0>(c, o0, p0, sdesc(SB0 + sv * SLOT, 8192));
    issue_qk<SP0, true, 2>(c, s, qs, dq0, sdesc(SB0 + sk * SLOT, 0));
    sn = acquire(c, r);
    wg_wait<0>();
    reg_fence(s);
  } else {
    pack_rows(a0, SM_C, qs);
    stage_rows(c, q0a, qs);
    proj_end<0>(c, o1, h);
    TRACE(unit, 2);
    float sc = SM_C;
    if (PACK1 < 8) {
#pragma unroll
      for (int j = 0; j < 4 * PACK1; j++) q1[j] = pack_bf16(o1[2 * j] * SM_C, o1[2 * j + 1] * SM_C);
      if (PACK1) sched_fence<3>(sk, q1[4 * PACK1 - 1]);
      issue_qk_rs<0>(s, qs, sdesc(SB0 + sk * SLOT, 0));
      sched_fence<0>(sk, sc);
#pragma unroll
      for (int j = 4 * PACK1; j < 32; j++) q1[j] = pack_bf16(o1[2 * j] * sc, o1[2 * j + 1] * sc);
      stage_rows<~RM1>(c, q1a, q1);
    } else {
      pack_rows(o1, sc, q1);
      if (PACK1 == 8) stage_rows<~RM1>(c, q1a, q1);
      sched_fence<0>(sk, q1);
      issue_qk_rs<0>(s, qs, sdesc(SB0 + sk * SLOT, 0));
      if (PACK1 == 9) stage_rows<~RM1>(c, q1a, q1);
    }
    issue_qk_rs<1>(s1, q1, sdesc(SB0 + sk * SLOT, 0));
    bool have = peek<2>(c, r);
    wg_wait<1>();
    reg_fence(s);
    exps<SP0, true>(c, s, p0, st0);
    sched_fence<1>(sk, p0);
    acquire2(c, r, sv, sn, __all_sync(0xffffffffu, have));
    wg_wait<0>();
    reg_fence(s1);
    fence_async_smem();
    __syncwarp();
    wg_fence();
    issue_qk<SP0, false, 2, true, RM0>(c, s, qs, dq0, sdesc(SB0 + sn * SLOT, 0));
    issue_pv<SP0, false, 0>(c, o0, p0, sdesc(SB0 + sv * SLOT, 8192));
    sched_fence<2>(sk, s1);
    release(c, sk);
    have = peek<1>(c, r);
    sk = sn;
    exps<SP1, true>(c, s1, p1, st1);
    reg_fence(p1);
    wg_fence();
    issue_pv<SP1, false, 1>(c, o1, p1, sdesc(SB0 + sv * SLOT, 8192));
    sn = acquire(c, r, __all_sync(0xffffffffu, have));
    if (LAG_BAR & 1) bar_sync(4, 256);
    wg_wait<1>();
    reg_fence(s);
  }
  TRACE_IN(unit, 4);
  T2C(unit, 51);
#pragma unroll 1
  for (int j = 1; j < 15; j++) {
    const uint32_t sv_prev = sv, sk_prev = sk;
    sv = sn;
    const uint32_t dv = sdesc(SB0 + sv * SLOT, 8192);
    reg_fence(p0);
    exps<SP0, false>(c, s, p0, st0);
    batch<SP1, SP0, 0, 3>(c, s, q1, dq1, sdesc(SB0 + sk * SLOT, 0), o0, p0, dv);
    sk = acquire(c, r);
    wg_wait<1>();
    reg_fence(s); reg_fence(p1);
    release(c, sv_prev); release(c, sk_prev);
    exps<SP1, false>(c, s, p1, st1);
    batch<SP0, SP1, 1, 4>(c, s, qs, dq0, sdesc(SB0 + sk * SLOT, 0), o1, p1, dv);
    sn = acquire(c, r);
    if (SP0) wg_wait<0>(); else wg_wait<1>();
    reg_fence(s);
  }
  TRACE_IN(unit, 5);
  T2C(unit + 1, 52);
  const uint32_t sv_prev = sv;
  sv = sn;
  const uint32_t dv = sdesc(SB0 + sv * SLOT, 8192);
  reg_fence(p0);
  exps<SP0, false>(c, s, p0, st0);
  batch<SP1, SP0, 0, 5>(c, s, q1, dq1, sdesc(SB0 + sk * SLOT, 0), o0, p0, dv);
  asm volatile("ld.volatile.shared.u32 %0, [%1];" : "=r"(d) : "r"(c.sb + DESC_OFF + ((unit + 1) & 3) * 4) : "memory");
  const bool have = peek<2 + SP0>(c, r);
  wg_wait<1>();
  reg_fence(s); reg_fence(p1);
  release(c, sv_prev); release(c, sk);
  exps<SP1, false>(c, s, p1, st1);
  reg_fence(p1);
  wg_fence();
  issue_pv<SP1, true, 2>(c, o1, p1, dv);
  if (SP0) sched_fence<6>(sk, st0.l0, st1.l0, st1.l1); else sched_fence<5>(sk, st0.l0, st0.l1, st1.l0, st1.l1);
  c.lane = c.lane0 + (sk >> 5);
  const bool bad = finish_sums<SP0>(st0) | finish_sums<SP1>(st1);
  uint32_t any;
  asm volatile("{\n.reg .pred p, q;\nsetp.ne.u32 p, %1, 0;\nbar.red.or.pred q, %2, 128, p;\nselp.u32 %0, 1, 0, q;\n}"
               : "=r"(any) : "r"((uint32_t)bad), "n"(2 + SP0) : "memory");
  any = __any_sync(0xffffffffu, any);
  d = __shfl_sync(0xffffffffu, d, 0);
  if (d < (2u << 30) && !__all_sync(0xffffffffu, have)) { Ring t = r; Slots u; begin_acquire<SP0>(c, t, u, true); }
  wg_wait<0>();
  reg_fence(o0); reg_fence(o1);
  release(c, sv);
  return any;
}

template <int WG>
__device__ __forceinline__ void consumer(Ctx c, const __nv_bfloat16* const* kv) {
  asm volatile("setmaxnreg.inc.sync.aligned.u32 %0;" ::"n"(WG ? REG_C : 504 - REG_C - REG_P));
  c.wg = WG;
  Ring r{0, 0, 0};
  float a0[64], a1[64], o1[64];
  Slots h;
  RowSum inv0, inv1;
  uint32_t oq[32];
  uint32_t d = c_sched.queue[blockIdx.x] * 1025, dc = 0, sw;
  int i = 0, nq;
begin:
  sw = d & (1u << 30);
  proj_begin<WG>(c, r, a0, h, true, sw);
  proj_half<WG, true, 1>(c, a1, h.w, h.x, sw);
  nq = 0;
#pragma unroll
  for (int k = 0; k < 64; k++) asm volatile("" : "=f"(o1[k]));
  asm volatile("" : "=f"(inv1.l0), "=f"(inv1.l1));
  while (true) {
    TRACE(i, 0); TRACE(i, 6);
    proj_main<WG>(c, r, a0, a1, h, d >> 30 ? ((d >> 16) & 63) + 1 : DM / 64, sw, i, dc, nq, o1, inv1);
    dc = d;
    TRACE(i, 1);
    if (d >> 30) goto out_tile;
    wg_wait<1>();
    acc_fence<WG>(a0);
    if (WG ? attention<WG>(c, r, i, d, a0, a1, o1, inv0, inv1, h, oq) : attention<WG>(c, r, i, d, a0, o1, a1, inv1, inv0, h, oq)) goto redo;
    if (d >= (2u << 30)) break;
    sw = d & (1u << 30);
    proj_begin<WG>(c, r, a0, h, false, sw);
    release_q<WG>(c);
    if (WG) sched_fence<8>(h.w, inv0.l0); else sched_fence<7>(h.w, inv0.l0, inv0.l1);
    o_first<WG>(c, dc, a1, inv0, oq);
    sched_fence<9>(h.w, inv1.l0);
    proj_half<WG, true, 1>(c, a1, h.w, h.x, sw);
    o_rest<WG>(c, dc, oq);
    nq = O_STEPS;
    TRACE(i, 3); TRACE(i, 7);
    i++;
  }
  release_q<WG>(c);
  o_first<WG>(c, dc, a1, inv0, oq);
  o_rest<WG>(c, dc, oq);
#pragma unroll
  for (int k = 1; k <= O_STEPS; k++) o_second<WG>(c, dc, k, o1, inv1);
next:
  TRACE(i, 3); TRACE(i, 7);
  if ((d >> 30) != 2) {
    i++;
    r.uniform();
    goto begin;
  }
  trace_dump(c);
  return;
out_tile:
  if (d & 96) goto finish;
  d = get_desc(c, i + 1);
  wg_wait<1>();
  acc_fence<WG>(a0);
  TRACE_O(0);
  stage_out<WG, 0>(c, a0);
  TRACE_O(1);
  proj_end<WG>(c, a1, h);
  TRACE_O(2);
  stage_out<WG, 1>(c, a1);
  TRACE(i, 2);
  goto next;
finish:
  {
    uint32_t q[32];
#pragma unroll 1
    for (int k = (d >> 5) & 3; k > 1; k--) {
      wg_wait<0>();
      acc_fence<WG>(a0); acc_fence<WG>(a1);
      if (k == ((d >> 5) & 3)) { release(c, h.x); release(c, h.w); }
      load_part<WG, 0>(c, r, q); add_part<WG>(c, q, a0);
      load_part<WG, 1>(c, r, q); add_part<WG>(c, q, a1);
#pragma unroll
      for (int t = 0; t < 4; t++) { release(c, r.slot); r.next(); }
    }
    load_part<WG, 0>(c, r, q);
    wg_wait<1>();
    acc_fence<WG>(a0);
    TRACE_O(0);
    add_part<WG>(c, q, a0);
    stage_out<WG, 0>(c, a0);
    TRACE_O(1);
    load_part<WG, 1>(c, r, q);
    wg_wait<0>();
    acc_fence<WG>(a1);
    TRACE_O(2);
    add_part<WG>(c, q, a1);
    stage_out<WG, 1>(c, a1);
    TRACE(i, 2); TRACE(i, 3); TRACE(i, 7);
    trace_dump(c);
    return;
  }
redo:
  {
    if (!WG) { stage_rows<RM1>(c, c.sb + QBUF_OFF + 16384, oq); __syncwarp(); }
    const size_t hoff = (size_t)(dc & 511) * (SK * DH);
    const int br = (dc >> 9) & 1;
#pragma unroll 1
    for (int part = 0; part < 2; part++) {
      const int t = WG ? 3 - part : part;
      redo_tile(c, c.sb + QBUF_OFF + t * 16384, t == 3 ? 4096 : 8192, kv[br] + hoff, kv[2 + br] + hoff, dc,
                t * 64 + (t == 3 ? 8 : 16) * c.warp);
    }
    o_done(c);
    release_q<WG>(c);
  }
  goto next;
}

template <bool SIMPLE>
__global__ void __launch_bounds__(384, 1) mha_fused_kernel(const __grid_constant__ Params P) {
  extern __shared__ __align__(1024) uint8_t smem_raw[];
  const uint32_t sbase = smem_u32(smem_raw);
  const int tid = threadIdx.x;
  const int wg = __shfl_sync(0xffffffffu, tid >> 7, 0);
  const int warp = __shfl_sync(0xffffffffu, (tid >> 5) & 3, 0);
  const int lane = tid & 31;
  const int cta = blockIdx.x;
  constexpr bool PAIR = !SIMPLE && CLUSTER;

  if (tid == 0) T3(15, 0);
  if ((sbase & 0xffffff) != SB0) __trap();
  {
    const int wi = wg * 4 + warp;
    asm volatile(ELECT "prefetch.tensormap [%0];\n}" ::"l"(&P.x[0][0] + wi) : "memory");
#pragma unroll
    for (int k = 0; k < 5; k++) {
      const int b = min(BAR_OFF + (wi * 5 + k) * 8, DESC_OFF - 8);
      asm volatile(ELECT "mbarrier.init.shared::cta.b64 [%0], %1;\n}"
                   ::"r"(sbase + b), "r"(b < BAR_EMPTY || b >= BAR_DESC ? 1 : b >= BAR_STG && b < BAR_OUT ? 4 : 8) : "memory");
    }
    asm volatile("fence.mbarrier_init.release.cluster;" ::: "memory");
    if (wi < 6) asm volatile(ELECT "prefetch.tensormap [%0];\n}" ::"l"(&P.x[0][0] + 12 + wi) : "memory");
  }
  if (PAIR) asm volatile("barrier.cluster.arrive.aligned;\nbarrier.cluster.wait.aligned;" ::: "memory"); else __syncthreads();

  if (wg == 2) {
    asm volatile("setmaxnreg.dec.sync.aligned.u32 %0;" ::"n"(REG_P));
    if (warp == 1) {
      const uint32_t qb = sbase + QBUF_OFF;
      const uint32_t ep = __shfl_sync(0xffffffffu, *(volatile unsigned*)&g_epoch + 1, 0);
      asm volatile("st.volatile.shared.u32 [%0], %1;" ::"r"(sbase + EPOCH_OFF), "r"(ep) : "memory");
      uint32_t dc = c_sched.queue[cta], qi = 0, piece = 0, na = 0;
      TTAIL(0);
      for (int i = 0; (dc >> 30) != 2; i++) {
        if (!(dc >> 30) && o_reuse<SIMPLE>((dc >> 5) & 31)) {
          const unsigned* rd = &g_rd[0][0] + ((dc & 1023) >> 2) - OR * 8;
          for (uint32_t n = 0; !__all_sync(0xffffffffu, reached(rd, ep * 5)); __nanosleep(300)) if (++n > (1u << 22)) __trap();
        }
        mbar_wait_w(sbase + BAR_GO, i & 1);
        if (piece == 0) {
          if (PAIR && (cta & 1)) {
            asm volatile(ELECT EXPECT("%0", "4") "mbarrier.arrive.shared::cluster.b64 _, [%1];\n}" ::"r"(sbase + BAR_MAIL), "r"(peer(sbase + BAR_MAIL)) : "memory");
            mbar_wait_w(sbase + BAR_MAIL, i & 1);
            qi = lds(sbase + EPOCH_OFF + 8);
          } else if (lane == 0) {
            qi = atomicAdd(&g_next, PAIR ? 2 : 1);
            if (qi == (SIMPLE ? Q_ALL : Q_RANGES) - (PAIR ? 2 : 1)) { g_next = 0; g_epoch = ep; }
          }
          qi = __shfl_sync(0xffffffffu, qi, 0);
          if (PAIR && !(cta & 1)) {
            mbar_wait_w(sbase + BAR_MAIL, i & 1);
            asm volatile(ELECT "st.async.shared::cluster.mbarrier::complete_tx::bytes.u32 [%0], %1, [%2];\n}"
                         ::"r"(peer(sbase + EPOCH_OFF + 8)), "r"(qi + 1), "r"(peer(sbase + BAR_MAIL)) : "memory");
          }
          qi += SIMPLE ? gridDim.x : NCTA;
        }
        uint32_t d;
        if (qi < (SIMPLE ? Q_ALL : Q_RANGES)) { d = c_sched.queue[qi]; if (d & 0x8000) d ^= (1u << 30) | (63u << 16) | 0x8000; else d |= o_slot<SIMPLE>(d >> 5) << 15 | (d & 31) << 10; }
        else if (SIMPLE) d = 2u << 30;
        else { const uint32_t e = qi - Q_RANGES, g = e / 5; d = c_sched.piece[g][piece++] | (g & 1 ? g * 5 + 4 - e : e - g * 5) << 8; }
        if ((d >> 30) == 1) {
          const uint32_t k0 = (d >> 22) & 63;
          const uint32_t run = __ffs(__ballot_sync(0xffffffffu, !reached(&g_cnt[d & 31][lane & 7], ep * 4)) & (0xffu << (k0 >> 3))) - 1;
          if (run <= (k0 + ((d >> 16) & 63)) >> 3) d |= run <= (k0 + O_STEPS) >> 3 ? (2u << 30) | 128 : 128;
        }
        asm volatile("st.volatile.shared.u32 [%0], %1;" ::"r"(sbase + EPOCH_OFF + 4), "r"(qi) : "memory");
        asm volatile("st.volatile.shared.u32 [%0], %1;" ::"r"(sbase + DESC_OFF + ((i + 1) & 3) * 4), "r"(d) : "memory");
        __syncwarp();
        mbar_arrive_warp(sbase + BAR_DESC);
        const Work w = decode(dc);
        dc = d;
        if (w.kind == 0) {
          mbar_wait_w(sbase + BAR_OUT, na++ & 1);
          TTAIL(1);
          T3(i, 0); T3(i, 1);
          asm volatile(ELECT "red.release.gpu.global.add.u32 [%0], 1;\n}" ::"l"(&g_cnt[w.beta][w.sub >> 2]) : "memory");
          T3(i, 2);
          TTAIL(2);
          continue;
        }
        const bool fin = w.mode != 1;
        uint64_t pol, pol2;
        asm volatile("createpolicy.fractional.L2::evict_first.b64 %0, 1.0;" : "=l"(pol));
        asm volatile("createpolicy.fractional.L2::evict_normal.b64 %0, 1.0;" : "=l"(pol2));
        if (!fin) pol = pol2;
        const CUtensorMap* m = fin ? P.out_st : P.o_st;
        const int c1 = fin ? (w.beta & 15) * SQ : 0;
        const int c2 = fin ? (w.beta >> 4) * (DM / 64) + w.sub * 2 : NBETA * 64 + w.range * 2;
        uint32_t pend = 0;
#pragma unroll 1
        for (int e = 0; e < 4; e++) {
          const int t = (ST_ORDER >> (4 * e)) & 3;
          mbar_wait_w(sbase + BAR_STG + (t ^ (t >> 1)) * 8, (i - na) & 1);
          tma_st3_hint_w(m + (t == 3), qb + t * 16384, 0, c1 + t * 64, c2, pol);
          bulk_commit();
          T2P(i + 1, 5, 2 * e);
          if (pend) {
            bulk_wait_read<1>();
            mbar_arrive8_w(pend);
            T2P(i + 1, 5, 2 * e - 1);
          }
          pend = sbase + BAR_EMPTY + (NS + t) * 8;
          if ((ST_NOW >> e) & 1) {
            bulk_wait_read<0>();
            mbar_arrive8_w(pend);
            pend = 0;
            T2P(i + 1, 5, 2 * e + 1);
          }
        }
        if (w.beta < N_EARLY) asm volatile(ELECT "red.relaxed.gpu.global.add.u32 [%0], 1;\n}" ::"l"(&g_rd[w.beta][7]) : "memory");
        T3(i, 0);
        if (piece >= 2) TTAIL(piece * 2 - 1);
        asm volatile("cp.async.bulk.wait_group 0;" ::: "memory");
        T3(i, 1);
        if (w.mode == 1) asm volatile(ELECT "st.release.gpu.global.u32 [%0], %1;\n}" ::"l"(&g_flag[w.range]), "r"(ep) : "memory");
        T3(i, 2);
        if (piece >= 2) TTAIL(piece * 2);
      }
      T3(15, 1);
    } else
    if (warp == 0) {
      Ring r{0, 1, 3};
      uint32_t d = c_sched.queue[cta];
      for (int i = 0;; i++) {
        const Work w = decode(d);
        if (w.kind == 2) break;
        const CUtensorMap* m = w.kind == 0 ? &P.wq[w.beta >> 4] : &P.wo[w.beta >> 4];
        for (int ks = 0; ks < w.nsteps; ks++) {
          const uint32_t b = borrow(ks, w.nsteps);
          r.next_if(b == 2);
          const uint32_t bar = sbase + BAR_FULL + r.slot * 8;
          mbar_wait_w(bar + (BAR_EMPTY - BAR_FULL), r.phase);
          if (w.kind == 0) tma_ld3_w(sbase + r.slot * SLOT, m, 0, ks * 64, w.sub * 2, bar, 16384);
          else tma_ld_wo_w(sbase + r.slot * SLOT, m, w.sub * 128, (w.k0 + ks) * 2, bar);
          if (w.kind != 0 && w.beta < N_EARLY && (ks & 7) == 5 && ks > 5)
            asm volatile(ELECT "red.relaxed.gpu.global.add.u32 [%0], 1;\n}" ::"l"(&g_rd[w.beta][(ks >> 3) - 1]) : "memory");
          if (ks < 10) T2P(i, 2, ks);
          if (w.kind != 0 && ks == max(w.nsteps - GO_P, 4)) mbar_arrive_warp(sbase + BAR_GO);
          r.next(); r.next_if(b == 2);
        }
        if (w.kind == 0) {
          r.phase ^= 1; r.next(); r.next();
        } else if (w.mode == 2) {
          for (int k = 1; k <= ((d >> 5) & 3); k++) {
            if (k == 1) TTAIL(9);
            wait_count(&g_flag[w.range + 5 * k], lds(sbase + EPOCH_OFF));
            TTAIL(10);
            asm volatile("fence.proxy.async.global;" ::: "memory");
#pragma unroll 1
            for (int t = 0; t < 4; t++) {
              mbar_wait_w(sbase + BAR_EMPTY + r.slot * 8, r.phase);
              tma_ld3_w(sbase + r.slot * SLOT, &P.o_st[t == 3], 0, t * 64, NBETA * 64 + (w.range + 5 * k) * 2, sbase + BAR_FULL + r.slot * 8,
                        t == 3 ? 8192 : 16384);
              r.next();
            }
          }
        }
        mbar_wait_w(sbase + BAR_DESC, i & 1);
        d = __shfl_sync(0xffffffffu, lds(sbase + DESC_OFF + ((i + 1) & 3) * 4), 0);
      }
    } else {
      const int hi = warp - 2;
      uint64_t pol_stream;
      uint32_t rdy = 0;
      asm volatile("createpolicy.fractional.L2::evict_first.b64 %0, 1.0;" : "=l"(pol_stream));
      Ring r{0, 1, 3};
      uint32_t d = c_sched.queue[cta];
      for (int i = 0;; i++) {
        const Work w = decode(d);
        if (w.kind == 2) break;
        const CUtensorMap* m = w.kind == 0 ? &P.x[hi][w.beta >> 4] : &P.o_ld[hi];
        int c1 = (w.kind == 0 ? (w.beta & 15) : o_slot<SIMPLE>(w.beta) * 64 + w.k0) * SQ + hi * 128;
        int k_wait = -1;
        const bool both = PAIR && (w.kind == 0 || w.sub != 4), mine = !both || hi == (cta & 1);
        if (w.kind != 0 && mine) {
          if (d & 128) k_wait = d >= (3u << 30) ? 0 : 8 - (w.k0 & 7);
          asm volatile("fence.proxy.async.global;" ::: "memory");
        }
        const int rank = i == 0 ? cta : __shfl_sync(0xffffffffu, lds(sbase + EPOCH_OFF + 4), 0) - NCTA;
        for (int ks = 0; ks < w.nsteps; ks++) {
          if (ks == k_wait) {
            wait_count(&g_cnt[d & 31][(w.k0 + ks) >> 3], lds(sbase + EPOCH_OFF) * 4);
            asm volatile("fence.proxy.async.global;" ::: "memory");
            k_wait = ((w.k0 + ks) | 7) + 1 - w.k0;
          }
          const uint32_t b = borrow(ks, w.nsteps);
          const bool bo = b != 2;
          r.next_if(hi && !bo); r.next_if(hi && !bo);
          const uint32_t sl = bo ? NS + (b ^ (3 * hi)) : r.slot, bar = sbase + BAR_FULL + sl * 8;
          mbar_wait_w(bar + (BAR_EMPTY - BAR_FULL), bo ? (r.xp >> b) & 1 : r.phase);
          const uint32_t bytes = hi ? 96 * 128 : 128 * 128;
          if (!mine) {
            asm volatile(ELECT EXPECT("%0", "%2") "mbarrier.arrive.shared::cluster.b64 _, [%1];\n}"
                         ::"r"(bar), "r"(peer(bar + (BAR_RDY - BAR_FULL))), "r"(bytes) : "memory");
          } else if (both) {
            mbar_wait_w(bar + (BAR_RDY - BAR_FULL), (rdy >> sl) & 1);
            rdy ^= 1 << sl;
            if (w.kind == 0) tma_ld2_both_w(sbase + sl * SLOT, m, ks * 64, c1, bar, bytes);
            else tma_ld2_both_hint_w(sbase + sl * SLOT, m, 0, c1, bar, bytes, pol_stream);
          } else if (!PAIR && w.kind == 0) tma_ld2_w(sbase + sl * SLOT, m, ks * 64, c1, bar, bytes);
          else tma_ld2_hint_w(sbase + sl * SLOT, m, 0, c1, bar, bytes, pol_stream);
          if (w.kind != 0) c1 += SQ;
          if (i == 0 && ks == PF_STEP)
            asm volatile(ELECT "cp.async.bulk.prefetch.tensor.3d.L2.global.L2::cache_hint [%0, {0, %1, 0}], %2;\n}"
                         ::"l"(&P.kv[hi][0]), "r"(d * SK), "l"(pol_stream) : "memory");
          if (ks < 10) T2P(i, 3 + hi, ks);
          if (!hi && w.kind != 0 && !(ks & 3)) TCLK(i * 16 + (ks >> 2));
          r.next(); r.next_if(!hi && !bo); r.next_if(!hi && !bo);
          r.xp ^= 1 << b;
        }
        r.xp ^= 3;
        if (w.kind == 0) {
          m = &P.kv[hi][w.beta >> 4];
          c1 = (d & 511) * SK;
          for (int j = 0; j < 16; j++) {
            if (hi) r.next();
            const uint32_t bar = sbase + BAR_FULL + r.slot * 8;
            const bool tight = i < KV_WIN_UNITS && j < KV_WIN_TILES + ((KV_WIN_RAMP * rank) >> 5);
            {
              const int s2 = (int)r.slot - (tight ? 2 : KV_WIN_D);
              mbar_wait_w(sbase + BAR_FULL + (s2 < 0 ? s2 + NS : s2) * 8, s2 < 0 ? r.phase : r.phase ^ 1);
            }
            if (j == 15 && hi) mbar_wait_w(sbase + BAR_DESC, i & 1);
            mbar_wait_w(sbase + BAR_EMPTY + r.slot * 8, r.phase);
            tma_ld3_hint_w(sbase + r.slot * SLOT, m, 0, c1, 0, bar, pol_stream);
            T2P(i, 3 + hi, 16 + j);
            if (!hi) TCLK(i * 16 + j);
            if (j == 14 && !hi) mbar_arrive_warp(sbase + BAR_GO);
            c1 += 64;
            r.next();
            if (!hi) r.next();
          }
        }
        mbar_wait_w(sbase + BAR_DESC, i & 1);
        d = __shfl_sync(0xffffffffu, lds(sbase + DESC_OFF + ((i + 1) & 3) * 4), 0);
      }
    }
  } else {
    Ctx c;
    c.sb = sbase; c.wg = wg; c.warp = warp; c.src = 0; c.mqk = 0; c.mpv = 0; c.lead = lane == 0; c.lane0 = c.lane = lane;
    if (wg == 0) consumer<0>(c, P.kp); else consumer<1>(c, P.kp);
  }
}

typedef CUresult (*EncodeFn)(CUtensorMap*, CUtensorMapDataType, cuuint32_t, void*, const cuuint64_t*, const cuuint64_t*,
                             const cuuint32_t*, const cuuint32_t*, CUtensorMapInterleave, CUtensorMapSwizzle,
                             CUtensorMapL2promotion, CUtensorMapFloatOOBfill);

void make_map(EncodeFn enc, CUtensorMap* m, const void* ptr, int rank, const cuuint64_t* dims, const cuuint64_t* strides,
              const cuuint32_t* box, int promo = 2, CUtensorMapSwizzle swz = CU_TENSOR_MAP_SWIZZLE_128B) {
  cuuint32_t es[5] = {1, 1, 1, 1, 1};
  enc(m, CU_TENSOR_MAP_DATA_TYPE_BFLOAT16, rank, const_cast<void*>(ptr), dims, strides, box, es,
      CU_TENSOR_MAP_INTERLEAVE_NONE, swz, promo == 2 ? CU_TENSOR_MAP_L2_PROMOTION_L2_256B : promo == 1 ? CU_TENSOR_MAP_L2_PROMOTION_L2_128B : CU_TENSOR_MAP_L2_PROMOTION_NONE,
      CU_TENSOR_MAP_FLOAT_OOB_FILL_NONE);
}

}

extern "C" void kernel_launch(void* const* d_in, const int* in_sizes, int n_in, void* d_out, int out_size) {
  (void)in_sizes; (void)n_in; (void)out_size;
  static EncodeFn enc = nullptr;
  static void* o_ptr = nullptr;
  static int n_sm = 0;
  cudaLaunchAttribute at;
  at.id = cudaLaunchAttributeClusterDimension;
  at.val.clusterDim.x = CLUSTER ? 2 : 1; at.val.clusterDim.y = 1; at.val.clusterDim.z = 1;
  cudaLaunchConfig_t cfg = {};
  cfg.gridDim = dim3(NCTA); cfg.blockDim = dim3(384); cfg.dynamicSmemBytes = SMEM_BYTES; cfg.attrs = &at; cfg.numAttrs = 1;
  if (!enc) {
    void* fn = nullptr;
    cudaDriverEntryPointQueryResult qr;
    cudaGetDriverEntryPoint("cuTensorMapEncodeTiled", &fn, cudaEnableDefault, &qr);
    enc = (EncodeFn)fn;
    cudaGetSymbolAddress(&o_ptr, g_o);
    cudaFuncSetAttribute(mha_fused_kernel<false>, cudaFuncAttributeMaxDynamicSharedMemorySize, SMEM_BYTES);
    cudaFuncSetAttribute(mha_fused_kernel<true>, cudaFuncAttributeMaxDynamicSharedMemorySize, SMEM_BYTES);
    int dev = 0;
    cudaGetDevice(&dev);
    cudaDeviceGetAttribute(&n_sm, cudaDevAttrMultiProcessorCount, dev);
    int n_cl = 0;
    cudaOccupancyMaxActiveClusters(&n_cl, mha_fused_kernel<false>, &cfg);
    if (n_cl * (CLUSTER ? 2 : 1) < NCTA && n_sm >= NCTA) n_sm = NCTA - 1;
  }
  Params P;
  for (int br = 0; br < 2; br++) {
    const void* x = d_in[br * 5 + 0]; const void* kc = d_in[br * 5 + 1]; const void* vc = d_in[br * 5 + 2];
    const void* wq = d_in[br * 5 + 3]; const void* wo = d_in[br * 5 + 4];
    { cuuint64_t d[2] = {DM, (cuuint64_t)NB * SQ}, s[1] = {DM * 2}; cuuint32_t b[2] = {64, 128}, b2[2] = {64, 96};
      make_map(enc, &P.x[0][br], x, 2, d, s, b, PR_X); make_map(enc, &P.x[1][br], x, 2, d, s, b2, PR_X); }
    { cuuint64_t d[3] = {64, DM, HD / 64}, s[2] = {HD * 2, 128}; cuuint32_t b[3] = {64, 64, 2}; make_map(enc, &P.wq[br], wq, 3, d, s, b, PR_W); }
    { cuuint64_t d[5] = {DM, 2, 4, 4, HD / 32}, s[4] = {DM * 2, 8 * DM * 2, 2 * DM * 2, 32 * DM * 2}; cuuint32_t b[5] = {64, 2, 4, 4, 2};
      make_map(enc, &P.wo[br], wo, 5, d, s, b, PR_W); }
    { cuuint64_t d[3] = {64, (cuuint64_t)NB * NH * SK, 2}, s[2] = {DH * 2, 128}; cuuint32_t b[3] = {64, 64, 2};
      make_map(enc, &P.kv[0][br], kc, 3, d, s, b, PR_KV); make_map(enc, &P.kv[1][br], vc, 3, d, s, b, PR_KV); }
    P.kp[br] = (const __nv_bfloat16*)kc; P.vp[br] = (const __nv_bfloat16*)vc;

  }
  { cuuint64_t d[2] = {64, (cuuint64_t)NBETA * 64 * SQ}, s[1] = {128}; cuuint32_t b[2] = {64, 128}, b2[2] = {64, 96};
    make_map(enc, &P.o_ld[0], o_ptr, 2, d, s, b, 2, CU_TENSOR_MAP_SWIZZLE_NONE); make_map(enc, &P.o_ld[1], o_ptr, 2, d, s, b2, 2, CU_TENSOR_MAP_SWIZZLE_NONE); }
  { cuuint64_t d[3] = {64, SQ, O_BLOCKS}, s[2] = {128, SQ * 128}; cuuint32_t b[3] = {64, 64, 2}, b2[3] = {64, 32, 2};
    make_map(enc, &P.o_st[0], o_ptr, 3, d, s, b); make_map(enc, &P.o_st[1], o_ptr, 3, d, s, b2); }
  { cuuint64_t d[3] = {64, (cuuint64_t)NB * SQ, 2 * DM / 64}, s[2] = {2 * DM * 2, 128}; cuuint32_t b[3] = {64, 64, 2}, b2[3] = {64, 32, 2};
    make_map(enc, &P.out_st[0], d_out, 3, d, s, b); make_map(enc, &P.out_st[1], d_out, 3, d, s, b2); }
  if (n_sm >= NCTA) cudaLaunchKernelEx(&cfg, mha_fused_kernel<false>, P);
  else mha_fused_kernel<true><<<n_sm, 384, SMEM_BYTES>>>(P);
}
```

```cpp
#include <cuda_runtime.h>
#include <cuda_bf16.h>
#include <cuda.h>
#include <stdint.h>
#include <stdlib.h>

namespace {

__device__ __forceinline__ void wgmma_proj(float (&d)[64], uint64_t da, uint64_t db, int scaleD) {
  asm volatile("{\n.reg .pred p;\nsetp.ne.b32 p, %66, 0;\n"
      "wgmma.mma_async.sync.aligned.m64n128k16.f32.bf16.bf16 "
      "{%0, %1, %2, %3, %4, %5, %6, %7, %8, %9, %10, %11, %12, %13, %14, %15, %16, %17, %18, %19, %20, %21, %22, %23, %24, %25, %26, %27, %28, %29, %30, "
      "%31, %32, %33, %34, %35, %36, %37, %38, %39, %40, %41, %42, %43, %44, %45, %46, %47, %48, %49, %50, %51, %52, %53, %54, %55, %56, %57, %58, %59, %60, "
      "%61, %62, %63}, "
      "%64, %65, p, 1, 1, 0, 1;\n}\n"
      : "+f"(d[0]), "+f"(d[1]), "+f"(d[2]), "+f"(d[3]), "+f"(d[4]), "+f"(d[5]), "+f"(d[6]), "+f"(d[7]), "+f"(d[8]), "+f"(d[9]), "+f"(d[10]), "+f"(d[11]),
        "+f"(d[12]), "+f"(d[13]), "+f"(d[14]), "+f"(d[15]), "+f"(d[16]), "+f"(d[17]), "+f"(d[18]), "+f"(d[19]), "+f"(d[20]), "+f"(d[21]), "+f"(d[22]),
        "+f"(d[23]), "+f"(d[24]), "+f"(d[25]), "+f"(d[26]), "+f"(d[27]), "+f"(d[28]), "+f"(d[29]), "+f"(d[30]), "+f"(d[31]), "+f"(d[32]), "+f"(d[33]),
        "+f"(d[34]), "+f"(d[35]), "+f"(d[36]), "+f"(d[37]), "+f"(d[38]), "+f"(d[39]), "+f"(d[40]), "+f"(d[41]), "+f"(d[42]), "+f"(d[43]), "+f"(d[44]),
        "+f"(d[45]), "+f"(d[46]), "+f"(d[47]), "+f"(d[48]), "+f"(d[49]), "+f"(d[50]), "+f"(d[51]), "+f"(d[52]), "+f"(d[53]), "+f"(d[54]), "+f"(d[55]),
        "+f"(d[56]), "+f"(d[57]), "+f"(d[58]), "+f"(d[59]), "+f"(d[60]), "+f"(d[61]), "+f"(d[62]), "+f"(d[63])
      : "l"(da), "l"(db), "r"(scaleD));
}
__device__ __forceinline__ void wgmma_proj96(float (&d)[64], uint64_t da, uint64_t db, int scaleD) {
  asm volatile("{\n.reg .pred p;\nsetp.ne.b32 p, %50, 0;\n"
      "wgmma.mma_async.sync.aligned.m64n96k16.f32.bf16.bf16 "
      "{%0, %1, %2, %3, %4, %5, %6, %7, %8, %9, %10, %11, %12, %13, %14, %15, %16, %17, %18, %19, %20, %21, %22, %23, %24, %25, %26, %27, %28, %29, %30, "
      "%31, %32, %33, %34, %35, %36, %37, %38, %39, %40, %41, %42, %43, %44, %45, %46, %47}, "
      "%48, %49, p, 1, 1, 1, 0;\n}\n"
      : "+f"(d[0]), "+f"(d[1]), "+f"(d[2]), "+f"(d[3]), "+f"(d[4]), "+f"(d[5]), "+f"(d[6]), "+f"(d[7]), "+f"(d[8]), "+f"(d[9]), "+f"(d[10]), "+f"(d[11]),
        "+f"(d[12]), "+f"(d[13]), "+f"(d[14]), "+f"(d[15]), "+f"(d[16]), "+f"(d[17]), "+f"(d[18]), "+f"(d[19]), "+f"(d[20]), "+f"(d[21]), "+f"(d[22]),
        "+f"(d[23]), "+f"(d[24]), "+f"(d[25]), "+f"(d[26]), "+f"(d[27]), "+f"(d[28]), "+f"(d[29]), "+f"(d[30]), "+f"(d[31]), "+f"(d[32]), "+f"(d[33]),
        "+f"(d[34]), "+f"(d[35]), "+f"(d[36]), "+f"(d[37]), "+f"(d[38]), "+f"(d[39]), "+f"(d[40]), "+f"(d[41]), "+f"(d[42]), "+f"(d[43]), "+f"(d[44]),
        "+f"(d[45]), "+f"(d[46]), "+f"(d[47])
      : "l"(da), "l"(db), "r"(scaleD));
}
__device__ __forceinline__ void wgmma_qk(float (&d)[32], uint64_t da, uint64_t db, int scaleD) {
  asm volatile("{\n.reg .pred p;\nsetp.ne.b32 p, %34, 0;\n"
      "wgmma.mma_async.sync.aligned.m64n64k16.f32.bf16.bf16 "
      "{%0, %1, %2, %3, %4, %5, %6, %7, %8, %9, %10, %11, %12, %13, %14, %15, %16, %17, %18, %19, %20, %21, %22, %23, %24, %25, %26, %27, %28, %29, %30, "
      "%31}, "
      "%32, %33, p, 1, 1, 0, 0;\n}\n"
      : "+f"(d[0]), "+f"(d[1]), "+f"(d[2]), "+f"(d[3]), "+f"(d[4]), "+f"(d[5]), "+f"(d[6]), "+f"(d[7]), "+f"(d[8]), "+f"(d[9]), "+f"(d[10]), "+f"(d[11]),
        "+f"(d[12]), "+f"(d[13]), "+f"(d[14]), "+f"(d[15]), "+f"(d[16]), "+f"(d[17]), "+f"(d[18]), "+f"(d[19]), "+f"(d[20]), "+f"(d[21]), "+f"(d[22]),
        "+f"(d[23]), "+f"(d[24]), "+f"(d[25]), "+f"(d[26]), "+f"(d[27]), "+f"(d[28]), "+f"(d[29]), "+f"(d[30]), "+f"(d[31])
      : "l"(da), "l"(db), "r"(scaleD));
}
__device__ __forceinline__ void wgmma_qk_rs(float (&d)[32], uint32_t a0, uint32_t a1, uint32_t a2, uint32_t a3, uint64_t db, int scaleD) {
  asm volatile("{\n.reg .pred p;\nsetp.ne.b32 p, %37, 0;\n"
      "wgmma.mma_async.sync.aligned.m64n64k16.f32.bf16.bf16 "
      "{%0, %1, %2, %3, %4, %5, %6, %7, %8, %9, %10, %11, %12, %13, %14, %15, %16, %17, %18, %19, %20, %21, %22, %23, %24, %25, %26, %27, %28, %29, %30, "
      "%31}, "
      "{%32, %33, %34, %35}, %36, p, 1, 1, 0;\n}\n"
      : "+f"(d[0]), "+f"(d[1]), "+f"(d[2]), "+f"(d[3]), "+f"(d[4]), "+f"(d[5]), "+f"(d[6]), "+f"(d[7]), "+f"(d[8]), "+f"(d[9]), "+f"(d[10]), "+f"(d[11]),
        "+f"(d[12]), "+f"(d[13]), "+f"(d[14]), "+f"(d[15]), "+f"(d[16]), "+f"(d[17]), "+f"(d[18]), "+f"(d[19]), "+f"(d[20]), "+f"(d[21]), "+f"(d[22]),
        "+f"(d[23]), "+f"(d[24]), "+f"(d[25]), "+f"(d[26]), "+f"(d[27]), "+f"(d[28]), "+f"(d[29]), "+f"(d[30]), "+f"(d[31])
      : "r"(a0), "r"(a1), "r"(a2), "r"(a3), "l"(db), "r"(scaleD));
}
__device__ __forceinline__ void wgmma_pv(float (&d)[64], uint32_t a0, uint32_t a1, uint32_t a2, uint32_t a3, uint64_t db, int scaleD) {
  asm volatile("{\n.reg .pred p;\nsetp.ne.b32 p, %69, 0;\n"
      "wgmma.mma_async.sync.aligned.m64n128k16.f32.bf16.bf16 "
      "{%0, %1, %2, %3, %4, %5, %6, %7, %8, %9, %10, %11, %12, %13, %14, %15, %16, %17, %18, %19, %20, %21, %22, %23, %24, %25, %26, %27, %28, %29, %30, "
      "%31, %32, %33, %34, %35, %36, %37, %38, %39, %40, %41, %42, %43, %44, %45, %46, %47, %48, %49, %50, %51, %52, %53, %54, %55, %56, %57, %58, %59, %60, "
      "%61, %62, %63}, "
      "{%64, %65, %66, %67}, %68, p, 1, 1, 1;\n}\n"
      : "+f"(d[0]), "+f"(d[1]), "+f"(d[2]), "+f"(d[3]), "+f"(d[4]), "+f"(d[5]), "+f"(d[6]), "+f"(d[7]), "+f"(d[8]), "+f"(d[9]), "+f"(d[10]), "+f"(d[11]),
        "+f"(d[12]), "+f"(d[13]), "+f"(d[14]), "+f"(d[15]), "+f"(d[16]), "+f"(d[17]), "+f"(d[18]), "+f"(d[19]), "+f"(d[20]), "+f"(d[21]), "+f"(d[22]),
        "+f"(d[23]), "+f"(d[24]), "+f"(d[25]), "+f"(d[26]), "+f"(d[27]), "+f"(d[28]), "+f"(d[29]), "+f"(d[30]), "+f"(d[31]), "+f"(d[32]), "+f"(d[33]),
        "+f"(d[34]), "+f"(d[35]), "+f"(d[36]), "+f"(d[37]), "+f"(d[38]), "+f"(d[39]), "+f"(d[40]), "+f"(d[41]), "+f"(d[42]), "+f"(d[43]), "+f"(d[44]),
        "+f"(d[45]), "+f"(d[46]), "+f"(d[47]), "+f"(d[48]), "+f"(d[49]), "+f"(d[50]), "+f"(d[51]), "+f"(d[52]), "+f"(d[53]), "+f"(d[54]), "+f"(d[55]),
        "+f"(d[56]), "+f"(d[57]), "+f"(d[58]), "+f"(d[59]), "+f"(d[60]), "+f"(d[61]), "+f"(d[62]), "+f"(d[63])
      : "r"(a0), "r"(a1), "r"(a2), "r"(a3), "l"(db), "r"(scaleD));
}
__device__ __forceinline__ void wgmma_qk_sp(float (&d)[32], uint32_t a0, uint32_t a1, uint32_t a2, uint32_t a3, uint64_t db, int scaleD, uint32_t meta) {
  asm volatile("{\n.reg .pred p;\nsetp.ne.b32 p, %37, 0;\n"
      "wgmma.mma_async.sp.sync.aligned.m64n64k32.f32.bf16.bf16 "
      "{%0, %1, %2, %3, %4, %5, %6, %7, %8, %9, %10, %11, %12, %13, %14, %15, %16, %17, %18, %19, %20, %21, %22, %23, %24, %25, %26, %27, %28, %29, %30, "
      "%31}, "
      "{%32, %33, %34, %35}, %36, %38, 0, p, 1, 1, 0;\n}\n"
      : "+f"(d[0]), "+f"(d[1]), "+f"(d[2]), "+f"(d[3]), "+f"(d[4]), "+f"(d[5]), "+f"(d[6]), "+f"(d[7]), "+f"(d[8]), "+f"(d[9]), "+f"(d[10]), "+f"(d[11]),
        "+f"(d[12]), "+f"(d[13]), "+f"(d[14]), "+f"(d[15]), "+f"(d[16]), "+f"(d[17]), "+f"(d[18]), "+f"(d[19]), "+f"(d[20]), "+f"(d[21]), "+f"(d[22]),
        "+f"(d[23]), "+f"(d[24]), "+f"(d[25]), "+f"(d[26]), "+f"(d[27]), "+f"(d[28]), "+f"(d[29]), "+f"(d[30]), "+f"(d[31])
      : "r"(a0), "r"(a1), "r"(a2), "r"(a3), "l"(db), "r"(scaleD), "r"(meta));
}
__device__ __forceinline__ void wgmma_pv_sp(float (&d)[64], uint32_t a0, uint32_t a1, uint32_t a2, uint32_t a3, uint64_t db, int scaleD, uint32_t meta) {
  asm volatile("{\n.reg .pred p;\nsetp.ne.b32 p, %69, 0;\n"
      "wgmma.mma_async.sp.sync.aligned.m64n128k32.f32.bf16.bf16 "
      "{%0, %1, %2, %3, %4, %5, %6, %7, %8, %9, %10, %11, %12, %13, %14, %15, %16, %17, %18, %19, %20, %21, %22, %23, %24, %25, %26, %27, %28, %29, %30, "
      "%31, %32, %33, %34, %35, %36, %37, %38, %39, %40, %41, %42, %43, %44, %45, %46, %47, %48, %49, %50, %51, %52, %53, %54, %55, %56, %57, %58, %59, %60, "
      "%61, %62, %63}, "
      "{%64, %65, %66, %67}, %68, %70, 0, p, 1, 1, 1;\n}\n"
      : "+f"(d[0]), "+f"(d[1]), "+f"(d[2]), "+f"(d[3]), "+f"(d[4]), "+f"(d[5]), "+f"(d[6]), "+f"(d[7]), "+f"(d[8]), "+f"(d[9]), "+f"(d[10]), "+f"(d[11]),
        "+f"(d[12]), "+f"(d[13]), "+f"(d[14]), "+f"(d[15]), "+f"(d[16]), "+f"(d[17]), "+f"(d[18]), "+f"(d[19]), "+f"(d[20]), "+f"(d[21]), "+f"(d[22]),
        "+f"(d[23]), "+f"(d[24]), "+f"(d[25]), "+f"(d[26]), "+f"(d[27]), "+f"(d[28]), "+f"(d[29]), "+f"(d[30]), "+f"(d[31]), "+f"(d[32]), "+f"(d[33]),
        "+f"(d[34]), "+f"(d[35]), "+f"(d[36]), "+f"(d[37]), "+f"(d[38]), "+f"(d[39]), "+f"(d[40]), "+f"(d[41]), "+f"(d[42]), "+f"(d[43]), "+f"(d[44]),
        "+f"(d[45]), "+f"(d[46]), "+f"(d[47]), "+f"(d[48]), "+f"(d[49]), "+f"(d[50]), "+f"(d[51]), "+f"(d[52]), "+f"(d[53]), "+f"(d[54]), "+f"(d[55]),
        "+f"(d[56]), "+f"(d[57]), "+f"(d[58]), "+f"(d[59]), "+f"(d[60]), "+f"(d[61]), "+f"(d[62]), "+f"(d[63])
      : "r"(a0), "r"(a1), "r"(a2), "r"(a3), "l"(db), "r"(scaleD), "r"(meta));
}
__device__ __forceinline__ void wgmma_proj_init(float (&d)[64], uint64_t da, uint64_t db, int scaleD) {
  asm volatile("{\n.reg .pred p;\nsetp.ne.b32 p, %66, 0;\n"
      "wgmma.mma_async.sync.aligned.m64n128k16.f32.bf16.bf16 "
      "{%0, %1, %2, %3, %4, %5, %6, %7, %8, %9, %10, %11, %12, %13, %14, %15, %16, %17, %18, %19, %20, %21, %22, %23, %24, %25, %26, %27, %28, %29, %30, "
      "%31, %32, %33, %34, %35, %36, %37, %38, %39, %40, %41, %42, %43, %44, %45, %46, %47, %48, %49, %50, %51, %52, %53, %54, %55, %56, %57, %58, %59, %60, "
      "%61, %62, %63}, "
      "%64, %65, p, 1, 1, 0, 1;\n}\n"
      : "=f"(d[0]), "=f"(d[1]), "=f"(d[2]), "=f"(d[3]), "=f"(d[4]), "=f"(d[5]), "=f"(d[6]), "=f"(d[7]), "=f"(d[8]), "=f"(d[9]), "=f"(d[10]), "=f"(d[11]),
        "=f"(d[12]), "=f"(d[13]), "=f"(d[14]), "=f"(d[15]), "=f"(d[16]), "=f"(d[17]), "=f"(d[18]), "=f"(d[19]), "=f"(d[20]), "=f"(d[21]), "=f"(d[22]),
        "=f"(d[23]), "=f"(d[24]), "=f"(d[25]), "=f"(d[26]), "=f"(d[27]), "=f"(d[28]), "=f"(d[29]), "=f"(d[30]), "=f"(d[31]), "=f"(d[32]), "=f"(d[33]),
        "=f"(d[34]), "=f"(d[35]), "=f"(d[36]), "=f"(d[37]), "=f"(d[38]), "=f"(d[39]), "=f"(d[40]), "=f"(d[41]), "=f"(d[42]), "=f"(d[43]), "=f"(d[44]),
        "=f"(d[45]), "=f"(d[46]), "=f"(d[47]), "=f"(d[48]), "=f"(d[49]), "=f"(d[50]), "=f"(d[51]), "=f"(d[52]), "=f"(d[53]), "=f"(d[54]), "=f"(d[55]),
        "=f"(d[56]), "=f"(d[57]), "=f"(d[58]), "=f"(d[59]), "=f"(d[60]), "=f"(d[61]), "=f"(d[62]), "=f"(d[63])
      : "l"(da), "l"(db), "r"(scaleD));
}
__device__ __forceinline__ void wgmma_proj96_init(float (&d)[64], uint64_t da, uint64_t db, int scaleD) {
  asm volatile("{\n.reg .pred p;\nsetp.ne.b32 p, %50, 0;\n"
      "wgmma.mma_async.sync.aligned.m64n96k16.f32.bf16.bf16 "
      "{%0, %1, %2, %3, %4, %5, %6, %7, %8, %9, %10, %11, %12, %13, %14, %15, %16, %17, %18, %19, %20, %21, %22, %23, %24, %25, %26, %27, %28, %29, %30, "
      "%31, %32, %33, %34, %35, %36, %37, %38, %39, %40, %41, %42, %43, %44, %45, %46, %47}, "
      "%48, %49, p, 1, 1, 1, 0;\n}\n"
      : "=f"(d[0]), "=f"(d[1]), "=f"(d[2]), "=f"(d[3]), "=f"(d[4]), "=f"(d[5]), "=f"(d[6]), "=f"(d[7]), "=f"(d[8]), "=f"(d[9]), "=f"(d[10]), "=f"(d[11]),
        "=f"(d[12]), "=f"(d[13]), "=f"(d[14]), "=f"(d[15]), "=f"(d[16]), "=f"(d[17]), "=f"(d[18]), "=f"(d[19]), "=f"(d[20]), "=f"(d[21]), "=f"(d[22]),
        "=f"(d[23]), "=f"(d[24]), "=f"(d[25]), "=f"(d[26]), "=f"(d[27]), "=f"(d[28]), "=f"(d[29]), "=f"(d[30]), "=f"(d[31]), "=f"(d[32]), "=f"(d[33]),
        "=f"(d[34]), "=f"(d[35]), "=f"(d[36]), "=f"(d[37]), "=f"(d[38]), "=f"(d[39]), "=f"(d[40]), "=f"(d[41]), "=f"(d[42]), "=f"(d[43]), "=f"(d[44]),
        "=f"(d[45]), "=f"(d[46]), "=f"(d[47])
      : "l"(da), "l"(db), "r"(scaleD));
}
__device__ __forceinline__ void wgmma_qk_init(float (&d)[32], uint64_t da, uint64_t db, int scaleD) {
  asm volatile("{\n.reg .pred p;\nsetp.ne.b32 p, %34, 0;\n"
      "wgmma.mma_async.sync.aligned.m64n64k16.f32.bf16.bf16 "
      "{%0, %1, %2, %3, %4, %5, %6, %7, %8, %9, %10, %11, %12, %13, %14, %15, %16, %17, %18, %19, %20, %21, %22, %23, %24, %25, %26, %27, %28, %29, %30, "
      "%31}, "
      "%32, %33, p, 1, 1, 0, 0;\n}\n"
      : "=f"(d[0]), "=f"(d[1]), "=f"(d[2]), "=f"(d[3]), "=f"(d[4]), "=f"(d[5]), "=f"(d[6]), "=f"(d[7]), "=f"(d[8]), "=f"(d[9]), "=f"(d[10]), "=f"(d[11]),
        "=f"(d[12]), "=f"(d[13]), "=f"(d[14]), "=f"(d[15]), "=f"(d[16]), "=f"(d[17]), "=f"(d[18]), "=f"(d[19]), "=f"(d[20]), "=f"(d[21]), "=f"(d[22]),
        "=f"(d[23]), "=f"(d[24]), "=f"(d[25]), "=f"(d[26]), "=f"(d[27]), "=f"(d[28]), "=f"(d[29]), "=f"(d[30]), "=f"(d[31])
      : "l"(da), "l"(db), "r"(scaleD));
}
__device__ __forceinline__ void wgmma_qk_rs_init(float (&d)[32], uint32_t a0, uint32_t a1, uint32_t a2, uint32_t a3, uint64_t db, int scaleD) {
  asm volatile("{\n.reg .pred p;\nsetp.ne.b32 p, %37, 0;\n"
      "wgmma.mma_async.sync.aligned.m64n64k16.f32.bf16.bf16 "
      "{%0, %1, %2, %3, %4, %5, %6, %7, %8, %9, %10, %11, %12, %13, %14, %15, %16, %17, %18, %19, %20, %21, %22, %23, %24, %25, %26, %27, %28, %29, %30, "
      "%31}, "
      "{%32, %33, %34, %35}, %36, p, 1, 1, 0;\n}\n"
      : "=f"(d[0]), "=f"(d[1]), "=f"(d[2]), "=f"(d[3]), "=f"(d[4]), "=f"(d[5]), "=f"(d[6]), "=f"(d[7]), "=f"(d[8]), "=f"(d[9]), "=f"(d[10]), "=f"(d[11]),
        "=f"(d[12]), "=f"(d[13]), "=f"(d[14]), "=f"(d[15]), "=f"(d[16]), "=f"(d[17]), "=f"(d[18]), "=f"(d[19]), "=f"(d[20]), "=f"(d[21]), "=f"(d[22]),
        "=f"(d[23]), "=f"(d[24]), "=f"(d[25]), "=f"(d[26]), "=f"(d[27]), "=f"(d[28]), "=f"(d[29]), "=f"(d[30]), "=f"(d[31])
      : "r"(a0), "r"(a1), "r"(a2), "r"(a3), "l"(db), "r"(scaleD));
}
__device__ __forceinline__ void wgmma_pv_init(float (&d)[64], uint32_t a0, uint32_t a1, uint32_t a2, uint32_t a3, uint64_t db, int scaleD) {
  asm volatile("{\n.reg .pred p;\nsetp.ne.b32 p, %69, 0;\n"
      "wgmma.mma_async.sync.aligned.m64n128k16.f32.bf16.bf16 "
      "{%0, %1, %2, %3, %4, %5, %6, %7, %8, %9, %10, %11, %12, %13, %14, %15, %16, %17, %18, %19, %20, %21, %22, %23, %24, %25, %26, %27, %28, %29, %30, "
      "%31, %32, %33, %34, %35, %36, %37, %38, %39, %40, %41, %42, %43, %44, %45, %46, %47, %48, %49, %50, %51, %52, %53, %54, %55, %56, %57, %58, %59, %60, "
      "%61, %62, %63}, "
      "{%64, %65, %66, %67}, %68, p, 1, 1, 1;\n}\n"
      : "=f"(d[0]), "=f"(d[1]), "=f"(d[2]), "=f"(d[3]), "=f"(d[4]), "=f"(d[5]), "=f"(d[6]), "=f"(d[7]), "=f"(d[8]), "=f"(d[9]), "=f"(d[10]), "=f"(d[11]),
        "=f"(d[12]), "=f"(d[13]), "=f"(d[14]), "=f"(d[15]), "=f"(d[16]), "=f"(d[17]), "=f"(d[18]), "=f"(d[19]), "=f"(d[20]), "=f"(d[21]), "=f"(d[22]),
        "=f"(d[23]), "=f"(d[24]), "=f"(d[25]), "=f"(d[26]), "=f"(d[27]), "=f"(d[28]), "=f"(d[29]), "=f"(d[30]), "=f"(d[31]), "=f"(d[32]), "=f"(d[33]),
        "=f"(d[34]), "=f"(d[35]), "=f"(d[36]), "=f"(d[37]), "=f"(d[38]), "=f"(d[39]), "=f"(d[40]), "=f"(d[41]), "=f"(d[42]), "=f"(d[43]), "=f"(d[44]),
        "=f"(d[45]), "=f"(d[46]), "=f"(d[47]), "=f"(d[48]), "=f"(d[49]), "=f"(d[50]), "=f"(d[51]), "=f"(d[52]), "=f"(d[53]), "=f"(d[54]), "=f"(d[55]),
        "=f"(d[56]), "=f"(d[57]), "=f"(d[58]), "=f"(d[59]), "=f"(d[60]), "=f"(d[61]), "=f"(d[62]), "=f"(d[63])
      : "r"(a0), "r"(a1), "r"(a2), "r"(a3), "l"(db), "r"(scaleD));
}
__device__ __forceinline__ void wgmma_qk_sp_init(float (&d)[32], uint32_t a0, uint32_t a1, uint32_t a2, uint32_t a3, uint64_t db, int scaleD, uint32_t meta) {
  asm volatile("{\n.reg .pred p;\nsetp.ne.b32 p, %37, 0;\n"
      "wgmma.mma_async.sp.sync.aligned.m64n64k32.f32.bf16.bf16 "
      "{%0, %1, %2, %3, %4, %5, %6, %7, %8, %9, %10, %11, %12, %13, %14, %15, %16, %17, %18, %19, %20, %21, %22, %23, %24, %25, %26, %27, %28, %29, %30, "
      "%31}, "
      "{%32, %33, %34, %35}, %36, %38, 0, p, 1, 1, 0;\n}\n"
      : "=f"(d[0]), "=f"(d[1]), "=f"(d[2]), "=f"(d[3]), "=f"(d[4]), "=f"(d[5]), "=f"(d[6]), "=f"(d[7]), "=f"(d[8]), "=f"(d[9]), "=f"(d[10]), "=f"(d[11]),
        "=f"(d[12]), "=f"(d[13]), "=f"(d[14]), "=f"(d[15]), "=f"(d[16]), "=f"(d[17]), "=f"(d[18]), "=f"(d[19]), "=f"(d[20]), "=f"(d[21]), "=f"(d[22]),
        "=f"(d[23]), "=f"(d[24]), "=f"(d[25]), "=f"(d[26]), "=f"(d[27]), "=f"(d[28]), "=f"(d[29]), "=f"(d[30]), "=f"(d[31])
      : "r"(a0), "r"(a1), "r"(a2), "r"(a3), "l"(db), "r"(scaleD), "r"(meta));
}
__device__ __forceinline__ void wgmma_pv_sp_init(float (&d)[64], uint32_t a0, uint32_t a1, uint32_t a2, uint32_t a3, uint64_t db, int scaleD, uint32_t meta) {
  asm volatile("{\n.reg .pred p;\nsetp.ne.b32 p, %69, 0;\n"
      "wgmma.mma_async.sp.sync.aligned.m64n128k32.f32.bf16.bf16 "
      "{%0, %1, %2, %3, %4, %5, %6, %7, %8, %9, %10, %11, %12, %13, %14, %15, %16, %17, %18, %19, %20, %21, %22, %23, %24, %25, %26, %27, %28, %29, %30, "
      "%31, %32, %33, %34, %35, %36, %37, %38, %39, %40, %41, %42, %43, %44, %45, %46, %47, %48, %49, %50, %51, %52, %53, %54, %55, %56, %57, %58, %59, %60, "
      "%61, %62, %63}, "
      "{%64, %65, %66, %67}, %68, %70, 0, p, 1, 1, 1;\n}\n"
      : "=f"(d[0]), "=f"(d[1]), "=f"(d[2]), "=f"(d[3]), "=f"(d[4]), "=f"(d[5]), "=f"(d[6]), "=f"(d[7]), "=f"(d[8]), "=f"(d[9]), "=f"(d[10]), "=f"(d[11]),
        "=f"(d[12]), "=f"(d[13]), "=f"(d[14]), "=f"(d[15]), "=f"(d[16]), "=f"(d[17]), "=f"(d[18]), "=f"(d[19]), "=f"(d[20]), "=f"(d[21]), "=f"(d[22]),
        "=f"(d[23]), "=f"(d[24]), "=f"(d[25]), "=f"(d[26]), "=f"(d[27]), "=f"(d[28]), "=f"(d[29]), "=f"(d[30]), "=f"(d[31]), "=f"(d[32]), "=f"(d[33]),
        "=f"(d[34]), "=f"(d[35]), "=f"(d[36]), "=f"(d[37]), "=f"(d[38]), "=f"(d[39]), "=f"(d[40]), "=f"(d[41]), "=f"(d[42]), "=f"(d[43]), "=f"(d[44]),
        "=f"(d[45]), "=f"(d[46]), "=f"(d[47]), "=f"(d[48]), "=f"(d[49]), "=f"(d[50]), "=f"(d[51]), "=f"(d[52]), "=f"(d[53]), "=f"(d[54]), "=f"(d[55]),
        "=f"(d[56]), "=f"(d[57]), "=f"(d[58]), "=f"(d[59]), "=f"(d[60]), "=f"(d[61]), "=f"(d[62]), "=f"(d[63])
      : "r"(a0), "r"(a1), "r"(a2), "r"(a3), "l"(db), "r"(scaleD), "r"(meta));
}

constexpr int NB = 16, SQ = 224, DM = 640, NH = 32, SK = 1024, DH = 128;
constexpr int HD = NH * DH;
constexpr int NBETA = 2 * NB;
constexpr int NCTA = 132;
constexpr uint32_t SB0 = 1024;
constexpr int NS = 10;
constexpr int SLOT = 16384;
constexpr int QBUF_OFF = NS * SLOT;
constexpr int NSX = NS + 4;
constexpr int BAR_OFF = NSX * SLOT;
constexpr int BAR_FULL = BAR_OFF;
constexpr int BAR_EMPTY = BAR_OFF + 8 * NSX;
constexpr int BAR_STG = BAR_OFF + 16 * NSX;
constexpr int BAR_OUT = BAR_STG + 32;
constexpr int BAR_DESC = BAR_OUT + 8;
constexpr int BAR_GO = BAR_DESC + 8;
constexpr int BAR_MAIL = BAR_GO + 8;
constexpr int BAR_RDY = BAR_MAIL + 8;
constexpr int DESC_OFF = BAR_RDY + 8 * NSX;
constexpr int EPOCH_OFF = DESC_OFF + 16;
constexpr int TRACE_OFF = EPOCH_OFF + 16;
constexpr int SMEM_BYTES = TRACE_OFF;
constexpr float SM_C = 0.08838834764831845f * 1.4426950408889634f;
constexpr float SUM_HI = 1099511627776.f, SUM_LO = 1.f / 1099511627776.f;
constexpr uint32_t META_QK = 0xEEEE4444u;
constexpr uint32_t META_PV = 0x44EEEE44u;

#define QK_EARLY_MASK 3
#define ST_ORDER 0x2310
#define LAG_BAR 2
#define ST_NOW 8
#define PF_STEP 5
#define KV_WIN_UNITS 2
#define KV_WIN_D 4
#define SF 0xeebf
#define O_STEPS 4
#define KV_WIN_RAMP 4
#define PDEPTH 0
#define KV_WIN_TILES -2
#define PR_KV 2
#define PR_X 2
#define PR_W 2
#define REG_C 232
#define REG_P 24
#define GO_P 4
#define P_POS 216
#define OR 6
#define OR0 0
#define B_LATE 23
#define H_LATE 24
#define RM0 1
#define RM1 0xab
#define RM2 0
#define CLUSTER 1
#define PAIRB 1
#define LATE0 1
#define LATE1 2
#define GO_J 14
#define PR_O 2
#define KG 5
#define PK 44
#define EARLY_MASK 0x3fffu
#define PIECE_TABLE 0x50188016,0x65e88038,0x50321819,0x6c8d1830,0x403f2812,0x80000000,0x50215014,0x695a503c,0x5029b813,0x6c4eb85e,0x501b4815,0x689d4834,0x502b1017,0x6ccc1039,0x50312010,0x80000000,0x500e681b,0x65e8683f,0x502ea011,0x80000000,0x63b1902e,0x80000000,0x63f0603b,0x80000000,0x64ad003d,0x80000000,0x64eca83a,0x80000000,0x5024581c,0x80000000,0x5012b01a,0x6a95b033,0x5011081d,0x6b130837,0x5016701f,0x6c8d7056,0x501ec81e,0x80000000,0x6723302f,0x80000000,0x501b380f,0x80000000,0x67234035,0x80000000,0x500d980e,0x6bd09831,0x56587816,0x80000000,0x50168818,0x80000000,0x57d1c01e,0x80000000

struct Params {
  CUtensorMap x[2][2], wq[2], kv[2][2], wo[2];
  CUtensorMap o_ld[2], o_st[2], out_st[2];
  const __nv_bfloat16* kp[2];
  const __nv_bfloat16* vp[2];
};

constexpr int NPART = 32 * 5, O_BLOCKS = NBETA * 64 + 2 * NPART;
__device__ __align__(128) __nv_bfloat16 g_o[(size_t)O_BLOCKS * SQ * 64];
__device__ unsigned g_cnt[NBETA][8];
__device__ unsigned g_rd[NBETA][8];
__device__ unsigned g_epoch, g_next;
__device__ unsigned g_flag[NPART];

__device__ __forceinline__ uint32_t smem_u32(const void* p) { return (uint32_t)__cvta_generic_to_shared(p); }
__device__ __forceinline__ void mbar_arrive(uint32_t bar) {
  asm volatile("mbarrier.arrive.shared::cta.b64 _, [%0];" ::"r"(bar) : "memory");
}
__device__ __forceinline__ void mbar_arrive_warp(uint32_t bar) {
  asm volatile("{\n.reg .pred p;\nelect.sync _|p, 0xffffffff;\n@p mbarrier.arrive.shared::cta.b64 _, [%0];\n}" ::"r"(bar) : "memory");
}
__device__ __forceinline__ int lane_now() { int l; asm volatile("mov.u32 %0, %%laneid;" : "=r"(l)); return l; }
__device__ __forceinline__ bool mbar_try(uint32_t bar, uint32_t parity) {
  uint32_t ok;
  asm volatile("{\n.reg .pred p;\nmbarrier.try_wait.parity.shared::cta.b64 p, [%1], %2;\nselp.u32 %0, 1, 0, p;\n}"
               : "=r"(ok) : "r"(bar), "r"(parity) : "memory");
  return ok;
}
__device__ __forceinline__ bool mbar_test(uint32_t bar, uint32_t parity) {
  uint32_t ok;
  asm volatile("{\n.reg .pred p;\nmbarrier.test_wait.parity.shared::cta.b64 p, [%1], %2;\nselp.u32 %0, 1, 0, p;\n}"
               : "=r"(ok) : "r"(bar), "r"(parity) : "memory");
  return ok;
}
__device__ __forceinline__ void mbar_wait_w(uint32_t bar, uint32_t parity) {
  uint32_t n = 0;
  while (!__all_sync(0xffffffffu, mbar_try(bar, parity))) {
    if (++n > (1u << 22)) __trap();
  }
}
#define ELECT "{\n.reg .pred p;\nelect.sync _|p, 0xffffffff;\n@p "
__device__ __forceinline__ void tma_st3_hint_w(const CUtensorMap* m, uint32_t src, int c0, int c1, int c2, uint64_t pol) {
  asm volatile(ELECT "cp.async.bulk.tensor.3d.global.shared::cta.bulk_group.L2::cache_hint [%0, {%2, %3, %4}], [%1], %5;\n}"
               ::"l"(m), "r"(src), "r"(c0), "r"(c1), "r"(c2), "l"(pol) : "memory");
}
#define EXPECT(bar, bytes) "mbarrier.arrive.expect_tx.shared::cta.b64 _, [" bar "], " bytes ";\n@p "
__device__ __forceinline__ void tma_ld2_w(uint32_t dst, const CUtensorMap* m, int c0, int c1, uint32_t bar, uint32_t bytes) {
  asm volatile(ELECT EXPECT("%2", "%5") "cp.async.bulk.tensor.2d.shared::cluster.global.mbarrier::complete_tx::bytes [%0], [%1, {%3, %4}], [%2];\n}"
               ::"r"(dst), "l"(m), "r"(bar), "r"(c0), "r"(c1), "r"(bytes) : "memory");
}
__device__ __forceinline__ void tma_ld2_hint_w(uint32_t dst, const CUtensorMap* m, int c0, int c1, uint32_t bar, uint32_t bytes, uint64_t pol) {
  asm volatile(ELECT EXPECT("%2", "%6") "cp.async.bulk.tensor.2d.shared::cluster.global.mbarrier::complete_tx::bytes.L2::cache_hint"
               " [%0], [%1, {%3, %4}], [%2], %5;\n}"
               ::"r"(dst), "l"(m), "r"(bar), "r"(c0), "r"(c1), "l"(pol), "r"(bytes) : "memory");
}
__device__ __forceinline__ void tma_ld3_w(uint32_t dst, const CUtensorMap* m, int c0, int c1, int c2, uint32_t bar, uint32_t bytes) {
  asm volatile(ELECT EXPECT("%2", "%6") "cp.async.bulk.tensor.3d.shared::cluster.global.mbarrier::complete_tx::bytes [%0], [%1, {%3, %4, %5}], [%2];\n}"
               ::"r"(dst), "l"(m), "r"(bar), "r"(c0), "r"(c1), "r"(c2), "r"(bytes) : "memory");
}
__device__ __forceinline__ void tma_ld3_hint_w(uint32_t dst, const CUtensorMap* m, int c0, int c1, int c2, uint32_t bar, uint64_t pol) {
  asm volatile(ELECT EXPECT("%2", "16384") "cp.async.bulk.tensor.3d.shared::cluster.global.mbarrier::complete_tx::bytes.L2::cache_hint"
               " [%0], [%1, {%3, %4, %5}], [%2], %6;\n}"
               ::"r"(dst), "l"(m), "r"(bar), "r"(c0), "r"(c1), "r"(c2), "l"(pol) : "memory");
}
__device__ __forceinline__ void tma_ld_wo_w(uint32_t dst, const CUtensorMap* m, int col, int grp, uint32_t bar) {
  asm volatile(ELECT EXPECT("%2", "16384") "cp.async.bulk.tensor.5d.shared::cluster.global.mbarrier::complete_tx::bytes [%0], [%1, {%3, 0, 0, 0, %4}], [%2];\n"
               "@p cp.async.bulk.tensor.5d.shared::cluster.global.mbarrier::complete_tx::bytes [%5], [%1, {%6, 0, 0, 0, %4}], [%2];\n}"
               ::"r"(dst), "l"(m), "r"(bar), "r"(col), "r"(grp), "r"(dst + 8192), "r"(col + 64) : "memory");
}
__device__ __forceinline__ void mbar_arrive8_w(uint32_t bar) {
  asm volatile(ELECT "mbarrier.arrive.shared::cta.b64 _, [%0], 8;\n}" ::"r"(bar) : "memory");
}
__device__ __forceinline__ uint32_t peer(uint32_t a) { uint32_t r; asm("mapa.shared::cluster.u32 %0, %1, %2;" : "=r"(r) : "r"(a), "r"(~blockIdx.x & 1)); return r; }
__device__ __forceinline__ void tma_ld2_both_w(uint32_t dst, const CUtensorMap* m, int c0, int c1, uint32_t bar, uint32_t bytes) {
  asm volatile(ELECT EXPECT("%2", "%5") "cp.async.bulk.tensor.2d.shared::cluster.global.mbarrier::complete_tx::bytes.multicast::cluster"
               " [%0], [%1, {%3, %4}], [%2], %6;\n}"
               ::"r"(dst), "l"(m), "r"(bar), "r"(c0), "r"(c1), "r"(bytes), "h"((uint16_t)3) : "memory");
}
__device__ __forceinline__ void tma_ld2_both_hint_w(uint32_t dst, const CUtensorMap* m, int c0, int c1, uint32_t bar, uint32_t bytes, uint64_t pol) {
  asm volatile(ELECT EXPECT("%2", "%6") "cp.async.bulk.tensor.2d.shared::cluster.global.mbarrier::complete_tx::bytes.multicast::cluster.L2::cache_hint"
               " [%0], [%1, {%3, %4}], [%2], %7, %5;\n}"
               ::"r"(dst), "l"(m), "r"(bar), "r"(c0), "r"(c1), "l"(pol), "r"(bytes), "h"((uint16_t)3) : "memory");
}
__device__ __forceinline__ void bulk_commit() { asm volatile("cp.async.bulk.commit_group;" ::: "memory"); }
template <int N> __device__ __forceinline__ void bulk_wait_read() { asm volatile("cp.async.bulk.wait_group.read %0;" ::"n"(N) : "memory"); }
__device__ __forceinline__ void wg_fence() { asm volatile("wgmma.fence.sync.aligned;" ::: "memory"); }
__device__ __forceinline__ void wg_commit() { asm volatile("wgmma.commit_group.sync.aligned;" ::: "memory"); }
template <int N> __device__ __forceinline__ void wg_wait() { asm volatile("wgmma.wait_group.sync.aligned %0;" ::"n"(N) : "memory"); }
__device__ __forceinline__ void fence_async_smem() { asm volatile("fence.proxy.async.shared::cta;" ::: "memory"); }
__device__ __forceinline__ void bar_sync(int id, int n) { asm volatile("bar.sync %0, %1;" ::"r"(id), "r"(n) : "memory"); }
__device__ __forceinline__ void touch(float& a) { asm volatile("neg.f32 %0, %0;" : "+f"(a)); }
__device__ __forceinline__ void touch(uint32_t& a) { asm volatile("not.b32 %0, %0;" : "+r"(a)); }
template <typename T, int N> __device__ __forceinline__ void touch(T (&a)[N]) {
#pragma unroll
  for (int i = 0; i < N; i++) touch(a[i]);
}
template <int ID, typename... A> __device__ __forceinline__ void sched_fence(uint32_t x, A&... a) {
  if (!((SF >> ID) & 1)) return;
  asm volatile("" : "+r"(x)::"memory");
#pragma unroll 1
  for (; __builtin_expect(x >= 100 + ID, 0); x >>= 1) { (touch(a), ...); __nanosleep(x); }
}
template <int N> __device__ __forceinline__ void reg_fence(float (&a)[N]) {
#pragma unroll
  for (int i = 0; i < N; i++) asm volatile("" : "+f"(a[i])::"memory");
}
template <int N> __device__ __forceinline__ void reg_fence(uint32_t (&a)[N]) {
#pragma unroll
  for (int i = 0; i < N; i++) asm volatile("" : "+r"(a[i])::"memory");
}
__device__ __forceinline__ float ex2(float x) { float y; asm("ex2.approx.ftz.f32 %0, %1;" : "=f"(y) : "f"(x)); return y; }
__device__ __forceinline__ uint32_t pack_bf16(float lo, float hi) {
  uint32_t r; asm("cvt.rn.bf16x2.f32 %0, %1, %2;" : "=r"(r) : "f"(hi), "f"(lo)); return r;
}
__device__ __forceinline__ void stsm4(uint32_t a, uint32_t r0, uint32_t r1, uint32_t r2, uint32_t r3) {
  asm volatile("stmatrix.sync.aligned.m8n8.x4.shared.b16 [%0], {%1, %2, %3, %4};" ::"r"(a), "r"(r0), "r"(r1), "r"(r2), "r"(r3) : "memory");
}
__device__ __forceinline__ void stsm4t(uint32_t a, uint32_t r0, uint32_t r1, uint32_t r2, uint32_t r3) {
  asm volatile("stmatrix.sync.aligned.m8n8.x4.trans.shared.b16 [%0], {%1, %2, %3, %4};" ::"r"(a), "r"(r0), "r"(r1), "r"(r2), "r"(r3) : "memory");
}
__device__ __forceinline__ void ldsm4(uint32_t a, uint32_t& r0, uint32_t& r1, uint32_t& r2, uint32_t& r3) {
  asm volatile("ldmatrix.sync.aligned.m8n8.x4.shared.b16 {%0, %1, %2, %3}, [%4];" : "=r"(r0), "=r"(r1), "=r"(r2), "=r"(r3) : "r"(a) : "memory");
}
__device__ __forceinline__ void sts16(uint32_t a, uint32_t v) { asm volatile("st.shared.u16 [%0], %1;" ::"r"(a), "h"((uint16_t)v) : "memory"); }
__device__ __forceinline__ void mma16816(float& c0, float& c1, float& c2, float& c3, uint32_t a0, uint32_t a1, uint32_t a2, uint32_t a3,
                                         uint32_t b0, uint32_t b1) {
  asm volatile("mma.sync.aligned.m16n8k16.row.col.f32.bf16.bf16.f32 {%0, %1, %2, %3}, {%4, %5, %6, %7}, {%8, %9}, {%0, %1, %2, %3};"
               : "+f"(c0), "+f"(c1), "+f"(c2), "+f"(c3) : "r"(a0), "r"(a1), "r"(a2), "r"(a3), "r"(b0), "r"(b1));
}
__device__ __forceinline__ uint32_t sdesc(uint32_t addr, uint32_t lbo) { return (addr >> 4) + ((lbo >> 4) << 16); }
__device__ __forceinline__ uint64_t desc64(uint32_t lo, uint32_t hi) { uint64_t d; asm("mov.b64 %0, {%1, %2};" : "=l"(d) : "r"(lo), "r"(hi)); return d; }
__device__ __forceinline__ void dadd(uint64_t& d, uint32_t inc) {
  asm("{\n.reg .b32 l, h;\nmov.b64 {l, h}, %0;\nadd.u32 l, l, %1;\nmov.b64 %0, {l, h};\n}" : "+l"(d) : "r"(inc));
}

struct Ring {
  uint32_t slot, phase, xp;
  __device__ __forceinline__ void uniform() {
    slot = __shfl_sync(0xffffffffu, slot, 0); phase = __shfl_sync(0xffffffffu, phase, 0); xp = __shfl_sync(0xffffffffu, xp, 0);
  }
  __device__ __forceinline__ void next() { if (++slot == NS) { slot = 0; phase ^= 1; } }
  __device__ __forceinline__ void next_if(bool p) { slot += p; if (slot == NS) { slot = 0; phase ^= 1; } }
};
__device__ __forceinline__ uint32_t borrow(int ks, int n) {
  const int k = ks + 1;
  return k >= 4 && !(k & 2) && k < n ? k & 1 : 2;
}

constexpr uint32_t Q_RANGES = NBETA * NH + __builtin_popcount(EARLY_MASK) * 5, Q_ALL = NBETA * (NH + 5);
constexpr int NRANGE = NCTA / 5;
struct Work { int kind, mode, k0, nsteps, range, beta, sub; };
struct Sched { uint16_t queue[Q_ALL]; uint32_t piece[NRANGE + 1][4]; };
constexpr Sched make_sched() {
  Sched s{};
  int q = 0, a = 0;
  for (int t = 0, e = 0; a < NBETA * NH; t++) {
    for (; e < NBETA && 8 * (e & ~PAIRB) + PK <= t && a >= P_POS; e++)
      for (int col = 0; col < 5 && (EARLY_MASK >> e & 1); col++) s.queue[q++] = 0x8000 | (e & 1 ? 4 - col : col) << 8 | e;
    for (int b = 0; b < NBETA; b++)
      for (int h = 0; h < NH; h++)
        if ((b >= B_LATE && h >= H_LATE ? 300 + b : 8 * (b & ~PAIRB) + KG * (h >> 2)) == t) { s.queue[q++] = b << 5 | h; a++; }
  }
  for (int b = 0; b < NBETA; b++)
    for (int col = 0; col < 5 && !(EARLY_MASK >> b & 1); col++) s.queue[q++] = 0x8000 | col << 8 | b;
  constexpr uint32_t T[NRANGE * 2] = {PIECE_TABLE};
  for (int g = 0; g <= NRANGE; g++)
    for (int n = 0; n < 4; n++) s.piece[g][n] = g < NRANGE && n < 2 ? T[2 * g + n] : 2u << 30;
  return s;
}
__constant__ Sched c_sched = make_sched();
constexpr int N_EARLY = __builtin_popcount(EARLY_MASK);
constexpr bool reuse_ok() {
  const Sched s = make_sched();
  int first[NBETA + OR] = {};
  for (int q = Q_RANGES - 1; q >= 0; q--) if (!(s.queue[q] & 0x8000)) first[s.queue[q] >> 5] = q;
  for (int q = 0; q < Q_RANGES; q++) if ((s.queue[q] & 0x8000) && (s.queue[q] & 31) >= OR0 && q - first[(s.queue[q] & 31) + OR] > NCTA - 32) return false;
  return true;
}
static_assert(reuse_ok());
template <bool SIMPLE> __device__ __forceinline__ bool o_reuse(uint32_t b) { return !SIMPLE && b - (OR0 + OR) < N_EARLY - OR0; }
template <bool SIMPLE> __device__ __forceinline__ uint32_t o_slot(uint32_t b) { return o_reuse<SIMPLE>(b) ? OR0 + (b - OR0) % OR : b; }
__device__ __forceinline__ Work decode(uint32_t d) {
  Work w;
  w.kind = d >> 30; if (w.kind == 3) w.kind = 1;
  w.mode = (d >> 28) & 3; w.k0 = (d >> 22) & 63;
  if (w.kind == 0) { w.beta = (d >> 5) & 31; w.sub = d & 31; w.nsteps = DM / 64; }
  else { w.beta = d & 31; w.sub = (d >> 8) & 7; w.nsteps = ((d >> 16) & 63) + 1; }
  w.range = ((d >> 11) & 31) * 5 + w.sub;
  return w;
}

__device__ __forceinline__ bool reached(const unsigned* cnt, unsigned target) {
  unsigned v;
  asm volatile("ld.acquire.gpu.global.u32 %0, [%1];" : "=r"(v) : "l"(cnt) : "memory");
  return (int)(v - target) >= 0;
}
__device__ __forceinline__ void wait_count(const unsigned* cnt, unsigned target) {
  unsigned n = 0;
  while (!__all_sync(0xffffffffu, reached(cnt, target))) { if (++n > (1u << 24)) __trap(); }
}
__device__ __forceinline__ uint32_t lds(uint32_t a) { uint32_t v; asm volatile("ld.volatile.shared.u32 %0, [%1];" : "=r"(v) : "r"(a) : "memory"); return v; }

#define TRACE(u, e)
#define T3(u, e)
#define T2C(u, e)
#define T2P(u, r, e)
#define TTAIL(k)
#define TCLK(k)
#define TO -1
#define TRACE_O(k) if (TO == k) TRACE(i, 5)
#define TRACE_P(u, e)
#define TRACE_IN(u, e)

struct Ctx {
  uint32_t sb;
  int wg, warp;
  uint32_t mqk, mpv;
  bool lead;
  int lane0, lane;
  int src;
};
template <int N> __device__ __forceinline__ uint32_t dhi(uint32_t lo) { return 0x40000040u + (lo >> (26 + N)); }
__device__ __forceinline__ void release(const Ctx& c, uint32_t slot) {
  if (c.lead) mbar_arrive(c.sb + BAR_EMPTY + slot * 8);
}
__device__ __forceinline__ uint32_t acquire(const Ctx& c, Ring& r, bool have = false) {
  const uint32_t s = r.slot;
  if (!have) mbar_wait_w(c.sb + BAR_FULL + s * 8, r.phase);
  r.next();
  return s;
}
__device__ __forceinline__ void mbar_wait2_w(uint32_t b0, uint32_t p0, uint32_t b1, uint32_t p1) {
  uint32_t n = 0;
  while (!__all_sync(0xffffffffu, mbar_try(b0, p0) & mbar_try(b1, p1))) {
    if (++n > (1u << 22)) __trap();
  }
}
__device__ __forceinline__ void mbar_wait3_w(uint32_t b0, uint32_t p0, uint32_t b1, uint32_t p1, uint32_t b2, uint32_t p2) {
  uint32_t n = 0;
  while (!__all_sync(0xffffffffu, mbar_try(b0, p0) & mbar_try(b1, p1) & mbar_try(b2, p2))) {
    if (++n > (1u << 22)) __trap();
  }
}
__device__ __forceinline__ void acquire2(const Ctx& c, Ring& r, uint32_t& s0, uint32_t& s1, bool have = false) {
  const uint32_t p0 = r.phase;
  s0 = r.slot; r.next(); s1 = r.slot;
  if (!have) mbar_wait2_w(c.sb + BAR_FULL + s0 * 8, p0, c.sb + BAR_FULL + s1 * 8, r.phase);
  r.next();
}
template <int N>
__device__ __forceinline__ bool peek(const Ctx& c, Ring r) {
  bool ok = true;
#pragma unroll
  for (int k = 0; k < N; k++) { ok &= mbar_test(c.sb + BAR_FULL + r.slot * 8, r.phase); r.next(); }
  return ok;
}
__device__ __forceinline__ void staged(const Ctx& c, int part) {
  fence_async_smem();
  __syncwarp();
  mbar_arrive_warp(c.sb + BAR_STG + c.wg * 16 + part * 8);
}

template <int WG, bool FIRST, int H>
__device__ __forceinline__ void proj_half(const Ctx& c, float (&acc)[64], uint32_t w, uint32_t x, uint32_t sw) {
  uint64_t dx = desc64((SB0 + x * SLOT + (WG ? 0 : H * 8192)) >> 4, dhi<0>(x) + sw);
  uint64_t dw = desc64(WG ? (SB0 + w * SLOT + H * 8192) >> 4 : sdesc(SB0 + w * SLOT, 8192), dhi<1>(x));
  wg_fence();
  if (WG) { if (FIRST) wgmma_proj96_init(acc, dw, dx, 0); else wgmma_proj96(acc, dw, dx, 1); }
  else { if (FIRST) wgmma_proj_init(acc, dx, dw, 0); else wgmma_proj(acc, dx, dw, 1); }
#pragma unroll
  for (int k = 1; k < 4; k++) {
    dadd(dx, k == 2 ? 2 + (sw >> 30) * 28 : 2); dadd(dw, 128);
    if (WG) wgmma_proj96(acc, dw, dx, 1); else wgmma_proj(acc, dx, dw, 1);
  }
  wg_commit();
}

__device__ __forceinline__ void proj_store16(uint32_t a, const float* f, float sc) {
  stsm4t(a, pack_bf16(f[0] * sc, f[1] * sc), pack_bf16(f[2] * sc, f[3] * sc), pack_bf16(f[4] * sc, f[5] * sc), pack_bf16(f[6] * sc, f[7] * sc));
}

__device__ __forceinline__ uint32_t stage_off(const Ctx& c) {
  const int lane = c.lane, mi = lane >> 3, r8 = lane & 7;
  return ((mi >> 1) * 8 + r8) * 128 + (((2 * c.warp + (mi & 1)) ^ r8) << 4);
}
__device__ __forceinline__ uint32_t q3_swz(uint32_t r8) { return ((r8 & 3) << 1) | (r8 >> 2); }
template <int H>
__device__ __forceinline__ void stage_t2(const Ctx& c, const float (&a)[64], float sc) {
  const uint32_t base = c.sb + QBUF_OFF + 2 * 16384 + H * 8192 + stage_off(c);
#pragma unroll
  for (int jj = 0; jj < 4; jj++) proj_store16(base + jj * 2048, &a[jj * 8], sc);
}
template <int H, bool IS_Q>
__device__ __forceinline__ void stage_t3(const Ctx& c, const float (&a)[64], float sc) {
  const uint32_t off = stage_off(c), r8 = (off >> 7) & 7;
  const uint32_t t3 = c.sb + QBUF_OFF + 3 * 16384 + H * 4096 + (IS_Q ? off ^ ((r8 ^ q3_swz(r8)) << 4) : off);
  proj_store16(t3, &a[32], sc);
  proj_store16(t3 + 2048, &a[40], sc);
}

template <int WG, int h>
__device__ __forceinline__ void load_part(const Ctx& c, Ring r, uint32_t (&q)[32]) {
  uint32_t n = 0;
  while (!h && !__all_sync(0xffffffffu, peek<4>(c, r))) {
    if (++n > (1u << 26)) __trap();
  }
  const int lane = c.lane, mi = lane >> 3, r8 = lane & 7;
  if (WG) { r.next(); r.next(); }
  const uint32_t off = c.sb + (WG ? stage_off(c) : (16 * c.warp + (mi & 1) * 8 + r8) * 128), t0 = off + r.slot * SLOT;
  r.next();
  const uint32_t t1 = off + r.slot * SLOT;
#pragma unroll
    for (int jj = 0; jj < (WG ? 6 : 8); jj++) {
      uint32_t* p = &q[4 * jj];
      if (WG) asm volatile("ldmatrix.sync.aligned.m8n8.x4.trans.shared.b16 {%0, %1, %2, %3}, [%4];" : "=r"(p[0]), "=r"(p[1]), "=r"(p[2]), "=r"(p[3])
                           : "r"((jj < 4 ? t0 + h * 8192 : t1 + h * 4096) + (jj & 3) * 2048) : "memory");
      else ldsm4((h ? t1 : t0) + (jj >> 2) * 8192 + (((((2 * jj) & 7) + (mi >> 1)) ^ r8) << 4), p[0], p[1], p[2], p[3]);
    }
}
template <int WG>
__device__ __forceinline__ void add_part(const Ctx& c, const uint32_t (&q)[32], float (&a)[64]) {
  const uint32_t one = (c.lane >> 3) == (c.lane & 3) ? 0x3f80u << (c.lane & 4) * 4 : 0;
#pragma unroll
  for (int i = 0; i < (WG ? 12 : 16); i++)
    asm("mma.sync.aligned.m16n8k8.row.col.f32.bf16.bf16.f32 {%0, %1, %2, %3}, {%4, %5}, {%6}, {%0, %1, %2, %3};"
        : "+f"(a[4 * i]), "+f"(a[4 * i + 1]), "+f"(a[4 * i + 2]), "+f"(a[4 * i + 3]) : "r"(q[2 * i]), "r"(q[2 * i + 1]), "r"(one));
}

__device__ __forceinline__ void trace_dump(const Ctx& c) {
}
struct RowSum { float l0, l1; };
__device__ __forceinline__ const char* o_addr(uint32_t item, int row, int lane) {
  return reinterpret_cast<const char*>(g_o) + (((item >> 10) * (2 * SQ) + row) * 128 + (lane ^ (lane >> 3)) * 16);
}
__device__ __forceinline__ void o_stg(const char* p, int i, const uint32_t* q) {
  asm volatile("st.global.v4.b32 [%0], {%1, %2, %3, %4};"
               ::"l"(p + (i >> 1) * (SQ * 128) + (i & 1) * 512), "r"(q[0]), "r"(q[1]), "r"(q[2]), "r"(q[3]) : "memory");
}
template <int MODE, int I0 = 0, int NI = 4>
__device__ __forceinline__ void o_emit(const char* p, const float (&o)[64], float inv) {
#pragma unroll
  for (int i = I0; i < I0 + NI; i++) {
    uint32_t q[4];
#pragma unroll
    for (int j = 0; j < 4; j++) q[j] = pack_bf16(o[16 * i + 4 * j + 2 * MODE] * inv, o[16 * i + 4 * j + 2 * MODE + 1] * inv);
    o_stg(p, i, q);
  }
}
__device__ __forceinline__ void o_done(const Ctx& c) {
  __syncwarp();
  mbar_arrive_warp(c.sb + BAR_OUT);
  __syncwarp();
}
template <int WG>
__device__ __forceinline__ void o_first(const Ctx& c, uint32_t item, float (&o)[64], const RowSum& inv, uint32_t (&q)[32]) {
  const char* p = o_addr(item, WG ? 192 + 8 * c.warp : 64 + 16 * c.warp, c.lane);
  reg_fence(o);
#pragma unroll
  for (int j = 0; j < 16; j++) {
    if (WG) q[j] = pack_bf16((o[4 * j] + o[4 * j + 2]) * inv.l0, (o[4 * j + 1] + o[4 * j + 3]) * inv.l0);
    else q[j] = pack_bf16(o[4 * j] * inv.l0, o[4 * j + 1] * inv.l0);
    if (!WG && (j & 3) == 3 && (j >> 2) < 8 - LATE0) o_stg(p, j >> 2, q + j - 3);
  }
#pragma unroll
  for (int j = 0; j < 16; j++) {
    if (!WG) q[16 + j] = pack_bf16(o[4 * j + 2] * inv.l1, o[4 * j + 3] * inv.l1);
    if ((j & 3) == 3 && (j >> 2) < 4 - (WG ? LATE1 : LATE0)) o_stg(WG ? p : p + 1024, j >> 2, q + (WG ? 0 : 16) + j - 3);
  }
}
template <int WG>
__device__ __forceinline__ void o_rest(const Ctx& c, uint32_t item, uint32_t (&q)[32]) {
  const char* p = o_addr(item, WG ? 192 + 8 * c.warp : 64 + 16 * c.warp, c.lane);
#pragma unroll
  for (int i = WG ? 4 - LATE1 : 8 - LATE0; i < (WG ? 4 : 8); i++) o_stg(p + (i >> 2) * 1024, i & 3, q + 4 * i);
}
template <int K0, int K1>
__device__ __forceinline__ void o_piece(const Ctx& c, const char* p, int k, const float (&o)[64], const RowSum& inv) {
  constexpr int NI = 8 / O_STEPS, M = K0 * NI / 4;
  if constexpr (K1 - K0 == 1) {
    o_emit<M, K0 * NI % 4, NI>(p + M * 1024, o, M ? inv.l1 : inv.l0);
    if (K1 == O_STEPS) o_done(c);
  } else {
    if (k <= (K0 + K1) / 2) o_piece<K0, (K0 + K1) / 2>(c, p, k, o, inv); else o_piece<(K0 + K1) / 2, K1>(c, p, k, o, inv);
  }
}
template <int WG>
__device__ __forceinline__ void o_second(const Ctx& c, uint32_t item, int k, float (&o)[64], const RowSum& inv) {
  reg_fence(o);
  o_piece<0, O_STEPS>(c, o_addr(item, 128 * WG + 16 * c.warp, c.lane0 + (k >> 8)), k, o, inv);
}
template <int WG>
__device__ __forceinline__ void release_q(const Ctx& c) {
#pragma unroll
  for (int t = 0; t < 2; t++)
    if (c.lead) asm volatile("mbarrier.arrive.shared::cta.b64 _, [%0], 2;" ::"r"(c.sb + BAR_EMPTY + (NS + 2 * WG + t) * 8) : "memory");
  __syncwarp();
}
struct Slots { uint32_t w, x, o, po; };
template <int WG>
__device__ __forceinline__ void acc_fence(float (&a)[64]) {
#pragma unroll
  for (int i = 0; i < (WG ? 48 : 64); i++) asm volatile("" : "+f"(a[i])::"memory");
}
template <int WG>
__device__ __forceinline__ void begin_acquire(const Ctx& c, Ring& r, Slots& h, bool wait) {
  const uint32_t s0 = r.slot, p0 = r.phase, f = c.sb + BAR_FULL;
  r.next();
  const uint32_t p1 = r.phase;
  h.w = r.slot; r.next();
  h.x = WG ? r.slot : s0; h.o = WG ? s0 : r.slot; h.po = r.phase;
  if (wait) { if (WG) mbar_wait3_w(f + s0 * 8, p0, f + h.w * 8, p1, f + h.x * 8, r.phase); else mbar_wait2_w(f + s0 * 8, p0, f + h.w * 8, p1); }
  r.next();
}
template <int WG>
__device__ __forceinline__ void proj_begin(const Ctx& c, Ring& r, float (&a0)[64], Slots& h, bool wait, uint32_t sw) {
  begin_acquire<WG>(c, r, h, wait);
  proj_half<WG, true, 0>(c, a0, h.w, h.x, sw);
  if (WG) release(c, h.o);
}
template <int WG>
__device__ __forceinline__ void proj_main(Ctx& c, Ring& r, float (&a0)[64], float (&a1)[64], Slots& h, int n, uint32_t sw, int unit,
                                          uint32_t item, int nq, float (&o1)[64], const RowSum& inv) {
  constexpr bool DEEP = (PDEPTH >> WG) & 1;
  T2C(unit, 3);
  int ks = 1;
#pragma unroll 1
  do {
    const Slots p = h;
    const uint32_t b = borrow(ks, n), tile = NS + (WG ? 3 - b : b), f = c.sb + BAR_FULL;
    const uint32_t s0 = b != 2 ? tile : r.slot, p0 = b != 2 ? (r.xp >> b) & 1 : r.phase;
    r.next_if(b == 2);
    const uint32_t p1 = r.phase;
    h.w = r.slot; r.next();
    const uint32_t s2 = b != 2 ? tile : r.slot;
    h.po = b != 2 ? p0 : r.phase;
    r.next_if(b == 2);
    r.xp ^= 1 << b;
    h.x = WG ? s2 : s0; h.o = WG ? s0 : s2;
    mbar_wait3_w(f + s0 * 8, p0, f + h.w * 8, p1, f + (WG ? s2 : p.o) * 8, WG ? h.po : p.po);
    if (ks < 10) T2C(unit, ks * 4);
    if (DEEP) {
      proj_half<WG, false, 0>(c, a0, h.w, h.x, sw);
      release(c, WG ? h.o : p.o);
      if (ks < 10) T2C(unit, ks * 4 + 1);
      wg_wait<1>();
      if (ks < 10) T2C(unit, ks * 4 + 2);
      release(c, p.x); release(c, p.w);
    } else {
      release(c, WG ? h.o : p.o);
      wg_wait<0>();
      release(c, p.x); release(c, p.w);
      if (ks < 10) T2C(unit, ks * 4 + 1);
      proj_half<WG, false, 0>(c, a0, h.w, h.x, sw);
      if (ks < 10) T2C(unit, ks * 4 + 2);
    }
    proj_half<WG, false, 1>(c, a1, h.w, h.x, sw);
    if (ks < 10) T2C(unit, ks * 4 + 3);
    if (ks <= nq) o_second<WG>(c, item, ks, o1, inv);
  } while (++ks != n);
  {
    const uint32_t e0 = c.sb + BAR_EMPTY + (NS + 3 * WG) * 8, e1 = c.sb + BAR_EMPTY + (NS + 1 + WG) * 8;
    const uint32_t p0 = (r.xp ^ unit ^ 1) & 1, p1 = ((r.xp >> 1) ^ unit ^ 1) & 1;
    const uint32_t k0 = sw ? e0 : c.sb + BAR_FULL + r.slot * 8, pk = sw ? p0 : r.phase;
    uint32_t cnt = 0;
    while (!__all_sync(0xffffffffu, mbar_try(e0, p0) & mbar_try(e1, p1) & mbar_try(k0, pk) & (WG || mbar_try(c.sb + BAR_FULL + h.o * 8, h.po)))) {
      if (++cnt > (1u << 22)) __trap();
    }
  }
  c.lane = c.lane0 + (h.w >> 5);
  if (!WG) release(c, h.o);
}
template <int WG>
__device__ __forceinline__ void proj_end(const Ctx& c, float (&a1)[64], const Slots& h) {
  wg_wait<0>();
  acc_fence<WG>(a1);
  release(c, h.x); release(c, h.w);
}
__device__ __forceinline__ uint32_t get_desc(const Ctx& c, int i) {
  uint32_t d;
  mbar_wait_w(c.sb + BAR_DESC, (i - 1) & 1);
  asm volatile("ld.volatile.shared.u32 %0, [%1];" : "=r"(d) : "r"(c.sb + DESC_OFF + (i & 3) * 4) : "memory");
  return __shfl_sync(0xffffffffu, d, 0);
}

__device__ __forceinline__ float quad_max(float x) {
  x = fmaxf(x, __shfl_xor_sync(0xffffffffu, x, 1));
  return fmaxf(x, __shfl_xor_sync(0xffffffffu, x, 2));
}
__device__ __forceinline__ float quad_sum(float x) {
  x += __shfl_xor_sync(0xffffffffu, x, 1);
  return x + __shfl_xor_sync(0xffffffffu, x, 2);
}
template <bool SP, bool FIRST>
__device__ __forceinline__ void exps(const Ctx& c, const float (&s)[32], uint32_t (&p)[SP ? 8 : 16], RowSum& st) {
  if constexpr (SP) {
    uint32_t q[8];
    float t;
#pragma unroll
    for (int j = 0; j < 8; j++) {
      const float e0 = ex2(s[4 * j] + s[4 * j + 2]), e1 = ex2(s[4 * j + 1] + s[4 * j + 3]);
      if (j == 0) t = e0 + e1; else t += e0 + e1;
      q[j] = pack_bf16(e0, e1);
    }
    const bool odd = c.src & 2;
#pragma unroll
    for (int g = 0; g < 4; g++) {
      p[2 * g] = __shfl_sync(0xffffffffu, odd ? q[2 * g + 1] : q[2 * g], c.src);
      p[2 * g + 1] = __shfl_sync(0xffffffffu, odd ? q[2 * g] : q[2 * g + 1], c.src ^ 1);
    }
    st.l0 = FIRST ? t : st.l0 + t;
  } else {
    float t0, t1;
#pragma unroll
    for (int j = 0; j < 8; j++) {
      const float e0 = ex2(s[4 * j]), e1 = ex2(s[4 * j + 1]), e2 = ex2(s[4 * j + 2]), e3 = ex2(s[4 * j + 3]);
      if (j == 0) { t0 = e0 + e1; t1 = e2 + e3; } else { t0 += e0 + e1; t1 += e2 + e3; }
      p[2 * j] = pack_bf16(e0, e1);
      p[2 * j + 1] = pack_bf16(e2, e3);
    }
    st.l0 = FIRST ? t0 : st.l0 + t0;
    st.l1 = FIRST ? t1 : st.l1 + t1;
  }
}
template <bool SP>
__device__ __forceinline__ bool finish_sums(RowSum& st) {
  const float a = quad_sum(st.l0), b = SP ? a : quad_sum(st.l1);
  st.l0 = __fdividef(1.f, a); st.l1 = __fdividef(1.f, b);
  return !(a >= SUM_LO && a <= SUM_HI && b >= SUM_LO && b <= SUM_HI);
}
template <bool SP, bool INIT, int SITE, bool COMMIT = true, int RM = 0>
__device__ __forceinline__ void issue_qk(const Ctx& c, float (&s)[32], const uint32_t (&qs)[32], uint32_t dq, uint32_t dk) {
  uint64_t a = desc64(dq, dhi<SITE & 1>(dk)), b = desc64(dk, dhi<1 - (SITE & 1)>(dk));
  if (SP) {
    if (INIT) wgmma_qk_sp_init(s, qs[0], qs[1], qs[2], qs[3], b, 0, c.mqk); else wgmma_qk_sp(s, qs[0], qs[1], qs[2], qs[3], b, 0, c.mqk);
#pragma unroll
    for (int k = 1; k < 4; k++) { dadd(b, k == 2 ? 508 : 4); wgmma_qk_sp(s, qs[4 * k], qs[4 * k + 1], qs[4 * k + 2], qs[4 * k + 3], b, 1, c.mqk); }
  } else {
    if (RM & 1) wgmma_qk_rs(s, qs[0], qs[1], qs[2], qs[3], b, 0); else if (INIT) wgmma_qk_init(s, a, b, 0); else wgmma_qk(s, a, b, 0);
#pragma unroll
    for (int k = 1; k < 8; k++) {
      dadd(a, k == 4 ? 506 : 2); dadd(b, k == 4 ? 506 : 2);
      if (RM >> k & 1) wgmma_qk_rs(s, qs[4 * k], qs[4 * k + 1], qs[4 * k + 2], qs[4 * k + 3], b, 1); else wgmma_qk(s, a, b, 1);
    }
  }
  if (COMMIT) wg_commit();
}
template <bool SP, bool ACC, int SITE, bool SPLIT = false>
__device__ __forceinline__ void issue_pv(const Ctx& c, float (&o)[64], const uint32_t (&p)[SP ? 8 : 16], uint32_t dv) {
  uint64_t b = desc64(dv, dhi<SITE & 1>(dv));
  if constexpr (SP) {
    if (ACC) wgmma_pv_sp(o, p[0], p[1], p[2], p[3], b, 1, c.mpv); else wgmma_pv_sp_init(o, p[0], p[1], p[2], p[3], b, 0, c.mpv);
    if (SPLIT) wg_commit();
    dadd(b, 256);
    wgmma_pv_sp(o, p[4], p[5], p[6], p[7], b, 1, c.mpv);
  } else {
    if (ACC) wgmma_pv(o, p[0], p[1], p[2], p[3], b, 1); else wgmma_pv_init(o, p[0], p[1], p[2], p[3], b, 0);
#pragma unroll
    for (int k = 1; k < 4; k++) { dadd(b, 128); wgmma_pv(o, p[4 * k], p[4 * k + 1], p[4 * k + 2], p[4 * k + 3], b, 1); }
  }
  wg_commit();
}
__device__ __forceinline__ void pack_rows(const float (&o)[64], float sc, uint32_t (&q)[32]) {
#pragma unroll
  for (int j = 0; j < 32; j++) q[j] = pack_bf16(o[2 * j] * sc, o[2 * j + 1] * sc);
}
template <int MASK = 255>
__device__ __forceinline__ void stage_rows(const Ctx& c, uint32_t tile_addr, const uint32_t (&q)[32]) {
  const int lane = c.lane, mi = lane >> 3, r8 = lane & 7;
  const uint32_t row_addr = tile_addr + (16 * c.warp + (mi & 1) * 8 + r8) * 128;
#pragma unroll
  for (int jj = 0; jj < 8; jj++)
    if (MASK >> jj & 1) stsm4(row_addr + (jj >> 2) * 8192 + (((((2 * jj) & 7) + (mi >> 1)) ^ r8) << 4), q[4 * jj], q[4 * jj + 1], q[4 * jj + 2], q[4 * jj + 3]);
}
__device__ __forceinline__ void stage_rows(const Ctx& c, uint32_t tile_addr, const float (&o)[64], float sc) {
  uint32_t q[32];
  pack_rows(o, sc, q);
  stage_rows(c, tile_addr, q);
}
template <int WG, int H>
__device__ __forceinline__ void stage_out(const Ctx& c, const float (&a)[64]) {
  if (WG) { stage_t3<H, false>(c, a, 1.f); if (H) staged(c, 0); stage_t2<H>(c, a, 1.f); }
  else stage_rows(c, c.sb + QBUF_OFF + H * 16384, a, 1.f);
  if (H || !WG) staged(c, H);
}
template <int SITE>
__device__ __forceinline__ void issue_qk_rs(float (&s)[32], uint32_t (&q)[32], uint32_t dk) {
  uint64_t b = desc64(dk, dhi<SITE>(dk));
  reg_fence(q);
  wg_fence();
  wgmma_qk_rs_init(s, q[0], q[1], q[2], q[3], b, 0);
#pragma unroll
  for (int k = 1; k < 8; k++) { dadd(b, k == 4 ? 506 : 2); wgmma_qk_rs(s, q[4 * k], q[4 * k + 1], q[4 * k + 2], q[4 * k + 3], b, 1); }
  wg_commit();
}

__device__ __forceinline__ void redo_tile(const Ctx& c, uint32_t q_addr, uint32_t half, const __nv_bfloat16* kp, const __nv_bfloat16* vp,
                                          uint32_t item, int row) {
  float o[64];
  const int lane = lane_now(), g = lane >> 2, cc = lane & 3, mi = lane >> 3, r8 = lane & 7;
  const uint32_t qa = q_addr + (half == 4096 ? 8 * c.warp + r8 : 16 * c.warp + (mi & 1) * 8 + r8) * 128, swz = half == 4096 ? q3_swz(r8) : r8;
  const uint32_t* kq = reinterpret_cast<const uint32_t*>(kp + g * DH) + cc;
  const unsigned short* vq = reinterpret_cast<const unsigned short*>(vp + 2 * cc * DH) + g;
  float m0 = -INFINITY, m1 = -INFINITY, l0 = 0.f, l1 = 0.f;
#pragma unroll
  for (int i = 0; i < 64; i++) o[i] = 0.f;
#pragma unroll 1
  for (int kb = 0; kb < SK / 16; kb++) {
    float z[8] = {0.f, 0.f, 0.f, 0.f, 0.f, 0.f, 0.f, 0.f};
#pragma unroll 2
    for (int kk = 0; kk < 8; kk++) {
      uint32_t a0, a1, a2, a3;
      ldsm4(qa + (kk >> 2) * half + ((((kk & 3) * 2 + (mi >> 1)) ^ swz) << 4), a0, a1, a2, a3);
      const uint32_t* kr = kq + kb * (16 * DH / 2) + kk * 8;
      mma16816(z[0], z[1], z[2], z[3], a0, a1, a2, a3, __ldg(kr), __ldg(kr + 4));
      mma16816(z[4], z[5], z[6], z[7], a0, a1, a2, a3, __ldg(kr + 8 * DH / 2), __ldg(kr + 8 * DH / 2 + 4));
    }
    const float n0 = fmaxf(m0, quad_max(fmaxf(fmaxf(z[0], z[1]), fmaxf(z[4], z[5]))));
    const float n1 = fmaxf(m1, quad_max(fmaxf(fmaxf(z[2], z[3]), fmaxf(z[6], z[7]))));
    const float al0 = ex2(m0 - n0), al1 = ex2(m1 - n1);
    m0 = n0; m1 = n1;
#pragma unroll
    for (int i = 0; i < 8; i++) z[i] = ex2(z[i] - ((i & 2) ? n1 : n0));
    l0 = l0 * al0 + (z[0] + z[1]) + (z[4] + z[5]);
    l1 = l1 * al1 + (z[2] + z[3]) + (z[6] + z[7]);
    const uint32_t a0 = pack_bf16(z[0], z[1]), a1 = pack_bf16(z[2], z[3]), a2 = pack_bf16(z[4], z[5]), a3 = pack_bf16(z[6], z[7]);
    const unsigned short* vr = vq + kb * (16 * DH);
#pragma unroll
    for (int nb = 0; nb < 16; nb++) {
      o[4 * nb] *= al0; o[4 * nb + 1] *= al0; o[4 * nb + 2] *= al1; o[4 * nb + 3] *= al1;
      const uint32_t b0 = __ldg(vr + nb * 8) | ((uint32_t)__ldg(vr + nb * 8 + DH) << 16);
      const uint32_t b1 = __ldg(vr + nb * 8 + 8 * DH) | ((uint32_t)__ldg(vr + nb * 8 + 9 * DH) << 16);
      mma16816(o[4 * nb], o[4 * nb + 1], o[4 * nb + 2], o[4 * nb + 3], a0, a1, a2, a3, b0, b1);
    }
  }
  const char* p = o_addr(item, row, lane);
  o_emit<0>(p, o, __fdividef(1.f, quad_sum(l0)));
  o_emit<1>(half == 4096 ? p : p + 1024, o, __fdividef(1.f, quad_sum(l1)));
}

template <bool SPA, bool SPB, int SITE, int ID>
__device__ __forceinline__ void batch(const Ctx& c, float (&s)[32], const uint32_t (&qs)[32], uint32_t dq, uint32_t dk, float (&ob)[64],
                                      uint32_t (&pb)[SPB ? 8 : 16], uint32_t dv) {
  if constexpr (SPA) {
    reg_fence(pb);
    wg_fence();
    issue_pv<SPB, true, ID>(c, ob, pb, dv);
    issue_qk<SPA, false, ID>(c, s, qs, dq, dk);
  } else {
    constexpr bool EARLY = ((QK_EARLY_MASK >> (SITE + (SPB ? 2 : 0))) & 1) != 0;
    if (!EARLY) reg_fence(pb);
    wg_fence();
    issue_qk<SPA, false, ID, !SPB, SITE ? RM0 : SPB ? RM2 : RM1>(c, s, qs, dq, dk);
    if (EARLY) { reg_fence(pb); wg_fence(); }
    issue_pv<SPB, true, ID, SPB>(c, ob, pb, dv);
  }
}

template <bool SP0>
__device__ __forceinline__ bool attention(Ctx& c, Ring& r, int unit, uint32_t& d, const float (&a0)[64], float (&o0)[64], float (&o1)[64],
                                          RowSum& st0, RowSum& st1, const Slots& h, uint32_t (&q1)[32]) {
  constexpr bool SP1 = false;
  if (SP0) { c.mqk = META_QK + (d >> 28); c.mpv = META_PV + (d >> 28); asm volatile("" : "+r"(c.mqk), "+r"(c.mpv)); }
  if (SP0) c.src = (c.lane & 28) | ((c.lane & 1) << 1) | ((c.lane >> 1) & 1);
  float s[32];
  uint32_t p0[SP0 ? 8 : 16], p1[16];
  const uint32_t q0a = c.sb + QBUF_OFF + (SP0 ? 3 : 0) * 16384, q1a = c.sb + QBUF_OFF + (SP0 ? 2 : 1) * 16384;
  const uint32_t dq0 = sdesc(SB0 + QBUF_OFF, 0), dq1 = sdesc(SB0 + QBUF_OFF + (SP0 ? 2 : 1) * 16384, 0);
  uint32_t sk = acquire(c, r, true), sv, sn;
  uint32_t qs[32];
  float s1[32];
  if (SP0) {
    stage_t3<0, true>(c, a0, SM_C);
    stage_t2<0>(c, a0, SM_C);
    proj_end<1>(c, o0, h);
    stage_t3<1, true>(c, o0, SM_C);
    stage_t2<1>(c, o0, SM_C);
    bar_sync(5, 128);
    const int g = c.lane >> 2, cc = c.lane & 3;
    const uint32_t qa = q0a + (8 * c.warp + g) * 128 + (cc & 1) * 8;
#pragma unroll
    for (int k = 0; k < 8; k++)
      asm volatile("ld.shared.v2.u32 {%0, %1}, [%2];" : "=r"(qs[2 * k]), "=r"(qs[2 * k + 1])
                   : "r"(qa + (k >> 2) * 4096 + ((((k & 3) * 2 + (cc >> 1)) ^ q3_swz(g)) << 4)) : "memory");
    fence_async_smem();
    bar_sync(1, 256);
    TRACE(unit, 2);
    wg_fence();
    issue_qk<SP1, true, 1>(c, s1, qs, dq1, sdesc(SB0 + sk * SLOT, 0));
#pragma unroll
    for (int k = 0; k < 8; k++)
      if (RM2 >> k & 1) ldsm4(q1a + (k >> 2) * 8192 + (16 * c.warp + (c.lane & 15)) * 128 + (((2 * (k & 3) + (c.lane >> 4)) ^ (c.lane & 7)) << 4),
                              q1[4 * k], q1[4 * k + 1], q1[4 * k + 2], q1[4 * k + 3]);
#pragma unroll
    for (int k = 0; k < 16; k++) asm volatile("" : "+r"(qs[k])::"memory");
    wg_fence();
    issue_qk<SP0, true, 0>(c, s, qs, dq0, sdesc(SB0 + sk * SLOT, 0));
    const bool have = peek<2>(c, r);
    wg_wait<1>();
    reg_fence(s1);
    exps<SP1, true>(c, s1, p1, st1);
    sched_fence<11>(sk, p1);
    acquire2(c, r, sv, sn, __all_sync(0xffffffffu, have));
    wg_wait<0>();
    wg_fence();
    issue_pv<SP1, false, 1>(c, o1, p1, sdesc(SB0 + sv * SLOT, 8192));
    if (LAG_BAR & 1) asm volatile("bar.arrive 4, 256;" ::: "memory");
    sched_fence<12>(sk, s);
    release(c, sk);
    sk = sn;
    exps<SP0, true>(c, s, p0, st0);
    reg_fence(p0);
    wg_fence();
    issue_pv<SP0, false, 0>(c, o0, p0, sdesc(SB0 + sv * SLOT, 8192));
    issue_qk<SP0, true, 2>(c, s, qs, dq0, sdesc(SB0 + sk * SLOT, 0));
    sn = acquire(c, r);
    wg_wait<0>();
    reg_fence(s);
  } else {
    pack_rows(a0, SM_C, qs);
    stage_rows(c, q0a, qs);
    proj_end<0>(c, o1, h);
    TRACE(unit, 2);
    float sc = SM_C;
    issue_qk_rs<0>(s, qs, sdesc(SB0 + sk * SLOT, 0));
    sched_fence<0>(sk, sc);
    pack_rows(o1, sc, q1);
    stage_rows<~RM1>(c, q1a, q1);
    issue_qk_rs<1>(s1, q1, sdesc(SB0 + sk * SLOT, 0));
    asm volatile("bar.arrive 1, 256;" ::: "memory");
    bool have = peek<2>(c, r);
    wg_wait<1>();
    reg_fence(s);
    exps<SP0, true>(c, s, p0, st0);
    sched_fence<1>(sk, p0);
    acquire2(c, r, sv, sn, __all_sync(0xffffffffu, have));
    wg_wait<0>();
    reg_fence(s1);
    fence_async_smem();
    __syncwarp();
    wg_fence();
    issue_qk<SP0, false, 2, true, RM0>(c, s, qs, dq0, sdesc(SB0 + sn * SLOT, 0));
    issue_pv<SP0, false, 0>(c, o0, p0, sdesc(SB0 + sv * SLOT, 8192));
    sched_fence<2>(sk, s1);
    release(c, sk);
    have = peek<1>(c, r);
    sk = sn;
    exps<SP1, true>(c, s1, p1, st1);
    reg_fence(p1);
    wg_fence();
    issue_pv<SP1, false, 1>(c, o1, p1, sdesc(SB0 + sv * SLOT, 8192));
    sn = acquire(c, r, __all_sync(0xffffffffu, have));
    if (LAG_BAR & 1) bar_sync(4, 256);
    wg_wait<1>();
    reg_fence(s);
  }
  TRACE_IN(unit, 4);
  T2C(unit, 51);
#pragma unroll 1
  for (int j = 1; j < 15; j++) {
    const uint32_t sv_prev = sv, sk_prev = sk;
    sv = sn;
    const uint32_t dv = sdesc(SB0 + sv * SLOT, 8192);
    reg_fence(p0);
    exps<SP0, false>(c, s, p0, st0);
    batch<SP1, SP0, 0, 3>(c, s, q1, dq1, sdesc(SB0 + sk * SLOT, 0), o0, p0, dv);
    sk = acquire(c, r);
    wg_wait<1>();
    reg_fence(s); reg_fence(p1);
    release(c, sv_prev); release(c, sk_prev);
    exps<SP1, false>(c, s, p1, st1);
    batch<SP0, SP1, 1, 4>(c, s, qs, dq0, sdesc(SB0 + sk * SLOT, 0), o1, p1, dv);
    sn = acquire(c, r);
    if (SP0) wg_wait<0>(); else wg_wait<1>();
    reg_fence(s);
  }
  TRACE_IN(unit, 5);
  T2C(unit + 1, 52);
  const uint32_t sv_prev = sv;
  sv = sn;
  const uint32_t dv = sdesc(SB0 + sv * SLOT, 8192);
  reg_fence(p0);
  exps<SP0, false>(c, s, p0, st0);
  batch<SP1, SP0, 0, 5>(c, s, q1, dq1, sdesc(SB0 + sk * SLOT, 0), o0, p0, dv);
  asm volatile("ld.volatile.shared.u32 %0, [%1];" : "=r"(d) : "r"(c.sb + DESC_OFF + ((unit + 1) & 3) * 4) : "memory");
  const bool have = peek<2 + SP0>(c, r);
  wg_wait<1>();
  reg_fence(s); reg_fence(p1);
  release(c, sv_prev); release(c, sk);
  exps<SP1, false>(c, s, p1, st1);
  reg_fence(p1);
  wg_fence();
  issue_pv<SP1, true, 2>(c, o1, p1, dv);
  if (SP0) sched_fence<6>(sk, st0.l0, st1.l0, st1.l1); else sched_fence<5>(sk, st0.l0, st0.l1, st1.l0, st1.l1);
  c.lane = c.lane0 + (sk >> 5);
  const bool bad = finish_sums<SP0>(st0) | finish_sums<SP1>(st1);
  uint32_t any;
  asm volatile("{\n.reg .pred p, q;\nsetp.ne.u32 p, %1, 0;\nbar.red.or.pred q, %2, 128, p;\nselp.u32 %0, 1, 0, q;\n}"
               : "=r"(any) : "r"((uint32_t)bad), "n"(2 + SP0) : "memory");
  any = __any_sync(0xffffffffu, any);
  d = __shfl_sync(0xffffffffu, d, 0);
  if (d < (2u << 30) && !__all_sync(0xffffffffu, have)) { Ring t = r; Slots u; begin_acquire<SP0>(c, t, u, true); }
  wg_wait<0>();
  reg_fence(o0); reg_fence(o1);
  release(c, sv);
  return any;
}

template <int WG>
__device__ __forceinline__ void consumer(Ctx c, const __nv_bfloat16* const* kv) {
  asm volatile("setmaxnreg.inc.sync.aligned.u32 %0;" ::"n"(WG ? REG_C : 504 - REG_C - REG_P));
  c.wg = WG;
  Ring r{0, 0, 0};
  float a0[64], a1[64], o1[64];
  Slots h;
  RowSum inv0, inv1;
  uint32_t oq[32];
  uint32_t d = c_sched.queue[blockIdx.x] * 1025, dc = 0, sw;
  int i = 0, nq;
begin:
  sw = d & (1u << 30);
  proj_begin<WG>(c, r, a0, h, true, sw);
  proj_half<WG, true, 1>(c, a1, h.w, h.x, sw);
  nq = 0;
#pragma unroll
  for (int k = 0; k < 64; k++) asm volatile("" : "=f"(o1[k]));
  asm volatile("" : "=f"(inv1.l0), "=f"(inv1.l1));
  while (true) {
    TRACE(i, 0); TRACE(i, 6);
    proj_main<WG>(c, r, a0, a1, h, d >> 30 ? ((d >> 16) & 63) + 1 : DM / 64, sw, i, dc, nq, o1, inv1);
    dc = d;
    TRACE(i, 1);
    if (d >> 30) goto out_tile;
    wg_wait<1>();
    acc_fence<WG>(a0);
    if (WG ? attention<WG>(c, r, i, d, a0, a1, o1, inv0, inv1, h, oq) : attention<WG>(c, r, i, d, a0, o1, a1, inv1, inv0, h, oq)) goto redo;
    if (d >= (2u << 30)) break;
    sw = d & (1u << 30);
    proj_begin<WG>(c, r, a0, h, false, sw);
    release_q<WG>(c);
    if (WG) sched_fence<8>(h.w, inv0.l0); else sched_fence<7>(h.w, inv0.l0, inv0.l1);
    o_first<WG>(c, dc, a1, inv0, oq);
    sched_fence<9>(h.w, inv1.l0);
    proj_half<WG, true, 1>(c, a1, h.w, h.x, sw);
    o_rest<WG>(c, dc, oq);
    nq = O_STEPS;
    TRACE(i, 3); TRACE(i, 7);
    i++;
  }
  release_q<WG>(c);
  o_first<WG>(c, dc, a1, inv0, oq);
  o_rest<WG>(c, dc, oq);
#pragma unroll
  for (int k = 1; k <= O_STEPS; k++) o_second<WG>(c, dc, k, o1, inv1);
next:
  TRACE(i, 3); TRACE(i, 7);
  if ((d >> 30) != 2) {
    i++;
    r.uniform();
    goto begin;
  }
  trace_dump(c);
  return;
out_tile:
  if (d & 96) goto finish;
  d = get_desc(c, i + 1);
  wg_wait<1>();
  acc_fence<WG>(a0);
  TRACE_O(0);
  stage_out<WG, 0>(c, a0);
  TRACE_O(1);
  proj_end<WG>(c, a1, h);
  TRACE_O(2);
  stage_out<WG, 1>(c, a1);
  TRACE(i, 2);
  goto next;
finish:
  {
    uint32_t q[32];
#pragma unroll 1
    for (int k = (d >> 5) & 3; k > 1; k--) {
      wg_wait<0>();
      acc_fence<WG>(a0); acc_fence<WG>(a1);
      if (k == ((d >> 5) & 3)) { release(c, h.x); release(c, h.w); }
      load_part<WG, 0>(c, r, q); add_part<WG>(c, q, a0);
      load_part<WG, 1>(c, r, q); add_part<WG>(c, q, a1);
#pragma unroll
      for (int t = 0; t < 4; t++) { release(c, r.slot); r.next(); }
    }
    load_part<WG, 0>(c, r, q);
    wg_wait<1>();
    acc_fence<WG>(a0);
    TRACE_O(0);
    add_part<WG>(c, q, a0);
    stage_out<WG, 0>(c, a0);
    TRACE_O(1);
    load_part<WG, 1>(c, r, q);
    wg_wait<0>();
    acc_fence<WG>(a1);
    TRACE_O(2);
    add_part<WG>(c, q, a1);
    stage_out<WG, 1>(c, a1);
    TRACE(i, 2); TRACE(i, 3); TRACE(i, 7);
    trace_dump(c);
    return;
  }
redo:
  {
    if (!WG) { stage_rows<RM1>(c, c.sb + QBUF_OFF + 16384, oq); __syncwarp(); }
    const size_t hoff = (size_t)(dc & 511) * (SK * DH);
    const int br = (dc >> 9) & 1;
#pragma unroll 1
    for (int part = 0; part < 2; part++) {
      const int t = WG ? 3 - part : part;
      redo_tile(c, c.sb + QBUF_OFF + t * 16384, t == 3 ? 4096 : 8192, kv[br] + hoff, kv[2 + br] + hoff, dc,
                t * 64 + (t == 3 ? 8 : 16) * c.warp);
    }
    o_done(c);
    release_q<WG>(c);
  }
  goto next;
}

template <bool SIMPLE>
__global__ void __launch_bounds__(384, 1) mha_fused_kernel(const __grid_constant__ Params P) {
  extern __shared__ __align__(1024) uint8_t smem_raw[];
  const uint32_t sbase = smem_u32(smem_raw);
  const int tid = threadIdx.x;
  const int wg = __shfl_sync(0xffffffffu, tid >> 7, 0);
  const int warp = __shfl_sync(0xffffffffu, (tid >> 5) & 3, 0);
  const int lane = tid & 31;
  const int cta = blockIdx.x;
  constexpr bool PAIR = !SIMPLE && CLUSTER;

  if (tid == 0) T3(15, 0);
  if ((sbase & 0xffffff) != SB0) __trap();
  {
    const int wi = wg * 4 + warp;
    asm volatile(ELECT "prefetch.tensormap [%0];\n}" ::"l"(&P.x[0][0] + wi) : "memory");
#pragma unroll
    for (int k = 0; k < 5; k++) {
      const int b = min(BAR_OFF + (wi * 5 + k) * 8, DESC_OFF - 8);
      asm volatile(ELECT "mbarrier.init.shared::cta.b64 [%0], %1;\n}"
                   ::"r"(sbase + b), "r"(b < BAR_EMPTY || b >= BAR_DESC ? 1 : b >= BAR_STG && b < BAR_OUT ? 4 : 8) : "memory");
    }
    asm volatile("fence.mbarrier_init.release.cluster;" ::: "memory");
    if (wi < 6) asm volatile(ELECT "prefetch.tensormap [%0];\n}" ::"l"(&P.x[0][0] + 12 + wi) : "memory");
  }
  if (PAIR) asm volatile("barrier.cluster.arrive.aligned;\nbarrier.cluster.wait.aligned;" ::: "memory"); else __syncthreads();

  if (wg == 2) {
    asm volatile("setmaxnreg.dec.sync.aligned.u32 %0;" ::"n"(REG_P));
    if (warp == 1) {
      const uint32_t qb = sbase + QBUF_OFF;
      const uint32_t ep = __shfl_sync(0xffffffffu, *(volatile unsigned*)&g_epoch + 1, 0);
      asm volatile("st.volatile.shared.u32 [%0], %1;" ::"r"(sbase + EPOCH_OFF), "r"(ep) : "memory");
      uint32_t dc = c_sched.queue[cta], qi = 0, piece = 0, na = 0;
      TTAIL(0);
      for (int i = 0; (dc >> 30) != 2; i++) {
        if (!(dc >> 30) && o_reuse<SIMPLE>((dc >> 5) & 31)) {
          const unsigned* rd = &g_rd[0][0] + ((dc & 1023) >> 2) - OR * 8;
          for (uint32_t n = 0; !__all_sync(0xffffffffu, reached(rd, ep * 5)); __nanosleep(300)) if (++n > (1u << 22)) __trap();
        }
        mbar_wait_w(sbase + BAR_GO, i & 1);
        if (piece == 0) {
          if (PAIR && (cta & 1)) {
            asm volatile(ELECT EXPECT("%0", "4") "mbarrier.arrive.shared::cluster.b64 _, [%1];\n}" ::"r"(sbase + BAR_MAIL), "r"(peer(sbase + BAR_MAIL)) : "memory");
            mbar_wait_w(sbase + BAR_MAIL, i & 1);
            qi = lds(sbase + EPOCH_OFF + 8);
          } else if (lane == 0) {
            qi = atomicAdd(&g_next, PAIR ? 2 : 1);
            if (qi == (SIMPLE ? Q_ALL : Q_RANGES) - (PAIR ? 2 : 1)) { g_next = 0; g_epoch = ep; }
          }
          qi = __shfl_sync(0xffffffffu, qi, 0);
          if (PAIR && !(cta & 1)) {
            mbar_wait_w(sbase + BAR_MAIL, i & 1);
            asm volatile(ELECT "st.async.shared::cluster.mbarrier::complete_tx::bytes.u32 [%0], %1, [%2];\n}"
                         ::"r"(peer(sbase + EPOCH_OFF + 8)), "r"(qi + 1), "r"(peer(sbase + BAR_MAIL)) : "memory");
          }
          qi += SIMPLE ? gridDim.x : NCTA;
        }
        uint32_t d;
        if (qi < (SIMPLE ? Q_ALL : Q_RANGES)) { d = c_sched.queue[qi]; if (d & 0x8000) d ^= (1u << 30) | (63u << 16) | 0x8000; else d |= o_slot<SIMPLE>(d >> 5) << 15 | (d & 31) << 10; }
        else if (SIMPLE) d = 2u << 30;
        else { const uint32_t e = qi - Q_RANGES, g = e / 5; d = c_sched.piece[g][piece++] | (g & 1 ? g * 5 + 4 - e : e - g * 5) << 8; }
        if ((d >> 30) == 1) {
          const uint32_t k0 = (d >> 22) & 63;
          const uint32_t run = __ffs(__ballot_sync(0xffffffffu, !reached(&g_cnt[d & 31][lane & 7], ep * 4)) & (0xffu << (k0 >> 3))) - 1;
          if (run <= (k0 + ((d >> 16) & 63)) >> 3) d |= run <= (k0 + O_STEPS) >> 3 ? (2u << 30) | 128 : 128;
        }
        asm volatile("st.volatile.shared.u32 [%0], %1;" ::"r"(sbase + EPOCH_OFF + 4), "r"(qi) : "memory");
        asm volatile("st.volatile.shared.u32 [%0], %1;" ::"r"(sbase + DESC_OFF + ((i + 1) & 3) * 4), "r"(d) : "memory");
        __syncwarp();
        mbar_arrive_warp(sbase + BAR_DESC);
        const Work w = decode(dc);
        dc = d;
        if (w.kind == 0) {
          mbar_wait_w(sbase + BAR_OUT, na++ & 1);
          TTAIL(1);
          T3(i, 0); T3(i, 1);
          asm volatile(ELECT "red.release.gpu.global.add.u32 [%0], 1;\n}" ::"l"(&g_cnt[w.beta][w.sub >> 2]) : "memory");
          T3(i, 2);
          TTAIL(2);
          continue;
        }
        const bool fin = w.mode != 1;
        uint64_t pol, pol2;
        asm volatile("createpolicy.fractional.L2::evict_first.b64 %0, 1.0;" : "=l"(pol));
        asm volatile("createpolicy.fractional.L2::evict_normal.b64 %0, 1.0;" : "=l"(pol2));
        if (!fin) pol = pol2;
        const CUtensorMap* m = fin ? P.out_st : P.o_st;
        const int c1 = fin ? (w.beta & 15) * SQ : 0;
        const int c2 = fin ? (w.beta >> 4) * (DM / 64) + w.sub * 2 : NBETA * 64 + w.range * 2;
        uint32_t pend = 0;
#pragma unroll 1
        for (int e = 0; e < 4; e++) {
          const int t = (ST_ORDER >> (4 * e)) & 3;
          mbar_wait_w(sbase + BAR_STG + (t ^ (t >> 1)) * 8, (i - na) & 1);
          tma_st3_hint_w(m + (t == 3), qb + t * 16384, 0, c1 + t * 64, c2, pol);
          bulk_commit();
          T2P(i + 1, 5, 2 * e);
          if (pend) {
            bulk_wait_read<1>();
            mbar_arrive8_w(pend);
            T2P(i + 1, 5, 2 * e - 1);
          }
          pend = sbase + BAR_EMPTY + (NS + t) * 8;
          if ((ST_NOW >> e) & 1) {
            bulk_wait_read<0>();
            mbar_arrive8_w(pend);
            pend = 0;
            T2P(i + 1, 5, 2 * e + 1);
          }
        }
        if (w.beta < N_EARLY) asm volatile(ELECT "red.relaxed.gpu.global.add.u32 [%0], 1;\n}" ::"l"(&g_rd[w.beta][7]) : "memory");
        T3(i, 0);
        if (piece >= 2) TTAIL(piece * 2 - 1);
        asm volatile("cp.async.bulk.wait_group 0;" ::: "memory");
        T3(i, 1);
        if (w.mode == 1) asm volatile(ELECT "st.release.gpu.global.u32 [%0], %1;\n}" ::"l"(&g_flag[w.range]), "r"(ep) : "memory");
        T3(i, 2);
        if (piece >= 2) TTAIL(piece * 2);
      }
      T3(15, 1);
    } else
    if (warp == 0) {
      Ring r{0, 1, 3};
      uint32_t d = c_sched.queue[cta];
      for (int i = 0;; i++) {
        const Work w = decode(d);
        if (w.kind == 2) break;
        const CUtensorMap* m = w.kind == 0 ? &P.wq[w.beta >> 4] : &P.wo[w.beta >> 4];
        for (int ks = 0; ks < w.nsteps; ks++) {
          const uint32_t b = borrow(ks, w.nsteps);
          r.next_if(b == 2);
          const uint32_t bar = sbase + BAR_FULL + r.slot * 8;
          mbar_wait_w(bar + (BAR_EMPTY - BAR_FULL), r.phase);
          if (w.kind == 0) tma_ld3_w(sbase + r.slot * SLOT, m, 0, ks * 64, w.sub * 2, bar, 16384);
          else tma_ld_wo_w(sbase + r.slot * SLOT, m, w.sub * 128, (w.k0 + ks) * 2, bar);
          if (w.kind != 0 && w.beta < N_EARLY && (ks & 7) == 5 && ks > 5)
            asm volatile(ELECT "red.relaxed.gpu.global.add.u32 [%0], 1;\n}" ::"l"(&g_rd[w.beta][(ks >> 3) - 1]) : "memory");
          if (ks < 10) T2P(i, 2, ks);
          if (w.kind != 0 && ks == max(w.nsteps - GO_P, 4)) mbar_arrive_warp(sbase + BAR_GO);
          r.next(); r.next_if(b == 2);
        }
        if (w.kind == 0) {
          r.phase ^= 1; r.next(); r.next();
        } else if (w.mode == 2) {
          for (int k = 1; k <= ((d >> 5) & 3); k++) {
            if (k == 1) TTAIL(9);
            wait_count(&g_flag[w.range + 5 * k], lds(sbase + EPOCH_OFF));
            TTAIL(10);
            asm volatile("fence.proxy.async.global;" ::: "memory");
#pragma unroll 1
            for (int t = 0; t < 4; t++) {
              mbar_wait_w(sbase + BAR_EMPTY + r.slot * 8, r.phase);
              tma_ld3_w(sbase + r.slot * SLOT, &P.o_st[t == 3], 0, t * 64, NBETA * 64 + (w.range + 5 * k) * 2, sbase + BAR_FULL + r.slot * 8,
                        t == 3 ? 8192 : 16384);
              r.next();
            }
          }
        }
        mbar_wait_w(sbase + BAR_DESC, i & 1);
        d = __shfl_sync(0xffffffffu, lds(sbase + DESC_OFF + ((i + 1) & 3) * 4), 0);
      }
    } else {
      const int hi = warp - 2;
      uint64_t pol_stream;
      uint32_t rdy = 0;
      asm volatile("createpolicy.fractional.L2::evict_first.b64 %0, 1.0;" : "=l"(pol_stream));
      Ring r{0, 1, 3};
      uint32_t d = c_sched.queue[cta];
      for (int i = 0;; i++) {
        const Work w = decode(d);
        if (w.kind == 2) break;
        const CUtensorMap* m = w.kind == 0 ? &P.x[hi][w.beta >> 4] : &P.o_ld[hi];
        int c1 = (w.kind == 0 ? (w.beta & 15) : o_slot<SIMPLE>(w.beta) * 64 + w.k0) * SQ + hi * 128;
        int k_wait = -1;
        const bool both = PAIR && (w.kind == 0 || w.sub != 4), mine = !both || hi == (cta & 1);
        if (w.kind != 0 && mine) {
          if (d & 128) k_wait = d >= (3u << 30) ? 0 : 8 - (w.k0 & 7);
          asm volatile("fence.proxy.async.global;" ::: "memory");
        }
        const int rank = i == 0 ? cta : __shfl_sync(0xffffffffu, lds(sbase + EPOCH_OFF + 4), 0) - NCTA;
        for (int ks = 0; ks < w.nsteps; ks++) {
          if (ks == k_wait) {
            wait_count(&g_cnt[d & 31][(w.k0 + ks) >> 3], lds(sbase + EPOCH_OFF) * 4);
            asm volatile("fence.proxy.async.global;" ::: "memory");
            k_wait = ((w.k0 + ks) | 7) + 1 - w.k0;
          }
          const uint32_t b = borrow(ks, w.nsteps);
          const bool bo = b != 2;
          r.next_if(hi && !bo); r.next_if(hi && !bo);
          const uint32_t sl = bo ? NS + (b ^ (3 * hi)) : r.slot, bar = sbase + BAR_FULL + sl * 8;
          mbar_wait_w(bar + (BAR_EMPTY - BAR_FULL), bo ? (r.xp >> b) & 1 : r.phase);
          const uint32_t bytes = hi ? 96 * 128 : 128 * 128;
          if (!mine) {
            asm volatile(ELECT EXPECT("%0", "%2") "mbarrier.arrive.shared::cluster.b64 _, [%1];\n}"
                         ::"r"(bar), "r"(peer(bar + (BAR_RDY - BAR_FULL))), "r"(bytes) : "memory");
          } else if (both) {
            mbar_wait_w(bar + (BAR_RDY - BAR_FULL), (rdy >> sl) & 1);
            rdy ^= 1 << sl;
            if (w.kind == 0) tma_ld2_both_w(sbase + sl * SLOT, m, ks * 64, c1, bar, bytes);
            else tma_ld2_both_hint_w(sbase + sl * SLOT, m, 0, c1, bar, bytes, pol_stream);
          } else if (!PAIR && w.kind == 0) tma_ld2_w(sbase + sl * SLOT, m, ks * 64, c1, bar, bytes);
          else tma_ld2_hint_w(sbase + sl * SLOT, m, 0, c1, bar, bytes, pol_stream);
          if (w.kind != 0) c1 += SQ;
          if (i == 0 && ks == PF_STEP)
            asm volatile(ELECT "cp.async.bulk.prefetch.tensor.3d.L2.global.L2::cache_hint [%0, {0, %1, 0}], %2;\n}"
                         ::"l"(&P.kv[hi][0]), "r"(d * SK), "l"(pol_stream) : "memory");
          if (ks < 10) T2P(i, 3 + hi, ks);
          if (!hi && w.kind != 0 && !(ks & 3)) TCLK(i * 16 + (ks >> 2));
          r.next(); r.next_if(!hi && !bo); r.next_if(!hi && !bo);
          r.xp ^= 1 << b;
        }
        r.xp ^= 3;
        if (w.kind == 0) {
          m = &P.kv[hi][w.beta >> 4];
          c1 = (d & 511) * SK;
          for (int j = 0; j < 16; j++) {
            if (hi) r.next();
            const uint32_t bar = sbase + BAR_FULL + r.slot * 8;
            const bool tight = i < KV_WIN_UNITS && j < KV_WIN_TILES + ((KV_WIN_RAMP * rank) >> 5);
            {
              const int s2 = (int)r.slot - (tight ? 2 : KV_WIN_D);
              mbar_wait_w(sbase + BAR_FULL + (s2 < 0 ? s2 + NS : s2) * 8, s2 < 0 ? r.phase : r.phase ^ 1);
            }
            if (j == 15 && hi) mbar_wait_w(sbase + BAR_DESC, i & 1);
            mbar_wait_w(sbase + BAR_EMPTY + r.slot * 8, r.phase);
            tma_ld3_hint_w(sbase + r.slot * SLOT, m, 0, c1, 0, bar, pol_stream);
            T2P(i, 3 + hi, 16 + j);
            if (!hi) TCLK(i * 16 + j);
            if (j == GO_J && !hi) mbar_arrive_warp(sbase + BAR_GO);
            c1 += 64;
            r.next();
            if (!hi) r.next();
          }
        }
        mbar_wait_w(sbase + BAR_DESC, i & 1);
        d = __shfl_sync(0xffffffffu, lds(sbase + DESC_OFF + ((i + 1) & 3) * 4), 0);
      }
    }
  } else {
    Ctx c;
    c.sb = sbase; c.wg = wg; c.warp = warp; c.src = 0; c.mqk = 0; c.mpv = 0; c.lead = lane == 0; c.lane0 = c.lane = lane;
    if (wg == 0) consumer<0>(c, P.kp); else consumer<1>(c, P.kp);
  }
}

typedef CUresult (*EncodeFn)(CUtensorMap*, CUtensorMapDataType, cuuint32_t, void*, const cuuint64_t*, const cuuint64_t*,
                             const cuuint32_t*, const cuuint32_t*, CUtensorMapInterleave, CUtensorMapSwizzle,
                             CUtensorMapL2promotion, CUtensorMapFloatOOBfill);

void make_map(EncodeFn enc, CUtensorMap* m, const void* ptr, int rank, const cuuint64_t* dims, const cuuint64_t* strides,
              const cuuint32_t* box, int promo = 2, CUtensorMapSwizzle swz = CU_TENSOR_MAP_SWIZZLE_128B) {
  cuuint32_t es[5] = {1, 1, 1, 1, 1};
  enc(m, CU_TENSOR_MAP_DATA_TYPE_BFLOAT16, rank, const_cast<void*>(ptr), dims, strides, box, es,
      CU_TENSOR_MAP_INTERLEAVE_NONE, swz, promo == 2 ? CU_TENSOR_MAP_L2_PROMOTION_L2_256B : promo == 1 ? CU_TENSOR_MAP_L2_PROMOTION_L2_128B : CU_TENSOR_MAP_L2_PROMOTION_NONE,
      CU_TENSOR_MAP_FLOAT_OOB_FILL_NONE);
}

}

extern "C" void kernel_launch(void* const* d_in, const int* in_sizes, int n_in, void* d_out, int out_size) {
  (void)in_sizes; (void)n_in; (void)out_size;
  static EncodeFn enc = nullptr;
  static void* o_ptr = nullptr;
  static int n_sm = 0;
  cudaLaunchAttribute at;
  at.id = cudaLaunchAttributeClusterDimension;
  at.val.clusterDim.x = CLUSTER ? 2 : 1; at.val.clusterDim.y = 1; at.val.clusterDim.z = 1;
  cudaLaunchConfig_t cfg = {};
  cfg.gridDim = dim3(NCTA); cfg.blockDim = dim3(384); cfg.dynamicSmemBytes = SMEM_BYTES; cfg.attrs = &at; cfg.numAttrs = 1;
  if (!enc) {
    void* fn = nullptr;
    cudaDriverEntryPointQueryResult qr;
    cudaGetDriverEntryPoint("cuTensorMapEncodeTiled", &fn, cudaEnableDefault, &qr);
    enc = (EncodeFn)fn;
    cudaGetSymbolAddress(&o_ptr, g_o);
    cudaFuncSetAttribute(mha_fused_kernel<false>, cudaFuncAttributeMaxDynamicSharedMemorySize, SMEM_BYTES);
    cudaFuncSetAttribute(mha_fused_kernel<true>, cudaFuncAttributeMaxDynamicSharedMemorySize, SMEM_BYTES);
    int dev = 0;
    cudaGetDevice(&dev);
    cudaDeviceGetAttribute(&n_sm, cudaDevAttrMultiProcessorCount, dev);
    int n_cl = 0;
    cudaOccupancyMaxActiveClusters(&n_cl, mha_fused_kernel<false>, &cfg);
    if (n_cl * (CLUSTER ? 2 : 1) < NCTA && n_sm >= NCTA) n_sm = NCTA - 1;
  }
  Params P;
  for (int br = 0; br < 2; br++) {
    const void* x = d_in[br * 5 + 0]; const void* kc = d_in[br * 5 + 1]; const void* vc = d_in[br * 5 + 2];
    const void* wq = d_in[br * 5 + 3]; const void* wo = d_in[br * 5 + 4];
    { cuuint64_t d[2] = {DM, (cuuint64_t)NB * SQ}, s[1] = {DM * 2}; cuuint32_t b[2] = {64, 128}, b2[2] = {64, 96};
      make_map(enc, &P.x[0][br], x, 2, d, s, b, PR_X); make_map(enc, &P.x[1][br], x, 2, d, s, b2, PR_X); }
    { cuuint64_t d[3] = {64, DM, HD / 64}, s[2] = {HD * 2, 128}; cuuint32_t b[3] = {64, 64, 2}; make_map(enc, &P.wq[br], wq, 3, d, s, b, PR_W); }
    { cuuint64_t d[5] = {DM, 2, 4, 4, HD / 32}, s[4] = {DM * 2, 8 * DM * 2, 2 * DM * 2, 32 * DM * 2}; cuuint32_t b[5] = {64, 2, 4, 4, 2};
      make_map(enc, &P.wo[br], wo, 5, d, s, b, PR_W); }
    { cuuint64_t d[3] = {64, (cuuint64_t)NB * NH * SK, 2}, s[2] = {DH * 2, 128}; cuuint32_t b[3] = {64, 64, 2};
      make_map(enc, &P.kv[0][br], kc, 3, d, s, b, PR_KV); make_map(enc, &P.kv[1][br], vc, 3, d, s, b, PR_KV); }
    P.kp[br] = (const __nv_bfloat16*)kc; P.vp[br] = (const __nv_bfloat16*)vc;

  }
  { cuuint64_t d[2] = {64, (cuuint64_t)NBETA * 64 * SQ}, s[1] = {128}; cuuint32_t b[2] = {64, 128}, b2[2] = {64, 96};
    make_map(enc, &P.o_ld[0], o_ptr, 2, d, s, b, PR_O, CU_TENSOR_MAP_SWIZZLE_NONE); make_map(enc, &P.o_ld[1], o_ptr, 2, d, s, b2, PR_O, CU_TENSOR_MAP_SWIZZLE_NONE); }
  { cuuint64_t d[3] = {64, SQ, O_BLOCKS}, s[2] = {128, SQ * 128}; cuuint32_t b[3] = {64, 64, 2}, b2[3] = {64, 32, 2};
    make_map(enc, &P.o_st[0], o_ptr, 3, d, s, b); make_map(enc, &P.o_st[1], o_ptr, 3, d, s, b2); }
  { cuuint64_t d[3] = {64, (cuuint64_t)NB * SQ, 2 * DM / 64}, s[2] = {2 * DM * 2, 128}; cuuint32_t b[3] = {64, 64, 2}, b2[3] = {64, 32, 2};
    make_map(enc, &P.out_st[0], d_out, 3, d, s, b); make_map(enc, &P.out_st[1], d_out, 3, d, s, b2); }
  if (n_sm >= NCTA) cudaLaunchKernelEx(&cfg, mha_fused_kernel<false>, P);
  else mha_fused_kernel<true><<<n_sm, 384, SMEM_BYTES>>>(P);
}
```

```cpp
#include <cuda_runtime.h>
#include <cuda_bf16.h>
#include <cuda.h>
#include <stdint.h>
#include <stdlib.h>

namespace {

__device__ __forceinline__ void wgmma_proj(float (&d)[64], uint64_t da, uint64_t db, int scaleD) {
  asm volatile("{\n.reg .pred p;\nsetp.ne.b32 p, %66, 0;\n"
      "wgmma.mma_async.sync.aligned.m64n128k16.f32.bf16.bf16 "
      "{%0, %1, %2, %3, %4, %5, %6, %7, %8, %9, %10, %11, %12, %13, %14, %15, %16, %17, %18, %19, %20, %21, %22, %23, %24, %25, %26, %27, %28, %29, %30, "
      "%31, %32, %33, %34, %35, %36, %37, %38, %39, %40, %41, %42, %43, %44, %45, %46, %47, %48, %49, %50, %51, %52, %53, %54, %55, %56, %57, %58, %59, %60, "
      "%61, %62, %63}, "
      "%64, %65, p, 1, 1, 0, 1;\n}\n"
      : "+f"(d[0]), "+f"(d[1]), "+f"(d[2]), "+f"(d[3]), "+f"(d[4]), "+f"(d[5]), "+f"(d[6]), "+f"(d[7]), "+f"(d[8]), "+f"(d[9]), "+f"(d[10]), "+f"(d[11]),
        "+f"(d[12]), "+f"(d[13]), "+f"(d[14]), "+f"(d[15]), "+f"(d[16]), "+f"(d[17]), "+f"(d[18]), "+f"(d[19]), "+f"(d[20]), "+f"(d[21]), "+f"(d[22]),
        "+f"(d[23]), "+f"(d[24]), "+f"(d[25]), "+f"(d[26]), "+f"(d[27]), "+f"(d[28]), "+f"(d[29]), "+f"(d[30]), "+f"(d[31]), "+f"(d[32]), "+f"(d[33]),
        "+f"(d[34]), "+f"(d[35]), "+f"(d[36]), "+f"(d[37]), "+f"(d[38]), "+f"(d[39]), "+f"(d[40]), "+f"(d[41]), "+f"(d[42]), "+f"(d[43]), "+f"(d[44]),
        "+f"(d[45]), "+f"(d[46]), "+f"(d[47]), "+f"(d[48]), "+f"(d[49]), "+f"(d[50]), "+f"(d[51]), "+f"(d[52]), "+f"(d[53]), "+f"(d[54]), "+f"(d[55]),
        "+f"(d[56]), "+f"(d[57]), "+f"(d[58]), "+f"(d[59]), "+f"(d[60]), "+f"(d[61]), "+f"(d[62]), "+f"(d[63])
      : "l"(da), "l"(db), "r"(scaleD));
}
__device__ __forceinline__ void wgmma_proj96(float (&d)[64], uint64_t da, uint64_t db, int scaleD) {
  asm volatile("{\n.reg .pred p;\nsetp.ne.b32 p, %50, 0;\n"
      "wgmma.mma_async.sync.aligned.m64n96k16.f32.bf16.bf16 "
      "{%0, %1, %2, %3, %4, %5, %6, %7, %8, %9, %10, %11, %12, %13, %14, %15, %16, %17, %18, %19, %20, %21, %22, %23, %24, %25, %26, %27, %28, %29, %30, "
      "%31, %32, %33, %34, %35, %36, %37, %38, %39, %40, %41, %42, %43, %44, %45, %46, %47}, "
      "%48, %49, p, 1, 1, 1, 0;\n}\n"
      : "+f"(d[0]), "+f"(d[1]), "+f"(d[2]), "+f"(d[3]), "+f"(d[4]), "+f"(d[5]), "+f"(d[6]), "+f"(d[7]), "+f"(d[8]), "+f"(d[9]), "+f"(d[10]), "+f"(d[11]),
        "+f"(d[12]), "+f"(d[13]), "+f"(d[14]), "+f"(d[15]), "+f"(d[16]), "+f"(d[17]), "+f"(d[18]), "+f"(d[19]), "+f"(d[20]), "+f"(d[21]), "+f"(d[22]),
        "+f"(d[23]), "+f"(d[24]), "+f"(d[25]), "+f"(d[26]), "+f"(d[27]), "+f"(d[28]), "+f"(d[29]), "+f"(d[30]), "+f"(d[31]), "+f"(d[32]), "+f"(d[33]),
        "+f"(d[34]), "+f"(d[35]), "+f"(d[36]), "+f"(d[37]), "+f"(d[38]), "+f"(d[39]), "+f"(d[40]), "+f"(d[41]), "+f"(d[42]), "+f"(d[43]), "+f"(d[44]),
        "+f"(d[45]), "+f"(d[46]), "+f"(d[47])
      : "l"(da), "l"(db), "r"(scaleD));
}
__device__ __forceinline__ void wgmma_qk(float (&d)[32], uint64_t da, uint64_t db, int scaleD) {
  asm volatile("{\n.reg .pred p;\nsetp.ne.b32 p, %34, 0;\n"
      "wgmma.mma_async.sync.aligned.m64n64k16.f32.bf16.bf16 "
      "{%0, %1, %2, %3, %4, %5, %6, %7, %8, %9, %10, %11, %12, %13, %14, %15, %16, %17, %18, %19, %20, %21, %22, %23, %24, %25, %26, %27, %28, %29, %30, "
      "%31}, "
      "%32, %33, p, 1, 1, 0, 0;\n}\n"
      : "+f"(d[0]), "+f"(d[1]), "+f"(d[2]), "+f"(d[3]), "+f"(d[4]), "+f"(d[5]), "+f"(d[6]), "+f"(d[7]), "+f"(d[8]), "+f"(d[9]), "+f"(d[10]), "+f"(d[11]),
        "+f"(d[12]), "+f"(d[13]), "+f"(d[14]), "+f"(d[15]), "+f"(d[16]), "+f"(d[17]), "+f"(d[18]), "+f"(d[19]), "+f"(d[20]), "+f"(d[21]), "+f"(d[22]),
        "+f"(d[23]), "+f"(d[24]), "+f"(d[25]), "+f"(d[26]), "+f"(d[27]), "+f"(d[28]), "+f"(d[29]), "+f"(d[30]), "+f"(d[31])
      : "l"(da), "l"(db), "r"(scaleD));
}
__device__ __forceinline__ void wgmma_qk_rs(float (&d)[32], uint32_t a0, uint32_t a1, uint32_t a2, uint32_t a3, uint64_t db, int scaleD) {
  asm volatile("{\n.reg .pred p;\nsetp.ne.b32 p, %37, 0;\n"
      "wgmma.mma_async.sync.aligned.m64n64k16.f32.bf16.bf16 "
      "{%0, %1, %2, %3, %4, %5, %6, %7, %8, %9, %10, %11, %12, %13, %14, %15, %16, %17, %18, %19, %20, %21, %22, %23, %24, %25, %26, %27, %28, %29, %30, "
      "%31}, "
      "{%32, %33, %34, %35}, %36, p, 1, 1, 0;\n}\n"
      : "+f"(d[0]), "+f"(d[1]), "+f"(d[2]), "+f"(d[3]), "+f"(d[4]), "+f"(d[5]), "+f"(d[6]), "+f"(d[7]), "+f"(d[8]), "+f"(d[9]), "+f"(d[10]), "+f"(d[11]),
        "+f"(d[12]), "+f"(d[13]), "+f"(d[14]), "+f"(d[15]), "+f"(d[16]), "+f"(d[17]), "+f"(d[18]), "+f"(d[19]), "+f"(d[20]), "+f"(d[21]), "+f"(d[22]),
        "+f"(d[23]), "+f"(d[24]), "+f"(d[25]), "+f"(d[26]), "+f"(d[27]), "+f"(d[28]), "+f"(d[29]), "+f"(d[30]), "+f"(d[31])
      : "r"(a0), "r"(a1), "r"(a2), "r"(a3), "l"(db), "r"(scaleD));
}
__device__ __forceinline__ void wgmma_pv(float (&d)[64], uint32_t a0, uint32_t a1, uint32_t a2, uint32_t a3, uint64_t db, int scaleD) {
  asm volatile("{\n.reg .pred p;\nsetp.ne.b32 p, %69, 0;\n"
      "wgmma.mma_async.sync.aligned.m64n128k16.f32.bf16.bf16 "
      "{%0, %1, %2, %3, %4, %5, %6, %7, %8, %9, %10, %11, %12, %13, %14, %15, %16, %17, %18, %19, %20, %21, %22, %23, %24, %25, %26, %27, %28, %29, %30, "
      "%31, %32, %33, %34, %35, %36, %37, %38, %39, %40, %41, %42, %43, %44, %45, %46, %47, %48, %49, %50, %51, %52, %53, %54, %55, %56, %57, %58, %59, %60, "
      "%61, %62, %63}, "
      "{%64, %65, %66, %67}, %68, p, 1, 1, 1;\n}\n"
      : "+f"(d[0]), "+f"(d[1]), "+f"(d[2]), "+f"(d[3]), "+f"(d[4]), "+f"(d[5]), "+f"(d[6]), "+f"(d[7]), "+f"(d[8]), "+f"(d[9]), "+f"(d[10]), "+f"(d[11]),
        "+f"(d[12]), "+f"(d[13]), "+f"(d[14]), "+f"(d[15]), "+f"(d[16]), "+f"(d[17]), "+f"(d[18]), "+f"(d[19]), "+f"(d[20]), "+f"(d[21]), "+f"(d[22]),
        "+f"(d[23]), "+f"(d[24]), "+f"(d[25]), "+f"(d[26]), "+f"(d[27]), "+f"(d[28]), "+f"(d[29]), "+f"(d[30]), "+f"(d[31]), "+f"(d[32]), "+f"(d[33]),
        "+f"(d[34]), "+f"(d[35]), "+f"(d[36]), "+f"(d[37]), "+f"(d[38]), "+f"(d[39]), "+f"(d[40]), "+f"(d[41]), "+f"(d[42]), "+f"(d[43]), "+f"(d[44]),
        "+f"(d[45]), "+f"(d[46]), "+f"(d[47]), "+f"(d[48]), "+f"(d[49]), "+f"(d[50]), "+f"(d[51]), "+f"(d[52]), "+f"(d[53]), "+f"(d[54]), "+f"(d[55]),
        "+f"(d[56]), "+f"(d[57]), "+f"(d[58]), "+f"(d[59]), "+f"(d[60]), "+f"(d[61]), "+f"(d[62]), "+f"(d[63])
      : "r"(a0), "r"(a1), "r"(a2), "r"(a3), "l"(db), "r"(scaleD));
}
__device__ __forceinline__ void wgmma_qk_sp(float (&d)[32], uint32_t a0, uint32_t a1, uint32_t a2, uint32_t a3, uint64_t db, int scaleD, uint32_t meta) {
  asm volatile("{\n.reg .pred p;\nsetp.ne.b32 p, %37, 0;\n"
      "wgmma.mma_async.sp.sync.aligned.m64n64k32.f32.bf16.bf16 "
      "{%0, %1, %2, %3, %4, %5, %6, %7, %8, %9, %10, %11, %12, %13, %14, %15, %16, %17, %18, %19, %20, %21, %22, %23, %24, %25, %26, %27, %28, %29, %30, "
      "%31}, "
      "{%32, %33, %34, %35}, %36, %38, 0, p, 1, 1, 0;\n}\n"
      : "+f"(d[0]), "+f"(d[1]), "+f"(d[2]), "+f"(d[3]), "+f"(d[4]), "+f"(d[5]), "+f"(d[6]), "+f"(d[7]), "+f"(d[8]), "+f"(d[9]), "+f"(d[10]), "+f"(d[11]),
        "+f"(d[12]), "+f"(d[13]), "+f"(d[14]), "+f"(d[15]), "+f"(d[16]), "+f"(d[17]), "+f"(d[18]), "+f"(d[19]), "+f"(d[20]), "+f"(d[21]), "+f"(d[22]),
        "+f"(d[23]), "+f"(d[24]), "+f"(d[25]), "+f"(d[26]), "+f"(d[27]), "+f"(d[28]), "+f"(d[29]), "+f"(d[30]), "+f"(d[31])
      : "r"(a0), "r"(a1), "r"(a2), "r"(a3), "l"(db), "r"(scaleD), "r"(meta));
}
__device__ __forceinline__ void wgmma_pv_sp(float (&d)[64], uint32_t a0, uint32_t a1, uint32_t a2, uint32_t a3, uint64_t db, int scaleD, uint32_t meta) {
  asm volatile("{\n.reg .pred p;\nsetp.ne.b32 p, %69, 0;\n"
      "wgmma.mma_async.sp.sync.aligned.m64n128k32.f32.bf16.bf16 "
      "{%0, %1, %2, %3, %4, %5, %6, %7, %8, %9, %10, %11, %12, %13, %14, %15, %16, %17, %18, %19, %20, %21, %22, %23, %24, %25, %26, %27, %28, %29, %30, "
      "%31, %32, %33, %34, %35, %36, %37, %38, %39, %40, %41, %42, %43, %44, %45, %46, %47, %48, %49, %50, %51, %52, %53, %54, %55, %56, %57, %58, %59, %60, "
      "%61, %62, %63}, "
      "{%64, %65, %66, %67}, %68, %70, 0, p, 1, 1, 1;\n}\n"
      : "+f"(d[0]), "+f"(d[1]), "+f"(d[2]), "+f"(d[3]), "+f"(d[4]), "+f"(d[5]), "+f"(d[6]), "+f"(d[7]), "+f"(d[8]), "+f"(d[9]), "+f"(d[10]), "+f"(d[11]),
        "+f"(d[12]), "+f"(d[13]), "+f"(d[14]), "+f"(d[15]), "+f"(d[16]), "+f"(d[17]), "+f"(d[18]), "+f"(d[19]), "+f"(d[20]), "+f"(d[21]), "+f"(d[22]),
        "+f"(d[23]), "+f"(d[24]), "+f"(d[25]), "+f"(d[26]), "+f"(d[27]), "+f"(d[28]), "+f"(d[29]), "+f"(d[30]), "+f"(d[31]), "+f"(d[32]), "+f"(d[33]),
        "+f"(d[34]), "+f"(d[35]), "+f"(d[36]), "+f"(d[37]), "+f"(d[38]), "+f"(d[39]), "+f"(d[40]), "+f"(d[41]), "+f"(d[42]), "+f"(d[43]), "+f"(d[44]),
        "+f"(d[45]), "+f"(d[46]), "+f"(d[47]), "+f"(d[48]), "+f"(d[49]), "+f"(d[50]), "+f"(d[51]), "+f"(d[52]), "+f"(d[53]), "+f"(d[54]), "+f"(d[55]),
        "+f"(d[56]), "+f"(d[57]), "+f"(d[58]), "+f"(d[59]), "+f"(d[60]), "+f"(d[61]), "+f"(d[62]), "+f"(d[63])
      : "r"(a0), "r"(a1), "r"(a2), "r"(a3), "l"(db), "r"(scaleD), "r"(meta));
}
__device__ __forceinline__ void wgmma_proj_init(float (&d)[64], uint64_t da, uint64_t db, int scaleD) {
  asm volatile("{\n.reg .pred p;\nsetp.ne.b32 p, %66, 0;\n"
      "wgmma.mma_async.sync.aligned.m64n128k16.f32.bf16.bf16 "
      "{%0, %1, %2, %3, %4, %5, %6, %7, %8, %9, %10, %11, %12, %13, %14, %15, %16, %17, %18, %19, %20, %21, %22, %23, %24, %25, %26, %27, %28, %29, %30, "
      "%31, %32, %33, %34, %35, %36, %37, %38, %39, %40, %41, %42, %43, %44, %45, %46, %47, %48, %49, %50, %51, %52, %53, %54, %55, %56, %57, %58, %59, %60, "
      "%61, %62, %63}, "
      "%64, %65, p, 1, 1, 0, 1;\n}\n"
      : "=f"(d[0]), "=f"(d[1]), "=f"(d[2]), "=f"(d[3]), "=f"(d[4]), "=f"(d[5]), "=f"(d[6]), "=f"(d[7]), "=f"(d[8]), "=f"(d[9]), "=f"(d[10]), "=f"(d[11]),
        "=f"(d[12]), "=f"(d[13]), "=f"(d[14]), "=f"(d[15]), "=f"(d[16]), "=f"(d[17]), "=f"(d[18]), "=f"(d[19]), "=f"(d[20]), "=f"(d[21]), "=f"(d[22]),
        "=f"(d[23]), "=f"(d[24]), "=f"(d[25]), "=f"(d[26]), "=f"(d[27]), "=f"(d[28]), "=f"(d[29]), "=f"(d[30]), "=f"(d[31]), "=f"(d[32]), "=f"(d[33]),
        "=f"(d[34]), "=f"(d[35]), "=f"(d[36]), "=f"(d[37]), "=f"(d[38]), "=f"(d[39]), "=f"(d[40]), "=f"(d[41]), "=f"(d[42]), "=f"(d[43]), "=f"(d[44]),
        "=f"(d[45]), "=f"(d[46]), "=f"(d[47]), "=f"(d[48]), "=f"(d[49]), "=f"(d[50]), "=f"(d[51]), "=f"(d[52]), "=f"(d[53]), "=f"(d[54]), "=f"(d[55]),
        "=f"(d[56]), "=f"(d[57]), "=f"(d[58]), "=f"(d[59]), "=f"(d[60]), "=f"(d[61]), "=f"(d[62]), "=f"(d[63])
      : "l"(da), "l"(db), "r"(scaleD));
}
__device__ __forceinline__ void wgmma_proj96_init(float (&d)[64], uint64_t da, uint64_t db, int scaleD) {
  asm volatile("{\n.reg .pred p;\nsetp.ne.b32 p, %50, 0;\n"
      "wgmma.mma_async.sync.aligned.m64n96k16.f32.bf16.bf16 "
      "{%0, %1, %2, %3, %4, %5, %6, %7, %8, %9, %10, %11, %12, %13, %14, %15, %16, %17, %18, %19, %20, %21, %22, %23, %24, %25, %26, %27, %28, %29, %30, "
      "%31, %32, %33, %34, %35, %36, %37, %38, %39, %40, %41, %42, %43, %44, %45, %46, %47}, "
      "%48, %49, p, 1, 1, 1, 0;\n}\n"
      : "=f"(d[0]), "=f"(d[1]), "=f"(d[2]), "=f"(d[3]), "=f"(d[4]), "=f"(d[5]), "=f"(d[6]), "=f"(d[7]), "=f"(d[8]), "=f"(d[9]), "=f"(d[10]), "=f"(d[11]),
        "=f"(d[12]), "=f"(d[13]), "=f"(d[14]), "=f"(d[15]), "=f"(d[16]), "=f"(d[17]), "=f"(d[18]), "=f"(d[19]), "=f"(d[20]), "=f"(d[21]), "=f"(d[22]),
        "=f"(d[23]), "=f"(d[24]), "=f"(d[25]), "=f"(d[26]), "=f"(d[27]), "=f"(d[28]), "=f"(d[29]), "=f"(d[30]), "=f"(d[31]), "=f"(d[32]), "=f"(d[33]),
        "=f"(d[34]), "=f"(d[35]), "=f"(d[36]), "=f"(d[37]), "=f"(d[38]), "=f"(d[39]), "=f"(d[40]), "=f"(d[41]), "=f"(d[42]), "=f"(d[43]), "=f"(d[44]),
        "=f"(d[45]), "=f"(d[46]), "=f"(d[47])
      : "l"(da), "l"(db), "r"(scaleD));
}
__device__ __forceinline__ void wgmma_qk_init(float (&d)[32], uint64_t da, uint64_t db, int scaleD) {
  asm volatile("{\n.reg .pred p;\nsetp.ne.b32 p, %34, 0;\n"
      "wgmma.mma_async.sync.aligned.m64n64k16.f32.bf16.bf16 "
      "{%0, %1, %2, %3, %4, %5, %6, %7, %8, %9, %10, %11, %12, %13, %14, %15, %16, %17, %18, %19, %20, %21, %22, %23, %24, %25, %26, %27, %28, %29, %30, "
      "%31}, "
      "%32, %33, p, 1, 1, 0, 0;\n}\n"
      : "=f"(d[0]), "=f"(d[1]), "=f"(d[2]), "=f"(d[3]), "=f"(d[4]), "=f"(d[5]), "=f"(d[6]), "=f"(d[7]), "=f"(d[8]), "=f"(d[9]), "=f"(d[10]), "=f"(d[11]),
        "=f"(d[12]), "=f"(d[13]), "=f"(d[14]), "=f"(d[15]), "=f"(d[16]), "=f"(d[17]), "=f"(d[18]), "=f"(d[19]), "=f"(d[20]), "=f"(d[21]), "=f"(d[22]),
        "=f"(d[23]), "=f"(d[24]), "=f"(d[25]), "=f"(d[26]), "=f"(d[27]), "=f"(d[28]), "=f"(d[29]), "=f"(d[30]), "=f"(d[31])
      : "l"(da), "l"(db), "r"(scaleD));
}
__device__ __forceinline__ void wgmma_qk_rs_init(float (&d)[32], uint32_t a0, uint32_t a1, uint32_t a2, uint32_t a3, uint64_t db, int scaleD) {
  asm volatile("{\n.reg .pred p;\nsetp.ne.b32 p, %37, 0;\n"
      "wgmma.mma_async.sync.aligned.m64n64k16.f32.bf16.bf16 "
      "{%0, %1, %2, %3, %4, %5, %6, %7, %8, %9, %10, %11, %12, %13, %14, %15, %16, %17, %18, %19, %20, %21, %22, %23, %24, %25, %26, %27, %28, %29, %30, "
      "%31}, "
      "{%32, %33, %34, %35}, %36, p, 1, 1, 0;\n}\n"
      : "=f"(d[0]), "=f"(d[1]), "=f"(d[2]), "=f"(d[3]), "=f"(d[4]), "=f"(d[5]), "=f"(d[6]), "=f"(d[7]), "=f"(d[8]), "=f"(d[9]), "=f"(d[10]), "=f"(d[11]),
        "=f"(d[12]), "=f"(d[13]), "=f"(d[14]), "=f"(d[15]), "=f"(d[16]), "=f"(d[17]), "=f"(d[18]), "=f"(d[19]), "=f"(d[20]), "=f"(d[21]), "=f"(d[22]),
        "=f"(d[23]), "=f"(d[24]), "=f"(d[25]), "=f"(d[26]), "=f"(d[27]), "=f"(d[28]), "=f"(d[29]), "=f"(d[30]), "=f"(d[31])
      : "r"(a0), "r"(a1), "r"(a2), "r"(a3), "l"(db), "r"(scaleD));
}
__device__ __forceinline__ void wgmma_pv_init(float (&d)[64], uint32_t a0, uint32_t a1, uint32_t a2, uint32_t a3, uint64_t db, int scaleD) {
  asm volatile("{\n.reg .pred p;\nsetp.ne.b32 p, %69, 0;\n"
      "wgmma.mma_async.sync.aligned.m64n128k16.f32.bf16.bf16 "
      "{%0, %1, %2, %3, %4, %5, %6, %7, %8, %9, %10, %11, %12, %13, %14, %15, %16, %17, %18, %19, %20, %21, %22, %23, %24, %25, %26, %27, %28, %29, %30, "
      "%31, %32, %33, %34, %35, %36, %37, %38, %39, %40, %41, %42, %43, %44, %45, %46, %47, %48, %49, %50, %51, %52, %53, %54, %55, %56, %57, %58, %59, %60, "
      "%61, %62, %63}, "
      "{%64, %65, %66, %67}, %68, p, 1, 1, 1;\n}\n"
      : "=f"(d[0]), "=f"(d[1]), "=f"(d[2]), "=f"(d[3]), "=f"(d[4]), "=f"(d[5]), "=f"(d[6]), "=f"(d[7]), "=f"(d[8]), "=f"(d[9]), "=f"(d[10]), "=f"(d[11]),
        "=f"(d[12]), "=f"(d[13]), "=f"(d[14]), "=f"(d[15]), "=f"(d[16]), "=f"(d[17]), "=f"(d[18]), "=f"(d[19]), "=f"(d[20]), "=f"(d[21]), "=f"(d[22]),
        "=f"(d[23]), "=f"(d[24]), "=f"(d[25]), "=f"(d[26]), "=f"(d[27]), "=f"(d[28]), "=f"(d[29]), "=f"(d[30]), "=f"(d[31]), "=f"(d[32]), "=f"(d[33]),
        "=f"(d[34]), "=f"(d[35]), "=f"(d[36]), "=f"(d[37]), "=f"(d[38]), "=f"(d[39]), "=f"(d[40]), "=f"(d[41]), "=f"(d[42]), "=f"(d[43]), "=f"(d[44]),
        "=f"(d[45]), "=f"(d[46]), "=f"(d[47]), "=f"(d[48]), "=f"(d[49]), "=f"(d[50]), "=f"(d[51]), "=f"(d[52]), "=f"(d[53]), "=f"(d[54]), "=f"(d[55]),
        "=f"(d[56]), "=f"(d[57]), "=f"(d[58]), "=f"(d[59]), "=f"(d[60]), "=f"(d[61]), "=f"(d[62]), "=f"(d[63])
      : "r"(a0), "r"(a1), "r"(a2), "r"(a3), "l"(db), "r"(scaleD));
}
__device__ __forceinline__ void wgmma_qk_sp_init(float (&d)[32], uint32_t a0, uint32_t a1, uint32_t a2, uint32_t a3, uint64_t db, int scaleD, uint32_t meta) {
  asm volatile("{\n.reg .pred p;\nsetp.ne.b32 p, %37, 0;\n"
      "wgmma.mma_async.sp.sync.aligned.m64n64k32.f32.bf16.bf16 "
      "{%0, %1, %2, %3, %4, %5, %6, %7, %8, %9, %10, %11, %12, %13, %14, %15, %16, %17, %18, %19, %20, %21, %22, %23, %24, %25, %26, %27, %28, %29, %30, "
      "%31}, "
      "{%32, %33, %34, %35}, %36, %38, 0, p, 1, 1, 0;\n}\n"
      : "=f"(d[0]), "=f"(d[1]), "=f"(d[2]), "=f"(d[3]), "=f"(d[4]), "=f"(d[5]), "=f"(d[6]), "=f"(d[7]), "=f"(d[8]), "=f"(d[9]), "=f"(d[10]), "=f"(d[11]),
        "=f"(d[12]), "=f"(d[13]), "=f"(d[14]), "=f"(d[15]), "=f"(d[16]), "=f"(d[17]), "=f"(d[18]), "=f"(d[19]), "=f"(d[20]), "=f"(d[21]), "=f"(d[22]),
        "=f"(d[23]), "=f"(d[24]), "=f"(d[25]), "=f"(d[26]), "=f"(d[27]), "=f"(d[28]), "=f"(d[29]), "=f"(d[30]), "=f"(d[31])
      : "r"(a0), "r"(a1), "r"(a2), "r"(a3), "l"(db), "r"(scaleD), "r"(meta));
}
__device__ __forceinline__ void wgmma_pv_sp_init(float (&d)[64], uint32_t a0, uint32_t a1, uint32_t a2, uint32_t a3, uint64_t db, int scaleD, uint32_t meta) {
  asm volatile("{\n.reg .pred p;\nsetp.ne.b32 p, %69, 0;\n"
      "wgmma.mma_async.sp.sync.aligned.m64n128k32.f32.bf16.bf16 "
      "{%0, %1, %2, %3, %4, %5, %6, %7, %8, %9, %10, %11, %12, %13, %14, %15, %16, %17, %18, %19, %20, %21, %22, %23, %24, %25, %26, %27, %28, %29, %30, "
      "%31, %32, %33, %34, %35, %36, %37, %38, %39, %40, %41, %42, %43, %44, %45, %46, %47, %48, %49, %50, %51, %52, %53, %54, %55, %56, %57, %58, %59, %60, "
      "%61, %62, %63}, "
      "{%64, %65, %66, %67}, %68, %70, 0, p, 1, 1, 1;\n}\n"
      : "=f"(d[0]), "=f"(d[1]), "=f"(d[2]), "=f"(d[3]), "=f"(d[4]), "=f"(d[5]), "=f"(d[6]), "=f"(d[7]), "=f"(d[8]), "=f"(d[9]), "=f"(d[10]), "=f"(d[11]),
        "=f"(d[12]), "=f"(d[13]), "=f"(d[14]), "=f"(d[15]), "=f"(d[16]), "=f"(d[17]), "=f"(d[18]), "=f"(d[19]), "=f"(d[20]), "=f"(d[21]), "=f"(d[22]),
        "=f"(d[23]), "=f"(d[24]), "=f"(d[25]), "=f"(d[26]), "=f"(d[27]), "=f"(d[28]), "=f"(d[29]), "=f"(d[30]), "=f"(d[31]), "=f"(d[32]), "=f"(d[33]),
        "=f"(d[34]), "=f"(d[35]), "=f"(d[36]), "=f"(d[37]), "=f"(d[38]), "=f"(d[39]), "=f"(d[40]), "=f"(d[41]), "=f"(d[42]), "=f"(d[43]), "=f"(d[44]),
        "=f"(d[45]), "=f"(d[46]), "=f"(d[47]), "=f"(d[48]), "=f"(d[49]), "=f"(d[50]), "=f"(d[51]), "=f"(d[52]), "=f"(d[53]), "=f"(d[54]), "=f"(d[55]),
        "=f"(d[56]), "=f"(d[57]), "=f"(d[58]), "=f"(d[59]), "=f"(d[60]), "=f"(d[61]), "=f"(d[62]), "=f"(d[63])
      : "r"(a0), "r"(a1), "r"(a2), "r"(a3), "l"(db), "r"(scaleD), "r"(meta));
}

constexpr int NB = 16, SQ = 224, DM = 640, NH = 32, SK = 1024, DH = 128;
constexpr int HD = NH * DH;
constexpr int NBETA = 2 * NB;
constexpr int NCTA = 132;
constexpr uint32_t SB0 = 1024;
constexpr int NS = 10;
constexpr int SLOT = 16384;
constexpr int QBUF_OFF = NS * SLOT;
constexpr int NSX = NS + 4;
constexpr int BAR_OFF = NSX * SLOT;
constexpr int BAR_FULL = BAR_OFF;
constexpr int BAR_EMPTY = BAR_OFF + 8 * NSX;
constexpr int BAR_STG = BAR_OFF + 16 * NSX;
constexpr int BAR_OUT = BAR_STG + 32;
constexpr int BAR_DESC = BAR_OUT + 8;
constexpr int BAR_GO = BAR_DESC + 8;
constexpr int BAR_MAIL = BAR_GO + 8;
constexpr int BAR_RDY = BAR_MAIL + 8;
constexpr int DESC_OFF = BAR_RDY + 8 * NSX;
constexpr int EPOCH_OFF = DESC_OFF + 16;
constexpr int TRACE_OFF = EPOCH_OFF + 16;
constexpr int SMEM_BYTES = TRACE_OFF;
constexpr float SM_C = 0.08838834764831845f * 1.4426950408889634f;
constexpr float SUM_HI = 1099511627776.f, SUM_LO = 1.f / 1099511627776.f;
constexpr uint32_t META_QK = 0xEEEE4444u;
constexpr uint32_t META_PV = 0x44EEEE44u;

#define QK_EARLY_MASK 3
#define ST_ORDER 0x2310
#define LAG_BAR 2
#define ST_NOW 8
#define PF_STEP 5
#define KV_WIN_UNITS 2
#define KV_WIN_D 4
#define SF 0xeebf
#define O_STEPS 4
#define KV_WIN_RAMP 4
#define PDEPTH 0
#define KV_WIN_TILES -2
#define REG_C 232
#define REG_P 24
#define GO_P 6
#define P_POS 216
#define OR 6
#define OR0 0
#define B_LATE 23
#define H_LATE 24
#define RM0 1
#define RM1 0xab
#define RM2 0
#define CLUSTER 1
#define PAIRB 1
#define LATE0 1
#define LATE1 2
#define GO_J 13
#define KG 5
#define PK 44
#define EARLY_MASK 0x3fffu
#define PIECE_TABLE 0x50188016,0x65e88038,0x50321819,0x6c8d1830,0x403f2812,0x80000000,0x50215014,0x695a503c,0x5029b813,0x6c4eb85e,0x501b4815,0x689d4834,0x502b1017,0x6ccc1039,0x50312010,0x80000000,0x500e681b,0x65e8683f,0x502ea011,0x80000000,0x63b1902e,0x80000000,0x63f0603b,0x80000000,0x64ad003d,0x80000000,0x64eca83a,0x80000000,0x5024581c,0x80000000,0x5012b01a,0x6a95b033,0x5011081d,0x6b130837,0x5016701f,0x6c8d7056,0x501ec81e,0x80000000,0x6723302f,0x80000000,0x501b380f,0x80000000,0x67234035,0x80000000,0x500d980e,0x6bd09831,0x56587816,0x80000000,0x50168818,0x80000000,0x57d1c01e,0x80000000

struct Params {
  CUtensorMap x[2][2], wq[2], kv[2][2], wo[2];
  CUtensorMap o_ld[2], o_st[2], out_st[2];
  const __nv_bfloat16* kp[2];
  const __nv_bfloat16* vp[2];
};

constexpr int NPART = 32 * 5, O_BLOCKS = NBETA * 64 + 2 * NPART;
__device__ __align__(128) __nv_bfloat16 g_o[(size_t)O_BLOCKS * SQ * 64];
__device__ unsigned g_cnt[NBETA][8];
__device__ unsigned g_rd[NBETA][8];
__device__ unsigned g_epoch, g_next;
__device__ unsigned g_flag[NPART];

__device__ __forceinline__ uint32_t smem_u32(const void* p) { return (uint32_t)__cvta_generic_to_shared(p); }
__device__ __forceinline__ void mbar_arrive(uint32_t bar) {
  asm volatile("mbarrier.arrive.shared::cta.b64 _, [%0];" ::"r"(bar) : "memory");
}
__device__ __forceinline__ void mbar_arrive_warp(uint32_t bar) {
  asm volatile("{\n.reg .pred p;\nelect.sync _|p, 0xffffffff;\n@p mbarrier.arrive.shared::cta.b64 _, [%0];\n}" ::"r"(bar) : "memory");
}
__device__ __forceinline__ int lane_now() { int l; asm volatile("mov.u32 %0, %%laneid;" : "=r"(l)); return l; }
__device__ __forceinline__ bool mbar_try(uint32_t bar, uint32_t parity) {
  uint32_t ok;
  asm volatile("{\n.reg .pred p;\nmbarrier.try_wait.parity.shared::cta.b64 p, [%1], %2;\nselp.u32 %0, 1, 0, p;\n}"
               : "=r"(ok) : "r"(bar), "r"(parity) : "memory");
  return ok;
}
__device__ __forceinline__ bool mbar_test(uint32_t bar, uint32_t parity) {
  uint32_t ok;
  asm volatile("{\n.reg .pred p;\nmbarrier.test_wait.parity.shared::cta.b64 p, [%1], %2;\nselp.u32 %0, 1, 0, p;\n}"
               : "=r"(ok) : "r"(bar), "r"(parity) : "memory");
  return ok;
}
__device__ __forceinline__ void mbar_wait_w(uint32_t bar, uint32_t parity) {
  uint32_t n = 0;
  while (!__all_sync(0xffffffffu, mbar_try(bar, parity))) {
    if (++n > (1u << 22)) __trap();
  }
}
#define ELECT "{\n.reg .pred p;\nelect.sync _|p, 0xffffffff;\n@p "
__device__ __forceinline__ void tma_st3_hint_w(const CUtensorMap* m, uint32_t src, int c0, int c1, int c2, uint64_t pol) {
  asm volatile(ELECT "cp.async.bulk.tensor.3d.global.shared::cta.bulk_group.L2::cache_hint [%0, {%2, %3, %4}], [%1], %5;\n}"
               ::"l"(m), "r"(src), "r"(c0), "r"(c1), "r"(c2), "l"(pol) : "memory");
}
#define EXPECT(bar, bytes) "mbarrier.arrive.expect_tx.shared::cta.b64 _, [" bar "], " bytes ";\n@p "
__device__ __forceinline__ void tma_ld2_w(uint32_t dst, const CUtensorMap* m, int c0, int c1, uint32_t bar, uint32_t bytes) {
  asm volatile(ELECT EXPECT("%2", "%5") "cp.async.bulk.tensor.2d.shared::cluster.global.mbarrier::complete_tx::bytes [%0], [%1, {%3, %4}], [%2];\n}"
               ::"r"(dst), "l"(m), "r"(bar), "r"(c0), "r"(c1), "r"(bytes) : "memory");
}
__device__ __forceinline__ void tma_ld2_hint_w(uint32_t dst, const CUtensorMap* m, int c0, int c1, uint32_t bar, uint32_t bytes, uint64_t pol) {
  asm volatile(ELECT EXPECT("%2", "%6") "cp.async.bulk.tensor.2d.shared::cluster.global.mbarrier::complete_tx::bytes.L2::cache_hint"
               " [%0], [%1, {%3, %4}], [%2], %5;\n}"
               ::"r"(dst), "l"(m), "r"(bar), "r"(c0), "r"(c1), "l"(pol), "r"(bytes) : "memory");
}
__device__ __forceinline__ void tma_ld3_w(uint32_t dst, const CUtensorMap* m, int c0, int c1, int c2, uint32_t bar, uint32_t bytes) {
  asm volatile(ELECT EXPECT("%2", "%6") "cp.async.bulk.tensor.3d.shared::cluster.global.mbarrier::complete_tx::bytes [%0], [%1, {%3, %4, %5}], [%2];\n}"
               ::"r"(dst), "l"(m), "r"(bar), "r"(c0), "r"(c1), "r"(c2), "r"(bytes) : "memory");
}
__device__ __forceinline__ void tma_ld_kv_w(uint32_t dst, const CUtensorMap* m, int grp, uint32_t bar, uint64_t pol) {
  asm volatile(ELECT EXPECT("%2", "16384") "cp.async.bulk.tensor.4d.shared::cluster.global.mbarrier::complete_tx::bytes.L2::cache_hint"
               " [%0], [%1, {0, 0, 0, %3}], [%2], %4;\n}"
               ::"r"(dst), "l"(m), "r"(bar), "r"(grp), "l"(pol) : "memory");
}
__device__ __forceinline__ void tma_ld_wo_w(uint32_t dst, const CUtensorMap* m, int col, int grp, uint32_t bar) {
  asm volatile(ELECT EXPECT("%2", "16384") "cp.async.bulk.tensor.5d.shared::cluster.global.mbarrier::complete_tx::bytes [%0], [%1, {%3, 0, 0, 0, %4}], [%2];\n"
               "@p cp.async.bulk.tensor.5d.shared::cluster.global.mbarrier::complete_tx::bytes [%5], [%1, {%6, 0, 0, 0, %4}], [%2];\n}"
               ::"r"(dst), "l"(m), "r"(bar), "r"(col), "r"(grp), "r"(dst + 8192), "r"(col + 64) : "memory");
}
__device__ __forceinline__ void mbar_arrive8_w(uint32_t bar) {
  asm volatile(ELECT "mbarrier.arrive.shared::cta.b64 _, [%0], 8;\n}" ::"r"(bar) : "memory");
}
__device__ __forceinline__ uint32_t peer(uint32_t a) { uint32_t r; asm("mapa.shared::cluster.u32 %0, %1, %2;" : "=r"(r) : "r"(a), "r"(~blockIdx.x & 1)); return r; }
__device__ __forceinline__ void tma_ld2_both_w(uint32_t dst, const CUtensorMap* m, int c0, int c1, uint32_t bar, uint32_t bytes) {
  asm volatile(ELECT EXPECT("%2", "%5") "cp.async.bulk.tensor.2d.shared::cluster.global.mbarrier::complete_tx::bytes.multicast::cluster"
               " [%0], [%1, {%3, %4}], [%2], %6;\n}"
               ::"r"(dst), "l"(m), "r"(bar), "r"(c0), "r"(c1), "r"(bytes), "h"((uint16_t)3) : "memory");
}
__device__ __forceinline__ void tma_ld2_both_hint_w(uint32_t dst, const CUtensorMap* m, int c0, int c1, uint32_t bar, uint32_t bytes, uint64_t pol) {
  asm volatile(ELECT EXPECT("%2", "%6") "cp.async.bulk.tensor.2d.shared::cluster.global.mbarrier::complete_tx::bytes.multicast::cluster.L2::cache_hint"
               " [%0], [%1, {%3, %4}], [%2], %7, %5;\n}"
               ::"r"(dst), "l"(m), "r"(bar), "r"(c0), "r"(c1), "l"(pol), "r"(bytes), "h"((uint16_t)3) : "memory");
}
__device__ __forceinline__ void bulk_commit() { asm volatile("cp.async.bulk.commit_group;" ::: "memory"); }
template <int N> __device__ __forceinline__ void bulk_wait_read() { asm volatile("cp.async.bulk.wait_group.read %0;" ::"n"(N) : "memory"); }
__device__ __forceinline__ void wg_fence() { asm volatile("wgmma.fence.sync.aligned;" ::: "memory"); }
__device__ __forceinline__ void wg_commit() { asm volatile("wgmma.commit_group.sync.aligned;" ::: "memory"); }
template <int N> __device__ __forceinline__ void wg_wait() { asm volatile("wgmma.wait_group.sync.aligned %0;" ::"n"(N) : "memory"); }
__device__ __forceinline__ void fence_async_smem() { asm volatile("fence.proxy.async.shared::cta;" ::: "memory"); }
__device__ __forceinline__ void bar_sync(int id, int n) { asm volatile("bar.sync %0, %1;" ::"r"(id), "r"(n) : "memory"); }
__device__ __forceinline__ void touch(float& a) { asm volatile("neg.f32 %0, %0;" : "+f"(a)); }
__device__ __forceinline__ void touch(uint32_t& a) { asm volatile("not.b32 %0, %0;" : "+r"(a)); }
template <typename T, int N> __device__ __forceinline__ void touch(T (&a)[N]) {
#pragma unroll
  for (int i = 0; i < N; i++) touch(a[i]);
}
template <int ID, typename... A> __device__ __forceinline__ void sched_fence(uint32_t x, A&... a) {
  if (!((SF >> ID) & 1)) return;
  asm volatile("" : "+r"(x)::"memory");
#pragma unroll 1
  for (; __builtin_expect(x >= 100 + ID, 0); x >>= 1) { (touch(a), ...); __nanosleep(x); }
}
template <int N> __device__ __forceinline__ void reg_fence(float (&a)[N]) {
#pragma unroll
  for (int i = 0; i < N; i++) asm volatile("" : "+f"(a[i])::"memory");
}
template <int N> __device__ __forceinline__ void reg_fence(uint32_t (&a)[N]) {
#pragma unroll
  for (int i = 0; i < N; i++) asm volatile("" : "+r"(a[i])::"memory");
}
__device__ __forceinline__ float ex2(float x) { float y; asm("ex2.approx.ftz.f32 %0, %1;" : "=f"(y) : "f"(x)); return y; }
__device__ __forceinline__ uint32_t pack_bf16(float lo, float hi) {
  uint32_t r; asm("cvt.rn.bf16x2.f32 %0, %1, %2;" : "=r"(r) : "f"(hi), "f"(lo)); return r;
}
__device__ __forceinline__ void stsm4(uint32_t a, uint32_t r0, uint32_t r1, uint32_t r2, uint32_t r3) {
  asm volatile("stmatrix.sync.aligned.m8n8.x4.shared.b16 [%0], {%1, %2, %3, %4};" ::"r"(a), "r"(r0), "r"(r1), "r"(r2), "r"(r3) : "memory");
}
__device__ __forceinline__ void stsm4t(uint32_t a, uint32_t r0, uint32_t r1, uint32_t r2, uint32_t r3) {
  asm volatile("stmatrix.sync.aligned.m8n8.x4.trans.shared.b16 [%0], {%1, %2, %3, %4};" ::"r"(a), "r"(r0), "r"(r1), "r"(r2), "r"(r3) : "memory");
}
__device__ __forceinline__ void ldsm4(uint32_t a, uint32_t& r0, uint32_t& r1, uint32_t& r2, uint32_t& r3) {
  asm volatile("ldmatrix.sync.aligned.m8n8.x4.shared.b16 {%0, %1, %2, %3}, [%4];" : "=r"(r0), "=r"(r1), "=r"(r2), "=r"(r3) : "r"(a) : "memory");
}
__device__ __forceinline__ void sts16(uint32_t a, uint32_t v) { asm volatile("st.shared.u16 [%0], %1;" ::"r"(a), "h"((uint16_t)v) : "memory"); }
__device__ __forceinline__ void mma16816(float& c0, float& c1, float& c2, float& c3, uint32_t a0, uint32_t a1, uint32_t a2, uint32_t a3,
                                         uint32_t b0, uint32_t b1) {
  asm volatile("mma.sync.aligned.m16n8k16.row.col.f32.bf16.bf16.f32 {%0, %1, %2, %3}, {%4, %5, %6, %7}, {%8, %9}, {%0, %1, %2, %3};"
               : "+f"(c0), "+f"(c1), "+f"(c2), "+f"(c3) : "r"(a0), "r"(a1), "r"(a2), "r"(a3), "r"(b0), "r"(b1));
}
__device__ __forceinline__ uint32_t sdesc(uint32_t addr, uint32_t lbo) { return (addr >> 4) + ((lbo >> 4) << 16); }
__device__ __forceinline__ uint64_t desc64(uint32_t lo, uint32_t hi) { uint64_t d; asm("mov.b64 %0, {%1, %2};" : "=l"(d) : "r"(lo), "r"(hi)); return d; }
__device__ __forceinline__ void dadd(uint64_t& d, uint32_t inc) {
  asm("{\n.reg .b32 l, h;\nmov.b64 {l, h}, %0;\nadd.u32 l, l, %1;\nmov.b64 %0, {l, h};\n}" : "+l"(d) : "r"(inc));
}

struct Ring {
  uint32_t slot, phase, xp;
  __device__ __forceinline__ void uniform() {
    slot = __shfl_sync(0xffffffffu, slot, 0); phase = __shfl_sync(0xffffffffu, phase, 0); xp = __shfl_sync(0xffffffffu, xp, 0);
  }
  __device__ __forceinline__ void next() { if (++slot == NS) { slot = 0; phase ^= 1; } }
  __device__ __forceinline__ void next_if(bool p) { slot += p; if (slot == NS) { slot = 0; phase ^= 1; } }
};
__device__ __forceinline__ uint32_t borrow(int ks, int n) {
  const int k = ks + 1;
  return k >= 4 && !(k & 2) && k < n ? k & 1 : 2;
}

constexpr uint32_t Q_RANGES = NBETA * NH + __builtin_popcount(EARLY_MASK) * 5, Q_ALL = NBETA * (NH + 5);
constexpr int NRANGE = NCTA / 5;
struct Work { int kind, mode, k0, nsteps, range, beta, sub; };
struct Sched { uint16_t queue[Q_ALL]; uint32_t piece[NRANGE + 1][4]; };
constexpr Sched make_sched() {
  Sched s{};
  int q = 0, a = 0;
  for (int t = 0, e = 0; a < NBETA * NH; t++) {
    for (; e < NBETA && 8 * (e & ~PAIRB) + PK <= t && a >= P_POS; e++)
      for (int col = 0; col < 5 && (EARLY_MASK >> e & 1); col++) s.queue[q++] = 0x8000 | (e & 1 ? 4 - col : col) << 8 | e;
    for (int b = 0; b < NBETA; b++)
      for (int h = 0; h < NH; h++)
        if ((b >= B_LATE && h >= H_LATE ? 300 + b : 8 * (b & ~PAIRB) + KG * (h >> 2)) == t) { s.queue[q++] = b << 5 | h; a++; }
  }
  for (int b = 0; b < NBETA; b++)
    for (int col = 0; col < 5 && !(EARLY_MASK >> b & 1); col++) s.queue[q++] = 0x8000 | col << 8 | b;
  constexpr uint32_t T[NRANGE * 2] = {PIECE_TABLE};
  for (int g = 0; g <= NRANGE; g++)
    for (int n = 0; n < 4; n++) s.piece[g][n] = g < NRANGE && n < 2 ? T[2 * g + n] : 2u << 30;
  return s;
}
__constant__ Sched c_sched = make_sched();
constexpr int N_EARLY = __builtin_popcount(EARLY_MASK);
constexpr bool reuse_ok() {
  const Sched s = make_sched();
  int first[NBETA + OR] = {};
  for (int q = Q_RANGES - 1; q >= 0; q--) if (!(s.queue[q] & 0x8000)) first[s.queue[q] >> 5] = q;
  for (int q = 0; q < Q_RANGES; q++) if ((s.queue[q] & 0x8000) && (s.queue[q] & 31) >= OR0 && q - first[(s.queue[q] & 31) + OR] > NCTA - 32) return false;
  return true;
}
static_assert(reuse_ok());
template <bool SIMPLE> __device__ __forceinline__ bool o_reuse(uint32_t b) { return !SIMPLE && b - (OR0 + OR) < N_EARLY - OR0; }
template <bool SIMPLE> __device__ __forceinline__ uint32_t o_slot(uint32_t b) { return o_reuse<SIMPLE>(b) ? OR0 + (b - OR0) % OR : b; }
__device__ __forceinline__ Work decode(uint32_t d) {
  Work w;
  w.kind = d >> 30; if (w.kind == 3) w.kind = 1;
  w.mode = (d >> 28) & 3; w.k0 = (d >> 22) & 63;
  if (w.kind == 0) { w.beta = (d >> 5) & 31; w.sub = d & 31; w.nsteps = DM / 64; }
  else { w.beta = d & 31; w.sub = (d >> 8) & 7; w.nsteps = ((d >> 16) & 63) + 1; }
  w.range = ((d >> 11) & 31) * 5 + w.sub;
  return w;
}

__device__ __forceinline__ bool reached(const unsigned* cnt, unsigned target) {
  unsigned v;
  asm volatile("ld.acquire.gpu.global.u32 %0, [%1];" : "=r"(v) : "l"(cnt) : "memory");
  return (int)(v - target) >= 0;
}
__device__ __forceinline__ void wait_count(const unsigned* cnt, unsigned target) {
  unsigned n = 0;
  while (!__all_sync(0xffffffffu, reached(cnt, target))) { if (++n > (1u << 24)) __trap(); }
}
__device__ __forceinline__ uint32_t lds(uint32_t a) { uint32_t v; asm volatile("ld.volatile.shared.u32 %0, [%1];" : "=r"(v) : "r"(a) : "memory"); return v; }

#define TRACE(u, e)
#define T3(u, e)
#define T2C(u, e)
#define T2P(u, r, e)
#define TTAIL(k)
#define TCLK(k)
#define TO -1
#define TRACE_O(k) if (TO == k) TRACE(i, 5)
#define TRACE_P(u, e)
#define TRACE_IN(u, e)

struct Ctx {
  uint32_t sb;
  int wg, warp;
  uint32_t mqk, mpv;
  bool lead;
  int lane0, lane;
  int src;
};
template <int N> __device__ __forceinline__ uint32_t dhi(uint32_t lo) { return 0x40000040u + (lo >> (26 + N)); }
__device__ __forceinline__ void release(const Ctx& c, uint32_t slot) {
  if (c.lead) mbar_arrive(c.sb + BAR_EMPTY + slot * 8);
}
__device__ __forceinline__ uint32_t acquire(const Ctx& c, Ring& r, bool have = false) {
  const uint32_t s = r.slot;
  if (!have) mbar_wait_w(c.sb + BAR_FULL + s * 8, r.phase);
  r.next();
  return s;
}
__device__ __forceinline__ void mbar_wait2_w(uint32_t b0, uint32_t p0, uint32_t b1, uint32_t p1) {
  uint32_t n = 0;
  while (!__all_sync(0xffffffffu, mbar_try(b0, p0) & mbar_try(b1, p1))) {
    if (++n > (1u << 22)) __trap();
  }
}
__device__ __forceinline__ void mbar_wait3_w(uint32_t b0, uint32_t p0, uint32_t b1, uint32_t p1, uint32_t b2, uint32_t p2) {
  uint32_t n = 0;
  while (!__all_sync(0xffffffffu, mbar_try(b0, p0) & mbar_try(b1, p1) & mbar_try(b2, p2))) {
    if (++n > (1u << 22)) __trap();
  }
}
__device__ __forceinline__ void acquire2(const Ctx& c, Ring& r, uint32_t& s0, uint32_t& s1, bool have = false) {
  const uint32_t p0 = r.phase;
  s0 = r.slot; r.next(); s1 = r.slot;
  if (!have) mbar_wait2_w(c.sb + BAR_FULL + s0 * 8, p0, c.sb + BAR_FULL + s1 * 8, r.phase);
  r.next();
}
template <int N>
__device__ __forceinline__ bool peek(const Ctx& c, Ring r) {
  bool ok = true;
#pragma unroll
  for (int k = 0; k < N; k++) { ok &= mbar_test(c.sb + BAR_FULL + r.slot * 8, r.phase); r.next(); }
  return ok;
}
__device__ __forceinline__ void staged(const Ctx& c, int part) {
  fence_async_smem();
  __syncwarp();
  mbar_arrive_warp(c.sb + BAR_STG + c.wg * 16 + part * 8);
}

template <int WG, bool FIRST, int H>
__device__ __forceinline__ void proj_half(const Ctx& c, float (&acc)[64], uint32_t w, uint32_t x, uint32_t sw) {
  uint64_t dx = desc64((SB0 + x * SLOT + (WG ? 0 : H * 8192)) >> 4, dhi<0>(x) + sw);
  uint64_t dw = desc64(WG ? (SB0 + w * SLOT + H * 8192) >> 4 : sdesc(SB0 + w * SLOT, 8192), dhi<1>(x));
  wg_fence();
  if (WG) { if (FIRST) wgmma_proj96_init(acc, dw, dx, 0); else wgmma_proj96(acc, dw, dx, 1); }
  else { if (FIRST) wgmma_proj_init(acc, dx, dw, 0); else wgmma_proj(acc, dx, dw, 1); }
#pragma unroll
  for (int k = 1; k < 4; k++) {
    dadd(dx, k == 2 ? 2 + (sw >> 30) * 28 : 2); dadd(dw, 128);
    if (WG) wgmma_proj96(acc, dw, dx, 1); else wgmma_proj(acc, dx, dw, 1);
  }
  wg_commit();
}

__device__ __forceinline__ void proj_store16(uint32_t a, const float* f, float sc) {
  stsm4t(a, pack_bf16(f[0] * sc, f[1] * sc), pack_bf16(f[2] * sc, f[3] * sc), pack_bf16(f[4] * sc, f[5] * sc), pack_bf16(f[6] * sc, f[7] * sc));
}

__device__ __forceinline__ uint32_t stage_off(const Ctx& c) {
  const int lane = c.lane, mi = lane >> 3, r8 = lane & 7;
  return ((mi >> 1) * 8 + r8) * 128 + (((2 * c.warp + (mi & 1)) ^ r8) << 4);
}
__device__ __forceinline__ uint32_t q3_swz(uint32_t r8) { return ((r8 & 3) << 1) | (r8 >> 2); }
template <int H>
__device__ __forceinline__ void stage_t2(const Ctx& c, const float (&a)[64], float sc) {
  const uint32_t base = c.sb + QBUF_OFF + 2 * 16384 + H * 8192 + stage_off(c);
#pragma unroll
  for (int jj = 0; jj < 4; jj++) proj_store16(base + jj * 2048, &a[jj * 8], sc);
}
template <int H, bool IS_Q>
__device__ __forceinline__ void stage_t3(const Ctx& c, const float (&a)[64], float sc) {
  const uint32_t off = stage_off(c), r8 = (off >> 7) & 7;
  const uint32_t t3 = c.sb + QBUF_OFF + 3 * 16384 + H * 4096 + (IS_Q ? off ^ ((r8 ^ q3_swz(r8)) << 4) : off);
  proj_store16(t3, &a[32], sc);
  proj_store16(t3 + 2048, &a[40], sc);
}

template <int WG, int h>
__device__ __forceinline__ void load_part(const Ctx& c, Ring r, uint32_t (&q)[32]) {
  uint32_t n = 0;
  while (!h && !__all_sync(0xffffffffu, peek<4>(c, r))) {
    if (++n > (1u << 26)) __trap();
  }
  const int lane = c.lane, mi = lane >> 3, r8 = lane & 7;
  if (WG) { r.next(); r.next(); }
  const uint32_t off = c.sb + (WG ? stage_off(c) : (16 * c.warp + (mi & 1) * 8 + r8) * 128), t0 = off + r.slot * SLOT;
  r.next();
  const uint32_t t1 = off + r.slot * SLOT;
#pragma unroll
    for (int jj = 0; jj < (WG ? 6 : 8); jj++) {
      uint32_t* p = &q[4 * jj];
      if (WG) asm volatile("ldmatrix.sync.aligned.m8n8.x4.trans.shared.b16 {%0, %1, %2, %3}, [%4];" : "=r"(p[0]), "=r"(p[1]), "=r"(p[2]), "=r"(p[3])
                           : "r"((jj < 4 ? t0 + h * 8192 : t1 + h * 4096) + (jj & 3) * 2048) : "memory");
      else ldsm4((h ? t1 : t0) + (jj >> 2) * 8192 + (((((2 * jj) & 7) + (mi >> 1)) ^ r8) << 4), p[0], p[1], p[2], p[3]);
    }
}
template <int WG>
__device__ __forceinline__ void add_part(const Ctx& c, const uint32_t (&q)[32], float (&a)[64]) {
  const uint32_t one = (c.lane >> 3) == (c.lane & 3) ? 0x3f80u << (c.lane & 4) * 4 : 0;
#pragma unroll
  for (int i = 0; i < (WG ? 12 : 16); i++)
    asm("mma.sync.aligned.m16n8k8.row.col.f32.bf16.bf16.f32 {%0, %1, %2, %3}, {%4, %5}, {%6}, {%0, %1, %2, %3};"
        : "+f"(a[4 * i]), "+f"(a[4 * i + 1]), "+f"(a[4 * i + 2]), "+f"(a[4 * i + 3]) : "r"(q[2 * i]), "r"(q[2 * i + 1]), "r"(one));
}

__device__ __forceinline__ void trace_dump(const Ctx& c) {
}
struct RowSum { float l0, l1; };
__device__ __forceinline__ const char* o_addr(uint32_t item, int row, int lane) {
  return reinterpret_cast<const char*>(g_o) + (((item >> 10) * (2 * SQ) + row) * 128 + (lane ^ (lane >> 3)) * 16);
}
__device__ __forceinline__ void o_stg(const char* p, int i, const uint32_t* q) {
  asm volatile("st.global.v4.b32 [%0], {%1, %2, %3, %4};"
               ::"l"(p + (i >> 1) * (SQ * 128) + (i & 1) * 512), "r"(q[0]), "r"(q[1]), "r"(q[2]), "r"(q[3]) : "memory");
}
template <int MODE, int I0 = 0, int NI = 4>
__device__ __forceinline__ void o_emit(const char* p, const float (&o)[64], float inv) {
#pragma unroll
  for (int i = I0; i < I0 + NI; i++) {
    uint32_t q[4];
#pragma unroll
    for (int j = 0; j < 4; j++) q[j] = pack_bf16(o[16 * i + 4 * j + 2 * MODE] * inv, o[16 * i + 4 * j + 2 * MODE + 1] * inv);
    o_stg(p, i, q);
  }
}
__device__ __forceinline__ void o_done(const Ctx& c) {
  __syncwarp();
  mbar_arrive_warp(c.sb + BAR_OUT);
  __syncwarp();
}
template <int WG>
__device__ __forceinline__ void o_first(const Ctx& c, uint32_t item, float (&o)[64], const RowSum& inv, uint32_t (&q)[32]) {
  const char* p = o_addr(item, WG ? 192 + 8 * c.warp : 64 + 16 * c.warp, c.lane);
  reg_fence(o);
#pragma unroll
  for (int j = 0; j < 16; j++) {
    if (WG) q[j] = pack_bf16((o[4 * j] + o[4 * j + 2]) * inv.l0, (o[4 * j + 1] + o[4 * j + 3]) * inv.l0);
    else q[j] = pack_bf16(o[4 * j] * inv.l0, o[4 * j + 1] * inv.l0);
    if (!WG && (j & 3) == 3 && (j >> 2) < 8 - LATE0) o_stg(p, j >> 2, q + j - 3);
  }
#pragma unroll
  for (int j = 0; j < 16; j++) {
    if (!WG) q[16 + j] = pack_bf16(o[4 * j + 2] * inv.l1, o[4 * j + 3] * inv.l1);
    if ((j & 3) == 3 && (j >> 2) < 4 - (WG ? LATE1 : LATE0)) o_stg(WG ? p : p + 1024, j >> 2, q + (WG ? 0 : 16) + j - 3);
  }
}
template <int WG>
__device__ __forceinline__ void o_rest(const Ctx& c, uint32_t item, uint32_t (&q)[32]) {
  const char* p = o_addr(item, WG ? 192 + 8 * c.warp : 64 + 16 * c.warp, c.lane);
#pragma unroll
  for (int i = WG ? 4 - LATE1 : 8 - LATE0; i < (WG ? 4 : 8); i++) o_stg(p + (i >> 2) * 1024, i & 3, q + 4 * i);
}
template <int K0, int K1>
__device__ __forceinline__ void o_piece(const Ctx& c, const char* p, int k, const float (&o)[64], const RowSum& inv) {
  constexpr int NI = 8 / O_STEPS, M = K0 * NI / 4;
  if constexpr (K1 - K0 == 1) {
    o_emit<M, K0 * NI % 4, NI>(p + M * 1024, o, M ? inv.l1 : inv.l0);
    if (K1 == O_STEPS) o_done(c);
  } else {
    if (k <= (K0 + K1) / 2) o_piece<K0, (K0 + K1) / 2>(c, p, k, o, inv); else o_piece<(K0 + K1) / 2, K1>(c, p, k, o, inv);
  }
}
template <int WG>
__device__ __forceinline__ void o_second(const Ctx& c, uint32_t item, int k, float (&o)[64], const RowSum& inv) {
  reg_fence(o);
  o_piece<0, O_STEPS>(c, o_addr(item, 128 * WG + 16 * c.warp, c.lane0 + (k >> 8)), k, o, inv);
}
template <int WG>
__device__ __forceinline__ void release_q(const Ctx& c) {
#pragma unroll
  for (int t = 0; t < 2; t++)
    if (c.lead) asm volatile("mbarrier.arrive.shared::cta.b64 _, [%0], 2;" ::"r"(c.sb + BAR_EMPTY + (NS + 2 * WG + t) * 8) : "memory");
  __syncwarp();
}
struct Slots { uint32_t w, x, o, po; };
template <int WG>
__device__ __forceinline__ void acc_fence(float (&a)[64]) {
#pragma unroll
  for (int i = 0; i < (WG ? 48 : 64); i++) asm volatile("" : "+f"(a[i])::"memory");
}
template <int WG>
__device__ __forceinline__ void begin_acquire(const Ctx& c, Ring& r, Slots& h, bool wait) {
  const uint32_t s0 = r.slot, p0 = r.phase, f = c.sb + BAR_FULL;
  r.next();
  const uint32_t p1 = r.phase;
  h.w = r.slot; r.next();
  h.x = WG ? r.slot : s0; h.o = WG ? s0 : r.slot; h.po = r.phase;
  if (wait) { if (WG) mbar_wait3_w(f + s0 * 8, p0, f + h.w * 8, p1, f + h.x * 8, r.phase); else mbar_wait2_w(f + s0 * 8, p0, f + h.w * 8, p1); }
  r.next();
}
template <int WG>
__device__ __forceinline__ void proj_begin(const Ctx& c, Ring& r, float (&a0)[64], Slots& h, bool wait, uint32_t sw) {
  begin_acquire<WG>(c, r, h, wait);
  proj_half<WG, true, 0>(c, a0, h.w, h.x, sw);
  if (WG) release(c, h.o);
}
template <int WG>
__device__ __forceinline__ void proj_main(Ctx& c, Ring& r, float (&a0)[64], float (&a1)[64], Slots& h, int n, uint32_t sw, int unit,
                                          uint32_t item, int nq, float (&o1)[64], const RowSum& inv) {
  constexpr bool DEEP = (PDEPTH >> WG) & 1;
  T2C(unit, 3);
  int ks = 1;
#pragma unroll 1
  do {
    const Slots p = h;
    const uint32_t b = borrow(ks, n), tile = NS + (WG ? 3 - b : b), f = c.sb + BAR_FULL;
    const uint32_t s0 = b != 2 ? tile : r.slot, p0 = b != 2 ? (r.xp >> b) & 1 : r.phase;
    r.next_if(b == 2);
    const uint32_t p1 = r.phase;
    h.w = r.slot; r.next();
    const uint32_t s2 = b != 2 ? tile : r.slot;
    h.po = b != 2 ? p0 : r.phase;
    r.next_if(b == 2);
    r.xp ^= 1 << b;
    h.x = WG ? s2 : s0; h.o = WG ? s0 : s2;
    mbar_wait3_w(f + s0 * 8, p0, f + h.w * 8, p1, f + (WG ? s2 : p.o) * 8, WG ? h.po : p.po);
    if (ks < 10) T2C(unit, ks * 4);
    if (DEEP) {
      proj_half<WG, false, 0>(c, a0, h.w, h.x, sw);
      release(c, WG ? h.o : p.o);
      if (ks < 10) T2C(unit, ks * 4 + 1);
      wg_wait<1>();
      if (ks < 10) T2C(unit, ks * 4 + 2);
      release(c, p.x); release(c, p.w);
    } else {
      release(c, WG ? h.o : p.o);
      wg_wait<0>();
      release(c, p.x); release(c, p.w);
      if (ks < 10) T2C(unit, ks * 4 + 1);
      proj_half<WG, false, 0>(c, a0, h.w, h.x, sw);
      if (ks < 10) T2C(unit, ks * 4 + 2);
    }
    proj_half<WG, false, 1>(c, a1, h.w, h.x, sw);
    if (ks < 10) T2C(unit, ks * 4 + 3);
    if (ks <= nq) o_second<WG>(c, item, ks, o1, inv);
  } while (++ks != n);
  {
    const uint32_t e0 = c.sb + BAR_EMPTY + (NS + 3 * WG) * 8, e1 = c.sb + BAR_EMPTY + (NS + 1 + WG) * 8;
    const uint32_t p0 = (r.xp ^ unit ^ 1) & 1, p1 = ((r.xp >> 1) ^ unit ^ 1) & 1;
    const uint32_t k0 = sw ? e0 : c.sb + BAR_FULL + r.slot * 8, pk = sw ? p0 : r.phase;
    uint32_t cnt = 0;
    while (!__all_sync(0xffffffffu, mbar_try(e0, p0) & mbar_try(e1, p1) & mbar_try(k0, pk) & (WG || mbar_try(c.sb + BAR_FULL + h.o * 8, h.po)))) {
      if (++cnt > (1u << 22)) __trap();
    }
  }
  c.lane = c.lane0 + (h.w >> 5);
  if (!WG) release(c, h.o);
}
template <int WG>
__device__ __forceinline__ void proj_end(const Ctx& c, float (&a1)[64], const Slots& h) {
  wg_wait<0>();
  acc_fence<WG>(a1);
  release(c, h.x); release(c, h.w);
}
__device__ __forceinline__ uint32_t get_desc(const Ctx& c, int i) {
  uint32_t d;
  mbar_wait_w(c.sb + BAR_DESC, (i - 1) & 1);
  asm volatile("ld.volatile.shared.u32 %0, [%1];" : "=r"(d) : "r"(c.sb + DESC_OFF + (i & 3) * 4) : "memory");
  return __shfl_sync(0xffffffffu, d, 0);
}

__device__ __forceinline__ float quad_max(float x) {
  x = fmaxf(x, __shfl_xor_sync(0xffffffffu, x, 1));
  return fmaxf(x, __shfl_xor_sync(0xffffffffu, x, 2));
}
__device__ __forceinline__ float quad_sum(float x) {
  x += __shfl_xor_sync(0xffffffffu, x, 1);
  return x + __shfl_xor_sync(0xffffffffu, x, 2);
}
template <bool SP, bool FIRST>
__device__ __forceinline__ void exps(const Ctx& c, const float (&s)[32], uint32_t (&p)[SP ? 8 : 16], RowSum& st) {
  if constexpr (SP) {
    uint32_t q[8];
    float t;
#pragma unroll
    for (int j = 0; j < 8; j++) {
      const float e0 = ex2(s[4 * j] + s[4 * j + 2]), e1 = ex2(s[4 * j + 1] + s[4 * j + 3]);
      if (j == 0) t = e0 + e1; else t += e0 + e1;
      q[j] = pack_bf16(e0, e1);
    }
    const bool odd = c.src & 2;
#pragma unroll
    for (int g = 0; g < 4; g++) {
      p[2 * g] = __shfl_sync(0xffffffffu, odd ? q[2 * g + 1] : q[2 * g], c.src);
      p[2 * g + 1] = __shfl_sync(0xffffffffu, odd ? q[2 * g] : q[2 * g + 1], c.src ^ 1);
    }
    st.l0 = FIRST ? t : st.l0 + t;
  } else {
    float t0, t1;
#pragma unroll
    for (int j = 0; j < 8; j++) {
      const float e0 = ex2(s[4 * j]), e1 = ex2(s[4 * j + 1]), e2 = ex2(s[4 * j + 2]), e3 = ex2(s[4 * j + 3]);
      if (j == 0) { t0 = e0 + e1; t1 = e2 + e3; } else { t0 += e0 + e1; t1 += e2 + e3; }
      p[2 * j] = pack_bf16(e0, e1);
      p[2 * j + 1] = pack_bf16(e2, e3);
    }
    st.l0 = FIRST ? t0 : st.l0 + t0;
    st.l1 = FIRST ? t1 : st.l1 + t1;
  }
}
template <bool SP>
__device__ __forceinline__ bool finish_sums(RowSum& st) {
  const float a = quad_sum(st.l0), b = SP ? a : quad_sum(st.l1);
  st.l0 = __fdividef(1.f, a); st.l1 = __fdividef(1.f, b);
  return !(a >= SUM_LO && a <= SUM_HI && b >= SUM_LO && b <= SUM_HI);
}
template <bool SP, bool INIT, int SITE, bool COMMIT = true, int RM = 0>
__device__ __forceinline__ void issue_qk(const Ctx& c, float (&s)[32], const uint32_t (&qs)[32], uint32_t dq, uint32_t dk) {
  uint64_t a = desc64(dq, dhi<SITE & 1>(dk)), b = desc64(dk, dhi<1 - (SITE & 1)>(dk) + 64);
  if (SP) {
    if (INIT) wgmma_qk_sp_init(s, qs[0], qs[1], qs[2], qs[3], b, 0, c.mqk); else wgmma_qk_sp(s, qs[0], qs[1], qs[2], qs[3], b, 0, c.mqk);
#pragma unroll
    for (int k = 1; k < 4; k++) { dadd(b, k == 2 ? 60 : 4); wgmma_qk_sp(s, qs[4 * k], qs[4 * k + 1], qs[4 * k + 2], qs[4 * k + 3], b, 1, c.mqk); }
  } else {
    if (RM & 1) wgmma_qk_rs(s, qs[0], qs[1], qs[2], qs[3], b, 0); else if (INIT) wgmma_qk_init(s, a, b, 0); else wgmma_qk(s, a, b, 0);
#pragma unroll
    for (int k = 1; k < 8; k++) {
      dadd(a, k == 4 ? 506 : 2); dadd(b, k == 4 ? 58 : 2);
      if (RM >> k & 1) wgmma_qk_rs(s, qs[4 * k], qs[4 * k + 1], qs[4 * k + 2], qs[4 * k + 3], b, 1); else wgmma_qk(s, a, b, 1);
    }
  }
  if (COMMIT) wg_commit();
}
template <bool SP, bool ACC, int SITE, bool SPLIT = false>
__device__ __forceinline__ void issue_pv(const Ctx& c, float (&o)[64], const uint32_t (&p)[SP ? 8 : 16], uint32_t dv) {
  uint64_t b = desc64(dv, dhi<SITE & 1>(dv) + 64);
  if constexpr (SP) {
    if (ACC) wgmma_pv_sp(o, p[0], p[1], p[2], p[3], b, 1, c.mpv); else wgmma_pv_sp_init(o, p[0], p[1], p[2], p[3], b, 0, c.mpv);
    if (SPLIT) wg_commit();
    dadd(b, 512);
    wgmma_pv_sp(o, p[4], p[5], p[6], p[7], b, 1, c.mpv);
  } else {
    if (ACC) wgmma_pv(o, p[0], p[1], p[2], p[3], b, 1); else wgmma_pv_init(o, p[0], p[1], p[2], p[3], b, 0);
#pragma unroll
    for (int k = 1; k < 4; k++) { dadd(b, 256); wgmma_pv(o, p[4 * k], p[4 * k + 1], p[4 * k + 2], p[4 * k + 3], b, 1); }
  }
  wg_commit();
}
__device__ __forceinline__ void pack_rows(const float (&o)[64], float sc, uint32_t (&q)[32]) {
#pragma unroll
  for (int j = 0; j < 32; j++) q[j] = pack_bf16(o[2 * j] * sc, o[2 * j + 1] * sc);
}
template <int MASK = 255>
__device__ __forceinline__ void stage_rows(const Ctx& c, uint32_t tile_addr, const uint32_t (&q)[32]) {
  const int lane = c.lane, mi = lane >> 3, r8 = lane & 7;
  const uint32_t row_addr = tile_addr + (16 * c.warp + (mi & 1) * 8 + r8) * 128;
#pragma unroll
  for (int jj = 0; jj < 8; jj++)
    if (MASK >> jj & 1) stsm4(row_addr + (jj >> 2) * 8192 + (((((2 * jj) & 7) + (mi >> 1)) ^ r8) << 4), q[4 * jj], q[4 * jj + 1], q[4 * jj + 2], q[4 * jj + 3]);
}
__device__ __forceinline__ void stage_rows(const Ctx& c, uint32_t tile_addr, const float (&o)[64], float sc) {
  uint32_t q[32];
  pack_rows(o, sc, q);
  stage_rows(c, tile_addr, q);
}
template <int WG, int H>
__device__ __forceinline__ void stage_out(const Ctx& c, const float (&a)[64]) {
  if (WG) { stage_t3<H, false>(c, a, 1.f); if (H) staged(c, 0); stage_t2<H>(c, a, 1.f); }
  else stage_rows(c, c.sb + QBUF_OFF + H * 16384, a, 1.f);
  if (H || !WG) staged(c, H);
}
template <int SITE>
__device__ __forceinline__ void issue_qk_rs(float (&s)[32], uint32_t (&q)[32], uint32_t dk) {
  uint64_t b = desc64(dk, dhi<SITE>(dk) + 64);
  reg_fence(q);
  wg_fence();
  wgmma_qk_rs_init(s, q[0], q[1], q[2], q[3], b, 0);
#pragma unroll
  for (int k = 1; k < 8; k++) { dadd(b, k == 4 ? 58 : 2); wgmma_qk_rs(s, q[4 * k], q[4 * k + 1], q[4 * k + 2], q[4 * k + 3], b, 1); }
  wg_commit();
}

__device__ __forceinline__ void redo_tile(const Ctx& c, uint32_t q_addr, uint32_t half, const __nv_bfloat16* kp, const __nv_bfloat16* vp,
                                          uint32_t item, int row) {
  float o[64];
  const int lane = lane_now(), g = lane >> 2, cc = lane & 3, mi = lane >> 3, r8 = lane & 7;
  const uint32_t qa = q_addr + (half == 4096 ? 8 * c.warp + r8 : 16 * c.warp + (mi & 1) * 8 + r8) * 128, swz = half == 4096 ? q3_swz(r8) : r8;
  const uint32_t* kq = reinterpret_cast<const uint32_t*>(kp + g * DH) + cc;
  const unsigned short* vq = reinterpret_cast<const unsigned short*>(vp + 2 * cc * DH) + g;
  float m0 = -INFINITY, m1 = -INFINITY, l0 = 0.f, l1 = 0.f;
#pragma unroll
  for (int i = 0; i < 64; i++) o[i] = 0.f;
#pragma unroll 1
  for (int kb = 0; kb < SK / 16; kb++) {
    float z[8] = {0.f, 0.f, 0.f, 0.f, 0.f, 0.f, 0.f, 0.f};
#pragma unroll 2
    for (int kk = 0; kk < 8; kk++) {
      uint32_t a0, a1, a2, a3;
      ldsm4(qa + (kk >> 2) * half + ((((kk & 3) * 2 + (mi >> 1)) ^ swz) << 4), a0, a1, a2, a3);
      const uint32_t* kr = kq + kb * (16 * DH / 2) + kk * 8;
      mma16816(z[0], z[1], z[2], z[3], a0, a1, a2, a3, __ldg(kr), __ldg(kr + 4));
      mma16816(z[4], z[5], z[6], z[7], a0, a1, a2, a3, __ldg(kr + 8 * DH / 2), __ldg(kr + 8 * DH / 2 + 4));
    }
    const float n0 = fmaxf(m0, quad_max(fmaxf(fmaxf(z[0], z[1]), fmaxf(z[4], z[5]))));
    const float n1 = fmaxf(m1, quad_max(fmaxf(fmaxf(z[2], z[3]), fmaxf(z[6], z[7]))));
    const float al0 = ex2(m0 - n0), al1 = ex2(m1 - n1);
    m0 = n0; m1 = n1;
#pragma unroll
    for (int i = 0; i < 8; i++) z[i] = ex2(z[i] - ((i & 2) ? n1 : n0));
    l0 = l0 * al0 + (z[0] + z[1]) + (z[4] + z[5]);
    l1 = l1 * al1 + (z[2] + z[3]) + (z[6] + z[7]);
    const uint32_t a0 = pack_bf16(z[0], z[1]), a1 = pack_bf16(z[2], z[3]), a2 = pack_bf16(z[4], z[5]), a3 = pack_bf16(z[6], z[7]);
    const unsigned short* vr = vq + kb * (16 * DH);
#pragma unroll
    for (int nb = 0; nb < 16; nb++) {
      o[4 * nb] *= al0; o[4 * nb + 1] *= al0; o[4 * nb + 2] *= al1; o[4 * nb + 3] *= al1;
      const uint32_t b0 = __ldg(vr + nb * 8) | ((uint32_t)__ldg(vr + nb * 8 + DH) << 16);
      const uint32_t b1 = __ldg(vr + nb * 8 + 8 * DH) | ((uint32_t)__ldg(vr + nb * 8 + 9 * DH) << 16);
      mma16816(o[4 * nb], o[4 * nb + 1], o[4 * nb + 2], o[4 * nb + 3], a0, a1, a2, a3, b0, b1);
    }
  }
  const char* p = o_addr(item, row, lane);
  o_emit<0>(p, o, __fdividef(1.f, quad_sum(l0)));
  o_emit<1>(half == 4096 ? p : p + 1024, o, __fdividef(1.f, quad_sum(l1)));
}

template <bool SPA, bool SPB, int SITE, int ID>
__device__ __forceinline__ void batch(const Ctx& c, float (&s)[32], const uint32_t (&qs)[32], uint32_t dq, uint32_t dk, float (&ob)[64],
                                      uint32_t (&pb)[SPB ? 8 : 16], uint32_t dv) {
  if constexpr (SPA) {
    reg_fence(pb);
    wg_fence();
    issue_pv<SPB, true, ID>(c, ob, pb, dv);
    issue_qk<SPA, false, ID>(c, s, qs, dq, dk);
  } else {
    constexpr bool EARLY = ((QK_EARLY_MASK >> (SITE + (SPB ? 2 : 0))) & 1) != 0;
    if (!EARLY) reg_fence(pb);
    wg_fence();
    issue_qk<SPA, false, ID, !SPB, SITE ? RM0 : SPB ? RM2 : RM1>(c, s, qs, dq, dk);
    if (EARLY) { reg_fence(pb); wg_fence(); }
    issue_pv<SPB, true, ID, SPB>(c, ob, pb, dv);
  }
}

template <bool SP0>
__device__ __forceinline__ bool attention(Ctx& c, Ring& r, int unit, uint32_t& d, const float (&a0)[64], float (&o0)[64], float (&o1)[64],
                                          RowSum& st0, RowSum& st1, const Slots& h, uint32_t (&q1)[32]) {
  constexpr bool SP1 = false;
  if (SP0) { c.mqk = META_QK + (d >> 28); c.mpv = META_PV + (d >> 28); asm volatile("" : "+r"(c.mqk), "+r"(c.mpv)); }
  if (SP0) c.src = (c.lane & 28) | ((c.lane & 1) << 1) | ((c.lane >> 1) & 1);
  float s[32];
  uint32_t p0[SP0 ? 8 : 16], p1[16];
  const uint32_t q0a = c.sb + QBUF_OFF + (SP0 ? 3 : 0) * 16384, q1a = c.sb + QBUF_OFF + (SP0 ? 2 : 1) * 16384;
  const uint32_t dq0 = sdesc(SB0 + QBUF_OFF, 0), dq1 = sdesc(SB0 + QBUF_OFF + (SP0 ? 2 : 1) * 16384, 0);
  uint32_t sk = acquire(c, r, true), sv, sn;
  uint32_t qs[32];
  float s1[32];
  if (SP0) {
    stage_t3<0, true>(c, a0, SM_C);
    stage_t2<0>(c, a0, SM_C);
    proj_end<1>(c, o0, h);
    stage_t3<1, true>(c, o0, SM_C);
    stage_t2<1>(c, o0, SM_C);
    bar_sync(5, 128);
    const int g = c.lane >> 2, cc = c.lane & 3;
    const uint32_t qa = q0a + (8 * c.warp + g) * 128 + (cc & 1) * 8;
#pragma unroll
    for (int k = 0; k < 8; k++)
      asm volatile("ld.shared.v2.u32 {%0, %1}, [%2];" : "=r"(qs[2 * k]), "=r"(qs[2 * k + 1])
                   : "r"(qa + (k >> 2) * 4096 + ((((k & 3) * 2 + (cc >> 1)) ^ q3_swz(g)) << 4)) : "memory");
    fence_async_smem();
    bar_sync(1, 256);
    TRACE(unit, 2);
    wg_fence();
    issue_qk<SP1, true, 1>(c, s1, qs, dq1, sdesc(SB0 + sk * SLOT, 0));
#pragma unroll
    for (int k = 0; k < 8; k++)
      if (RM2 >> k & 1) ldsm4(q1a + (k >> 2) * 8192 + (16 * c.warp + (c.lane & 15)) * 128 + (((2 * (k & 3) + (c.lane >> 4)) ^ (c.lane & 7)) << 4),
                              q1[4 * k], q1[4 * k + 1], q1[4 * k + 2], q1[4 * k + 3]);
#pragma unroll
    for (int k = 0; k < 16; k++) asm volatile("" : "+r"(qs[k])::"memory");
    wg_fence();
    issue_qk<SP0, true, 0>(c, s, qs, dq0, sdesc(SB0 + sk * SLOT, 0));
    const bool have = peek<2>(c, r);
    wg_wait<1>();
    reg_fence(s1);
    exps<SP1, true>(c, s1, p1, st1);
    sched_fence<11>(sk, p1);
    acquire2(c, r, sv, sn, __all_sync(0xffffffffu, have));
    wg_wait<0>();
    wg_fence();
    issue_pv<SP1, false, 1>(c, o1, p1, sdesc(SB0 + sv * SLOT, 1024));
    if (LAG_BAR & 1) asm volatile("bar.arrive 4, 256;" ::: "memory");
    sched_fence<12>(sk, s);
    release(c, sk);
    sk = sn;
    exps<SP0, true>(c, s, p0, st0);
    reg_fence(p0);
    wg_fence();
    issue_pv<SP0, false, 0>(c, o0, p0, sdesc(SB0 + sv * SLOT, 1024));
    issue_qk<SP0, true, 2>(c, s, qs, dq0, sdesc(SB0 + sk * SLOT, 0));
    sn = acquire(c, r);
    wg_wait<0>();
    reg_fence(s);
  } else {
    pack_rows(a0, SM_C, qs);
    stage_rows(c, q0a, qs);
    proj_end<0>(c, o1, h);
    TRACE(unit, 2);
    float sc = SM_C;
    issue_qk_rs<0>(s, qs, sdesc(SB0 + sk * SLOT, 0));
    sched_fence<0>(sk, sc);
    pack_rows(o1, sc, q1);
    stage_rows<~RM1>(c, q1a, q1);
    issue_qk_rs<1>(s1, q1, sdesc(SB0 + sk * SLOT, 0));
    asm volatile("bar.arrive 1, 256;" ::: "memory");
    bool have = peek<2>(c, r);
    wg_wait<1>();
    reg_fence(s);
    exps<SP0, true>(c, s, p0, st0);
    sched_fence<1>(sk, p0);
    acquire2(c, r, sv, sn, __all_sync(0xffffffffu, have));
    wg_wait<0>();
    reg_fence(s1);
    fence_async_smem();
    __syncwarp();
    wg_fence();
    issue_qk<SP0, false, 2, true, RM0>(c, s, qs, dq0, sdesc(SB0 + sn * SLOT, 0));
    issue_pv<SP0, false, 0>(c, o0, p0, sdesc(SB0 + sv * SLOT, 1024));
    sched_fence<2>(sk, s1);
    release(c, sk);
    have = peek<1>(c, r);
    sk = sn;
    exps<SP1, true>(c, s1, p1, st1);
    reg_fence(p1);
    wg_fence();
    issue_pv<SP1, false, 1>(c, o1, p1, sdesc(SB0 + sv * SLOT, 1024));
    sn = acquire(c, r, __all_sync(0xffffffffu, have));
    if (LAG_BAR & 1) bar_sync(4, 256);
    wg_wait<1>();
    reg_fence(s);
  }
  TRACE_IN(unit, 4);
  T2C(unit, 51);
#pragma unroll 1
  for (int j = 1; j < 15; j++) {
    const uint32_t sv_prev = sv, sk_prev = sk;
    sv = sn;
    const uint32_t dv = sdesc(SB0 + sv * SLOT, 1024);
    reg_fence(p0);
    exps<SP0, false>(c, s, p0, st0);
    batch<SP1, SP0, 0, 3>(c, s, q1, dq1, sdesc(SB0 + sk * SLOT, 0), o0, p0, dv);
    sk = acquire(c, r);
    wg_wait<1>();
    reg_fence(s); reg_fence(p1);
    release(c, sv_prev); release(c, sk_prev);
    exps<SP1, false>(c, s, p1, st1);
    batch<SP0, SP1, 1, 4>(c, s, qs, dq0, sdesc(SB0 + sk * SLOT, 0), o1, p1, dv);
    sn = acquire(c, r);
    if (SP0) wg_wait<0>(); else wg_wait<1>();
    reg_fence(s);
  }
  TRACE_IN(unit, 5);
  T2C(unit + 1, 52);
  const uint32_t sv_prev = sv;
  sv = sn;
  const uint32_t dv = sdesc(SB0 + sv * SLOT, 1024);
  reg_fence(p0);
  exps<SP0, false>(c, s, p0, st0);
  batch<SP1, SP0, 0, 5>(c, s, q1, dq1, sdesc(SB0 + sk * SLOT, 0), o0, p0, dv);
  asm volatile("ld.volatile.shared.u32 %0, [%1];" : "=r"(d) : "r"(c.sb + DESC_OFF + ((unit + 1) & 3) * 4) : "memory");
  const bool have = peek<2 + SP0>(c, r);
  wg_wait<1>();
  reg_fence(s); reg_fence(p1);
  release(c, sv_prev); release(c, sk);
  exps<SP1, false>(c, s, p1, st1);
  reg_fence(p1);
  wg_fence();
  issue_pv<SP1, true, 2>(c, o1, p1, dv);
  if (SP0) sched_fence<6>(sk, st0.l0, st1.l0, st1.l1); else sched_fence<5>(sk, st0.l0, st0.l1, st1.l0, st1.l1);
  c.lane = c.lane0 + (sk >> 5);
  const bool bad = finish_sums<SP0>(st0) | finish_sums<SP1>(st1);
  uint32_t any;
  asm volatile("{\n.reg .pred p, q;\nsetp.ne.u32 p, %1, 0;\nbar.red.or.pred q, %2, 128, p;\nselp.u32 %0, 1, 0, q;\n}"
               : "=r"(any) : "r"((uint32_t)bad), "n"(2 + SP0) : "memory");
  any = __any_sync(0xffffffffu, any);
  d = __shfl_sync(0xffffffffu, d, 0);
  if (d < (2u << 30) && !__all_sync(0xffffffffu, have)) { Ring t = r; Slots u; begin_acquire<SP0>(c, t, u, true); }
  wg_wait<0>();
  reg_fence(o0); reg_fence(o1);
  release(c, sv);
  return any;
}

template <int WG>
__device__ __forceinline__ void consumer(Ctx c, const __nv_bfloat16* const* kv) {
  asm volatile("setmaxnreg.inc.sync.aligned.u32 %0;" ::"n"(WG ? REG_C : 504 - REG_C - REG_P));
  c.wg = WG;
  Ring r{0, 0, 0};
  float a0[64], a1[64], o1[64];
  Slots h;
  RowSum inv0, inv1;
  uint32_t oq[32];
  uint32_t d = c_sched.queue[blockIdx.x] * 1025, dc = 0, sw;
  int i = 0, nq;
begin:
  sw = d & (1u << 30);
  proj_begin<WG>(c, r, a0, h, true, sw);
  proj_half<WG, true, 1>(c, a1, h.w, h.x, sw);
  nq = 0;
#pragma unroll
  for (int k = 0; k < 64; k++) asm volatile("" : "=f"(o1[k]));
  asm volatile("" : "=f"(inv1.l0), "=f"(inv1.l1));
  while (true) {
    TRACE(i, 0); TRACE(i, 6);
    proj_main<WG>(c, r, a0, a1, h, d >> 30 ? ((d >> 16) & 63) + 1 : DM / 64, sw, i, dc, nq, o1, inv1);
    dc = d;
    TRACE(i, 1);
    if (d >> 30) goto out_tile;
    wg_wait<1>();
    acc_fence<WG>(a0);
    if (WG ? attention<WG>(c, r, i, d, a0, a1, o1, inv0, inv1, h, oq) : attention<WG>(c, r, i, d, a0, o1, a1, inv1, inv0, h, oq)) goto redo;
    if (d >= (2u << 30)) break;
    sw = d & (1u << 30);
    proj_begin<WG>(c, r, a0, h, false, sw);
    release_q<WG>(c);
    if (WG) sched_fence<8>(h.w, inv0.l0); else sched_fence<7>(h.w, inv0.l0, inv0.l1);
    o_first<WG>(c, dc, a1, inv0, oq);
    sched_fence<9>(h.w, inv1.l0);
    proj_half<WG, true, 1>(c, a1, h.w, h.x, sw);
    o_rest<WG>(c, dc, oq);
    nq = O_STEPS;
    TRACE(i, 3); TRACE(i, 7);
    i++;
  }
  release_q<WG>(c);
  o_first<WG>(c, dc, a1, inv0, oq);
  o_rest<WG>(c, dc, oq);
#pragma unroll
  for (int k = 1; k <= O_STEPS; k++) o_second<WG>(c, dc, k, o1, inv1);
next:
  TRACE(i, 3); TRACE(i, 7);
  if ((d >> 30) != 2) {
    i++;
    r.uniform();
    goto begin;
  }
  trace_dump(c);
  return;
out_tile:
  if (d & 96) goto finish;
  d = get_desc(c, i + 1);
  wg_wait<1>();
  acc_fence<WG>(a0);
  TRACE_O(0);
  stage_out<WG, 0>(c, a0);
  TRACE_O(1);
  proj_end<WG>(c, a1, h);
  TRACE_O(2);
  stage_out<WG, 1>(c, a1);
  TRACE(i, 2);
  goto next;
finish:
  {
    uint32_t q[32];
#pragma unroll 1
    for (int k = (d >> 5) & 3; k > 1; k--) {
      wg_wait<0>();
      acc_fence<WG>(a0); acc_fence<WG>(a1);
      if (k == ((d >> 5) & 3)) { release(c, h.x); release(c, h.w); }
      load_part<WG, 0>(c, r, q); add_part<WG>(c, q, a0);
      load_part<WG, 1>(c, r, q); add_part<WG>(c, q, a1);
#pragma unroll
      for (int t = 0; t < 4; t++) { release(c, r.slot); r.next(); }
    }
    load_part<WG, 0>(c, r, q);
    wg_wait<1>();
    acc_fence<WG>(a0);
    TRACE_O(0);
    add_part<WG>(c, q, a0);
    stage_out<WG, 0>(c, a0);
    TRACE_O(1);
    load_part<WG, 1>(c, r, q);
    wg_wait<0>();
    acc_fence<WG>(a1);
    TRACE_O(2);
    add_part<WG>(c, q, a1);
    stage_out<WG, 1>(c, a1);
    TRACE(i, 2); TRACE(i, 3); TRACE(i, 7);
    trace_dump(c);
    return;
  }
redo:
  {
    if (!WG) { stage_rows<RM1>(c, c.sb + QBUF_OFF + 16384, oq); __syncwarp(); }
    const size_t hoff = (size_t)(dc & 511) * (SK * DH);
    const int br = (dc >> 9) & 1;
#pragma unroll 1
    for (int part = 0; part < 2; part++) {
      const int t = WG ? 3 - part : part;
      redo_tile(c, c.sb + QBUF_OFF + t * 16384, t == 3 ? 4096 : 8192, kv[br] + hoff, kv[2 + br] + hoff, dc,
                t * 64 + (t == 3 ? 8 : 16) * c.warp);
    }
    o_done(c);
    release_q<WG>(c);
  }
  goto next;
}

template <bool SIMPLE>
__global__ void __launch_bounds__(384, 1) mha_fused_kernel(const __grid_constant__ Params P) {
  extern __shared__ __align__(1024) uint8_t smem_raw[];
  const uint32_t sbase = smem_u32(smem_raw);
  const int tid = threadIdx.x;
  const int wg = __shfl_sync(0xffffffffu, tid >> 7, 0);
  const int warp = __shfl_sync(0xffffffffu, (tid >> 5) & 3, 0);
  const int lane = tid & 31;
  const int cta = blockIdx.x;
  constexpr bool PAIR = !SIMPLE && CLUSTER;

  if (tid == 0) T3(15, 0);
  if ((sbase & 0xffffff) != SB0) __trap();
  {
    const int wi = wg * 4 + warp;
    asm volatile(ELECT "prefetch.tensormap [%0];\n}" ::"l"(&P.x[0][0] + wi) : "memory");
#pragma unroll
    for (int k = 0; k < 5; k++) {
      const int b = min(BAR_OFF + (wi * 5 + k) * 8, DESC_OFF - 8);
      asm volatile(ELECT "mbarrier.init.shared::cta.b64 [%0], %1;\n}"
                   ::"r"(sbase + b), "r"(b < BAR_EMPTY || b >= BAR_DESC ? 1 : b >= BAR_STG && b < BAR_OUT ? 4 : 8) : "memory");
    }
    asm volatile("fence.mbarrier_init.release.cluster;" ::: "memory");
    if (wi < 6) asm volatile(ELECT "prefetch.tensormap [%0];\n}" ::"l"(&P.x[0][0] + 12 + wi) : "memory");
  }
  if (PAIR) asm volatile("barrier.cluster.arrive.aligned;\nbarrier.cluster.wait.aligned;" ::: "memory"); else __syncthreads();

  if (wg == 2) {
    asm volatile("setmaxnreg.dec.sync.aligned.u32 %0;" ::"n"(REG_P));
    if (warp == 1) {
      const uint32_t qb = sbase + QBUF_OFF;
      const uint32_t ep = __shfl_sync(0xffffffffu, *(volatile unsigned*)&g_epoch + 1, 0);
      asm volatile("st.volatile.shared.u32 [%0], %1;" ::"r"(sbase + EPOCH_OFF), "r"(ep) : "memory");
      uint32_t dc = c_sched.queue[cta], qi = 0, piece = 0, na = 0;
      TTAIL(0);
      for (int i = 0; (dc >> 30) != 2; i++) {
        if (!(dc >> 30) && o_reuse<SIMPLE>((dc >> 5) & 31)) {
          const unsigned* rd = &g_rd[0][0] + ((dc & 1023) >> 2) - OR * 8;
          for (uint32_t n = 0; !__all_sync(0xffffffffu, reached(rd, ep * 5)); __nanosleep(300)) if (++n > (1u << 22)) __trap();
        }
        mbar_wait_w(sbase + BAR_GO, i & 1);
        if (piece == 0) {
          if (PAIR && (cta & 1)) {
            asm volatile(ELECT EXPECT("%0", "4") "mbarrier.arrive.shared::cluster.b64 _, [%1];\n}" ::"r"(sbase + BAR_MAIL), "r"(peer(sbase + BAR_MAIL)) : "memory");
            mbar_wait_w(sbase + BAR_MAIL, i & 1);
            qi = lds(sbase + EPOCH_OFF + 8);
          } else if (lane == 0) {
            qi = atomicAdd(&g_next, PAIR ? 2 : 1);
            if (qi == (SIMPLE ? Q_ALL : Q_RANGES) - (PAIR ? 2 : 1)) { g_next = 0; g_epoch = ep; }
          }
          qi = __shfl_sync(0xffffffffu, qi, 0);
          if (PAIR && !(cta & 1)) {
            mbar_wait_w(sbase + BAR_MAIL, i & 1);
            asm volatile(ELECT "st.async.shared::cluster.mbarrier::complete_tx::bytes.u32 [%0], %1, [%2];\n}"
                         ::"r"(peer(sbase + EPOCH_OFF + 8)), "r"(qi + 1), "r"(peer(sbase + BAR_MAIL)) : "memory");
          }
          qi += SIMPLE ? gridDim.x : NCTA;
        }
        uint32_t d;
        if (qi < (SIMPLE ? Q_ALL : Q_RANGES)) { d = c_sched.queue[qi]; if (d & 0x8000) d ^= (1u << 30) | (63u << 16) | 0x8000; else d |= o_slot<SIMPLE>(d >> 5) << 15 | (d & 31) << 10; }
        else if (SIMPLE) d = 2u << 30;
        else { const uint32_t e = qi - Q_RANGES, g = e / 5; d = c_sched.piece[g][piece++] | (g & 1 ? g * 5 + 4 - e : e - g * 5) << 8; }
        if ((d >> 30) == 1) {
          const uint32_t k0 = (d >> 22) & 63;
          const uint32_t run = __ffs(__ballot_sync(0xffffffffu, !reached(&g_cnt[d & 31][lane & 7], ep * 4)) & (0xffu << (k0 >> 3))) - 1;
          if (run <= (k0 + ((d >> 16) & 63)) >> 3) d |= run <= (k0 + O_STEPS) >> 3 ? (2u << 30) | 128 : 128;
        }
        asm volatile("st.volatile.shared.u32 [%0], %1;" ::"r"(sbase + EPOCH_OFF + 4), "r"(qi) : "memory");
        asm volatile("st.volatile.shared.u32 [%0], %1;" ::"r"(sbase + DESC_OFF + ((i + 1) & 3) * 4), "r"(d) : "memory");
        __syncwarp();
        mbar_arrive_warp(sbase + BAR_DESC);
        const Work w = decode(dc);
        dc = d;
        if (w.kind == 0) {
          mbar_wait_w(sbase + BAR_OUT, na++ & 1);
          TTAIL(1);
          T3(i, 0); T3(i, 1);
          asm volatile(ELECT "red.release.gpu.global.add.u32 [%0], 1;\n}" ::"l"(&g_cnt[w.beta][w.sub >> 2]) : "memory");
          T3(i, 2);
          TTAIL(2);
          continue;
        }
        const bool fin = w.mode != 1;
        uint64_t pol, pol2;
        asm volatile("createpolicy.fractional.L2::evict_first.b64 %0, 1.0;" : "=l"(pol));
        asm volatile("createpolicy.fractional.L2::evict_normal.b64 %0, 1.0;" : "=l"(pol2));
        if (!fin) pol = pol2;
        const CUtensorMap* m = fin ? P.out_st : P.o_st;
        const int c1 = fin ? (w.beta & 15) * SQ : 0;
        const int c2 = fin ? (w.beta >> 4) * (DM / 64) + w.sub * 2 : NBETA * 64 + w.range * 2;
        uint32_t pend = 0;
#pragma unroll 1
        for (int e = 0; e < 4; e++) {
          const int t = (ST_ORDER >> (4 * e)) & 3;
          mbar_wait_w(sbase + BAR_STG + (t ^ (t >> 1)) * 8, (i - na) & 1);
          tma_st3_hint_w(m + (t == 3), qb + t * 16384, 0, c1 + t * 64, c2, pol);
          bulk_commit();
          T2P(i + 1, 5, 2 * e);
          if (pend) {
            bulk_wait_read<1>();
            mbar_arrive8_w(pend);
            T2P(i + 1, 5, 2 * e - 1);
          }
          pend = sbase + BAR_EMPTY + (NS + t) * 8;
          if ((ST_NOW >> e) & 1) {
            bulk_wait_read<0>();
            mbar_arrive8_w(pend);
            pend = 0;
            T2P(i + 1, 5, 2 * e + 1);
          }
        }
        if (w.beta < N_EARLY) asm volatile(ELECT "red.relaxed.gpu.global.add.u32 [%0], 1;\n}" ::"l"(&g_rd[w.beta][7]) : "memory");
        T3(i, 0);
        if (piece >= 2) TTAIL(piece * 2 - 1);
        asm volatile("cp.async.bulk.wait_group 0;" ::: "memory");
        T3(i, 1);
        if (w.mode == 1) asm volatile(ELECT "st.release.gpu.global.u32 [%0], %1;\n}" ::"l"(&g_flag[w.range]), "r"(ep) : "memory");
        T3(i, 2);
        if (piece >= 2) TTAIL(piece * 2);
      }
      T3(15, 1);
    } else
    if (warp == 0) {
      Ring r{0, 1, 3};
      uint32_t d = c_sched.queue[cta];
      for (int i = 0;; i++) {
        const Work w = decode(d);
        if (w.kind == 2) break;
        const CUtensorMap* m = w.kind == 0 ? &P.wq[w.beta >> 4] : &P.wo[w.beta >> 4];
        for (int ks = 0; ks < w.nsteps; ks++) {
          const uint32_t b = borrow(ks, w.nsteps);
          r.next_if(b == 2);
          const uint32_t bar = sbase + BAR_FULL + r.slot * 8;
          mbar_wait_w(bar + (BAR_EMPTY - BAR_FULL), r.phase);
          if (w.kind == 0) tma_ld3_w(sbase + r.slot * SLOT, m, 0, ks * 64, w.sub * 2, bar, 16384);
          else tma_ld_wo_w(sbase + r.slot * SLOT, m, w.sub * 128, (w.k0 + ks) * 2, bar);
          if (w.kind != 0 && w.beta < N_EARLY && (ks & 7) == 5 && ks > 5)
            asm volatile(ELECT "red.relaxed.gpu.global.add.u32 [%0], 1;\n}" ::"l"(&g_rd[w.beta][(ks >> 3) - 1]) : "memory");
          if (ks < 10) T2P(i, 2, ks);
          if (w.kind != 0 && ks == max(w.nsteps - GO_P, 4)) mbar_arrive_warp(sbase + BAR_GO);
          r.next(); r.next_if(b == 2);
        }
        if (w.kind == 0) {
          r.phase ^= 1; r.next(); r.next();
        } else if (w.mode == 2) {
          for (int k = 1; k <= ((d >> 5) & 3); k++) {
            if (k == 1) TTAIL(9);
            wait_count(&g_flag[w.range + 5 * k], lds(sbase + EPOCH_OFF));
            TTAIL(10);
            asm volatile("fence.proxy.async.global;" ::: "memory");
#pragma unroll 1
            for (int t = 0; t < 4; t++) {
              mbar_wait_w(sbase + BAR_EMPTY + r.slot * 8, r.phase);
              tma_ld3_w(sbase + r.slot * SLOT, &P.o_st[t == 3], 0, t * 64, NBETA * 64 + (w.range + 5 * k) * 2, sbase + BAR_FULL + r.slot * 8,
                        t == 3 ? 8192 : 16384);
              r.next();
            }
          }
        }
        mbar_wait_w(sbase + BAR_DESC, i & 1);
        d = __shfl_sync(0xffffffffu, lds(sbase + DESC_OFF + ((i + 1) & 3) * 4), 0);
      }
    } else {
      const int hi = warp - 2;
      uint64_t pol_stream;
      uint32_t rdy = 0;
      asm volatile("createpolicy.fractional.L2::evict_first.b64 %0, 1.0;" : "=l"(pol_stream));
      Ring r{0, 1, 3};
      uint32_t d = c_sched.queue[cta];
      for (int i = 0;; i++) {
        const Work w = decode(d);
        if (w.kind == 2) break;
        const CUtensorMap* m = w.kind == 0 ? &P.x[hi][w.beta >> 4] : &P.o_ld[hi];
        int c1 = (w.kind == 0 ? (w.beta & 15) : o_slot<SIMPLE>(w.beta) * 64 + w.k0) * SQ + hi * 128;
        int k_wait = -1;
        const bool both = PAIR && (w.kind == 0 || w.sub != 4), mine = !both || hi == (cta & 1);
        if (w.kind != 0 && mine) {
          if (d & 128) k_wait = d >= (3u << 30) ? 0 : 8 - (w.k0 & 7);
          asm volatile("fence.proxy.async.global;" ::: "memory");
        }
        const int rank = i == 0 ? cta : __shfl_sync(0xffffffffu, lds(sbase + EPOCH_OFF + 4), 0) - NCTA;
        for (int ks = 0; ks < w.nsteps; ks++) {
          if (ks == k_wait) {
            wait_count(&g_cnt[d & 31][(w.k0 + ks) >> 3], lds(sbase + EPOCH_OFF) * 4);
            asm volatile("fence.proxy.async.global;" ::: "memory");
            k_wait = ((w.k0 + ks) | 7) + 1 - w.k0;
          }
          const uint32_t b = borrow(ks, w.nsteps);
          const bool bo = b != 2;
          r.next_if(hi && !bo); r.next_if(hi && !bo);
          const uint32_t sl = bo ? NS + (b ^ (3 * hi)) : r.slot, bar = sbase + BAR_FULL + sl * 8;
          mbar_wait_w(bar + (BAR_EMPTY - BAR_FULL), bo ? (r.xp >> b) & 1 : r.phase);
          const uint32_t bytes = hi ? 96 * 128 : 128 * 128;
          if (!mine) {
            asm volatile(ELECT EXPECT("%0", "%2") "mbarrier.arrive.shared::cluster.b64 _, [%1];\n}"
                         ::"r"(bar), "r"(peer(bar + (BAR_RDY - BAR_FULL))), "r"(bytes) : "memory");
          } else if (both) {
            mbar_wait_w(bar + (BAR_RDY - BAR_FULL), (rdy >> sl) & 1);
            rdy ^= 1 << sl;
            if (w.kind == 0) tma_ld2_both_w(sbase + sl * SLOT, m, ks * 64, c1, bar, bytes);
            else tma_ld2_both_hint_w(sbase + sl * SLOT, m, 0, c1, bar, bytes, pol_stream);
          } else if (!PAIR && w.kind == 0) tma_ld2_w(sbase + sl * SLOT, m, ks * 64, c1, bar, bytes);
          else tma_ld2_hint_w(sbase + sl * SLOT, m, 0, c1, bar, bytes, pol_stream);
          if (w.kind != 0) c1 += SQ;
          if (i == 0 && ks == PF_STEP)
            asm volatile(ELECT "cp.async.bulk.prefetch.tensor.4d.L2.global.L2::cache_hint [%0, {0, 0, 0, %1}], %2;\n}"
                         ::"l"(&P.kv[hi][0]), "r"(d * (SK / 8)), "l"(pol_stream) : "memory");
          if (ks < 10) T2P(i, 3 + hi, ks);
          if (!hi && w.kind != 0 && !(ks & 3)) TCLK(i * 16 + (ks >> 2));
          r.next(); r.next_if(!hi && !bo); r.next_if(!hi && !bo);
          r.xp ^= 1 << b;
        }
        r.xp ^= 3;
        if (w.kind == 0) {
          m = &P.kv[hi][w.beta >> 4];
          c1 = (d & 511) * (SK / 8);
          for (int j = 0; j < 16; j++) {
            if (hi) r.next();
            const uint32_t bar = sbase + BAR_FULL + r.slot * 8;
            const bool tight = i < KV_WIN_UNITS && j < KV_WIN_TILES + ((KV_WIN_RAMP * rank) >> 5);
            {
              const int s2 = (int)r.slot - (tight ? 2 : KV_WIN_D);
              mbar_wait_w(sbase + BAR_FULL + (s2 < 0 ? s2 + NS : s2) * 8, s2 < 0 ? r.phase : r.phase ^ 1);
            }
            if (j == 15 && hi) mbar_wait_w(sbase + BAR_DESC, i & 1);
            mbar_wait_w(sbase + BAR_EMPTY + r.slot * 8, r.phase);
            tma_ld_kv_w(sbase + r.slot * SLOT, m, c1, bar, pol_stream);
            T2P(i, 3 + hi, 16 + j);
            if (!hi) TCLK(i * 16 + j);
            if (j == GO_J && !hi) mbar_arrive_warp(sbase + BAR_GO);
            c1 += 8;
            r.next();
            if (!hi) r.next();
          }
        }
        mbar_wait_w(sbase + BAR_DESC, i & 1);
        d = __shfl_sync(0xffffffffu, lds(sbase + DESC_OFF + ((i + 1) & 3) * 4), 0);
      }
    }
  } else {
    Ctx c;
    c.sb = sbase; c.wg = wg; c.warp = warp; c.src = 0; c.mqk = 0; c.mpv = 0; c.lead = lane == 0; c.lane0 = c.lane = lane;
    if (wg == 0) consumer<0>(c, P.kp); else consumer<1>(c, P.kp);
  }
}

typedef CUresult (*EncodeFn)(CUtensorMap*, CUtensorMapDataType, cuuint32_t, void*, const cuuint64_t*, const cuuint64_t*,
                             const cuuint32_t*, const cuuint32_t*, CUtensorMapInterleave, CUtensorMapSwizzle,
                             CUtensorMapL2promotion, CUtensorMapFloatOOBfill);

void make_map(EncodeFn enc, CUtensorMap* m, const void* ptr, int rank, const cuuint64_t* dims, const cuuint64_t* strides,
              const cuuint32_t* box, CUtensorMapSwizzle swz = CU_TENSOR_MAP_SWIZZLE_128B) {
  cuuint32_t es[5] = {1, 1, 1, 1, 1};
  enc(m, CU_TENSOR_MAP_DATA_TYPE_BFLOAT16, rank, const_cast<void*>(ptr), dims, strides, box, es,
      CU_TENSOR_MAP_INTERLEAVE_NONE, swz, CU_TENSOR_MAP_L2_PROMOTION_NONE,
      CU_TENSOR_MAP_FLOAT_OOB_FILL_NONE);
}

}

extern "C" void kernel_launch(void* const* d_in, const int* in_sizes, int n_in, void* d_out, int out_size) {
  (void)in_sizes; (void)n_in; (void)out_size;
  static EncodeFn enc = nullptr;
  static void* o_ptr = nullptr;
  static int n_sm = 0;
  cudaLaunchAttribute at;
  at.id = cudaLaunchAttributeClusterDimension;
  at.val.clusterDim.x = CLUSTER ? 2 : 1; at.val.clusterDim.y = 1; at.val.clusterDim.z = 1;
  cudaLaunchConfig_t cfg = {};
  cfg.gridDim = dim3(NCTA); cfg.blockDim = dim3(384); cfg.dynamicSmemBytes = SMEM_BYTES; cfg.attrs = &at; cfg.numAttrs = 1;
  if (!enc) {
    void* fn = nullptr;
    cudaDriverEntryPointQueryResult qr;
    cudaGetDriverEntryPoint("cuTensorMapEncodeTiled", &fn, cudaEnableDefault, &qr);
    enc = (EncodeFn)fn;
    cudaGetSymbolAddress(&o_ptr, g_o);
    cudaFuncSetAttribute(mha_fused_kernel<false>, cudaFuncAttributeMaxDynamicSharedMemorySize, SMEM_BYTES);
    cudaFuncSetAttribute(mha_fused_kernel<true>, cudaFuncAttributeMaxDynamicSharedMemorySize, SMEM_BYTES);
    int dev = 0;
    cudaGetDevice(&dev);
    cudaDeviceGetAttribute(&n_sm, cudaDevAttrMultiProcessorCount, dev);
    int n_cl = 0;
    cudaOccupancyMaxActiveClusters(&n_cl, mha_fused_kernel<false>, &cfg);
    if (n_cl * (CLUSTER ? 2 : 1) < NCTA && n_sm >= NCTA) n_sm = NCTA - 1;
  }
  Params P;
  for (int br = 0; br < 2; br++) {
    const void* x = d_in[br * 5 + 0]; const void* kc = d_in[br * 5 + 1]; const void* vc = d_in[br * 5 + 2];
    const void* wq = d_in[br * 5 + 3]; const void* wo = d_in[br * 5 + 4];
    { cuuint64_t d[2] = {DM, (cuuint64_t)NB * SQ}, s[1] = {DM * 2}; cuuint32_t b[2] = {64, 128}, b2[2] = {64, 96};
      make_map(enc, &P.x[0][br], x, 2, d, s, b); make_map(enc, &P.x[1][br], x, 2, d, s, b2); }
    { cuuint64_t d[3] = {64, DM, HD / 64}, s[2] = {HD * 2, 128}; cuuint32_t b[3] = {64, 64, 2}; make_map(enc, &P.wq[br], wq, 3, d, s, b); }
    { cuuint64_t d[5] = {DM, 2, 4, 4, HD / 32}, s[4] = {DM * 2, 8 * DM * 2, 2 * DM * 2, 32 * DM * 2}; cuuint32_t b[5] = {64, 2, 4, 4, 2};
      make_map(enc, &P.wo[br], wo, 5, d, s, b); }
    { cuuint64_t d[4] = {64, 8, 2, (cuuint64_t)NB * NH * SK / 8}, s[3] = {DH * 2, 128, DH * 16}; cuuint32_t b[4] = {64, 8, 2, 8};
      make_map(enc, &P.kv[0][br], kc, 4, d, s, b); make_map(enc, &P.kv[1][br], vc, 4, d, s, b); }
    P.kp[br] = (const __nv_bfloat16*)kc; P.vp[br] = (const __nv_bfloat16*)vc;

  }
  { cuuint64_t d[2] = {64, (cuuint64_t)NBETA * 64 * SQ}, s[1] = {128}; cuuint32_t b[2] = {64, 128}, b2[2] = {64, 96};
    make_map(enc, &P.o_ld[0], o_ptr, 2, d, s, b, CU_TENSOR_MAP_SWIZZLE_NONE); make_map(enc, &P.o_ld[1], o_ptr, 2, d, s, b2, CU_TENSOR_MAP_SWIZZLE_NONE); }
  { cuuint64_t d[3] = {64, SQ, O_BLOCKS}, s[2] = {128, SQ * 128}; cuuint32_t b[3] = {64, 64, 2}, b2[3] = {64, 32, 2};
    make_map(enc, &P.o_st[0], o_ptr, 3, d, s, b); make_map(enc, &P.o_st[1], o_ptr, 3, d, s, b2); }
  { cuuint64_t d[3] = {64, (cuuint64_t)NB * SQ, 2 * DM / 64}, s[2] = {2 * DM * 2, 128}; cuuint32_t b[3] = {64, 64, 2}, b2[3] = {64, 32, 2};
    make_map(enc, &P.out_st[0], d_out, 3, d, s, b); make_map(enc, &P.out_st[1], d_out, 3, d, s, b2); }
  if (n_sm >= NCTA) cudaLaunchKernelEx(&cfg, mha_fused_kernel<false>, P);
  else mha_fused_kernel<true><<<n_sm, 384, SMEM_BYTES>>>(P);
}
```

```cpp
#include <cuda_runtime.h>
#include <cuda_bf16.h>
#include <cuda.h>
#include <stdint.h>
#include <stdlib.h>

namespace {

__device__ __forceinline__ void wgmma_proj(float (&d)[64], uint64_t da, uint64_t db, int scaleD) {
  asm volatile("{\n.reg .pred p;\nsetp.ne.b32 p, %66, 0;\n"
      "wgmma.mma_async.sync.aligned.m64n128k16.f32.bf16.bf16 "
      "{%0, %1, %2, %3, %4, %5, %6, %7, %8, %9, %10, %11, %12, %13, %14, %15, %16, %17, %18, %19, %20, %21, %22, %23, %24, %25, %26, %27, %28, %29, %30, "
      "%31, %32, %33, %34, %35, %36, %37, %38, %39, %40, %41, %42, %43, %44, %45, %46, %47, %48, %49, %50, %51, %52, %53, %54, %55, %56, %57, %58, %59, %60, "
      "%61, %62, %63}, "
      "%64, %65, p, 1, 1, 0, 1;\n}\n"
      : "+f"(d[0]), "+f"(d[1]), "+f"(d[2]), "+f"(d[3]), "+f"(d[4]), "+f"(d[5]), "+f"(d[6]), "+f"(d[7]), "+f"(d[8]), "+f"(d[9]), "+f"(d[10]), "+f"(d[11]),
        "+f"(d[12]), "+f"(d[13]), "+f"(d[14]), "+f"(d[15]), "+f"(d[16]), "+f"(d[17]), "+f"(d[18]), "+f"(d[19]), "+f"(d[20]), "+f"(d[21]), "+f"(d[22]),
        "+f"(d[23]), "+f"(d[24]), "+f"(d[25]), "+f"(d[26]), "+f"(d[27]), "+f"(d[28]), "+f"(d[29]), "+f"(d[30]), "+f"(d[31]), "+f"(d[32]), "+f"(d[33]),
        "+f"(d[34]), "+f"(d[35]), "+f"(d[36]), "+f"(d[37]), "+f"(d[38]), "+f"(d[39]), "+f"(d[40]), "+f"(d[41]), "+f"(d[42]), "+f"(d[43]), "+f"(d[44]),
        "+f"(d[45]), "+f"(d[46]), "+f"(d[47]), "+f"(d[48]), "+f"(d[49]), "+f"(d[50]), "+f"(d[51]), "+f"(d[52]), "+f"(d[53]), "+f"(d[54]), "+f"(d[55]),
        "+f"(d[56]), "+f"(d[57]), "+f"(d[58]), "+f"(d[59]), "+f"(d[60]), "+f"(d[61]), "+f"(d[62]), "+f"(d[63])
      : "l"(da), "l"(db), "r"(scaleD));
}
__device__ __forceinline__ void wgmma_proj96(float (&d)[64], uint64_t da, uint64_t db, int scaleD) {
  asm volatile("{\n.reg .pred p;\nsetp.ne.b32 p, %50, 0;\n"
      "wgmma.mma_async.sync.aligned.m64n96k16.f32.bf16.bf16 "
      "{%0, %1, %2, %3, %4, %5, %6, %7, %8, %9, %10, %11, %12, %13, %14, %15, %16, %17, %18, %19, %20, %21, %22, %23, %24, %25, %26, %27, %28, %29, %30, "
      "%31, %32, %33, %34, %35, %36, %37, %38, %39, %40, %41, %42, %43, %44, %45, %46, %47}, "
      "%48, %49, p, 1, 1, 1, 0;\n}\n"
      : "+f"(d[0]), "+f"(d[1]), "+f"(d[2]), "+f"(d[3]), "+f"(d[4]), "+f"(d[5]), "+f"(d[6]), "+f"(d[7]), "+f"(d[8]), "+f"(d[9]), "+f"(d[10]), "+f"(d[11]),
        "+f"(d[12]), "+f"(d[13]), "+f"(d[14]), "+f"(d[15]), "+f"(d[16]), "+f"(d[17]), "+f"(d[18]), "+f"(d[19]), "+f"(d[20]), "+f"(d[21]), "+f"(d[22]),
        "+f"(d[23]), "+f"(d[24]), "+f"(d[25]), "+f"(d[26]), "+f"(d[27]), "+f"(d[28]), "+f"(d[29]), "+f"(d[30]), "+f"(d[31]), "+f"(d[32]), "+f"(d[33]),
        "+f"(d[34]), "+f"(d[35]), "+f"(d[36]), "+f"(d[37]), "+f"(d[38]), "+f"(d[39]), "+f"(d[40]), "+f"(d[41]), "+f"(d[42]), "+f"(d[43]), "+f"(d[44]),
        "+f"(d[45]), "+f"(d[46]), "+f"(d[47])
      : "l"(da), "l"(db), "r"(scaleD));
}
__device__ __forceinline__ void wgmma_qk(float (&d)[32], uint64_t da, uint64_t db, int scaleD) {
  asm volatile("{\n.reg .pred p;\nsetp.ne.b32 p, %34, 0;\n"
      "wgmma.mma_async.sync.aligned.m64n64k16.f32.bf16.bf16 "
      "{%0, %1, %2, %3, %4, %5, %6, %7, %8, %9, %10, %11, %12, %13, %14, %15, %16, %17, %18, %19, %20, %21, %22, %23, %24, %25, %26, %27, %28, %29, %30, "
      "%31}, "
      "%32, %33, p, 1, 1, 0, 0;\n}\n"
      : "+f"(d[0]), "+f"(d[1]), "+f"(d[2]), "+f"(d[3]), "+f"(d[4]), "+f"(d[5]), "+f"(d[6]), "+f"(d[7]), "+f"(d[8]), "+f"(d[9]), "+f"(d[10]), "+f"(d[11]),
        "+f"(d[12]), "+f"(d[13]), "+f"(d[14]), "+f"(d[15]), "+f"(d[16]), "+f"(d[17]), "+f"(d[18]), "+f"(d[19]), "+f"(d[20]), "+f"(d[21]), "+f"(d[22]),
        "+f"(d[23]), "+f"(d[24]), "+f"(d[25]), "+f"(d[26]), "+f"(d[27]), "+f"(d[28]), "+f"(d[29]), "+f"(d[30]), "+f"(d[31])
      : "l"(da), "l"(db), "r"(scaleD));
}
__device__ __forceinline__ void wgmma_qk_rs(float (&d)[32], uint32_t a0, uint32_t a1, uint32_t a2, uint32_t a3, uint64_t db, int scaleD) {
  asm volatile("{\n.reg .pred p;\nsetp.ne.b32 p, %37, 0;\n"
      "wgmma.mma_async.sync.aligned.m64n64k16.f32.bf16.bf16 "
      "{%0, %1, %2, %3, %4, %5, %6, %7, %8, %9, %10, %11, %12, %13, %14, %15, %16, %17, %18, %19, %20, %21, %22, %23, %24, %25, %26, %27, %28, %29, %30, "
      "%31}, "
      "{%32, %33, %34, %35}, %36, p, 1, 1, 0;\n}\n"
      : "+f"(d[0]), "+f"(d[1]), "+f"(d[2]), "+f"(d[3]), "+f"(d[4]), "+f"(d[5]), "+f"(d[6]), "+f"(d[7]), "+f"(d[8]), "+f"(d[9]), "+f"(d[10]), "+f"(d[11]),
        "+f"(d[12]), "+f"(d[13]), "+f"(d[14]), "+f"(d[15]), "+f"(d[16]), "+f"(d[17]), "+f"(d[18]), "+f"(d[19]), "+f"(d[20]), "+f"(d[21]), "+f"(d[22]),
        "+f"(d[23]), "+f"(d[24]), "+f"(d[25]), "+f"(d[26]), "+f"(d[27]), "+f"(d[28]), "+f"(d[29]), "+f"(d[30]), "+f"(d[31])
      : "r"(a0), "r"(a1), "r"(a2), "r"(a3), "l"(db), "r"(scaleD));
}
__device__ __forceinline__ void wgmma_pv(float (&d)[64], uint32_t a0, uint32_t a1, uint32_t a2, uint32_t a3, uint64_t db, int scaleD) {
  asm volatile("{\n.reg .pred p;\nsetp.ne.b32 p, %69, 0;\n"
      "wgmma.mma_async.sync.aligned.m64n128k16.f32.bf16.bf16 "
      "{%0, %1, %2, %3, %4, %5, %6, %7, %8, %9, %10, %11, %12, %13, %14, %15, %16, %17, %18, %19, %20, %21, %22, %23, %24, %25, %26, %27, %28, %29, %30, "
      "%31, %32, %33, %34, %35, %36, %37, %38, %39, %40, %41, %42, %43, %44, %45, %46, %47, %48, %49, %50, %51, %52, %53, %54, %55, %56, %57, %58, %59, %60, "
      "%61, %62, %63}, "
      "{%64, %65, %66, %67}, %68, p, 1, 1, 1;\n}\n"
      : "+f"(d[0]), "+f"(d[1]), "+f"(d[2]), "+f"(d[3]), "+f"(d[4]), "+f"(d[5]), "+f"(d[6]), "+f"(d[7]), "+f"(d[8]), "+f"(d[9]), "+f"(d[10]), "+f"(d[11]),
        "+f"(d[12]), "+f"(d[13]), "+f"(d[14]), "+f"(d[15]), "+f"(d[16]), "+f"(d[17]), "+f"(d[18]), "+f"(d[19]), "+f"(d[20]), "+f"(d[21]), "+f"(d[22]),
        "+f"(d[23]), "+f"(d[24]), "+f"(d[25]), "+f"(d[26]), "+f"(d[27]), "+f"(d[28]), "+f"(d[29]), "+f"(d[30]), "+f"(d[31]), "+f"(d[32]), "+f"(d[33]),
        "+f"(d[34]), "+f"(d[35]), "+f"(d[36]), "+f"(d[37]), "+f"(d[38]), "+f"(d[39]), "+f"(d[40]), "+f"(d[41]), "+f"(d[42]), "+f"(d[43]), "+f"(d[44]),
        "+f"(d[45]), "+f"(d[46]), "+f"(d[47]), "+f"(d[48]), "+f"(d[49]), "+f"(d[50]), "+f"(d[51]), "+f"(d[52]), "+f"(d[53]), "+f"(d[54]), "+f"(d[55]),
        "+f"(d[56]), "+f"(d[57]), "+f"(d[58]), "+f"(d[59]), "+f"(d[60]), "+f"(d[61]), "+f"(d[62]), "+f"(d[63])
      : "r"(a0), "r"(a1), "r"(a2), "r"(a3), "l"(db), "r"(scaleD));
}
__device__ __forceinline__ void wgmma_qk_sp(float (&d)[32], uint32_t a0, uint32_t a1, uint32_t a2, uint32_t a3, uint64_t db, int scaleD, uint32_t meta) {
  asm volatile("{\n.reg .pred p;\nsetp.ne.b32 p, %37, 0;\n"
      "wgmma.mma_async.sp.sync.aligned.m64n64k32.f32.bf16.bf16 "
      "{%0, %1, %2, %3, %4, %5, %6, %7, %8, %9, %10, %11, %12, %13, %14, %15, %16, %17, %18, %19, %20, %21, %22, %23, %24, %25, %26, %27, %28, %29, %30, "
      "%31}, "
      "{%32, %33, %34, %35}, %36, %38, 0, p, 1, 1, 0;\n}\n"
      : "+f"(d[0]), "+f"(d[1]), "+f"(d[2]), "+f"(d[3]), "+f"(d[4]), "+f"(d[5]), "+f"(d[6]), "+f"(d[7]), "+f"(d[8]), "+f"(d[9]), "+f"(d[10]), "+f"(d[11]),
        "+f"(d[12]), "+f"(d[13]), "+f"(d[14]), "+f"(d[15]), "+f"(d[16]), "+f"(d[17]), "+f"(d[18]), "+f"(d[19]), "+f"(d[20]), "+f"(d[21]), "+f"(d[22]),
        "+f"(d[23]), "+f"(d[24]), "+f"(d[25]), "+f"(d[26]), "+f"(d[27]), "+f"(d[28]), "+f"(d[29]), "+f"(d[30]), "+f"(d[31])
      : "r"(a0), "r"(a1), "r"(a2), "r"(a3), "l"(db), "r"(scaleD), "r"(meta));
}
__device__ __forceinline__ void wgmma_pv_sp(float (&d)[64], uint32_t a0, uint32_t a1, uint32_t a2, uint32_t a3, uint64_t db, int scaleD, uint32_t meta) {
  asm volatile("{\n.reg .pred p;\nsetp.ne.b32 p, %69, 0;\n"
      "wgmma.mma_async.sp.sync.aligned.m64n128k32.f32.bf16.bf16 "
      "{%0, %1, %2, %3, %4, %5, %6, %7, %8, %9, %10, %11, %12, %13, %14, %15, %16, %17, %18, %19, %20, %21, %22, %23, %24, %25, %26, %27, %28, %29, %30, "
      "%31, %32, %33, %34, %35, %36, %37, %38, %39, %40, %41, %42, %43, %44, %45, %46, %47, %48, %49, %50, %51, %52, %53, %54, %55, %56, %57, %58, %59, %60, "
      "%61, %62, %63}, "
      "{%64, %65, %66, %67}, %68, %70, 0, p, 1, 1, 1;\n}\n"
      : "+f"(d[0]), "+f"(d[1]), "+f"(d[2]), "+f"(d[3]), "+f"(d[4]), "+f"(d[5]), "+f"(d[6]), "+f"(d[7]), "+f"(d[8]), "+f"(d[9]), "+f"(d[10]), "+f"(d[11]),
        "+f"(d[12]), "+f"(d[13]), "+f"(d[14]), "+f"(d[15]), "+f"(d[16]), "+f"(d[17]), "+f"(d[18]), "+f"(d[19]), "+f"(d[20]), "+f"(d[21]), "+f"(d[22]),
        "+f"(d[23]), "+f"(d[24]), "+f"(d[25]), "+f"(d[26]), "+f"(d[27]), "+f"(d[28]), "+f"(d[29]), "+f"(d[30]), "+f"(d[31]), "+f"(d[32]), "+f"(d[33]),
        "+f"(d[34]), "+f"(d[35]), "+f"(d[36]), "+f"(d[37]), "+f"(d[38]), "+f"(d[39]), "+f"(d[40]), "+f"(d[41]), "+f"(d[42]), "+f"(d[43]), "+f"(d[44]),
        "+f"(d[45]), "+f"(d[46]), "+f"(d[47]), "+f"(d[48]), "+f"(d[49]), "+f"(d[50]), "+f"(d[51]), "+f"(d[52]), "+f"(d[53]), "+f"(d[54]), "+f"(d[55]),
        "+f"(d[56]), "+f"(d[57]), "+f"(d[58]), "+f"(d[59]), "+f"(d[60]), "+f"(d[61]), "+f"(d[62]), "+f"(d[63])
      : "r"(a0), "r"(a1), "r"(a2), "r"(a3), "l"(db), "r"(scaleD), "r"(meta));
}
__device__ __forceinline__ void wgmma_proj_init(float (&d)[64], uint64_t da, uint64_t db, int scaleD) {
  asm volatile("{\n.reg .pred p;\nsetp.ne.b32 p, %66, 0;\n"
      "wgmma.mma_async.sync.aligned.m64n128k16.f32.bf16.bf16 "
      "{%0, %1, %2, %3, %4, %5, %6, %7, %8, %9, %10, %11, %12, %13, %14, %15, %16, %17, %18, %19, %20, %21, %22, %23, %24, %25, %26, %27, %28, %29, %30, "
      "%31, %32, %33, %34, %35, %36, %37, %38, %39, %40, %41, %42, %43, %44, %45, %46, %47, %48, %49, %50, %51, %52, %53, %54, %55, %56, %57, %58, %59, %60, "
      "%61, %62, %63}, "
      "%64, %65, p, 1, 1, 0, 1;\n}\n"
      : "=f"(d[0]), "=f"(d[1]), "=f"(d[2]), "=f"(d[3]), "=f"(d[4]), "=f"(d[5]), "=f"(d[6]), "=f"(d[7]), "=f"(d[8]), "=f"(d[9]), "=f"(d[10]), "=f"(d[11]),
        "=f"(d[12]), "=f"(d[13]), "=f"(d[14]), "=f"(d[15]), "=f"(d[16]), "=f"(d[17]), "=f"(d[18]), "=f"(d[19]), "=f"(d[20]), "=f"(d[21]), "=f"(d[22]),
        "=f"(d[23]), "=f"(d[24]), "=f"(d[25]), "=f"(d[26]), "=f"(d[27]), "=f"(d[28]), "=f"(d[29]), "=f"(d[30]), "=f"(d[31]), "=f"(d[32]), "=f"(d[33]),
        "=f"(d[34]), "=f"(d[35]), "=f"(d[36]), "=f"(d[37]), "=f"(d[38]), "=f"(d[39]), "=f"(d[40]), "=f"(d[41]), "=f"(d[42]), "=f"(d[43]), "=f"(d[44]),
        "=f"(d[45]), "=f"(d[46]), "=f"(d[47]), "=f"(d[48]), "=f"(d[49]), "=f"(d[50]), "=f"(d[51]), "=f"(d[52]), "=f"(d[53]), "=f"(d[54]), "=f"(d[55]),
        "=f"(d[56]), "=f"(d[57]), "=f"(d[58]), "=f"(d[59]), "=f"(d[60]), "=f"(d[61]), "=f"(d[62]), "=f"(d[63])
      : "l"(da), "l"(db), "r"(scaleD));
}
__device__ __forceinline__ void wgmma_proj96_init(float (&d)[64], uint64_t da, uint64_t db, int scaleD) {
  asm volatile("{\n.reg .pred p;\nsetp.ne.b32 p, %50, 0;\n"
      "wgmma.mma_async.sync.aligned.m64n96k16.f32.bf16.bf16 "
      "{%0, %1, %2, %3, %4, %5, %6, %7, %8, %9, %10, %11, %12, %13, %14, %15, %16, %17, %18, %19, %20, %21, %22, %23, %24, %25, %26, %27, %28, %29, %30, "
      "%31, %32, %33, %34, %35, %36, %37, %38, %39, %40, %41, %42, %43, %44, %45, %46, %47}, "
      "%48, %49, p, 1, 1, 1, 0;\n}\n"
      : "=f"(d[0]), "=f"(d[1]), "=f"(d[2]), "=f"(d[3]), "=f"(d[4]), "=f"(d[5]), "=f"(d[6]), "=f"(d[7]), "=f"(d[8]), "=f"(d[9]), "=f"(d[10]), "=f"(d[11]),
        "=f"(d[12]), "=f"(d[13]), "=f"(d[14]), "=f"(d[15]), "=f"(d[16]), "=f"(d[17]), "=f"(d[18]), "=f"(d[19]), "=f"(d[20]), "=f"(d[21]), "=f"(d[22]),
        "=f"(d[23]), "=f"(d[24]), "=f"(d[25]), "=f"(d[26]), "=f"(d[27]), "=f"(d[28]), "=f"(d[29]), "=f"(d[30]), "=f"(d[31]), "=f"(d[32]), "=f"(d[33]),
        "=f"(d[34]), "=f"(d[35]), "=f"(d[36]), "=f"(d[37]), "=f"(d[38]), "=f"(d[39]), "=f"(d[40]), "=f"(d[41]), "=f"(d[42]), "=f"(d[43]), "=f"(d[44]),
        "=f"(d[45]), "=f"(d[46]), "=f"(d[47])
      : "l"(da), "l"(db), "r"(scaleD));
}
__device__ __forceinline__ void wgmma_qk_init(float (&d)[32], uint64_t da, uint64_t db, int scaleD) {
  asm volatile("{\n.reg .pred p;\nsetp.ne.b32 p, %34, 0;\n"
      "wgmma.mma_async.sync.aligned.m64n64k16.f32.bf16.bf16 "
      "{%0, %1, %2, %3, %4, %5, %6, %7, %8, %9, %10, %11, %12, %13, %14, %15, %16, %17, %18, %19, %20, %21, %22, %23, %24, %25, %26, %27, %28, %29, %30, "
      "%31}, "
      "%32, %33, p, 1, 1, 0, 0;\n}\n"
      : "=f"(d[0]), "=f"(d[1]), "=f"(d[2]), "=f"(d[3]), "=f"(d[4]), "=f"(d[5]), "=f"(d[6]), "=f"(d[7]), "=f"(d[8]), "=f"(d[9]), "=f"(d[10]), "=f"(d[11]),
        "=f"(d[12]), "=f"(d[13]), "=f"(d[14]), "=f"(d[15]), "=f"(d[16]), "=f"(d[17]), "=f"(d[18]), "=f"(d[19]), "=f"(d[20]), "=f"(d[21]), "=f"(d[22]),
        "=f"(d[23]), "=f"(d[24]), "=f"(d[25]), "=f"(d[26]), "=f"(d[27]), "=f"(d[28]), "=f"(d[29]), "=f"(d[30]), "=f"(d[31])
      : "l"(da), "l"(db), "r"(scaleD));
}
__device__ __forceinline__ void wgmma_qk_rs_init(float (&d)[32], uint32_t a0, uint32_t a1, uint32_t a2, uint32_t a3, uint64_t db, int scaleD) {
  asm volatile("{\n.reg .pred p;\nsetp.ne.b32 p, %37, 0;\n"
      "wgmma.mma_async.sync.aligned.m64n64k16.f32.bf16.bf16 "
      "{%0, %1, %2, %3, %4, %5, %6, %7, %8, %9, %10, %11, %12, %13, %14, %15, %16, %17, %18, %19, %20, %21, %22, %23, %24, %25, %26, %27, %28, %29, %30, "
      "%31}, "
      "{%32, %33, %34, %35}, %36, p, 1, 1, 0;\n}\n"
      : "=f"(d[0]), "=f"(d[1]), "=f"(d[2]), "=f"(d[3]), "=f"(d[4]), "=f"(d[5]), "=f"(d[6]), "=f"(d[7]), "=f"(d[8]), "=f"(d[9]), "=f"(d[10]), "=f"(d[11]),
        "=f"(d[12]), "=f"(d[13]), "=f"(d[14]), "=f"(d[15]), "=f"(d[16]), "=f"(d[17]), "=f"(d[18]), "=f"(d[19]), "=f"(d[20]), "=f"(d[21]), "=f"(d[22]),
        "=f"(d[23]), "=f"(d[24]), "=f"(d[25]), "=f"(d[26]), "=f"(d[27]), "=f"(d[28]), "=f"(d[29]), "=f"(d[30]), "=f"(d[31])
      : "r"(a0), "r"(a1), "r"(a2), "r"(a3), "l"(db), "r"(scaleD));
}
__device__ __forceinline__ void wgmma_pv_init(float (&d)[64], uint32_t a0, uint32_t a1, uint32_t a2, uint32_t a3, uint64_t db, int scaleD) {
  asm volatile("{\n.reg .pred p;\nsetp.ne.b32 p, %69, 0;\n"
      "wgmma.mma_async.sync.aligned.m64n128k16.f32.bf16.bf16 "
      "{%0, %1, %2, %3, %4, %5, %6, %7, %8, %9, %10, %11, %12, %13, %14, %15, %16, %17, %18, %19, %20, %21, %22, %23, %24, %25, %26, %27, %28, %29, %30, "
      "%31, %32, %33, %34, %35, %36, %37, %38, %39, %40, %41, %42, %43, %44, %45, %46, %47, %48, %49, %50, %51, %52, %53, %54, %55, %56, %57, %58, %59, %60, "
      "%61, %62, %63}, "
      "{%64, %65, %66, %67}, %68, p, 1, 1, 1;\n}\n"
      : "=f"(d[0]), "=f"(d[1]), "=f"(d[2]), "=f"(d[3]), "=f"(d[4]), "=f"(d[5]), "=f"(d[6]), "=f"(d[7]), "=f"(d[8]), "=f"(d[9]), "=f"(d[10]), "=f"(d[11]),
        "=f"(d[12]), "=f"(d[13]), "=f"(d[14]), "=f"(d[15]), "=f"(d[16]), "=f"(d[17]), "=f"(d[18]), "=f"(d[19]), "=f"(d[20]), "=f"(d[21]), "=f"(d[22]),
        "=f"(d[23]), "=f"(d[24]), "=f"(d[25]), "=f"(d[26]), "=f"(d[27]), "=f"(d[28]), "=f"(d[29]), "=f"(d[30]), "=f"(d[31]), "=f"(d[32]), "=f"(d[33]),
        "=f"(d[34]), "=f"(d[35]), "=f"(d[36]), "=f"(d[37]), "=f"(d[38]), "=f"(d[39]), "=f"(d[40]), "=f"(d[41]), "=f"(d[42]), "=f"(d[43]), "=f"(d[44]),
        "=f"(d[45]), "=f"(d[46]), "=f"(d[47]), "=f"(d[48]), "=f"(d[49]), "=f"(d[50]), "=f"(d[51]), "=f"(d[52]), "=f"(d[53]), "=f"(d[54]), "=f"(d[55]),
        "=f"(d[56]), "=f"(d[57]), "=f"(d[58]), "=f"(d[59]), "=f"(d[60]), "=f"(d[61]), "=f"(d[62]), "=f"(d[63])
      : "r"(a0), "r"(a1), "r"(a2), "r"(a3), "l"(db), "r"(scaleD));
}
__device__ __forceinline__ void wgmma_qk_sp_init(float (&d)[32], uint32_t a0, uint32_t a1, uint32_t a2, uint32_t a3, uint64_t db, int scaleD, uint32_t meta) {
  asm volatile("{\n.reg .pred p;\nsetp.ne.b32 p, %37, 0;\n"
      "wgmma.mma_async.sp.sync.aligned.m64n64k32.f32.bf16.bf16 "
      "{%0, %1, %2, %3, %4, %5, %6, %7, %8, %9, %10, %11, %12, %13, %14, %15, %16, %17, %18, %19, %20, %21, %22, %23, %24, %25, %26, %27, %28, %29, %30, "
      "%31}, "
      "{%32, %33, %34, %35}, %36, %38, 0, p, 1, 1, 0;\n}\n"
      : "=f"(d[0]), "=f"(d[1]), "=f"(d[2]), "=f"(d[3]), "=f"(d[4]), "=f"(d[5]), "=f"(d[6]), "=f"(d[7]), "=f"(d[8]), "=f"(d[9]), "=f"(d[10]), "=f"(d[11]),
        "=f"(d[12]), "=f"(d[13]), "=f"(d[14]), "=f"(d[15]), "=f"(d[16]), "=f"(d[17]), "=f"(d[18]), "=f"(d[19]), "=f"(d[20]), "=f"(d[21]), "=f"(d[22]),
        "=f"(d[23]), "=f"(d[24]), "=f"(d[25]), "=f"(d[26]), "=f"(d[27]), "=f"(d[28]), "=f"(d[29]), "=f"(d[30]), "=f"(d[31])
      : "r"(a0), "r"(a1), "r"(a2), "r"(a3), "l"(db), "r"(scaleD), "r"(meta));
}
__device__ __forceinline__ void wgmma_pv_sp_init(float (&d)[64], uint32_t a0, uint32_t a1, uint32_t a2, uint32_t a3, uint64_t db, int scaleD, uint32_t meta) {
  asm volatile("{\n.reg .pred p;\nsetp.ne.b32 p, %69, 0;\n"
      "wgmma.mma_async.sp.sync.aligned.m64n128k32.f32.bf16.bf16 "
      "{%0, %1, %2, %3, %4, %5, %6, %7, %8, %9, %10, %11, %12, %13, %14, %15, %16, %17, %18, %19, %20, %21, %22, %23, %24, %25, %26, %27, %28, %29, %30, "
      "%31, %32, %33, %34, %35, %36, %37, %38, %39, %40, %41, %42, %43, %44, %45, %46, %47, %48, %49, %50, %51, %52, %53, %54, %55, %56, %57, %58, %59, %60, "
      "%61, %62, %63}, "
      "{%64, %65, %66, %67}, %68, %70, 0, p, 1, 1, 1;\n}\n"
      : "=f"(d[0]), "=f"(d[1]), "=f"(d[2]), "=f"(d[3]), "=f"(d[4]), "=f"(d[5]), "=f"(d[6]), "=f"(d[7]), "=f"(d[8]), "=f"(d[9]), "=f"(d[10]), "=f"(d[11]),
        "=f"(d[12]), "=f"(d[13]), "=f"(d[14]), "=f"(d[15]), "=f"(d[16]), "=f"(d[17]), "=f"(d[18]), "=f"(d[19]), "=f"(d[20]), "=f"(d[21]), "=f"(d[22]),
        "=f"(d[23]), "=f"(d[24]), "=f"(d[25]), "=f"(d[26]), "=f"(d[27]), "=f"(d[28]), "=f"(d[29]), "=f"(d[30]), "=f"(d[31]), "=f"(d[32]), "=f"(d[33]),
        "=f"(d[34]), "=f"(d[35]), "=f"(d[36]), "=f"(d[37]), "=f"(d[38]), "=f"(d[39]), "=f"(d[40]), "=f"(d[41]), "=f"(d[42]), "=f"(d[43]), "=f"(d[44]),
        "=f"(d[45]), "=f"(d[46]), "=f"(d[47]), "=f"(d[48]), "=f"(d[49]), "=f"(d[50]), "=f"(d[51]), "=f"(d[52]), "=f"(d[53]), "=f"(d[54]), "=f"(d[55]),
        "=f"(d[56]), "=f"(d[57]), "=f"(d[58]), "=f"(d[59]), "=f"(d[60]), "=f"(d[61]), "=f"(d[62]), "=f"(d[63])
      : "r"(a0), "r"(a1), "r"(a2), "r"(a3), "l"(db), "r"(scaleD), "r"(meta));
}

constexpr int NB = 16, SQ = 224, DM = 640, NH = 32, SK = 1024, DH = 128;
constexpr int HD = NH * DH;
constexpr int NBETA = 2 * NB;
constexpr int NCTA = 132;
constexpr uint32_t SB0 = 1024;
constexpr int NS = 10;
constexpr int SLOT = 16384;
constexpr int QBUF_OFF = NS * SLOT;
constexpr int NSX = NS + 4;
constexpr int BAR_OFF = NSX * SLOT;
constexpr int BAR_FULL = BAR_OFF;
constexpr int BAR_EMPTY = BAR_OFF + 8 * NSX;
constexpr int BAR_STG = BAR_OFF + 16 * NSX;
constexpr int BAR_OUT = BAR_STG + 32;
constexpr int BAR_DESC = BAR_OUT + 8;
constexpr int BAR_GO = BAR_DESC + 8;
constexpr int BAR_MAIL = BAR_GO + 8;
constexpr int BAR_RDY = BAR_MAIL + 8;
constexpr int DESC_OFF = BAR_RDY + 8 * NSX;
constexpr int EPOCH_OFF = DESC_OFF + 16;
constexpr int TRACE_OFF = EPOCH_OFF + 16;
constexpr int SMEM_BYTES = TRACE_OFF;
constexpr float SM_C = 0.08838834764831845f * 1.4426950408889634f;
constexpr float SUM_HI = 1099511627776.f, SUM_LO = 1.f / 1099511627776.f;
constexpr uint32_t META_QK = 0xEEEE4444u;
constexpr uint32_t META_PV = 0x44EEEE44u;

#define QK_EARLY_MASK 3
#define ST_ORDER 0x2310
#define LAG_BAR 2
#define ST_NOW 8
#define PF_STEP 5
#define KV_WIN_UNITS 2
#define KV_WIN_D 4
#define SF 0xeebf
#define O_STEPS 4
#define KV_WIN_RAMP 4
#define PDEPTH 0
#define KV_WIN_TILES -2
#define REG_C 232
#define REG_P 24
#define GO_P 6
#define P_POS 216
#define OR 6
#define OR0 0
#define B_LATE 23
#define H_LATE 24
#define RM0 1
#define RM1 0xab
#define RM2 0
#define PAIRB 1
#define LATE0 1
#define LATE1 2
#define GO_J 13
#define KG 5
#define PK 44
#define EARLY_MASK 0x3fffu
#define PIECE_TABLE 0x50188016,0x65e88038,0x50321819,0x6c8d1830,0x403f2812,0x80000000,0x50215014,0x695a503c,0x5029b813,0x6c4eb85e,0x501b4815,0x689d4834,0x502b1017,0x6ccc1039,0x50312010,0x80000000,0x500e681b,0x65e8683f,0x502ea011,0x80000000,0x63b1902e,0x80000000,0x63f0603b,0x80000000,0x64ad003d,0x80000000,0x64eca83a,0x80000000,0x5024581c,0x80000000,0x5012b01a,0x6a95b033,0x5011081d,0x6b130837,0x5016701f,0x6c8d7056,0x501ec81e,0x80000000,0x6723302f,0x80000000,0x501b380f,0x80000000,0x67234035,0x80000000,0x500d980e,0x6bd09831,0x56587816,0x80000000,0x50168818,0x80000000,0x57d1c01e,0x80000000

struct Params {
  CUtensorMap x[2][2], wq[2], kv[2][2], wo[2];
  CUtensorMap o_ld[2], o_st[2], out_st[2];
  const __nv_bfloat16* kp[2];
  const __nv_bfloat16* vp[2];
};

constexpr int NPART = 32 * 5, O_BLOCKS = NBETA * 64 + 2 * NPART;
__device__ __align__(128) __nv_bfloat16 g_o[(size_t)O_BLOCKS * SQ * 64];
__device__ unsigned g_cnt[NBETA][8];
__device__ unsigned g_rd[NBETA][8];
__device__ unsigned g_epoch, g_next;
__device__ unsigned g_flag[NPART];

__device__ __forceinline__ uint32_t smem_u32(const void* p) { return (uint32_t)__cvta_generic_to_shared(p); }
__device__ __forceinline__ void mbar_arrive(uint32_t bar) {
  asm volatile("mbarrier.arrive.shared::cta.b64 _, [%0];" ::"r"(bar) : "memory");
}
__device__ __forceinline__ void mbar_arrive_warp(uint32_t bar) {
  asm volatile("{\n.reg .pred p;\nelect.sync _|p, 0xffffffff;\n@p mbarrier.arrive.shared::cta.b64 _, [%0];\n}" ::"r"(bar) : "memory");
}
__device__ __forceinline__ int lane_now() { int l; asm volatile("mov.u32 %0, %%laneid;" : "=r"(l)); return l; }
__device__ __forceinline__ bool mbar_try(uint32_t bar, uint32_t parity) {
  uint32_t ok;
  asm volatile("{\n.reg .pred p;\nmbarrier.try_wait.parity.shared::cta.b64 p, [%1], %2;\nselp.u32 %0, 1, 0, p;\n}"
               : "=r"(ok) : "r"(bar), "r"(parity) : "memory");
  return ok;
}
__device__ __forceinline__ bool mbar_test(uint32_t bar, uint32_t parity) {
  uint32_t ok;
  asm volatile("{\n.reg .pred p;\nmbarrier.test_wait.parity.shared::cta.b64 p, [%1], %2;\nselp.u32 %0, 1, 0, p;\n}"
               : "=r"(ok) : "r"(bar), "r"(parity) : "memory");
  return ok;
}
__device__ __forceinline__ void mbar_wait_w(uint32_t bar, uint32_t parity) {
  uint32_t n = 0;
  while (!__all_sync(0xffffffffu, mbar_try(bar, parity))) {
    if (++n > (1u << 22)) __trap();
  }
}
#define ELECT "{\n.reg .pred p;\nelect.sync _|p, 0xffffffff;\n@p "
__device__ __forceinline__ void tma_st3_w(const CUtensorMap* m, uint32_t src, int c1, int c2) {
  asm volatile(ELECT "cp.async.bulk.tensor.3d.global.shared::cta.bulk_group [%0, {0, %2, %3}], [%1];\n}"
               ::"l"(m), "r"(src), "r"(c1), "r"(c2) : "memory");
}
#define EXPECT(bar, bytes) "mbarrier.arrive.expect_tx.shared::cta.b64 _, [" bar "], " bytes ";\n@p "
__device__ __forceinline__ void tma_ld2_w(uint32_t dst, const CUtensorMap* m, int c0, int c1, uint32_t bar, uint32_t bytes) {
  asm volatile(ELECT EXPECT("%2", "%5") "cp.async.bulk.tensor.2d.shared::cluster.global.mbarrier::complete_tx::bytes [%0], [%1, {%3, %4}], [%2];\n}"
               ::"r"(dst), "l"(m), "r"(bar), "r"(c0), "r"(c1), "r"(bytes) : "memory");
}
__device__ __forceinline__ void tma_ld2_hint_w(uint32_t dst, const CUtensorMap* m, int c0, int c1, uint32_t bar, uint32_t bytes, uint64_t pol) {
  asm volatile(ELECT EXPECT("%2", "%6") "cp.async.bulk.tensor.2d.shared::cluster.global.mbarrier::complete_tx::bytes.L2::cache_hint"
               " [%0], [%1, {%3, %4}], [%2], %5;\n}"
               ::"r"(dst), "l"(m), "r"(bar), "r"(c0), "r"(c1), "l"(pol), "r"(bytes) : "memory");
}
__device__ __forceinline__ void tma_ld3_w(uint32_t dst, const CUtensorMap* m, int c0, int c1, int c2, uint32_t bar, uint32_t bytes) {
  asm volatile(ELECT EXPECT("%2", "%6") "cp.async.bulk.tensor.3d.shared::cluster.global.mbarrier::complete_tx::bytes [%0], [%1, {%3, %4, %5}], [%2];\n}"
               ::"r"(dst), "l"(m), "r"(bar), "r"(c0), "r"(c1), "r"(c2), "r"(bytes) : "memory");
}
__device__ __forceinline__ void tma_ld_kv_w(uint32_t dst, const CUtensorMap* m, int grp, uint32_t bar, uint64_t pol) {
  asm volatile(ELECT EXPECT("%2", "16384") "cp.async.bulk.tensor.4d.shared::cluster.global.mbarrier::complete_tx::bytes.L2::cache_hint"
               " [%0], [%1, {0, 0, 0, %3}], [%2], %4;\n}"
               ::"r"(dst), "l"(m), "r"(bar), "r"(grp), "l"(pol) : "memory");
}
__device__ __forceinline__ void tma_ld_wo_w(uint32_t dst, const CUtensorMap* m, int col, int grp, uint32_t bar) {
  asm volatile(ELECT EXPECT("%2", "16384") "cp.async.bulk.tensor.5d.shared::cluster.global.mbarrier::complete_tx::bytes [%0], [%1, {%3, 0, 0, 0, %4}], [%2];\n"
               "@p cp.async.bulk.tensor.5d.shared::cluster.global.mbarrier::complete_tx::bytes [%5], [%1, {%6, 0, 0, 0, %4}], [%2];\n}"
               ::"r"(dst), "l"(m), "r"(bar), "r"(col), "r"(grp), "r"(dst + 8192), "r"(col + 64) : "memory");
}
__device__ __forceinline__ void mbar_arrive8_w(uint32_t bar) {
  asm volatile(ELECT "mbarrier.arrive.shared::cta.b64 _, [%0], 8;\n}" ::"r"(bar) : "memory");
}
__device__ __forceinline__ uint32_t peer(uint32_t a) { uint32_t r; asm("mapa.shared::cluster.u32 %0, %1, %2;" : "=r"(r) : "r"(a), "r"(~blockIdx.x & 1)); return r; }
__device__ __forceinline__ void tma_ld2_both_w(uint32_t dst, const CUtensorMap* m, int c0, int c1, uint32_t bar, uint32_t bytes) {
  asm volatile(ELECT EXPECT("%2", "%5") "cp.async.bulk.tensor.2d.shared::cluster.global.mbarrier::complete_tx::bytes.multicast::cluster"
               " [%0], [%1, {%3, %4}], [%2], %6;\n}"
               ::"r"(dst), "l"(m), "r"(bar), "r"(c0), "r"(c1), "r"(bytes), "h"((uint16_t)3) : "memory");
}
__device__ __forceinline__ void tma_ld2_both_hint_w(uint32_t dst, const CUtensorMap* m, int c0, int c1, uint32_t bar, uint32_t bytes, uint64_t pol) {
  asm volatile(ELECT EXPECT("%2", "%6") "cp.async.bulk.tensor.2d.shared::cluster.global.mbarrier::complete_tx::bytes.multicast::cluster.L2::cache_hint"
               " [%0], [%1, {%3, %4}], [%2], %7, %5;\n}"
               ::"r"(dst), "l"(m), "r"(bar), "r"(c0), "r"(c1), "l"(pol), "r"(bytes), "h"((uint16_t)3) : "memory");
}
__device__ __forceinline__ void bulk_commit() { asm volatile("cp.async.bulk.commit_group;" ::: "memory"); }
template <int N> __device__ __forceinline__ void bulk_wait_read() { asm volatile("cp.async.bulk.wait_group.read %0;" ::"n"(N) : "memory"); }
__device__ __forceinline__ void wg_fence() { asm volatile("wgmma.fence.sync.aligned;" ::: "memory"); }
__device__ __forceinline__ void wg_commit() { asm volatile("wgmma.commit_group.sync.aligned;" ::: "memory"); }
template <int N> __device__ __forceinline__ void wg_wait() { asm volatile("wgmma.wait_group.sync.aligned %0;" ::"n"(N) : "memory"); }
__device__ __forceinline__ void fence_async_smem() { asm volatile("fence.proxy.async.shared::cta;" ::: "memory"); }
__device__ __forceinline__ void bar_sync(int id, int n) { asm volatile("bar.sync %0, %1;" ::"r"(id), "r"(n) : "memory"); }
__device__ __forceinline__ void touch(float& a) { asm volatile("neg.f32 %0, %0;" : "+f"(a)); }
__device__ __forceinline__ void touch(uint32_t& a) { asm volatile("not.b32 %0, %0;" : "+r"(a)); }
template <typename T, int N> __device__ __forceinline__ void touch(T (&a)[N]) {
#pragma unroll
  for (int i = 0; i < N; i++) touch(a[i]);
}
template <int ID, typename... A> __device__ __forceinline__ void sched_fence(uint32_t x, A&... a) {
  if (!((SF >> ID) & 1)) return;
  asm volatile("" : "+r"(x)::"memory");
#pragma unroll 1
  for (; __builtin_expect(x >= 100 + ID, 0); x >>= 1) { (touch(a), ...); __nanosleep(x); }
}
template <int N> __device__ __forceinline__ void reg_fence(float (&a)[N]) {
#pragma unroll
  for (int i = 0; i < N; i++) asm volatile("" : "+f"(a[i])::"memory");
}
template <int N> __device__ __forceinline__ void reg_fence(uint32_t (&a)[N]) {
#pragma unroll
  for (int i = 0; i < N; i++) asm volatile("" : "+r"(a[i])::"memory");
}
__device__ __forceinline__ float ex2(float x) { float y; asm("ex2.approx.ftz.f32 %0, %1;" : "=f"(y) : "f"(x)); return y; }
__device__ __forceinline__ uint32_t pack_bf16(float lo, float hi) {
  uint32_t r; asm("cvt.rn.bf16x2.f32 %0, %1, %2;" : "=r"(r) : "f"(hi), "f"(lo)); return r;
}
__device__ __forceinline__ void stsm4(uint32_t a, uint32_t r0, uint32_t r1, uint32_t r2, uint32_t r3) {
  asm volatile("stmatrix.sync.aligned.m8n8.x4.shared.b16 [%0], {%1, %2, %3, %4};" ::"r"(a), "r"(r0), "r"(r1), "r"(r2), "r"(r3) : "memory");
}
__device__ __forceinline__ void stsm4t(uint32_t a, uint32_t r0, uint32_t r1, uint32_t r2, uint32_t r3) {
  asm volatile("stmatrix.sync.aligned.m8n8.x4.trans.shared.b16 [%0], {%1, %2, %3, %4};" ::"r"(a), "r"(r0), "r"(r1), "r"(r2), "r"(r3) : "memory");
}
__device__ __forceinline__ void ldsm4(uint32_t a, uint32_t& r0, uint32_t& r1, uint32_t& r2, uint32_t& r3) {
  asm volatile("ldmatrix.sync.aligned.m8n8.x4.shared.b16 {%0, %1, %2, %3}, [%4];" : "=r"(r0), "=r"(r1), "=r"(r2), "=r"(r3) : "r"(a) : "memory");
}
__device__ __forceinline__ void sts16(uint32_t a, uint32_t v) { asm volatile("st.shared.u16 [%0], %1;" ::"r"(a), "h"((uint16_t)v) : "memory"); }
__device__ __forceinline__ void mma16816(float& c0, float& c1, float& c2, float& c3, uint32_t a0, uint32_t a1, uint32_t a2, uint32_t a3,
                                         uint32_t b0, uint32_t b1) {
  asm volatile("mma.sync.aligned.m16n8k16.row.col.f32.bf16.bf16.f32 {%0, %1, %2, %3}, {%4, %5, %6, %7}, {%8, %9}, {%0, %1, %2, %3};"
               : "+f"(c0), "+f"(c1), "+f"(c2), "+f"(c3) : "r"(a0), "r"(a1), "r"(a2), "r"(a3), "r"(b0), "r"(b1));
}
__device__ __forceinline__ uint32_t sdesc(uint32_t addr, uint32_t lbo) { return (addr >> 4) + ((lbo >> 4) << 16); }
__device__ __forceinline__ uint64_t desc64(uint32_t lo, uint32_t hi) { uint64_t d; asm("mov.b64 %0, {%1, %2};" : "=l"(d) : "r"(lo), "r"(hi)); return d; }
__device__ __forceinline__ void dadd(uint64_t& d, uint32_t inc) {
  asm("{\n.reg .b32 l, h;\nmov.b64 {l, h}, %0;\nadd.u32 l, l, %1;\nmov.b64 %0, {l, h};\n}" : "+l"(d) : "r"(inc));
}

struct Ring {
  uint32_t slot, phase, xp;
  __device__ __forceinline__ void uniform() {
    slot = __shfl_sync(0xffffffffu, slot, 0); phase = __shfl_sync(0xffffffffu, phase, 0); xp = __shfl_sync(0xffffffffu, xp, 0);
  }
  __device__ __forceinline__ void next() { if (++slot == NS) { slot = 0; phase ^= 1; } }
  __device__ __forceinline__ void next_if(bool p) { slot += p; if (slot == NS) { slot = 0; phase ^= 1; } }
};
__device__ __forceinline__ uint32_t borrow(int ks, int n) {
  const int k = ks + 1;
  return k >= 4 && !(k & 2) && k < n ? k & 1 : 2;
}

constexpr uint32_t Q_RANGES = NBETA * NH + __builtin_popcount(EARLY_MASK) * 5, Q_ALL = NBETA * (NH + 5);
constexpr int NRANGE = NCTA / 5;
struct Work { int kind, mode, k0, nsteps, range, beta, sub; };
struct Sched { uint16_t queue[Q_ALL]; uint32_t piece[NRANGE + 1][4]; };
constexpr Sched make_sched() {
  Sched s{};
  int q = 0, a = 0;
  for (int t = 0, e = 0; a < NBETA * NH; t++) {
    for (; e < NBETA && 8 * (e & ~PAIRB) + PK <= t && a >= P_POS; e++)
      for (int col = 0; col < 5 && (EARLY_MASK >> e & 1); col++) s.queue[q++] = 0x8000 | (e & 1 ? 4 - col : col) << 8 | e;
    for (int b = 0; b < NBETA; b++)
      for (int h = 0; h < NH; h++)
        if ((b >= B_LATE && h >= H_LATE ? 300 + b : 8 * (b & ~PAIRB) + KG * (h >> 2)) == t) { s.queue[q++] = b << 5 | h; a++; }
  }
  for (int b = 0; b < NBETA; b++)
    for (int col = 0; col < 5 && !(EARLY_MASK >> b & 1); col++) s.queue[q++] = 0x8000 | col << 8 | b;
  constexpr uint32_t T[NRANGE * 2] = {PIECE_TABLE};
  for (int g = 0; g <= NRANGE; g++)
    for (int n = 0; n < 4; n++) s.piece[g][n] = g < NRANGE && n < 2 ? T[2 * g + n] : 2u << 30;
  return s;
}
__constant__ Sched c_sched = make_sched();
constexpr int N_EARLY = __builtin_popcount(EARLY_MASK);
constexpr bool reuse_ok() {
  const Sched s = make_sched();
  int first[NBETA + OR] = {};
  for (int q = Q_RANGES - 1; q >= 0; q--) if (!(s.queue[q] & 0x8000)) first[s.queue[q] >> 5] = q;
  for (int q = 0; q < Q_RANGES; q++) if ((s.queue[q] & 0x8000) && (s.queue[q] & 31) >= OR0 && q - first[(s.queue[q] & 31) + OR] > NCTA - 32) return false;
  return first[OR0 + OR] >= NCTA && P_POS >= NCTA;
}
static_assert(reuse_ok());
template <bool SIMPLE> __device__ __forceinline__ bool o_reuse(uint32_t b) { return !SIMPLE && b - (OR0 + OR) < N_EARLY - OR0; }
template <bool SIMPLE> __device__ __forceinline__ uint32_t o_slot(uint32_t b) { return o_reuse<SIMPLE>(b) ? OR0 + (b - OR0) % OR : b; }
__device__ __forceinline__ Work decode(uint32_t d) {
  Work w;
  w.kind = d >> 30; if (w.kind == 3) w.kind = 1;
  w.mode = (d >> 28) & 3; w.k0 = (d >> 22) & 63;
  if (w.kind == 0) { w.beta = (d >> 5) & 31; w.sub = d & 31; w.nsteps = DM / 64; }
  else { w.beta = d & 31; w.sub = (d >> 8) & 7; w.nsteps = ((d >> 16) & 63) + 1; }
  w.range = ((d >> 11) & 31) * 5 + w.sub;
  return w;
}

__device__ __forceinline__ bool reached(const unsigned* cnt, unsigned target) {
  unsigned v;
  asm volatile("ld.acquire.gpu.global.u32 %0, [%1];" : "=r"(v) : "l"(cnt) : "memory");
  return (int)(v - target) >= 0;
}
__device__ __forceinline__ void wait_count(const unsigned* cnt, unsigned target) {
  unsigned n = 0;
  while (!__all_sync(0xffffffffu, reached(cnt, target))) { if (++n > (1u << 24)) __trap(); }
}
__device__ __forceinline__ uint32_t lds(uint32_t a) { uint32_t v; asm volatile("ld.volatile.shared.u32 %0, [%1];" : "=r"(v) : "r"(a) : "memory"); return v; }

#define TRACE(u, e)
#define T3(u, e)
#define T2C(u, e)
#define T2P(u, r, e)
#define TTAIL(k)
#define TCLK(k)
#define TO -1
#define TRACE_O(k) if (TO == k) TRACE(i, 5)
#define TRACE_P(u, e)
#define TRACE_IN(u, e)

struct Ctx {
  uint32_t sb;
  int wg, warp;
  uint32_t mqk, mpv;
  bool lead;
  int lane0, lane;
  int src;
};
template <int N> __device__ __forceinline__ uint32_t dhi(uint32_t lo) { return 0x40000040u + (lo >> (26 + N)); }
__device__ __forceinline__ void release(const Ctx& c, uint32_t slot) {
  if (c.lead) mbar_arrive(c.sb + BAR_EMPTY + slot * 8);
}
__device__ __forceinline__ uint32_t acquire(const Ctx& c, Ring& r, bool have = false) {
  const uint32_t s = r.slot;
  if (!have) mbar_wait_w(c.sb + BAR_FULL + s * 8, r.phase);
  r.next();
  return s;
}
__device__ __forceinline__ void mbar_wait2_w(uint32_t b0, uint32_t p0, uint32_t b1, uint32_t p1) {
  uint32_t n = 0;
  while (!__all_sync(0xffffffffu, mbar_try(b0, p0) & mbar_try(b1, p1))) {
    if (++n > (1u << 22)) __trap();
  }
}
__device__ __forceinline__ void mbar_wait3_w(uint32_t b0, uint32_t p0, uint32_t b1, uint32_t p1, uint32_t b2, uint32_t p2) {
  uint32_t n = 0;
  while (!__all_sync(0xffffffffu, mbar_try(b0, p0) & mbar_try(b1, p1) & mbar_try(b2, p2))) {
    if (++n > (1u << 22)) __trap();
  }
}
__device__ __forceinline__ void acquire2(const Ctx& c, Ring& r, uint32_t& s0, uint32_t& s1, bool have = false) {
  const uint32_t p0 = r.phase;
  s0 = r.slot; r.next(); s1 = r.slot;
  if (!have) mbar_wait2_w(c.sb + BAR_FULL + s0 * 8, p0, c.sb + BAR_FULL + s1 * 8, r.phase);
  r.next();
}
template <int N>
__device__ __forceinline__ bool peek(const Ctx& c, Ring r) {
  bool ok = true;
#pragma unroll
  for (int k = 0; k < N; k++) { ok &= mbar_test(c.sb + BAR_FULL + r.slot * 8, r.phase); r.next(); }
  return ok;
}
__device__ __forceinline__ void staged(const Ctx& c, int part) {
  fence_async_smem();
  __syncwarp();
  mbar_arrive_warp(c.sb + BAR_STG + c.wg * 16 + part * 8);
}

template <int WG, bool FIRST, int H>
__device__ __forceinline__ void proj_half(const Ctx& c, float (&acc)[64], uint32_t w, uint32_t x, uint32_t sw) {
  uint64_t dx = desc64((SB0 + x * SLOT + (WG ? 0 : H * 8192)) >> 4, dhi<0>(x) + sw);
  uint64_t dw = desc64(WG ? (SB0 + w * SLOT + H * 8192) >> 4 : sdesc(SB0 + w * SLOT, 8192), dhi<1>(x));
  wg_fence();
  if (WG) { if (FIRST) wgmma_proj96_init(acc, dw, dx, 0); else wgmma_proj96(acc, dw, dx, 1); }
  else { if (FIRST) wgmma_proj_init(acc, dx, dw, 0); else wgmma_proj(acc, dx, dw, 1); }
#pragma unroll
  for (int k = 1; k < 4; k++) {
    dadd(dx, k == 2 ? 2 + (sw >> 30) * 28 : 2); dadd(dw, 128);
    if (WG) wgmma_proj96(acc, dw, dx, 1); else wgmma_proj(acc, dx, dw, 1);
  }
  wg_commit();
}

__device__ __forceinline__ void proj_store16(uint32_t a, const float* f, float sc) {
  stsm4t(a, pack_bf16(f[0] * sc, f[1] * sc), pack_bf16(f[2] * sc, f[3] * sc), pack_bf16(f[4] * sc, f[5] * sc), pack_bf16(f[6] * sc, f[7] * sc));
}

__device__ __forceinline__ uint32_t stage_off(const Ctx& c) {
  const int lane = c.lane, mi = lane >> 3, r8 = lane & 7;
  return ((mi >> 1) * 8 + r8) * 128 + (((2 * c.warp + (mi & 1)) ^ r8) << 4);
}
__device__ __forceinline__ uint32_t q3_swz(uint32_t r8) { return ((r8 & 3) << 1) | (r8 >> 2); }
template <int H>
__device__ __forceinline__ void stage_t2(const Ctx& c, const float (&a)[64], float sc) {
  const uint32_t base = c.sb + QBUF_OFF + 2 * 16384 + H * 8192 + stage_off(c);
#pragma unroll
  for (int jj = 0; jj < 4; jj++) proj_store16(base + jj * 2048, &a[jj * 8], sc);
}
template <int H, bool IS_Q>
__device__ __forceinline__ void stage_t3(const Ctx& c, const float (&a)[64], float sc) {
  const uint32_t off = stage_off(c), r8 = (off >> 7) & 7;
  const uint32_t t3 = c.sb + QBUF_OFF + 3 * 16384 + H * 4096 + (IS_Q ? off ^ ((r8 ^ q3_swz(r8)) << 4) : off);
  proj_store16(t3, &a[32], sc);
  proj_store16(t3 + 2048, &a[40], sc);
}

template <int WG, int h>
__device__ __forceinline__ void load_part(const Ctx& c, Ring r, uint32_t (&q)[32]) {
  uint32_t n = 0;
  while (!h && !__all_sync(0xffffffffu, peek<4>(c, r))) {
    if (++n > (1u << 26)) __trap();
  }
  const int lane = c.lane, mi = lane >> 3, r8 = lane & 7;
  if (WG) { r.next(); r.next(); }
  const uint32_t off = c.sb + (WG ? stage_off(c) : (16 * c.warp + (mi & 1) * 8 + r8) * 128), t0 = off + r.slot * SLOT;
  r.next();
  const uint32_t t1 = off + r.slot * SLOT;
#pragma unroll
    for (int jj = 0; jj < (WG ? 6 : 8); jj++) {
      uint32_t* p = &q[4 * jj];
      if (WG) asm volatile("ldmatrix.sync.aligned.m8n8.x4.trans.shared.b16 {%0, %1, %2, %3}, [%4];" : "=r"(p[0]), "=r"(p[1]), "=r"(p[2]), "=r"(p[3])
                           : "r"((jj < 4 ? t0 + h * 8192 : t1 + h * 4096) + (jj & 3) * 2048) : "memory");
      else ldsm4((h ? t1 : t0) + (jj >> 2) * 8192 + (((((2 * jj) & 7) + (mi >> 1)) ^ r8) << 4), p[0], p[1], p[2], p[3]);
    }
}
template <int WG>
__device__ __forceinline__ void add_part(const Ctx& c, const uint32_t (&q)[32], float (&a)[64]) {
  const uint32_t one = (c.lane >> 3) == (c.lane & 3) ? 0x3f80u << (c.lane & 4) * 4 : 0;
#pragma unroll
  for (int i = 0; i < (WG ? 12 : 16); i++)
    asm("mma.sync.aligned.m16n8k8.row.col.f32.bf16.bf16.f32 {%0, %1, %2, %3}, {%4, %5}, {%6}, {%0, %1, %2, %3};"
        : "+f"(a[4 * i]), "+f"(a[4 * i + 1]), "+f"(a[4 * i + 2]), "+f"(a[4 * i + 3]) : "r"(q[2 * i]), "r"(q[2 * i + 1]), "r"(one));
}

__device__ __forceinline__ void trace_dump(const Ctx& c) {
}
struct RowSum { float l0, l1; };
__device__ __forceinline__ const char* o_addr(uint32_t item, int row, int lane) {
  return reinterpret_cast<const char*>(g_o) + (((item >> 10) * (2 * SQ) + row) * 128 + (lane ^ (lane >> 3)) * 16);
}
__device__ __forceinline__ void o_stg(const char* p, int i, const uint32_t* q) {
  asm volatile("st.global.v4.b32 [%0], {%1, %2, %3, %4};"
               ::"l"(p + (i >> 1) * (SQ * 128) + (i & 1) * 512), "r"(q[0]), "r"(q[1]), "r"(q[2]), "r"(q[3]) : "memory");
}
template <int MODE, int I0 = 0, int NI = 4>
__device__ __forceinline__ void o_emit(const char* p, const float (&o)[64], float inv) {
#pragma unroll
  for (int i = I0; i < I0 + NI; i++) {
    uint32_t q[4];
#pragma unroll
    for (int j = 0; j < 4; j++) q[j] = pack_bf16(o[16 * i + 4 * j + 2 * MODE] * inv, o[16 * i + 4 * j + 2 * MODE + 1] * inv);
    o_stg(p, i, q);
  }
}
__device__ __forceinline__ void o_done(const Ctx& c) {
  __syncwarp();
  mbar_arrive_warp(c.sb + BAR_OUT);
  __syncwarp();
}
template <int WG>
__device__ __forceinline__ void o_first(const Ctx& c, uint32_t item, float (&o)[64], const RowSum& inv, uint32_t (&q)[32]) {
  const char* p = o_addr(item, WG ? 192 + 8 * c.warp : 64 + 16 * c.warp, c.lane);
  reg_fence(o);
#pragma unroll
  for (int j = 0; j < 16; j++) {
    if (WG) q[j] = pack_bf16((o[4 * j] + o[4 * j + 2]) * inv.l0, (o[4 * j + 1] + o[4 * j + 3]) * inv.l0);
    else q[j] = pack_bf16(o[4 * j] * inv.l0, o[4 * j + 1] * inv.l0);
    if (!WG && (j & 3) == 3 && (j >> 2) < 8 - LATE0) o_stg(p, j >> 2, q + j - 3);
  }
#pragma unroll
  for (int j = 0; j < 16; j++) {
    if (!WG) q[16 + j] = pack_bf16(o[4 * j + 2] * inv.l1, o[4 * j + 3] * inv.l1);
    if ((j & 3) == 3 && (j >> 2) < 4 - (WG ? LATE1 : LATE0)) o_stg(WG ? p : p + 1024, j >> 2, q + (WG ? 0 : 16) + j - 3);
  }
}
template <int WG>
__device__ __forceinline__ void o_rest(const Ctx& c, uint32_t item, uint32_t (&q)[32]) {
  const char* p = o_addr(item, WG ? 192 + 8 * c.warp : 64 + 16 * c.warp, c.lane);
#pragma unroll
  for (int i = WG ? 4 - LATE1 : 8 - LATE0; i < (WG ? 4 : 8); i++) o_stg(p + (i >> 2) * 1024, i & 3, q + 4 * i);
}
template <int K0, int K1>
__device__ __forceinline__ void o_piece(const Ctx& c, const char* p, int k, const float (&o)[64], const RowSum& inv) {
  constexpr int NI = 8 / O_STEPS, M = K0 * NI / 4;
  if constexpr (K1 - K0 == 1) {
    o_emit<M, K0 * NI % 4, NI>(p + M * 1024, o, M ? inv.l1 : inv.l0);
    if (K1 == O_STEPS) o_done(c);
  } else {
    if (k <= (K0 + K1) / 2) o_piece<K0, (K0 + K1) / 2>(c, p, k, o, inv); else o_piece<(K0 + K1) / 2, K1>(c, p, k, o, inv);
  }
}
template <int WG>
__device__ __forceinline__ void o_second(const Ctx& c, uint32_t item, int k, float (&o)[64], const RowSum& inv) {
  reg_fence(o);
  o_piece<0, O_STEPS>(c, o_addr(item, 128 * WG + 16 * c.warp, c.lane0 + (k >> 8)), k, o, inv);
}
template <int WG>
__device__ __forceinline__ void release_q(const Ctx& c) {
#pragma unroll
  for (int t = 0; t < 2; t++)
    if (c.lead) asm volatile("mbarrier.arrive.shared::cta.b64 _, [%0], 2;" ::"r"(c.sb + BAR_EMPTY + (NS + 2 * WG + t) * 8) : "memory");
  __syncwarp();
}
struct Slots { uint32_t w, x, o, po; };
template <int WG>
__device__ __forceinline__ void acc_fence(float (&a)[64]) {
#pragma unroll
  for (int i = 0; i < (WG ? 48 : 64); i++) asm volatile("" : "+f"(a[i])::"memory");
}
template <int WG>
__device__ __forceinline__ void begin_acquire(const Ctx& c, Ring& r, Slots& h, bool wait) {
  const uint32_t s0 = r.slot, p0 = r.phase, f = c.sb + BAR_FULL;
  r.next();
  const uint32_t p1 = r.phase;
  h.w = r.slot; r.next();
  h.x = WG ? r.slot : s0; h.o = WG ? s0 : r.slot; h.po = r.phase;
  if (wait) { if (WG) mbar_wait3_w(f + s0 * 8, p0, f + h.w * 8, p1, f + h.x * 8, r.phase); else mbar_wait2_w(f + s0 * 8, p0, f + h.w * 8, p1); }
  r.next();
}
template <int WG>
__device__ __forceinline__ void proj_begin(const Ctx& c, Ring& r, float (&a0)[64], Slots& h, bool wait, uint32_t sw) {
  begin_acquire<WG>(c, r, h, wait);
  proj_half<WG, true, 0>(c, a0, h.w, h.x, sw);
  if (WG) release(c, h.o);
}
template <int WG>
__device__ __forceinline__ void proj_main(Ctx& c, Ring& r, float (&a0)[64], float (&a1)[64], Slots& h, int n, uint32_t sw, int unit,
                                          uint32_t item, int nq, float (&o1)[64], const RowSum& inv) {
  constexpr bool DEEP = (PDEPTH >> WG) & 1;
  T2C(unit, 3);
  int ks = 1;
#pragma unroll 1
  do {
    const Slots p = h;
    const uint32_t b = borrow(ks, n), tile = NS + (WG ? 3 - b : b), f = c.sb + BAR_FULL;
    const uint32_t s0 = b != 2 ? tile : r.slot, p0 = b != 2 ? (r.xp >> b) & 1 : r.phase;
    r.next_if(b == 2);
    const uint32_t p1 = r.phase;
    h.w = r.slot; r.next();
    const uint32_t s2 = b != 2 ? tile : r.slot;
    h.po = b != 2 ? p0 : r.phase;
    r.next_if(b == 2);
    r.xp ^= 1 << b;
    h.x = WG ? s2 : s0; h.o = WG ? s0 : s2;
    mbar_wait3_w(f + s0 * 8, p0, f + h.w * 8, p1, f + (WG ? s2 : p.o) * 8, WG ? h.po : p.po);
    if (ks < 10) T2C(unit, ks * 4);
    if (DEEP) {
      proj_half<WG, false, 0>(c, a0, h.w, h.x, sw);
      release(c, WG ? h.o : p.o);
      if (ks < 10) T2C(unit, ks * 4 + 1);
      wg_wait<1>();
      if (ks < 10) T2C(unit, ks * 4 + 2);
      release(c, p.x); release(c, p.w);
    } else {
      release(c, WG ? h.o : p.o);
      wg_wait<0>();
      release(c, p.x); release(c, p.w);
      if (ks < 10) T2C(unit, ks * 4 + 1);
      proj_half<WG, false, 0>(c, a0, h.w, h.x, sw);
      if (ks < 10) T2C(unit, ks * 4 + 2);
    }
    proj_half<WG, false, 1>(c, a1, h.w, h.x, sw);
    if (ks < 10) T2C(unit, ks * 4 + 3);
    if (ks <= nq) o_second<WG>(c, item, ks, o1, inv);
  } while (++ks != n);
  {
    const uint32_t e0 = c.sb + BAR_EMPTY + (NS + 3 * WG) * 8, e1 = c.sb + BAR_EMPTY + (NS + 1 + WG) * 8;
    const uint32_t p0 = (r.xp ^ unit ^ 1) & 1, p1 = ((r.xp >> 1) ^ unit ^ 1) & 1;
    const uint32_t k0 = sw ? e0 : c.sb + BAR_FULL + r.slot * 8, pk = sw ? p0 : r.phase;
    uint32_t cnt = 0;
    while (!__all_sync(0xffffffffu, mbar_try(e0, p0) & mbar_try(e1, p1) & mbar_try(k0, pk) & (WG || mbar_try(c.sb + BAR_FULL + h.o * 8, h.po)))) {
      if (++cnt > (1u << 22)) __trap();
    }
  }
  c.lane = c.lane0 + (h.w >> 5);
  if (!WG) release(c, h.o);
}
template <int WG>
__device__ __forceinline__ void proj_end(const Ctx& c, float (&a1)[64], const Slots& h) {
  wg_wait<0>();
  acc_fence<WG>(a1);
  release(c, h.x); release(c, h.w);
}
__device__ __forceinline__ uint32_t get_desc(const Ctx& c, int i) {
  uint32_t d;
  mbar_wait_w(c.sb + BAR_DESC, (i - 1) & 1);
  asm volatile("ld.volatile.shared.u32 %0, [%1];" : "=r"(d) : "r"(c.sb + DESC_OFF + (i & 3) * 4) : "memory");
  return __shfl_sync(0xffffffffu, d, 0);
}

__device__ __forceinline__ float quad_max(float x) {
  x = fmaxf(x, __shfl_xor_sync(0xffffffffu, x, 1));
  return fmaxf(x, __shfl_xor_sync(0xffffffffu, x, 2));
}
__device__ __forceinline__ float quad_sum(float x) {
  x += __shfl_xor_sync(0xffffffffu, x, 1);
  return x + __shfl_xor_sync(0xffffffffu, x, 2);
}
template <bool SP, bool FIRST>
__device__ __forceinline__ void exps(const Ctx& c, const float (&s)[32], uint32_t (&p)[SP ? 8 : 16], RowSum& st) {
  if constexpr (SP) {
    uint32_t q[8];
    float t;
#pragma unroll
    for (int j = 0; j < 8; j++) {
      const float e0 = ex2(s[4 * j] + s[4 * j + 2]), e1 = ex2(s[4 * j + 1] + s[4 * j + 3]);
      if (j == 0) t = e0 + e1; else t += e0 + e1;
      q[j] = pack_bf16(e0, e1);
    }
    const bool odd = c.src & 2;
#pragma unroll
    for (int g = 0; g < 4; g++) {
      p[2 * g] = __shfl_sync(0xffffffffu, odd ? q[2 * g + 1] : q[2 * g], c.src);
      p[2 * g + 1] = __shfl_sync(0xffffffffu, odd ? q[2 * g] : q[2 * g + 1], c.src ^ 1);
    }
    st.l0 = FIRST ? t : st.l0 + t;
  } else {
    float t0, t1;
#pragma unroll
    for (int j = 0; j < 8; j++) {
      const float e0 = ex2(s[4 * j]), e1 = ex2(s[4 * j + 1]), e2 = ex2(s[4 * j + 2]), e3 = ex2(s[4 * j + 3]);
      if (j == 0) { t0 = e0 + e1; t1 = e2 + e3; } else { t0 += e0 + e1; t1 += e2 + e3; }
      p[2 * j] = pack_bf16(e0, e1);
      p[2 * j + 1] = pack_bf16(e2, e3);
    }
    st.l0 = FIRST ? t0 : st.l0 + t0;
    st.l1 = FIRST ? t1 : st.l1 + t1;
  }
}
template <bool SP>
__device__ __forceinline__ bool finish_sums(RowSum& st) {
  const float a = quad_sum(st.l0), b = SP ? a : quad_sum(st.l1);
  st.l0 = __fdividef(1.f, a); st.l1 = __fdividef(1.f, b);
  return !(a >= SUM_LO && a <= SUM_HI && b >= SUM_LO && b <= SUM_HI);
}
template <bool SP, bool INIT, int SITE, bool COMMIT = true, int RM = 0>
__device__ __forceinline__ void issue_qk(const Ctx& c, float (&s)[32], const uint32_t (&qs)[32], uint32_t dq, uint32_t dk) {
  uint64_t a = desc64(dq, dhi<SITE & 1>(dk)), b = desc64(dk, dhi<1 - (SITE & 1)>(dk) + 64);
  if (SP) {
    if (INIT) wgmma_qk_sp_init(s, qs[0], qs[1], qs[2], qs[3], b, 0, c.mqk); else wgmma_qk_sp(s, qs[0], qs[1], qs[2], qs[3], b, 0, c.mqk);
#pragma unroll
    for (int k = 1; k < 4; k++) { dadd(b, k == 2 ? 60 : 4); wgmma_qk_sp(s, qs[4 * k], qs[4 * k + 1], qs[4 * k + 2], qs[4 * k + 3], b, 1, c.mqk); }
  } else {
    if (RM & 1) wgmma_qk_rs(s, qs[0], qs[1], qs[2], qs[3], b, 0); else if (INIT) wgmma_qk_init(s, a, b, 0); else wgmma_qk(s, a, b, 0);
#pragma unroll
    for (int k = 1; k < 8; k++) {
      dadd(a, k == 4 ? 506 : 2); dadd(b, k == 4 ? 58 : 2);
      if (RM >> k & 1) wgmma_qk_rs(s, qs[4 * k], qs[4 * k + 1], qs[4 * k + 2], qs[4 * k + 3], b, 1); else wgmma_qk(s, a, b, 1);
    }
  }
  if (COMMIT) wg_commit();
}
template <bool SP, bool ACC, int SITE, bool SPLIT = false>
__device__ __forceinline__ void issue_pv(const Ctx& c, float (&o)[64], const uint32_t (&p)[SP ? 8 : 16], uint32_t dv) {
  uint64_t b = desc64(dv, dhi<SITE & 1>(dv) + 64);
  if constexpr (SP) {
    if (ACC) wgmma_pv_sp(o, p[0], p[1], p[2], p[3], b, 1, c.mpv); else wgmma_pv_sp_init(o, p[0], p[1], p[2], p[3], b, 0, c.mpv);
    if (SPLIT) wg_commit();
    dadd(b, 512);
    wgmma_pv_sp(o, p[4], p[5], p[6], p[7], b, 1, c.mpv);
  } else {
    if (ACC) wgmma_pv(o, p[0], p[1], p[2], p[3], b, 1); else wgmma_pv_init(o, p[0], p[1], p[2], p[3], b, 0);
#pragma unroll
    for (int k = 1; k < 4; k++) { dadd(b, 256); wgmma_pv(o, p[4 * k], p[4 * k + 1], p[4 * k + 2], p[4 * k + 3], b, 1); }
  }
  wg_commit();
}
__device__ __forceinline__ void pack_rows(const float (&o)[64], float sc, uint32_t (&q)[32]) {
#pragma unroll
  for (int j = 0; j < 32; j++) q[j] = pack_bf16(o[2 * j] * sc, o[2 * j + 1] * sc);
}
template <int MASK = 255>
__device__ __forceinline__ void stage_rows(const Ctx& c, uint32_t tile_addr, const uint32_t (&q)[32]) {
  const int lane = c.lane, mi = lane >> 3, r8 = lane & 7;
  const uint32_t row_addr = tile_addr + (16 * c.warp + (mi & 1) * 8 + r8) * 128;
#pragma unroll
  for (int jj = 0; jj < 8; jj++)
    if (MASK >> jj & 1) stsm4(row_addr + (jj >> 2) * 8192 + (((((2 * jj) & 7) + (mi >> 1)) ^ r8) << 4), q[4 * jj], q[4 * jj + 1], q[4 * jj + 2], q[4 * jj + 3]);
}
__device__ __forceinline__ void stage_rows(const Ctx& c, uint32_t tile_addr, const float (&o)[64], float sc) {
  uint32_t q[32];
  pack_rows(o, sc, q);
  stage_rows(c, tile_addr, q);
}
template <int WG, int H>
__device__ __forceinline__ void stage_out(const Ctx& c, const float (&a)[64]) {
  if (WG) { stage_t3<H, false>(c, a, 1.f); if (H) staged(c, 0); stage_t2<H>(c, a, 1.f); }
  else stage_rows(c, c.sb + QBUF_OFF + H * 16384, a, 1.f);
  if (H || !WG) staged(c, H);
}
template <int SITE>
__device__ __forceinline__ void issue_qk_rs(float (&s)[32], uint32_t (&q)[32], uint32_t dk) {
  uint64_t b = desc64(dk, dhi<SITE>(dk) + 64);
  reg_fence(q);
  wg_fence();
  wgmma_qk_rs_init(s, q[0], q[1], q[2], q[3], b, 0);
#pragma unroll
  for (int k = 1; k < 8; k++) { dadd(b, k == 4 ? 58 : 2); wgmma_qk_rs(s, q[4 * k], q[4 * k + 1], q[4 * k + 2], q[4 * k + 3], b, 1); }
  wg_commit();
}

__device__ __forceinline__ void redo_tile(const Ctx& c, uint32_t q_addr, uint32_t half, const __nv_bfloat16* kp, const __nv_bfloat16* vp,
                                          uint32_t item, int row) {
  float o[64];
  const int lane = lane_now(), g = lane >> 2, cc = lane & 3, mi = lane >> 3, r8 = lane & 7;
  const uint32_t qa = q_addr + (half == 4096 ? 8 * c.warp + r8 : 16 * c.warp + (mi & 1) * 8 + r8) * 128, swz = half == 4096 ? q3_swz(r8) : r8;
  const uint32_t* kq = reinterpret_cast<const uint32_t*>(kp + g * DH) + cc;
  const unsigned short* vq = reinterpret_cast<const unsigned short*>(vp + 2 * cc * DH) + g;
  float m0 = -INFINITY, m1 = -INFINITY, l0 = 0.f, l1 = 0.f;
#pragma unroll
  for (int i = 0; i < 64; i++) o[i] = 0.f;
#pragma unroll 1
  for (int kb = 0; kb < SK / 16; kb++) {
    float z[8] = {0.f, 0.f, 0.f, 0.f, 0.f, 0.f, 0.f, 0.f};
#pragma unroll 2
    for (int kk = 0; kk < 8; kk++) {
      uint32_t a0, a1, a2, a3;
      ldsm4(qa + (kk >> 2) * half + ((((kk & 3) * 2 + (mi >> 1)) ^ swz) << 4), a0, a1, a2, a3);
      const uint32_t* kr = kq + kb * (16 * DH / 2) + kk * 8;
      mma16816(z[0], z[1], z[2], z[3], a0, a1, a2, a3, __ldg(kr), __ldg(kr + 4));
      mma16816(z[4], z[5], z[6], z[7], a0, a1, a2, a3, __ldg(kr + 8 * DH / 2), __ldg(kr + 8 * DH / 2 + 4));
    }
    const float n0 = fmaxf(m0, quad_max(fmaxf(fmaxf(z[0], z[1]), fmaxf(z[4], z[5]))));
    const float n1 = fmaxf(m1, quad_max(fmaxf(fmaxf(z[2], z[3]), fmaxf(z[6], z[7]))));
    const float al0 = ex2(m0 - n0), al1 = ex2(m1 - n1);
    m0 = n0; m1 = n1;
#pragma unroll
    for (int i = 0; i < 8; i++) z[i] = ex2(z[i] - ((i & 2) ? n1 : n0));
    l0 = l0 * al0 + (z[0] + z[1]) + (z[4] + z[5]);
    l1 = l1 * al1 + (z[2] + z[3]) + (z[6] + z[7]);
    const uint32_t a0 = pack_bf16(z[0], z[1]), a1 = pack_bf16(z[2], z[3]), a2 = pack_bf16(z[4], z[5]), a3 = pack_bf16(z[6], z[7]);
    const unsigned short* vr = vq + kb * (16 * DH);
#pragma unroll
    for (int nb = 0; nb < 16; nb++) {
      o[4 * nb] *= al0; o[4 * nb + 1] *= al0; o[4 * nb + 2] *= al1; o[4 * nb + 3] *= al1;
      const uint32_t b0 = __ldg(vr + nb * 8) | ((uint32_t)__ldg(vr + nb * 8 + DH) << 16);
      const uint32_t b1 = __ldg(vr + nb * 8 + 8 * DH) | ((uint32_t)__ldg(vr + nb * 8 + 9 * DH) << 16);
      mma16816(o[4 * nb], o[4 * nb + 1], o[4 * nb + 2], o[4 * nb + 3], a0, a1, a2, a3, b0, b1);
    }
  }
  const char* p = o_addr(item, row, lane);
  o_emit<0>(p, o, __fdividef(1.f, quad_sum(l0)));
  o_emit<1>(half == 4096 ? p : p + 1024, o, __fdividef(1.f, quad_sum(l1)));
}

template <bool SPA, bool SPB, int SITE, int ID>
__device__ __forceinline__ void batch(const Ctx& c, float (&s)[32], const uint32_t (&qs)[32], uint32_t dq, uint32_t dk, float (&ob)[64],
                                      uint32_t (&pb)[SPB ? 8 : 16], uint32_t dv) {
  if constexpr (SPA) {
    reg_fence(pb);
    wg_fence();
    issue_pv<SPB, true, ID>(c, ob, pb, dv);
    issue_qk<SPA, false, ID>(c, s, qs, dq, dk);
  } else {
    constexpr bool EARLY = ((QK_EARLY_MASK >> (SITE + (SPB ? 2 : 0))) & 1) != 0;
    if (!EARLY) reg_fence(pb);
    wg_fence();
    issue_qk<SPA, false, ID, !SPB, SITE ? RM0 : SPB ? RM2 : RM1>(c, s, qs, dq, dk);
    if (EARLY) { reg_fence(pb); wg_fence(); }
    issue_pv<SPB, true, ID, SPB>(c, ob, pb, dv);
  }
}

template <bool SP0>
__device__ __forceinline__ bool attention(Ctx& c, Ring& r, int unit, uint32_t& d, const float (&a0)[64], float (&o0)[64], float (&o1)[64],
                                          RowSum& st0, RowSum& st1, const Slots& h, uint32_t (&q1)[32]) {
  constexpr bool SP1 = false;
  if (SP0) { c.mqk = META_QK + (d >> 28); c.mpv = META_PV + (d >> 28); asm volatile("" : "+r"(c.mqk), "+r"(c.mpv)); }
  if (SP0) c.src = (c.lane & 28) | ((c.lane & 1) << 1) | ((c.lane >> 1) & 1);
  float s[32];
  uint32_t p0[SP0 ? 8 : 16], p1[16];
  const uint32_t q0a = c.sb + QBUF_OFF + (SP0 ? 3 : 0) * 16384, q1a = c.sb + QBUF_OFF + (SP0 ? 2 : 1) * 16384;
  const uint32_t dq0 = sdesc(SB0 + QBUF_OFF, 0), dq1 = sdesc(SB0 + QBUF_OFF + (SP0 ? 2 : 1) * 16384, 0);
  uint32_t sk = acquire(c, r, true), sv, sn;
  uint32_t qs[32];
  float s1[32];
  if (SP0) {
    stage_t3<0, true>(c, a0, SM_C);
    stage_t2<0>(c, a0, SM_C);
    proj_end<1>(c, o0, h);
    stage_t3<1, true>(c, o0, SM_C);
    stage_t2<1>(c, o0, SM_C);
    bar_sync(5, 128);
    const int g = c.lane >> 2, cc = c.lane & 3;
    const uint32_t qa = q0a + (8 * c.warp + g) * 128 + (cc & 1) * 8;
#pragma unroll
    for (int k = 0; k < 8; k++)
      asm volatile("ld.shared.v2.u32 {%0, %1}, [%2];" : "=r"(qs[2 * k]), "=r"(qs[2 * k + 1])
                   : "r"(qa + (k >> 2) * 4096 + ((((k & 3) * 2 + (cc >> 1)) ^ q3_swz(g)) << 4)) : "memory");
    fence_async_smem();
    bar_sync(1, 256);
    TRACE(unit, 2);
    wg_fence();
    issue_qk<SP1, true, 1>(c, s1, qs, dq1, sdesc(SB0 + sk * SLOT, 0));
#pragma unroll
    for (int k = 0; k < 8; k++)
      if (RM2 >> k & 1) ldsm4(q1a + (k >> 2) * 8192 + (16 * c.warp + (c.lane & 15)) * 128 + (((2 * (k & 3) + (c.lane >> 4)) ^ (c.lane & 7)) << 4),
                              q1[4 * k], q1[4 * k + 1], q1[4 * k + 2], q1[4 * k + 3]);
#pragma unroll
    for (int k = 0; k < 16; k++) asm volatile("" : "+r"(qs[k])::"memory");
    wg_fence();
    issue_qk<SP0, true, 0>(c, s, qs, dq0, sdesc(SB0 + sk * SLOT, 0));
    const bool have = peek<2>(c, r);
    wg_wait<1>();
    reg_fence(s1);
    exps<SP1, true>(c, s1, p1, st1);
    sched_fence<11>(sk, p1);
    acquire2(c, r, sv, sn, __all_sync(0xffffffffu, have));
    wg_wait<0>();
    wg_fence();
    issue_pv<SP1, false, 1>(c, o1, p1, sdesc(SB0 + sv * SLOT, 1024));
    if (LAG_BAR & 1) asm volatile("bar.arrive 4, 256;" ::: "memory");
    sched_fence<12>(sk, s);
    release(c, sk);
    sk = sn;
    exps<SP0, true>(c, s, p0, st0);
    reg_fence(p0);
    wg_fence();
    issue_pv<SP0, false, 0>(c, o0, p0, sdesc(SB0 + sv * SLOT, 1024));
    issue_qk<SP0, true, 2>(c, s, qs, dq0, sdesc(SB0 + sk * SLOT, 0));
    sn = acquire(c, r);
    wg_wait<0>();
    reg_fence(s);
  } else {
    pack_rows(a0, SM_C, qs);
    stage_rows(c, q0a, qs);
    proj_end<0>(c, o1, h);
    TRACE(unit, 2);
    float sc = SM_C;
    issue_qk_rs<0>(s, qs, sdesc(SB0 + sk * SLOT, 0));
    sched_fence<0>(sk, sc);
    pack_rows(o1, sc, q1);
    stage_rows<~RM1>(c, q1a, q1);
    issue_qk_rs<1>(s1, q1, sdesc(SB0 + sk * SLOT, 0));
    asm volatile("bar.arrive 1, 256;" ::: "memory");
    bool have = peek<2>(c, r);
    wg_wait<1>();
    reg_fence(s);
    exps<SP0, true>(c, s, p0, st0);
    sched_fence<1>(sk, p0);
    acquire2(c, r, sv, sn, __all_sync(0xffffffffu, have));
    wg_wait<0>();
    reg_fence(s1);
    fence_async_smem();
    __syncwarp();
    wg_fence();
    issue_qk<SP0, false, 2, true, RM0>(c, s, qs, dq0, sdesc(SB0 + sn * SLOT, 0));
    issue_pv<SP0, false, 0>(c, o0, p0, sdesc(SB0 + sv * SLOT, 1024));
    sched_fence<2>(sk, s1);
    release(c, sk);
    have = peek<1>(c, r);
    sk = sn;
    exps<SP1, true>(c, s1, p1, st1);
    reg_fence(p1);
    wg_fence();
    issue_pv<SP1, false, 1>(c, o1, p1, sdesc(SB0 + sv * SLOT, 1024));
    sn = acquire(c, r, __all_sync(0xffffffffu, have));
    if (LAG_BAR & 1) bar_sync(4, 256);
    wg_wait<1>();
    reg_fence(s);
  }
  TRACE_IN(unit, 4);
  T2C(unit, 51);
#pragma unroll 1
  for (int j = 1; j < 15; j++) {
    const uint32_t sv_prev = sv, sk_prev = sk;
    sv = sn;
    const uint32_t dv = sdesc(SB0 + sv * SLOT, 1024);
    reg_fence(p0);
    exps<SP0, false>(c, s, p0, st0);
    batch<SP1, SP0, 0, 3>(c, s, q1, dq1, sdesc(SB0 + sk * SLOT, 0), o0, p0, dv);
    sk = acquire(c, r);
    wg_wait<1>();
    reg_fence(s); reg_fence(p1);
    release(c, sv_prev); release(c, sk_prev);
    exps<SP1, false>(c, s, p1, st1);
    batch<SP0, SP1, 1, 4>(c, s, qs, dq0, sdesc(SB0 + sk * SLOT, 0), o1, p1, dv);
    sn = acquire(c, r);
    if (SP0) wg_wait<0>(); else wg_wait<1>();
    reg_fence(s);
  }
  TRACE_IN(unit, 5);
  T2C(unit + 1, 52);
  const uint32_t sv_prev = sv;
  sv = sn;
  const uint32_t dv = sdesc(SB0 + sv * SLOT, 1024);
  reg_fence(p0);
  exps<SP0, false>(c, s, p0, st0);
  batch<SP1, SP0, 0, 5>(c, s, q1, dq1, sdesc(SB0 + sk * SLOT, 0), o0, p0, dv);
  asm volatile("ld.volatile.shared.u32 %0, [%1];" : "=r"(d) : "r"(c.sb + DESC_OFF + ((unit + 1) & 3) * 4) : "memory");
  const bool have = peek<2 + SP0>(c, r);
  wg_wait<1>();
  reg_fence(s); reg_fence(p1);
  release(c, sv_prev); release(c, sk);
  exps<SP1, false>(c, s, p1, st1);
  reg_fence(p1);
  wg_fence();
  issue_pv<SP1, true, 2>(c, o1, p1, dv);
  if (SP0) sched_fence<6>(sk, st0.l0, st1.l0, st1.l1); else sched_fence<5>(sk, st0.l0, st0.l1, st1.l0, st1.l1);
  c.lane = c.lane0 + (sk >> 5);
  const bool bad = finish_sums<SP0>(st0) | finish_sums<SP1>(st1);
  uint32_t any;
  asm volatile("{\n.reg .pred p, q;\nsetp.ne.u32 p, %1, 0;\nbar.red.or.pred q, %2, 128, p;\nselp.u32 %0, 1, 0, q;\n}"
               : "=r"(any) : "r"((uint32_t)bad), "n"(2 + SP0) : "memory");
  any = __any_sync(0xffffffffu, any);
  d = __shfl_sync(0xffffffffu, d, 0);
  if (d < (2u << 30) && !__all_sync(0xffffffffu, have)) { Ring t = r; Slots u; begin_acquire<SP0>(c, t, u, true); }
  wg_wait<0>();
  reg_fence(o0); reg_fence(o1);
  release(c, sv);
  return any;
}

template <int WG>
__device__ __forceinline__ void consumer(Ctx c, const __nv_bfloat16* const* kv) {
  asm volatile("setmaxnreg.inc.sync.aligned.u32 %0;" ::"n"(WG ? REG_C : 504 - REG_C - REG_P));
  c.wg = WG;
  Ring r{0, 0, 0};
  float a0[64], a1[64], o1[64];
  Slots h;
  RowSum inv0, inv1;
  uint32_t oq[32];
  uint32_t d = c_sched.queue[blockIdx.x] * 1025, dc = 0, sw;
  int i = 0, nq;
begin:
  sw = d & (1u << 30);
  proj_begin<WG>(c, r, a0, h, true, sw);
  proj_half<WG, true, 1>(c, a1, h.w, h.x, sw);
  nq = 0;
#pragma unroll
  for (int k = 0; k < 64; k++) asm volatile("" : "=f"(o1[k]));
  asm volatile("" : "=f"(inv1.l0), "=f"(inv1.l1));
  while (true) {
    TRACE(i, 0); TRACE(i, 6);
    proj_main<WG>(c, r, a0, a1, h, d >> 30 ? ((d >> 16) & 63) + 1 : DM / 64, sw, i, dc, nq, o1, inv1);
    dc = d;
    TRACE(i, 1);
    if (d >> 30) goto out_tile;
    wg_wait<1>();
    acc_fence<WG>(a0);
    if (WG ? attention<WG>(c, r, i, d, a0, a1, o1, inv0, inv1, h, oq) : attention<WG>(c, r, i, d, a0, o1, a1, inv1, inv0, h, oq)) goto redo;
    if (d >= (2u << 30)) break;
    sw = d & (1u << 30);
    proj_begin<WG>(c, r, a0, h, false, sw);
    release_q<WG>(c);
    if (WG) sched_fence<8>(h.w, inv0.l0); else sched_fence<7>(h.w, inv0.l0, inv0.l1);
    o_first<WG>(c, dc, a1, inv0, oq);
    sched_fence<9>(h.w, inv1.l0);
    proj_half<WG, true, 1>(c, a1, h.w, h.x, sw);
    o_rest<WG>(c, dc, oq);
    nq = O_STEPS;
    TRACE(i, 3); TRACE(i, 7);
    i++;
  }
  release_q<WG>(c);
  o_first<WG>(c, dc, a1, inv0, oq);
  o_rest<WG>(c, dc, oq);
#pragma unroll
  for (int k = 1; k <= O_STEPS; k++) o_second<WG>(c, dc, k, o1, inv1);
next:
  TRACE(i, 3); TRACE(i, 7);
  if ((d >> 30) != 2) {
    i++;
    r.uniform();
    goto begin;
  }
  trace_dump(c);
  return;
out_tile:
  if (d & 96) goto finish;
  d = get_desc(c, i + 1);
  wg_wait<1>();
  acc_fence<WG>(a0);
  TRACE_O(0);
  stage_out<WG, 0>(c, a0);
  TRACE_O(1);
  proj_end<WG>(c, a1, h);
  TRACE_O(2);
  stage_out<WG, 1>(c, a1);
  TRACE(i, 2);
  goto next;
finish:
  {
    uint32_t q[32];
#pragma unroll 1
    for (int k = (d >> 5) & 3; k > 1; k--) {
      wg_wait<0>();
      acc_fence<WG>(a0); acc_fence<WG>(a1);
      if (k == ((d >> 5) & 3)) { release(c, h.x); release(c, h.w); }
      load_part<WG, 0>(c, r, q); add_part<WG>(c, q, a0);
      load_part<WG, 1>(c, r, q); add_part<WG>(c, q, a1);
#pragma unroll
      for (int t = 0; t < 4; t++) { release(c, r.slot); r.next(); }
    }
    load_part<WG, 0>(c, r, q);
    wg_wait<1>();
    acc_fence<WG>(a0);
    TRACE_O(0);
    add_part<WG>(c, q, a0);
    stage_out<WG, 0>(c, a0);
    TRACE_O(1);
    load_part<WG, 1>(c, r, q);
    wg_wait<0>();
    acc_fence<WG>(a1);
    TRACE_O(2);
    add_part<WG>(c, q, a1);
    stage_out<WG, 1>(c, a1);
    TRACE(i, 2); TRACE(i, 3); TRACE(i, 7);
    trace_dump(c);
    return;
  }
redo:
  {
    if (!WG) { stage_rows<RM1>(c, c.sb + QBUF_OFF + 16384, oq); __syncwarp(); }
    const size_t hoff = (size_t)(dc & 511) * (SK * DH);
    const int br = (dc >> 9) & 1;
#pragma unroll 1
    for (int part = 0; part < 2; part++) {
      const int t = WG ? 3 - part : part;
      redo_tile(c, c.sb + QBUF_OFF + t * 16384, t == 3 ? 4096 : 8192, kv[br] + hoff, kv[2 + br] + hoff, dc,
                t * 64 + (t == 3 ? 8 : 16) * c.warp);
    }
    o_done(c);
    release_q<WG>(c);
  }
  goto next;
}

template <bool SIMPLE>
__global__ void __launch_bounds__(384, 1) mha_fused_kernel(const __grid_constant__ Params P) {
  extern __shared__ __align__(1024) uint8_t smem_raw[];
  const uint32_t sbase = smem_u32(smem_raw);
  const int tid = threadIdx.x;
  const int wg = __shfl_sync(0xffffffffu, tid >> 7, 0);
  const int warp = __shfl_sync(0xffffffffu, (tid >> 5) & 3, 0);
  const int lane = tid & 31;
  const int cta = blockIdx.x;
  constexpr bool PAIR = !SIMPLE;

  if (tid == 0) T3(15, 0);
  if ((sbase & 0xffffff) != SB0) __trap();
  {
    const int wi = wg * 4 + warp;
    asm volatile(ELECT "prefetch.tensormap [%0];\n}" ::"l"(&P.x[0][0] + wi) : "memory");
#pragma unroll
    for (int k = 0; k < 5; k++) {
      const int b = min(BAR_OFF + (wi * 5 + k) * 8, DESC_OFF - 8);
      asm volatile(ELECT "mbarrier.init.shared::cta.b64 [%0], %1;\n}"
                   ::"r"(sbase + b), "r"(b < BAR_EMPTY || b >= BAR_DESC ? 1 : b >= BAR_STG && b < BAR_OUT ? 4 : 8) : "memory");
    }
    asm volatile("fence.mbarrier_init.release.cluster;" ::: "memory");
    if (wi < 6) asm volatile(ELECT "prefetch.tensormap [%0];\n}" ::"l"(&P.x[0][0] + 12 + wi) : "memory");
  }
  if (PAIR) asm volatile("barrier.cluster.arrive.aligned;\nbarrier.cluster.wait.aligned;" ::: "memory"); else __syncthreads();

  if (wg == 2) {
    asm volatile("setmaxnreg.dec.sync.aligned.u32 %0;" ::"n"(REG_P));
    if (warp == 1) {
      const uint32_t qb = sbase + QBUF_OFF;
      const uint32_t ep = __shfl_sync(0xffffffffu, *(volatile unsigned*)&g_epoch + 1, 0);
      asm volatile("st.volatile.shared.u32 [%0], %1;" ::"r"(sbase + EPOCH_OFF), "r"(ep) : "memory");
      uint32_t dc = c_sched.queue[cta], qi = 0, piece = 0, na = 0;
      TTAIL(0);
      for (int i = 0; (dc >> 30) != 2; i++) {
        if (!(dc >> 30) && o_reuse<SIMPLE>((dc >> 5) & 31)) {
          const unsigned* rd = &g_rd[0][0] + ((dc & 1023) >> 2) - OR * 8;
          for (uint32_t n = 0; !__all_sync(0xffffffffu, reached(rd, ep * 5)); __nanosleep(300)) if (++n > (1u << 22)) __trap();
        }
        mbar_wait_w(sbase + BAR_GO, i & 1);
        if (piece == 0) {
          if (PAIR && (cta & 1)) {
            asm volatile(ELECT EXPECT("%0", "4") "mbarrier.arrive.shared::cluster.b64 _, [%1];\n}" ::"r"(sbase + BAR_MAIL), "r"(peer(sbase + BAR_MAIL)) : "memory");
            mbar_wait_w(sbase + BAR_MAIL, i & 1);
            qi = lds(sbase + EPOCH_OFF + 8);
          } else if (lane == 0) {
            qi = atomicAdd(&g_next, PAIR ? 2 : 1);
            if (qi == (SIMPLE ? Q_ALL : Q_RANGES) - (PAIR ? 2 : 1)) { g_next = 0; g_epoch = ep; }
          }
          qi = __shfl_sync(0xffffffffu, qi, 0);
          if (PAIR && !(cta & 1)) {
            mbar_wait_w(sbase + BAR_MAIL, i & 1);
            asm volatile(ELECT "st.async.shared::cluster.mbarrier::complete_tx::bytes.u32 [%0], %1, [%2];\n}"
                         ::"r"(peer(sbase + EPOCH_OFF + 8)), "r"(qi + 1), "r"(peer(sbase + BAR_MAIL)) : "memory");
          }
          qi += SIMPLE ? gridDim.x : NCTA;
        }
        uint32_t d;
        if (qi < (SIMPLE ? Q_ALL : Q_RANGES)) { d = c_sched.queue[qi]; if (d & 0x8000) d ^= (1u << 30) | (63u << 16) | 0x8000; else d |= o_slot<SIMPLE>(d >> 5) << 15 | (d & 31) << 10; }
        else if (SIMPLE) d = 2u << 30;
        else { const uint32_t e = qi - Q_RANGES, g = e / 5; d = c_sched.piece[g][piece++] | (g & 1 ? g * 5 + 4 - e : e - g * 5) << 8; }
        if ((d >> 30) == 1) {
          const uint32_t k0 = (d >> 22) & 63;
          const uint32_t run = __ffs(__ballot_sync(0xffffffffu, !reached(&g_cnt[d & 31][lane & 7], ep * 4)) & (0xffu << (k0 >> 3))) - 1;
          if (run <= (k0 + ((d >> 16) & 63)) >> 3) d |= run <= (k0 + O_STEPS) >> 3 ? (2u << 30) | 128 : 128;
        }
        asm volatile("st.volatile.shared.u32 [%0], %1;" ::"r"(sbase + EPOCH_OFF + 4), "r"(qi) : "memory");
        asm volatile("st.volatile.shared.u32 [%0], %1;" ::"r"(sbase + DESC_OFF + ((i + 1) & 3) * 4), "r"(d) : "memory");
        __syncwarp();
        mbar_arrive_warp(sbase + BAR_DESC);
        const Work w = decode(dc);
        dc = d;
        if (w.kind == 0) {
          mbar_wait_w(sbase + BAR_OUT, na++ & 1);
          TTAIL(1);
          T3(i, 0); T3(i, 1);
          asm volatile(ELECT "red.release.gpu.global.add.u32 [%0], 1;\n}" ::"l"(&g_cnt[w.beta][w.sub >> 2]) : "memory");
          T3(i, 2);
          TTAIL(2);
          continue;
        }
        const bool fin = w.mode != 1;
        const CUtensorMap* m = fin ? P.out_st : P.o_st;
        const int c1 = fin ? (w.beta & 15) * SQ : 0;
        const int c2 = fin ? (w.beta >> 4) * (DM / 64) + w.sub * 2 : NBETA * 64 + w.range * 2;
        uint32_t pend = 0;
#pragma unroll 1
        for (int e = 0; e < 4; e++) {
          const int t = (ST_ORDER >> (4 * e)) & 3;
          mbar_wait_w(sbase + BAR_STG + (t ^ (t >> 1)) * 8, (i - na) & 1);
          tma_st3_w(m + (t == 3), qb + t * 16384, c1 + t * 64, c2);
          bulk_commit();
          T2P(i + 1, 5, 2 * e);
          if (pend) {
            bulk_wait_read<1>();
            mbar_arrive8_w(pend);
            T2P(i + 1, 5, 2 * e - 1);
          }
          pend = sbase + BAR_EMPTY + (NS + t) * 8;
          if ((ST_NOW >> e) & 1) {
            bulk_wait_read<0>();
            mbar_arrive8_w(pend);
            pend = 0;
            T2P(i + 1, 5, 2 * e + 1);
          }
        }
        if (w.beta < N_EARLY) asm volatile(ELECT "red.relaxed.gpu.global.add.u32 [%0], 1;\n}" ::"l"(&g_rd[w.beta][7]) : "memory");
        T3(i, 0);
        if (piece >= 2) TTAIL(piece * 2 - 1);
        asm volatile("cp.async.bulk.wait_group 0;" ::: "memory");
        T3(i, 1);
        if (w.mode == 1) asm volatile(ELECT "st.release.gpu.global.u32 [%0], %1;\n}" ::"l"(&g_flag[w.range]), "r"(ep) : "memory");
        T3(i, 2);
        if (piece >= 2) TTAIL(piece * 2);
      }
      T3(15, 1);
    } else
    if (warp == 0) {
      Ring r{0, 1, 3};
      uint32_t d = c_sched.queue[cta];
      for (int i = 0;; i++) {
        const Work w = decode(d);
        if (w.kind == 2) break;
        const CUtensorMap* m = w.kind == 0 ? &P.wq[w.beta >> 4] : &P.wo[w.beta >> 4];
        for (int ks = 0; ks < w.nsteps; ks++) {
          const uint32_t b = borrow(ks, w.nsteps);
          r.next_if(b == 2);
          const uint32_t bar = sbase + BAR_FULL + r.slot * 8;
          mbar_wait_w(bar + (BAR_EMPTY - BAR_FULL), r.phase);
          if (w.kind == 0) tma_ld3_w(sbase + r.slot * SLOT, m, 0, ks * 64, w.sub * 2, bar, 16384);
          else tma_ld_wo_w(sbase + r.slot * SLOT, m, w.sub * 128, (w.k0 + ks) * 2, bar);
          if (w.kind != 0 && w.beta < N_EARLY && (ks & 7) == 5 && ks > 5)
            asm volatile(ELECT "red.relaxed.gpu.global.add.u32 [%0], 1;\n}" ::"l"(&g_rd[w.beta][(ks >> 3) - 1]) : "memory");
          if (ks < 10) T2P(i, 2, ks);
          if (w.kind != 0 && ks == max(w.nsteps - GO_P, 4)) mbar_arrive_warp(sbase + BAR_GO);
          r.next(); r.next_if(b == 2);
        }
        if (w.kind == 0) {
          r.phase ^= 1; r.next(); r.next();
        } else if (w.mode == 2) {
          for (int k = 1; k <= ((d >> 5) & 3); k++) {
            if (k == 1) TTAIL(9);
            wait_count(&g_flag[w.range + 5 * k], lds(sbase + EPOCH_OFF));
            TTAIL(10);
            asm volatile("fence.proxy.async.global;" ::: "memory");
#pragma unroll 1
            for (int t = 0; t < 4; t++) {
              mbar_wait_w(sbase + BAR_EMPTY + r.slot * 8, r.phase);
              tma_ld3_w(sbase + r.slot * SLOT, &P.o_st[t == 3], 0, t * 64, NBETA * 64 + (w.range + 5 * k) * 2, sbase + BAR_FULL + r.slot * 8,
                        t == 3 ? 8192 : 16384);
              r.next();
            }
          }
        }
        mbar_wait_w(sbase + BAR_DESC, i & 1);
        d = __shfl_sync(0xffffffffu, lds(sbase + DESC_OFF + ((i + 1) & 3) * 4), 0);
      }
    } else {
      const int hi = warp - 2;
      uint64_t pol_stream;
      uint32_t rdy = 0;
      asm volatile("createpolicy.fractional.L2::evict_first.b64 %0, 1.0;" : "=l"(pol_stream));
      Ring r{0, 1, 3};
      uint32_t d = c_sched.queue[cta];
      for (int i = 0;; i++) {
        const Work w = decode(d);
        if (w.kind == 2) break;
        const CUtensorMap* m = w.kind == 0 ? &P.x[hi][w.beta >> 4] : &P.o_ld[hi];
        int c1 = (w.kind == 0 ? (w.beta & 15) : o_slot<SIMPLE>(w.beta) * 64 + w.k0) * SQ + hi * 128;
        int k_wait = -1;
        const bool both = PAIR && (w.kind == 0 || w.sub != 4), mine = !both || hi == (cta & 1);
        if (w.kind != 0 && mine) {
          if (d & 128) k_wait = d >= (3u << 30) ? 0 : 8 - (w.k0 & 7);
          asm volatile("fence.proxy.async.global;" ::: "memory");
        }
        const int rank = i == 0 ? cta : __shfl_sync(0xffffffffu, lds(sbase + EPOCH_OFF + 4), 0) - NCTA;
        for (int ks = 0; ks < w.nsteps; ks++) {
          if (ks == k_wait) {
            wait_count(&g_cnt[d & 31][(w.k0 + ks) >> 3], lds(sbase + EPOCH_OFF) * 4);
            asm volatile("fence.proxy.async.global;" ::: "memory");
            k_wait = ((w.k0 + ks) | 7) + 1 - w.k0;
          }
          const uint32_t b = borrow(ks, w.nsteps);
          const bool bo = b != 2;
          r.next_if(hi && !bo); r.next_if(hi && !bo);
          const uint32_t sl = bo ? NS + (b ^ (3 * hi)) : r.slot, bar = sbase + BAR_FULL + sl * 8;
          mbar_wait_w(bar + (BAR_EMPTY - BAR_FULL), bo ? (r.xp >> b) & 1 : r.phase);
          const uint32_t bytes = hi ? 96 * 128 : 128 * 128;
          if (!mine) {
            asm volatile(ELECT EXPECT("%0", "%2") "mbarrier.arrive.shared::cluster.b64 _, [%1];\n}"
                         ::"r"(bar), "r"(peer(bar + (BAR_RDY - BAR_FULL))), "r"(bytes) : "memory");
          } else if (both) {
            mbar_wait_w(bar + (BAR_RDY - BAR_FULL), (rdy >> sl) & 1);
            rdy ^= 1 << sl;
            if (w.kind == 0) tma_ld2_both_w(sbase + sl * SLOT, m, ks * 64, c1, bar, bytes);
            else tma_ld2_both_hint_w(sbase + sl * SLOT, m, 0, c1, bar, bytes, pol_stream);
          } else if (!PAIR && w.kind == 0) tma_ld2_w(sbase + sl * SLOT, m, ks * 64, c1, bar, bytes);
          else tma_ld2_hint_w(sbase + sl * SLOT, m, 0, c1, bar, bytes, pol_stream);
          if (w.kind != 0) c1 += SQ;
          if (i == 0 && ks == PF_STEP)
            asm volatile(ELECT "cp.async.bulk.prefetch.tensor.4d.L2.global.L2::cache_hint [%0, {0, 0, 0, %1}], %2;\n}"
                         ::"l"(&P.kv[hi][0]), "r"(d * (SK / 8)), "l"(pol_stream) : "memory");
          if (ks < 10) T2P(i, 3 + hi, ks);
          if (!hi && w.kind != 0 && !(ks & 3)) TCLK(i * 16 + (ks >> 2));
          r.next(); r.next_if(!hi && !bo); r.next_if(!hi && !bo);
          r.xp ^= 1 << b;
        }
        r.xp ^= 3;
        if (w.kind == 0) {
          m = &P.kv[hi][w.beta >> 4];
          c1 = (d & 511) * (SK / 8);
          for (int j = 0; j < 16; j++) {
            if (hi) r.next();
            const uint32_t bar = sbase + BAR_FULL + r.slot * 8;
            const bool tight = i < KV_WIN_UNITS && j < KV_WIN_TILES + ((KV_WIN_RAMP * rank) >> 5);
            {
              const int s2 = (int)r.slot - (tight ? 2 : KV_WIN_D);
              mbar_wait_w(sbase + BAR_FULL + (s2 < 0 ? s2 + NS : s2) * 8, s2 < 0 ? r.phase : r.phase ^ 1);
            }
            if (j == 15 && hi) mbar_wait_w(sbase + BAR_DESC, i & 1);
            mbar_wait_w(sbase + BAR_EMPTY + r.slot * 8, r.phase);
            tma_ld_kv_w(sbase + r.slot * SLOT, m, c1, bar, pol_stream);
            T2P(i, 3 + hi, 16 + j);
            if (!hi) TCLK(i * 16 + j);
            if (j == GO_J && !hi) mbar_arrive_warp(sbase + BAR_GO);
            c1 += 8;
            r.next();
            if (!hi) r.next();
          }
        }
        mbar_wait_w(sbase + BAR_DESC, i & 1);
        d = __shfl_sync(0xffffffffu, lds(sbase + DESC_OFF + ((i + 1) & 3) * 4), 0);
      }
    }
  } else {
    Ctx c;
    c.sb = sbase; c.wg = wg; c.warp = warp; c.src = 0; c.mqk = 0; c.mpv = 0; c.lead = lane == 0; c.lane0 = c.lane = lane;
    if (wg == 0) consumer<0>(c, P.kp); else consumer<1>(c, P.kp);
  }
}

typedef CUresult (*EncodeFn)(CUtensorMap*, CUtensorMapDataType, cuuint32_t, void*, const cuuint64_t*, const cuuint64_t*,
                             const cuuint32_t*, const cuuint32_t*, CUtensorMapInterleave, CUtensorMapSwizzle,
                             CUtensorMapL2promotion, CUtensorMapFloatOOBfill);

void make_map(EncodeFn enc, CUtensorMap* m, const void* ptr, int rank, const cuuint64_t* dims, const cuuint64_t* strides,
              const cuuint32_t* box, CUtensorMapSwizzle swz = CU_TENSOR_MAP_SWIZZLE_128B) {
  cuuint32_t es[5] = {1, 1, 1, 1, 1};
  enc(m, CU_TENSOR_MAP_DATA_TYPE_BFLOAT16, rank, const_cast<void*>(ptr), dims, strides, box, es,
      CU_TENSOR_MAP_INTERLEAVE_NONE, swz, CU_TENSOR_MAP_L2_PROMOTION_NONE,
      CU_TENSOR_MAP_FLOAT_OOB_FILL_NONE);
}

}

extern "C" void kernel_launch(void* const* d_in, const int* in_sizes, int n_in, void* d_out, int out_size) {
  (void)in_sizes; (void)n_in; (void)out_size;
  static EncodeFn enc = nullptr;
  static void* o_ptr = nullptr;
  static int n_sm = 0;
  cudaLaunchAttribute at;
  at.id = cudaLaunchAttributeClusterDimension;
  at.val.clusterDim.x = 2; at.val.clusterDim.y = 1; at.val.clusterDim.z = 1;
  cudaLaunchConfig_t cfg = {};
  cfg.gridDim = dim3(NCTA); cfg.blockDim = dim3(384); cfg.dynamicSmemBytes = SMEM_BYTES; cfg.attrs = &at; cfg.numAttrs = 1;
  if (!enc) {
    void* fn = nullptr;
    cudaDriverEntryPointQueryResult qr;
    cudaGetDriverEntryPoint("cuTensorMapEncodeTiled", &fn, cudaEnableDefault, &qr);
    enc = (EncodeFn)fn;
    cudaGetSymbolAddress(&o_ptr, g_o);
    cudaFuncSetAttribute(mha_fused_kernel<false>, cudaFuncAttributeMaxDynamicSharedMemorySize, SMEM_BYTES);
    cudaFuncSetAttribute(mha_fused_kernel<true>, cudaFuncAttributeMaxDynamicSharedMemorySize, SMEM_BYTES);
    int dev = 0;
    cudaGetDevice(&dev);
    cudaDeviceGetAttribute(&n_sm, cudaDevAttrMultiProcessorCount, dev);
    int n_cl = 0;
    cudaOccupancyMaxActiveClusters(&n_cl, mha_fused_kernel<false>, &cfg);
    if (n_cl * 2 < NCTA && n_sm >= NCTA) n_sm = NCTA - 1;
  }
  Params P;
  for (int br = 0; br < 2; br++) {
    const void* x = d_in[br * 5 + 0]; const void* kc = d_in[br * 5 + 1]; const void* vc = d_in[br * 5 + 2];
    const void* wq = d_in[br * 5 + 3]; const void* wo = d_in[br * 5 + 4];
    { cuuint64_t d[2] = {DM, (cuuint64_t)NB * SQ}, s[1] = {DM * 2}; cuuint32_t b[2] = {64, 128}, b2[2] = {64, 96};
      make_map(enc, &P.x[0][br], x, 2, d, s, b); make_map(enc, &P.x[1][br], x, 2, d, s, b2); }
    { cuuint64_t d[3] = {64, DM, HD / 64}, s[2] = {HD * 2, 128}; cuuint32_t b[3] = {64, 64, 2}; make_map(enc, &P.wq[br], wq, 3, d, s, b); }
    { cuuint64_t d[5] = {DM, 2, 4, 4, HD / 32}, s[4] = {DM * 2, 8 * DM * 2, 2 * DM * 2, 32 * DM * 2}; cuuint32_t b[5] = {64, 2, 4, 4, 2};
      make_map(enc, &P.wo[br], wo, 5, d, s, b); }
    { cuuint64_t d[4] = {64, 8, 2, (cuuint64_t)NB * NH * SK / 8}, s[3] = {DH * 2, 128, DH * 16}; cuuint32_t b[4] = {64, 8, 2, 8};
      make_map(enc, &P.kv[0][br], kc, 4, d, s, b); make_map(enc, &P.kv[1][br], vc, 4, d, s, b); }
    P.kp[br] = (const __nv_bfloat16*)kc; P.vp[br] = (const __nv_bfloat16*)vc;

  }
  { cuuint64_t d[2] = {64, (cuuint64_t)NBETA * 64 * SQ}, s[1] = {128}; cuuint32_t b[2] = {64, 128}, b2[2] = {64, 96};
    make_map(enc, &P.o_ld[0], o_ptr, 2, d, s, b, CU_TENSOR_MAP_SWIZZLE_NONE); make_map(enc, &P.o_ld[1], o_ptr, 2, d, s, b2, CU_TENSOR_MAP_SWIZZLE_NONE); }
  { cuuint64_t d[3] = {64, SQ, O_BLOCKS}, s[2] = {128, SQ * 128}; cuuint32_t b[3] = {64, 64, 2}, b2[3] = {64, 32, 2};
    make_map(enc, &P.o_st[0], o_ptr, 3, d, s, b); make_map(enc, &P.o_st[1], o_ptr, 3, d, s, b2); }
  { cuuint64_t d[3] = {64, (cuuint64_t)NB * SQ, 2 * DM / 64}, s[2] = {2 * DM * 2, 128}; cuuint32_t b[3] = {64, 64, 2}, b2[3] = {64, 32, 2};
    make_map(enc, &P.out_st[0], d_out, 3, d, s, b); make_map(enc, &P.out_st[1], d_out, 3, d, s, b2); }
  if (n_sm >= NCTA) cudaLaunchKernelEx(&cfg, mha_fused_kernel<false>, P);
  else mha_fused_kernel<true><<<n_sm, 384, SMEM_BYTES>>>(P);
}
```

```cpp
#include <cuda_runtime.h>
#include <cuda_bf16.h>
#include <cuda.h>
#include <stdint.h>
#include <stdlib.h>

namespace {

__device__ __forceinline__ void wgmma_proj(float (&d)[64], uint64_t da, uint64_t db, int scaleD) {
  asm volatile("{\n.reg .pred p;\nsetp.ne.b32 p, %66, 0;\n"
      "wgmma.mma_async.sync.aligned.m64n128k16.f32.bf16.bf16 "
      "{%0, %1, %2, %3, %4, %5, %6, %7, %8, %9, %10, %11, %12, %13, %14, %15, %16, %17, %18, %19, %20, %21, %22, %23, %24, %25, %26, %27, %28, %29, %30, "
      "%31, %32, %33, %34, %35, %36, %37, %38, %39, %40, %41, %42, %43, %44, %45, %46, %47, %48, %49, %50, %51, %52, %53, %54, %55, %56, %57, %58, %59, %60, "
      "%61, %62, %63}, "
      "%64, %65, p, 1, 1, 0, 1;\n}\n"
      : "+f"(d[0]), "+f"(d[1]), "+f"(d[2]), "+f"(d[3]), "+f"(d[4]), "+f"(d[5]), "+f"(d[6]), "+f"(d[7]), "+f"(d[8]), "+f"(d[9]), "+f"(d[10]), "+f"(d[11]),
        "+f"(d[12]), "+f"(d[13]), "+f"(d[14]), "+f"(d[15]), "+f"(d[16]), "+f"(d[17]), "+f"(d[18]), "+f"(d[19]), "+f"(d[20]), "+f"(d[21]), "+f"(d[22]),
        "+f"(d[23]), "+f"(d[24]), "+f"(d[25]), "+f"(d[26]), "+f"(d[27]), "+f"(d[28]), "+f"(d[29]), "+f"(d[30]), "+f"(d[31]), "+f"(d[32]), "+f"(d[33]),
        "+f"(d[34]), "+f"(d[35]), "+f"(d[36]), "+f"(d[37]), "+f"(d[38]), "+f"(d[39]), "+f"(d[40]), "+f"(d[41]), "+f"(d[42]), "+f"(d[43]), "+f"(d[44]),
        "+f"(d[45]), "+f"(d[46]), "+f"(d[47]), "+f"(d[48]), "+f"(d[49]), "+f"(d[50]), "+f"(d[51]), "+f"(d[52]), "+f"(d[53]), "+f"(d[54]), "+f"(d[55]),
        "+f"(d[56]), "+f"(d[57]), "+f"(d[58]), "+f"(d[59]), "+f"(d[60]), "+f"(d[61]), "+f"(d[62]), "+f"(d[63])
      : "l"(da), "l"(db), "r"(scaleD));
}
__device__ __forceinline__ void wgmma_proj96(float (&d)[64], uint64_t da, uint64_t db, int scaleD) {
  asm volatile("{\n.reg .pred p;\nsetp.ne.b32 p, %50, 0;\n"
      "wgmma.mma_async.sync.aligned.m64n96k16.f32.bf16.bf16 "
      "{%0, %1, %2, %3, %4, %5, %6, %7, %8, %9, %10, %11, %12, %13, %14, %15, %16, %17, %18, %19, %20, %21, %22, %23, %24, %25, %26, %27, %28, %29, %30, "
      "%31, %32, %33, %34, %35, %36, %37, %38, %39, %40, %41, %42, %43, %44, %45, %46, %47}, "
      "%48, %49, p, 1, 1, 1, 0;\n}\n"
      : "+f"(d[0]), "+f"(d[1]), "+f"(d[2]), "+f"(d[3]), "+f"(d[4]), "+f"(d[5]), "+f"(d[6]), "+f"(d[7]), "+f"(d[8]), "+f"(d[9]), "+f"(d[10]), "+f"(d[11]),
        "+f"(d[12]), "+f"(d[13]), "+f"(d[14]), "+f"(d[15]), "+f"(d[16]), "+f"(d[17]), "+f"(d[18]), "+f"(d[19]), "+f"(d[20]), "+f"(d[21]), "+f"(d[22]),
        "+f"(d[23]), "+f"(d[24]), "+f"(d[25]), "+f"(d[26]), "+f"(d[27]), "+f"(d[28]), "+f"(d[29]), "+f"(d[30]), "+f"(d[31]), "+f"(d[32]), "+f"(d[33]),
        "+f"(d[34]), "+f"(d[35]), "+f"(d[36]), "+f"(d[37]), "+f"(d[38]), "+f"(d[39]), "+f"(d[40]), "+f"(d[41]), "+f"(d[42]), "+f"(d[43]), "+f"(d[44]),
        "+f"(d[45]), "+f"(d[46]), "+f"(d[47])
      : "l"(da), "l"(db), "r"(scaleD));
}
__device__ __forceinline__ void wgmma_qk(float (&d)[32], uint64_t da, uint64_t db, int scaleD) {
  asm volatile("{\n.reg .pred p;\nsetp.ne.b32 p, %34, 0;\n"
      "wgmma.mma_async.sync.aligned.m64n64k16.f32.bf16.bf16 "
      "{%0, %1, %2, %3, %4, %5, %6, %7, %8, %9, %10, %11, %12, %13, %14, %15, %16, %17, %18, %19, %20, %21, %22, %23, %24, %25, %26, %27, %28, %29, %30, "
      "%31}, "
      "%32, %33, p, 1, 1, 0, 0;\n}\n"
      : "+f"(d[0]), "+f"(d[1]), "+f"(d[2]), "+f"(d[3]), "+f"(d[4]), "+f"(d[5]), "+f"(d[6]), "+f"(d[7]), "+f"(d[8]), "+f"(d[9]), "+f"(d[10]), "+f"(d[11]),
        "+f"(d[12]), "+f"(d[13]), "+f"(d[14]), "+f"(d[15]), "+f"(d[16]), "+f"(d[17]), "+f"(d[18]), "+f"(d[19]), "+f"(d[20]), "+f"(d[21]), "+f"(d[22]),
        "+f"(d[23]), "+f"(d[24]), "+f"(d[25]), "+f"(d[26]), "+f"(d[27]), "+f"(d[28]), "+f"(d[29]), "+f"(d[30]), "+f"(d[31])
      : "l"(da), "l"(db), "r"(scaleD));
}
__device__ __forceinline__ void wgmma_qk_rs(float (&d)[32], uint32_t a0, uint32_t a1, uint32_t a2, uint32_t a3, uint64_t db, int scaleD) {
  asm volatile("{\n.reg .pred p;\nsetp.ne.b32 p, %37, 0;\n"
      "wgmma.mma_async.sync.aligned.m64n64k16.f32.bf16.bf16 "
      "{%0, %1, %2, %3, %4, %5, %6, %7, %8, %9, %10, %11, %12, %13, %14, %15, %16, %17, %18, %19, %20, %21, %22, %23, %24, %25, %26, %27, %28, %29, %30, "
      "%31}, "
      "{%32, %33, %34, %35}, %36, p, 1, 1, 0;\n}\n"
      : "+f"(d[0]), "+f"(d[1]), "+f"(d[2]), "+f"(d[3]), "+f"(d[4]), "+f"(d[5]), "+f"(d[6]), "+f"(d[7]), "+f"(d[8]), "+f"(d[9]), "+f"(d[10]), "+f"(d[11]),
        "+f"(d[12]), "+f"(d[13]), "+f"(d[14]), "+f"(d[15]), "+f"(d[16]), "+f"(d[17]), "+f"(d[18]), "+f"(d[19]), "+f"(d[20]), "+f"(d[21]), "+f"(d[22]),
        "+f"(d[23]), "+f"(d[24]), "+f"(d[25]), "+f"(d[26]), "+f"(d[27]), "+f"(d[28]), "+f"(d[29]), "+f"(d[30]), "+f"(d[31])
      : "r"(a0), "r"(a1), "r"(a2), "r"(a3), "l"(db), "r"(scaleD));
}
__device__ __forceinline__ void wgmma_pv(float (&d)[64], uint32_t a0, uint32_t a1, uint32_t a2, uint32_t a3, uint64_t db, int scaleD) {
  asm volatile("{\n.reg .pred p;\nsetp.ne.b32 p, %69, 0;\n"
      "wgmma.mma_async.sync.aligned.m64n128k16.f32.bf16.bf16 "
      "{%0, %1, %2, %3, %4, %5, %6, %7, %8, %9, %10, %11, %12, %13, %14, %15, %16, %17, %18, %19, %20, %21, %22, %23, %24, %25, %26, %27, %28, %29, %30, "
      "%31, %32, %33, %34, %35, %36, %37, %38, %39, %40, %41, %42, %43, %44, %45, %46, %47, %48, %49, %50, %51, %52, %53, %54, %55, %56, %57, %58, %59, %60, "
      "%61, %62, %63}, "
      "{%64, %65, %66, %67}, %68, p, 1, 1, 1;\n}\n"
      : "+f"(d[0]), "+f"(d[1]), "+f"(d[2]), "+f"(d[3]), "+f"(d[4]), "+f"(d[5]), "+f"(d[6]), "+f"(d[7]), "+f"(d[8]), "+f"(d[9]), "+f"(d[10]), "+f"(d[11]),
        "+f"(d[12]), "+f"(d[13]), "+f"(d[14]), "+f"(d[15]), "+f"(d[16]), "+f"(d[17]), "+f"(d[18]), "+f"(d[19]), "+f"(d[20]), "+f"(d[21]), "+f"(d[22]),
        "+f"(d[23]), "+f"(d[24]), "+f"(d[25]), "+f"(d[26]), "+f"(d[27]), "+f"(d[28]), "+f"(d[29]), "+f"(d[30]), "+f"(d[31]), "+f"(d[32]), "+f"(d[33]),
        "+f"(d[34]), "+f"(d[35]), "+f"(d[36]), "+f"(d[37]), "+f"(d[38]), "+f"(d[39]), "+f"(d[40]), "+f"(d[41]), "+f"(d[42]), "+f"(d[43]), "+f"(d[44]),
        "+f"(d[45]), "+f"(d[46]), "+f"(d[47]), "+f"(d[48]), "+f"(d[49]), "+f"(d[50]), "+f"(d[51]), "+f"(d[52]), "+f"(d[53]), "+f"(d[54]), "+f"(d[55]),
        "+f"(d[56]), "+f"(d[57]), "+f"(d[58]), "+f"(d[59]), "+f"(d[60]), "+f"(d[61]), "+f"(d[62]), "+f"(d[63])
      : "r"(a0), "r"(a1), "r"(a2), "r"(a3), "l"(db), "r"(scaleD));
}
__device__ __forceinline__ void wgmma_qk_sp(float (&d)[32], uint32_t a0, uint32_t a1, uint32_t a2, uint32_t a3, uint64_t db, int scaleD, uint32_t meta) {
  asm volatile("{\n.reg .pred p;\nsetp.ne.b32 p, %37, 0;\n"
      "wgmma.mma_async.sp.sync.aligned.m64n64k32.f32.bf16.bf16 "
      "{%0, %1, %2, %3, %4, %5, %6, %7, %8, %9, %10, %11, %12, %13, %14, %15, %16, %17, %18, %19, %20, %21, %22, %23, %24, %25, %26, %27, %28, %29, %30, "
      "%31}, "
      "{%32, %33, %34, %35}, %36, %38, 0, p, 1, 1, 0;\n}\n"
      : "+f"(d[0]), "+f"(d[1]), "+f"(d[2]), "+f"(d[3]), "+f"(d[4]), "+f"(d[5]), "+f"(d[6]), "+f"(d[7]), "+f"(d[8]), "+f"(d[9]), "+f"(d[10]), "+f"(d[11]),
        "+f"(d[12]), "+f"(d[13]), "+f"(d[14]), "+f"(d[15]), "+f"(d[16]), "+f"(d[17]), "+f"(d[18]), "+f"(d[19]), "+f"(d[20]), "+f"(d[21]), "+f"(d[22]),
        "+f"(d[23]), "+f"(d[24]), "+f"(d[25]), "+f"(d[26]), "+f"(d[27]), "+f"(d[28]), "+f"(d[29]), "+f"(d[30]), "+f"(d[31])
      : "r"(a0), "r"(a1), "r"(a2), "r"(a3), "l"(db), "r"(scaleD), "r"(meta));
}
__device__ __forceinline__ void wgmma_pv_sp(float (&d)[64], uint32_t a0, uint32_t a1, uint32_t a2, uint32_t a3, uint64_t db, int scaleD, uint32_t meta) {
  asm volatile("{\n.reg .pred p;\nsetp.ne.b32 p, %69, 0;\n"
      "wgmma.mma_async.sp.sync.aligned.m64n128k32.f32.bf16.bf16 "
      "{%0, %1, %2, %3, %4, %5, %6, %7, %8, %9, %10, %11, %12, %13, %14, %15, %16, %17, %18, %19, %20, %21, %22, %23, %24, %25, %26, %27, %28, %29, %30, "
      "%31, %32, %33, %34, %35, %36, %37, %38, %39, %40, %41, %42, %43, %44, %45, %46, %47, %48, %49, %50, %51, %52, %53, %54, %55, %56, %57, %58, %59, %60, "
      "%61, %62, %63}, "
      "{%64, %65, %66, %67}, %68, %70, 0, p, 1, 1, 1;\n}\n"
      : "+f"(d[0]), "+f"(d[1]), "+f"(d[2]), "+f"(d[3]), "+f"(d[4]), "+f"(d[5]), "+f"(d[6]), "+f"(d[7]), "+f"(d[8]), "+f"(d[9]), "+f"(d[10]), "+f"(d[11]),
        "+f"(d[12]), "+f"(d[13]), "+f"(d[14]), "+f"(d[15]), "+f"(d[16]), "+f"(d[17]), "+f"(d[18]), "+f"(d[19]), "+f"(d[20]), "+f"(d[21]), "+f"(d[22]),
        "+f"(d[23]), "+f"(d[24]), "+f"(d[25]), "+f"(d[26]), "+f"(d[27]), "+f"(d[28]), "+f"(d[29]), "+f"(d[30]), "+f"(d[31]), "+f"(d[32]), "+f"(d[33]),
        "+f"(d[34]), "+f"(d[35]), "+f"(d[36]), "+f"(d[37]), "+f"(d[38]), "+f"(d[39]), "+f"(d[40]), "+f"(d[41]), "+f"(d[42]), "+f"(d[43]), "+f"(d[44]),
        "+f"(d[45]), "+f"(d[46]), "+f"(d[47]), "+f"(d[48]), "+f"(d[49]), "+f"(d[50]), "+f"(d[51]), "+f"(d[52]), "+f"(d[53]), "+f"(d[54]), "+f"(d[55]),
        "+f"(d[56]), "+f"(d[57]), "+f"(d[58]), "+f"(d[59]), "+f"(d[60]), "+f"(d[61]), "+f"(d[62]), "+f"(d[63])
      : "r"(a0), "r"(a1), "r"(a2), "r"(a3), "l"(db), "r"(scaleD), "r"(meta));
}
__device__ __forceinline__ void wgmma_proj_init(float (&d)[64], uint64_t da, uint64_t db, int scaleD) {
  asm volatile("{\n.reg .pred p;\nsetp.ne.b32 p, %66, 0;\n"
      "wgmma.mma_async.sync.aligned.m64n128k16.f32.bf16.bf16 "
      "{%0, %1, %2, %3, %4, %5, %6, %7, %8, %9, %10, %11, %12, %13, %14, %15, %16, %17, %18, %19, %20, %21, %22, %23, %24, %25, %26, %27, %28, %29, %30, "
      "%31, %32, %33, %34, %35, %36, %37, %38, %39, %40, %41, %42, %43, %44, %45, %46, %47, %48, %49, %50, %51, %52, %53, %54, %55, %56, %57, %58, %59, %60, "
      "%61, %62, %63}, "
      "%64, %65, p, 1, 1, 0, 1;\n}\n"
      : "=f"(d[0]), "=f"(d[1]), "=f"(d[2]), "=f"(d[3]), "=f"(d[4]), "=f"(d[5]), "=f"(d[6]), "=f"(d[7]), "=f"(d[8]), "=f"(d[9]), "=f"(d[10]), "=f"(d[11]),
        "=f"(d[12]), "=f"(d[13]), "=f"(d[14]), "=f"(d[15]), "=f"(d[16]), "=f"(d[17]), "=f"(d[18]), "=f"(d[19]), "=f"(d[20]), "=f"(d[21]), "=f"(d[22]),
        "=f"(d[23]), "=f"(d[24]), "=f"(d[25]), "=f"(d[26]), "=f"(d[27]), "=f"(d[28]), "=f"(d[29]), "=f"(d[30]), "=f"(d[31]), "=f"(d[32]), "=f"(d[33]),
        "=f"(d[34]), "=f"(d[35]), "=f"(d[36]), "=f"(d[37]), "=f"(d[38]), "=f"(d[39]), "=f"(d[40]), "=f"(d[41]), "=f"(d[42]), "=f"(d[43]), "=f"(d[44]),
        "=f"(d[45]), "=f"(d[46]), "=f"(d[47]), "=f"(d[48]), "=f"(d[49]), "=f"(d[50]), "=f"(d[51]), "=f"(d[52]), "=f"(d[53]), "=f"(d[54]), "=f"(d[55]),
        "=f"(d[56]), "=f"(d[57]), "=f"(d[58]), "=f"(d[59]), "=f"(d[60]), "=f"(d[61]), "=f"(d[62]), "=f"(d[63])
      : "l"(da), "l"(db), "r"(scaleD));
}
__device__ __forceinline__ void wgmma_proj96_init(float (&d)[64], uint64_t da, uint64_t db, int scaleD) {
  asm volatile("{\n.reg .pred p;\nsetp.ne.b32 p, %50, 0;\n"
      "wgmma.mma_async.sync.aligned.m64n96k16.f32.bf16.bf16 "
      "{%0, %1, %2, %3, %4, %5, %6, %7, %8, %9, %10, %11, %12, %13, %14, %15, %16, %17, %18, %19, %20, %21, %22, %23, %24, %25, %26, %27, %28, %29, %30, "
      "%31, %32, %33, %34, %35, %36, %37, %38, %39, %40, %41, %42, %43, %44, %45, %46, %47}, "
      "%48, %49, p, 1, 1, 1, 0;\n}\n"
      : "=f"(d[0]), "=f"(d[1]), "=f"(d[2]), "=f"(d[3]), "=f"(d[4]), "=f"(d[5]), "=f"(d[6]), "=f"(d[7]), "=f"(d[8]), "=f"(d[9]), "=f"(d[10]), "=f"(d[11]),
        "=f"(d[12]), "=f"(d[13]), "=f"(d[14]), "=f"(d[15]), "=f"(d[16]), "=f"(d[17]), "=f"(d[18]), "=f"(d[19]), "=f"(d[20]), "=f"(d[21]), "=f"(d[22]),
        "=f"(d[23]), "=f"(d[24]), "=f"(d[25]), "=f"(d[26]), "=f"(d[27]), "=f"(d[28]), "=f"(d[29]), "=f"(d[30]), "=f"(d[31]), "=f"(d[32]), "=f"(d[33]),
        "=f"(d[34]), "=f"(d[35]), "=f"(d[36]), "=f"(d[37]), "=f"(d[38]), "=f"(d[39]), "=f"(d[40]), "=f"(d[41]), "=f"(d[42]), "=f"(d[43]), "=f"(d[44]),
        "=f"(d[45]), "=f"(d[46]), "=f"(d[47])
      : "l"(da), "l"(db), "r"(scaleD));
}
__device__ __forceinline__ void wgmma_qk_init(float (&d)[32], uint64_t da, uint64_t db, int scaleD) {
  asm volatile("{\n.reg .pred p;\nsetp.ne.b32 p, %34, 0;\n"
      "wgmma.mma_async.sync.aligned.m64n64k16.f32.bf16.bf16 "
      "{%0, %1, %2, %3, %4, %5, %6, %7, %8, %9, %10, %11, %12, %13, %14, %15, %16, %17, %18, %19, %20, %21, %22, %23, %24, %25, %26, %27, %28, %29, %30, "
      "%31}, "
      "%32, %33, p, 1, 1, 0, 0;\n}\n"
      : "=f"(d[0]), "=f"(d[1]), "=f"(d[2]), "=f"(d[3]), "=f"(d[4]), "=f"(d[5]), "=f"(d[6]), "=f"(d[7]), "=f"(d[8]), "=f"(d[9]), "=f"(d[10]), "=f"(d[11]),
        "=f"(d[12]), "=f"(d[13]), "=f"(d[14]), "=f"(d[15]), "=f"(d[16]), "=f"(d[17]), "=f"(d[18]), "=f"(d[19]), "=f"(d[20]), "=f"(d[21]), "=f"(d[22]),
        "=f"(d[23]), "=f"(d[24]), "=f"(d[25]), "=f"(d[26]), "=f"(d[27]), "=f"(d[28]), "=f"(d[29]), "=f"(d[30]), "=f"(d[31])
      : "l"(da), "l"(db), "r"(scaleD));
}
__device__ __forceinline__ void wgmma_qk_rs_init(float (&d)[32], uint32_t a0, uint32_t a1, uint32_t a2, uint32_t a3, uint64_t db, int scaleD) {
  asm volatile("{\n.reg .pred p;\nsetp.ne.b32 p, %37, 0;\n"
      "wgmma.mma_async.sync.aligned.m64n64k16.f32.bf16.bf16 "
      "{%0, %1, %2, %3, %4, %5, %6, %7, %8, %9, %10, %11, %12, %13, %14, %15, %16, %17, %18, %19, %20, %21, %22, %23, %24, %25, %26, %27, %28, %29, %30, "
      "%31}, "
      "{%32, %33, %34, %35}, %36, p, 1, 1, 0;\n}\n"
      : "=f"(d[0]), "=f"(d[1]), "=f"(d[2]), "=f"(d[3]), "=f"(d[4]), "=f"(d[5]), "=f"(d[6]), "=f"(d[7]), "=f"(d[8]), "=f"(d[9]), "=f"(d[10]), "=f"(d[11]),
        "=f"(d[12]), "=f"(d[13]), "=f"(d[14]), "=f"(d[15]), "=f"(d[16]), "=f"(d[17]), "=f"(d[18]), "=f"(d[19]), "=f"(d[20]), "=f"(d[21]), "=f"(d[22]),
        "=f"(d[23]), "=f"(d[24]), "=f"(d[25]), "=f"(d[26]), "=f"(d[27]), "=f"(d[28]), "=f"(d[29]), "=f"(d[30]), "=f"(d[31])
      : "r"(a0), "r"(a1), "r"(a2), "r"(a3), "l"(db), "r"(scaleD));
}
__device__ __forceinline__ void wgmma_pv_init(float (&d)[64], uint32_t a0, uint32_t a1, uint32_t a2, uint32_t a3, uint64_t db, int scaleD) {
  asm volatile("{\n.reg .pred p;\nsetp.ne.b32 p, %69, 0;\n"
      "wgmma.mma_async.sync.aligned.m64n128k16.f32.bf16.bf16 "
      "{%0, %1, %2, %3, %4, %5, %6, %7, %8, %9, %10, %11, %12, %13, %14, %15, %16, %17, %18, %19, %20, %21, %22, %23, %24, %25, %26, %27, %28, %29, %30, "
      "%31, %32, %33, %34, %35, %36, %37, %38, %39, %40, %41, %42, %43, %44, %45, %46, %47, %48, %49, %50, %51, %52, %53, %54, %55, %56, %57, %58, %59, %60, "
      "%61, %62, %63}, "
      "{%64, %65, %66, %67}, %68, p, 1, 1, 1;\n}\n"
      : "=f"(d[0]), "=f"(d[1]), "=f"(d[2]), "=f"(d[3]), "=f"(d[4]), "=f"(d[5]), "=f"(d[6]), "=f"(d[7]), "=f"(d[8]), "=f"(d[9]), "=f"(d[10]), "=f"(d[11]),
        "=f"(d[12]), "=f"(d[13]), "=f"(d[14]), "=f"(d[15]), "=f"(d[16]), "=f"(d[17]), "=f"(d[18]), "=f"(d[19]), "=f"(d[20]), "=f"(d[21]), "=f"(d[22]),
        "=f"(d[23]), "=f"(d[24]), "=f"(d[25]), "=f"(d[26]), "=f"(d[27]), "=f"(d[28]), "=f"(d[29]), "=f"(d[30]), "=f"(d[31]), "=f"(d[32]), "=f"(d[33]),
        "=f"(d[34]), "=f"(d[35]), "=f"(d[36]), "=f"(d[37]), "=f"(d[38]), "=f"(d[39]), "=f"(d[40]), "=f"(d[41]), "=f"(d[42]), "=f"(d[43]), "=f"(d[44]),
        "=f"(d[45]), "=f"(d[46]), "=f"(d[47]), "=f"(d[48]), "=f"(d[49]), "=f"(d[50]), "=f"(d[51]), "=f"(d[52]), "=f"(d[53]), "=f"(d[54]), "=f"(d[55]),
        "=f"(d[56]), "=f"(d[57]), "=f"(d[58]), "=f"(d[59]), "=f"(d[60]), "=f"(d[61]), "=f"(d[62]), "=f"(d[63])
      : "r"(a0), "r"(a1), "r"(a2), "r"(a3), "l"(db), "r"(scaleD));
}
__device__ __forceinline__ void wgmma_qk_sp_init(float (&d)[32], uint32_t a0, uint32_t a1, uint32_t a2, uint32_t a3, uint64_t db, int scaleD, uint32_t meta) {
  asm volatile("{\n.reg .pred p;\nsetp.ne.b32 p, %37, 0;\n"
      "wgmma.mma_async.sp.sync.aligned.m64n64k32.f32.bf16.bf16 "
      "{%0, %1, %2, %3, %4, %5, %6, %7, %8, %9, %10, %11, %12, %13, %14, %15, %16, %17, %18, %19, %20, %21, %22, %23, %24, %25, %26, %27, %28, %29, %30, "
      "%31}, "
      "{%32, %33, %34, %35}, %36, %38, 0, p, 1, 1, 0;\n}\n"
      : "=f"(d[0]), "=f"(d[1]), "=f"(d[2]), "=f"(d[3]), "=f"(d[4]), "=f"(d[5]), "=f"(d[6]), "=f"(d[7]), "=f"(d[8]), "=f"(d[9]), "=f"(d[10]), "=f"(d[11]),
        "=f"(d[12]), "=f"(d[13]), "=f"(d[14]), "=f"(d[15]), "=f"(d[16]), "=f"(d[17]), "=f"(d[18]), "=f"(d[19]), "=f"(d[20]), "=f"(d[21]), "=f"(d[22]),
        "=f"(d[23]), "=f"(d[24]), "=f"(d[25]), "=f"(d[26]), "=f"(d[27]), "=f"(d[28]), "=f"(d[29]), "=f"(d[30]), "=f"(d[31])
      : "r"(a0), "r"(a1), "r"(a2), "r"(a3), "l"(db), "r"(scaleD), "r"(meta));
}
__device__ __forceinline__ void wgmma_pv_sp_init(float (&d)[64], uint32_t a0, uint32_t a1, uint32_t a2, uint32_t a3, uint64_t db, int scaleD, uint32_t meta) {
  asm volatile("{\n.reg .pred p;\nsetp.ne.b32 p, %69, 0;\n"
      "wgmma.mma_async.sp.sync.aligned.m64n128k32.f32.bf16.bf16 "
      "{%0, %1, %2, %3, %4, %5, %6, %7, %8, %9, %10, %11, %12, %13, %14, %15, %16, %17, %18, %19, %20, %21, %22, %23, %24, %25, %26, %27, %28, %29, %30, "
      "%31, %32, %33, %34, %35, %36, %37, %38, %39, %40, %41, %42, %43, %44, %45, %46, %47, %48, %49, %50, %51, %52, %53, %54, %55, %56, %57, %58, %59, %60, "
      "%61, %62, %63}, "
      "{%64, %65, %66, %67}, %68, %70, 0, p, 1, 1, 1;\n}\n"
      : "=f"(d[0]), "=f"(d[1]), "=f"(d[2]), "=f"(d[3]), "=f"(d[4]), "=f"(d[5]), "=f"(d[6]), "=f"(d[7]), "=f"(d[8]), "=f"(d[9]), "=f"(d[10]), "=f"(d[11]),
        "=f"(d[12]), "=f"(d[13]), "=f"(d[14]), "=f"(d[15]), "=f"(d[16]), "=f"(d[17]), "=f"(d[18]), "=f"(d[19]), "=f"(d[20]), "=f"(d[21]), "=f"(d[22]),
        "=f"(d[23]), "=f"(d[24]), "=f"(d[25]), "=f"(d[26]), "=f"(d[27]), "=f"(d[28]), "=f"(d[29]), "=f"(d[30]), "=f"(d[31]), "=f"(d[32]), "=f"(d[33]),
        "=f"(d[34]), "=f"(d[35]), "=f"(d[36]), "=f"(d[37]), "=f"(d[38]), "=f"(d[39]), "=f"(d[40]), "=f"(d[41]), "=f"(d[42]), "=f"(d[43]), "=f"(d[44]),
        "=f"(d[45]), "=f"(d[46]), "=f"(d[47]), "=f"(d[48]), "=f"(d[49]), "=f"(d[50]), "=f"(d[51]), "=f"(d[52]), "=f"(d[53]), "=f"(d[54]), "=f"(d[55]),
        "=f"(d[56]), "=f"(d[57]), "=f"(d[58]), "=f"(d[59]), "=f"(d[60]), "=f"(d[61]), "=f"(d[62]), "=f"(d[63])
      : "r"(a0), "r"(a1), "r"(a2), "r"(a3), "l"(db), "r"(scaleD), "r"(meta));
}

constexpr int NB = 16, SQ = 224, DM = 640, NH = 32, SK = 1024, DH = 128;
constexpr int HD = NH * DH;
constexpr int NBETA = 2 * NB;
constexpr int NCTA = 132;
constexpr uint32_t SB0 = 1024;
constexpr int NS = 10;
constexpr int SLOT = 16384;
constexpr int QBUF_OFF = NS * SLOT;
constexpr int NSX = NS + 4;
constexpr int BAR_OFF = NSX * SLOT;
constexpr int BAR_FULL = BAR_OFF;
constexpr int BAR_EMPTY = BAR_OFF + 8 * NSX;
constexpr int BAR_STG = BAR_OFF + 16 * NSX;
constexpr int BAR_OUT = BAR_STG + 32;
constexpr int BAR_DESC = BAR_OUT + 8;
constexpr int BAR_GO = BAR_DESC + 8;
constexpr int BAR_MAIL = BAR_GO + 8;
constexpr int BAR_RDY = BAR_MAIL + 8;
constexpr int DESC_OFF = BAR_RDY + 8 * NSX;
constexpr int EPOCH_OFF = DESC_OFF + 16;
constexpr int TRACE_OFF = EPOCH_OFF + 16;
constexpr int SMEM_BYTES = TRACE_OFF;
constexpr float SM_C = 0.08838834764831845f * 1.4426950408889634f;
constexpr float SUM_HI = 1099511627776.f, SUM_LO = 1.f / 1099511627776.f;
constexpr uint32_t META_QK = 0xEEEE4444u;
constexpr uint32_t META_PV = 0x44EEEE44u;

#define QK_EARLY_MASK 3
#define ST_ORDER 0x2310
#define LAG_BAR 2
#define ST_NOW 8
#define PF_STEP 5
#define KV_WIN_UNITS 2
#define KV_WIN_D 4
#define SF 0xeebf
#define O_STEPS 4
#define KV_WIN_RAMP 4
#define PDEPTH 0
#define KV_WIN_TILES -2
#define REG_C 232
#define REG_P 24
#define GO_P 6
#define P_POS 216
#define OR 6
#define OR0 0
#define B_LATE 23
#define H_LATE 24
#define RM0 1
#define RM1 0xab
#define RM2 0
#define PAIRB 1
#define LATE0 1
#define LATE1 2
#define GO_J 13
#define LATE_G 0
#define KG 5
#define PK 44
#define EARLY_MASK 0x3fffu
#define PIECE_TABLE 0x50188016,0x65e88038,0x50321819,0x6c8d1830,0x403f2812,0x80000000,0x50215014,0x695a503c,0x5029b813,0x6c4eb85e,0x501b4815,0x689d4834,0x502b1017,0x6ccc1039,0x50312010,0x80000000,0x500e681b,0x65e8683f,0x502ea011,0x80000000,0x63b1902e,0x80000000,0x63f0603b,0x80000000,0x64ad003d,0x80000000,0x64eca83a,0x80000000,0x5024581c,0x80000000,0x5012b01a,0x6a95b033,0x5011081d,0x6b130837,0x5016701f,0x6c8d7056,0x501ec81e,0x80000000,0x6723302f,0x80000000,0x501b380f,0x80000000,0x67234035,0x80000000,0x500d980e,0x6bd09831,0x56587816,0x80000000,0x50168818,0x80000000,0x57d1c01e,0x80000000

struct Params {
  CUtensorMap x[2][2], wq[2], kv[2][2], wo[2];
  CUtensorMap o_ld[2], o_st[2], out_st[2];
  const __nv_bfloat16* kp[2];
  const __nv_bfloat16* vp[2];
};

constexpr int NPART = 32 * 5, O_BLOCKS = NBETA * 64 + 2 * NPART;
__device__ __align__(128) __nv_bfloat16 g_o[(size_t)O_BLOCKS * SQ * 64];
__device__ unsigned g_cnt[NBETA][8];
__device__ unsigned g_rd[NBETA][8];
__device__ unsigned g_epoch, g_next;
__device__ unsigned g_flag[NPART];

__device__ __forceinline__ uint32_t smem_u32(const void* p) { return (uint32_t)__cvta_generic_to_shared(p); }
__device__ __forceinline__ void mbar_arrive(uint32_t bar) {
  asm volatile("mbarrier.arrive.shared::cta.b64 _, [%0];" ::"r"(bar) : "memory");
}
__device__ __forceinline__ void mbar_arrive_warp(uint32_t bar) {
  asm volatile("{\n.reg .pred p;\nelect.sync _|p, 0xffffffff;\n@p mbarrier.arrive.shared::cta.b64 _, [%0];\n}" ::"r"(bar) : "memory");
}
__device__ __forceinline__ int lane_now() { int l; asm volatile("mov.u32 %0, %%laneid;" : "=r"(l)); return l; }
__device__ __forceinline__ bool mbar_try(uint32_t bar, uint32_t parity) {
  uint32_t ok;
  asm volatile("{\n.reg .pred p;\nmbarrier.try_wait.parity.shared::cta.b64 p, [%1], %2;\nselp.u32 %0, 1, 0, p;\n}"
               : "=r"(ok) : "r"(bar), "r"(parity) : "memory");
  return ok;
}
__device__ __forceinline__ bool mbar_test(uint32_t bar, uint32_t parity) {
  uint32_t ok;
  asm volatile("{\n.reg .pred p;\nmbarrier.test_wait.parity.shared::cta.b64 p, [%1], %2;\nselp.u32 %0, 1, 0, p;\n}"
               : "=r"(ok) : "r"(bar), "r"(parity) : "memory");
  return ok;
}
__device__ __forceinline__ void mbar_wait_w(uint32_t bar, uint32_t parity) {
  uint32_t n = 0;
  while (!__all_sync(0xffffffffu, mbar_try(bar, parity))) {
    if (++n > (1u << 22)) __trap();
  }
}
#define ELECT "{\n.reg .pred p;\nelect.sync _|p, 0xffffffff;\n@p "
__device__ __forceinline__ void tma_st3_w(const CUtensorMap* m, uint32_t src, int c1, int c2) {
  asm volatile(ELECT "cp.async.bulk.tensor.3d.global.shared::cta.bulk_group [%0, {0, %2, %3}], [%1];\n}"
               ::"l"(m), "r"(src), "r"(c1), "r"(c2) : "memory");
}
#define EXPECT(bar, bytes) "mbarrier.arrive.expect_tx.shared::cta.b64 _, [" bar "], " bytes ";\n@p "
__device__ __forceinline__ void tma_ld2_w(uint32_t dst, const CUtensorMap* m, int c0, int c1, uint32_t bar, uint32_t bytes) {
  asm volatile(ELECT EXPECT("%2", "%5") "cp.async.bulk.tensor.2d.shared::cluster.global.mbarrier::complete_tx::bytes [%0], [%1, {%3, %4}], [%2];\n}"
               ::"r"(dst), "l"(m), "r"(bar), "r"(c0), "r"(c1), "r"(bytes) : "memory");
}
__device__ __forceinline__ void tma_ld2_hint_w(uint32_t dst, const CUtensorMap* m, int c0, int c1, uint32_t bar, uint32_t bytes, uint64_t pol) {
  asm volatile(ELECT EXPECT("%2", "%6") "cp.async.bulk.tensor.2d.shared::cluster.global.mbarrier::complete_tx::bytes.L2::cache_hint"
               " [%0], [%1, {%3, %4}], [%2], %5;\n}"
               ::"r"(dst), "l"(m), "r"(bar), "r"(c0), "r"(c1), "l"(pol), "r"(bytes) : "memory");
}
__device__ __forceinline__ void tma_ld3_w(uint32_t dst, const CUtensorMap* m, int c0, int c1, int c2, uint32_t bar, uint32_t bytes) {
  asm volatile(ELECT EXPECT("%2", "%6") "cp.async.bulk.tensor.3d.shared::cluster.global.mbarrier::complete_tx::bytes [%0], [%1, {%3, %4, %5}], [%2];\n}"
               ::"r"(dst), "l"(m), "r"(bar), "r"(c0), "r"(c1), "r"(c2), "r"(bytes) : "memory");
}
__device__ __forceinline__ void tma_ld_kv_w(uint32_t dst, const CUtensorMap* m, int grp, uint32_t bar, uint64_t pol) {
  asm volatile(ELECT EXPECT("%2", "16384") "cp.async.bulk.tensor.4d.shared::cluster.global.mbarrier::complete_tx::bytes.L2::cache_hint"
               " [%0], [%1, {0, 0, 0, %3}], [%2], %4;\n}"
               ::"r"(dst), "l"(m), "r"(bar), "r"(grp), "l"(pol) : "memory");
}
__device__ __forceinline__ void tma_ld_wo_w(uint32_t dst, const CUtensorMap* m, int col, int grp, uint32_t bar) {
  asm volatile(ELECT EXPECT("%2", "16384") "cp.async.bulk.tensor.5d.shared::cluster.global.mbarrier::complete_tx::bytes [%0], [%1, {%3, 0, 0, 0, %4}], [%2];\n"
               "@p cp.async.bulk.tensor.5d.shared::cluster.global.mbarrier::complete_tx::bytes [%5], [%1, {%6, 0, 0, 0, %4}], [%2];\n}"
               ::"r"(dst), "l"(m), "r"(bar), "r"(col), "r"(grp), "r"(dst + 8192), "r"(col + 64) : "memory");
}
__device__ __forceinline__ void mbar_arrive8_w(uint32_t bar) {
  asm volatile(ELECT "mbarrier.arrive.shared::cta.b64 _, [%0], 8;\n}" ::"r"(bar) : "memory");
}
__device__ __forceinline__ uint32_t peer(uint32_t a) { uint32_t r; asm("mapa.shared::cluster.u32 %0, %1, %2;" : "=r"(r) : "r"(a), "r"(~blockIdx.x & 1)); return r; }
__device__ __forceinline__ void tma_ld2_both_w(uint32_t dst, const CUtensorMap* m, int c0, int c1, uint32_t bar, uint32_t bytes) {
  asm volatile(ELECT EXPECT("%2", "%5") "cp.async.bulk.tensor.2d.shared::cluster.global.mbarrier::complete_tx::bytes.multicast::cluster"
               " [%0], [%1, {%3, %4}], [%2], %6;\n}"
               ::"r"(dst), "l"(m), "r"(bar), "r"(c0), "r"(c1), "r"(bytes), "h"((uint16_t)3) : "memory");
}
__device__ __forceinline__ void tma_ld2_both_hint_w(uint32_t dst, const CUtensorMap* m, int c0, int c1, uint32_t bar, uint32_t bytes, uint64_t pol) {
  asm volatile(ELECT EXPECT("%2", "%6") "cp.async.bulk.tensor.2d.shared::cluster.global.mbarrier::complete_tx::bytes.multicast::cluster.L2::cache_hint"
               " [%0], [%1, {%3, %4}], [%2], %7, %5;\n}"
               ::"r"(dst), "l"(m), "r"(bar), "r"(c0), "r"(c1), "l"(pol), "r"(bytes), "h"((uint16_t)3) : "memory");
}
__device__ __forceinline__ void bulk_commit() { asm volatile("cp.async.bulk.commit_group;" ::: "memory"); }
template <int N> __device__ __forceinline__ void bulk_wait_read() { asm volatile("cp.async.bulk.wait_group.read %0;" ::"n"(N) : "memory"); }
__device__ __forceinline__ void wg_fence() { asm volatile("wgmma.fence.sync.aligned;" ::: "memory"); }
__device__ __forceinline__ void wg_commit() { asm volatile("wgmma.commit_group.sync.aligned;" ::: "memory"); }
template <int N> __device__ __forceinline__ void wg_wait() { asm volatile("wgmma.wait_group.sync.aligned %0;" ::"n"(N) : "memory"); }
__device__ __forceinline__ void fence_async_smem() { asm volatile("fence.proxy.async.shared::cta;" ::: "memory"); }
__device__ __forceinline__ void bar_sync(int id, int n) { asm volatile("bar.sync %0, %1;" ::"r"(id), "r"(n) : "memory"); }
__device__ __forceinline__ void touch(float& a) { asm volatile("neg.f32 %0, %0;" : "+f"(a)); }
__device__ __forceinline__ void touch(uint32_t& a) { asm volatile("not.b32 %0, %0;" : "+r"(a)); }
template <typename T, int N> __device__ __forceinline__ void touch(T (&a)[N]) {
#pragma unroll
  for (int i = 0; i < N; i++) touch(a[i]);
}
template <int ID, typename... A> __device__ __forceinline__ void sched_fence(uint32_t x, A&... a) {
  if (!((SF >> ID) & 1)) return;
  asm volatile("" : "+r"(x)::"memory");
#pragma unroll 1
  for (; __builtin_expect(x >= 100 + ID, 0); x >>= 1) { (touch(a), ...); __nanosleep(x); }
}
template <int N> __device__ __forceinline__ void reg_fence(float (&a)[N]) {
#pragma unroll
  for (int i = 0; i < N; i++) asm volatile("" : "+f"(a[i])::"memory");
}
template <int N> __device__ __forceinline__ void reg_fence(uint32_t (&a)[N]) {
#pragma unroll
  for (int i = 0; i < N; i++) asm volatile("" : "+r"(a[i])::"memory");
}
__device__ __forceinline__ float ex2(float x) { float y; asm("ex2.approx.ftz.f32 %0, %1;" : "=f"(y) : "f"(x)); return y; }
__device__ __forceinline__ uint32_t pack_bf16(float lo, float hi) {
  uint32_t r; asm("cvt.rn.bf16x2.f32 %0, %1, %2;" : "=r"(r) : "f"(hi), "f"(lo)); return r;
}
__device__ __forceinline__ void stsm4(uint32_t a, uint32_t r0, uint32_t r1, uint32_t r2, uint32_t r3) {
  asm volatile("stmatrix.sync.aligned.m8n8.x4.shared.b16 [%0], {%1, %2, %3, %4};" ::"r"(a), "r"(r0), "r"(r1), "r"(r2), "r"(r3) : "memory");
}
__device__ __forceinline__ void stsm4t(uint32_t a, uint32_t r0, uint32_t r1, uint32_t r2, uint32_t r3) {
  asm volatile("stmatrix.sync.aligned.m8n8.x4.trans.shared.b16 [%0], {%1, %2, %3, %4};" ::"r"(a), "r"(r0), "r"(r1), "r"(r2), "r"(r3) : "memory");
}
__device__ __forceinline__ void ldsm4(uint32_t a, uint32_t& r0, uint32_t& r1, uint32_t& r2, uint32_t& r3) {
  asm volatile("ldmatrix.sync.aligned.m8n8.x4.shared.b16 {%0, %1, %2, %3}, [%4];" : "=r"(r0), "=r"(r1), "=r"(r2), "=r"(r3) : "r"(a) : "memory");
}
__device__ __forceinline__ void sts16(uint32_t a, uint32_t v) { asm volatile("st.shared.u16 [%0], %1;" ::"r"(a), "h"((uint16_t)v) : "memory"); }
__device__ __forceinline__ void mma16816(float& c0, float& c1, float& c2, float& c3, uint32_t a0, uint32_t a1, uint32_t a2, uint32_t a3,
                                         uint32_t b0, uint32_t b1) {
  asm volatile("mma.sync.aligned.m16n8k16.row.col.f32.bf16.bf16.f32 {%0, %1, %2, %3}, {%4, %5, %6, %7}, {%8, %9}, {%0, %1, %2, %3};"
               : "+f"(c0), "+f"(c1), "+f"(c2), "+f"(c3) : "r"(a0), "r"(a1), "r"(a2), "r"(a3), "r"(b0), "r"(b1));
}
__device__ __forceinline__ uint32_t sdesc(uint32_t addr, uint32_t lbo) { return (addr >> 4) + ((lbo >> 4) << 16); }
__device__ __forceinline__ uint64_t desc64(uint32_t lo, uint32_t hi) { uint64_t d; asm("mov.b64 %0, {%1, %2};" : "=l"(d) : "r"(lo), "r"(hi)); return d; }
__device__ __forceinline__ void dadd(uint64_t& d, uint32_t inc) {
  asm("{\n.reg .b32 l, h;\nmov.b64 {l, h}, %0;\nadd.u32 l, l, %1;\nmov.b64 %0, {l, h};\n}" : "+l"(d) : "r"(inc));
}

struct Ring {
  uint32_t slot, phase, xp;
  __device__ __forceinline__ void uniform() {
    slot = __shfl_sync(0xffffffffu, slot, 0); phase = __shfl_sync(0xffffffffu, phase, 0); xp = __shfl_sync(0xffffffffu, xp, 0);
  }
  __device__ __forceinline__ void next() { if (++slot == NS) { slot = 0; phase ^= 1; } }
  __device__ __forceinline__ void next_if(bool p) { slot += p; if (slot == NS) { slot = 0; phase ^= 1; } }
};
__device__ __forceinline__ uint32_t borrow(int ks, int n) {
  const int k = ks + 1;
  return k >= 4 && !(k & 2) && k < n ? k & 1 : 2;
}

constexpr uint32_t Q_RANGES = NBETA * NH + __builtin_popcount(EARLY_MASK) * 5, Q_ALL = NBETA * (NH + 5);
constexpr int NRANGE = NCTA / 5;
struct Work { int kind, mode, k0, nsteps, range, beta, sub; };
struct Sched { uint16_t queue[Q_ALL]; uint32_t piece[NRANGE + 1][4]; };
constexpr Sched make_sched() {
  Sched s{};
  int q = 0, a = 0;
  for (int t = 0, e = 0; a < NBETA * NH; t++) {
    for (; e < NBETA && 8 * (e & ~PAIRB) + PK <= t && a >= P_POS; e++)
      for (int col = 0; col < 5 && (EARLY_MASK >> e & 1); col++) s.queue[q++] = 0x8000 | (e & 1 ? 4 - col : col) << 8 | e;
    for (int b = 0; b < NBETA; b++)
      for (int h = 0; h < NH; h++)
        if ((b >= B_LATE && h >= H_LATE ? 300 + b + LATE_G * (h >> 2) : 8 * (b & ~PAIRB) + KG * (h >> 2)) == t) { s.queue[q++] = b << 5 | h; a++; }
  }
  for (int b = 0; b < NBETA; b++)
    for (int col = 0; col < 5 && !(EARLY_MASK >> b & 1); col++) s.queue[q++] = 0x8000 | col << 8 | b;
  constexpr uint32_t T[NRANGE * 2] = {PIECE_TABLE};
  for (int g = 0; g <= NRANGE; g++)
    for (int n = 0; n < 4; n++) s.piece[g][n] = g < NRANGE && n < 2 ? T[2 * g + n] : 2u << 30;
  return s;
}
__constant__ Sched c_sched = make_sched();
constexpr int N_EARLY = __builtin_popcount(EARLY_MASK);
constexpr bool reuse_ok() {
  const Sched s = make_sched();
  int first[NBETA + OR] = {};
  for (int q = Q_RANGES - 1; q >= 0; q--) if (!(s.queue[q] & 0x8000)) first[s.queue[q] >> 5] = q;
  for (int q = 0; q < Q_RANGES; q++) if ((s.queue[q] & 0x8000) && (s.queue[q] & 31) >= OR0 && q - first[(s.queue[q] & 31) + OR] > NCTA - 32) return false;
  return first[OR0 + OR] >= NCTA && P_POS >= NCTA;
}
static_assert(reuse_ok());
template <bool SIMPLE> __device__ __forceinline__ bool o_reuse(uint32_t b) { return !SIMPLE && b - (OR0 + OR) < N_EARLY - OR0; }
template <bool SIMPLE> __device__ __forceinline__ uint32_t o_slot(uint32_t b) { return o_reuse<SIMPLE>(b) ? OR0 + (b - OR0) % OR : b; }
__device__ __forceinline__ Work decode(uint32_t d) {
  Work w;
  w.kind = d >> 30; if (w.kind == 3) w.kind = 1;
  w.mode = (d >> 28) & 3; w.k0 = (d >> 22) & 63;
  if (w.kind == 0) { w.beta = (d >> 5) & 31; w.sub = d & 31; w.nsteps = DM / 64; }
  else { w.beta = d & 31; w.sub = (d >> 8) & 7; w.nsteps = ((d >> 16) & 63) + 1; }
  w.range = ((d >> 11) & 31) * 5 + w.sub;
  return w;
}

__device__ __forceinline__ bool reached(const unsigned* cnt, unsigned target) {
  unsigned v;
  asm volatile("ld.acquire.gpu.global.u32 %0, [%1];" : "=r"(v) : "l"(cnt) : "memory");
  return (int)(v - target) >= 0;
}
__device__ __forceinline__ void wait_count(const unsigned* cnt, unsigned target) {
  unsigned n = 0;
  while (!__all_sync(0xffffffffu, reached(cnt, target))) { if (++n > (1u << 24)) __trap(); }
}
__device__ __forceinline__ uint32_t lds(uint32_t a) { uint32_t v; asm volatile("ld.volatile.shared.u32 %0, [%1];" : "=r"(v) : "r"(a) : "memory"); return v; }

#define TRACE(u, e)
#define T3(u, e)
#define T2C(u, e)
#define T2P(u, r, e)
#define TTAIL(k)
#define TCLK(k)
#define TO -1
#define TRACE_O(k) if (TO == k) TRACE(i, 5)
#define TRACE_P(u, e)
#define TRACE_IN(u, e)

struct Ctx {
  uint32_t sb;
  int wg, warp;
  uint32_t mqk, mpv;
  bool lead;
  int lane0, lane;
  int src;
};
template <int N> __device__ __forceinline__ uint32_t dhi(uint32_t lo) { return 0x40000040u + (lo >> (26 + N)); }
__device__ __forceinline__ void release(const Ctx& c, uint32_t slot) {
  if (c.lead) mbar_arrive(c.sb + BAR_EMPTY + slot * 8);
}
__device__ __forceinline__ uint32_t acquire(const Ctx& c, Ring& r, bool have = false) {
  const uint32_t s = r.slot;
  if (!have) mbar_wait_w(c.sb + BAR_FULL + s * 8, r.phase);
  r.next();
  return s;
}
__device__ __forceinline__ void mbar_wait2_w(uint32_t b0, uint32_t p0, uint32_t b1, uint32_t p1) {
  uint32_t n = 0;
  while (!__all_sync(0xffffffffu, mbar_try(b0, p0) & mbar_try(b1, p1))) {
    if (++n > (1u << 22)) __trap();
  }
}
__device__ __forceinline__ void mbar_wait3_w(uint32_t b0, uint32_t p0, uint32_t b1, uint32_t p1, uint32_t b2, uint32_t p2) {
  uint32_t n = 0;
  while (!__all_sync(0xffffffffu, mbar_try(b0, p0) & mbar_try(b1, p1) & mbar_try(b2, p2))) {
    if (++n > (1u << 22)) __trap();
  }
}
__device__ __forceinline__ void acquire2(const Ctx& c, Ring& r, uint32_t& s0, uint32_t& s1, bool have = false) {
  const uint32_t p0 = r.phase;
  s0 = r.slot; r.next(); s1 = r.slot;
  if (!have) mbar_wait2_w(c.sb + BAR_FULL + s0 * 8, p0, c.sb + BAR_FULL + s1 * 8, r.phase);
  r.next();
}
template <int N>
__device__ __forceinline__ bool peek(const Ctx& c, Ring r) {
  bool ok = true;
#pragma unroll
  for (int k = 0; k < N; k++) { ok &= mbar_test(c.sb + BAR_FULL + r.slot * 8, r.phase); r.next(); }
  return ok;
}
__device__ __forceinline__ void staged(const Ctx& c, int part) {
  fence_async_smem();
  __syncwarp();
  mbar_arrive_warp(c.sb + BAR_STG + c.wg * 16 + part * 8);
}

template <int WG, bool FIRST, int H>
__device__ __forceinline__ void proj_half(const Ctx& c, float (&acc)[64], uint32_t w, uint32_t x, uint32_t sw) {
  uint64_t dx = desc64((SB0 + x * SLOT + (WG ? 0 : H * 8192)) >> 4, dhi<0>(x) + sw);
  uint64_t dw = desc64(WG ? (SB0 + w * SLOT + H * 8192) >> 4 : sdesc(SB0 + w * SLOT, 8192), dhi<1>(x));
  wg_fence();
  if (WG) { if (FIRST) wgmma_proj96_init(acc, dw, dx, 0); else wgmma_proj96(acc, dw, dx, 1); }
  else { if (FIRST) wgmma_proj_init(acc, dx, dw, 0); else wgmma_proj(acc, dx, dw, 1); }
#pragma unroll
  for (int k = 1; k < 4; k++) {
    dadd(dx, k == 2 ? 2 + (sw >> 30) * 28 : 2); dadd(dw, 128);
    if (WG) wgmma_proj96(acc, dw, dx, 1); else wgmma_proj(acc, dx, dw, 1);
  }
  wg_commit();
}

__device__ __forceinline__ void proj_store16(uint32_t a, const float* f, float sc) {
  stsm4t(a, pack_bf16(f[0] * sc, f[1] * sc), pack_bf16(f[2] * sc, f[3] * sc), pack_bf16(f[4] * sc, f[5] * sc), pack_bf16(f[6] * sc, f[7] * sc));
}

__device__ __forceinline__ uint32_t stage_off(const Ctx& c) {
  const int lane = c.lane, mi = lane >> 3, r8 = lane & 7;
  return ((mi >> 1) * 8 + r8) * 128 + (((2 * c.warp + (mi & 1)) ^ r8) << 4);
}
__device__ __forceinline__ uint32_t q3_swz(uint32_t r8) { return ((r8 & 3) << 1) | (r8 >> 2); }
template <int H>
__device__ __forceinline__ void stage_t2(const Ctx& c, const float (&a)[64], float sc) {
  const uint32_t base = c.sb + QBUF_OFF + 2 * 16384 + H * 8192 + stage_off(c);
#pragma unroll
  for (int jj = 0; jj < 4; jj++) proj_store16(base + jj * 2048, &a[jj * 8], sc);
}
template <int H, bool IS_Q>
__device__ __forceinline__ void stage_t3(const Ctx& c, const float (&a)[64], float sc) {
  const uint32_t off = stage_off(c), r8 = (off >> 7) & 7;
  const uint32_t t3 = c.sb + QBUF_OFF + 3 * 16384 + H * 4096 + (IS_Q ? off ^ ((r8 ^ q3_swz(r8)) << 4) : off);
  proj_store16(t3, &a[32], sc);
  proj_store16(t3 + 2048, &a[40], sc);
}

template <int WG, int h, int NW = 4>
__device__ __forceinline__ void load_part(const Ctx& c, Ring r, uint32_t (&q)[32]) {
  uint32_t n = 0;
  while (NW && !__all_sync(0xffffffffu, peek<NW>(c, r))) {
    if (++n > (1u << 26)) __trap();
  }
  const int lane = c.lane, mi = lane >> 3, r8 = lane & 7;
  if (WG) { r.next(); r.next(); }
  const uint32_t off = c.sb + (WG ? stage_off(c) : (16 * c.warp + (mi & 1) * 8 + r8) * 128), t0 = off + r.slot * SLOT;
  r.next();
  const uint32_t t1 = off + r.slot * SLOT;
#pragma unroll
    for (int jj = 0; jj < (WG ? 6 : 8); jj++) {
      uint32_t* p = &q[4 * jj];
      if (WG) asm volatile("ldmatrix.sync.aligned.m8n8.x4.trans.shared.b16 {%0, %1, %2, %3}, [%4];" : "=r"(p[0]), "=r"(p[1]), "=r"(p[2]), "=r"(p[3])
                           : "r"((jj < 4 ? t0 + h * 8192 : t1 + h * 4096) + (jj & 3) * 2048) : "memory");
      else ldsm4((h ? t1 : t0) + (jj >> 2) * 8192 + (((((2 * jj) & 7) + (mi >> 1)) ^ r8) << 4), p[0], p[1], p[2], p[3]);
    }
}
template <int WG>
__device__ __forceinline__ void add_part(const Ctx& c, const uint32_t (&q)[32], float (&a)[64]) {
  const uint32_t one = (c.lane >> 3) == (c.lane & 3) ? 0x3f80u << (c.lane & 4) * 4 : 0;
#pragma unroll
  for (int i = 0; i < (WG ? 12 : 16); i++)
    asm("mma.sync.aligned.m16n8k8.row.col.f32.bf16.bf16.f32 {%0, %1, %2, %3}, {%4, %5}, {%6}, {%0, %1, %2, %3};"
        : "+f"(a[4 * i]), "+f"(a[4 * i + 1]), "+f"(a[4 * i + 2]), "+f"(a[4 * i + 3]) : "r"(q[2 * i]), "r"(q[2 * i + 1]), "r"(one));
}

__device__ __forceinline__ void trace_dump(const Ctx& c) {
}
struct RowSum { float l0, l1; };
__device__ __forceinline__ const char* o_addr(uint32_t item, int row, int lane) {
  return reinterpret_cast<const char*>(g_o) + (((item >> 10) * (2 * SQ) + row) * 128 + (lane ^ (lane >> 3)) * 16);
}
__device__ __forceinline__ void o_stg(const char* p, int i, const uint32_t* q) {
  asm volatile("st.global.v4.b32 [%0], {%1, %2, %3, %4};"
               ::"l"(p + (i >> 1) * (SQ * 128) + (i & 1) * 512), "r"(q[0]), "r"(q[1]), "r"(q[2]), "r"(q[3]) : "memory");
}
template <int MODE, int I0 = 0, int NI = 4>
__device__ __forceinline__ void o_emit(const char* p, const float (&o)[64], float inv) {
#pragma unroll
  for (int i = I0; i < I0 + NI; i++) {
    uint32_t q[4];
#pragma unroll
    for (int j = 0; j < 4; j++) q[j] = pack_bf16(o[16 * i + 4 * j + 2 * MODE] * inv, o[16 * i + 4 * j + 2 * MODE + 1] * inv);
    o_stg(p, i, q);
  }
}
__device__ __forceinline__ void o_done(const Ctx& c) {
  __syncwarp();
  mbar_arrive_warp(c.sb + BAR_OUT);
  __syncwarp();
}
template <int WG>
__device__ __forceinline__ void o_first(const Ctx& c, uint32_t item, float (&o)[64], const RowSum& inv, uint32_t (&q)[32]) {
  const char* p = o_addr(item, WG ? 192 + 8 * c.warp : 64 + 16 * c.warp, c.lane);
  reg_fence(o);
#pragma unroll
  for (int j = 0; j < 16; j++) {
    if (WG) q[j] = pack_bf16((o[4 * j] + o[4 * j + 2]) * inv.l0, (o[4 * j + 1] + o[4 * j + 3]) * inv.l0);
    else q[j] = pack_bf16(o[4 * j] * inv.l0, o[4 * j + 1] * inv.l0);
    if (!WG && (j & 3) == 3 && (j >> 2) < 8 - LATE0) o_stg(p, j >> 2, q + j - 3);
  }
#pragma unroll
  for (int j = 0; j < 16; j++) {
    if (!WG) q[16 + j] = pack_bf16(o[4 * j + 2] * inv.l1, o[4 * j + 3] * inv.l1);
    if ((j & 3) == 3 && (j >> 2) < 4 - (WG ? LATE1 : LATE0)) o_stg(WG ? p : p + 1024, j >> 2, q + (WG ? 0 : 16) + j - 3);
  }
}
template <int WG>
__device__ __forceinline__ void o_rest(const Ctx& c, uint32_t item, uint32_t (&q)[32]) {
  const char* p = o_addr(item, WG ? 192 + 8 * c.warp : 64 + 16 * c.warp, c.lane);
#pragma unroll
  for (int i = WG ? 4 - LATE1 : 8 - LATE0; i < (WG ? 4 : 8); i++) o_stg(p + (i >> 2) * 1024, i & 3, q + 4 * i);
}
template <int K0, int K1>
__device__ __forceinline__ void o_piece(const Ctx& c, const char* p, int k, const float (&o)[64], const RowSum& inv) {
  constexpr int NI = 8 / O_STEPS, M = K0 * NI / 4;
  if constexpr (K1 - K0 == 1) {
    o_emit<M, K0 * NI % 4, NI>(p + M * 1024, o, M ? inv.l1 : inv.l0);
    if (K1 == O_STEPS) o_done(c);
  } else {
    if (k <= (K0 + K1) / 2) o_piece<K0, (K0 + K1) / 2>(c, p, k, o, inv); else o_piece<(K0 + K1) / 2, K1>(c, p, k, o, inv);
  }
}
template <int WG>
__device__ __forceinline__ void o_second(const Ctx& c, uint32_t item, int k, float (&o)[64], const RowSum& inv) {
  reg_fence(o);
  o_piece<0, O_STEPS>(c, o_addr(item, 128 * WG + 16 * c.warp, c.lane0 + (k >> 8)), k, o, inv);
}
template <int WG>
__device__ __forceinline__ void release_q(const Ctx& c) {
#pragma unroll
  for (int t = 0; t < 2; t++)
    if (c.lead) asm volatile("mbarrier.arrive.shared::cta.b64 _, [%0], 2;" ::"r"(c.sb + BAR_EMPTY + (NS + 2 * WG + t) * 8) : "memory");
  __syncwarp();
}
struct Slots { uint32_t w, x, o, po; };
template <int WG>
__device__ __forceinline__ void acc_fence(float (&a)[64]) {
#pragma unroll
  for (int i = 0; i < (WG ? 48 : 64); i++) asm volatile("" : "+f"(a[i])::"memory");
}
template <int WG>
__device__ __forceinline__ void begin_acquire(const Ctx& c, Ring& r, Slots& h, bool wait) {
  const uint32_t s0 = r.slot, p0 = r.phase, f = c.sb + BAR_FULL;
  r.next();
  const uint32_t p1 = r.phase;
  h.w = r.slot; r.next();
  h.x = WG ? r.slot : s0; h.o = WG ? s0 : r.slot; h.po = r.phase;
  if (wait) { if (WG) mbar_wait3_w(f + s0 * 8, p0, f + h.w * 8, p1, f + h.x * 8, r.phase); else mbar_wait2_w(f + s0 * 8, p0, f + h.w * 8, p1); }
  r.next();
}
template <int WG>
__device__ __forceinline__ void proj_begin(const Ctx& c, Ring& r, float (&a0)[64], Slots& h, bool wait, uint32_t sw) {
  begin_acquire<WG>(c, r, h, wait);
  proj_half<WG, true, 0>(c, a0, h.w, h.x, sw);
  if (WG) release(c, h.o);
}
template <int WG>
__device__ __forceinline__ void proj_main(Ctx& c, Ring& r, float (&a0)[64], float (&a1)[64], Slots& h, int n, uint32_t sw, int unit,
                                          uint32_t item, int nq, float (&o1)[64], const RowSum& inv) {
  constexpr bool DEEP = (PDEPTH >> WG) & 1;
  T2C(unit, 3);
  int ks = 1;
#pragma unroll 1
  do {
    const Slots p = h;
    const uint32_t b = borrow(ks, n), tile = NS + (WG ? 3 - b : b), f = c.sb + BAR_FULL;
    const uint32_t s0 = b != 2 ? tile : r.slot, p0 = b != 2 ? (r.xp >> b) & 1 : r.phase;
    r.next_if(b == 2);
    const uint32_t p1 = r.phase;
    h.w = r.slot; r.next();
    const uint32_t s2 = b != 2 ? tile : r.slot;
    h.po = b != 2 ? p0 : r.phase;
    r.next_if(b == 2);
    r.xp ^= 1 << b;
    h.x = WG ? s2 : s0; h.o = WG ? s0 : s2;
    mbar_wait3_w(f + s0 * 8, p0, f + h.w * 8, p1, f + (WG ? s2 : p.o) * 8, WG ? h.po : p.po);
    if (ks < 10) T2C(unit, ks * 4);
    if (DEEP) {
      proj_half<WG, false, 0>(c, a0, h.w, h.x, sw);
      release(c, WG ? h.o : p.o);
      if (ks < 10) T2C(unit, ks * 4 + 1);
      wg_wait<1>();
      if (ks < 10) T2C(unit, ks * 4 + 2);
      release(c, p.x); release(c, p.w);
    } else {
      release(c, WG ? h.o : p.o);
      wg_wait<0>();
      release(c, p.x); release(c, p.w);
      if (ks < 10) T2C(unit, ks * 4 + 1);
      proj_half<WG, false, 0>(c, a0, h.w, h.x, sw);
      if (ks < 10) T2C(unit, ks * 4 + 2);
    }
    proj_half<WG, false, 1>(c, a1, h.w, h.x, sw);
    if (ks < 10) T2C(unit, ks * 4 + 3);
    if (ks <= nq) o_second<WG>(c, item, ks, o1, inv);
  } while (++ks != n);
  {
    const uint32_t e0 = c.sb + BAR_EMPTY + (NS + 3 * WG) * 8, e1 = c.sb + BAR_EMPTY + (NS + 1 + WG) * 8;
    const uint32_t p0 = (r.xp ^ unit ^ 1) & 1, p1 = ((r.xp >> 1) ^ unit ^ 1) & 1;
    const uint32_t k0 = sw ? e0 : c.sb + BAR_FULL + r.slot * 8, pk = sw ? p0 : r.phase;
    uint32_t cnt = 0;
    while (!__all_sync(0xffffffffu, mbar_try(e0, p0) & mbar_try(e1, p1) & mbar_try(k0, pk) & (WG || mbar_try(c.sb + BAR_FULL + h.o * 8, h.po)))) {
      if (++cnt > (1u << 22)) __trap();
    }
  }
  c.lane = c.lane0 + (h.w >> 5);
  if (!WG) release(c, h.o);
}
template <int WG>
__device__ __forceinline__ void proj_end(const Ctx& c, float (&a1)[64], const Slots& h) {
  wg_wait<0>();
  acc_fence<WG>(a1);
  release(c, h.x); release(c, h.w);
}
__device__ __forceinline__ uint32_t get_desc(const Ctx& c, int i) {
  uint32_t d;
  mbar_wait_w(c.sb + BAR_DESC, (i - 1) & 1);
  asm volatile("ld.volatile.shared.u32 %0, [%1];" : "=r"(d) : "r"(c.sb + DESC_OFF + (i & 3) * 4) : "memory");
  return __shfl_sync(0xffffffffu, d, 0);
}

__device__ __forceinline__ float quad_max(float x) {
  x = fmaxf(x, __shfl_xor_sync(0xffffffffu, x, 1));
  return fmaxf(x, __shfl_xor_sync(0xffffffffu, x, 2));
}
__device__ __forceinline__ float quad_sum(float x) {
  x += __shfl_xor_sync(0xffffffffu, x, 1);
  return x + __shfl_xor_sync(0xffffffffu, x, 2);
}
template <bool SP, bool FIRST>
__device__ __forceinline__ void exps(const Ctx& c, const float (&s)[32], uint32_t (&p)[SP ? 8 : 16], RowSum& st) {
  if constexpr (SP) {
    uint32_t q[8];
    float t;
#pragma unroll
    for (int j = 0; j < 8; j++) {
      const float e0 = ex2(s[4 * j] + s[4 * j + 2]), e1 = ex2(s[4 * j + 1] + s[4 * j + 3]);
      if (j == 0) t = e0 + e1; else t += e0 + e1;
      q[j] = pack_bf16(e0, e1);
    }
    const bool odd = c.src & 2;
#pragma unroll
    for (int g = 0; g < 4; g++) {
      p[2 * g] = __shfl_sync(0xffffffffu, odd ? q[2 * g + 1] : q[2 * g], c.src);
      p[2 * g + 1] = __shfl_sync(0xffffffffu, odd ? q[2 * g] : q[2 * g + 1], c.src ^ 1);
    }
    st.l0 = FIRST ? t : st.l0 + t;
  } else {
    float t0, t1;
#pragma unroll
    for (int j = 0; j < 8; j++) {
      const float e0 = ex2(s[4 * j]), e1 = ex2(s[4 * j + 1]), e2 = ex2(s[4 * j + 2]), e3 = ex2(s[4 * j + 3]);
      if (j == 0) { t0 = e0 + e1; t1 = e2 + e3; } else { t0 += e0 + e1; t1 += e2 + e3; }
      p[2 * j] = pack_bf16(e0, e1);
      p[2 * j + 1] = pack_bf16(e2, e3);
    }
    st.l0 = FIRST ? t0 : st.l0 + t0;
    st.l1 = FIRST ? t1 : st.l1 + t1;
  }
}
template <bool SP>
__device__ __forceinline__ bool finish_sums(RowSum& st) {
  const float a = quad_sum(st.l0), b = SP ? a : quad_sum(st.l1);
  st.l0 = __fdividef(1.f, a); st.l1 = __fdividef(1.f, b);
  return !(a >= SUM_LO && a <= SUM_HI && b >= SUM_LO && b <= SUM_HI);
}
template <bool SP, bool INIT, int SITE, bool COMMIT = true, int RM = 0>
__device__ __forceinline__ void issue_qk(const Ctx& c, float (&s)[32], const uint32_t (&qs)[32], uint32_t dq, uint32_t dk) {
  uint64_t a = desc64(dq, dhi<SITE & 1>(dk)), b = desc64(dk, dhi<1 - (SITE & 1)>(dk) + 64);
  if (SP) {
    if (INIT) wgmma_qk_sp_init(s, qs[0], qs[1], qs[2], qs[3], b, 0, c.mqk); else wgmma_qk_sp(s, qs[0], qs[1], qs[2], qs[3], b, 0, c.mqk);
#pragma unroll
    for (int k = 1; k < 4; k++) { dadd(b, k == 2 ? 60 : 4); wgmma_qk_sp(s, qs[4 * k], qs[4 * k + 1], qs[4 * k + 2], qs[4 * k + 3], b, 1, c.mqk); }
  } else {
    if (RM & 1) wgmma_qk_rs(s, qs[0], qs[1], qs[2], qs[3], b, 0); else if (INIT) wgmma_qk_init(s, a, b, 0); else wgmma_qk(s, a, b, 0);
#pragma unroll
    for (int k = 1; k < 8; k++) {
      dadd(a, k == 4 ? 506 : 2); dadd(b, k == 4 ? 58 : 2);
      if (RM >> k & 1) wgmma_qk_rs(s, qs[4 * k], qs[4 * k + 1], qs[4 * k + 2], qs[4 * k + 3], b, 1); else wgmma_qk(s, a, b, 1);
    }
  }
  if (COMMIT) wg_commit();
}
template <bool SP, bool ACC, int SITE, bool SPLIT = false>
__device__ __forceinline__ void issue_pv(const Ctx& c, float (&o)[64], const uint32_t (&p)[SP ? 8 : 16], uint32_t dv) {
  uint64_t b = desc64(dv, dhi<SITE & 1>(dv) + 64);
  if constexpr (SP) {
    if (ACC) wgmma_pv_sp(o, p[0], p[1], p[2], p[3], b, 1, c.mpv); else wgmma_pv_sp_init(o, p[0], p[1], p[2], p[3], b, 0, c.mpv);
    if (SPLIT) wg_commit();
    dadd(b, 512);
    wgmma_pv_sp(o, p[4], p[5], p[6], p[7], b, 1, c.mpv);
  } else {
    if (ACC) wgmma_pv(o, p[0], p[1], p[2], p[3], b, 1); else wgmma_pv_init(o, p[0], p[1], p[2], p[3], b, 0);
#pragma unroll
    for (int k = 1; k < 4; k++) { dadd(b, 256); wgmma_pv(o, p[4 * k], p[4 * k + 1], p[4 * k + 2], p[4 * k + 3], b, 1); }
  }
  wg_commit();
}
__device__ __forceinline__ void pack_rows(const float (&o)[64], float sc, uint32_t (&q)[32]) {
#pragma unroll
  for (int j = 0; j < 32; j++) q[j] = pack_bf16(o[2 * j] * sc, o[2 * j + 1] * sc);
}
template <int MASK = 255>
__device__ __forceinline__ void stage_rows(const Ctx& c, uint32_t tile_addr, const uint32_t (&q)[32]) {
  const int lane = c.lane, mi = lane >> 3, r8 = lane & 7;
  const uint32_t row_addr = tile_addr + (16 * c.warp + (mi & 1) * 8 + r8) * 128;
#pragma unroll
  for (int jj = 0; jj < 8; jj++)
    if (MASK >> jj & 1) stsm4(row_addr + (jj >> 2) * 8192 + (((((2 * jj) & 7) + (mi >> 1)) ^ r8) << 4), q[4 * jj], q[4 * jj + 1], q[4 * jj + 2], q[4 * jj + 3]);
}
__device__ __forceinline__ void stage_rows(const Ctx& c, uint32_t tile_addr, const float (&o)[64], float sc) {
  uint32_t q[32];
  pack_rows(o, sc, q);
  stage_rows(c, tile_addr, q);
}
template <int WG, int H>
__device__ __forceinline__ void stage_out(const Ctx& c, const float (&a)[64]) {
  if (WG) { stage_t3<H, false>(c, a, 1.f); if (H) staged(c, 0); stage_t2<H>(c, a, 1.f); }
  else stage_rows(c, c.sb + QBUF_OFF + H * 16384, a, 1.f);
  if (H || !WG) staged(c, H);
}
template <int SITE>
__device__ __forceinline__ void issue_qk_rs(float (&s)[32], uint32_t (&q)[32], uint32_t dk) {
  uint64_t b = desc64(dk, dhi<SITE>(dk) + 64);
  reg_fence(q);
  wg_fence();
  wgmma_qk_rs_init(s, q[0], q[1], q[2], q[3], b, 0);
#pragma unroll
  for (int k = 1; k < 8; k++) { dadd(b, k == 4 ? 58 : 2); wgmma_qk_rs(s, q[4 * k], q[4 * k + 1], q[4 * k + 2], q[4 * k + 3], b, 1); }
  wg_commit();
}

__device__ __forceinline__ void redo_tile(const Ctx& c, uint32_t q_addr, uint32_t half, const __nv_bfloat16* kp, const __nv_bfloat16* vp,
                                          uint32_t item, int row) {
  float o[64];
  const int lane = lane_now(), g = lane >> 2, cc = lane & 3, mi = lane >> 3, r8 = lane & 7;
  const uint32_t qa = q_addr + (half == 4096 ? 8 * c.warp + r8 : 16 * c.warp + (mi & 1) * 8 + r8) * 128, swz = half == 4096 ? q3_swz(r8) : r8;
  const uint32_t* kq = reinterpret_cast<const uint32_t*>(kp + g * DH) + cc;
  const unsigned short* vq = reinterpret_cast<const unsigned short*>(vp + 2 * cc * DH) + g;
  float m0 = -INFINITY, m1 = -INFINITY, l0 = 0.f, l1 = 0.f;
#pragma unroll
  for (int i = 0; i < 64; i++) o[i] = 0.f;
#pragma unroll 1
  for (int kb = 0; kb < SK / 16; kb++) {
    float z[8] = {0.f, 0.f, 0.f, 0.f, 0.f, 0.f, 0.f, 0.f};
#pragma unroll 2
    for (int kk = 0; kk < 8; kk++) {
      uint32_t a0, a1, a2, a3;
      ldsm4(qa + (kk >> 2) * half + ((((kk & 3) * 2 + (mi >> 1)) ^ swz) << 4), a0, a1, a2, a3);
      const uint32_t* kr = kq + kb * (16 * DH / 2) + kk * 8;
      mma16816(z[0], z[1], z[2], z[3], a0, a1, a2, a3, __ldg(kr), __ldg(kr + 4));
      mma16816(z[4], z[5], z[6], z[7], a0, a1, a2, a3, __ldg(kr + 8 * DH / 2), __ldg(kr + 8 * DH / 2 + 4));
    }
    const float n0 = fmaxf(m0, quad_max(fmaxf(fmaxf(z[0], z[1]), fmaxf(z[4], z[5]))));
    const float n1 = fmaxf(m1, quad_max(fmaxf(fmaxf(z[2], z[3]), fmaxf(z[6], z[7]))));
    const float al0 = ex2(m0 - n0), al1 = ex2(m1 - n1);
    m0 = n0; m1 = n1;
#pragma unroll
    for (int i = 0; i < 8; i++) z[i] = ex2(z[i] - ((i & 2) ? n1 : n0));
    l0 = l0 * al0 + (z[0] + z[1]) + (z[4] + z[5]);
    l1 = l1 * al1 + (z[2] + z[3]) + (z[6] + z[7]);
    const uint32_t a0 = pack_bf16(z[0], z[1]), a1 = pack_bf16(z[2], z[3]), a2 = pack_bf16(z[4], z[5]), a3 = pack_bf16(z[6], z[7]);
    const unsigned short* vr = vq + kb * (16 * DH);
#pragma unroll
    for (int nb = 0; nb < 16; nb++) {
      o[4 * nb] *= al0; o[4 * nb + 1] *= al0; o[4 * nb + 2] *= al1; o[4 * nb + 3] *= al1;
      const uint32_t b0 = __ldg(vr + nb * 8) | ((uint32_t)__ldg(vr + nb * 8 + DH) << 16);
      const uint32_t b1 = __ldg(vr + nb * 8 + 8 * DH) | ((uint32_t)__ldg(vr + nb * 8 + 9 * DH) << 16);
      mma16816(o[4 * nb], o[4 * nb + 1], o[4 * nb + 2], o[4 * nb + 3], a0, a1, a2, a3, b0, b1);
    }
  }
  const char* p = o_addr(item, row, lane);
  o_emit<0>(p, o, __fdividef(1.f, quad_sum(l0)));
  o_emit<1>(half == 4096 ? p : p + 1024, o, __fdividef(1.f, quad_sum(l1)));
}

template <bool SPA, bool SPB, int SITE, int ID>
__device__ __forceinline__ void batch(const Ctx& c, float (&s)[32], const uint32_t (&qs)[32], uint32_t dq, uint32_t dk, float (&ob)[64],
                                      uint32_t (&pb)[SPB ? 8 : 16], uint32_t dv) {
  if constexpr (SPA) {
    reg_fence(pb);
    wg_fence();
    issue_pv<SPB, true, ID>(c, ob, pb, dv);
    issue_qk<SPA, false, ID>(c, s, qs, dq, dk);
  } else {
    constexpr bool EARLY = ((QK_EARLY_MASK >> (SITE + (SPB ? 2 : 0))) & 1) != 0;
    if (!EARLY) reg_fence(pb);
    wg_fence();
    issue_qk<SPA, false, ID, !SPB, SITE ? RM0 : SPB ? RM2 : RM1>(c, s, qs, dq, dk);
    if (EARLY) { reg_fence(pb); wg_fence(); }
    issue_pv<SPB, true, ID, SPB>(c, ob, pb, dv);
  }
}

template <bool SP0>
__device__ __forceinline__ bool attention(Ctx& c, Ring& r, int unit, uint32_t& d, const float (&a0)[64], float (&o0)[64], float (&o1)[64],
                                          RowSum& st0, RowSum& st1, const Slots& h, uint32_t (&q1)[32]) {
  constexpr bool SP1 = false;
  if (SP0) { c.mqk = META_QK + (d >> 28); c.mpv = META_PV + (d >> 28); asm volatile("" : "+r"(c.mqk), "+r"(c.mpv)); }
  if (SP0) c.src = (c.lane & 28) | ((c.lane & 1) << 1) | ((c.lane >> 1) & 1);
  float s[32];
  uint32_t p0[SP0 ? 8 : 16], p1[16];
  const uint32_t q0a = c.sb + QBUF_OFF + (SP0 ? 3 : 0) * 16384, q1a = c.sb + QBUF_OFF + (SP0 ? 2 : 1) * 16384;
  const uint32_t dq0 = sdesc(SB0 + QBUF_OFF, 0), dq1 = sdesc(SB0 + QBUF_OFF + (SP0 ? 2 : 1) * 16384, 0);
  uint32_t sk = acquire(c, r, true), sv, sn;
  uint32_t qs[32];
  float s1[32];
  if (SP0) {
    stage_t3<0, true>(c, a0, SM_C);
    stage_t2<0>(c, a0, SM_C);
    proj_end<1>(c, o0, h);
    stage_t3<1, true>(c, o0, SM_C);
    stage_t2<1>(c, o0, SM_C);
    bar_sync(5, 128);
    const int g = c.lane >> 2, cc = c.lane & 3;
    const uint32_t qa = q0a + (8 * c.warp + g) * 128 + (cc & 1) * 8;
#pragma unroll
    for (int k = 0; k < 8; k++)
      asm volatile("ld.shared.v2.u32 {%0, %1}, [%2];" : "=r"(qs[2 * k]), "=r"(qs[2 * k + 1])
                   : "r"(qa + (k >> 2) * 4096 + ((((k & 3) * 2 + (cc >> 1)) ^ q3_swz(g)) << 4)) : "memory");
    fence_async_smem();
    bar_sync(1, 256);
    TRACE(unit, 2);
    wg_fence();
    issue_qk<SP1, true, 1>(c, s1, qs, dq1, sdesc(SB0 + sk * SLOT, 0));
#pragma unroll
    for (int k = 0; k < 8; k++)
      if (RM2 >> k & 1) ldsm4(q1a + (k >> 2) * 8192 + (16 * c.warp + (c.lane & 15)) * 128 + (((2 * (k & 3) + (c.lane >> 4)) ^ (c.lane & 7)) << 4),
                              q1[4 * k], q1[4 * k + 1], q1[4 * k + 2], q1[4 * k + 3]);
#pragma unroll
    for (int k = 0; k < 16; k++) asm volatile("" : "+r"(qs[k])::"memory");
    wg_fence();
    issue_qk<SP0, true, 0>(c, s, qs, dq0, sdesc(SB0 + sk * SLOT, 0));
    const bool have = peek<2>(c, r);
    wg_wait<1>();
    reg_fence(s1);
    exps<SP1, true>(c, s1, p1, st1);
    sched_fence<11>(sk, p1);
    acquire2(c, r, sv, sn, __all_sync(0xffffffffu, have));
    wg_wait<0>();
    wg_fence();
    issue_pv<SP1, false, 1>(c, o1, p1, sdesc(SB0 + sv * SLOT, 1024));
    if (LAG_BAR & 1) asm volatile("bar.arrive 4, 256;" ::: "memory");
    sched_fence<12>(sk, s);
    release(c, sk);
    sk = sn;
    exps<SP0, true>(c, s, p0, st0);
    reg_fence(p0);
    wg_fence();
    issue_pv<SP0, false, 0>(c, o0, p0, sdesc(SB0 + sv * SLOT, 1024));
    issue_qk<SP0, true, 2>(c, s, qs, dq0, sdesc(SB0 + sk * SLOT, 0));
    sn = acquire(c, r);
    wg_wait<0>();
    reg_fence(s);
  } else {
    pack_rows(a0, SM_C, qs);
    stage_rows(c, q0a, qs);
    proj_end<0>(c, o1, h);
    TRACE(unit, 2);
    float sc = SM_C;
    issue_qk_rs<0>(s, qs, sdesc(SB0 + sk * SLOT, 0));
    sched_fence<0>(sk, sc);
    pack_rows(o1, sc, q1);
    stage_rows<~RM1>(c, q1a, q1);
    issue_qk_rs<1>(s1, q1, sdesc(SB0 + sk * SLOT, 0));
    asm volatile("bar.arrive 1, 256;" ::: "memory");
    bool have = peek<2>(c, r);
    wg_wait<1>();
    reg_fence(s);
    exps<SP0, true>(c, s, p0, st0);
    sched_fence<1>(sk, p0);
    acquire2(c, r, sv, sn, __all_sync(0xffffffffu, have));
    wg_wait<0>();
    reg_fence(s1);
    fence_async_smem();
    __syncwarp();
    wg_fence();
    issue_qk<SP0, false, 2, true, RM0>(c, s, qs, dq0, sdesc(SB0 + sn * SLOT, 0));
    issue_pv<SP0, false, 0>(c, o0, p0, sdesc(SB0 + sv * SLOT, 1024));
    sched_fence<2>(sk, s1);
    release(c, sk);
    have = peek<1>(c, r);
    sk = sn;
    exps<SP1, true>(c, s1, p1, st1);
    reg_fence(p1);
    wg_fence();
    issue_pv<SP1, false, 1>(c, o1, p1, sdesc(SB0 + sv * SLOT, 1024));
    sn = acquire(c, r, __all_sync(0xffffffffu, have));
    if (LAG_BAR & 1) bar_sync(4, 256);
    wg_wait<1>();
    reg_fence(s);
  }
  TRACE_IN(unit, 4);
  T2C(unit, 51);
#pragma unroll 1
  for (int j = 1; j < 15; j++) {
    const uint32_t sv_prev = sv, sk_prev = sk;
    sv = sn;
    const uint32_t dv = sdesc(SB0 + sv * SLOT, 1024);
    reg_fence(p0);
    exps<SP0, false>(c, s, p0, st0);
    batch<SP1, SP0, 0, 3>(c, s, q1, dq1, sdesc(SB0 + sk * SLOT, 0), o0, p0, dv);
    sk = acquire(c, r);
    wg_wait<1>();
    reg_fence(s); reg_fence(p1);
    release(c, sv_prev); release(c, sk_prev);
    exps<SP1, false>(c, s, p1, st1);
    batch<SP0, SP1, 1, 4>(c, s, qs, dq0, sdesc(SB0 + sk * SLOT, 0), o1, p1, dv);
    sn = acquire(c, r);
    if (SP0) wg_wait<0>(); else wg_wait<1>();
    reg_fence(s);
  }
  TRACE_IN(unit, 5);
  T2C(unit + 1, 52);
  const uint32_t sv_prev = sv;
  sv = sn;
  const uint32_t dv = sdesc(SB0 + sv * SLOT, 1024);
  reg_fence(p0);
  exps<SP0, false>(c, s, p0, st0);
  batch<SP1, SP0, 0, 5>(c, s, q1, dq1, sdesc(SB0 + sk * SLOT, 0), o0, p0, dv);
  asm volatile("ld.volatile.shared.u32 %0, [%1];" : "=r"(d) : "r"(c.sb + DESC_OFF + ((unit + 1) & 3) * 4) : "memory");
  const bool have = peek<2 + SP0>(c, r);
  wg_wait<1>();
  reg_fence(s); reg_fence(p1);
  release(c, sv_prev); release(c, sk);
  exps<SP1, false>(c, s, p1, st1);
  reg_fence(p1);
  wg_fence();
  issue_pv<SP1, true, 2>(c, o1, p1, dv);
  if (SP0) sched_fence<6>(sk, st0.l0, st1.l0, st1.l1); else sched_fence<5>(sk, st0.l0, st0.l1, st1.l0, st1.l1);
  c.lane = c.lane0 + (sk >> 5);
  const bool bad = finish_sums<SP0>(st0) | finish_sums<SP1>(st1);
  uint32_t any;
  asm volatile("{\n.reg .pred p, q;\nsetp.ne.u32 p, %1, 0;\nbar.red.or.pred q, %2, 128, p;\nselp.u32 %0, 1, 0, q;\n}"
               : "=r"(any) : "r"((uint32_t)bad), "n"(2 + SP0) : "memory");
  any = __any_sync(0xffffffffu, any);
  d = __shfl_sync(0xffffffffu, d, 0);
  if (d < (2u << 30) && !__all_sync(0xffffffffu, have)) { Ring t = r; Slots u; begin_acquire<SP0>(c, t, u, true); }
  wg_wait<0>();
  reg_fence(o0); reg_fence(o1);
  release(c, sv);
  return any;
}

template <int WG>
__device__ __forceinline__ void consumer(Ctx c, const __nv_bfloat16* const* kv) {
  asm volatile("setmaxnreg.inc.sync.aligned.u32 %0;" ::"n"(WG ? REG_C : 504 - REG_C - REG_P));
  c.wg = WG;
  Ring r{0, 0, 0};
  float a0[64], a1[64], o1[64];
  Slots h;
  RowSum inv0, inv1;
  uint32_t oq[32];
  uint32_t d = c_sched.queue[blockIdx.x] * 1025, dc = 0, sw;
  int i = 0, nq;
begin:
  sw = d & (1u << 30);
  proj_begin<WG>(c, r, a0, h, true, sw);
  proj_half<WG, true, 1>(c, a1, h.w, h.x, sw);
  nq = 0;
#pragma unroll
  for (int k = 0; k < 64; k++) asm volatile("" : "=f"(o1[k]));
  asm volatile("" : "=f"(inv1.l0), "=f"(inv1.l1));
  while (true) {
    TRACE(i, 0); TRACE(i, 6);
    proj_main<WG>(c, r, a0, a1, h, d >> 30 ? ((d >> 16) & 63) + 1 : DM / 64, sw, i, dc, nq, o1, inv1);
    dc = d;
    TRACE(i, 1);
    if (d >> 30) goto out_tile;
    wg_wait<1>();
    acc_fence<WG>(a0);
    if (WG ? attention<WG>(c, r, i, d, a0, a1, o1, inv0, inv1, h, oq) : attention<WG>(c, r, i, d, a0, o1, a1, inv1, inv0, h, oq)) goto redo;
    if (d >= (2u << 30)) break;
    sw = d & (1u << 30);
    proj_begin<WG>(c, r, a0, h, false, sw);
    release_q<WG>(c);
    if (WG) sched_fence<8>(h.w, inv0.l0); else sched_fence<7>(h.w, inv0.l0, inv0.l1);
    o_first<WG>(c, dc, a1, inv0, oq);
    sched_fence<9>(h.w, inv1.l0);
    proj_half<WG, true, 1>(c, a1, h.w, h.x, sw);
    o_rest<WG>(c, dc, oq);
    nq = O_STEPS;
    TRACE(i, 3); TRACE(i, 7);
    i++;
  }
  release_q<WG>(c);
  o_first<WG>(c, dc, a1, inv0, oq);
  o_rest<WG>(c, dc, oq);
#pragma unroll
  for (int k = 1; k <= O_STEPS; k++) o_second<WG>(c, dc, k, o1, inv1);
next:
  TRACE(i, 3); TRACE(i, 7);
  if ((d >> 30) != 2) {
    i++;
    r.uniform();
    goto begin;
  }
  trace_dump(c);
  return;
out_tile:
  if (d & 96) goto finish;
  d = get_desc(c, i + 1);
  wg_wait<1>();
  acc_fence<WG>(a0);
  TRACE_O(0);
  stage_out<WG, 0>(c, a0);
  TRACE_O(1);
  proj_end<WG>(c, a1, h);
  TRACE_O(2);
  stage_out<WG, 1>(c, a1);
  TRACE(i, 2);
  goto next;
finish:
  {
    uint32_t q[32];
#pragma unroll 1
    for (int k = (d >> 5) & 3; k > 1; k--) {
      wg_wait<0>();
      acc_fence<WG>(a0); acc_fence<WG>(a1);
      if (k == ((d >> 5) & 3)) { release(c, h.x); release(c, h.w); }
      load_part<WG, 0>(c, r, q); add_part<WG>(c, q, a0);
      load_part<WG, 1, 0>(c, r, q); add_part<WG>(c, q, a1);
#pragma unroll
      for (int t = 0; t < 4; t++) { release(c, r.slot); r.next(); }
    }
    load_part<WG, 0, WG ? 4 : 1>(c, r, q);
    wg_wait<1>();
    acc_fence<WG>(a0);
    TRACE_O(0);
    add_part<WG>(c, q, a0);
    stage_out<WG, 0>(c, a0);
    TRACE_O(1);
    load_part<WG, 1, WG ? 0 : 2>(c, r, q);
    wg_wait<0>();
    acc_fence<WG>(a1);
    TRACE_O(2);
    add_part<WG>(c, q, a1);
    stage_out<WG, 1>(c, a1);
    TRACE(i, 2); TRACE(i, 3); TRACE(i, 7);
    trace_dump(c);
    return;
  }
redo:
  {
    if (!WG) { stage_rows<RM1>(c, c.sb + QBUF_OFF + 16384, oq); __syncwarp(); }
    const size_t hoff = (size_t)(dc & 511) * (SK * DH);
    const int br = (dc >> 9) & 1;
#pragma unroll 1
    for (int part = 0; part < 2; part++) {
      const int t = WG ? 3 - part : part;
      redo_tile(c, c.sb + QBUF_OFF + t * 16384, t == 3 ? 4096 : 8192, kv[br] + hoff, kv[2 + br] + hoff, dc,
                t * 64 + (t == 3 ? 8 : 16) * c.warp);
    }
    o_done(c);
    release_q<WG>(c);
  }
  goto next;
}

template <bool SIMPLE>
__global__ void __launch_bounds__(384, 1) mha_fused_kernel(const __grid_constant__ Params P) {
  extern __shared__ __align__(1024) uint8_t smem_raw[];
  const uint32_t sbase = smem_u32(smem_raw);
  const int tid = threadIdx.x;
  const int wg = __shfl_sync(0xffffffffu, tid >> 7, 0);
  const int warp = __shfl_sync(0xffffffffu, (tid >> 5) & 3, 0);
  const int lane = tid & 31;
  const int cta = blockIdx.x;
  constexpr bool PAIR = !SIMPLE;

  if (tid == 0) T3(15, 0);
  if ((sbase & 0xffffff) != SB0) __trap();
  {
    const int wi = wg * 4 + warp;
    asm volatile(ELECT "prefetch.tensormap [%0];\n}" ::"l"(&P.x[0][0] + wi) : "memory");
#pragma unroll
    for (int k = 0; k < 5; k++) {
      const int b = min(BAR_OFF + (wi * 5 + k) * 8, DESC_OFF - 8);
      asm volatile(ELECT "mbarrier.init.shared::cta.b64 [%0], %1;\n}"
                   ::"r"(sbase + b), "r"(b < BAR_EMPTY || b >= BAR_DESC ? 1 : b >= BAR_STG && b < BAR_OUT ? 4 : 8) : "memory");
    }
    asm volatile("fence.mbarrier_init.release.cluster;" ::: "memory");
    if (wi < 6) asm volatile(ELECT "prefetch.tensormap [%0];\n}" ::"l"(&P.x[0][0] + 12 + wi) : "memory");
  }
  if (PAIR) asm volatile("barrier.cluster.arrive.aligned;\nbarrier.cluster.wait.aligned;" ::: "memory"); else __syncthreads();

  if (wg == 2) {
    asm volatile("setmaxnreg.dec.sync.aligned.u32 %0;" ::"n"(REG_P));
    if (warp == 1) {
      const uint32_t qb = sbase + QBUF_OFF;
      const uint32_t ep = __shfl_sync(0xffffffffu, *(volatile unsigned*)&g_epoch + 1, 0);
      asm volatile("st.volatile.shared.u32 [%0], %1;" ::"r"(sbase + EPOCH_OFF), "r"(ep) : "memory");
      uint32_t dc = c_sched.queue[cta], qi = 0, piece = 0, na = 0;
      TTAIL(0);
      for (int i = 0; (dc >> 30) != 2; i++) {
        if (!(dc >> 30) && o_reuse<SIMPLE>((dc >> 5) & 31)) {
          const unsigned* rd = &g_rd[0][0] + ((dc & 1023) >> 2) - OR * 8;
          for (uint32_t n = 0; !__all_sync(0xffffffffu, reached(rd, ep * 5)); __nanosleep(300)) if (++n > (1u << 22)) __trap();
        }
        mbar_wait_w(sbase + BAR_GO, i & 1);
        if (piece == 0) {
          if (PAIR && (cta & 1)) {
            asm volatile(ELECT EXPECT("%0", "4") "mbarrier.arrive.shared::cluster.b64 _, [%1];\n}" ::"r"(sbase + BAR_MAIL), "r"(peer(sbase + BAR_MAIL)) : "memory");
            mbar_wait_w(sbase + BAR_MAIL, i & 1);
            qi = lds(sbase + EPOCH_OFF + 8);
          } else if (lane == 0) {
            qi = atomicAdd(&g_next, PAIR ? 2 : 1);
            if (qi == (SIMPLE ? Q_ALL : Q_RANGES) - (PAIR ? 2 : 1)) { g_next = 0; g_epoch = ep; }
          }
          qi = __shfl_sync(0xffffffffu, qi, 0);
          if (PAIR && !(cta & 1)) {
            mbar_wait_w(sbase + BAR_MAIL, i & 1);
            asm volatile(ELECT "st.async.shared::cluster.mbarrier::complete_tx::bytes.u32 [%0], %1, [%2];\n}"
                         ::"r"(peer(sbase + EPOCH_OFF + 8)), "r"(qi + 1), "r"(peer(sbase + BAR_MAIL)) : "memory");
          }
          qi += SIMPLE ? gridDim.x : NCTA;
        }
        uint32_t d;
        if (qi < (SIMPLE ? Q_ALL : Q_RANGES)) { d = c_sched.queue[qi]; if (d & 0x8000) d ^= (1u << 30) | (63u << 16) | 0x8000; else d |= o_slot<SIMPLE>(d >> 5) << 15 | (d & 31) << 10; }
        else if (SIMPLE) d = 2u << 30;
        else { const uint32_t e = qi - Q_RANGES, g = e / 5; d = c_sched.piece[g][piece++] | (g & 1 ? g * 5 + 4 - e : e - g * 5) << 8; }
        if ((d >> 30) == 1) {
          const uint32_t k0 = (d >> 22) & 63;
          const uint32_t run = __ffs(__ballot_sync(0xffffffffu, !reached(&g_cnt[d & 31][lane & 7], ep * 4)) & (0xffu << (k0 >> 3))) - 1;
          if (run <= (k0 + ((d >> 16) & 63)) >> 3) d |= run <= (k0 + O_STEPS) >> 3 ? (2u << 30) | 128 : 128;
        }
        asm volatile("st.volatile.shared.u32 [%0], %1;" ::"r"(sbase + EPOCH_OFF + 4), "r"(qi) : "memory");
        asm volatile("st.volatile.shared.u32 [%0], %1;" ::"r"(sbase + DESC_OFF + ((i + 1) & 3) * 4), "r"(d) : "memory");
        __syncwarp();
        mbar_arrive_warp(sbase + BAR_DESC);
        const Work w = decode(dc);
        dc = d;
        if (w.kind == 0) {
          mbar_wait_w(sbase + BAR_OUT, na++ & 1);
          TTAIL(1);
          T3(i, 0); T3(i, 1);
          asm volatile(ELECT "red.release.gpu.global.add.u32 [%0], 1;\n}" ::"l"(&g_cnt[w.beta][w.sub >> 2]) : "memory");
          T3(i, 2);
          TTAIL(2);
          continue;
        }
        const bool fin = w.mode != 1;
        const CUtensorMap* m = fin ? P.out_st : P.o_st;
        const int c1 = fin ? (w.beta & 15) * SQ : 0;
        const int c2 = fin ? (w.beta >> 4) * (DM / 64) + w.sub * 2 : NBETA * 64 + w.range * 2;
        uint32_t pend = 0;
#pragma unroll 1
        for (int e = 0; e < 4; e++) {
          const int t = (ST_ORDER >> (4 * e)) & 3;
          mbar_wait_w(sbase + BAR_STG + (t ^ (t >> 1)) * 8, (i - na) & 1);
          tma_st3_w(m + (t == 3), qb + t * 16384, c1 + t * 64, c2);
          bulk_commit();
          T2P(i + 1, 5, 2 * e);
          if (e == 3 && w.mode == 1 && (d >> 30) == 2) {
            asm volatile("cp.async.bulk.wait_group 2;" ::: "memory");
            asm volatile(ELECT "st.release.gpu.global.u32 [%0], %1;\n}" ::"l"(&g_flag[w.range]), "r"(2 * ep - 1) : "memory");
          }
          if (pend && (d >> 30) != 2) {
            bulk_wait_read<1>();
            mbar_arrive8_w(pend);
            T2P(i + 1, 5, 2 * e - 1);
          }
          pend = sbase + BAR_EMPTY + (NS + t) * 8;
          if ((ST_NOW >> e) & 1) {
            bulk_wait_read<0>();
            mbar_arrive8_w(pend);
            pend = 0;
            T2P(i + 1, 5, 2 * e + 1);
          }
        }
        if (w.beta < N_EARLY) asm volatile(ELECT "red.relaxed.gpu.global.add.u32 [%0], 1;\n}" ::"l"(&g_rd[w.beta][7]) : "memory");
        T3(i, 0);
        if (piece >= 2) TTAIL(piece * 2 - 1);
        asm volatile("cp.async.bulk.wait_group 0;" ::: "memory");
        T3(i, 1);
        if (w.mode == 1) asm volatile(ELECT "st.release.gpu.global.u32 [%0], %1;\n}" ::"l"(&g_flag[w.range]), "r"(2 * ep) : "memory");
        T3(i, 2);
        if (piece >= 2) TTAIL(piece * 2);
      }
      T3(15, 1);
    } else
    if (warp == 0) {
      Ring r{0, 1, 3};
      uint32_t d = c_sched.queue[cta];
      for (int i = 0;; i++) {
        const Work w = decode(d);
        if (w.kind == 2) break;
        const CUtensorMap* m = w.kind == 0 ? &P.wq[w.beta >> 4] : &P.wo[w.beta >> 4];
        for (int ks = 0; ks < w.nsteps; ks++) {
          const uint32_t b = borrow(ks, w.nsteps);
          r.next_if(b == 2);
          const uint32_t bar = sbase + BAR_FULL + r.slot * 8;
          mbar_wait_w(bar + (BAR_EMPTY - BAR_FULL), r.phase);
          if (w.kind == 0) tma_ld3_w(sbase + r.slot * SLOT, m, 0, ks * 64, w.sub * 2, bar, 16384);
          else tma_ld_wo_w(sbase + r.slot * SLOT, m, w.sub * 128, (w.k0 + ks) * 2, bar);
          if (w.kind != 0 && w.beta < N_EARLY && (ks & 7) == 5 && ks > 5)
            asm volatile(ELECT "red.relaxed.gpu.global.add.u32 [%0], 1;\n}" ::"l"(&g_rd[w.beta][(ks >> 3) - 1]) : "memory");
          if (ks < 10) T2P(i, 2, ks);
          if (w.kind != 0 && ks == max(w.nsteps - GO_P, 4)) mbar_arrive_warp(sbase + BAR_GO);
          r.next(); r.next_if(b == 2);
        }
        if (w.kind == 0) {
          r.phase ^= 1; r.next(); r.next();
        } else if (w.mode == 2) {
          for (int k = 1; k <= ((d >> 5) & 3); k++) {
            if (k == 1) TTAIL(9);
            bool all = false;
#pragma unroll 1
            for (int t = 0; t < 4; t++) {
              if (!(t & 1) && !all) {
                const uint32_t ep2 = 2 * lds(sbase + EPOCH_OFF);
                uint32_t v, n = 0;
                do {
                  asm volatile("ld.acquire.gpu.global.u32 %0, [%1];" : "=r"(v) : "l"(&g_flag[w.range + 5 * k]) : "memory");
                  v = __shfl_sync(0xffffffffu, v - ep2, 0);
                  if (++n > (1u << 24)) __trap();
                } while ((int)v < (t >> 1) - 1);
                all = v == 0;
                TTAIL(10);
                asm volatile("fence.proxy.async.global;" ::: "memory");
              }
              mbar_wait_w(sbase + BAR_EMPTY + r.slot * 8, r.phase);
              tma_ld3_w(sbase + r.slot * SLOT, &P.o_st[t == 3], 0, t * 64, NBETA * 64 + (w.range + 5 * k) * 2, sbase + BAR_FULL + r.slot * 8,
                        t == 3 ? 8192 : 16384);
              r.next();
            }
          }
        }
        mbar_wait_w(sbase + BAR_DESC, i & 1);
        d = __shfl_sync(0xffffffffu, lds(sbase + DESC_OFF + ((i + 1) & 3) * 4), 0);
      }
    } else {
      const int hi = warp - 2;
      uint64_t pol_stream;
      uint32_t rdy = 0;
      asm volatile("createpolicy.fractional.L2::evict_first.b64 %0, 1.0;" : "=l"(pol_stream));
      Ring r{0, 1, 3};
      uint32_t d = c_sched.queue[cta];
      for (int i = 0;; i++) {
        const Work w = decode(d);
        if (w.kind == 2) break;
        const CUtensorMap* m = w.kind == 0 ? &P.x[hi][w.beta >> 4] : &P.o_ld[hi];
        int c1 = (w.kind == 0 ? (w.beta & 15) : o_slot<SIMPLE>(w.beta) * 64 + w.k0) * SQ + hi * 128;
        int k_wait = -1;
        const bool both = PAIR && (w.kind == 0 || w.sub != 4), mine = !both || hi == (cta & 1);
        if (w.kind != 0 && mine) {
          if (d & 128) k_wait = d >= (3u << 30) ? 0 : 8 - (w.k0 & 7);
          asm volatile("fence.proxy.async.global;" ::: "memory");
        }
        const int rank = i == 0 ? cta : __shfl_sync(0xffffffffu, lds(sbase + EPOCH_OFF + 4), 0) - NCTA;
        for (int ks = 0; ks < w.nsteps; ks++) {
          if (ks == k_wait) {
            wait_count(&g_cnt[d & 31][(w.k0 + ks) >> 3], lds(sbase + EPOCH_OFF) * 4);
            asm volatile("fence.proxy.async.global;" ::: "memory");
            k_wait = ((w.k0 + ks) | 7) + 1 - w.k0;
          }
          const uint32_t b = borrow(ks, w.nsteps);
          const bool bo = b != 2;
          r.next_if(hi && !bo); r.next_if(hi && !bo);
          const uint32_t sl = bo ? NS + (b ^ (3 * hi)) : r.slot, bar = sbase + BAR_FULL + sl * 8;
          mbar_wait_w(bar + (BAR_EMPTY - BAR_FULL), bo ? (r.xp >> b) & 1 : r.phase);
          const uint32_t bytes = hi ? 96 * 128 : 128 * 128;
          if (!mine) {
            asm volatile(ELECT EXPECT("%0", "%2") "mbarrier.arrive.shared::cluster.b64 _, [%1];\n}"
                         ::"r"(bar), "r"(peer(bar + (BAR_RDY - BAR_FULL))), "r"(bytes) : "memory");
          } else if (both) {
            mbar_wait_w(bar + (BAR_RDY - BAR_FULL), (rdy >> sl) & 1);
            rdy ^= 1 << sl;
            if (w.kind == 0) tma_ld2_both_w(sbase + sl * SLOT, m, ks * 64, c1, bar, bytes);
            else tma_ld2_both_hint_w(sbase + sl * SLOT, m, 0, c1, bar, bytes, pol_stream);
          } else if (!PAIR && w.kind == 0) tma_ld2_w(sbase + sl * SLOT, m, ks * 64, c1, bar, bytes);
          else tma_ld2_hint_w(sbase + sl * SLOT, m, 0, c1, bar, bytes, pol_stream);
          if (w.kind != 0) c1 += SQ;
          if (i == 0 && ks == PF_STEP)
            asm volatile(ELECT "cp.async.bulk.prefetch.tensor.4d.L2.global.L2::cache_hint [%0, {0, 0, 0, %1}], %2;\n}"
                         ::"l"(&P.kv[hi][0]), "r"(d * (SK / 8)), "l"(pol_stream) : "memory");
          if (ks < 10) T2P(i, 3 + hi, ks);
          if (!hi && w.kind != 0 && !(ks & 3)) TCLK(i * 16 + (ks >> 2));
          r.next(); r.next_if(!hi && !bo); r.next_if(!hi && !bo);
          r.xp ^= 1 << b;
        }
        r.xp ^= 3;
        if (w.kind == 0) {
          m = &P.kv[hi][w.beta >> 4];
          c1 = (d & 511) * (SK / 8);
          for (int j = 0; j < 16; j++) {
            if (hi) r.next();
            const uint32_t bar = sbase + BAR_FULL + r.slot * 8;
            const bool tight = i < KV_WIN_UNITS && j < KV_WIN_TILES + ((KV_WIN_RAMP * rank) >> 5);
            {
              const int s2 = (int)r.slot - (tight ? 2 : KV_WIN_D);
              mbar_wait_w(sbase + BAR_FULL + (s2 < 0 ? s2 + NS : s2) * 8, s2 < 0 ? r.phase : r.phase ^ 1);
            }
            if (j == 15 && hi) mbar_wait_w(sbase + BAR_DESC, i & 1);
            mbar_wait_w(sbase + BAR_EMPTY + r.slot * 8, r.phase);
            tma_ld_kv_w(sbase + r.slot * SLOT, m, c1, bar, pol_stream);
            T2P(i, 3 + hi, 16 + j);
            if (!hi) TCLK(i * 16 + j);
            if (j == GO_J && !hi) mbar_arrive_warp(sbase + BAR_GO);
            c1 += 8;
            r.next();
            if (!hi) r.next();
          }
        }
        mbar_wait_w(sbase + BAR_DESC, i & 1);
        d = __shfl_sync(0xffffffffu, lds(sbase + DESC_OFF + ((i + 1) & 3) * 4), 0);
      }
    }
  } else {
    Ctx c;
    c.sb = sbase; c.wg = wg; c.warp = warp; c.src = 0; c.mqk = 0; c.mpv = 0; c.lead = lane == 0; c.lane0 = c.lane = lane;
    if (wg == 0) consumer<0>(c, P.kp); else consumer<1>(c, P.kp);
  }
}

typedef CUresult (*EncodeFn)(CUtensorMap*, CUtensorMapDataType, cuuint32_t, void*, const cuuint64_t*, const cuuint64_t*,
                             const cuuint32_t*, const cuuint32_t*, CUtensorMapInterleave, CUtensorMapSwizzle,
                             CUtensorMapL2promotion, CUtensorMapFloatOOBfill);

void make_map(EncodeFn enc, CUtensorMap* m, const void* ptr, int rank, const cuuint64_t* dims, const cuuint64_t* strides,
              const cuuint32_t* box, CUtensorMapSwizzle swz = CU_TENSOR_MAP_SWIZZLE_128B) {
  cuuint32_t es[5] = {1, 1, 1, 1, 1};
  enc(m, CU_TENSOR_MAP_DATA_TYPE_BFLOAT16, rank, const_cast<void*>(ptr), dims, strides, box, es,
      CU_TENSOR_MAP_INTERLEAVE_NONE, swz, CU_TENSOR_MAP_L2_PROMOTION_NONE,
      CU_TENSOR_MAP_FLOAT_OOB_FILL_NONE);
}

}

extern "C" void kernel_launch(void* const* d_in, const int* in_sizes, int n_in, void* d_out, int out_size) {
  (void)in_sizes; (void)n_in; (void)out_size;
  static EncodeFn enc = nullptr;
  static void* o_ptr = nullptr;
  static int n_sm = 0;
  cudaLaunchAttribute at;
  at.id = cudaLaunchAttributeClusterDimension;
  at.val.clusterDim.x = 2; at.val.clusterDim.y = 1; at.val.clusterDim.z = 1;
  cudaLaunchConfig_t cfg = {};
  cfg.gridDim = dim3(NCTA); cfg.blockDim = dim3(384); cfg.dynamicSmemBytes = SMEM_BYTES; cfg.attrs = &at; cfg.numAttrs = 1;
  if (!enc) {
    void* fn = nullptr;
    cudaDriverEntryPointQueryResult qr;
    cudaGetDriverEntryPoint("cuTensorMapEncodeTiled", &fn, cudaEnableDefault, &qr);
    enc = (EncodeFn)fn;
    cudaGetSymbolAddress(&o_ptr, g_o);
    cudaFuncSetAttribute(mha_fused_kernel<false>, cudaFuncAttributeMaxDynamicSharedMemorySize, SMEM_BYTES);
    cudaFuncSetAttribute(mha_fused_kernel<true>, cudaFuncAttributeMaxDynamicSharedMemorySize, SMEM_BYTES);
    int dev = 0;
    cudaGetDevice(&dev);
    cudaDeviceGetAttribute(&n_sm, cudaDevAttrMultiProcessorCount, dev);
    int n_cl = 0;
    cudaOccupancyMaxActiveClusters(&n_cl, mha_fused_kernel<false>, &cfg);
    if (n_cl * 2 < NCTA && n_sm >= NCTA) n_sm = NCTA - 1;
  }
  Params P;
  for (int br = 0; br < 2; br++) {
    const void* x = d_in[br * 5 + 0]; const void* kc = d_in[br * 5 + 1]; const void* vc = d_in[br * 5 + 2];
    const void* wq = d_in[br * 5 + 3]; const void* wo = d_in[br * 5 + 4];
    { cuuint64_t d[2] = {DM, (cuuint64_t)NB * SQ}, s[1] = {DM * 2}; cuuint32_t b[2] = {64, 128}, b2[2] = {64, 96};
      make_map(enc, &P.x[0][br], x, 2, d, s, b); make_map(enc, &P.x[1][br], x, 2, d, s, b2); }
    { cuuint64_t d[3] = {64, DM, HD / 64}, s[2] = {HD * 2, 128}; cuuint32_t b[3] = {64, 64, 2}; make_map(enc, &P.wq[br], wq, 3, d, s, b); }
    { cuuint64_t d[5] = {DM, 2, 4, 4, HD / 32}, s[4] = {DM * 2, 8 * DM * 2, 2 * DM * 2, 32 * DM * 2}; cuuint32_t b[5] = {64, 2, 4, 4, 2};
      make_map(enc, &P.wo[br], wo, 5, d, s, b); }
    { cuuint64_t d[4] = {64, 8, 2, (cuuint64_t)NB * NH * SK / 8}, s[3] = {DH * 2, 128, DH * 16}; cuuint32_t b[4] = {64, 8, 2, 8};
      make_map(enc, &P.kv[0][br], kc, 4, d, s, b); make_map(enc, &P.kv[1][br], vc, 4, d, s, b); }
    P.kp[br] = (const __nv_bfloat16*)kc; P.vp[br] = (const __nv_bfloat16*)vc;

  }
  { cuuint64_t d[2] = {64, (cuuint64_t)NBETA * 64 * SQ}, s[1] = {128}; cuuint32_t b[2] = {64, 128}, b2[2] = {64, 96};
    make_map(enc, &P.o_ld[0], o_ptr, 2, d, s, b, CU_TENSOR_MAP_SWIZZLE_NONE); make_map(enc, &P.o_ld[1], o_ptr, 2, d, s, b2, CU_TENSOR_MAP_SWIZZLE_NONE); }
  { cuuint64_t d[3] = {64, SQ, O_BLOCKS}, s[2] = {128, SQ * 128}; cuuint32_t b[3] = {64, 64, 2}, b2[3] = {64, 32, 2};
    make_map(enc, &P.o_st[0], o_ptr, 3, d, s, b); make_map(enc, &P.o_st[1], o_ptr, 3, d, s, b2); }
  { cuuint64_t d[3] = {64, (cuuint64_t)NB * SQ, 2 * DM / 64}, s[2] = {2 * DM * 2, 128}; cuuint32_t b[3] = {64, 64, 2}, b2[3] = {64, 32, 2};
    make_map(enc, &P.out_st[0], d_out, 3, d, s, b); make_map(enc, &P.out_st[1], d_out, 3, d, s, b2); }
  if (n_sm >= NCTA) cudaLaunchKernelEx(&cfg, mha_fused_kernel<false>, P);
  else mha_fused_kernel<true><<<n_sm, 384, SMEM_BYTES>>>(P);
}
```

```cpp
#include <cuda_runtime.h>
#include <cuda_bf16.h>
#include <cuda.h>
#include <stdint.h>
#include <stdlib.h>

namespace {

__device__ __forceinline__ void wgmma_proj(float (&d)[64], uint64_t da, uint64_t db, int scaleD) {
  asm volatile("{\n.reg .pred p;\nsetp.ne.b32 p, %66, 0;\n"
      "wgmma.mma_async.sync.aligned.m64n128k16.f32.bf16.bf16 "
      "{%0, %1, %2, %3, %4, %5, %6, %7, %8, %9, %10, %11, %12, %13, %14, %15, %16, %17, %18, %19, %20, %21, %22, %23, %24, %25, %26, %27, %28, %29, %30, "
      "%31, %32, %33, %34, %35, %36, %37, %38, %39, %40, %41, %42, %43, %44, %45, %46, %47, %48, %49, %50, %51, %52, %53, %54, %55, %56, %57, %58, %59, %60, "
      "%61, %62, %63}, "
      "%64, %65, p, 1, 1, 0, 1;\n}\n"
      : "+f"(d[0]), "+f"(d[1]), "+f"(d[2]), "+f"(d[3]), "+f"(d[4]), "+f"(d[5]), "+f"(d[6]), "+f"(d[7]), "+f"(d[8]), "+f"(d[9]), "+f"(d[10]), "+f"(d[11]),
        "+f"(d[12]), "+f"(d[13]), "+f"(d[14]), "+f"(d[15]), "+f"(d[16]), "+f"(d[17]), "+f"(d[18]), "+f"(d[19]), "+f"(d[20]), "+f"(d[21]), "+f"(d[22]),
        "+f"(d[23]), "+f"(d[24]), "+f"(d[25]), "+f"(d[26]), "+f"(d[27]), "+f"(d[28]), "+f"(d[29]), "+f"(d[30]), "+f"(d[31]), "+f"(d[32]), "+f"(d[33]),
        "+f"(d[34]), "+f"(d[35]), "+f"(d[36]), "+f"(d[37]), "+f"(d[38]), "+f"(d[39]), "+f"(d[40]), "+f"(d[41]), "+f"(d[42]), "+f"(d[43]), "+f"(d[44]),
        "+f"(d[45]), "+f"(d[46]), "+f"(d[47]), "+f"(d[48]), "+f"(d[49]), "+f"(d[50]), "+f"(d[51]), "+f"(d[52]), "+f"(d[53]), "+f"(d[54]), "+f"(d[55]),
        "+f"(d[56]), "+f"(d[57]), "+f"(d[58]), "+f"(d[59]), "+f"(d[60]), "+f"(d[61]), "+f"(d[62]), "+f"(d[63])
      : "l"(da), "l"(db), "r"(scaleD));
}
__device__ __forceinline__ void wgmma_proj96(float (&d)[64], uint64_t da, uint64_t db, int scaleD) {
  asm volatile("{\n.reg .pred p;\nsetp.ne.b32 p, %50, 0;\n"
      "wgmma.mma_async.sync.aligned.m64n96k16.f32.bf16.bf16 "
      "{%0, %1, %2, %3, %4, %5, %6, %7, %8, %9, %10, %11, %12, %13, %14, %15, %16, %17, %18, %19, %20, %21, %22, %23, %24, %25, %26, %27, %28, %29, %30, "
      "%31, %32, %33, %34, %35, %36, %37, %38, %39, %40, %41, %42, %43, %44, %45, %46, %47}, "
      "%48, %49, p, 1, 1, 1, 0;\n}\n"
      : "+f"(d[0]), "+f"(d[1]), "+f"(d[2]), "+f"(d[3]), "+f"(d[4]), "+f"(d[5]), "+f"(d[6]), "+f"(d[7]), "+f"(d[8]), "+f"(d[9]), "+f"(d[10]), "+f"(d[11]),
        "+f"(d[12]), "+f"(d[13]), "+f"(d[14]), "+f"(d[15]), "+f"(d[16]), "+f"(d[17]), "+f"(d[18]), "+f"(d[19]), "+f"(d[20]), "+f"(d[21]), "+f"(d[22]),
        "+f"(d[23]), "+f"(d[24]), "+f"(d[25]), "+f"(d[26]), "+f"(d[27]), "+f"(d[28]), "+f"(d[29]), "+f"(d[30]), "+f"(d[31]), "+f"(d[32]), "+f"(d[33]),
        "+f"(d[34]), "+f"(d[35]), "+f"(d[36]), "+f"(d[37]), "+f"(d[38]), "+f"(d[39]), "+f"(d[40]), "+f"(d[41]), "+f"(d[42]), "+f"(d[43]), "+f"(d[44]),
        "+f"(d[45]), "+f"(d[46]), "+f"(d[47])
      : "l"(da), "l"(db), "r"(scaleD));
}
__device__ __forceinline__ void wgmma_qk(float (&d)[32], uint64_t da, uint64_t db, int scaleD) {
  asm volatile("{\n.reg .pred p;\nsetp.ne.b32 p, %34, 0;\n"
      "wgmma.mma_async.sync.aligned.m64n64k16.f32.bf16.bf16 "
      "{%0, %1, %2, %3, %4, %5, %6, %7, %8, %9, %10, %11, %12, %13, %14, %15, %16, %17, %18, %19, %20, %21, %22, %23, %24, %25, %26, %27, %28, %29, %30, "
      "%31}, "
      "%32, %33, p, 1, 1, 0, 0;\n}\n"
      : "+f"(d[0]), "+f"(d[1]), "+f"(d[2]), "+f"(d[3]), "+f"(d[4]), "+f"(d[5]), "+f"(d[6]), "+f"(d[7]), "+f"(d[8]), "+f"(d[9]), "+f"(d[10]), "+f"(d[11]),
        "+f"(d[12]), "+f"(d[13]), "+f"(d[14]), "+f"(d[15]), "+f"(d[16]), "+f"(d[17]), "+f"(d[18]), "+f"(d[19]), "+f"(d[20]), "+f"(d[21]), "+f"(d[22]),
        "+f"(d[23]), "+f"(d[24]), "+f"(d[25]), "+f"(d[26]), "+f"(d[27]), "+f"(d[28]), "+f"(d[29]), "+f"(d[30]), "+f"(d[31])
      : "l"(da), "l"(db), "r"(scaleD));
}
__device__ __forceinline__ void wgmma_qk_rs(float (&d)[32], uint32_t a0, uint32_t a1, uint32_t a2, uint32_t a3, uint64_t db, int scaleD) {
  asm volatile("{\n.reg .pred p;\nsetp.ne.b32 p, %37, 0;\n"
      "wgmma.mma_async.sync.aligned.m64n64k16.f32.bf16.bf16 "
      "{%0, %1, %2, %3, %4, %5, %6, %7, %8, %9, %10, %11, %12, %13, %14, %15, %16, %17, %18, %19, %20, %21, %22, %23, %24, %25, %26, %27, %28, %29, %30, "
      "%31}, "
      "{%32, %33, %34, %35}, %36, p, 1, 1, 0;\n}\n"
      : "+f"(d[0]), "+f"(d[1]), "+f"(d[2]), "+f"(d[3]), "+f"(d[4]), "+f"(d[5]), "+f"(d[6]), "+f"(d[7]), "+f"(d[8]), "+f"(d[9]), "+f"(d[10]), "+f"(d[11]),
        "+f"(d[12]), "+f"(d[13]), "+f"(d[14]), "+f"(d[15]), "+f"(d[16]), "+f"(d[17]), "+f"(d[18]), "+f"(d[19]), "+f"(d[20]), "+f"(d[21]), "+f"(d[22]),
        "+f"(d[23]), "+f"(d[24]), "+f"(d[25]), "+f"(d[26]), "+f"(d[27]), "+f"(d[28]), "+f"(d[29]), "+f"(d[30]), "+f"(d[31])
      : "r"(a0), "r"(a1), "r"(a2), "r"(a3), "l"(db), "r"(scaleD));
}
__device__ __forceinline__ void wgmma_pv(float (&d)[64], uint32_t a0, uint32_t a1, uint32_t a2, uint32_t a3, uint64_t db, int scaleD) {
  asm volatile("{\n.reg .pred p;\nsetp.ne.b32 p, %69, 0;\n"
      "wgmma.mma_async.sync.aligned.m64n128k16.f32.bf16.bf16 "
      "{%0, %1, %2, %3, %4, %5, %6, %7, %8, %9, %10, %11, %12, %13, %14, %15, %16, %17, %18, %19, %20, %21, %22, %23, %24, %25, %26, %27, %28, %29, %30, "
      "%31, %32, %33, %34, %35, %36, %37, %38, %39, %40, %41, %42, %43, %44, %45, %46, %47, %48, %49, %50, %51, %52, %53, %54, %55, %56, %57, %58, %59, %60, "
      "%61, %62, %63}, "
      "{%64, %65, %66, %67}, %68, p, 1, 1, 1;\n}\n"
      : "+f"(d[0]), "+f"(d[1]), "+f"(d[2]), "+f"(d[3]), "+f"(d[4]), "+f"(d[5]), "+f"(d[6]), "+f"(d[7]), "+f"(d[8]), "+f"(d[9]), "+f"(d[10]), "+f"(d[11]),
        "+f"(d[12]), "+f"(d[13]), "+f"(d[14]), "+f"(d[15]), "+f"(d[16]), "+f"(d[17]), "+f"(d[18]), "+f"(d[19]), "+f"(d[20]), "+f"(d[21]), "+f"(d[22]),
        "+f"(d[23]), "+f"(d[24]), "+f"(d[25]), "+f"(d[26]), "+f"(d[27]), "+f"(d[28]), "+f"(d[29]), "+f"(d[30]), "+f"(d[31]), "+f"(d[32]), "+f"(d[33]),
        "+f"(d[34]), "+f"(d[35]), "+f"(d[36]), "+f"(d[37]), "+f"(d[38]), "+f"(d[39]), "+f"(d[40]), "+f"(d[41]), "+f"(d[42]), "+f"(d[43]), "+f"(d[44]),
        "+f"(d[45]), "+f"(d[46]), "+f"(d[47]), "+f"(d[48]), "+f"(d[49]), "+f"(d[50]), "+f"(d[51]), "+f"(d[52]), "+f"(d[53]), "+f"(d[54]), "+f"(d[55]),
        "+f"(d[56]), "+f"(d[57]), "+f"(d[58]), "+f"(d[59]), "+f"(d[60]), "+f"(d[61]), "+f"(d[62]), "+f"(d[63])
      : "r"(a0), "r"(a1), "r"(a2), "r"(a3), "l"(db), "r"(scaleD));
}
__device__ __forceinline__ void wgmma_qk_sp(float (&d)[32], uint32_t a0, uint32_t a1, uint32_t a2, uint32_t a3, uint64_t db, int scaleD, uint32_t meta) {
  asm volatile("{\n.reg .pred p;\nsetp.ne.b32 p, %37, 0;\n"
      "wgmma.mma_async.sp.sync.aligned.m64n64k32.f32.bf16.bf16 "
      "{%0, %1, %2, %3, %4, %5, %6, %7, %8, %9, %10, %11, %12, %13, %14, %15, %16, %17, %18, %19, %20, %21, %22, %23, %24, %25, %26, %27, %28, %29, %30, "
      "%31}, "
      "{%32, %33, %34, %35}, %36, %38, 0, p, 1, 1, 0;\n}\n"
      : "+f"(d[0]), "+f"(d[1]), "+f"(d[2]), "+f"(d[3]), "+f"(d[4]), "+f"(d[5]), "+f"(d[6]), "+f"(d[7]), "+f"(d[8]), "+f"(d[9]), "+f"(d[10]), "+f"(d[11]),
        "+f"(d[12]), "+f"(d[13]), "+f"(d[14]), "+f"(d[15]), "+f"(d[16]), "+f"(d[17]), "+f"(d[18]), "+f"(d[19]), "+f"(d[20]), "+f"(d[21]), "+f"(d[22]),
        "+f"(d[23]), "+f"(d[24]), "+f"(d[25]), "+f"(d[26]), "+f"(d[27]), "+f"(d[28]), "+f"(d[29]), "+f"(d[30]), "+f"(d[31])
      : "r"(a0), "r"(a1), "r"(a2), "r"(a3), "l"(db), "r"(scaleD), "r"(meta));
}
__device__ __forceinline__ void wgmma_pv_sp(float (&d)[64], uint32_t a0, uint32_t a1, uint32_t a2, uint32_t a3, uint64_t db, int scaleD, uint32_t meta) {
  asm volatile("{\n.reg .pred p;\nsetp.ne.b32 p, %69, 0;\n"
      "wgmma.mma_async.sp.sync.aligned.m64n128k32.f32.bf16.bf16 "
      "{%0, %1, %2, %3, %4, %5, %6, %7, %8, %9, %10, %11, %12, %13, %14, %15, %16, %17, %18, %19, %20, %21, %22, %23, %24, %25, %26, %27, %28, %29, %30, "
      "%31, %32, %33, %34, %35, %36, %37, %38, %39, %40, %41, %42, %43, %44, %45, %46, %47, %48, %49, %50, %51, %52, %53, %54, %55, %56, %57, %58, %59, %60, "
      "%61, %62, %63}, "
      "{%64, %65, %66, %67}, %68, %70, 0, p, 1, 1, 1;\n}\n"
      : "+f"(d[0]), "+f"(d[1]), "+f"(d[2]), "+f"(d[3]), "+f"(d[4]), "+f"(d[5]), "+f"(d[6]), "+f"(d[7]), "+f"(d[8]), "+f"(d[9]), "+f"(d[10]), "+f"(d[11]),
        "+f"(d[12]), "+f"(d[13]), "+f"(d[14]), "+f"(d[15]), "+f"(d[16]), "+f"(d[17]), "+f"(d[18]), "+f"(d[19]), "+f"(d[20]), "+f"(d[21]), "+f"(d[22]),
        "+f"(d[23]), "+f"(d[24]), "+f"(d[25]), "+f"(d[26]), "+f"(d[27]), "+f"(d[28]), "+f"(d[29]), "+f"(d[30]), "+f"(d[31]), "+f"(d[32]), "+f"(d[33]),
        "+f"(d[34]), "+f"(d[35]), "+f"(d[36]), "+f"(d[37]), "+f"(d[38]), "+f"(d[39]), "+f"(d[40]), "+f"(d[41]), "+f"(d[42]), "+f"(d[43]), "+f"(d[44]),
        "+f"(d[45]), "+f"(d[46]), "+f"(d[47]), "+f"(d[48]), "+f"(d[49]), "+f"(d[50]), "+f"(d[51]), "+f"(d[52]), "+f"(d[53]), "+f"(d[54]), "+f"(d[55]),
        "+f"(d[56]), "+f"(d[57]), "+f"(d[58]), "+f"(d[59]), "+f"(d[60]), "+f"(d[61]), "+f"(d[62]), "+f"(d[63])
      : "r"(a0), "r"(a1), "r"(a2), "r"(a3), "l"(db), "r"(scaleD), "r"(meta));
}
__device__ __forceinline__ void wgmma_proj_init(float (&d)[64], uint64_t da, uint64_t db, int scaleD) {
  asm volatile("{\n.reg .pred p;\nsetp.ne.b32 p, %66, 0;\n"
      "wgmma.mma_async.sync.aligned.m64n128k16.f32.bf16.bf16 "
      "{%0, %1, %2, %3, %4, %5, %6, %7, %8, %9, %10, %11, %12, %13, %14, %15, %16, %17, %18, %19, %20, %21, %22, %23, %24, %25, %26, %27, %28, %29, %30, "
      "%31, %32, %33, %34, %35, %36, %37, %38, %39, %40, %41, %42, %43, %44, %45, %46, %47, %48, %49, %50, %51, %52, %53, %54, %55, %56, %57, %58, %59, %60, "
      "%61, %62, %63}, "
      "%64, %65, p, 1, 1, 0, 1;\n}\n"
      : "=f"(d[0]), "=f"(d[1]), "=f"(d[2]), "=f"(d[3]), "=f"(d[4]), "=f"(d[5]), "=f"(d[6]), "=f"(d[7]), "=f"(d[8]), "=f"(d[9]), "=f"(d[10]), "=f"(d[11]),
        "=f"(d[12]), "=f"(d[13]), "=f"(d[14]), "=f"(d[15]), "=f"(d[16]), "=f"(d[17]), "=f"(d[18]), "=f"(d[19]), "=f"(d[20]), "=f"(d[21]), "=f"(d[22]),
        "=f"(d[23]), "=f"(d[24]), "=f"(d[25]), "=f"(d[26]), "=f"(d[27]), "=f"(d[28]), "=f"(d[29]), "=f"(d[30]), "=f"(d[31]), "=f"(d[32]), "=f"(d[33]),
        "=f"(d[34]), "=f"(d[35]), "=f"(d[36]), "=f"(d[37]), "=f"(d[38]), "=f"(d[39]), "=f"(d[40]), "=f"(d[41]), "=f"(d[42]), "=f"(d[43]), "=f"(d[44]),
        "=f"(d[45]), "=f"(d[46]), "=f"(d[47]), "=f"(d[48]), "=f"(d[49]), "=f"(d[50]), "=f"(d[51]), "=f"(d[52]), "=f"(d[53]), "=f"(d[54]), "=f"(d[55]),
        "=f"(d[56]), "=f"(d[57]), "=f"(d[58]), "=f"(d[59]), "=f"(d[60]), "=f"(d[61]), "=f"(d[62]), "=f"(d[63])
      : "l"(da), "l"(db), "r"(scaleD));
}
__device__ __forceinline__ void wgmma_proj96_init(float (&d)[64], uint64_t da, uint64_t db, int scaleD) {
  asm volatile("{\n.reg .pred p;\nsetp.ne.b32 p, %50, 0;\n"
      "wgmma.mma_async.sync.aligned.m64n96k16.f32.bf16.bf16 "
      "{%0, %1, %2, %3, %4, %5, %6, %7, %8, %9, %10, %11, %12, %13, %14, %15, %16, %17, %18, %19, %20, %21, %22, %23, %24, %25, %26, %27, %28, %29, %30, "
      "%31, %32, %33, %34, %35, %36, %37, %38, %39, %40, %41, %42, %43, %44, %45, %46, %47}, "
      "%48, %49, p, 1, 1, 1, 0;\n}\n"
      : "=f"(d[0]), "=f"(d[1]), "=f"(d[2]), "=f"(d[3]), "=f"(d[4]), "=f"(d[5]), "=f"(d[6]), "=f"(d[7]), "=f"(d[8]), "=f"(d[9]), "=f"(d[10]), "=f"(d[11]),
        "=f"(d[12]), "=f"(d[13]), "=f"(d[14]), "=f"(d[15]), "=f"(d[16]), "=f"(d[17]), "=f"(d[18]), "=f"(d[19]), "=f"(d[20]), "=f"(d[21]), "=f"(d[22]),
        "=f"(d[23]), "=f"(d[24]), "=f"(d[25]), "=f"(d[26]), "=f"(d[27]), "=f"(d[28]), "=f"(d[29]), "=f"(d[30]), "=f"(d[31]), "=f"(d[32]), "=f"(d[33]),
        "=f"(d[34]), "=f"(d[35]), "=f"(d[36]), "=f"(d[37]), "=f"(d[38]), "=f"(d[39]), "=f"(d[40]), "=f"(d[41]), "=f"(d[42]), "=f"(d[43]), "=f"(d[44]),
        "=f"(d[45]), "=f"(d[46]), "=f"(d[47])
      : "l"(da), "l"(db), "r"(scaleD));
}
__device__ __forceinline__ void wgmma_qk_init(float (&d)[32], uint64_t da, uint64_t db, int scaleD) {
  asm volatile("{\n.reg .pred p;\nsetp.ne.b32 p, %34, 0;\n"
      "wgmma.mma_async.sync.aligned.m64n64k16.f32.bf16.bf16 "
      "{%0, %1, %2, %3, %4, %5, %6, %7, %8, %9, %10, %11, %12, %13, %14, %15, %16, %17, %18, %19, %20, %21, %22, %23, %24, %25, %26, %27, %28, %29, %30, "
      "%31}, "
      "%32, %33, p, 1, 1, 0, 0;\n}\n"
      : "=f"(d[0]), "=f"(d[1]), "=f"(d[2]), "=f"(d[3]), "=f"(d[4]), "=f"(d[5]), "=f"(d[6]), "=f"(d[7]), "=f"(d[8]), "=f"(d[9]), "=f"(d[10]), "=f"(d[11]),
        "=f"(d[12]), "=f"(d[13]), "=f"(d[14]), "=f"(d[15]), "=f"(d[16]), "=f"(d[17]), "=f"(d[18]), "=f"(d[19]), "=f"(d[20]), "=f"(d[21]), "=f"(d[22]),
        "=f"(d[23]), "=f"(d[24]), "=f"(d[25]), "=f"(d[26]), "=f"(d[27]), "=f"(d[28]), "=f"(d[29]), "=f"(d[30]), "=f"(d[31])
      : "l"(da), "l"(db), "r"(scaleD));
}
__device__ __forceinline__ void wgmma_qk_rs_init(float (&d)[32], uint32_t a0, uint32_t a1, uint32_t a2, uint32_t a3, uint64_t db, int scaleD) {
  asm volatile("{\n.reg .pred p;\nsetp.ne.b32 p, %37, 0;\n"
      "wgmma.mma_async.sync.aligned.m64n64k16.f32.bf16.bf16 "
      "{%0, %1, %2, %3, %4, %5, %6, %7, %8, %9, %10, %11, %12, %13, %14, %15, %16, %17, %18, %19, %20, %21, %22, %23, %24, %25, %26, %27, %28, %29, %30, "
      "%31}, "
      "{%32, %33, %34, %35}, %36, p, 1, 1, 0;\n}\n"
      : "=f"(d[0]), "=f"(d[1]), "=f"(d[2]), "=f"(d[3]), "=f"(d[4]), "=f"(d[5]), "=f"(d[6]), "=f"(d[7]), "=f"(d[8]), "=f"(d[9]), "=f"(d[10]), "=f"(d[11]),
        "=f"(d[12]), "=f"(d[13]), "=f"(d[14]), "=f"(d[15]), "=f"(d[16]), "=f"(d[17]), "=f"(d[18]), "=f"(d[19]), "=f"(d[20]), "=f"(d[21]), "=f"(d[22]),
        "=f"(d[23]), "=f"(d[24]), "=f"(d[25]), "=f"(d[26]), "=f"(d[27]), "=f"(d[28]), "=f"(d[29]), "=f"(d[30]), "=f"(d[31])
      : "r"(a0), "r"(a1), "r"(a2), "r"(a3), "l"(db), "r"(scaleD));
}
__device__ __forceinline__ void wgmma_pv_init(float (&d)[64], uint32_t a0, uint32_t a1, uint32_t a2, uint32_t a3, uint64_t db, int scaleD) {
  asm volatile("{\n.reg .pred p;\nsetp.ne.b32 p, %69, 0;\n"
      "wgmma.mma_async.sync.aligned.m64n128k16.f32.bf16.bf16 "
      "{%0, %1, %2, %3, %4, %5, %6, %7, %8, %9, %10, %11, %12, %13, %14, %15, %16, %17, %18, %19, %20, %21, %22, %23, %24, %25, %26, %27, %28, %29, %30, "
      "%31, %32, %33, %34, %35, %36, %37, %38, %39, %40, %41, %42, %43, %44, %45, %46, %47, %48, %49, %50, %51, %52, %53, %54, %55, %56, %57, %58, %59, %60, "
      "%61, %62, %63}, "
      "{%64, %65, %66, %67}, %68, p, 1, 1, 1;\n}\n"
      : "=f"(d[0]), "=f"(d[1]), "=f"(d[2]), "=f"(d[3]), "=f"(d[4]), "=f"(d[5]), "=f"(d[6]), "=f"(d[7]), "=f"(d[8]), "=f"(d[9]), "=f"(d[10]), "=f"(d[11]),
        "=f"(d[12]), "=f"(d[13]), "=f"(d[14]), "=f"(d[15]), "=f"(d[16]), "=f"(d[17]), "=f"(d[18]), "=f"(d[19]), "=f"(d[20]), "=f"(d[21]), "=f"(d[22]),
        "=f"(d[23]), "=f"(d[24]), "=f"(d[25]), "=f"(d[26]), "=f"(d[27]), "=f"(d[28]), "=f"(d[29]), "=f"(d[30]), "=f"(d[31]), "=f"(d[32]), "=f"(d[33]),
        "=f"(d[34]), "=f"(d[35]), "=f"(d[36]), "=f"(d[37]), "=f"(d[38]), "=f"(d[39]), "=f"(d[40]), "=f"(d[41]), "=f"(d[42]), "=f"(d[43]), "=f"(d[44]),
        "=f"(d[45]), "=f"(d[46]), "=f"(d[47]), "=f"(d[48]), "=f"(d[49]), "=f"(d[50]), "=f"(d[51]), "=f"(d[52]), "=f"(d[53]), "=f"(d[54]), "=f"(d[55]),
        "=f"(d[56]), "=f"(d[57]), "=f"(d[58]), "=f"(d[59]), "=f"(d[60]), "=f"(d[61]), "=f"(d[62]), "=f"(d[63])
      : "r"(a0), "r"(a1), "r"(a2), "r"(a3), "l"(db), "r"(scaleD));
}
__device__ __forceinline__ void wgmma_qk_sp_init(float (&d)[32], uint32_t a0, uint32_t a1, uint32_t a2, uint32_t a3, uint64_t db, int scaleD, uint32_t meta) {
  asm volatile("{\n.reg .pred p;\nsetp.ne.b32 p, %37, 0;\n"
      "wgmma.mma_async.sp.sync.aligned.m64n64k32.f32.bf16.bf16 "
      "{%0, %1, %2, %3, %4, %5, %6, %7, %8, %9, %10, %11, %12, %13, %14, %15, %16, %17, %18, %19, %20, %21, %22, %23, %24, %25, %26, %27, %28, %29, %30, "
      "%31}, "
      "{%32, %33, %34, %35}, %36, %38, 0, p, 1, 1, 0;\n}\n"
      : "=f"(d[0]), "=f"(d[1]), "=f"(d[2]), "=f"(d[3]), "=f"(d[4]), "=f"(d[5]), "=f"(d[6]), "=f"(d[7]), "=f"(d[8]), "=f"(d[9]), "=f"(d[10]), "=f"(d[11]),
        "=f"(d[12]), "=f"(d[13]), "=f"(d[14]), "=f"(d[15]), "=f"(d[16]), "=f"(d[17]), "=f"(d[18]), "=f"(d[19]), "=f"(d[20]), "=f"(d[21]), "=f"(d[22]),
        "=f"(d[23]), "=f"(d[24]), "=f"(d[25]), "=f"(d[26]), "=f"(d[27]), "=f"(d[28]), "=f"(d[29]), "=f"(d[30]), "=f"(d[31])
      : "r"(a0), "r"(a1), "r"(a2), "r"(a3), "l"(db), "r"(scaleD), "r"(meta));
}
__device__ __forceinline__ void wgmma_pv_sp_init(float (&d)[64], uint32_t a0, uint32_t a1, uint32_t a2, uint32_t a3, uint64_t db, int scaleD, uint32_t meta) {
  asm volatile("{\n.reg .pred p;\nsetp.ne.b32 p, %69, 0;\n"
      "wgmma.mma_async.sp.sync.aligned.m64n128k32.f32.bf16.bf16 "
      "{%0, %1, %2, %3, %4, %5, %6, %7, %8, %9, %10, %11, %12, %13, %14, %15, %16, %17, %18, %19, %20, %21, %22, %23, %24, %25, %26, %27, %28, %29, %30, "
      "%31, %32, %33, %34, %35, %36, %37, %38, %39, %40, %41, %42, %43, %44, %45, %46, %47, %48, %49, %50, %51, %52, %53, %54, %55, %56, %57, %58, %59, %60, "
      "%61, %62, %63}, "
      "{%64, %65, %66, %67}, %68, %70, 0, p, 1, 1, 1;\n}\n"
      : "=f"(d[0]), "=f"(d[1]), "=f"(d[2]), "=f"(d[3]), "=f"(d[4]), "=f"(d[5]), "=f"(d[6]), "=f"(d[7]), "=f"(d[8]), "=f"(d[9]), "=f"(d[10]), "=f"(d[11]),
        "=f"(d[12]), "=f"(d[13]), "=f"(d[14]), "=f"(d[15]), "=f"(d[16]), "=f"(d[17]), "=f"(d[18]), "=f"(d[19]), "=f"(d[20]), "=f"(d[21]), "=f"(d[22]),
        "=f"(d[23]), "=f"(d[24]), "=f"(d[25]), "=f"(d[26]), "=f"(d[27]), "=f"(d[28]), "=f"(d[29]), "=f"(d[30]), "=f"(d[31]), "=f"(d[32]), "=f"(d[33]),
        "=f"(d[34]), "=f"(d[35]), "=f"(d[36]), "=f"(d[37]), "=f"(d[38]), "=f"(d[39]), "=f"(d[40]), "=f"(d[41]), "=f"(d[42]), "=f"(d[43]), "=f"(d[44]),
        "=f"(d[45]), "=f"(d[46]), "=f"(d[47]), "=f"(d[48]), "=f"(d[49]), "=f"(d[50]), "=f"(d[51]), "=f"(d[52]), "=f"(d[53]), "=f"(d[54]), "=f"(d[55]),
        "=f"(d[56]), "=f"(d[57]), "=f"(d[58]), "=f"(d[59]), "=f"(d[60]), "=f"(d[61]), "=f"(d[62]), "=f"(d[63])
      : "r"(a0), "r"(a1), "r"(a2), "r"(a3), "l"(db), "r"(scaleD), "r"(meta));
}

constexpr int NB = 16, SQ = 224, DM = 640, NH = 32, SK = 1024, DH = 128;
constexpr int HD = NH * DH;
constexpr int NBETA = 2 * NB;
constexpr int NCTA = 132;
constexpr uint32_t SB0 = 1024;
constexpr int NS = 10;
constexpr int SLOT = 16384;
constexpr int QBUF_OFF = NS * SLOT;
constexpr int NSX = NS + 4;
constexpr int BAR_OFF = NSX * SLOT;
constexpr int BAR_FULL = BAR_OFF;
constexpr int BAR_EMPTY = BAR_OFF + 8 * NSX;
constexpr int BAR_STG = BAR_OFF + 16 * NSX;
constexpr int BAR_OUT = BAR_STG + 32;
constexpr int BAR_DESC = BAR_OUT + 8;
constexpr int BAR_GO = BAR_DESC + 8;
constexpr int BAR_MAIL = BAR_GO + 8;
constexpr int BAR_RDY = BAR_MAIL + 8;
constexpr int DESC_OFF = BAR_RDY + 8 * NSX;
constexpr int EPOCH_OFF = DESC_OFF + 16;
constexpr int TRACE_OFF = EPOCH_OFF + 16;
constexpr int SMEM_BYTES = TRACE_OFF;
constexpr float SM_C = 0.08838834764831845f * 1.4426950408889634f;
constexpr float SUM_HI = 1099511627776.f, SUM_LO = 1.f / 1099511627776.f;
constexpr uint32_t META_QK = 0xEEEE4444u;
constexpr uint32_t META_PV = 0x44EEEE44u;

#define QK_EARLY_MASK 3
#define ST_ORDER 0x2310
#define LAG_BAR 2
#define ST_NOW 8
#define PF_STEP 5
#define KV_WIN_UNITS 2
#define KV_WIN_D 4
#define SF 0xeebf
#define O_STEPS 4
#define KV_WIN_RAMP 4
#define PDEPTH 0
#define KV_WIN_TILES -2
#define REG_C 232
#define REG_P 24
#define GO_P 6
#define P_POS 216
#define OR 6
#define OR0 0
#define B_LATE 24
#define H_LATE 24
#define RM0 1
#define RM1 0xab
#define RM2 0
#define PAIRB 1
#define LATE0 1
#define LATE1 2
#define GO_J 13
#define LATE_G 32
#define KG 5
#define PK 44
#define EARLY_MASK 0xffffu
#define PIECE_TABLE 0x5036c811,0x80000000,0x50111815,0x65e8183b,0x5014b81d,0x66e4b83f,0x5016201b,0x6723203e,0x501e9019,0x69d89054,0x50168816,0x67e08839,0x501ba813,0x69d8a85d,0x502e6817,0x80000000,0x500ba014,0x6723a033,0x646e003a,0x80000000,0x64ad1035,0x80000000,0x652b4030,0x80000000,0x5024781c,0x80000000,0x65e88036,0x80000000,0x50203812,0x80000000,0x539e5818,0x80000000,0x501ac01f,0x6dc8c031,0x501b281e,0x80000000,0x531a9814,0x80000000,0x500d6018,0x6bd06037,0x685e3032,0x80000000,0x695a703c,0x80000000,0x50134810,0x80000000,0x5551b01d,0x80000000,0x5010081a,0x80000000,0x6b525058,0x80000000

struct Params {
  CUtensorMap x[2][2], wq[2], kv[2][2], wo[2];
  CUtensorMap o_ld[2], o_st[2], out_st[2];
  const __nv_bfloat16* kp[2];
  const __nv_bfloat16* vp[2];
};

constexpr int NPART = 32 * 5, O_BLOCKS = NBETA * 64 + 2 * NPART;
__device__ __align__(128) __nv_bfloat16 g_o[(size_t)O_BLOCKS * SQ * 64];
__device__ unsigned g_cnt[NBETA][8];
__device__ unsigned g_rd[NBETA][8];
__device__ unsigned g_epoch, g_next;
__device__ unsigned g_flag[NPART];

__device__ __forceinline__ uint32_t smem_u32(const void* p) { return (uint32_t)__cvta_generic_to_shared(p); }
__device__ __forceinline__ void mbar_arrive(uint32_t bar) {
  asm volatile("mbarrier.arrive.shared::cta.b64 _, [%0];" ::"r"(bar) : "memory");
}
__device__ __forceinline__ void mbar_arrive_warp(uint32_t bar) {
  asm volatile("{\n.reg .pred p;\nelect.sync _|p, 0xffffffff;\n@p mbarrier.arrive.shared::cta.b64 _, [%0];\n}" ::"r"(bar) : "memory");
}
__device__ __forceinline__ int lane_now() { int l; asm volatile("mov.u32 %0, %%laneid;" : "=r"(l)); return l; }
__device__ __forceinline__ bool mbar_try(uint32_t bar, uint32_t parity) {
  uint32_t ok;
  asm volatile("{\n.reg .pred p;\nmbarrier.try_wait.parity.shared::cta.b64 p, [%1], %2;\nselp.u32 %0, 1, 0, p;\n}"
               : "=r"(ok) : "r"(bar), "r"(parity) : "memory");
  return ok;
}
__device__ __forceinline__ bool mbar_test(uint32_t bar, uint32_t parity) {
  uint32_t ok;
  asm volatile("{\n.reg .pred p;\nmbarrier.test_wait.parity.shared::cta.b64 p, [%1], %2;\nselp.u32 %0, 1, 0, p;\n}"
               : "=r"(ok) : "r"(bar), "r"(parity) : "memory");
  return ok;
}
__device__ __forceinline__ void mbar_wait_w(uint32_t bar, uint32_t parity) {
  uint32_t n = 0;
  while (!__all_sync(0xffffffffu, mbar_try(bar, parity))) {
    if (++n > (1u << 22)) __trap();
  }
}
#define ELECT "{\n.reg .pred p;\nelect.sync _|p, 0xffffffff;\n@p "
__device__ __forceinline__ void tma_st3_w(const CUtensorMap* m, uint32_t src, int c1, int c2) {
  asm volatile(ELECT "cp.async.bulk.tensor.3d.global.shared::cta.bulk_group [%0, {0, %2, %3}], [%1];\n}"
               ::"l"(m), "r"(src), "r"(c1), "r"(c2) : "memory");
}
#define EXPECT(bar, bytes) "mbarrier.arrive.expect_tx.shared::cta.b64 _, [" bar "], " bytes ";\n@p "
__device__ __forceinline__ void tma_ld2_w(uint32_t dst, const CUtensorMap* m, int c0, int c1, uint32_t bar, uint32_t bytes) {
  asm volatile(ELECT EXPECT("%2", "%5") "cp.async.bulk.tensor.2d.shared::cluster.global.mbarrier::complete_tx::bytes [%0], [%1, {%3, %4}], [%2];\n}"
               ::"r"(dst), "l"(m), "r"(bar), "r"(c0), "r"(c1), "r"(bytes) : "memory");
}
__device__ __forceinline__ void tma_ld2_hint_w(uint32_t dst, const CUtensorMap* m, int c0, int c1, uint32_t bar, uint32_t bytes, uint64_t pol) {
  asm volatile(ELECT EXPECT("%2", "%6") "cp.async.bulk.tensor.2d.shared::cluster.global.mbarrier::complete_tx::bytes.L2::cache_hint"
               " [%0], [%1, {%3, %4}], [%2], %5;\n}"
               ::"r"(dst), "l"(m), "r"(bar), "r"(c0), "r"(c1), "l"(pol), "r"(bytes) : "memory");
}
__device__ __forceinline__ void tma_ld3_w(uint32_t dst, const CUtensorMap* m, int c0, int c1, int c2, uint32_t bar, uint32_t bytes) {
  asm volatile(ELECT EXPECT("%2", "%6") "cp.async.bulk.tensor.3d.shared::cluster.global.mbarrier::complete_tx::bytes [%0], [%1, {%3, %4, %5}], [%2];\n}"
               ::"r"(dst), "l"(m), "r"(bar), "r"(c0), "r"(c1), "r"(c2), "r"(bytes) : "memory");
}
__device__ __forceinline__ void tma_ld_kv_w(uint32_t dst, const CUtensorMap* m, int grp, uint32_t bar, uint64_t pol) {
  asm volatile(ELECT EXPECT("%2", "16384") "cp.async.bulk.tensor.4d.shared::cluster.global.mbarrier::complete_tx::bytes.L2::cache_hint"
               " [%0], [%1, {0, 0, 0, %3}], [%2], %4;\n}"
               ::"r"(dst), "l"(m), "r"(bar), "r"(grp), "l"(pol) : "memory");
}
__device__ __forceinline__ void tma_ld_wo_w(uint32_t dst, const CUtensorMap* m, int col, int grp, uint32_t bar) {
  asm volatile(ELECT EXPECT("%2", "16384") "cp.async.bulk.tensor.5d.shared::cluster.global.mbarrier::complete_tx::bytes [%0], [%1, {%3, 0, 0, 0, %4}], [%2];\n"
               "@p cp.async.bulk.tensor.5d.shared::cluster.global.mbarrier::complete_tx::bytes [%5], [%1, {%6, 0, 0, 0, %4}], [%2];\n}"
               ::"r"(dst), "l"(m), "r"(bar), "r"(col), "r"(grp), "r"(dst + 8192), "r"(col + 64) : "memory");
}
__device__ __forceinline__ void mbar_arrive8_w(uint32_t bar) {
  asm volatile(ELECT "mbarrier.arrive.shared::cta.b64 _, [%0], 8;\n}" ::"r"(bar) : "memory");
}
__device__ __forceinline__ uint32_t peer(uint32_t a) { uint32_t r; asm("mapa.shared::cluster.u32 %0, %1, %2;" : "=r"(r) : "r"(a), "r"(~blockIdx.x & 1)); return r; }
__device__ __forceinline__ void tma_ld2_both_w(uint32_t dst, const CUtensorMap* m, int c0, int c1, uint32_t bar, uint32_t bytes) {
  asm volatile(ELECT EXPECT("%2", "%5") "cp.async.bulk.tensor.2d.shared::cluster.global.mbarrier::complete_tx::bytes.multicast::cluster"
               " [%0], [%1, {%3, %4}], [%2], %6;\n}"
               ::"r"(dst), "l"(m), "r"(bar), "r"(c0), "r"(c1), "r"(bytes), "h"((uint16_t)3) : "memory");
}
__device__ __forceinline__ void tma_ld2_both_hint_w(uint32_t dst, const CUtensorMap* m, int c0, int c1, uint32_t bar, uint32_t bytes, uint64_t pol) {
  asm volatile(ELECT EXPECT("%2", "%6") "cp.async.bulk.tensor.2d.shared::cluster.global.mbarrier::complete_tx::bytes.multicast::cluster.L2::cache_hint"
               " [%0], [%1, {%3, %4}], [%2], %7, %5;\n}"
               ::"r"(dst), "l"(m), "r"(bar), "r"(c0), "r"(c1), "l"(pol), "r"(bytes), "h"((uint16_t)3) : "memory");
}
__device__ __forceinline__ void bulk_commit() { asm volatile("cp.async.bulk.commit_group;" ::: "memory"); }
template <int N> __device__ __forceinline__ void bulk_wait_read() { asm volatile("cp.async.bulk.wait_group.read %0;" ::"n"(N) : "memory"); }
__device__ __forceinline__ void wg_fence() { asm volatile("wgmma.fence.sync.aligned;" ::: "memory"); }
__device__ __forceinline__ void wg_commit() { asm volatile("wgmma.commit_group.sync.aligned;" ::: "memory"); }
template <int N> __device__ __forceinline__ void wg_wait() { asm volatile("wgmma.wait_group.sync.aligned %0;" ::"n"(N) : "memory"); }
__device__ __forceinline__ void fence_async_smem() { asm volatile("fence.proxy.async.shared::cta;" ::: "memory"); }
__device__ __forceinline__ void bar_sync(int id, int n) { asm volatile("bar.sync %0, %1;" ::"r"(id), "r"(n) : "memory"); }
__device__ __forceinline__ void touch(float& a) { asm volatile("neg.f32 %0, %0;" : "+f"(a)); }
__device__ __forceinline__ void touch(uint32_t& a) { asm volatile("not.b32 %0, %0;" : "+r"(a)); }
template <typename T, int N> __device__ __forceinline__ void touch(T (&a)[N]) {
#pragma unroll
  for (int i = 0; i < N; i++) touch(a[i]);
}
template <int ID, typename... A> __device__ __forceinline__ void sched_fence(uint32_t x, A&... a) {
  if (!((SF >> ID) & 1)) return;
  asm volatile("" : "+r"(x)::"memory");
#pragma unroll 1
  for (; __builtin_expect(x >= 100 + ID, 0); x >>= 1) { (touch(a), ...); __nanosleep(x); }
}
template <int N> __device__ __forceinline__ void reg_fence(float (&a)[N]) {
#pragma unroll
  for (int i = 0; i < N; i++) asm volatile("" : "+f"(a[i])::"memory");
}
template <int N> __device__ __forceinline__ void reg_fence(uint32_t (&a)[N]) {
#pragma unroll
  for (int i = 0; i < N; i++) asm volatile("" : "+r"(a[i])::"memory");
}
__device__ __forceinline__ float ex2(float x) { float y; asm("ex2.approx.ftz.f32 %0, %1;" : "=f"(y) : "f"(x)); return y; }
__device__ __forceinline__ uint32_t pack_bf16(float lo, float hi) {
  uint32_t r; asm("cvt.rn.bf16x2.f32 %0, %1, %2;" : "=r"(r) : "f"(hi), "f"(lo)); return r;
}
__device__ __forceinline__ void stsm4(uint32_t a, uint32_t r0, uint32_t r1, uint32_t r2, uint32_t r3) {
  asm volatile("stmatrix.sync.aligned.m8n8.x4.shared.b16 [%0], {%1, %2, %3, %4};" ::"r"(a), "r"(r0), "r"(r1), "r"(r2), "r"(r3) : "memory");
}
__device__ __forceinline__ void stsm4t(uint32_t a, uint32_t r0, uint32_t r1, uint32_t r2, uint32_t r3) {
  asm volatile("stmatrix.sync.aligned.m8n8.x4.trans.shared.b16 [%0], {%1, %2, %3, %4};" ::"r"(a), "r"(r0), "r"(r1), "r"(r2), "r"(r3) : "memory");
}
__device__ __forceinline__ void ldsm4(uint32_t a, uint32_t& r0, uint32_t& r1, uint32_t& r2, uint32_t& r3) {
  asm volatile("ldmatrix.sync.aligned.m8n8.x4.shared.b16 {%0, %1, %2, %3}, [%4];" : "=r"(r0), "=r"(r1), "=r"(r2), "=r"(r3) : "r"(a) : "memory");
}
__device__ __forceinline__ void sts16(uint32_t a, uint32_t v) { asm volatile("st.shared.u16 [%0], %1;" ::"r"(a), "h"((uint16_t)v) : "memory"); }
__device__ __forceinline__ void mma16816(float& c0, float& c1, float& c2, float& c3, uint32_t a0, uint32_t a1, uint32_t a2, uint32_t a3,
                                         uint32_t b0, uint32_t b1) {
  asm volatile("mma.sync.aligned.m16n8k16.row.col.f32.bf16.bf16.f32 {%0, %1, %2, %3}, {%4, %5, %6, %7}, {%8, %9}, {%0, %1, %2, %3};"
               : "+f"(c0), "+f"(c1), "+f"(c2), "+f"(c3) : "r"(a0), "r"(a1), "r"(a2), "r"(a3), "r"(b0), "r"(b1));
}
__device__ __forceinline__ uint32_t sdesc(uint32_t addr, uint32_t lbo) { return (addr >> 4) + ((lbo >> 4) << 16); }
__device__ __forceinline__ uint64_t desc64(uint32_t lo, uint32_t hi) { uint64_t d; asm("mov.b64 %0, {%1, %2};" : "=l"(d) : "r"(lo), "r"(hi)); return d; }
__device__ __forceinline__ void dadd(uint64_t& d, uint32_t inc) {
  asm("{\n.reg .b32 l, h;\nmov.b64 {l, h}, %0;\nadd.u32 l, l, %1;\nmov.b64 %0, {l, h};\n}" : "+l"(d) : "r"(inc));
}

struct Ring {
  uint32_t slot, phase, xp;
  __device__ __forceinline__ void uniform() {
    slot = __shfl_sync(0xffffffffu, slot, 0); phase = __shfl_sync(0xffffffffu, phase, 0); xp = __shfl_sync(0xffffffffu, xp, 0);
  }
  __device__ __forceinline__ void next() { if (++slot == NS) { slot = 0; phase ^= 1; } }
  __device__ __forceinline__ void next_if(bool p) { slot += p; if (slot == NS) { slot = 0; phase ^= 1; } }
};
__device__ __forceinline__ uint32_t borrow(int ks, int n) {
  const int k = ks + 1;
  return k >= 4 && !(k & 2) && k < n ? k & 1 : 2;
}

constexpr uint32_t Q_RANGES = NBETA * NH + __builtin_popcount(EARLY_MASK) * 5, Q_ALL = NBETA * (NH + 5);
constexpr int NRANGE = NCTA / 5;
struct Work { int kind, mode, k0, nsteps, range, beta, sub; };
struct Sched { uint16_t queue[Q_ALL]; uint32_t piece[NRANGE + 1][4]; };
constexpr Sched make_sched() {
  Sched s{};
  int q = 0, a = 0;
  for (int t = 0, e = 0; a < NBETA * NH; t++) {
    for (; e < NBETA && 8 * (e & ~PAIRB) + PK <= t && a >= P_POS; e++)
      for (int col = 0; col < 5 && (EARLY_MASK >> e & 1); col++) s.queue[q++] = 0x8000 | (e & 1 ? 4 - col : col) << 8 | e;
    for (int b = 0; b < NBETA; b++)
      for (int h = 0; h < NH; h++)
        if ((b >= B_LATE && h >= H_LATE ? 300 + b + LATE_G * (h >> 2) : 8 * (b & ~PAIRB) + KG * (h >> 2)) == t) { s.queue[q++] = b << 5 | h; a++; }
  }
  for (int b = 0; b < NBETA; b++)
    for (int col = 0; col < 5 && !(EARLY_MASK >> b & 1); col++) s.queue[q++] = 0x8000 | col << 8 | b;
  constexpr uint32_t T[NRANGE * 2] = {PIECE_TABLE};
  for (int g = 0; g <= NRANGE; g++)
    for (int n = 0; n < 4; n++) s.piece[g][n] = g < NRANGE && n < 2 ? T[2 * g + n] : 2u << 30;
  return s;
}
__constant__ Sched c_sched = make_sched();
constexpr int N_EARLY = __builtin_popcount(EARLY_MASK);
constexpr bool reuse_ok() {
  const Sched s = make_sched();
  int first[NBETA + OR] = {};
  for (int q = Q_RANGES - 1; q >= 0; q--) if (!(s.queue[q] & 0x8000)) first[s.queue[q] >> 5] = q;
  for (int q = 0; q < Q_RANGES; q++) if ((s.queue[q] & 0x8000) && (s.queue[q] & 31) >= OR0 && q - first[(s.queue[q] & 31) + OR] > NCTA - 32) return false;
  return first[OR0 + OR] >= NCTA && P_POS >= NCTA;
}
static_assert(reuse_ok());
template <bool SIMPLE> __device__ __forceinline__ bool o_reuse(uint32_t b) { return !SIMPLE && b - (OR0 + OR) < N_EARLY - OR0; }
template <bool SIMPLE> __device__ __forceinline__ uint32_t o_slot(uint32_t b) { return o_reuse<SIMPLE>(b) ? OR0 + (b - OR0) % OR : b; }
__device__ __forceinline__ Work decode(uint32_t d) {
  Work w;
  w.kind = d >> 30; if (w.kind == 3) w.kind = 1;
  w.mode = (d >> 28) & 3; w.k0 = (d >> 22) & 63;
  if (w.kind == 0) { w.beta = (d >> 5) & 31; w.sub = d & 31; w.nsteps = DM / 64; }
  else { w.beta = d & 31; w.sub = (d >> 8) & 7; w.nsteps = ((d >> 16) & 63) + 1; }
  w.range = ((d >> 11) & 31) * 5 + w.sub;
  return w;
}

__device__ __forceinline__ bool reached(const unsigned* cnt, unsigned target) {
  unsigned v;
  asm volatile("ld.acquire.gpu.global.u32 %0, [%1];" : "=r"(v) : "l"(cnt) : "memory");
  return (int)(v - target) >= 0;
}
__device__ __forceinline__ void wait_count(const unsigned* cnt, unsigned target) {
  unsigned n = 0;
  while (!__all_sync(0xffffffffu, reached(cnt, target))) { if (++n > (1u << 24)) __trap(); }
}
__device__ __forceinline__ uint32_t lds(uint32_t a) { uint32_t v; asm volatile("ld.volatile.shared.u32 %0, [%1];" : "=r"(v) : "r"(a) : "memory"); return v; }

#define TRACE(u, e)
#define T3(u, e)
#define T2C(u, e)
#define T2P(u, r, e)
#define TTAIL(k)
#define TCLK(k)
#define TO -1
#define TRACE_O(k) if (TO == k) TRACE(i, 5)
#define TRACE_P(u, e)
#define TRACE_IN(u, e)

struct Ctx {
  uint32_t sb;
  int wg, warp;
  uint32_t mqk, mpv;
  bool lead;
  int lane0, lane;
  int src;
};
template <int N> __device__ __forceinline__ uint32_t dhi(uint32_t lo) { return 0x40000040u + (lo >> (26 + N)); }
__device__ __forceinline__ void release(const Ctx& c, uint32_t slot) {
  if (c.lead) mbar_arrive(c.sb + BAR_EMPTY + slot * 8);
}
__device__ __forceinline__ uint32_t acquire(const Ctx& c, Ring& r, bool have = false) {
  const uint32_t s = r.slot;
  if (!have) mbar_wait_w(c.sb + BAR_FULL + s * 8, r.phase);
  r.next();
  return s;
}
__device__ __forceinline__ void mbar_wait2_w(uint32_t b0, uint32_t p0, uint32_t b1, uint32_t p1) {
  uint32_t n = 0;
  while (!__all_sync(0xffffffffu, mbar_try(b0, p0) & mbar_try(b1, p1))) {
    if (++n > (1u << 22)) __trap();
  }
}
__device__ __forceinline__ void mbar_wait3_w(uint32_t b0, uint32_t p0, uint32_t b1, uint32_t p1, uint32_t b2, uint32_t p2) {
  uint32_t n = 0;
  while (!__all_sync(0xffffffffu, mbar_try(b0, p0) & mbar_try(b1, p1) & mbar_try(b2, p2))) {
    if (++n > (1u << 22)) __trap();
  }
}
__device__ __forceinline__ void acquire2(const Ctx& c, Ring& r, uint32_t& s0, uint32_t& s1, bool have = false) {
  const uint32_t p0 = r.phase;
  s0 = r.slot; r.next(); s1 = r.slot;
  if (!have) mbar_wait2_w(c.sb + BAR_FULL + s0 * 8, p0, c.sb + BAR_FULL + s1 * 8, r.phase);
  r.next();
}
template <int N>
__device__ __forceinline__ bool peek(const Ctx& c, Ring r) {
  bool ok = true;
#pragma unroll
  for (int k = 0; k < N; k++) { ok &= mbar_test(c.sb + BAR_FULL + r.slot * 8, r.phase); r.next(); }
  return ok;
}
__device__ __forceinline__ void staged(const Ctx& c, int part) {
  fence_async_smem();
  __syncwarp();
  mbar_arrive_warp(c.sb + BAR_STG + c.wg * 16 + part * 8);
}

template <int WG, bool FIRST, int H>
__device__ __forceinline__ void proj_half(const Ctx& c, float (&acc)[64], uint32_t w, uint32_t x, uint32_t sw) {
  uint64_t dx = desc64((SB0 + x * SLOT + (WG ? 0 : H * 8192)) >> 4, dhi<0>(x) + sw);
  uint64_t dw = desc64(WG ? (SB0 + w * SLOT + H * 8192) >> 4 : sdesc(SB0 + w * SLOT, 8192), dhi<1>(x));
  wg_fence();
  if (WG) { if (FIRST) wgmma_proj96_init(acc, dw, dx, 0); else wgmma_proj96(acc, dw, dx, 1); }
  else { if (FIRST) wgmma_proj_init(acc, dx, dw, 0); else wgmma_proj(acc, dx, dw, 1); }
#pragma unroll
  for (int k = 1; k < 4; k++) {
    dadd(dx, k == 2 ? 2 + (sw >> 30) * 28 : 2); dadd(dw, 128);
    if (WG) wgmma_proj96(acc, dw, dx, 1); else wgmma_proj(acc, dx, dw, 1);
  }
  wg_commit();
}

__device__ __forceinline__ void proj_store16(uint32_t a, const float* f, float sc) {
  stsm4t(a, pack_bf16(f[0] * sc, f[1] * sc), pack_bf16(f[2] * sc, f[3] * sc), pack_bf16(f[4] * sc, f[5] * sc), pack_bf16(f[6] * sc, f[7] * sc));
}

__device__ __forceinline__ uint32_t stage_off(const Ctx& c) {
  const int lane = c.lane, mi = lane >> 3, r8 = lane & 7;
  return ((mi >> 1) * 8 + r8) * 128 + (((2 * c.warp + (mi & 1)) ^ r8) << 4);
}
__device__ __forceinline__ uint32_t q3_swz(uint32_t r8) { return ((r8 & 3) << 1) | (r8 >> 2); }
template <int H>
__device__ __forceinline__ void stage_t2(const Ctx& c, const float (&a)[64], float sc) {
  const uint32_t base = c.sb + QBUF_OFF + 2 * 16384 + H * 8192 + stage_off(c);
#pragma unroll
  for (int jj = 0; jj < 4; jj++) proj_store16(base + jj * 2048, &a[jj * 8], sc);
}
template <int H, bool IS_Q>
__device__ __forceinline__ void stage_t3(const Ctx& c, const float (&a)[64], float sc) {
  const uint32_t off = stage_off(c), r8 = (off >> 7) & 7;
  const uint32_t t3 = c.sb + QBUF_OFF + 3 * 16384 + H * 4096 + (IS_Q ? off ^ ((r8 ^ q3_swz(r8)) << 4) : off);
  proj_store16(t3, &a[32], sc);
  proj_store16(t3 + 2048, &a[40], sc);
}

template <int WG, int h, int NW = 4>
__device__ __forceinline__ void load_part(const Ctx& c, Ring r, uint32_t (&q)[32]) {
  uint32_t n = 0;
  while (NW && !__all_sync(0xffffffffu, peek<NW>(c, r))) {
    if (++n > (1u << 26)) __trap();
  }
  const int lane = c.lane, mi = lane >> 3, r8 = lane & 7;
  if (WG) { r.next(); r.next(); }
  const uint32_t off = c.sb + (WG ? stage_off(c) : (16 * c.warp + (mi & 1) * 8 + r8) * 128), t0 = off + r.slot * SLOT;
  r.next();
  const uint32_t t1 = off + r.slot * SLOT;
#pragma unroll
    for (int jj = 0; jj < (WG ? 6 : 8); jj++) {
      uint32_t* p = &q[4 * jj];
      if (WG) asm volatile("ldmatrix.sync.aligned.m8n8.x4.trans.shared.b16 {%0, %1, %2, %3}, [%4];" : "=r"(p[0]), "=r"(p[1]), "=r"(p[2]), "=r"(p[3])
                           : "r"((jj < 4 ? t0 + h * 8192 : t1 + h * 4096) + (jj & 3) * 2048) : "memory");
      else ldsm4((h ? t1 : t0) + (jj >> 2) * 8192 + (((((2 * jj) & 7) + (mi >> 1)) ^ r8) << 4), p[0], p[1], p[2], p[3]);
    }
}
template <int WG>
__device__ __forceinline__ void add_part(const Ctx& c, const uint32_t (&q)[32], float (&a)[64]) {
  const uint32_t one = (c.lane >> 3) == (c.lane & 3) ? 0x3f80u << (c.lane & 4) * 4 : 0;
#pragma unroll
  for (int i = 0; i < (WG ? 12 : 16); i++)
    asm("mma.sync.aligned.m16n8k8.row.col.f32.bf16.bf16.f32 {%0, %1, %2, %3}, {%4, %5}, {%6}, {%0, %1, %2, %3};"
        : "+f"(a[4 * i]), "+f"(a[4 * i + 1]), "+f"(a[4 * i + 2]), "+f"(a[4 * i + 3]) : "r"(q[2 * i]), "r"(q[2 * i + 1]), "r"(one));
}

__device__ __forceinline__ void trace_dump(const Ctx& c) {
}
struct RowSum { float l0, l1; };
__device__ __forceinline__ const char* o_addr(uint32_t item, int row, int lane) {
  return reinterpret_cast<const char*>(g_o) + (((item >> 10) * (2 * SQ) + row) * 128 + (lane ^ (lane >> 3)) * 16);
}
__device__ __forceinline__ void o_stg(const char* p, int i, const uint32_t* q) {
  asm volatile("st.global.v4.b32 [%0], {%1, %2, %3, %4};"
               ::"l"(p + (i >> 1) * (SQ * 128) + (i & 1) * 512), "r"(q[0]), "r"(q[1]), "r"(q[2]), "r"(q[3]) : "memory");
}
template <int MODE, int I0 = 0, int NI = 4>
__device__ __forceinline__ void o_emit(const char* p, const float (&o)[64], float inv) {
#pragma unroll
  for (int i = I0; i < I0 + NI; i++) {
    uint32_t q[4];
#pragma unroll
    for (int j = 0; j < 4; j++) q[j] = pack_bf16(o[16 * i + 4 * j + 2 * MODE] * inv, o[16 * i + 4 * j + 2 * MODE + 1] * inv);
    o_stg(p, i, q);
  }
}
__device__ __forceinline__ void o_done(const Ctx& c) {
  __syncwarp();
  mbar_arrive_warp(c.sb + BAR_OUT);
  __syncwarp();
}
template <int WG>
__device__ __forceinline__ void o_first(const Ctx& c, uint32_t item, float (&o)[64], const RowSum& inv, uint32_t (&q)[32]) {
  const char* p = o_addr(item, WG ? 192 + 8 * c.warp : 64 + 16 * c.warp, c.lane);
  reg_fence(o);
#pragma unroll
  for (int j = 0; j < 16; j++) {
    if (WG) q[j] = pack_bf16((o[4 * j] + o[4 * j + 2]) * inv.l0, (o[4 * j + 1] + o[4 * j + 3]) * inv.l0);
    else q[j] = pack_bf16(o[4 * j] * inv.l0, o[4 * j + 1] * inv.l0);
    if (!WG && (j & 3) == 3 && (j >> 2) < 8 - LATE0) o_stg(p, j >> 2, q + j - 3);
  }
#pragma unroll
  for (int j = 0; j < 16; j++) {
    if (!WG) q[16 + j] = pack_bf16(o[4 * j + 2] * inv.l1, o[4 * j + 3] * inv.l1);
    if ((j & 3) == 3 && (j >> 2) < 4 - (WG ? LATE1 : LATE0)) o_stg(WG ? p : p + 1024, j >> 2, q + (WG ? 0 : 16) + j - 3);
  }
}
template <int WG>
__device__ __forceinline__ void o_rest(const Ctx& c, uint32_t item, uint32_t (&q)[32]) {
  const char* p = o_addr(item, WG ? 192 + 8 * c.warp : 64 + 16 * c.warp, c.lane);
#pragma unroll
  for (int i = WG ? 4 - LATE1 : 8 - LATE0; i < (WG ? 4 : 8); i++) o_stg(p + (i >> 2) * 1024, i & 3, q + 4 * i);
}
template <int K0, int K1>
__device__ __forceinline__ void o_piece(const Ctx& c, const char* p, int k, const float (&o)[64], const RowSum& inv) {
  constexpr int NI = 8 / O_STEPS, M = K0 * NI / 4;
  if constexpr (K1 - K0 == 1) {
    o_emit<M, K0 * NI % 4, NI>(p + M * 1024, o, M ? inv.l1 : inv.l0);
    if (K1 == O_STEPS) o_done(c);
  } else {
    if (k <= (K0 + K1) / 2) o_piece<K0, (K0 + K1) / 2>(c, p, k, o, inv); else o_piece<(K0 + K1) / 2, K1>(c, p, k, o, inv);
  }
}
template <int WG>
__device__ __forceinline__ void o_second(const Ctx& c, uint32_t item, int k, float (&o)[64], const RowSum& inv) {
  reg_fence(o);
  o_piece<0, O_STEPS>(c, o_addr(item, 128 * WG + 16 * c.warp, c.lane0 + (k >> 8)), k, o, inv);
}
template <int WG>
__device__ __forceinline__ void release_q(const Ctx& c) {
#pragma unroll
  for (int t = 0; t < 2; t++)
    if (c.lead) asm volatile("mbarrier.arrive.shared::cta.b64 _, [%0], 2;" ::"r"(c.sb + BAR_EMPTY + (NS + 2 * WG + t) * 8) : "memory");
  __syncwarp();
}
struct Slots { uint32_t w, x, o, po; };
template <int WG>
__device__ __forceinline__ void acc_fence(float (&a)[64]) {
#pragma unroll
  for (int i = 0; i < (WG ? 48 : 64); i++) asm volatile("" : "+f"(a[i])::"memory");
}
template <int WG>
__device__ __forceinline__ void begin_acquire(const Ctx& c, Ring& r, Slots& h, bool wait) {
  const uint32_t s0 = r.slot, p0 = r.phase, f = c.sb + BAR_FULL;
  r.next();
  const uint32_t p1 = r.phase;
  h.w = r.slot; r.next();
  h.x = WG ? r.slot : s0; h.o = WG ? s0 : r.slot; h.po = r.phase;
  if (wait) { if (WG) mbar_wait3_w(f + s0 * 8, p0, f + h.w * 8, p1, f + h.x * 8, r.phase); else mbar_wait2_w(f + s0 * 8, p0, f + h.w * 8, p1); }
  r.next();
}
template <int WG>
__device__ __forceinline__ void proj_begin(const Ctx& c, Ring& r, float (&a0)[64], Slots& h, bool wait, uint32_t sw) {
  begin_acquire<WG>(c, r, h, wait);
  proj_half<WG, true, 0>(c, a0, h.w, h.x, sw);
  if (WG) release(c, h.o);
}
template <int WG>
__device__ __forceinline__ void proj_main(Ctx& c, Ring& r, float (&a0)[64], float (&a1)[64], Slots& h, int n, uint32_t sw, int unit,
                                          uint32_t item, int nq, float (&o1)[64], const RowSum& inv) {
  constexpr bool DEEP = (PDEPTH >> WG) & 1;
  T2C(unit, 3);
  int ks = 1;
#pragma unroll 1
  do {
    const Slots p = h;
    const uint32_t b = borrow(ks, n), tile = NS + (WG ? 3 - b : b), f = c.sb + BAR_FULL;
    const uint32_t s0 = b != 2 ? tile : r.slot, p0 = b != 2 ? (r.xp >> b) & 1 : r.phase;
    r.next_if(b == 2);
    const uint32_t p1 = r.phase;
    h.w = r.slot; r.next();
    const uint32_t s2 = b != 2 ? tile : r.slot;
    h.po = b != 2 ? p0 : r.phase;
    r.next_if(b == 2);
    r.xp ^= 1 << b;
    h.x = WG ? s2 : s0; h.o = WG ? s0 : s2;
    mbar_wait3_w(f + s0 * 8, p0, f + h.w * 8, p1, f + (WG ? s2 : p.o) * 8, WG ? h.po : p.po);
    if (ks < 10) T2C(unit, ks * 4);
    if (DEEP) {
      proj_half<WG, false, 0>(c, a0, h.w, h.x, sw);
      release(c, WG ? h.o : p.o);
      if (ks < 10) T2C(unit, ks * 4 + 1);
      wg_wait<1>();
      if (ks < 10) T2C(unit, ks * 4 + 2);
      release(c, p.x); release(c, p.w);
    } else {
      release(c, WG ? h.o : p.o);
      wg_wait<0>();
      release(c, p.x); release(c, p.w);
      if (ks < 10) T2C(unit, ks * 4 + 1);
      proj_half<WG, false, 0>(c, a0, h.w, h.x, sw);
      if (ks < 10) T2C(unit, ks * 4 + 2);
    }
    proj_half<WG, false, 1>(c, a1, h.w, h.x, sw);
    if (ks < 10) T2C(unit, ks * 4 + 3);
    if (ks <= nq) o_second<WG>(c, item, ks, o1, inv);
  } while (++ks != n);
  {
    const uint32_t e0 = c.sb + BAR_EMPTY + (NS + 3 * WG) * 8, e1 = c.sb + BAR_EMPTY + (NS + 1 + WG) * 8;
    const uint32_t p0 = (r.xp ^ unit ^ 1) & 1, p1 = ((r.xp >> 1) ^ unit ^ 1) & 1;
    const uint32_t k0 = sw ? e0 : c.sb + BAR_FULL + r.slot * 8, pk = sw ? p0 : r.phase;
    uint32_t cnt = 0;
    while (!__all_sync(0xffffffffu, mbar_try(e0, p0) & mbar_try(e1, p1) & mbar_try(k0, pk) & (WG || mbar_try(c.sb + BAR_FULL + h.o * 8, h.po)))) {
      if (++cnt > (1u << 22)) __trap();
    }
  }
  c.lane = c.lane0 + (h.w >> 5);
  if (!WG) release(c, h.o);
}
template <int WG>
__device__ __forceinline__ void proj_end(const Ctx& c, float (&a1)[64], const Slots& h) {
  wg_wait<0>();
  acc_fence<WG>(a1);
  release(c, h.x); release(c, h.w);
}
__device__ __forceinline__ uint32_t get_desc(const Ctx& c, int i) {
  uint32_t d;
  mbar_wait_w(c.sb + BAR_DESC, (i - 1) & 1);
  asm volatile("ld.volatile.shared.u32 %0, [%1];" : "=r"(d) : "r"(c.sb + DESC_OFF + (i & 3) * 4) : "memory");
  return __shfl_sync(0xffffffffu, d, 0);
}

__device__ __forceinline__ float quad_max(float x) {
  x = fmaxf(x, __shfl_xor_sync(0xffffffffu, x, 1));
  return fmaxf(x, __shfl_xor_sync(0xffffffffu, x, 2));
}
__device__ __forceinline__ float quad_sum(float x) {
  x += __shfl_xor_sync(0xffffffffu, x, 1);
  return x + __shfl_xor_sync(0xffffffffu, x, 2);
}
template <bool SP, bool FIRST>
__device__ __forceinline__ void exps(const Ctx& c, const float (&s)[32], uint32_t (&p)[SP ? 8 : 16], RowSum& st) {
  if constexpr (SP) {
    uint32_t q[8];
    float t;
#pragma unroll
    for (int j = 0; j < 8; j++) {
      const float e0 = ex2(s[4 * j] + s[4 * j + 2]), e1 = ex2(s[4 * j + 1] + s[4 * j + 3]);
      if (j == 0) t = e0 + e1; else t += e0 + e1;
      q[j] = pack_bf16(e0, e1);
    }
    const bool odd = c.src & 2;
#pragma unroll
    for (int g = 0; g < 4; g++) {
      p[2 * g] = __shfl_sync(0xffffffffu, odd ? q[2 * g + 1] : q[2 * g], c.src);
      p[2 * g + 1] = __shfl_sync(0xffffffffu, odd ? q[2 * g] : q[2 * g + 1], c.src ^ 1);
    }
    st.l0 = FIRST ? t : st.l0 + t;
  } else {
    float t0, t1;
#pragma unroll
    for (int j = 0; j < 8; j++) {
      const float e0 = ex2(s[4 * j]), e1 = ex2(s[4 * j + 1]), e2 = ex2(s[4 * j + 2]), e3 = ex2(s[4 * j + 3]);
      if (j == 0) { t0 = e0 + e1; t1 = e2 + e3; } else { t0 += e0 + e1; t1 += e2 + e3; }
      p[2 * j] = pack_bf16(e0, e1);
      p[2 * j + 1] = pack_bf16(e2, e3);
    }
    st.l0 = FIRST ? t0 : st.l0 + t0;
    st.l1 = FIRST ? t1 : st.l1 + t1;
  }
}
template <bool SP>
__device__ __forceinline__ bool finish_sums(RowSum& st) {
  const float a = quad_sum(st.l0), b = SP ? a : quad_sum(st.l1);
  st.l0 = __fdividef(1.f, a); st.l1 = __fdividef(1.f, b);
  return !(a >= SUM_LO && a <= SUM_HI && b >= SUM_LO && b <= SUM_HI);
}
template <bool SP, bool INIT, int SITE, bool COMMIT = true, int RM = 0>
__device__ __forceinline__ void issue_qk(const Ctx& c, float (&s)[32], const uint32_t (&qs)[32], uint32_t dq, uint32_t dk) {
  uint64_t a = desc64(dq, dhi<SITE & 1>(dk)), b = desc64(dk, dhi<1 - (SITE & 1)>(dk) + 64);
  if (SP) {
    if (INIT) wgmma_qk_sp_init(s, qs[0], qs[1], qs[2], qs[3], b, 0, c.mqk); else wgmma_qk_sp(s, qs[0], qs[1], qs[2], qs[3], b, 0, c.mqk);
#pragma unroll
    for (int k = 1; k < 4; k++) { dadd(b, k == 2 ? 60 : 4); wgmma_qk_sp(s, qs[4 * k], qs[4 * k + 1], qs[4 * k + 2], qs[4 * k + 3], b, 1, c.mqk); }
  } else {
    if (RM & 1) wgmma_qk_rs(s, qs[0], qs[1], qs[2], qs[3], b, 0); else if (INIT) wgmma_qk_init(s, a, b, 0); else wgmma_qk(s, a, b, 0);
#pragma unroll
    for (int k = 1; k < 8; k++) {
      dadd(a, k == 4 ? 506 : 2); dadd(b, k == 4 ? 58 : 2);
      if (RM >> k & 1) wgmma_qk_rs(s, qs[4 * k], qs[4 * k + 1], qs[4 * k + 2], qs[4 * k + 3], b, 1); else wgmma_qk(s, a, b, 1);
    }
  }
  if (COMMIT) wg_commit();
}
template <bool SP, bool ACC, int SITE, bool SPLIT = false>
__device__ __forceinline__ void issue_pv(const Ctx& c, float (&o)[64], const uint32_t (&p)[SP ? 8 : 16], uint32_t dv) {
  uint64_t b = desc64(dv, dhi<SITE & 1>(dv) + 64);
  if constexpr (SP) {
    if (ACC) wgmma_pv_sp(o, p[0], p[1], p[2], p[3], b, 1, c.mpv); else wgmma_pv_sp_init(o, p[0], p[1], p[2], p[3], b, 0, c.mpv);
    if (SPLIT) wg_commit();
    dadd(b, 512);
    wgmma_pv_sp(o, p[4], p[5], p[6], p[7], b, 1, c.mpv);
  } else {
    if (ACC) wgmma_pv(o, p[0], p[1], p[2], p[3], b, 1); else wgmma_pv_init(o, p[0], p[1], p[2], p[3], b, 0);
#pragma unroll
    for (int k = 1; k < 4; k++) { dadd(b, 256); wgmma_pv(o, p[4 * k], p[4 * k + 1], p[4 * k + 2], p[4 * k + 3], b, 1); }
  }
  wg_commit();
}
__device__ __forceinline__ void pack_rows(const float (&o)[64], float sc, uint32_t (&q)[32]) {
#pragma unroll
  for (int j = 0; j < 32; j++) q[j] = pack_bf16(o[2 * j] * sc, o[2 * j + 1] * sc);
}
template <int MASK = 255>
__device__ __forceinline__ void stage_rows(const Ctx& c, uint32_t tile_addr, const uint32_t (&q)[32]) {
  const int lane = c.lane, mi = lane >> 3, r8 = lane & 7;
  const uint32_t row_addr = tile_addr + (16 * c.warp + (mi & 1) * 8 + r8) * 128;
#pragma unroll
  for (int jj = 0; jj < 8; jj++)
    if (MASK >> jj & 1) stsm4(row_addr + (jj >> 2) * 8192 + (((((2 * jj) & 7) + (mi >> 1)) ^ r8) << 4), q[4 * jj], q[4 * jj + 1], q[4 * jj + 2], q[4 * jj + 3]);
}
__device__ __forceinline__ void stage_rows(const Ctx& c, uint32_t tile_addr, const float (&o)[64], float sc) {
  uint32_t q[32];
  pack_rows(o, sc, q);
  stage_rows(c, tile_addr, q);
}
template <int WG, int H>
__device__ __forceinline__ void stage_out(const Ctx& c, const float (&a)[64]) {
  if (WG) { stage_t3<H, false>(c, a, 1.f); if (H) staged(c, 0); stage_t2<H>(c, a, 1.f); }
  else stage_rows(c, c.sb + QBUF_OFF + H * 16384, a, 1.f);
  if (H || !WG) staged(c, H);
}
template <int SITE>
__device__ __forceinline__ void issue_qk_rs(float (&s)[32], uint32_t (&q)[32], uint32_t dk) {
  uint64_t b = desc64(dk, dhi<SITE>(dk) + 64);
  reg_fence(q);
  wg_fence();
  wgmma_qk_rs_init(s, q[0], q[1], q[2], q[3], b, 0);
#pragma unroll
  for (int k = 1; k < 8; k++) { dadd(b, k == 4 ? 58 : 2); wgmma_qk_rs(s, q[4 * k], q[4 * k + 1], q[4 * k + 2], q[4 * k + 3], b, 1); }
  wg_commit();
}

__device__ __forceinline__ void redo_tile(const Ctx& c, uint32_t q_addr, uint32_t half, const __nv_bfloat16* kp, const __nv_bfloat16* vp,
                                          uint32_t item, int row) {
  float o[64];
  const int lane = lane_now(), g = lane >> 2, cc = lane & 3, mi = lane >> 3, r8 = lane & 7;
  const uint32_t qa = q_addr + (half == 4096 ? 8 * c.warp + r8 : 16 * c.warp + (mi & 1) * 8 + r8) * 128, swz = half == 4096 ? q3_swz(r8) : r8;
  const uint32_t* kq = reinterpret_cast<const uint32_t*>(kp + g * DH) + cc;
  const unsigned short* vq = reinterpret_cast<const unsigned short*>(vp + 2 * cc * DH) + g;
  float m0 = -INFINITY, m1 = -INFINITY, l0 = 0.f, l1 = 0.f;
#pragma unroll
  for (int i = 0; i < 64; i++) o[i] = 0.f;
#pragma unroll 1
  for (int kb = 0; kb < SK / 16; kb++) {
    float z[8] = {0.f, 0.f, 0.f, 0.f, 0.f, 0.f, 0.f, 0.f};
#pragma unroll 2
    for (int kk = 0; kk < 8; kk++) {
      uint32_t a0, a1, a2, a3;
      ldsm4(qa + (kk >> 2) * half + ((((kk & 3) * 2 + (mi >> 1)) ^ swz) << 4), a0, a1, a2, a3);
      const uint32_t* kr = kq + kb * (16 * DH / 2) + kk * 8;
      mma16816(z[0], z[1], z[2], z[3], a0, a1, a2, a3, __ldg(kr), __ldg(kr + 4));
      mma16816(z[4], z[5], z[6], z[7], a0, a1, a2, a3, __ldg(kr + 8 * DH / 2), __ldg(kr + 8 * DH / 2 + 4));
    }
    const float n0 = fmaxf(m0, quad_max(fmaxf(fmaxf(z[0], z[1]), fmaxf(z[4], z[5]))));
    const float n1 = fmaxf(m1, quad_max(fmaxf(fmaxf(z[2], z[3]), fmaxf(z[6], z[7]))));
    const float al0 = ex2(m0 - n0), al1 = ex2(m1 - n1);
    m0 = n0; m1 = n1;
#pragma unroll
    for (int i = 0; i < 8; i++) z[i] = ex2(z[i] - ((i & 2) ? n1 : n0));
    l0 = l0 * al0 + (z[0] + z[1]) + (z[4] + z[5]);
    l1 = l1 * al1 + (z[2] + z[3]) + (z[6] + z[7]);
    const uint32_t a0 = pack_bf16(z[0], z[1]), a1 = pack_bf16(z[2], z[3]), a2 = pack_bf16(z[4], z[5]), a3 = pack_bf16(z[6], z[7]);
    const unsigned short* vr = vq + kb * (16 * DH);
#pragma unroll
    for (int nb = 0; nb < 16; nb++) {
      o[4 * nb] *= al0; o[4 * nb + 1] *= al0; o[4 * nb + 2] *= al1; o[4 * nb + 3] *= al1;
      const uint32_t b0 = __ldg(vr + nb * 8) | ((uint32_t)__ldg(vr + nb * 8 + DH) << 16);
      const uint32_t b1 = __ldg(vr + nb * 8 + 8 * DH) | ((uint32_t)__ldg(vr + nb * 8 + 9 * DH) << 16);
      mma16816(o[4 * nb], o[4 * nb + 1], o[4 * nb + 2], o[4 * nb + 3], a0, a1, a2, a3, b0, b1);
    }
  }
  const char* p = o_addr(item, row, lane);
  o_emit<0>(p, o, __fdividef(1.f, quad_sum(l0)));
  o_emit<1>(half == 4096 ? p : p + 1024, o, __fdividef(1.f, quad_sum(l1)));
}

template <bool SPA, bool SPB, int SITE, int ID>
__device__ __forceinline__ void batch(const Ctx& c, float (&s)[32], const uint32_t (&qs)[32], uint32_t dq, uint32_t dk, float (&ob)[64],
                                      uint32_t (&pb)[SPB ? 8 : 16], uint32_t dv) {
  if constexpr (SPA) {
    reg_fence(pb);
    wg_fence();
    issue_pv<SPB, true, ID>(c, ob, pb, dv);
    issue_qk<SPA, false, ID>(c, s, qs, dq, dk);
  } else {
    constexpr bool EARLY = ((QK_EARLY_MASK >> (SITE + (SPB ? 2 : 0))) & 1) != 0;
    if (!EARLY) reg_fence(pb);
    wg_fence();
    issue_qk<SPA, false, ID, !SPB, SITE ? RM0 : SPB ? RM2 : RM1>(c, s, qs, dq, dk);
    if (EARLY) { reg_fence(pb); wg_fence(); }
    issue_pv<SPB, true, ID, SPB>(c, ob, pb, dv);
  }
}

template <bool SP0>
__device__ __forceinline__ bool attention(Ctx& c, Ring& r, int unit, uint32_t& d, const float (&a0)[64], float (&o0)[64], float (&o1)[64],
                                          RowSum& st0, RowSum& st1, const Slots& h, uint32_t (&q1)[32]) {
  constexpr bool SP1 = false;
  if (SP0) { c.mqk = META_QK + (d >> 28); c.mpv = META_PV + (d >> 28); asm volatile("" : "+r"(c.mqk), "+r"(c.mpv)); }
  if (SP0) c.src = (c.lane & 28) | ((c.lane & 1) << 1) | ((c.lane >> 1) & 1);
  float s[32];
  uint32_t p0[SP0 ? 8 : 16], p1[16];
  const uint32_t q0a = c.sb + QBUF_OFF + (SP0 ? 3 : 0) * 16384, q1a = c.sb + QBUF_OFF + (SP0 ? 2 : 1) * 16384;
  const uint32_t dq0 = sdesc(SB0 + QBUF_OFF, 0), dq1 = sdesc(SB0 + QBUF_OFF + (SP0 ? 2 : 1) * 16384, 0);
  uint32_t sk = acquire(c, r, true), sv, sn;
  uint32_t qs[32];
  float s1[32];
  if (SP0) {
    stage_t3<0, true>(c, a0, SM_C);
    stage_t2<0>(c, a0, SM_C);
    proj_end<1>(c, o0, h);
    stage_t3<1, true>(c, o0, SM_C);
    stage_t2<1>(c, o0, SM_C);
    bar_sync(5, 128);
    const int g = c.lane >> 2, cc = c.lane & 3;
    const uint32_t qa = q0a + (8 * c.warp + g) * 128 + (cc & 1) * 8;
#pragma unroll
    for (int k = 0; k < 8; k++)
      asm volatile("ld.shared.v2.u32 {%0, %1}, [%2];" : "=r"(qs[2 * k]), "=r"(qs[2 * k + 1])
                   : "r"(qa + (k >> 2) * 4096 + ((((k & 3) * 2 + (cc >> 1)) ^ q3_swz(g)) << 4)) : "memory");
    fence_async_smem();
    bar_sync(1, 256);
    TRACE(unit, 2);
    wg_fence();
    issue_qk<SP1, true, 1>(c, s1, qs, dq1, sdesc(SB0 + sk * SLOT, 0));
#pragma unroll
    for (int k = 0; k < 8; k++)
      if (RM2 >> k & 1) ldsm4(q1a + (k >> 2) * 8192 + (16 * c.warp + (c.lane & 15)) * 128 + (((2 * (k & 3) + (c.lane >> 4)) ^ (c.lane & 7)) << 4),
                              q1[4 * k], q1[4 * k + 1], q1[4 * k + 2], q1[4 * k + 3]);
#pragma unroll
    for (int k = 0; k < 16; k++) asm volatile("" : "+r"(qs[k])::"memory");
    wg_fence();
    issue_qk<SP0, true, 0>(c, s, qs, dq0, sdesc(SB0 + sk * SLOT, 0));
    const bool have = peek<2>(c, r);
    wg_wait<1>();
    reg_fence(s1);
    exps<SP1, true>(c, s1, p1, st1);
    sched_fence<11>(sk, p1);
    acquire2(c, r, sv, sn, __all_sync(0xffffffffu, have));
    wg_wait<0>();
    wg_fence();
    issue_pv<SP1, false, 1>(c, o1, p1, sdesc(SB0 + sv * SLOT, 1024));
    if (LAG_BAR & 1) asm volatile("bar.arrive 4, 256;" ::: "memory");
    sched_fence<12>(sk, s);
    release(c, sk);
    sk = sn;
    exps<SP0, true>(c, s, p0, st0);
    reg_fence(p0);
    wg_fence();
    issue_pv<SP0, false, 0>(c, o0, p0, sdesc(SB0 + sv * SLOT, 1024));
    issue_qk<SP0, true, 2>(c, s, qs, dq0, sdesc(SB0 + sk * SLOT, 0));
    sn = acquire(c, r);
    wg_wait<0>();
    reg_fence(s);
  } else {
    pack_rows(a0, SM_C, qs);
    stage_rows(c, q0a, qs);
    proj_end<0>(c, o1, h);
    TRACE(unit, 2);
    float sc = SM_C;
    issue_qk_rs<0>(s, qs, sdesc(SB0 + sk * SLOT, 0));
    sched_fence<0>(sk, sc);
    pack_rows(o1, sc, q1);
    stage_rows<~RM1>(c, q1a, q1);
    issue_qk_rs<1>(s1, q1, sdesc(SB0 + sk * SLOT, 0));
    asm volatile("bar.arrive 1, 256;" ::: "memory");
    bool have = peek<2>(c, r);
    wg_wait<1>();
    reg_fence(s);
    exps<SP0, true>(c, s, p0, st0);
    sched_fence<1>(sk, p0);
    acquire2(c, r, sv, sn, __all_sync(0xffffffffu, have));
    wg_wait<0>();
    reg_fence(s1);
    fence_async_smem();
    __syncwarp();
    wg_fence();
    issue_qk<SP0, false, 2, true, RM0>(c, s, qs, dq0, sdesc(SB0 + sn * SLOT, 0));
    issue_pv<SP0, false, 0>(c, o0, p0, sdesc(SB0 + sv * SLOT, 1024));
    sched_fence<2>(sk, s1);
    release(c, sk);
    have = peek<1>(c, r);
    sk = sn;
    exps<SP1, true>(c, s1, p1, st1);
    reg_fence(p1);
    wg_fence();
    issue_pv<SP1, false, 1>(c, o1, p1, sdesc(SB0 + sv * SLOT, 1024));
    sn = acquire(c, r, __all_sync(0xffffffffu, have));
    if (LAG_BAR & 1) bar_sync(4, 256);
    wg_wait<1>();
    reg_fence(s);
  }
  TRACE_IN(unit, 4);
  T2C(unit, 51);
#pragma unroll 1
  for (int j = 1; j < 15; j++) {
    const uint32_t sv_prev = sv, sk_prev = sk;
    sv = sn;
    const uint32_t dv = sdesc(SB0 + sv * SLOT, 1024);
    reg_fence(p0);
    exps<SP0, false>(c, s, p0, st0);
    batch<SP1, SP0, 0, 3>(c, s, q1, dq1, sdesc(SB0 + sk * SLOT, 0), o0, p0, dv);
    sk = acquire(c, r);
    wg_wait<1>();
    reg_fence(s); reg_fence(p1);
    release(c, sv_prev); release(c, sk_prev);
    exps<SP1, false>(c, s, p1, st1);
    batch<SP0, SP1, 1, 4>(c, s, qs, dq0, sdesc(SB0 + sk * SLOT, 0), o1, p1, dv);
    sn = acquire(c, r);
    if (SP0) wg_wait<0>(); else wg_wait<1>();
    reg_fence(s);
  }
  TRACE_IN(unit, 5);
  T2C(unit + 1, 52);
  const uint32_t sv_prev = sv;
  sv = sn;
  const uint32_t dv = sdesc(SB0 + sv * SLOT, 1024);
  reg_fence(p0);
  exps<SP0, false>(c, s, p0, st0);
  batch<SP1, SP0, 0, 5>(c, s, q1, dq1, sdesc(SB0 + sk * SLOT, 0), o0, p0, dv);
  asm volatile("ld.volatile.shared.u32 %0, [%1];" : "=r"(d) : "r"(c.sb + DESC_OFF + ((unit + 1) & 3) * 4) : "memory");
  const bool have = peek<2 + SP0>(c, r);
  wg_wait<1>();
  reg_fence(s); reg_fence(p1);
  release(c, sv_prev); release(c, sk);
  exps<SP1, false>(c, s, p1, st1);
  reg_fence(p1);
  wg_fence();
  issue_pv<SP1, true, 2>(c, o1, p1, dv);
  if (SP0) sched_fence<6>(sk, st0.l0, st1.l0, st1.l1); else sched_fence<5>(sk, st0.l0, st0.l1, st1.l0, st1.l1);
  c.lane = c.lane0 + (sk >> 5);
  const bool bad = finish_sums<SP0>(st0) | finish_sums<SP1>(st1);
  uint32_t any;
  asm volatile("{\n.reg .pred p, q;\nsetp.ne.u32 p, %1, 0;\nbar.red.or.pred q, %2, 128, p;\nselp.u32 %0, 1, 0, q;\n}"
               : "=r"(any) : "r"((uint32_t)bad), "n"(2 + SP0) : "memory");
  any = __any_sync(0xffffffffu, any);
  d = __shfl_sync(0xffffffffu, d, 0);
  if (d < (2u << 30) && !__all_sync(0xffffffffu, have)) { Ring t = r; Slots u; begin_acquire<SP0>(c, t, u, true); }
  wg_wait<0>();
  reg_fence(o0); reg_fence(o1);
  release(c, sv);
  return any;
}

template <int WG>
__device__ __forceinline__ void consumer(Ctx c, const __nv_bfloat16* const* kv) {
  asm volatile("setmaxnreg.inc.sync.aligned.u32 %0;" ::"n"(WG ? REG_C : 504 - REG_C - REG_P));
  c.wg = WG;
  Ring r{0, 0, 0};
  float a0[64], a1[64], o1[64];
  Slots h;
  RowSum inv0, inv1;
  uint32_t oq[32];
  uint32_t d = c_sched.queue[blockIdx.x] * 1025, dc = 0, sw;
  int i = 0, nq;
begin:
  sw = d & (1u << 30);
  proj_begin<WG>(c, r, a0, h, true, sw);
  proj_half<WG, true, 1>(c, a1, h.w, h.x, sw);
  nq = 0;
#pragma unroll
  for (int k = 0; k < 64; k++) asm volatile("" : "=f"(o1[k]));
  asm volatile("" : "=f"(inv1.l0), "=f"(inv1.l1));
  while (true) {
    TRACE(i, 0); TRACE(i, 6);
    proj_main<WG>(c, r, a0, a1, h, d >> 30 ? ((d >> 16) & 63) + 1 : DM / 64, sw, i, dc, nq, o1, inv1);
    dc = d;
    TRACE(i, 1);
    if (d >> 30) goto out_tile;
    wg_wait<1>();
    acc_fence<WG>(a0);
    if (WG ? attention<WG>(c, r, i, d, a0, a1, o1, inv0, inv1, h, oq) : attention<WG>(c, r, i, d, a0, o1, a1, inv1, inv0, h, oq)) goto redo;
    if (d >= (2u << 30)) break;
    sw = d & (1u << 30);
    proj_begin<WG>(c, r, a0, h, false, sw);
    release_q<WG>(c);
    if (WG) sched_fence<8>(h.w, inv0.l0); else sched_fence<7>(h.w, inv0.l0, inv0.l1);
    o_first<WG>(c, dc, a1, inv0, oq);
    sched_fence<9>(h.w, inv1.l0);
    proj_half<WG, true, 1>(c, a1, h.w, h.x, sw);
    o_rest<WG>(c, dc, oq);
    nq = O_STEPS;
    TRACE(i, 3); TRACE(i, 7);
    i++;
  }
  release_q<WG>(c);
  o_first<WG>(c, dc, a1, inv0, oq);
  o_rest<WG>(c, dc, oq);
#pragma unroll
  for (int k = 1; k <= O_STEPS; k++) o_second<WG>(c, dc, k, o1, inv1);
next:
  TRACE(i, 3); TRACE(i, 7);
  if ((d >> 30) != 2) {
    i++;
    r.uniform();
    goto begin;
  }
  trace_dump(c);
  return;
out_tile:
  if (d & 96) goto finish;
  d = get_desc(c, i + 1);
  wg_wait<1>();
  acc_fence<WG>(a0);
  TRACE_O(0);
  stage_out<WG, 0>(c, a0);
  TRACE_O(1);
  proj_end<WG>(c, a1, h);
  TRACE_O(2);
  stage_out<WG, 1>(c, a1);
  TRACE(i, 2);
  goto next;
finish:
  {
    uint32_t q[32];
#pragma unroll 1
    for (int k = (d >> 5) & 3; k > 1; k--) {
      wg_wait<0>();
      acc_fence<WG>(a0); acc_fence<WG>(a1);
      if (k == ((d >> 5) & 3)) { release(c, h.x); release(c, h.w); }
      load_part<WG, 0>(c, r, q); add_part<WG>(c, q, a0);
      load_part<WG, 1, 0>(c, r, q); add_part<WG>(c, q, a1);
#pragma unroll
      for (int t = 0; t < 4; t++) { release(c, r.slot); r.next(); }
    }
    load_part<WG, 0, WG ? 4 : 1>(c, r, q);
    wg_wait<1>();
    acc_fence<WG>(a0);
    TRACE_O(0);
    add_part<WG>(c, q, a0);
    stage_out<WG, 0>(c, a0);
    TRACE_O(1);
    load_part<WG, 1, WG ? 0 : 2>(c, r, q);
    wg_wait<0>();
    acc_fence<WG>(a1);
    TRACE_O(2);
    add_part<WG>(c, q, a1);
    stage_out<WG, 1>(c, a1);
    TRACE(i, 2); TRACE(i, 3); TRACE(i, 7);
    trace_dump(c);
    return;
  }
redo:
  {
    if (!WG) { stage_rows<RM1>(c, c.sb + QBUF_OFF + 16384, oq); __syncwarp(); }
    const size_t hoff = (size_t)(dc & 511) * (SK * DH);
    const int br = (dc >> 9) & 1;
#pragma unroll 1
    for (int part = 0; part < 2; part++) {
      const int t = WG ? 3 - part : part;
      redo_tile(c, c.sb + QBUF_OFF + t * 16384, t == 3 ? 4096 : 8192, kv[br] + hoff, kv[2 + br] + hoff, dc,
                t * 64 + (t == 3 ? 8 : 16) * c.warp);
    }
    o_done(c);
    release_q<WG>(c);
  }
  goto next;
}

template <bool SIMPLE>
__global__ void __launch_bounds__(384, 1) mha_fused_kernel(const __grid_constant__ Params P) {
  extern __shared__ __align__(1024) uint8_t smem_raw[];
  const uint32_t sbase = smem_u32(smem_raw);
  const int tid = threadIdx.x;
  const int wg = __shfl_sync(0xffffffffu, tid >> 7, 0);
  const int warp = __shfl_sync(0xffffffffu, (tid >> 5) & 3, 0);
  const int lane = tid & 31;
  const int cta = blockIdx.x;
  constexpr bool PAIR = !SIMPLE;

  if (tid == 0) T3(15, 0);
  if ((sbase & 0xffffff) != SB0) __trap();
  {
    const int wi = wg * 4 + warp;
    asm volatile(ELECT "prefetch.tensormap [%0];\n}" ::"l"(&P.x[0][0] + wi) : "memory");
#pragma unroll
    for (int k = 0; k < 5; k++) {
      const int b = min(BAR_OFF + (wi * 5 + k) * 8, DESC_OFF - 8);
      asm volatile(ELECT "mbarrier.init.shared::cta.b64 [%0], %1;\n}"
                   ::"r"(sbase + b), "r"(b < BAR_EMPTY || b >= BAR_DESC ? 1 : b >= BAR_STG && b < BAR_OUT ? 4 : 8) : "memory");
    }
    asm volatile("fence.mbarrier_init.release.cluster;" ::: "memory");
    if (wi < 6) asm volatile(ELECT "prefetch.tensormap [%0];\n}" ::"l"(&P.x[0][0] + 12 + wi) : "memory");
  }
  if (PAIR) asm volatile("barrier.cluster.arrive.aligned;\nbarrier.cluster.wait.aligned;" ::: "memory"); else __syncthreads();

  if (wg == 2) {
    asm volatile("setmaxnreg.dec.sync.aligned.u32 %0;" ::"n"(REG_P));
    if (warp == 1) {
      const uint32_t qb = sbase + QBUF_OFF;
      const uint32_t ep = __shfl_sync(0xffffffffu, *(volatile unsigned*)&g_epoch + 1, 0);
      asm volatile("st.volatile.shared.u32 [%0], %1;" ::"r"(sbase + EPOCH_OFF), "r"(ep) : "memory");
      uint32_t dc = c_sched.queue[cta], qi = 0, piece = 0, na = 0;
      TTAIL(0);
      for (int i = 0; (dc >> 30) != 2; i++) {
        if (!(dc >> 30) && o_reuse<SIMPLE>((dc >> 5) & 31)) {
          const unsigned* rd = &g_rd[0][0] + ((dc & 1023) >> 2) - OR * 8;
          for (uint32_t n = 0; !__all_sync(0xffffffffu, reached(rd, ep * 5)); __nanosleep(300)) if (++n > (1u << 22)) __trap();
        }
        mbar_wait_w(sbase + BAR_GO, i & 1);
        if (piece == 0) {
          if (PAIR && (cta & 1)) {
            asm volatile(ELECT EXPECT("%0", "4") "mbarrier.arrive.shared::cluster.b64 _, [%1];\n}" ::"r"(sbase + BAR_MAIL), "r"(peer(sbase + BAR_MAIL)) : "memory");
            mbar_wait_w(sbase + BAR_MAIL, i & 1);
            qi = lds(sbase + EPOCH_OFF + 8);
          } else if (lane == 0) {
            qi = atomicAdd(&g_next, PAIR ? 2 : 1);
            if (qi == (SIMPLE ? Q_ALL : Q_RANGES) - (PAIR ? 2 : 1)) { g_next = 0; g_epoch = ep; }
          }
          qi = __shfl_sync(0xffffffffu, qi, 0);
          if (PAIR && !(cta & 1)) {
            mbar_wait_w(sbase + BAR_MAIL, i & 1);
            asm volatile(ELECT "st.async.shared::cluster.mbarrier::complete_tx::bytes.u32 [%0], %1, [%2];\n}"
                         ::"r"(peer(sbase + EPOCH_OFF + 8)), "r"(qi + 1), "r"(peer(sbase + BAR_MAIL)) : "memory");
          }
          qi += SIMPLE ? gridDim.x : NCTA;
        }
        uint32_t d;
        if (qi < (SIMPLE ? Q_ALL : Q_RANGES)) { d = c_sched.queue[qi]; if (d & 0x8000) d ^= (1u << 30) | (63u << 16) | 0x8000; else d |= o_slot<SIMPLE>(d >> 5) << 15 | (d & 31) << 10; }
        else if (SIMPLE) d = 2u << 30;
        else { const uint32_t e = qi - Q_RANGES, g = e / 5; d = c_sched.piece[g][piece++] | (g & 1 ? g * 5 + 4 - e : e - g * 5) << 8; }
        if ((d >> 30) == 1) {
          const uint32_t k0 = (d >> 22) & 63;
          const uint32_t run = __ffs(__ballot_sync(0xffffffffu, !reached(&g_cnt[d & 31][lane & 7], ep * 4)) & (0xffu << (k0 >> 3))) - 1;
          if (run <= (k0 + ((d >> 16) & 63)) >> 3) d |= run <= (k0 + O_STEPS) >> 3 ? (2u << 30) | 128 : 128;
        }
        asm volatile("st.volatile.shared.u32 [%0], %1;" ::"r"(sbase + EPOCH_OFF + 4), "r"(qi) : "memory");
        asm volatile("st.volatile.shared.u32 [%0], %1;" ::"r"(sbase + DESC_OFF + ((i + 1) & 3) * 4), "r"(d) : "memory");
        __syncwarp();
        mbar_arrive_warp(sbase + BAR_DESC);
        const Work w = decode(dc);
        dc = d;
        if (w.kind == 0) {
          mbar_wait_w(sbase + BAR_OUT, na++ & 1);
          TTAIL(1);
          T3(i, 0); T3(i, 1);
          asm volatile(ELECT "red.release.gpu.global.add.u32 [%0], 1;\n}" ::"l"(&g_cnt[w.beta][w.sub >> 2]) : "memory");
          T3(i, 2);
          TTAIL(2);
          continue;
        }
        const bool fin = w.mode != 1;
        const CUtensorMap* m = fin ? P.out_st : P.o_st;
        const int c1 = fin ? (w.beta & 15) * SQ : 0;
        const int c2 = fin ? (w.beta >> 4) * (DM / 64) + w.sub * 2 : NBETA * 64 + w.range * 2;
        uint32_t pend = 0;
#pragma unroll 1
        for (int e = 0; e < 4; e++) {
          const int t = (ST_ORDER >> (4 * e)) & 3;
          mbar_wait_w(sbase + BAR_STG + (t ^ (t >> 1)) * 8, (i - na) & 1);
          tma_st3_w(m + (t == 3), qb + t * 16384, c1 + t * 64, c2);
          bulk_commit();
          T2P(i + 1, 5, 2 * e);
          if (e == 3 && w.mode == 1 && (d >> 30) == 2) {
            asm volatile("cp.async.bulk.wait_group 2;" ::: "memory");
            asm volatile(ELECT "st.release.gpu.global.u32 [%0], %1;\n}" ::"l"(&g_flag[w.range]), "r"(2 * ep - 1) : "memory");
          }
          if (pend && (d >> 30) != 2) {
            bulk_wait_read<1>();
            mbar_arrive8_w(pend);
            T2P(i + 1, 5, 2 * e - 1);
          }
          pend = sbase + BAR_EMPTY + (NS + t) * 8;
          if ((ST_NOW >> e) & 1) {
            bulk_wait_read<0>();
            mbar_arrive8_w(pend);
            pend = 0;
            T2P(i + 1, 5, 2 * e + 1);
          }
        }
        if (w.beta < N_EARLY) asm volatile(ELECT "red.relaxed.gpu.global.add.u32 [%0], 1;\n}" ::"l"(&g_rd[w.beta][7]) : "memory");
        T3(i, 0);
        if (piece >= 2) TTAIL(piece * 2 - 1);
        asm volatile("cp.async.bulk.wait_group 0;" ::: "memory");
        T3(i, 1);
        if (w.mode == 1) asm volatile(ELECT "st.release.gpu.global.u32 [%0], %1;\n}" ::"l"(&g_flag[w.range]), "r"(2 * ep) : "memory");
        T3(i, 2);
        if (piece >= 2) TTAIL(piece * 2);
      }
      T3(15, 1);
    } else
    if (warp == 0) {
      Ring r{0, 1, 3};
      uint32_t d = c_sched.queue[cta];
      for (int i = 0;; i++) {
        const Work w = decode(d);
        if (w.kind == 2) break;
        const CUtensorMap* m = w.kind == 0 ? &P.wq[w.beta >> 4] : &P.wo[w.beta >> 4];
        for (int ks = 0; ks < w.nsteps; ks++) {
          const uint32_t b = borrow(ks, w.nsteps);
          r.next_if(b == 2);
          const uint32_t bar = sbase + BAR_FULL + r.slot * 8;
          mbar_wait_w(bar + (BAR_EMPTY - BAR_FULL), r.phase);
          if (w.kind == 0) tma_ld3_w(sbase + r.slot * SLOT, m, 0, ks * 64, w.sub * 2, bar, 16384);
          else tma_ld_wo_w(sbase + r.slot * SLOT, m, w.sub * 128, (w.k0 + ks) * 2, bar);
          if (w.kind != 0 && w.beta < N_EARLY && (ks & 7) == 5 && ks > 5)
            asm volatile(ELECT "red.relaxed.gpu.global.add.u32 [%0], 1;\n}" ::"l"(&g_rd[w.beta][(ks >> 3) - 1]) : "memory");
          if (ks < 10) T2P(i, 2, ks);
          if (w.kind != 0 && ks == max(w.nsteps - GO_P, 4)) mbar_arrive_warp(sbase + BAR_GO);
          r.next(); r.next_if(b == 2);
        }
        if (w.kind == 0) {
          r.phase ^= 1; r.next(); r.next();
        } else if (w.mode == 2) {
          for (int k = 1; k <= ((d >> 5) & 3); k++) {
            if (k == 1) TTAIL(9);
            bool all = false;
#pragma unroll 1
            for (int t = 0; t < 4; t++) {
              if (!(t & 1) && !all) {
                const uint32_t ep2 = 2 * lds(sbase + EPOCH_OFF);
                uint32_t v, n = 0;
                do {
                  asm volatile("ld.acquire.gpu.global.u32 %0, [%1];" : "=r"(v) : "l"(&g_flag[w.range + 5 * k]) : "memory");
                  v = __shfl_sync(0xffffffffu, v - ep2, 0);
                  if (++n > (1u << 24)) __trap();
                } while ((int)v < (t >> 1) - 1);
                all = v == 0;
                TTAIL(10);
                asm volatile("fence.proxy.async.global;" ::: "memory");
              }
              mbar_wait_w(sbase + BAR_EMPTY + r.slot * 8, r.phase);
              tma_ld3_w(sbase + r.slot * SLOT, &P.o_st[t == 3], 0, t * 64, NBETA * 64 + (w.range + 5 * k) * 2, sbase + BAR_FULL + r.slot * 8,
                        t == 3 ? 8192 : 16384);
              r.next();
            }
          }
        }
        mbar_wait_w(sbase + BAR_DESC, i & 1);
        d = __shfl_sync(0xffffffffu, lds(sbase + DESC_OFF + ((i + 1) & 3) * 4), 0);
      }
    } else {
      const int hi = warp - 2;
      uint64_t pol_stream;
      uint32_t rdy = 0;
      asm volatile("createpolicy.fractional.L2::evict_first.b64 %0, 1.0;" : "=l"(pol_stream));
      Ring r{0, 1, 3};
      uint32_t d = c_sched.queue[cta];
      for (int i = 0;; i++) {
        const Work w = decode(d);
        if (w.kind == 2) break;
        const CUtensorMap* m = w.kind == 0 ? &P.x[hi][w.beta >> 4] : &P.o_ld[hi];
        int c1 = (w.kind == 0 ? (w.beta & 15) : o_slot<SIMPLE>(w.beta) * 64 + w.k0) * SQ + hi * 128;
        int k_wait = -1;
        const bool both = PAIR && (w.kind == 0 || w.sub != 4), mine = !both || hi == (cta & 1);
        if (w.kind != 0 && mine) {
          if (d & 128) k_wait = d >= (3u << 30) ? 0 : 8 - (w.k0 & 7);
          asm volatile("fence.proxy.async.global;" ::: "memory");
        }
        const int rank = i == 0 ? cta : __shfl_sync(0xffffffffu, lds(sbase + EPOCH_OFF + 4), 0) - NCTA;
        for (int ks = 0; ks < w.nsteps; ks++) {
          if (ks == k_wait) {
            wait_count(&g_cnt[d & 31][(w.k0 + ks) >> 3], lds(sbase + EPOCH_OFF) * 4);
            asm volatile("fence.proxy.async.global;" ::: "memory");
            k_wait = ((w.k0 + ks) | 7) + 1 - w.k0;
          }
          const uint32_t b = borrow(ks, w.nsteps);
          const bool bo = b != 2;
          r.next_if(hi && !bo); r.next_if(hi && !bo);
          const uint32_t sl = bo ? NS + (b ^ (3 * hi)) : r.slot, bar = sbase + BAR_FULL + sl * 8;
          mbar_wait_w(bar + (BAR_EMPTY - BAR_FULL), bo ? (r.xp >> b) & 1 : r.phase);
          const uint32_t bytes = hi ? 96 * 128 : 128 * 128;
          if (!mine) {
            asm volatile(ELECT EXPECT("%0", "%2") "mbarrier.arrive.shared::cluster.b64 _, [%1];\n}"
                         ::"r"(bar), "r"(peer(bar + (BAR_RDY - BAR_FULL))), "r"(bytes) : "memory");
          } else if (both) {
            mbar_wait_w(bar + (BAR_RDY - BAR_FULL), (rdy >> sl) & 1);
            rdy ^= 1 << sl;
            if (w.kind == 0) tma_ld2_both_w(sbase + sl * SLOT, m, ks * 64, c1, bar, bytes);
            else tma_ld2_both_hint_w(sbase + sl * SLOT, m, 0, c1, bar, bytes, pol_stream);
          } else if (!PAIR && w.kind == 0) tma_ld2_w(sbase + sl * SLOT, m, ks * 64, c1, bar, bytes);
          else tma_ld2_hint_w(sbase + sl * SLOT, m, 0, c1, bar, bytes, pol_stream);
          if (w.kind != 0) c1 += SQ;
          if (i == 0 && ks == PF_STEP)
            asm volatile(ELECT "cp.async.bulk.prefetch.tensor.4d.L2.global.L2::cache_hint [%0, {0, 0, 0, %1}], %2;\n}"
                         ::"l"(&P.kv[hi][0]), "r"(d * (SK / 8)), "l"(pol_stream) : "memory");
          if (ks < 10) T2P(i, 3 + hi, ks);
          if (!hi && w.kind != 0 && !(ks & 3)) TCLK(i * 16 + (ks >> 2));
          r.next(); r.next_if(!hi && !bo); r.next_if(!hi && !bo);
          r.xp ^= 1 << b;
        }
        r.xp ^= 3;
        if (w.kind == 0) {
          m = &P.kv[hi][w.beta >> 4];
          c1 = (d & 511) * (SK / 8);
          for (int j = 0; j < 16; j++) {
            if (hi) r.next();
            const uint32_t bar = sbase + BAR_FULL + r.slot * 8;
            const bool tight = i < KV_WIN_UNITS && j < KV_WIN_TILES + ((KV_WIN_RAMP * rank) >> 5);
            {
              const int s2 = (int)r.slot - (tight ? 2 : KV_WIN_D);
              mbar_wait_w(sbase + BAR_FULL + (s2 < 0 ? s2 + NS : s2) * 8, s2 < 0 ? r.phase : r.phase ^ 1);
            }
            if (j == 15 && hi) mbar_wait_w(sbase + BAR_DESC, i & 1);
            mbar_wait_w(sbase + BAR_EMPTY + r.slot * 8, r.phase);
            tma_ld_kv_w(sbase + r.slot * SLOT, m, c1, bar, pol_stream);
            T2P(i, 3 + hi, 16 + j);
            if (!hi) TCLK(i * 16 + j);
            if (j == GO_J && !hi) mbar_arrive_warp(sbase + BAR_GO);
            c1 += 8;
            r.next();
            if (!hi) r.next();
          }
        }
        mbar_wait_w(sbase + BAR_DESC, i & 1);
        d = __shfl_sync(0xffffffffu, lds(sbase + DESC_OFF + ((i + 1) & 3) * 4), 0);
      }
    }
  } else {
    Ctx c;
    c.sb = sbase; c.wg = wg; c.warp = warp; c.src = 0; c.mqk = 0; c.mpv = 0; c.lead = lane == 0; c.lane0 = c.lane = lane;
    if (wg == 0) consumer<0>(c, P.kp); else consumer<1>(c, P.kp);
  }
}

typedef CUresult (*EncodeFn)(CUtensorMap*, CUtensorMapDataType, cuuint32_t, void*, const cuuint64_t*, const cuuint64_t*,
                             const cuuint32_t*, const cuuint32_t*, CUtensorMapInterleave, CUtensorMapSwizzle,
                             CUtensorMapL2promotion, CUtensorMapFloatOOBfill);

void make_map(EncodeFn enc, CUtensorMap* m, const void* ptr, int rank, const cuuint64_t* dims, const cuuint64_t* strides,
              const cuuint32_t* box, CUtensorMapSwizzle swz = CU_TENSOR_MAP_SWIZZLE_128B) {
  cuuint32_t es[5] = {1, 1, 1, 1, 1};
  enc(m, CU_TENSOR_MAP_DATA_TYPE_BFLOAT16, rank, const_cast<void*>(ptr), dims, strides, box, es,
      CU_TENSOR_MAP_INTERLEAVE_NONE, swz, CU_TENSOR_MAP_L2_PROMOTION_NONE,
      CU_TENSOR_MAP_FLOAT_OOB_FILL_NONE);
}

}

extern "C" void kernel_launch(void* const* d_in, const int* in_sizes, int n_in, void* d_out, int out_size) {
  (void)in_sizes; (void)n_in; (void)out_size;
  static EncodeFn enc = nullptr;
  static void* o_ptr = nullptr;
  static int n_sm = 0;
  cudaLaunchAttribute at;
  at.id = cudaLaunchAttributeClusterDimension;
  at.val.clusterDim.x = 2; at.val.clusterDim.y = 1; at.val.clusterDim.z = 1;
  cudaLaunchConfig_t cfg = {};
  cfg.gridDim = dim3(NCTA); cfg.blockDim = dim3(384); cfg.dynamicSmemBytes = SMEM_BYTES; cfg.attrs = &at; cfg.numAttrs = 1;
  if (!enc) {
    void* fn = nullptr;
    cudaDriverEntryPointQueryResult qr;
    cudaGetDriverEntryPoint("cuTensorMapEncodeTiled", &fn, cudaEnableDefault, &qr);
    enc = (EncodeFn)fn;
    cudaGetSymbolAddress(&o_ptr, g_o);
    cudaFuncSetAttribute(mha_fused_kernel<false>, cudaFuncAttributeMaxDynamicSharedMemorySize, SMEM_BYTES);
    cudaFuncSetAttribute(mha_fused_kernel<true>, cudaFuncAttributeMaxDynamicSharedMemorySize, SMEM_BYTES);
    int dev = 0;
    cudaGetDevice(&dev);
    cudaDeviceGetAttribute(&n_sm, cudaDevAttrMultiProcessorCount, dev);
    int n_cl = 0;
    cudaOccupancyMaxActiveClusters(&n_cl, mha_fused_kernel<false>, &cfg);
    if (n_cl * 2 < NCTA && n_sm >= NCTA) n_sm = NCTA - 1;
  }
  Params P;
  for (int br = 0; br < 2; br++) {
    const void* x = d_in[br * 5 + 0]; const void* kc = d_in[br * 5 + 1]; const void* vc = d_in[br * 5 + 2];
    const void* wq = d_in[br * 5 + 3]; const void* wo = d_in[br * 5 + 4];
    { cuuint64_t d[2] = {DM, (cuuint64_t)NB * SQ}, s[1] = {DM * 2}; cuuint32_t b[2] = {64, 128}, b2[2] = {64, 96};
      make_map(enc, &P.x[0][br], x, 2, d, s, b); make_map(enc, &P.x[1][br], x, 2, d, s, b2); }
    { cuuint64_t d[3] = {64, DM, HD / 64}, s[2] = {HD * 2, 128}; cuuint32_t b[3] = {64, 64, 2}; make_map(enc, &P.wq[br], wq, 3, d, s, b); }
    { cuuint64_t d[5] = {DM, 2, 4, 4, HD / 32}, s[4] = {DM * 2, 8 * DM * 2, 2 * DM * 2, 32 * DM * 2}; cuuint32_t b[5] = {64, 2, 4, 4, 2};
      make_map(enc, &P.wo[br], wo, 5, d, s, b); }
    { cuuint64_t d[4] = {64, 8, 2, (cuuint64_t)NB * NH * SK / 8}, s[3] = {DH * 2, 128, DH * 16}; cuuint32_t b[4] = {64, 8, 2, 8};
      make_map(enc, &P.kv[0][br], kc, 4, d, s, b); make_map(enc, &P.kv[1][br], vc, 4, d, s, b); }
    P.kp[br] = (const __nv_bfloat16*)kc; P.vp[br] = (const __nv_bfloat16*)vc;

  }
  { cuuint64_t d[2] = {64, (cuuint64_t)NBETA * 64 * SQ}, s[1] = {128}; cuuint32_t b[2] = {64, 128}, b2[2] = {64, 96};
    make_map(enc, &P.o_ld[0], o_ptr, 2, d, s, b, CU_TENSOR_MAP_SWIZZLE_NONE); make_map(enc, &P.o_ld[1], o_ptr, 2, d, s, b2, CU_TENSOR_MAP_SWIZZLE_NONE); }
  { cuuint64_t d[3] = {64, SQ, O_BLOCKS}, s[2] = {128, SQ * 128}; cuuint32_t b[3] = {64, 64, 2}, b2[3] = {64, 32, 2};
    make_map(enc, &P.o_st[0], o_ptr, 3, d, s, b); make_map(enc, &P.o_st[1], o_ptr, 3, d, s, b2); }
  { cuuint64_t d[3] = {64, (cuuint64_t)NB * SQ, 2 * DM / 64}, s[2] = {2 * DM * 2, 128}; cuuint32_t b[3] = {64, 64, 2}, b2[3] = {64, 32, 2};
    make_map(enc, &P.out_st[0], d_out, 3, d, s, b); make_map(enc, &P.out_st[1], d_out, 3, d, s, b2); }
  if (n_sm >= NCTA) cudaLaunchKernelEx(&cfg, mha_fused_kernel<false>, P);
  else mha_fused_kernel<true><<<n_sm, 384, SMEM_BYTES>>>(P);
}
```

```cpp
#include <cuda_runtime.h>
#include <cuda_bf16.h>
#include <cuda.h>
#include <stdint.h>
#include <stdlib.h>

namespace {

__device__ __forceinline__ void wgmma_proj(float (&d)[64], uint64_t da, uint64_t db, int scaleD) {
  asm volatile("{\n.reg .pred p;\nsetp.ne.b32 p, %66, 0;\n"
      "wgmma.mma_async.sync.aligned.m64n128k16.f32.bf16.bf16 "
      "{%0, %1, %2, %3, %4, %5, %6, %7, %8, %9, %10, %11, %12, %13, %14, %15, %16, %17, %18, %19, %20, %21, %22, %23, %24, %25, %26, %27, %28, %29, %30, "
      "%31, %32, %33, %34, %35, %36, %37, %38, %39, %40, %41, %42, %43, %44, %45, %46, %47, %48, %49, %50, %51, %52, %53, %54, %55, %56, %57, %58, %59, %60, "
      "%61, %62, %63}, "
      "%64, %65, p, 1, 1, 0, 1;\n}\n"
      : "+f"(d[0]), "+f"(d[1]), "+f"(d[2]), "+f"(d[3]), "+f"(d[4]), "+f"(d[5]), "+f"(d[6]), "+f"(d[7]), "+f"(d[8]), "+f"(d[9]), "+f"(d[10]), "+f"(d[11]),
        "+f"(d[12]), "+f"(d[13]), "+f"(d[14]), "+f"(d[15]), "+f"(d[16]), "+f"(d[17]), "+f"(d[18]), "+f"(d[19]), "+f"(d[20]), "+f"(d[21]), "+f"(d[22]),
        "+f"(d[23]), "+f"(d[24]), "+f"(d[25]), "+f"(d[26]), "+f"(d[27]), "+f"(d[28]), "+f"(d[29]), "+f"(d[30]), "+f"(d[31]), "+f"(d[32]), "+f"(d[33]),
        "+f"(d[34]), "+f"(d[35]), "+f"(d[36]), "+f"(d[37]), "+f"(d[38]), "+f"(d[39]), "+f"(d[40]), "+f"(d[41]), "+f"(d[42]), "+f"(d[43]), "+f"(d[44]),
        "+f"(d[45]), "+f"(d[46]), "+f"(d[47]), "+f"(d[48]), "+f"(d[49]), "+f"(d[50]), "+f"(d[51]), "+f"(d[52]), "+f"(d[53]), "+f"(d[54]), "+f"(d[55]),
        "+f"(d[56]), "+f"(d[57]), "+f"(d[58]), "+f"(d[59]), "+f"(d[60]), "+f"(d[61]), "+f"(d[62]), "+f"(d[63])
      : "l"(da), "l"(db), "r"(scaleD));
}
__device__ __forceinline__ void wgmma_proj96(float (&d)[64], uint64_t da, uint64_t db, int scaleD) {
  asm volatile("{\n.reg .pred p;\nsetp.ne.b32 p, %50, 0;\n"
      "wgmma.mma_async.sync.aligned.m64n96k16.f32.bf16.bf16 "
      "{%0, %1, %2, %3, %4, %5, %6, %7, %8, %9, %10, %11, %12, %13, %14, %15, %16, %17, %18, %19, %20, %21, %22, %23, %24, %25, %26, %27, %28, %29, %30, "
      "%31, %32, %33, %34, %35, %36, %37, %38, %39, %40, %41, %42, %43, %44, %45, %46, %47}, "
      "%48, %49, p, 1, 1, 1, 0;\n}\n"
      : "+f"(d[0]), "+f"(d[1]), "+f"(d[2]), "+f"(d[3]), "+f"(d[4]), "+f"(d[5]), "+f"(d[6]), "+f"(d[7]), "+f"(d[8]), "+f"(d[9]), "+f"(d[10]), "+f"(d[11]),
        "+f"(d[12]), "+f"(d[13]), "+f"(d[14]), "+f"(d[15]), "+f"(d[16]), "+f"(d[17]), "+f"(d[18]), "+f"(d[19]), "+f"(d[20]), "+f"(d[21]), "+f"(d[22]),
        "+f"(d[23]), "+f"(d[24]), "+f"(d[25]), "+f"(d[26]), "+f"(d[27]), "+f"(d[28]), "+f"(d[29]), "+f"(d[30]), "+f"(d[31]), "+f"(d[32]), "+f"(d[33]),
        "+f"(d[34]), "+f"(d[35]), "+f"(d[36]), "+f"(d[37]), "+f"(d[38]), "+f"(d[39]), "+f"(d[40]), "+f"(d[41]), "+f"(d[42]), "+f"(d[43]), "+f"(d[44]),
        "+f"(d[45]), "+f"(d[46]), "+f"(d[47])
      : "l"(da), "l"(db), "r"(scaleD));
}
__device__ __forceinline__ void wgmma_qk(float (&d)[32], uint64_t da, uint64_t db, int scaleD) {
  asm volatile("{\n.reg .pred p;\nsetp.ne.b32 p, %34, 0;\n"
      "wgmma.mma_async.sync.aligned.m64n64k16.f32.bf16.bf16 "
      "{%0, %1, %2, %3, %4, %5, %6, %7, %8, %9, %10, %11, %12, %13, %14, %15, %16, %17, %18, %19, %20, %21, %22, %23, %24, %25, %26, %27, %28, %29, %30, "
      "%31}, "
      "%32, %33, p, 1, 1, 0, 0;\n}\n"
      : "+f"(d[0]), "+f"(d[1]), "+f"(d[2]), "+f"(d[3]), "+f"(d[4]), "+f"(d[5]), "+f"(d[6]), "+f"(d[7]), "+f"(d[8]), "+f"(d[9]), "+f"(d[10]), "+f"(d[11]),
        "+f"(d[12]), "+f"(d[13]), "+f"(d[14]), "+f"(d[15]), "+f"(d[16]), "+f"(d[17]), "+f"(d[18]), "+f"(d[19]), "+f"(d[20]), "+f"(d[21]), "+f"(d[22]),
        "+f"(d[23]), "+f"(d[24]), "+f"(d[25]), "+f"(d[26]), "+f"(d[27]), "+f"(d[28]), "+f"(d[29]), "+f"(d[30]), "+f"(d[31])
      : "l"(da), "l"(db), "r"(scaleD));
}
__device__ __forceinline__ void wgmma_qk_rs(float (&d)[32], uint32_t a0, uint32_t a1, uint32_t a2, uint32_t a3, uint64_t db, int scaleD) {
  asm volatile("{\n.reg .pred p;\nsetp.ne.b32 p, %37, 0;\n"
      "wgmma.mma_async.sync.aligned.m64n64k16.f32.bf16.bf16 "
      "{%0, %1, %2, %3, %4, %5, %6, %7, %8, %9, %10, %11, %12, %13, %14, %15, %16, %17, %18, %19, %20, %21, %22, %23, %24, %25, %26, %27, %28, %29, %30, "
      "%31}, "
      "{%32, %33, %34, %35}, %36, p, 1, 1, 0;\n}\n"
      : "+f"(d[0]), "+f"(d[1]), "+f"(d[2]), "+f"(d[3]), "+f"(d[4]), "+f"(d[5]), "+f"(d[6]), "+f"(d[7]), "+f"(d[8]), "+f"(d[9]), "+f"(d[10]), "+f"(d[11]),
        "+f"(d[12]), "+f"(d[13]), "+f"(d[14]), "+f"(d[15]), "+f"(d[16]), "+f"(d[17]), "+f"(d[18]), "+f"(d[19]), "+f"(d[20]), "+f"(d[21]), "+f"(d[22]),
        "+f"(d[23]), "+f"(d[24]), "+f"(d[25]), "+f"(d[26]), "+f"(d[27]), "+f"(d[28]), "+f"(d[29]), "+f"(d[30]), "+f"(d[31])
      : "r"(a0), "r"(a1), "r"(a2), "r"(a3), "l"(db), "r"(scaleD));
}
__device__ __forceinline__ void wgmma_pv(float (&d)[64], uint32_t a0, uint32_t a1, uint32_t a2, uint32_t a3, uint64_t db, int scaleD) {
  asm volatile("{\n.reg .pred p;\nsetp.ne.b32 p, %69, 0;\n"
      "wgmma.mma_async.sync.aligned.m64n128k16.f32.bf16.bf16 "
      "{%0, %1, %2, %3, %4, %5, %6, %7, %8, %9, %10, %11, %12, %13, %14, %15, %16, %17, %18, %19, %20, %21, %22, %23, %24, %25, %26, %27, %28, %29, %30, "
      "%31, %32, %33, %34, %35, %36, %37, %38, %39, %40, %41, %42, %43, %44, %45, %46, %47, %48, %49, %50, %51, %52, %53, %54, %55, %56, %57, %58, %59, %60, "
      "%61, %62, %63}, "
      "{%64, %65, %66, %67}, %68, p, 1, 1, 1;\n}\n"
      : "+f"(d[0]), "+f"(d[1]), "+f"(d[2]), "+f"(d[3]), "+f"(d[4]), "+f"(d[5]), "+f"(d[6]), "+f"(d[7]), "+f"(d[8]), "+f"(d[9]), "+f"(d[10]), "+f"(d[11]),
        "+f"(d[12]), "+f"(d[13]), "+f"(d[14]), "+f"(d[15]), "+f"(d[16]), "+f"(d[17]), "+f"(d[18]), "+f"(d[19]), "+f"(d[20]), "+f"(d[21]), "+f"(d[22]),
        "+f"(d[23]), "+f"(d[24]), "+f"(d[25]), "+f"(d[26]), "+f"(d[27]), "+f"(d[28]), "+f"(d[29]), "+f"(d[30]), "+f"(d[31]), "+f"(d[32]), "+f"(d[33]),
        "+f"(d[34]), "+f"(d[35]), "+f"(d[36]), "+f"(d[37]), "+f"(d[38]), "+f"(d[39]), "+f"(d[40]), "+f"(d[41]), "+f"(d[42]), "+f"(d[43]), "+f"(d[44]),
        "+f"(d[45]), "+f"(d[46]), "+f"(d[47]), "+f"(d[48]), "+f"(d[49]), "+f"(d[50]), "+f"(d[51]), "+f"(d[52]), "+f"(d[53]), "+f"(d[54]), "+f"(d[55]),
        "+f"(d[56]), "+f"(d[57]), "+f"(d[58]), "+f"(d[59]), "+f"(d[60]), "+f"(d[61]), "+f"(d[62]), "+f"(d[63])
      : "r"(a0), "r"(a1), "r"(a2), "r"(a3), "l"(db), "r"(scaleD));
}
__device__ __forceinline__ void wgmma_qk_sp(float (&d)[32], uint32_t a0, uint32_t a1, uint32_t a2, uint32_t a3, uint64_t db, int scaleD, uint32_t meta) {
  asm volatile("{\n.reg .pred p;\nsetp.ne.b32 p, %37, 0;\n"
      "wgmma.mma_async.sp.sync.aligned.m64n64k32.f32.bf16.bf16 "
      "{%0, %1, %2, %3, %4, %5, %6, %7, %8, %9, %10, %11, %12, %13, %14, %15, %16, %17, %18, %19, %20, %21, %22, %23, %24, %25, %26, %27, %28, %29, %30, "
      "%31}, "
      "{%32, %33, %34, %35}, %36, %38, 0, p, 1, 1, 0;\n}\n"
      : "+f"(d[0]), "+f"(d[1]), "+f"(d[2]), "+f"(d[3]), "+f"(d[4]), "+f"(d[5]), "+f"(d[6]), "+f"(d[7]), "+f"(d[8]), "+f"(d[9]), "+f"(d[10]), "+f"(d[11]),
        "+f"(d[12]), "+f"(d[13]), "+f"(d[14]), "+f"(d[15]), "+f"(d[16]), "+f"(d[17]), "+f"(d[18]), "+f"(d[19]), "+f"(d[20]), "+f"(d[21]), "+f"(d[22]),
        "+f"(d[23]), "+f"(d[24]), "+f"(d[25]), "+f"(d[26]), "+f"(d[27]), "+f"(d[28]), "+f"(d[29]), "+f"(d[30]), "+f"(d[31])
      : "r"(a0), "r"(a1), "r"(a2), "r"(a3), "l"(db), "r"(scaleD), "r"(meta));
}
__device__ __forceinline__ void wgmma_pv_sp(float (&d)[64], uint32_t a0, uint32_t a1, uint32_t a2, uint32_t a3, uint64_t db, int scaleD, uint32_t meta) {
  asm volatile("{\n.reg .pred p;\nsetp.ne.b32 p, %69, 0;\n"
      "wgmma.mma_async.sp.sync.aligned.m64n128k32.f32.bf16.bf16 "
      "{%0, %1, %2, %3, %4, %5, %6, %7, %8, %9, %10, %11, %12, %13, %14, %15, %16, %17, %18, %19, %20, %21, %22, %23, %24, %25, %26, %27, %28, %29, %30, "
      "%31, %32, %33, %34, %35, %36, %37, %38, %39, %40, %41, %42, %43, %44, %45, %46, %47, %48, %49, %50, %51, %52, %53, %54, %55, %56, %57, %58, %59, %60, "
      "%61, %62, %63}, "
      "{%64, %65, %66, %67}, %68, %70, 0, p, 1, 1, 1;\n}\n"
      : "+f"(d[0]), "+f"(d[1]), "+f"(d[2]), "+f"(d[3]), "+f"(d[4]), "+f"(d[5]), "+f"(d[6]), "+f"(d[7]), "+f"(d[8]), "+f"(d[9]), "+f"(d[10]), "+f"(d[11]),
        "+f"(d[12]), "+f"(d[13]), "+f"(d[14]), "+f"(d[15]), "+f"(d[16]), "+f"(d[17]), "+f"(d[18]), "+f"(d[19]), "+f"(d[20]), "+f"(d[21]), "+f"(d[22]),
        "+f"(d[23]), "+f"(d[24]), "+f"(d[25]), "+f"(d[26]), "+f"(d[27]), "+f"(d[28]), "+f"(d[29]), "+f"(d[30]), "+f"(d[31]), "+f"(d[32]), "+f"(d[33]),
        "+f"(d[34]), "+f"(d[35]), "+f"(d[36]), "+f"(d[37]), "+f"(d[38]), "+f"(d[39]), "+f"(d[40]), "+f"(d[41]), "+f"(d[42]), "+f"(d[43]), "+f"(d[44]),
        "+f"(d[45]), "+f"(d[46]), "+f"(d[47]), "+f"(d[48]), "+f"(d[49]), "+f"(d[50]), "+f"(d[51]), "+f"(d[52]), "+f"(d[53]), "+f"(d[54]), "+f"(d[55]),
        "+f"(d[56]), "+f"(d[57]), "+f"(d[58]), "+f"(d[59]), "+f"(d[60]), "+f"(d[61]), "+f"(d[62]), "+f"(d[63])
      : "r"(a0), "r"(a1), "r"(a2), "r"(a3), "l"(db), "r"(scaleD), "r"(meta));
}
__device__ __forceinline__ void wgmma_proj_init(float (&d)[64], uint64_t da, uint64_t db, int scaleD) {
  asm volatile("{\n.reg .pred p;\nsetp.ne.b32 p, %66, 0;\n"
      "wgmma.mma_async.sync.aligned.m64n128k16.f32.bf16.bf16 "
      "{%0, %1, %2, %3, %4, %5, %6, %7, %8, %9, %10, %11, %12, %13, %14, %15, %16, %17, %18, %19, %20, %21, %22, %23, %24, %25, %26, %27, %28, %29, %30, "
      "%31, %32, %33, %34, %35, %36, %37, %38, %39, %40, %41, %42, %43, %44, %45, %46, %47, %48, %49, %50, %51, %52, %53, %54, %55, %56, %57, %58, %59, %60, "
      "%61, %62, %63}, "
      "%64, %65, p, 1, 1, 0, 1;\n}\n"
      : "=f"(d[0]), "=f"(d[1]), "=f"(d[2]), "=f"(d[3]), "=f"(d[4]), "=f"(d[5]), "=f"(d[6]), "=f"(d[7]), "=f"(d[8]), "=f"(d[9]), "=f"(d[10]), "=f"(d[11]),
        "=f"(d[12]), "=f"(d[13]), "=f"(d[14]), "=f"(d[15]), "=f"(d[16]), "=f"(d[17]), "=f"(d[18]), "=f"(d[19]), "=f"(d[20]), "=f"(d[21]), "=f"(d[22]),
        "=f"(d[23]), "=f"(d[24]), "=f"(d[25]), "=f"(d[26]), "=f"(d[27]), "=f"(d[28]), "=f"(d[29]), "=f"(d[30]), "=f"(d[31]), "=f"(d[32]), "=f"(d[33]),
        "=f"(d[34]), "=f"(d[35]), "=f"(d[36]), "=f"(d[37]), "=f"(d[38]), "=f"(d[39]), "=f"(d[40]), "=f"(d[41]), "=f"(d[42]), "=f"(d[43]), "=f"(d[44]),
        "=f"(d[45]), "=f"(d[46]), "=f"(d[47]), "=f"(d[48]), "=f"(d[49]), "=f"(d[50]), "=f"(d[51]), "=f"(d[52]), "=f"(d[53]), "=f"(d[54]), "=f"(d[55]),
        "=f"(d[56]), "=f"(d[57]), "=f"(d[58]), "=f"(d[59]), "=f"(d[60]), "=f"(d[61]), "=f"(d[62]), "=f"(d[63])
      : "l"(da), "l"(db), "r"(scaleD));
}
__device__ __forceinline__ void wgmma_proj96_init(float (&d)[64], uint64_t da, uint64_t db, int scaleD) {
  asm volatile("{\n.reg .pred p;\nsetp.ne.b32 p, %50, 0;\n"
      "wgmma.mma_async.sync.aligned.m64n96k16.f32.bf16.bf16 "
      "{%0, %1, %2, %3, %4, %5, %6, %7, %8, %9, %10, %11, %12, %13, %14, %15, %16, %17, %18, %19, %20, %21, %22, %23, %24, %25, %26, %27, %28, %29, %30, "
      "%31, %32, %33, %34, %35, %36, %37, %38, %39, %40, %41, %42, %43, %44, %45, %46, %47}, "
      "%48, %49, p, 1, 1, 1, 0;\n}\n"
      : "=f"(d[0]), "=f"(d[1]), "=f"(d[2]), "=f"(d[3]), "=f"(d[4]), "=f"(d[5]), "=f"(d[6]), "=f"(d[7]), "=f"(d[8]), "=f"(d[9]), "=f"(d[10]), "=f"(d[11]),
        "=f"(d[12]), "=f"(d[13]), "=f"(d[14]), "=f"(d[15]), "=f"(d[16]), "=f"(d[17]), "=f"(d[18]), "=f"(d[19]), "=f"(d[20]), "=f"(d[21]), "=f"(d[22]),
        "=f"(d[23]), "=f"(d[24]), "=f"(d[25]), "=f"(d[26]), "=f"(d[27]), "=f"(d[28]), "=f"(d[29]), "=f"(d[30]), "=f"(d[31]), "=f"(d[32]), "=f"(d[33]),
        "=f"(d[34]), "=f"(d[35]), "=f"(d[36]), "=f"(d[37]), "=f"(d[38]), "=f"(d[39]), "=f"(d[40]), "=f"(d[41]), "=f"(d[42]), "=f"(d[43]), "=f"(d[44]),
        "=f"(d[45]), "=f"(d[46]), "=f"(d[47])
      : "l"(da), "l"(db), "r"(scaleD));
}
__device__ __forceinline__ void wgmma_qk_init(float (&d)[32], uint64_t da, uint64_t db, int scaleD) {
  asm volatile("{\n.reg .pred p;\nsetp.ne.b32 p, %34, 0;\n"
      "wgmma.mma_async.sync.aligned.m64n64k16.f32.bf16.bf16 "
      "{%0, %1, %2, %3, %4, %5, %6, %7, %8, %9, %10, %11, %12, %13, %14, %15, %16, %17, %18, %19, %20, %21, %22, %23, %24, %25, %26, %27, %28, %29, %30, "
      "%31}, "
      "%32, %33, p, 1, 1, 0, 0;\n}\n"
      : "=f"(d[0]), "=f"(d[1]), "=f"(d[2]), "=f"(d[3]), "=f"(d[4]), "=f"(d[5]), "=f"(d[6]), "=f"(d[7]), "=f"(d[8]), "=f"(d[9]), "=f"(d[10]), "=f"(d[11]),
        "=f"(d[12]), "=f"(d[13]), "=f"(d[14]), "=f"(d[15]), "=f"(d[16]), "=f"(d[17]), "=f"(d[18]), "=f"(d[19]), "=f"(d[20]), "=f"(d[21]), "=f"(d[22]),
        "=f"(d[23]), "=f"(d[24]), "=f"(d[25]), "=f"(d[26]), "=f"(d[27]), "=f"(d[28]), "=f"(d[29]), "=f"(d[30]), "=f"(d[31])
      : "l"(da), "l"(db), "r"(scaleD));
}
__device__ __forceinline__ void wgmma_qk_rs_init(float (&d)[32], uint32_t a0, uint32_t a1, uint32_t a2, uint32_t a3, uint64_t db, int scaleD) {
  asm volatile("{\n.reg .pred p;\nsetp.ne.b32 p, %37, 0;\n"
      "wgmma.mma_async.sync.aligned.m64n64k16.f32.bf16.bf16 "
      "{%0, %1, %2, %3, %4, %5, %6, %7, %8, %9, %10, %11, %12, %13, %14, %15, %16, %17, %18, %19, %20, %21, %22, %23, %24, %25, %26, %27, %28, %29, %30, "
      "%31}, "
      "{%32, %33, %34, %35}, %36, p, 1, 1, 0;\n}\n"
      : "=f"(d[0]), "=f"(d[1]), "=f"(d[2]), "=f"(d[3]), "=f"(d[4]), "=f"(d[5]), "=f"(d[6]), "=f"(d[7]), "=f"(d[8]), "=f"(d[9]), "=f"(d[10]), "=f"(d[11]),
        "=f"(d[12]), "=f"(d[13]), "=f"(d[14]), "=f"(d[15]), "=f"(d[16]), "=f"(d[17]), "=f"(d[18]), "=f"(d[19]), "=f"(d[20]), "=f"(d[21]), "=f"(d[22]),
        "=f"(d[23]), "=f"(d[24]), "=f"(d[25]), "=f"(d[26]), "=f"(d[27]), "=f"(d[28]), "=f"(d[29]), "=f"(d[30]), "=f"(d[31])
      : "r"(a0), "r"(a1), "r"(a2), "r"(a3), "l"(db), "r"(scaleD));
}
__device__ __forceinline__ void wgmma_pv_init(float (&d)[64], uint32_t a0, uint32_t a1, uint32_t a2, uint32_t a3, uint64_t db, int scaleD) {
  asm volatile("{\n.reg .pred p;\nsetp.ne.b32 p, %69, 0;\n"
      "wgmma.mma_async.sync.aligned.m64n128k16.f32.bf16.bf16 "
      "{%0, %1, %2, %3, %4, %5, %6, %7, %8, %9, %10, %11, %12, %13, %14, %15, %16, %17, %18, %19, %20, %21, %22, %23, %24, %25, %26, %27, %28, %29, %30, "
      "%31, %32, %33, %34, %35, %36, %37, %38, %39, %40, %41, %42, %43, %44, %45, %46, %47, %48, %49, %50, %51, %52, %53, %54, %55, %56, %57, %58, %59, %60, "
      "%61, %62, %63}, "
      "{%64, %65, %66, %67}, %68, p, 1, 1, 1;\n}\n"
      : "=f"(d[0]), "=f"(d[1]), "=f"(d[2]), "=f"(d[3]), "=f"(d[4]), "=f"(d[5]), "=f"(d[6]), "=f"(d[7]), "=f"(d[8]), "=f"(d[9]), "=f"(d[10]), "=f"(d[11]),
        "=f"(d[12]), "=f"(d[13]), "=f"(d[14]), "=f"(d[15]), "=f"(d[16]), "=f"(d[17]), "=f"(d[18]), "=f"(d[19]), "=f"(d[20]), "=f"(d[21]), "=f"(d[22]),
        "=f"(d[23]), "=f"(d[24]), "=f"(d[25]), "=f"(d[26]), "=f"(d[27]), "=f"(d[28]), "=f"(d[29]), "=f"(d[30]), "=f"(d[31]), "=f"(d[32]), "=f"(d[33]),
        "=f"(d[34]), "=f"(d[35]), "=f"(d[36]), "=f"(d[37]), "=f"(d[38]), "=f"(d[39]), "=f"(d[40]), "=f"(d[41]), "=f"(d[42]), "=f"(d[43]), "=f"(d[44]),
        "=f"(d[45]), "=f"(d[46]), "=f"(d[47]), "=f"(d[48]), "=f"(d[49]), "=f"(d[50]), "=f"(d[51]), "=f"(d[52]), "=f"(d[53]), "=f"(d[54]), "=f"(d[55]),
        "=f"(d[56]), "=f"(d[57]), "=f"(d[58]), "=f"(d[59]), "=f"(d[60]), "=f"(d[61]), "=f"(d[62]), "=f"(d[63])
      : "r"(a0), "r"(a1), "r"(a2), "r"(a3), "l"(db), "r"(scaleD));
}
__device__ __forceinline__ void wgmma_qk_sp_init(float (&d)[32], uint32_t a0, uint32_t a1, uint32_t a2, uint32_t a3, uint64_t db, int scaleD, uint32_t meta) {
  asm volatile("{\n.reg .pred p;\nsetp.ne.b32 p, %37, 0;\n"
      "wgmma.mma_async.sp.sync.aligned.m64n64k32.f32.bf16.bf16 "
      "{%0, %1, %2, %3, %4, %5, %6, %7, %8, %9, %10, %11, %12, %13, %14, %15, %16, %17, %18, %19, %20, %21, %22, %23, %24, %25, %26, %27, %28, %29, %30, "
      "%31}, "
      "{%32, %33, %34, %35}, %36, %38, 0, p, 1, 1, 0;\n}\n"
      : "=f"(d[0]), "=f"(d[1]), "=f"(d[2]), "=f"(d[3]), "=f"(d[4]), "=f"(d[5]), "=f"(d[6]), "=f"(d[7]), "=f"(d[8]), "=f"(d[9]), "=f"(d[10]), "=f"(d[11]),
        "=f"(d[12]), "=f"(d[13]), "=f"(d[14]), "=f"(d[15]), "=f"(d[16]), "=f"(d[17]), "=f"(d[18]), "=f"(d[19]), "=f"(d[20]), "=f"(d[21]), "=f"(d[22]),
        "=f"(d[23]), "=f"(d[24]), "=f"(d[25]), "=f"(d[26]), "=f"(d[27]), "=f"(d[28]), "=f"(d[29]), "=f"(d[30]), "=f"(d[31])
      : "r"(a0), "r"(a1), "r"(a2), "r"(a3), "l"(db), "r"(scaleD), "r"(meta));
}
__device__ __forceinline__ void wgmma_pv_sp_init(float (&d)[64], uint32_t a0, uint32_t a1, uint32_t a2, uint32_t a3, uint64_t db, int scaleD, uint32_t meta) {
  asm volatile("{\n.reg .pred p;\nsetp.ne.b32 p, %69, 0;\n"
      "wgmma.mma_async.sp.sync.aligned.m64n128k32.f32.bf16.bf16 "
      "{%0, %1, %2, %3, %4, %5, %6, %7, %8, %9, %10, %11, %12, %13, %14, %15, %16, %17, %18, %19, %20, %21, %22, %23, %24, %25, %26, %27, %28, %29, %30, "
      "%31, %32, %33, %34, %35, %36, %37, %38, %39, %40, %41, %42, %43, %44, %45, %46, %47, %48, %49, %50, %51, %52, %53, %54, %55, %56, %57, %58, %59, %60, "
      "%61, %62, %63}, "
      "{%64, %65, %66, %67}, %68, %70, 0, p, 1, 1, 1;\n}\n"
      : "=f"(d[0]), "=f"(d[1]), "=f"(d[2]), "=f"(d[3]), "=f"(d[4]), "=f"(d[5]), "=f"(d[6]), "=f"(d[7]), "=f"(d[8]), "=f"(d[9]), "=f"(d[10]), "=f"(d[11]),
        "=f"(d[12]), "=f"(d[13]), "=f"(d[14]), "=f"(d[15]), "=f"(d[16]), "=f"(d[17]), "=f"(d[18]), "=f"(d[19]), "=f"(d[20]), "=f"(d[21]), "=f"(d[22]),
        "=f"(d[23]), "=f"(d[24]), "=f"(d[25]), "=f"(d[26]), "=f"(d[27]), "=f"(d[28]), "=f"(d[29]), "=f"(d[30]), "=f"(d[31]), "=f"(d[32]), "=f"(d[33]),
        "=f"(d[34]), "=f"(d[35]), "=f"(d[36]), "=f"(d[37]), "=f"(d[38]), "=f"(d[39]), "=f"(d[40]), "=f"(d[41]), "=f"(d[42]), "=f"(d[43]), "=f"(d[44]),
        "=f"(d[45]), "=f"(d[46]), "=f"(d[47]), "=f"(d[48]), "=f"(d[49]), "=f"(d[50]), "=f"(d[51]), "=f"(d[52]), "=f"(d[53]), "=f"(d[54]), "=f"(d[55]),
        "=f"(d[56]), "=f"(d[57]), "=f"(d[58]), "=f"(d[59]), "=f"(d[60]), "=f"(d[61]), "=f"(d[62]), "=f"(d[63])
      : "r"(a0), "r"(a1), "r"(a2), "r"(a3), "l"(db), "r"(scaleD), "r"(meta));
}

constexpr int NB = 16, SQ = 224, DM = 640, NH = 32, SK = 1024, DH = 128;
constexpr int HD = NH * DH;
constexpr int NBETA = 2 * NB;
constexpr int NCTA = 132;
constexpr uint32_t SB0 = 1024;
constexpr int NS = 10;
constexpr int SLOT = 16384;
constexpr int QBUF_OFF = NS * SLOT;
constexpr int NSX = NS + 4;
constexpr int BAR_OFF = NSX * SLOT;
constexpr int BAR_FULL = BAR_OFF;
constexpr int BAR_EMPTY = BAR_OFF + 8 * NSX;
constexpr int BAR_STG = BAR_OFF + 16 * NSX;
constexpr int BAR_OUT = BAR_STG + 32;
constexpr int BAR_DESC = BAR_OUT + 8;
constexpr int BAR_GO = BAR_DESC + 8;
constexpr int BAR_MAIL = BAR_GO + 8;
constexpr int BAR_RDY = BAR_MAIL + 8;
constexpr int DESC_OFF = BAR_RDY + 8 * NSX;
constexpr int EPOCH_OFF = DESC_OFF + 16;
constexpr int TRACE_OFF = EPOCH_OFF + 16;
constexpr int SMEM_BYTES = TRACE_OFF;
constexpr float SM_C = 0.08838834764831845f * 1.4426950408889634f;
constexpr float SUM_HI = 1099511627776.f, SUM_LO = 1.f / 1099511627776.f;
constexpr uint32_t META_QK = 0xEEEE4444u;
constexpr uint32_t META_PV = 0x44EEEE44u;

#define QK_EARLY_MASK 3
#define ST_ORDER 0x2310
#define LAG_BAR 2
#define ST_NOW 8
#define PF_STEP 3
#define KV_WIN_D 4
#define SF 0xeebf
#define O_STEPS 4
#define KV_WIN_RAMP 4
#define PDEPTH 0
#define KV_WIN_TILES -2
#define REG_C 232
#define REG_P 24
#define GO_P 6
#define P_POS 208
#define OR 6
#define OR0 0
#define B_LATE 22
#define H_LATE 24
#define RM0 1
#define RM1 0xab
#define RM2 0
#define PAIRB 1
#define LATE0 1
#define LATE1 2
#define GO_J 13
#define LATE_G 32
#define KG 5
#define PK 44
#define EARLY_MASK 0xffffu
#define PIECE_TABLE 0x5018a81d,0x6762a833,0x502b7814,0x6c4e7836,0x500e581a,0x656a5839,0x50146019,0x67236032,0x501cb013,0x691bb03f,0x5032201c,0x80000000,0x50308016,0x80000000,0x500ca011,0x6666a03d,0x63b1103b,0x80000000,0x642f2838,0x80000000,0x50264017,0x80000000,0x501b9010,0x6c4e9051,0x53639811,0x80000000,0x5023b81f,0x80000000,0x50210815,0x80000000,0x501ec81e,0x80000000,0x67238830,0x80000000,0x67e0c03e,0x80000000,0x501b6812,0x80000000,0x53d9501a,0x80000000,0x689d0035,0x80000000,0x500d181b,0x6ccc183c,0x69d83837,0x80000000,0x6a56485a,0x80000000,0x500f3018,0x80000000,0x6b137034,0x80000000

struct Params {
  CUtensorMap x[2][2], wq[2], kv[2][2], wo[2];
  CUtensorMap o_ld[2], o_st[2], out_st[2];
  const __nv_bfloat16* kp[2];
  const __nv_bfloat16* vp[2];
};

constexpr int NPART = 32 * 5, O_BLOCKS = NBETA * 64 + 2 * NPART;
__device__ __align__(128) __nv_bfloat16 g_o[(size_t)O_BLOCKS * SQ * 64];
__device__ unsigned g_cnt[NBETA][8];
__device__ unsigned g_rd[NBETA][8];
__device__ unsigned g_epoch, g_next;
__device__ unsigned g_flag[NPART];

__device__ __forceinline__ uint32_t smem_u32(const void* p) { return (uint32_t)__cvta_generic_to_shared(p); }
__device__ __forceinline__ void mbar_arrive(uint32_t bar) {
  asm volatile("mbarrier.arrive.shared::cta.b64 _, [%0];" ::"r"(bar) : "memory");
}
__device__ __forceinline__ void mbar_arrive_warp(uint32_t bar) {
  asm volatile("{\n.reg .pred p;\nelect.sync _|p, 0xffffffff;\n@p mbarrier.arrive.shared::cta.b64 _, [%0];\n}" ::"r"(bar) : "memory");
}
__device__ __forceinline__ int lane_now() { int l; asm volatile("mov.u32 %0, %%laneid;" : "=r"(l)); return l; }
__device__ __forceinline__ bool mbar_try(uint32_t bar, uint32_t parity) {
  uint32_t ok;
  asm volatile("{\n.reg .pred p;\nmbarrier.try_wait.parity.shared::cta.b64 p, [%1], %2;\nselp.u32 %0, 1, 0, p;\n}"
               : "=r"(ok) : "r"(bar), "r"(parity) : "memory");
  return ok;
}
__device__ __forceinline__ bool mbar_test(uint32_t bar, uint32_t parity) {
  uint32_t ok;
  asm volatile("{\n.reg .pred p;\nmbarrier.test_wait.parity.shared::cta.b64 p, [%1], %2;\nselp.u32 %0, 1, 0, p;\n}"
               : "=r"(ok) : "r"(bar), "r"(parity) : "memory");
  return ok;
}
__device__ __forceinline__ void mbar_wait_w(uint32_t bar, uint32_t parity) {
  uint32_t n = 0;
  while (!__all_sync(0xffffffffu, mbar_try(bar, parity))) {
    if (++n > (1u << 22)) __trap();
  }
}
#define ELECT "{\n.reg .pred p;\nelect.sync _|p, 0xffffffff;\n@p "
__device__ __forceinline__ void tma_st3_w(const CUtensorMap* m, uint32_t src, int c1, int c2) {
  asm volatile(ELECT "cp.async.bulk.tensor.3d.global.shared::cta.bulk_group [%0, {0, %2, %3}], [%1];\n}"
               ::"l"(m), "r"(src), "r"(c1), "r"(c2) : "memory");
}
#define EXPECT(bar, bytes) "mbarrier.arrive.expect_tx.shared::cta.b64 _, [" bar "], " bytes ";\n@p "
__device__ __forceinline__ void tma_ld2_w(uint32_t dst, const CUtensorMap* m, int c0, int c1, uint32_t bar, uint32_t bytes) {
  asm volatile(ELECT EXPECT("%2", "%5") "cp.async.bulk.tensor.2d.shared::cluster.global.mbarrier::complete_tx::bytes [%0], [%1, {%3, %4}], [%2];\n}"
               ::"r"(dst), "l"(m), "r"(bar), "r"(c0), "r"(c1), "r"(bytes) : "memory");
}
__device__ __forceinline__ void tma_ld2_hint_w(uint32_t dst, const CUtensorMap* m, int c0, int c1, uint32_t bar, uint32_t bytes, uint64_t pol) {
  asm volatile(ELECT EXPECT("%2", "%6") "cp.async.bulk.tensor.2d.shared::cluster.global.mbarrier::complete_tx::bytes.L2::cache_hint"
               " [%0], [%1, {%3, %4}], [%2], %5;\n}"
               ::"r"(dst), "l"(m), "r"(bar), "r"(c0), "r"(c1), "l"(pol), "r"(bytes) : "memory");
}
__device__ __forceinline__ void tma_ld3_w(uint32_t dst, const CUtensorMap* m, int c0, int c1, int c2, uint32_t bar, uint32_t bytes) {
  asm volatile(ELECT EXPECT("%2", "%6") "cp.async.bulk.tensor.3d.shared::cluster.global.mbarrier::complete_tx::bytes [%0], [%1, {%3, %4, %5}], [%2];\n}"
               ::"r"(dst), "l"(m), "r"(bar), "r"(c0), "r"(c1), "r"(c2), "r"(bytes) : "memory");
}
__device__ __forceinline__ void tma_ld_kv_w(uint32_t dst, const CUtensorMap* m, int grp, uint32_t bar, uint64_t pol) {
  asm volatile(ELECT EXPECT("%2", "16384") "cp.async.bulk.tensor.4d.shared::cluster.global.mbarrier::complete_tx::bytes.L2::cache_hint"
               " [%0], [%1, {0, 0, 0, %3}], [%2], %4;\n}"
               ::"r"(dst), "l"(m), "r"(bar), "r"(grp), "l"(pol) : "memory");
}
__device__ __forceinline__ void tma_ld_wo_w(uint32_t dst, const CUtensorMap* m, int col, int grp, uint32_t bar) {
  asm volatile(ELECT EXPECT("%2", "16384") "cp.async.bulk.tensor.5d.shared::cluster.global.mbarrier::complete_tx::bytes [%0], [%1, {%3, 0, 0, 0, %4}], [%2];\n"
               "@p cp.async.bulk.tensor.5d.shared::cluster.global.mbarrier::complete_tx::bytes [%5], [%1, {%6, 0, 0, 0, %4}], [%2];\n}"
               ::"r"(dst), "l"(m), "r"(bar), "r"(col), "r"(grp), "r"(dst + 8192), "r"(col + 64) : "memory");
}
__device__ __forceinline__ void mbar_arrive8_w(uint32_t bar) {
  asm volatile(ELECT "mbarrier.arrive.shared::cta.b64 _, [%0], 8;\n}" ::"r"(bar) : "memory");
}
__device__ __forceinline__ uint32_t peer(uint32_t a) { uint32_t r; asm("mapa.shared::cluster.u32 %0, %1, %2;" : "=r"(r) : "r"(a), "r"(~blockIdx.x & 1)); return r; }
__device__ __forceinline__ void tma_ld2_both_w(uint32_t dst, const CUtensorMap* m, int c0, int c1, uint32_t bar, uint32_t bytes) {
  asm volatile(ELECT EXPECT("%2", "%5") "cp.async.bulk.tensor.2d.shared::cluster.global.mbarrier::complete_tx::bytes.multicast::cluster"
               " [%0], [%1, {%3, %4}], [%2], %6;\n}"
               ::"r"(dst), "l"(m), "r"(bar), "r"(c0), "r"(c1), "r"(bytes), "h"((uint16_t)3) : "memory");
}
__device__ __forceinline__ void tma_ld2_both_hint_w(uint32_t dst, const CUtensorMap* m, int c0, int c1, uint32_t bar, uint32_t bytes, uint64_t pol) {
  asm volatile(ELECT EXPECT("%2", "%6") "cp.async.bulk.tensor.2d.shared::cluster.global.mbarrier::complete_tx::bytes.multicast::cluster.L2::cache_hint"
               " [%0], [%1, {%3, %4}], [%2], %7, %5;\n}"
               ::"r"(dst), "l"(m), "r"(bar), "r"(c0), "r"(c1), "l"(pol), "r"(bytes), "h"((uint16_t)3) : "memory");
}
__device__ __forceinline__ void bulk_commit() { asm volatile("cp.async.bulk.commit_group;" ::: "memory"); }
template <int N> __device__ __forceinline__ void bulk_wait_read() { asm volatile("cp.async.bulk.wait_group.read %0;" ::"n"(N) : "memory"); }
__device__ __forceinline__ void wg_fence() { asm volatile("wgmma.fence.sync.aligned;" ::: "memory"); }
__device__ __forceinline__ void wg_commit() { asm volatile("wgmma.commit_group.sync.aligned;" ::: "memory"); }
template <int N> __device__ __forceinline__ void wg_wait() { asm volatile("wgmma.wait_group.sync.aligned %0;" ::"n"(N) : "memory"); }
__device__ __forceinline__ void fence_async_smem() { asm volatile("fence.proxy.async.shared::cta;" ::: "memory"); }
__device__ __forceinline__ void bar_sync(int id, int n) { asm volatile("bar.sync %0, %1;" ::"r"(id), "r"(n) : "memory"); }
__device__ __forceinline__ void touch(float& a) { asm volatile("neg.f32 %0, %0;" : "+f"(a)); }
__device__ __forceinline__ void touch(uint32_t& a) { asm volatile("not.b32 %0, %0;" : "+r"(a)); }
template <typename T, int N> __device__ __forceinline__ void touch(T (&a)[N]) {
#pragma unroll
  for (int i = 0; i < N; i++) touch(a[i]);
}
template <int ID, typename... A> __device__ __forceinline__ void sched_fence(uint32_t x, A&... a) {
  if (!((SF >> ID) & 1)) return;
  asm volatile("" : "+r"(x)::"memory");
#pragma unroll 1
  for (; __builtin_expect(x >= 100 + ID, 0); x >>= 1) { (touch(a), ...); __nanosleep(x); }
}
template <int N> __device__ __forceinline__ void reg_fence(float (&a)[N]) {
#pragma unroll
  for (int i = 0; i < N; i++) asm volatile("" : "+f"(a[i])::"memory");
}
template <int N> __device__ __forceinline__ void reg_fence(uint32_t (&a)[N]) {
#pragma unroll
  for (int i = 0; i < N; i++) asm volatile("" : "+r"(a[i])::"memory");
}
__device__ __forceinline__ float ex2(float x) { float y; asm("ex2.approx.ftz.f32 %0, %1;" : "=f"(y) : "f"(x)); return y; }
__device__ __forceinline__ uint32_t pack_bf16(float lo, float hi) {
  uint32_t r; asm("cvt.rn.bf16x2.f32 %0, %1, %2;" : "=r"(r) : "f"(hi), "f"(lo)); return r;
}
__device__ __forceinline__ void stsm4(uint32_t a, uint32_t r0, uint32_t r1, uint32_t r2, uint32_t r3) {
  asm volatile("stmatrix.sync.aligned.m8n8.x4.shared.b16 [%0], {%1, %2, %3, %4};" ::"r"(a), "r"(r0), "r"(r1), "r"(r2), "r"(r3) : "memory");
}
__device__ __forceinline__ void stsm4t(uint32_t a, uint32_t r0, uint32_t r1, uint32_t r2, uint32_t r3) {
  asm volatile("stmatrix.sync.aligned.m8n8.x4.trans.shared.b16 [%0], {%1, %2, %3, %4};" ::"r"(a), "r"(r0), "r"(r1), "r"(r2), "r"(r3) : "memory");
}
__device__ __forceinline__ void ldsm4(uint32_t a, uint32_t& r0, uint32_t& r1, uint32_t& r2, uint32_t& r3) {
  asm volatile("ldmatrix.sync.aligned.m8n8.x4.shared.b16 {%0, %1, %2, %3}, [%4];" : "=r"(r0), "=r"(r1), "=r"(r2), "=r"(r3) : "r"(a) : "memory");
}
__device__ __forceinline__ void sts16(uint32_t a, uint32_t v) { asm volatile("st.shared.u16 [%0], %1;" ::"r"(a), "h"((uint16_t)v) : "memory"); }
__device__ __forceinline__ void mma16816(float& c0, float& c1, float& c2, float& c3, uint32_t a0, uint32_t a1, uint32_t a2, uint32_t a3,
                                         uint32_t b0, uint32_t b1) {
  asm volatile("mma.sync.aligned.m16n8k16.row.col.f32.bf16.bf16.f32 {%0, %1, %2, %3}, {%4, %5, %6, %7}, {%8, %9}, {%0, %1, %2, %3};"
               : "+f"(c0), "+f"(c1), "+f"(c2), "+f"(c3) : "r"(a0), "r"(a1), "r"(a2), "r"(a3), "r"(b0), "r"(b1));
}
__device__ __forceinline__ uint32_t sdesc(uint32_t addr, uint32_t lbo) { return (addr >> 4) + ((lbo >> 4) << 16); }
__device__ __forceinline__ uint64_t desc64(uint32_t lo, uint32_t hi) { uint64_t d; asm("mov.b64 %0, {%1, %2};" : "=l"(d) : "r"(lo), "r"(hi)); return d; }
__device__ __forceinline__ void dadd(uint64_t& d, uint32_t inc) {
  asm("{\n.reg .b32 l, h;\nmov.b64 {l, h}, %0;\nadd.u32 l, l, %1;\nmov.b64 %0, {l, h};\n}" : "+l"(d) : "r"(inc));
}

struct Ring {
  uint32_t slot, phase, xp;
  __device__ __forceinline__ void uniform() {
    slot = __shfl_sync(0xffffffffu, slot, 0); phase = __shfl_sync(0xffffffffu, phase, 0); xp = __shfl_sync(0xffffffffu, xp, 0);
  }
  __device__ __forceinline__ void next() { if (++slot == NS) { slot = 0; phase ^= 1; } }
  __device__ __forceinline__ void next_if(bool p) { slot += p; if (slot == NS) { slot = 0; phase ^= 1; } }
};
__device__ __forceinline__ uint32_t borrow(int ks, int n) {
  const int k = ks + 1;
  return k >= 4 && !(k & 2) && k < n ? k & 1 : 2;
}

constexpr uint32_t Q_RANGES = NBETA * NH + __builtin_popcount(EARLY_MASK) * 5, Q_ALL = NBETA * (NH + 5);
constexpr int NRANGE = NCTA / 5;
struct Work { int kind, mode, k0, nsteps, range, beta, sub; };
struct Sched { uint16_t queue[Q_ALL]; uint32_t piece[NRANGE + 1][4]; };
constexpr Sched make_sched() {
  Sched s{};
  int q = 0, a = 0;
  for (int t = 0, e = 0; a < NBETA * NH; t++) {
    for (; e < NBETA && 8 * (e & ~PAIRB) + PK <= t && a >= P_POS; e++)
      for (int col = 0; col < 5 && (EARLY_MASK >> e & 1); col++) s.queue[q++] = 0x8000 | (e & 1 ? 4 - col : col) << 8 | e;
    for (int b = 0; b < NBETA; b++)
      for (int h = 0; h < NH; h++)
        if ((b >= B_LATE && h >= H_LATE ? 300 + b + LATE_G * (h >> 2) : 8 * (b & ~PAIRB) + KG * (h >> 2)) == t) { s.queue[q++] = b << 5 | h; a++; }
  }
  for (int b = 0; b < NBETA; b++)
    for (int col = 0; col < 5 && !(EARLY_MASK >> b & 1); col++) s.queue[q++] = 0x8000 | col << 8 | b;
  constexpr uint32_t T[NRANGE * 2] = {PIECE_TABLE};
  for (int g = 0; g <= NRANGE; g++)
    for (int n = 0; n < 4; n++) s.piece[g][n] = g < NRANGE && n < 2 ? T[2 * g + n] : 2u << 30;
  return s;
}
__constant__ Sched c_sched = make_sched();
constexpr int N_EARLY = __builtin_popcount(EARLY_MASK);
constexpr bool reuse_ok() {
  const Sched s = make_sched();
  int first[NBETA + OR] = {};
  for (int q = Q_RANGES - 1; q >= 0; q--) if (!(s.queue[q] & 0x8000)) first[s.queue[q] >> 5] = q;
  for (int q = 0; q < Q_RANGES; q++) if ((s.queue[q] & 0x8000) && (s.queue[q] & 31) >= OR0 && q - first[(s.queue[q] & 31) + OR] > NCTA - 32) return false;
  return first[OR0 + OR] >= NCTA && P_POS >= NCTA;
}
static_assert(reuse_ok());
template <bool SIMPLE> __device__ __forceinline__ bool o_reuse(uint32_t b) { return !SIMPLE && b - (OR0 + OR) < N_EARLY - OR0; }
template <bool SIMPLE> __device__ __forceinline__ uint32_t o_slot(uint32_t b) { return o_reuse<SIMPLE>(b) ? OR0 + (b - OR0) % OR : b; }
__device__ __forceinline__ Work decode(uint32_t d) {
  Work w;
  w.kind = d >> 30; if (w.kind == 3) w.kind = 1;
  w.mode = (d >> 28) & 3; w.k0 = (d >> 22) & 63;
  if (w.kind == 0) { w.beta = (d >> 5) & 31; w.sub = d & 31; w.nsteps = DM / 64; }
  else { w.beta = d & 31; w.sub = (d >> 8) & 7; w.nsteps = ((d >> 16) & 63) + 1; }
  w.range = ((d >> 11) & 31) * 5 + w.sub;
  return w;
}

__device__ __forceinline__ bool reached(const unsigned* cnt, unsigned target) {
  unsigned v;
  asm volatile("ld.acquire.gpu.global.u32 %0, [%1];" : "=r"(v) : "l"(cnt) : "memory");
  return (int)(v - target) >= 0;
}
__device__ __forceinline__ void wait_count(const unsigned* cnt, unsigned target) {
  unsigned n = 0;
  while (!__all_sync(0xffffffffu, reached(cnt, target))) { if (++n > (1u << 24)) __trap(); }
}
__device__ __forceinline__ uint32_t lds(uint32_t a) { uint32_t v; asm volatile("ld.volatile.shared.u32 %0, [%1];" : "=r"(v) : "r"(a) : "memory"); return v; }

#define TRACE(u, e)
#define T3(u, e)
#define T2C(u, e)
#define T2P(u, r, e)
#define TTAIL(k)
#define TCLK(k)
#define TO -1
#define TRACE_O(k) if (TO == k) TRACE(i, 5)
#define TRACE_P(u, e)
#define TRACE_IN(u, e)

struct Ctx {
  uint32_t sb;
  int wg, warp;
  uint32_t mqk, mpv;
  bool lead;
  int lane0, lane;
  int src;
};
template <int N> __device__ __forceinline__ uint32_t dhi(uint32_t lo) { return 0x40000040u + (lo >> (26 + N)); }
__device__ __forceinline__ void release(const Ctx& c, uint32_t slot) {
  if (c.lead) mbar_arrive(c.sb + BAR_EMPTY + slot * 8);
}
__device__ __forceinline__ uint32_t acquire(const Ctx& c, Ring& r, bool have = false) {
  const uint32_t s = r.slot;
  if (!have) mbar_wait_w(c.sb + BAR_FULL + s * 8, r.phase);
  r.next();
  return s;
}
__device__ __forceinline__ void mbar_wait2_w(uint32_t b0, uint32_t p0, uint32_t b1, uint32_t p1) {
  uint32_t n = 0;
  while (!__all_sync(0xffffffffu, mbar_try(b0, p0) & mbar_try(b1, p1))) {
    if (++n > (1u << 22)) __trap();
  }
}
__device__ __forceinline__ void mbar_wait3_w(uint32_t b0, uint32_t p0, uint32_t b1, uint32_t p1, uint32_t b2, uint32_t p2) {
  uint32_t n = 0;
  while (!__all_sync(0xffffffffu, mbar_try(b0, p0) & mbar_try(b1, p1) & mbar_try(b2, p2))) {
    if (++n > (1u << 22)) __trap();
  }
}
__device__ __forceinline__ void acquire2(const Ctx& c, Ring& r, uint32_t& s0, uint32_t& s1, bool have = false) {
  const uint32_t p0 = r.phase;
  s0 = r.slot; r.next(); s1 = r.slot;
  if (!have) mbar_wait2_w(c.sb + BAR_FULL + s0 * 8, p0, c.sb + BAR_FULL + s1 * 8, r.phase);
  r.next();
}
template <int N>
__device__ __forceinline__ bool peek(const Ctx& c, Ring r) {
  bool ok = true;
#pragma unroll
  for (int k = 0; k < N; k++) { ok &= mbar_test(c.sb + BAR_FULL + r.slot * 8, r.phase); r.next(); }
  return ok;
}
__device__ __forceinline__ void staged(const Ctx& c, int part) {
  fence_async_smem();
  __syncwarp();
  mbar_arrive_warp(c.sb + BAR_STG + c.wg * 16 + part * 8);
}

template <int WG, bool FIRST, int H>
__device__ __forceinline__ void proj_half(const Ctx& c, float (&acc)[64], uint32_t w, uint32_t x, uint32_t sw) {
  uint64_t dx = desc64((SB0 + x * SLOT + (WG ? 0 : H * 8192)) >> 4, dhi<0>(x) + sw);
  uint64_t dw = desc64(WG ? (SB0 + w * SLOT + H * 8192) >> 4 : sdesc(SB0 + w * SLOT, 8192), dhi<1>(x));
  wg_fence();
  if (WG) { if (FIRST) wgmma_proj96_init(acc, dw, dx, 0); else wgmma_proj96(acc, dw, dx, 1); }
  else { if (FIRST) wgmma_proj_init(acc, dx, dw, 0); else wgmma_proj(acc, dx, dw, 1); }
#pragma unroll
  for (int k = 1; k < 4; k++) {
    dadd(dx, k == 2 ? 2 + (sw >> 30) * 28 : 2); dadd(dw, 128);
    if (WG) wgmma_proj96(acc, dw, dx, 1); else wgmma_proj(acc, dx, dw, 1);
  }
  wg_commit();
}

__device__ __forceinline__ void proj_store16(uint32_t a, const float* f, float sc) {
  stsm4t(a, pack_bf16(f[0] * sc, f[1] * sc), pack_bf16(f[2] * sc, f[3] * sc), pack_bf16(f[4] * sc, f[5] * sc), pack_bf16(f[6] * sc, f[7] * sc));
}

__device__ __forceinline__ uint32_t stage_off(const Ctx& c) {
  const int lane = c.lane, mi = lane >> 3, r8 = lane & 7;
  return ((mi >> 1) * 8 + r8) * 128 + (((2 * c.warp + (mi & 1)) ^ r8) << 4);
}
__device__ __forceinline__ uint32_t q3_swz(uint32_t r8) { return ((r8 & 3) << 1) | (r8 >> 2); }
template <int H>
__device__ __forceinline__ void stage_t2(const Ctx& c, const float (&a)[64], float sc) {
  const uint32_t base = c.sb + QBUF_OFF + 2 * 16384 + H * 8192 + stage_off(c);
#pragma unroll
  for (int jj = 0; jj < 4; jj++) proj_store16(base + jj * 2048, &a[jj * 8], sc);
}
template <int H, bool IS_Q>
__device__ __forceinline__ void stage_t3(const Ctx& c, const float (&a)[64], float sc) {
  const uint32_t off = stage_off(c), r8 = (off >> 7) & 7;
  const uint32_t t3 = c.sb + QBUF_OFF + 3 * 16384 + H * 4096 + (IS_Q ? off ^ ((r8 ^ q3_swz(r8)) << 4) : off);
  proj_store16(t3, &a[32], sc);
  proj_store16(t3 + 2048, &a[40], sc);
}

template <int WG, int h, int NW = 4>
__device__ __forceinline__ void load_part(const Ctx& c, Ring r, uint32_t (&q)[32]) {
  uint32_t n = 0;
  while (NW && !__all_sync(0xffffffffu, peek<NW>(c, r))) {
    if (++n > (1u << 26)) __trap();
  }
  const int lane = c.lane, mi = lane >> 3, r8 = lane & 7;
  if (WG) { r.next(); r.next(); }
  const uint32_t off = c.sb + (WG ? stage_off(c) : (16 * c.warp + (mi & 1) * 8 + r8) * 128), t0 = off + r.slot * SLOT;
  r.next();
  const uint32_t t1 = off + r.slot * SLOT;
#pragma unroll
    for (int jj = 0; jj < (WG ? 6 : 8); jj++) {
      uint32_t* p = &q[4 * jj];
      if (WG) asm volatile("ldmatrix.sync.aligned.m8n8.x4.trans.shared.b16 {%0, %1, %2, %3}, [%4];" : "=r"(p[0]), "=r"(p[1]), "=r"(p[2]), "=r"(p[3])
                           : "r"((jj < 4 ? t0 + h * 8192 : t1 + h * 4096) + (jj & 3) * 2048) : "memory");
      else ldsm4((h ? t1 : t0) + (jj >> 2) * 8192 + (((((2 * jj) & 7) + (mi >> 1)) ^ r8) << 4), p[0], p[1], p[2], p[3]);
    }
}
template <int WG>
__device__ __forceinline__ void add_part(const Ctx& c, const uint32_t (&q)[32], float (&a)[64]) {
  const uint32_t one = (c.lane >> 3) == (c.lane & 3) ? 0x3f80u << (c.lane & 4) * 4 : 0;
#pragma unroll
  for (int i = 0; i < (WG ? 12 : 16); i++)
    asm("mma.sync.aligned.m16n8k8.row.col.f32.bf16.bf16.f32 {%0, %1, %2, %3}, {%4, %5}, {%6}, {%0, %1, %2, %3};"
        : "+f"(a[4 * i]), "+f"(a[4 * i + 1]), "+f"(a[4 * i + 2]), "+f"(a[4 * i + 3]) : "r"(q[2 * i]), "r"(q[2 * i + 1]), "r"(one));
}

__device__ __forceinline__ void trace_dump(const Ctx& c) {
}
struct RowSum { float l0, l1; };
__device__ __forceinline__ const char* o_addr(uint32_t item, int row, int lane) {
  return reinterpret_cast<const char*>(g_o) + (((item >> 10) * (2 * SQ) + row) * 128 + (lane ^ (lane >> 3)) * 16);
}
__device__ __forceinline__ void o_stg(const char* p, int i, const uint32_t* q) {
  asm volatile("st.global.v4.b32 [%0], {%1, %2, %3, %4};"
               ::"l"(p + (i >> 1) * (SQ * 128) + (i & 1) * 512), "r"(q[0]), "r"(q[1]), "r"(q[2]), "r"(q[3]) : "memory");
}
template <int MODE, int I0 = 0, int NI = 4>
__device__ __forceinline__ void o_emit(const char* p, const float (&o)[64], float inv) {
#pragma unroll
  for (int i = I0; i < I0 + NI; i++) {
    uint32_t q[4];
#pragma unroll
    for (int j = 0; j < 4; j++) q[j] = pack_bf16(o[16 * i + 4 * j + 2 * MODE] * inv, o[16 * i + 4 * j + 2 * MODE + 1] * inv);
    o_stg(p, i, q);
  }
}
__device__ __forceinline__ void o_done(const Ctx& c) {
  __syncwarp();
  mbar_arrive_warp(c.sb + BAR_OUT);
  __syncwarp();
}
template <int WG>
__device__ __forceinline__ void o_first(const Ctx& c, uint32_t item, float (&o)[64], const RowSum& inv, uint32_t (&q)[32]) {
  const char* p = o_addr(item, WG ? 192 + 8 * c.warp : 64 + 16 * c.warp, c.lane);
  reg_fence(o);
#pragma unroll
  for (int j = 0; j < 16; j++) {
    if (WG) q[j] = pack_bf16((o[4 * j] + o[4 * j + 2]) * inv.l0, (o[4 * j + 1] + o[4 * j + 3]) * inv.l0);
    else q[j] = pack_bf16(o[4 * j] * inv.l0, o[4 * j + 1] * inv.l0);
    if (!WG && (j & 3) == 3 && (j >> 2) < 8 - LATE0) o_stg(p, j >> 2, q + j - 3);
  }
#pragma unroll
  for (int j = 0; j < 16; j++) {
    if (!WG) q[16 + j] = pack_bf16(o[4 * j + 2] * inv.l1, o[4 * j + 3] * inv.l1);
    if ((j & 3) == 3 && (j >> 2) < 4 - (WG ? LATE1 : LATE0)) o_stg(WG ? p : p + 1024, j >> 2, q + (WG ? 0 : 16) + j - 3);
  }
}
template <int WG>
__device__ __forceinline__ void o_rest(const Ctx& c, uint32_t item, uint32_t (&q)[32]) {
  const char* p = o_addr(item, WG ? 192 + 8 * c.warp : 64 + 16 * c.warp, c.lane);
#pragma unroll
  for (int i = WG ? 4 - LATE1 : 8 - LATE0; i < (WG ? 4 : 8); i++) o_stg(p + (i >> 2) * 1024, i & 3, q + 4 * i);
}
template <int K0, int K1>
__device__ __forceinline__ void o_piece(const Ctx& c, const char* p, int k, const float (&o)[64], const RowSum& inv) {
  constexpr int NI = 8 / O_STEPS, M = K0 * NI / 4;
  if constexpr (K1 - K0 == 1) {
    o_emit<M, K0 * NI % 4, NI>(p + M * 1024, o, M ? inv.l1 : inv.l0);
    if (K1 == O_STEPS) o_done(c);
  } else {
    if (k <= (K0 + K1) / 2) o_piece<K0, (K0 + K1) / 2>(c, p, k, o, inv); else o_piece<(K0 + K1) / 2, K1>(c, p, k, o, inv);
  }
}
template <int WG>
__device__ __forceinline__ void o_second(const Ctx& c, uint32_t item, int k, float (&o)[64], const RowSum& inv) {
  reg_fence(o);
  o_piece<0, O_STEPS>(c, o_addr(item, 128 * WG + 16 * c.warp, c.lane0 + (k >> 8)), k, o, inv);
}
template <int WG>
__device__ __forceinline__ void release_q(const Ctx& c) {
#pragma unroll
  for (int t = 0; t < 2; t++)
    if (c.lead) asm volatile("mbarrier.arrive.shared::cta.b64 _, [%0], 2;" ::"r"(c.sb + BAR_EMPTY + (NS + 2 * WG + t) * 8) : "memory");
  __syncwarp();
}
struct Slots { uint32_t w, x, o, po; };
template <int WG>
__device__ __forceinline__ void acc_fence(float (&a)[64]) {
#pragma unroll
  for (int i = 0; i < (WG ? 48 : 64); i++) asm volatile("" : "+f"(a[i])::"memory");
}
template <int WG>
__device__ __forceinline__ void begin_acquire(const Ctx& c, Ring& r, Slots& h, bool wait) {
  const uint32_t s0 = r.slot, p0 = r.phase, f = c.sb + BAR_FULL;
  r.next();
  const uint32_t p1 = r.phase;
  h.w = r.slot; r.next();
  h.x = WG ? r.slot : s0; h.o = WG ? s0 : r.slot; h.po = r.phase;
  if (wait) { if (WG) mbar_wait3_w(f + s0 * 8, p0, f + h.w * 8, p1, f + h.x * 8, r.phase); else mbar_wait2_w(f + s0 * 8, p0, f + h.w * 8, p1); }
  r.next();
}
template <int WG>
__device__ __forceinline__ void proj_begin(const Ctx& c, Ring& r, float (&a0)[64], Slots& h, bool wait, uint32_t sw) {
  begin_acquire<WG>(c, r, h, wait);
  proj_half<WG, true, 0>(c, a0, h.w, h.x, sw);
  if (WG) release(c, h.o);
}
template <int WG>
__device__ __forceinline__ void proj_main(Ctx& c, Ring& r, float (&a0)[64], float (&a1)[64], Slots& h, int n, uint32_t sw, int unit,
                                          uint32_t item, int nq, float (&o1)[64], const RowSum& inv) {
  constexpr bool DEEP = (PDEPTH >> WG) & 1;
  T2C(unit, 3);
  int ks = 1;
#pragma unroll 1
  do {
    const Slots p = h;
    const uint32_t b = borrow(ks, n), tile = NS + (WG ? 3 - b : b), f = c.sb + BAR_FULL;
    const uint32_t s0 = b != 2 ? tile : r.slot, p0 = b != 2 ? (r.xp >> b) & 1 : r.phase;
    r.next_if(b == 2);
    const uint32_t p1 = r.phase;
    h.w = r.slot; r.next();
    const uint32_t s2 = b != 2 ? tile : r.slot;
    h.po = b != 2 ? p0 : r.phase;
    r.next_if(b == 2);
    r.xp ^= 1 << b;
    h.x = WG ? s2 : s0; h.o = WG ? s0 : s2;
    mbar_wait3_w(f + s0 * 8, p0, f + h.w * 8, p1, f + (WG ? s2 : p.o) * 8, WG ? h.po : p.po);
    if (ks < 10) T2C(unit, ks * 4);
    if (DEEP) {
      proj_half<WG, false, 0>(c, a0, h.w, h.x, sw);
      release(c, WG ? h.o : p.o);
      if (ks < 10) T2C(unit, ks * 4 + 1);
      wg_wait<1>();
      if (ks < 10) T2C(unit, ks * 4 + 2);
      release(c, p.x); release(c, p.w);
    } else {
      release(c, WG ? h.o : p.o);
      wg_wait<0>();
      release(c, p.x); release(c, p.w);
      if (ks < 10) T2C(unit, ks * 4 + 1);
      proj_half<WG, false, 0>(c, a0, h.w, h.x, sw);
      if (ks < 10) T2C(unit, ks * 4 + 2);
    }
    proj_half<WG, false, 1>(c, a1, h.w, h.x, sw);
    if (ks < 10) T2C(unit, ks * 4 + 3);
    if (ks <= nq) o_second<WG>(c, item, ks, o1, inv);
  } while (++ks != n);
  {
    const uint32_t e0 = c.sb + BAR_EMPTY + (NS + 3 * WG) * 8, e1 = c.sb + BAR_EMPTY + (NS + 1 + WG) * 8;
    const uint32_t p0 = (r.xp ^ unit ^ 1) & 1, p1 = ((r.xp >> 1) ^ unit ^ 1) & 1;
    const uint32_t k0 = sw ? e0 : c.sb + BAR_FULL + r.slot * 8, pk = sw ? p0 : r.phase;
    uint32_t cnt = 0;
    while (!__all_sync(0xffffffffu, mbar_try(e0, p0) & mbar_try(e1, p1) & mbar_try(k0, pk) & (WG || mbar_try(c.sb + BAR_FULL + h.o * 8, h.po)))) {
      if (++cnt > (1u << 22)) __trap();
    }
  }
  c.lane = c.lane0 + (h.w >> 5);
  if (!WG) release(c, h.o);
}
template <int WG>
__device__ __forceinline__ void proj_end(const Ctx& c, float (&a1)[64], const Slots& h) {
  wg_wait<0>();
  acc_fence<WG>(a1);
  release(c, h.x); release(c, h.w);
}
__device__ __forceinline__ uint32_t get_desc(const Ctx& c, int i) {
  uint32_t d;
  mbar_wait_w(c.sb + BAR_DESC, (i - 1) & 1);
  asm volatile("ld.volatile.shared.u32 %0, [%1];" : "=r"(d) : "r"(c.sb + DESC_OFF + (i & 3) * 4) : "memory");
  return __shfl_sync(0xffffffffu, d, 0);
}

__device__ __forceinline__ float quad_max(float x) {
  x = fmaxf(x, __shfl_xor_sync(0xffffffffu, x, 1));
  return fmaxf(x, __shfl_xor_sync(0xffffffffu, x, 2));
}
__device__ __forceinline__ float quad_sum(float x) {
  x += __shfl_xor_sync(0xffffffffu, x, 1);
  return x + __shfl_xor_sync(0xffffffffu, x, 2);
}
template <bool SP, bool FIRST>
__device__ __forceinline__ void exps(const Ctx& c, const float (&s)[32], uint32_t (&p)[SP ? 8 : 16], RowSum& st) {
  if constexpr (SP) {
    uint32_t q[8];
    float t;
#pragma unroll
    for (int j = 0; j < 8; j++) {
      const float e0 = ex2(s[4 * j] + s[4 * j + 2]), e1 = ex2(s[4 * j + 1] + s[4 * j + 3]);
      if (j == 0) t = e0 + e1; else t += e0 + e1;
      q[j] = pack_bf16(e0, e1);
    }
    const bool odd = c.src & 2;
#pragma unroll
    for (int g = 0; g < 4; g++) {
      p[2 * g] = __shfl_sync(0xffffffffu, odd ? q[2 * g + 1] : q[2 * g], c.src);
      p[2 * g + 1] = __shfl_sync(0xffffffffu, odd ? q[2 * g] : q[2 * g + 1], c.src ^ 1);
    }
    st.l0 = FIRST ? t : st.l0 + t;
  } else {
    float t0, t1;
#pragma unroll
    for (int j = 0; j < 8; j++) {
      const float e0 = ex2(s[4 * j]), e1 = ex2(s[4 * j + 1]), e2 = ex2(s[4 * j + 2]), e3 = ex2(s[4 * j + 3]);
      if (j == 0) { t0 = e0 + e1; t1 = e2 + e3; } else { t0 += e0 + e1; t1 += e2 + e3; }
      p[2 * j] = pack_bf16(e0, e1);
      p[2 * j + 1] = pack_bf16(e2, e3);
    }
    st.l0 = FIRST ? t0 : st.l0 + t0;
    st.l1 = FIRST ? t1 : st.l1 + t1;
  }
}
template <bool SP>
__device__ __forceinline__ bool finish_sums(RowSum& st) {
  const float a = quad_sum(st.l0), b = SP ? a : quad_sum(st.l1);
  st.l0 = __fdividef(1.f, a); st.l1 = __fdividef(1.f, b);
  return !(a >= SUM_LO && a <= SUM_HI && b >= SUM_LO && b <= SUM_HI);
}
template <bool SP, bool INIT, int SITE, bool COMMIT = true, int RM = 0>
__device__ __forceinline__ void issue_qk(const Ctx& c, float (&s)[32], const uint32_t (&qs)[32], uint32_t dq, uint32_t dk) {
  uint64_t a = desc64(dq, dhi<SITE & 1>(dk)), b = desc64(dk, dhi<1 - (SITE & 1)>(dk) + 64);
  if (SP) {
    if (INIT) wgmma_qk_sp_init(s, qs[0], qs[1], qs[2], qs[3], b, 0, c.mqk); else wgmma_qk_sp(s, qs[0], qs[1], qs[2], qs[3], b, 0, c.mqk);
#pragma unroll
    for (int k = 1; k < 4; k++) { dadd(b, k == 2 ? 60 : 4); wgmma_qk_sp(s, qs[4 * k], qs[4 * k + 1], qs[4 * k + 2], qs[4 * k + 3], b, 1, c.mqk); }
  } else {
    if (RM & 1) wgmma_qk_rs(s, qs[0], qs[1], qs[2], qs[3], b, 0); else if (INIT) wgmma_qk_init(s, a, b, 0); else wgmma_qk(s, a, b, 0);
#pragma unroll
    for (int k = 1; k < 8; k++) {
      dadd(a, k == 4 ? 506 : 2); dadd(b, k == 4 ? 58 : 2);
      if (RM >> k & 1) wgmma_qk_rs(s, qs[4 * k], qs[4 * k + 1], qs[4 * k + 2], qs[4 * k + 3], b, 1); else wgmma_qk(s, a, b, 1);
    }
  }
  if (COMMIT) wg_commit();
}
template <bool SP, bool ACC, int SITE, bool SPLIT = false>
__device__ __forceinline__ void issue_pv(const Ctx& c, float (&o)[64], const uint32_t (&p)[SP ? 8 : 16], uint32_t dv) {
  uint64_t b = desc64(dv, dhi<SITE & 1>(dv) + 64);
  if constexpr (SP) {
    if (ACC) wgmma_pv_sp(o, p[0], p[1], p[2], p[3], b, 1, c.mpv); else wgmma_pv_sp_init(o, p[0], p[1], p[2], p[3], b, 0, c.mpv);
    if (SPLIT) wg_commit();
    dadd(b, 512);
    wgmma_pv_sp(o, p[4], p[5], p[6], p[7], b, 1, c.mpv);
  } else {
    if (ACC) wgmma_pv(o, p[0], p[1], p[2], p[3], b, 1); else wgmma_pv_init(o, p[0], p[1], p[2], p[3], b, 0);
#pragma unroll
    for (int k = 1; k < 4; k++) { dadd(b, 256); wgmma_pv(o, p[4 * k], p[4 * k + 1], p[4 * k + 2], p[4 * k + 3], b, 1); }
  }
  wg_commit();
}
__device__ __forceinline__ void pack_rows(const float (&o)[64], float sc, uint32_t (&q)[32]) {
#pragma unroll
  for (int j = 0; j < 32; j++) q[j] = pack_bf16(o[2 * j] * sc, o[2 * j + 1] * sc);
}
template <int MASK = 255>
__device__ __forceinline__ void stage_rows(const Ctx& c, uint32_t tile_addr, const uint32_t (&q)[32]) {
  const int lane = c.lane, mi = lane >> 3, r8 = lane & 7;
  const uint32_t row_addr = tile_addr + (16 * c.warp + (mi & 1) * 8 + r8) * 128;
#pragma unroll
  for (int jj = 0; jj < 8; jj++)
    if (MASK >> jj & 1) stsm4(row_addr + (jj >> 2) * 8192 + (((((2 * jj) & 7) + (mi >> 1)) ^ r8) << 4), q[4 * jj], q[4 * jj + 1], q[4 * jj + 2], q[4 * jj + 3]);
}
__device__ __forceinline__ void stage_rows(const Ctx& c, uint32_t tile_addr, const float (&o)[64], float sc) {
  uint32_t q[32];
  pack_rows(o, sc, q);
  stage_rows(c, tile_addr, q);
}
template <int WG, int H>
__device__ __forceinline__ void stage_out(const Ctx& c, const float (&a)[64]) {
  if (WG) { stage_t3<H, false>(c, a, 1.f); if (H) staged(c, 0); stage_t2<H>(c, a, 1.f); }
  else stage_rows(c, c.sb + QBUF_OFF + H * 16384, a, 1.f);
  if (H || !WG) staged(c, H);
}
template <int SITE>
__device__ __forceinline__ void issue_qk_rs(float (&s)[32], uint32_t (&q)[32], uint32_t dk) {
  uint64_t b = desc64(dk, dhi<SITE>(dk) + 64);
  reg_fence(q);
  wg_fence();
  wgmma_qk_rs_init(s, q[0], q[1], q[2], q[3], b, 0);
#pragma unroll
  for (int k = 1; k < 8; k++) { dadd(b, k == 4 ? 58 : 2); wgmma_qk_rs(s, q[4 * k], q[4 * k + 1], q[4 * k + 2], q[4 * k + 3], b, 1); }
  wg_commit();
}

__device__ __forceinline__ void redo_tile(const Ctx& c, uint32_t q_addr, uint32_t half, const __nv_bfloat16* kp, const __nv_bfloat16* vp,
                                          uint32_t item, int row) {
  float o[64];
  const int lane = lane_now(), g = lane >> 2, cc = lane & 3, mi = lane >> 3, r8 = lane & 7;
  const uint32_t qa = q_addr + (half == 4096 ? 8 * c.warp + r8 : 16 * c.warp + (mi & 1) * 8 + r8) * 128, swz = half == 4096 ? q3_swz(r8) : r8;
  const uint32_t* kq = reinterpret_cast<const uint32_t*>(kp + g * DH) + cc;
  const unsigned short* vq = reinterpret_cast<const unsigned short*>(vp + 2 * cc * DH) + g;
  float m0 = -INFINITY, m1 = -INFINITY, l0 = 0.f, l1 = 0.f;
#pragma unroll
  for (int i = 0; i < 64; i++) o[i] = 0.f;
#pragma unroll 1
  for (int kb = 0; kb < SK / 16; kb++) {
    float z[8] = {0.f, 0.f, 0.f, 0.f, 0.f, 0.f, 0.f, 0.f};
#pragma unroll 2
    for (int kk = 0; kk < 8; kk++) {
      uint32_t a0, a1, a2, a3;
      ldsm4(qa + (kk >> 2) * half + ((((kk & 3) * 2 + (mi >> 1)) ^ swz) << 4), a0, a1, a2, a3);
      const uint32_t* kr = kq + kb * (16 * DH / 2) + kk * 8;
      mma16816(z[0], z[1], z[2], z[3], a0, a1, a2, a3, __ldg(kr), __ldg(kr + 4));
      mma16816(z[4], z[5], z[6], z[7], a0, a1, a2, a3, __ldg(kr + 8 * DH / 2), __ldg(kr + 8 * DH / 2 + 4));
    }
    const float n0 = fmaxf(m0, quad_max(fmaxf(fmaxf(z[0], z[1]), fmaxf(z[4], z[5]))));
    const float n1 = fmaxf(m1, quad_max(fmaxf(fmaxf(z[2], z[3]), fmaxf(z[6], z[7]))));
    const float al0 = ex2(m0 - n0), al1 = ex2(m1 - n1);
    m0 = n0; m1 = n1;
#pragma unroll
    for (int i = 0; i < 8; i++) z[i] = ex2(z[i] - ((i & 2) ? n1 : n0));
    l0 = l0 * al0 + (z[0] + z[1]) + (z[4] + z[5]);
    l1 = l1 * al1 + (z[2] + z[3]) + (z[6] + z[7]);
    const uint32_t a0 = pack_bf16(z[0], z[1]), a1 = pack_bf16(z[2], z[3]), a2 = pack_bf16(z[4], z[5]), a3 = pack_bf16(z[6], z[7]);
    const unsigned short* vr = vq + kb * (16 * DH);
#pragma unroll
    for (int nb = 0; nb < 16; nb++) {
      o[4 * nb] *= al0; o[4 * nb + 1] *= al0; o[4 * nb + 2] *= al1; o[4 * nb + 3] *= al1;
      const uint32_t b0 = __ldg(vr + nb * 8) | ((uint32_t)__ldg(vr + nb * 8 + DH) << 16);
      const uint32_t b1 = __ldg(vr + nb * 8 + 8 * DH) | ((uint32_t)__ldg(vr + nb * 8 + 9 * DH) << 16);
      mma16816(o[4 * nb], o[4 * nb + 1], o[4 * nb + 2], o[4 * nb + 3], a0, a1, a2, a3, b0, b1);
    }
  }
  const char* p = o_addr(item, row, lane);
  o_emit<0>(p, o, __fdividef(1.f, quad_sum(l0)));
  o_emit<1>(half == 4096 ? p : p + 1024, o, __fdividef(1.f, quad_sum(l1)));
}

template <bool SPA, bool SPB, int SITE, int ID>
__device__ __forceinline__ void batch(const Ctx& c, float (&s)[32], const uint32_t (&qs)[32], uint32_t dq, uint32_t dk, float (&ob)[64],
                                      uint32_t (&pb)[SPB ? 8 : 16], uint32_t dv) {
  if constexpr (SPA) {
    reg_fence(pb);
    wg_fence();
    issue_pv<SPB, true, ID>(c, ob, pb, dv);
    issue_qk<SPA, false, ID>(c, s, qs, dq, dk);
  } else {
    constexpr bool EARLY = ((QK_EARLY_MASK >> (SITE + (SPB ? 2 : 0))) & 1) != 0;
    if (!EARLY) reg_fence(pb);
    wg_fence();
    issue_qk<SPA, false, ID, !SPB, SITE ? RM0 : SPB ? RM2 : RM1>(c, s, qs, dq, dk);
    if (EARLY) { reg_fence(pb); wg_fence(); }
    issue_pv<SPB, true, ID, SPB>(c, ob, pb, dv);
  }
}

template <bool SP0>
__device__ __forceinline__ bool attention(Ctx& c, Ring& r, int unit, uint32_t& d, const float (&a0)[64], float (&o0)[64], float (&o1)[64],
                                          RowSum& st0, RowSum& st1, const Slots& h, uint32_t (&q1)[32]) {
  constexpr bool SP1 = false;
  if (SP0) { c.mqk = META_QK + (d >> 28); c.mpv = META_PV + (d >> 28); asm volatile("" : "+r"(c.mqk), "+r"(c.mpv)); }
  if (SP0) c.src = (c.lane & 28) | ((c.lane & 1) << 1) | ((c.lane >> 1) & 1);
  float s[32];
  uint32_t p0[SP0 ? 8 : 16], p1[16];
  const uint32_t q0a = c.sb + QBUF_OFF + (SP0 ? 3 : 0) * 16384, q1a = c.sb + QBUF_OFF + (SP0 ? 2 : 1) * 16384;
  const uint32_t dq0 = sdesc(SB0 + QBUF_OFF, 0), dq1 = sdesc(SB0 + QBUF_OFF + (SP0 ? 2 : 1) * 16384, 0);
  uint32_t sk = acquire(c, r, true), sv, sn;
  uint32_t qs[32];
  float s1[32];
  if (SP0) {
    stage_t3<0, true>(c, a0, SM_C);
    stage_t2<0>(c, a0, SM_C);
    proj_end<1>(c, o0, h);
    stage_t3<1, true>(c, o0, SM_C);
    stage_t2<1>(c, o0, SM_C);
    bar_sync(5, 128);
    const int g = c.lane >> 2, cc = c.lane & 3;
    const uint32_t qa = q0a + (8 * c.warp + g) * 128 + (cc & 1) * 8;
#pragma unroll
    for (int k = 0; k < 8; k++)
      asm volatile("ld.shared.v2.u32 {%0, %1}, [%2];" : "=r"(qs[2 * k]), "=r"(qs[2 * k + 1])
                   : "r"(qa + (k >> 2) * 4096 + ((((k & 3) * 2 + (cc >> 1)) ^ q3_swz(g)) << 4)) : "memory");
    fence_async_smem();
    bar_sync(1, 256);
    TRACE(unit, 2);
    wg_fence();
    issue_qk<SP1, true, 1>(c, s1, qs, dq1, sdesc(SB0 + sk * SLOT, 0));
#pragma unroll
    for (int k = 0; k < 8; k++)
      if (RM2 >> k & 1) ldsm4(q1a + (k >> 2) * 8192 + (16 * c.warp + (c.lane & 15)) * 128 + (((2 * (k & 3) + (c.lane >> 4)) ^ (c.lane & 7)) << 4),
                              q1[4 * k], q1[4 * k + 1], q1[4 * k + 2], q1[4 * k + 3]);
#pragma unroll
    for (int k = 0; k < 16; k++) asm volatile("" : "+r"(qs[k])::"memory");
    wg_fence();
    issue_qk<SP0, true, 0>(c, s, qs, dq0, sdesc(SB0 + sk * SLOT, 0));
    const bool have = peek<2>(c, r);
    wg_wait<1>();
    reg_fence(s1);
    exps<SP1, true>(c, s1, p1, st1);
    sched_fence<11>(sk, p1);
    acquire2(c, r, sv, sn, __all_sync(0xffffffffu, have));
    wg_wait<0>();
    wg_fence();
    issue_pv<SP1, false, 1>(c, o1, p1, sdesc(SB0 + sv * SLOT, 1024));
    if (LAG_BAR & 1) asm volatile("bar.arrive 4, 256;" ::: "memory");
    sched_fence<12>(sk, s);
    release(c, sk);
    sk = sn;
    exps<SP0, true>(c, s, p0, st0);
    reg_fence(p0);
    wg_fence();
    issue_pv<SP0, false, 0>(c, o0, p0, sdesc(SB0 + sv * SLOT, 1024));
    issue_qk<SP0, true, 2>(c, s, qs, dq0, sdesc(SB0 + sk * SLOT, 0));
    sn = acquire(c, r);
    wg_wait<0>();
    reg_fence(s);
  } else {
    pack_rows(a0, SM_C, qs);
    stage_rows(c, q0a, qs);
    proj_end<0>(c, o1, h);
    TRACE(unit, 2);
    float sc = SM_C;
    issue_qk_rs<0>(s, qs, sdesc(SB0 + sk * SLOT, 0));
    sched_fence<0>(sk, sc);
    pack_rows(o1, sc, q1);
    stage_rows<~RM1>(c, q1a, q1);
    issue_qk_rs<1>(s1, q1, sdesc(SB0 + sk * SLOT, 0));
    asm volatile("bar.arrive 1, 256;" ::: "memory");
    bool have = peek<2>(c, r);
    wg_wait<1>();
    reg_fence(s);
    exps<SP0, true>(c, s, p0, st0);
    sched_fence<1>(sk, p0);
    acquire2(c, r, sv, sn, __all_sync(0xffffffffu, have));
    wg_wait<0>();
    reg_fence(s1);
    fence_async_smem();
    __syncwarp();
    wg_fence();
    issue_qk<SP0, false, 2, true, RM0>(c, s, qs, dq0, sdesc(SB0 + sn * SLOT, 0));
    issue_pv<SP0, false, 0>(c, o0, p0, sdesc(SB0 + sv * SLOT, 1024));
    sched_fence<2>(sk, s1);
    release(c, sk);
    have = peek<1>(c, r);
    sk = sn;
    exps<SP1, true>(c, s1, p1, st1);
    reg_fence(p1);
    wg_fence();
    issue_pv<SP1, false, 1>(c, o1, p1, sdesc(SB0 + sv * SLOT, 1024));
    sn = acquire(c, r, __all_sync(0xffffffffu, have));
    if (LAG_BAR & 1) bar_sync(4, 256);
    wg_wait<1>();
    reg_fence(s);
  }
  TRACE_IN(unit, 4);
  T2C(unit, 51);
#pragma unroll 1
  for (int j = 1; j < 15; j++) {
    const uint32_t sv_prev = sv, sk_prev = sk;
    sv = sn;
    const uint32_t dv = sdesc(SB0 + sv * SLOT, 1024);
    reg_fence(p0);
    exps<SP0, false>(c, s, p0, st0);
    batch<SP1, SP0, 0, 3>(c, s, q1, dq1, sdesc(SB0 + sk * SLOT, 0), o0, p0, dv);
    sk = acquire(c, r);
    wg_wait<1>();
    reg_fence(s); reg_fence(p1);
    release(c, sv_prev); release(c, sk_prev);
    exps<SP1, false>(c, s, p1, st1);
    batch<SP0, SP1, 1, 4>(c, s, qs, dq0, sdesc(SB0 + sk * SLOT, 0), o1, p1, dv);
    sn = acquire(c, r);
    if (SP0) wg_wait<0>(); else wg_wait<1>();
    reg_fence(s);
  }
  TRACE_IN(unit, 5);
  T2C(unit + 1, 52);
  const uint32_t sv_prev = sv;
  sv = sn;
  const uint32_t dv = sdesc(SB0 + sv * SLOT, 1024);
  reg_fence(p0);
  exps<SP0, false>(c, s, p0, st0);
  batch<SP1, SP0, 0, 5>(c, s, q1, dq1, sdesc(SB0 + sk * SLOT, 0), o0, p0, dv);
  asm volatile("ld.volatile.shared.u32 %0, [%1];" : "=r"(d) : "r"(c.sb + DESC_OFF + ((unit + 1) & 3) * 4) : "memory");
  const bool have = peek<2 + SP0>(c, r);
  wg_wait<1>();
  reg_fence(s); reg_fence(p1);
  release(c, sv_prev); release(c, sk);
  exps<SP1, false>(c, s, p1, st1);
  reg_fence(p1);
  wg_fence();
  issue_pv<SP1, true, 2>(c, o1, p1, dv);
  if (SP0) sched_fence<6>(sk, st0.l0, st1.l0, st1.l1); else sched_fence<5>(sk, st0.l0, st0.l1, st1.l0, st1.l1);
  c.lane = c.lane0 + (sk >> 5);
  const bool bad = finish_sums<SP0>(st0) | finish_sums<SP1>(st1);
  uint32_t any;
  asm volatile("{\n.reg .pred p, q;\nsetp.ne.u32 p, %1, 0;\nbar.red.or.pred q, %2, 128, p;\nselp.u32 %0, 1, 0, q;\n}"
               : "=r"(any) : "r"((uint32_t)bad), "n"(2 + SP0) : "memory");
  any = __any_sync(0xffffffffu, any);
  d = __shfl_sync(0xffffffffu, d, 0);
  if (d < (2u << 30) && !__all_sync(0xffffffffu, have)) { Ring t = r; Slots u; begin_acquire<SP0>(c, t, u, true); }
  wg_wait<0>();
  reg_fence(o0); reg_fence(o1);
  release(c, sv);
  return any;
}

template <int WG>
__device__ __forceinline__ void consumer(Ctx c, const __nv_bfloat16* const* kv) {
  asm volatile("setmaxnreg.inc.sync.aligned.u32 %0;" ::"n"(WG ? REG_C : 504 - REG_C - REG_P));
  c.wg = WG;
  Ring r{0, 0, 0};
  float a0[64], a1[64], o1[64];
  Slots h;
  RowSum inv0, inv1;
  uint32_t oq[32];
  uint32_t d = c_sched.queue[blockIdx.x] * 1025, dc = 0, sw;
  int i = 0, nq;
begin:
  sw = d & (1u << 30);
  proj_begin<WG>(c, r, a0, h, true, sw);
  proj_half<WG, true, 1>(c, a1, h.w, h.x, sw);
  nq = 0;
#pragma unroll
  for (int k = 0; k < 64; k++) asm volatile("" : "=f"(o1[k]));
  asm volatile("" : "=f"(inv1.l0), "=f"(inv1.l1));
  while (true) {
    TRACE(i, 0); TRACE(i, 6);
    proj_main<WG>(c, r, a0, a1, h, d >> 30 ? ((d >> 16) & 63) + 1 : DM / 64, sw, i, dc, nq, o1, inv1);
    dc = d;
    TRACE(i, 1);
    if (d >> 30) goto out_tile;
    wg_wait<1>();
    acc_fence<WG>(a0);
    if (WG ? attention<WG>(c, r, i, d, a0, a1, o1, inv0, inv1, h, oq) : attention<WG>(c, r, i, d, a0, o1, a1, inv1, inv0, h, oq)) goto redo;
    if (d >= (2u << 30)) break;
    sw = d & (1u << 30);
    proj_begin<WG>(c, r, a0, h, false, sw);
    release_q<WG>(c);
    if (WG) sched_fence<8>(h.w, inv0.l0); else sched_fence<7>(h.w, inv0.l0, inv0.l1);
    o_first<WG>(c, dc, a1, inv0, oq);
    sched_fence<9>(h.w, inv1.l0);
    proj_half<WG, true, 1>(c, a1, h.w, h.x, sw);
    o_rest<WG>(c, dc, oq);
    nq = O_STEPS;
    TRACE(i, 3); TRACE(i, 7);
    i++;
  }
  release_q<WG>(c);
  o_first<WG>(c, dc, a1, inv0, oq);
  o_rest<WG>(c, dc, oq);
#pragma unroll
  for (int k = 1; k <= O_STEPS; k++) o_second<WG>(c, dc, k, o1, inv1);
next:
  TRACE(i, 3); TRACE(i, 7);
  if ((d >> 30) != 2) {
    i++;
    r.uniform();
    goto begin;
  }
  trace_dump(c);
  return;
out_tile:
  if (d & 96) goto finish;
  d = get_desc(c, i + 1);
  wg_wait<1>();
  acc_fence<WG>(a0);
  TRACE_O(0);
  stage_out<WG, 0>(c, a0);
  TRACE_O(1);
  proj_end<WG>(c, a1, h);
  TRACE_O(2);
  stage_out<WG, 1>(c, a1);
  TRACE(i, 2);
  goto next;
finish:
  {
    uint32_t q[32];
#pragma unroll 1
    for (int k = (d >> 5) & 3; k > 1; k--) {
      wg_wait<0>();
      acc_fence<WG>(a0); acc_fence<WG>(a1);
      if (k == ((d >> 5) & 3)) { release(c, h.x); release(c, h.w); }
      load_part<WG, 0>(c, r, q); add_part<WG>(c, q, a0);
      load_part<WG, 1, 0>(c, r, q); add_part<WG>(c, q, a1);
#pragma unroll
      for (int t = 0; t < 4; t++) { release(c, r.slot); r.next(); }
    }
    load_part<WG, 0, WG ? 4 : 1>(c, r, q);
    wg_wait<1>();
    acc_fence<WG>(a0);
    TRACE_O(0);
    add_part<WG>(c, q, a0);
    stage_out<WG, 0>(c, a0);
    TRACE_O(1);
    load_part<WG, 1, WG ? 0 : 2>(c, r, q);
    wg_wait<0>();
    acc_fence<WG>(a1);
    TRACE_O(2);
    add_part<WG>(c, q, a1);
    stage_out<WG, 1>(c, a1);
    TRACE(i, 2); TRACE(i, 3); TRACE(i, 7);
    trace_dump(c);
    return;
  }
redo:
  {
    if (!WG) { stage_rows<RM1>(c, c.sb + QBUF_OFF + 16384, oq); __syncwarp(); }
    const size_t hoff = (size_t)(dc & 511) * (SK * DH);
    const int br = (dc >> 9) & 1;
#pragma unroll 1
    for (int part = 0; part < 2; part++) {
      const int t = WG ? 3 - part : part;
      redo_tile(c, c.sb + QBUF_OFF + t * 16384, t == 3 ? 4096 : 8192, kv[br] + hoff, kv[2 + br] + hoff, dc,
                t * 64 + (t == 3 ? 8 : 16) * c.warp);
    }
    o_done(c);
    release_q<WG>(c);
  }
  goto next;
}

template <bool SIMPLE>
__global__ void __launch_bounds__(384, 1) mha_fused_kernel(const __grid_constant__ Params P) {
  extern __shared__ __align__(1024) uint8_t smem_raw[];
  const uint32_t sbase = smem_u32(smem_raw);
  const int tid = threadIdx.x;
  const int wg = __shfl_sync(0xffffffffu, tid >> 7, 0);
  const int warp = __shfl_sync(0xffffffffu, (tid >> 5) & 3, 0);
  const int lane = tid & 31;
  const int cta = blockIdx.x;
  constexpr bool PAIR = !SIMPLE;

  if (tid == 0) T3(15, 0);
  if ((sbase & 0xffffff) != SB0) __trap();
  {
    const int wi = wg * 4 + warp;
    asm volatile(ELECT "prefetch.tensormap [%0];\n}" ::"l"(&P.x[0][0] + wi) : "memory");
#pragma unroll
    for (int k = 0; k < 5; k++) {
      const int b = min(BAR_OFF + (wi * 5 + k) * 8, DESC_OFF - 8);
      asm volatile(ELECT "mbarrier.init.shared::cta.b64 [%0], %1;\n}"
                   ::"r"(sbase + b), "r"(b < BAR_EMPTY || b >= BAR_DESC ? 1 : b >= BAR_STG && b < BAR_OUT ? 4 : 8) : "memory");
    }
    asm volatile("fence.mbarrier_init.release.cluster;" ::: "memory");
    if (wi < 6) asm volatile(ELECT "prefetch.tensormap [%0];\n}" ::"l"(&P.x[0][0] + 12 + wi) : "memory");
  }
  if (PAIR) asm volatile("barrier.cluster.arrive.aligned;\nbarrier.cluster.wait.aligned;" ::: "memory"); else __syncthreads();

  if (wg == 2) {
    asm volatile("setmaxnreg.dec.sync.aligned.u32 %0;" ::"n"(REG_P));
    if (warp == 1) {
      const uint32_t qb = sbase + QBUF_OFF;
      const uint32_t ep = __shfl_sync(0xffffffffu, *(volatile unsigned*)&g_epoch + 1, 0);
      asm volatile("st.volatile.shared.u32 [%0], %1;" ::"r"(sbase + EPOCH_OFF), "r"(ep) : "memory");
      uint32_t dc = c_sched.queue[cta], qi = 0, piece = 0, na = 0;
      TTAIL(0);
      for (int i = 0; (dc >> 30) != 2; i++) {
        if (!(dc >> 30) && o_reuse<SIMPLE>((dc >> 5) & 31)) {
          const unsigned* rd = &g_rd[0][0] + ((dc & 1023) >> 2) - OR * 8;
          for (uint32_t n = 0; !__all_sync(0xffffffffu, reached(rd, ep * 5)); __nanosleep(300)) if (++n > (1u << 22)) __trap();
        }
        mbar_wait_w(sbase + BAR_GO, i & 1);
        if (piece == 0) {
          if (PAIR && (cta & 1)) {
            asm volatile(ELECT EXPECT("%0", "4") "mbarrier.arrive.shared::cluster.b64 _, [%1];\n}" ::"r"(sbase + BAR_MAIL), "r"(peer(sbase + BAR_MAIL)) : "memory");
            mbar_wait_w(sbase + BAR_MAIL, i & 1);
            qi = lds(sbase + EPOCH_OFF + 8);
          } else if (lane == 0) {
            qi = atomicAdd(&g_next, PAIR ? 2 : 1);
            if (qi == (SIMPLE ? Q_ALL : Q_RANGES) - (PAIR ? 2 : 1)) { g_next = 0; g_epoch = ep; }
          }
          qi = __shfl_sync(0xffffffffu, qi, 0);
          if (PAIR && !(cta & 1)) {
            mbar_wait_w(sbase + BAR_MAIL, i & 1);
            asm volatile(ELECT "st.async.shared::cluster.mbarrier::complete_tx::bytes.u32 [%0], %1, [%2];\n}"
                         ::"r"(peer(sbase + EPOCH_OFF + 8)), "r"(qi + 1), "r"(peer(sbase + BAR_MAIL)) : "memory");
          }
          qi += SIMPLE ? gridDim.x : NCTA;
        }
        uint32_t d;
        if (qi < (SIMPLE ? Q_ALL : Q_RANGES)) { d = c_sched.queue[qi]; if (d & 0x8000) d ^= (1u << 30) | (63u << 16) | 0x8000; else d |= o_slot<SIMPLE>(d >> 5) << 15 | (d & 31) << 10; }
        else if (SIMPLE) d = 2u << 30;
        else { const uint32_t e = qi - Q_RANGES, g = e / 5; d = c_sched.piece[g][piece++] | (g & 1 ? g * 5 + 4 - e : e - g * 5) << 8; }
        if ((d >> 30) == 1) {
          const uint32_t k0 = (d >> 22) & 63;
          const uint32_t run = __ffs(__ballot_sync(0xffffffffu, !reached(&g_cnt[d & 31][lane & 7], ep * 4)) & (0xffu << (k0 >> 3))) - 1;
          if (run <= (k0 + ((d >> 16) & 63)) >> 3) d |= run <= (k0 + O_STEPS) >> 3 ? (2u << 30) | 128 : 128;
        }
        asm volatile("st.volatile.shared.u32 [%0], %1;" ::"r"(sbase + DESC_OFF + ((i + 1) & 3) * 4), "r"(d) : "memory");
        __syncwarp();
        mbar_arrive_warp(sbase + BAR_DESC);
        const Work w = decode(dc);
        dc = d;
        if (w.kind == 0) {
          mbar_wait_w(sbase + BAR_OUT, na++ & 1);
          TTAIL(1);
          T3(i, 0); T3(i, 1);
          asm volatile(ELECT "red.release.gpu.global.add.u32 [%0], 1;\n}" ::"l"(&g_cnt[w.beta][w.sub >> 2]) : "memory");
          T3(i, 2);
          TTAIL(2);
          continue;
        }
        const bool fin = w.mode != 1;
        const CUtensorMap* m = fin ? P.out_st : P.o_st;
        const int c1 = fin ? (w.beta & 15) * SQ : 0;
        const int c2 = fin ? (w.beta >> 4) * (DM / 64) + w.sub * 2 : NBETA * 64 + w.range * 2;
        uint32_t pend = 0;
#pragma unroll 1
        for (int e = 0; e < 4; e++) {
          const int t = (ST_ORDER >> (4 * e)) & 3;
          mbar_wait_w(sbase + BAR_STG + (t ^ (t >> 1)) * 8, (i - na) & 1);
          tma_st3_w(m + (t == 3), qb + t * 16384, c1 + t * 64, c2);
          bulk_commit();
          T2P(i + 1, 5, 2 * e);
          if (e == 3 && w.mode == 1 && (d >> 30) == 2) {
            asm volatile("cp.async.bulk.wait_group 2;" ::: "memory");
            asm volatile(ELECT "st.release.gpu.global.u32 [%0], %1;\n}" ::"l"(&g_flag[w.range]), "r"(2 * ep - 1) : "memory");
          }
          if (pend && (d >> 30) != 2) {
            bulk_wait_read<1>();
            mbar_arrive8_w(pend);
            T2P(i + 1, 5, 2 * e - 1);
          }
          pend = sbase + BAR_EMPTY + (NS + t) * 8;
          if ((ST_NOW >> e) & 1) {
            bulk_wait_read<0>();
            mbar_arrive8_w(pend);
            pend = 0;
            T2P(i + 1, 5, 2 * e + 1);
          }
        }
        if (w.beta < N_EARLY) asm volatile(ELECT "red.relaxed.gpu.global.add.u32 [%0], 1;\n}" ::"l"(&g_rd[w.beta][7]) : "memory");
        T3(i, 0);
        if (piece >= 2) TTAIL(piece * 2 - 1);
        asm volatile("cp.async.bulk.wait_group 0;" ::: "memory");
        T3(i, 1);
        if (w.mode == 1) asm volatile(ELECT "st.release.gpu.global.u32 [%0], %1;\n}" ::"l"(&g_flag[w.range]), "r"(2 * ep) : "memory");
        T3(i, 2);
        if (piece >= 2) TTAIL(piece * 2);
      }
      T3(15, 1);
    } else
    if (warp == 0) {
      Ring r{0, 1, 3};
      uint32_t d = c_sched.queue[cta];
      for (int i = 0;; i++) {
        const Work w = decode(d);
        if (w.kind == 2) break;
        const CUtensorMap* m = w.kind == 0 ? &P.wq[w.beta >> 4] : &P.wo[w.beta >> 4];
        for (int ks = 0; ks < w.nsteps; ks++) {
          const uint32_t b = borrow(ks, w.nsteps);
          r.next_if(b == 2);
          const uint32_t bar = sbase + BAR_FULL + r.slot * 8;
          mbar_wait_w(bar + (BAR_EMPTY - BAR_FULL), r.phase);
          if (w.kind == 0) tma_ld3_w(sbase + r.slot * SLOT, m, 0, ks * 64, w.sub * 2, bar, 16384);
          else tma_ld_wo_w(sbase + r.slot * SLOT, m, w.sub * 128, (w.k0 + ks) * 2, bar);
          if (w.kind != 0 && w.beta < N_EARLY && (ks & 7) == 5 && ks > 5)
            asm volatile(ELECT "red.relaxed.gpu.global.add.u32 [%0], 1;\n}" ::"l"(&g_rd[w.beta][(ks >> 3) - 1]) : "memory");
          if (ks < 10) T2P(i, 2, ks);
          if (w.kind != 0 && ks == max(w.nsteps - GO_P, 4)) mbar_arrive_warp(sbase + BAR_GO);
          r.next(); r.next_if(b == 2);
        }
        if (w.kind == 0) {
          r.phase ^= 1; r.next(); r.next();
        } else if (w.mode == 2) {
          for (int k = 1; k <= ((d >> 5) & 3); k++) {
            if (k == 1) TTAIL(9);
            bool all = false;
#pragma unroll 1
            for (int t = 0; t < 4; t++) {
              if (!(t & 1) && !all) {
                const uint32_t ep2 = 2 * lds(sbase + EPOCH_OFF);
                uint32_t v, n = 0;
                do {
                  asm volatile("ld.acquire.gpu.global.u32 %0, [%1];" : "=r"(v) : "l"(&g_flag[w.range + 5 * k]) : "memory");
                  v = __shfl_sync(0xffffffffu, v - ep2, 0);
                  if (++n > (1u << 24)) __trap();
                } while ((int)v < (t >> 1) - 1);
                all = v == 0;
                TTAIL(10);
                asm volatile("fence.proxy.async.global;" ::: "memory");
              }
              mbar_wait_w(sbase + BAR_EMPTY + r.slot * 8, r.phase);
              tma_ld3_w(sbase + r.slot * SLOT, &P.o_st[t == 3], 0, t * 64, NBETA * 64 + (w.range + 5 * k) * 2, sbase + BAR_FULL + r.slot * 8,
                        t == 3 ? 8192 : 16384);
              r.next();
            }
          }
        }
        mbar_wait_w(sbase + BAR_DESC, i & 1);
        d = __shfl_sync(0xffffffffu, lds(sbase + DESC_OFF + ((i + 1) & 3) * 4), 0);
      }
    } else {
      const int hi = warp - 2;
      uint64_t pol_stream;
      uint32_t rdy = 0;
      asm volatile("createpolicy.fractional.L2::evict_first.b64 %0, 1.0;" : "=l"(pol_stream));
      Ring r{0, 1, 3};
      uint32_t d = c_sched.queue[cta];
      for (int i = 0;; i++) {
        const Work w = decode(d);
        if (w.kind == 2) break;
        const CUtensorMap* m = w.kind == 0 ? &P.x[hi][w.beta >> 4] : &P.o_ld[hi];
        int c1 = (w.kind == 0 ? (w.beta & 15) : o_slot<SIMPLE>(w.beta) * 64 + w.k0) * SQ + hi * 128;
        int k_wait = -1;
        const bool both = PAIR && (w.kind == 0 || w.sub != 4), mine = !both || hi == (cta & 1);
        if (w.kind != 0 && mine) {
          if (d & 128) k_wait = d >= (3u << 30) ? 0 : 8 - (w.k0 & 7);
          asm volatile("fence.proxy.async.global;" ::: "memory");
        }
        for (int ks = 0; ks < w.nsteps; ks++) {
          if (ks == k_wait) {
            wait_count(&g_cnt[d & 31][(w.k0 + ks) >> 3], lds(sbase + EPOCH_OFF) * 4);
            asm volatile("fence.proxy.async.global;" ::: "memory");
            k_wait = ((w.k0 + ks) | 7) + 1 - w.k0;
          }
          const uint32_t b = borrow(ks, w.nsteps);
          const bool bo = b != 2;
          r.next_if(hi && !bo); r.next_if(hi && !bo);
          const uint32_t sl = bo ? NS + (b ^ (3 * hi)) : r.slot, bar = sbase + BAR_FULL + sl * 8;
          mbar_wait_w(bar + (BAR_EMPTY - BAR_FULL), bo ? (r.xp >> b) & 1 : r.phase);
          const uint32_t bytes = hi ? 96 * 128 : 128 * 128;
          if (!mine) {
            asm volatile(ELECT EXPECT("%0", "%2") "mbarrier.arrive.shared::cluster.b64 _, [%1];\n}"
                         ::"r"(bar), "r"(peer(bar + (BAR_RDY - BAR_FULL))), "r"(bytes) : "memory");
          } else if (both) {
            mbar_wait_w(bar + (BAR_RDY - BAR_FULL), (rdy >> sl) & 1);
            rdy ^= 1 << sl;
            if (w.kind == 0) tma_ld2_both_w(sbase + sl * SLOT, m, ks * 64, c1, bar, bytes);
            else tma_ld2_both_hint_w(sbase + sl * SLOT, m, 0, c1, bar, bytes, pol_stream);
          } else if (!PAIR && w.kind == 0) tma_ld2_w(sbase + sl * SLOT, m, ks * 64, c1, bar, bytes);
          else tma_ld2_hint_w(sbase + sl * SLOT, m, 0, c1, bar, bytes, pol_stream);
          if (w.kind != 0) c1 += SQ;
          if (i == 0 && ks == PF_STEP)
            asm volatile(ELECT "cp.async.bulk.prefetch.tensor.4d.L2.global.L2::cache_hint [%0, {0, 0, 0, %1}], %2;\n}"
                         ::"l"(&P.kv[hi][0]), "r"(d * (SK / 8)), "l"(pol_stream) : "memory");
          if (ks < 10) T2P(i, 3 + hi, ks);
          if (!hi && w.kind != 0 && !(ks & 3)) TCLK(i * 16 + (ks >> 2));
          r.next(); r.next_if(!hi && !bo); r.next_if(!hi && !bo);
          r.xp ^= 1 << b;
        }
        r.xp ^= 3;
        if (w.kind == 0) {
          m = &P.kv[hi][w.beta >> 4];
          c1 = (d & 511) * (SK / 8);
          for (int j = 0; j < 16; j++) {
            if (hi) r.next();
            const uint32_t bar = sbase + BAR_FULL + r.slot * 8;
            const bool tight = i == 0 && j < KV_WIN_TILES + ((KV_WIN_RAMP * cta) >> 5);
            {
              const int s2 = (int)r.slot - (tight ? 2 : KV_WIN_D);
              mbar_wait_w(sbase + BAR_FULL + (s2 < 0 ? s2 + NS : s2) * 8, s2 < 0 ? r.phase : r.phase ^ 1);
            }
            if (j == 15 && hi) mbar_wait_w(sbase + BAR_DESC, i & 1);
            mbar_wait_w(sbase + BAR_EMPTY + r.slot * 8, r.phase);
            tma_ld_kv_w(sbase + r.slot * SLOT, m, c1, bar, pol_stream);
            T2P(i, 3 + hi, 16 + j);
            if (!hi) TCLK(i * 16 + j);
            if (j == GO_J && !hi) mbar_arrive_warp(sbase + BAR_GO);
            c1 += 8;
            r.next();
            if (!hi) r.next();
          }
        }
        mbar_wait_w(sbase + BAR_DESC, i & 1);
        d = __shfl_sync(0xffffffffu, lds(sbase + DESC_OFF + ((i + 1) & 3) * 4), 0);
      }
    }
  } else {
    Ctx c;
    c.sb = sbase; c.wg = wg; c.warp = warp; c.src = 0; c.mqk = 0; c.mpv = 0; c.lead = lane == 0; c.lane0 = c.lane = lane;
    if (wg == 0) consumer<0>(c, P.kp); else consumer<1>(c, P.kp);
  }
}

typedef CUresult (*EncodeFn)(CUtensorMap*, CUtensorMapDataType, cuuint32_t, void*, const cuuint64_t*, const cuuint64_t*,
                             const cuuint32_t*, const cuuint32_t*, CUtensorMapInterleave, CUtensorMapSwizzle,
                             CUtensorMapL2promotion, CUtensorMapFloatOOBfill);

void make_map(EncodeFn enc, CUtensorMap* m, const void* ptr, int rank, const cuuint64_t* dims, const cuuint64_t* strides,
              const cuuint32_t* box, CUtensorMapSwizzle swz = CU_TENSOR_MAP_SWIZZLE_128B) {
  cuuint32_t es[5] = {1, 1, 1, 1, 1};
  enc(m, CU_TENSOR_MAP_DATA_TYPE_BFLOAT16, rank, const_cast<void*>(ptr), dims, strides, box, es,
      CU_TENSOR_MAP_INTERLEAVE_NONE, swz, CU_TENSOR_MAP_L2_PROMOTION_NONE,
      CU_TENSOR_MAP_FLOAT_OOB_FILL_NONE);
}

}

extern "C" void kernel_launch(void* const* d_in, const int* in_sizes, int n_in, void* d_out, int out_size) {
  (void)in_sizes; (void)n_in; (void)out_size;
  static EncodeFn enc = nullptr;
  static void* o_ptr = nullptr;
  static int n_sm = 0;
  cudaLaunchAttribute at;
  at.id = cudaLaunchAttributeClusterDimension;
  at.val.clusterDim.x = 2; at.val.clusterDim.y = 1; at.val.clusterDim.z = 1;
  cudaLaunchConfig_t cfg = {};
  cfg.gridDim = dim3(NCTA); cfg.blockDim = dim3(384); cfg.dynamicSmemBytes = SMEM_BYTES; cfg.attrs = &at; cfg.numAttrs = 1;
  if (!enc) {
    void* fn = nullptr;
    cudaDriverEntryPointQueryResult qr;
    cudaGetDriverEntryPoint("cuTensorMapEncodeTiled", &fn, cudaEnableDefault, &qr);
    enc = (EncodeFn)fn;
    cudaGetSymbolAddress(&o_ptr, g_o);
    cudaFuncSetAttribute(mha_fused_kernel<false>, cudaFuncAttributeMaxDynamicSharedMemorySize, SMEM_BYTES);
    cudaFuncSetAttribute(mha_fused_kernel<true>, cudaFuncAttributeMaxDynamicSharedMemorySize, SMEM_BYTES);
    int dev = 0;
    cudaGetDevice(&dev);
    cudaDeviceGetAttribute(&n_sm, cudaDevAttrMultiProcessorCount, dev);
    int n_cl = 0;
    cudaOccupancyMaxActiveClusters(&n_cl, mha_fused_kernel<false>, &cfg);
    if (n_cl * 2 < NCTA && n_sm >= NCTA) n_sm = NCTA - 1;
  }
  Params P;
  for (int br = 0; br < 2; br++) {
    const void* x = d_in[br * 5 + 0]; const void* kc = d_in[br * 5 + 1]; const void* vc = d_in[br * 5 + 2];
    const void* wq = d_in[br * 5 + 3]; const void* wo = d_in[br * 5 + 4];
    { cuuint64_t d[2] = {DM, (cuuint64_t)NB * SQ}, s[1] = {DM * 2}; cuuint32_t b[2] = {64, 128}, b2[2] = {64, 96};
      make_map(enc, &P.x[0][br], x, 2, d, s, b); make_map(enc, &P.x[1][br], x, 2, d, s, b2); }
    { cuuint64_t d[3] = {64, DM, HD / 64}, s[2] = {HD * 2, 128}; cuuint32_t b[3] = {64, 64, 2}; make_map(enc, &P.wq[br], wq, 3, d, s, b); }
    { cuuint64_t d[5] = {DM, 2, 4, 4, HD / 32}, s[4] = {DM * 2, 8 * DM * 2, 2 * DM * 2, 32 * DM * 2}; cuuint32_t b[5] = {64, 2, 4, 4, 2};
      make_map(enc, &P.wo[br], wo, 5, d, s, b); }
    { cuuint64_t d[4] = {64, 8, 2, (cuuint64_t)NB * NH * SK / 8}, s[3] = {DH * 2, 128, DH * 16}; cuuint32_t b[4] = {64, 8, 2, 8};
      make_map(enc, &P.kv[0][br], kc, 4, d, s, b); make_map(enc, &P.kv[1][br], vc, 4, d, s, b); }
    P.kp[br] = (const __nv_bfloat16*)kc; P.vp[br] = (const __nv_bfloat16*)vc;

  }
  { cuuint64_t d[2] = {64, (cuuint64_t)NBETA * 64 * SQ}, s[1] = {128}; cuuint32_t b[2] = {64, 128}, b2[2] = {64, 96};
    make_map(enc, &P.o_ld[0], o_ptr, 2, d, s, b, CU_TENSOR_MAP_SWIZZLE_NONE); make_map(enc, &P.o_ld[1], o_ptr, 2, d, s, b2, CU_TENSOR_MAP_SWIZZLE_NONE); }
  { cuuint64_t d[3] = {64, SQ, O_BLOCKS}, s[2] = {128, SQ * 128}; cuuint32_t b[3] = {64, 64, 2}, b2[3] = {64, 32, 2};
    make_map(enc, &P.o_st[0], o_ptr, 3, d, s, b); make_map(enc, &P.o_st[1], o_ptr, 3, d, s, b2); }
  { cuuint64_t d[3] = {64, (cuuint64_t)NB * SQ, 2 * DM / 64}, s[2] = {2 * DM * 2, 128}; cuuint32_t b[3] = {64, 64, 2}, b2[3] = {64, 32, 2};
    make_map(enc, &P.out_st[0], d_out, 3, d, s, b); make_map(enc, &P.out_st[1], d_out, 3, d, s, b2); }
  if (n_sm >= NCTA) cudaLaunchKernelEx(&cfg, mha_fused_kernel<false>, P);
  else mha_fused_kernel<true><<<n_sm, 384, SMEM_BYTES>>>(P);
}
```

```cpp
#include <cuda_runtime.h>
#include <cuda_bf16.h>
#include <cuda.h>
#include <stdint.h>
#include <stdlib.h>

namespace {

__device__ __forceinline__ void wgmma_proj(float (&d)[64], uint64_t da, uint64_t db, int scaleD) {
  asm volatile("{\n.reg .pred p;\nsetp.ne.b32 p, %66, 0;\n"
      "wgmma.mma_async.sync.aligned.m64n128k16.f32.bf16.bf16 "
      "{%0, %1, %2, %3, %4, %5, %6, %7, %8, %9, %10, %11, %12, %13, %14, %15, %16, %17, %18, %19, %20, %21, %22, %23, %24, %25, %26, %27, %28, %29, %30, "
      "%31, %32, %33, %34, %35, %36, %37, %38, %39, %40, %41, %42, %43, %44, %45, %46, %47, %48, %49, %50, %51, %52, %53, %54, %55, %56, %57, %58, %59, %60, "
      "%61, %62, %63}, "
      "%64, %65, p, 1, 1, 0, 1;\n}\n"
      : "+f"(d[0]), "+f"(d[1]), "+f"(d[2]), "+f"(d[3]), "+f"(d[4]), "+f"(d[5]), "+f"(d[6]), "+f"(d[7]), "+f"(d[8]), "+f"(d[9]), "+f"(d[10]), "+f"(d[11]),
        "+f"(d[12]), "+f"(d[13]), "+f"(d[14]), "+f"(d[15]), "+f"(d[16]), "+f"(d[17]), "+f"(d[18]), "+f"(d[19]), "+f"(d[20]), "+f"(d[21]), "+f"(d[22]),
        "+f"(d[23]), "+f"(d[24]), "+f"(d[25]), "+f"(d[26]), "+f"(d[27]), "+f"(d[28]), "+f"(d[29]), "+f"(d[30]), "+f"(d[31]), "+f"(d[32]), "+f"(d[33]),
        "+f"(d[34]), "+f"(d[35]), "+f"(d[36]), "+f"(d[37]), "+f"(d[38]), "+f"(d[39]), "+f"(d[40]), "+f"(d[41]), "+f"(d[42]), "+f"(d[43]), "+f"(d[44]),
        "+f"(d[45]), "+f"(d[46]), "+f"(d[47]), "+f"(d[48]), "+f"(d[49]), "+f"(d[50]), "+f"(d[51]), "+f"(d[52]), "+f"(d[53]), "+f"(d[54]), "+f"(d[55]),
        "+f"(d[56]), "+f"(d[57]), "+f"(d[58]), "+f"(d[59]), "+f"(d[60]), "+f"(d[61]), "+f"(d[62]), "+f"(d[63])
      : "l"(da), "l"(db), "r"(scaleD));
}
__device__ __forceinline__ void wgmma_proj96(float (&d)[64], uint64_t da, uint64_t db, int scaleD) {
  asm volatile("{\n.reg .pred p;\nsetp.ne.b32 p, %50, 0;\n"
      "wgmma.mma_async.sync.aligned.m64n96k16.f32.bf16.bf16 "
      "{%0, %1, %2, %3, %4, %5, %6, %7, %8, %9, %10, %11, %12, %13, %14, %15, %16, %17, %18, %19, %20, %21, %22, %23, %24, %25, %26, %27, %28, %29, %30, "
      "%31, %32, %33, %34, %35, %36, %37, %38, %39, %40, %41, %42, %43, %44, %45, %46, %47}, "
      "%48, %49, p, 1, 1, 1, 0;\n}\n"
      : "+f"(d[0]), "+f"(d[1]), "+f"(d[2]), "+f"(d[3]), "+f"(d[4]), "+f"(d[5]), "+f"(d[6]), "+f"(d[7]), "+f"(d[8]), "+f"(d[9]), "+f"(d[10]), "+f"(d[11]),
        "+f"(d[12]), "+f"(d[13]), "+f"(d[14]), "+f"(d[15]), "+f"(d[16]), "+f"(d[17]), "+f"(d[18]), "+f"(d[19]), "+f"(d[20]), "+f"(d[21]), "+f"(d[22]),
        "+f"(d[23]), "+f"(d[24]), "+f"(d[25]), "+f"(d[26]), "+f"(d[27]), "+f"(d[28]), "+f"(d[29]), "+f"(d[30]), "+f"(d[31]), "+f"(d[32]), "+f"(d[33]),
        "+f"(d[34]), "+f"(d[35]), "+f"(d[36]), "+f"(d[37]), "+f"(d[38]), "+f"(d[39]), "+f"(d[40]), "+f"(d[41]), "+f"(d[42]), "+f"(d[43]), "+f"(d[44]),
        "+f"(d[45]), "+f"(d[46]), "+f"(d[47])
      : "l"(da), "l"(db), "r"(scaleD));
}
__device__ __forceinline__ void wgmma_qk(float (&d)[32], uint64_t da, uint64_t db, int scaleD) {
  asm volatile("{\n.reg .pred p;\nsetp.ne.b32 p, %34, 0;\n"
      "wgmma.mma_async.sync.aligned.m64n64k16.f32.bf16.bf16 "
      "{%0, %1, %2, %3, %4, %5, %6, %7, %8, %9, %10, %11, %12, %13, %14, %15, %16, %17, %18, %19, %20, %21, %22, %23, %24, %25, %26, %27, %28, %29, %30, "
      "%31}, "
      "%32, %33, p, 1, 1, 0, 0;\n}\n"
      : "+f"(d[0]), "+f"(d[1]), "+f"(d[2]), "+f"(d[3]), "+f"(d[4]), "+f"(d[5]), "+f"(d[6]), "+f"(d[7]), "+f"(d[8]), "+f"(d[9]), "+f"(d[10]), "+f"(d[11]),
        "+f"(d[12]), "+f"(d[13]), "+f"(d[14]), "+f"(d[15]), "+f"(d[16]), "+f"(d[17]), "+f"(d[18]), "+f"(d[19]), "+f"(d[20]), "+f"(d[21]), "+f"(d[22]),
        "+f"(d[23]), "+f"(d[24]), "+f"(d[25]), "+f"(d[26]), "+f"(d[27]), "+f"(d[28]), "+f"(d[29]), "+f"(d[30]), "+f"(d[31])
      : "l"(da), "l"(db), "r"(scaleD));
}
__device__ __forceinline__ void wgmma_qk_rs(float (&d)[32], uint32_t a0, uint32_t a1, uint32_t a2, uint32_t a3, uint64_t db, int scaleD) {
  asm volatile("{\n.reg .pred p;\nsetp.ne.b32 p, %37, 0;\n"
      "wgmma.mma_async.sync.aligned.m64n64k16.f32.bf16.bf16 "
      "{%0, %1, %2, %3, %4, %5, %6, %7, %8, %9, %10, %11, %12, %13, %14, %15, %16, %17, %18, %19, %20, %21, %22, %23, %24, %25, %26, %27, %28, %29, %30, "
      "%31}, "
      "{%32, %33, %34, %35}, %36, p, 1, 1, 0;\n}\n"
      : "+f"(d[0]), "+f"(d[1]), "+f"(d[2]), "+f"(d[3]), "+f"(d[4]), "+f"(d[5]), "+f"(d[6]), "+f"(d[7]), "+f"(d[8]), "+f"(d[9]), "+f"(d[10]), "+f"(d[11]),
        "+f"(d[12]), "+f"(d[13]), "+f"(d[14]), "+f"(d[15]), "+f"(d[16]), "+f"(d[17]), "+f"(d[18]), "+f"(d[19]), "+f"(d[20]), "+f"(d[21]), "+f"(d[22]),
        "+f"(d[23]), "+f"(d[24]), "+f"(d[25]), "+f"(d[26]), "+f"(d[27]), "+f"(d[28]), "+f"(d[29]), "+f"(d[30]), "+f"(d[31])
      : "r"(a0), "r"(a1), "r"(a2), "r"(a3), "l"(db), "r"(scaleD));
}
__device__ __forceinline__ void wgmma_pv(float (&d)[64], uint32_t a0, uint32_t a1, uint32_t a2, uint32_t a3, uint64_t db, int scaleD) {
  asm volatile("{\n.reg .pred p;\nsetp.ne.b32 p, %69, 0;\n"
      "wgmma.mma_async.sync.aligned.m64n128k16.f32.bf16.bf16 "
      "{%0, %1, %2, %3, %4, %5, %6, %7, %8, %9, %10, %11, %12, %13, %14, %15, %16, %17, %18, %19, %20, %21, %22, %23, %24, %25, %26, %27, %28, %29, %30, "
      "%31, %32, %33, %34, %35, %36, %37, %38, %39, %40, %41, %42, %43, %44, %45, %46, %47, %48, %49, %50, %51, %52, %53, %54, %55, %56, %57, %58, %59, %60, "
      "%61, %62, %63}, "
      "{%64, %65, %66, %67}, %68, p, 1, 1, 1;\n}\n"
      : "+f"(d[0]), "+f"(d[1]), "+f"(d[2]), "+f"(d[3]), "+f"(d[4]), "+f"(d[5]), "+f"(d[6]), "+f"(d[7]), "+f"(d[8]), "+f"(d[9]), "+f"(d[10]), "+f"(d[11]),
        "+f"(d[12]), "+f"(d[13]), "+f"(d[14]), "+f"(d[15]), "+f"(d[16]), "+f"(d[17]), "+f"(d[18]), "+f"(d[19]), "+f"(d[20]), "+f"(d[21]), "+f"(d[22]),
        "+f"(d[23]), "+f"(d[24]), "+f"(d[25]), "+f"(d[26]), "+f"(d[27]), "+f"(d[28]), "+f"(d[29]), "+f"(d[30]), "+f"(d[31]), "+f"(d[32]), "+f"(d[33]),
        "+f"(d[34]), "+f"(d[35]), "+f"(d[36]), "+f"(d[37]), "+f"(d[38]), "+f"(d[39]), "+f"(d[40]), "+f"(d[41]), "+f"(d[42]), "+f"(d[43]), "+f"(d[44]),
        "+f"(d[45]), "+f"(d[46]), "+f"(d[47]), "+f"(d[48]), "+f"(d[49]), "+f"(d[50]), "+f"(d[51]), "+f"(d[52]), "+f"(d[53]), "+f"(d[54]), "+f"(d[55]),
        "+f"(d[56]), "+f"(d[57]), "+f"(d[58]), "+f"(d[59]), "+f"(d[60]), "+f"(d[61]), "+f"(d[62]), "+f"(d[63])
      : "r"(a0), "r"(a1), "r"(a2), "r"(a3), "l"(db), "r"(scaleD));
}
__device__ __forceinline__ void wgmma_qk_sp(float (&d)[32], uint32_t a0, uint32_t a1, uint32_t a2, uint32_t a3, uint64_t db, int scaleD, uint32_t meta) {
  asm volatile("{\n.reg .pred p;\nsetp.ne.b32 p, %37, 0;\n"
      "wgmma.mma_async.sp.sync.aligned.m64n64k32.f32.bf16.bf16 "
      "{%0, %1, %2, %3, %4, %5, %6, %7, %8, %9, %10, %11, %12, %13, %14, %15, %16, %17, %18, %19, %20, %21, %22, %23, %24, %25, %26, %27, %28, %29, %30, "
      "%31}, "
      "{%32, %33, %34, %35}, %36, %38, 0, p, 1, 1, 0;\n}\n"
      : "+f"(d[0]), "+f"(d[1]), "+f"(d[2]), "+f"(d[3]), "+f"(d[4]), "+f"(d[5]), "+f"(d[6]), "+f"(d[7]), "+f"(d[8]), "+f"(d[9]), "+f"(d[10]), "+f"(d[11]),
        "+f"(d[12]), "+f"(d[13]), "+f"(d[14]), "+f"(d[15]), "+f"(d[16]), "+f"(d[17]), "+f"(d[18]), "+f"(d[19]), "+f"(d[20]), "+f"(d[21]), "+f"(d[22]),
        "+f"(d[23]), "+f"(d[24]), "+f"(d[25]), "+f"(d[26]), "+f"(d[27]), "+f"(d[28]), "+f"(d[29]), "+f"(d[30]), "+f"(d[31])
      : "r"(a0), "r"(a1), "r"(a2), "r"(a3), "l"(db), "r"(scaleD), "r"(meta));
}
__device__ __forceinline__ void wgmma_pv_sp(float (&d)[64], uint32_t a0, uint32_t a1, uint32_t a2, uint32_t a3, uint64_t db, int scaleD, uint32_t meta) {
  asm volatile("{\n.reg .pred p;\nsetp.ne.b32 p, %69, 0;\n"
      "wgmma.mma_async.sp.sync.aligned.m64n128k32.f32.bf16.bf16 "
      "{%0, %1, %2, %3, %4, %5, %6, %7, %8, %9, %10, %11, %12, %13, %14, %15, %16, %17, %18, %19, %20, %21, %22, %23, %24, %25, %26, %27, %28, %29, %30, "
      "%31, %32, %33, %34, %35, %36, %37, %38, %39, %40, %41, %42, %43, %44, %45, %46, %47, %48, %49, %50, %51, %52, %53, %54, %55, %56, %57, %58, %59, %60, "
      "%61, %62, %63}, "
      "{%64, %65, %66, %67}, %68, %70, 0, p, 1, 1, 1;\n}\n"
      : "+f"(d[0]), "+f"(d[1]), "+f"(d[2]), "+f"(d[3]), "+f"(d[4]), "+f"(d[5]), "+f"(d[6]), "+f"(d[7]), "+f"(d[8]), "+f"(d[9]), "+f"(d[10]), "+f"(d[11]),
        "+f"(d[12]), "+f"(d[13]), "+f"(d[14]), "+f"(d[15]), "+f"(d[16]), "+f"(d[17]), "+f"(d[18]), "+f"(d[19]), "+f"(d[20]), "+f"(d[21]), "+f"(d[22]),
        "+f"(d[23]), "+f"(d[24]), "+f"(d[25]), "+f"(d[26]), "+f"(d[27]), "+f"(d[28]), "+f"(d[29]), "+f"(d[30]), "+f"(d[31]), "+f"(d[32]), "+f"(d[33]),
        "+f"(d[34]), "+f"(d[35]), "+f"(d[36]), "+f"(d[37]), "+f"(d[38]), "+f"(d[39]), "+f"(d[40]), "+f"(d[41]), "+f"(d[42]), "+f"(d[43]), "+f"(d[44]),
        "+f"(d[45]), "+f"(d[46]), "+f"(d[47]), "+f"(d[48]), "+f"(d[49]), "+f"(d[50]), "+f"(d[51]), "+f"(d[52]), "+f"(d[53]), "+f"(d[54]), "+f"(d[55]),
        "+f"(d[56]), "+f"(d[57]), "+f"(d[58]), "+f"(d[59]), "+f"(d[60]), "+f"(d[61]), "+f"(d[62]), "+f"(d[63])
      : "r"(a0), "r"(a1), "r"(a2), "r"(a3), "l"(db), "r"(scaleD), "r"(meta));
}
__device__ __forceinline__ void wgmma_proj_init(float (&d)[64], uint64_t da, uint64_t db, int scaleD) {
  asm volatile("{\n.reg .pred p;\nsetp.ne.b32 p, %66, 0;\n"
      "wgmma.mma_async.sync.aligned.m64n128k16.f32.bf16.bf16 "
      "{%0, %1, %2, %3, %4, %5, %6, %7, %8, %9, %10, %11, %12, %13, %14, %15, %16, %17, %18, %19, %20, %21, %22, %23, %24, %25, %26, %27, %28, %29, %30, "
      "%31, %32, %33, %34, %35, %36, %37, %38, %39, %40, %41, %42, %43, %44, %45, %46, %47, %48, %49, %50, %51, %52, %53, %54, %55, %56, %57, %58, %59, %60, "
      "%61, %62, %63}, "
      "%64, %65, p, 1, 1, 0, 1;\n}\n"
      : "=f"(d[0]), "=f"(d[1]), "=f"(d[2]), "=f"(d[3]), "=f"(d[4]), "=f"(d[5]), "=f"(d[6]), "=f"(d[7]), "=f"(d[8]), "=f"(d[9]), "=f"(d[10]), "=f"(d[11]),
        "=f"(d[12]), "=f"(d[13]), "=f"(d[14]), "=f"(d[15]), "=f"(d[16]), "=f"(d[17]), "=f"(d[18]), "=f"(d[19]), "=f"(d[20]), "=f"(d[21]), "=f"(d[22]),
        "=f"(d[23]), "=f"(d[24]), "=f"(d[25]), "=f"(d[26]), "=f"(d[27]), "=f"(d[28]), "=f"(d[29]), "=f"(d[30]), "=f"(d[31]), "=f"(d[32]), "=f"(d[33]),
        "=f"(d[34]), "=f"(d[35]), "=f"(d[36]), "=f"(d[37]), "=f"(d[38]), "=f"(d[39]), "=f"(d[40]), "=f"(d[41]), "=f"(d[42]), "=f"(d[43]), "=f"(d[44]),
        "=f"(d[45]), "=f"(d[46]), "=f"(d[47]), "=f"(d[48]), "=f"(d[49]), "=f"(d[50]), "=f"(d[51]), "=f"(d[52]), "=f"(d[53]), "=f"(d[54]), "=f"(d[55]),
        "=f"(d[56]), "=f"(d[57]), "=f"(d[58]), "=f"(d[59]), "=f"(d[60]), "=f"(d[61]), "=f"(d[62]), "=f"(d[63])
      : "l"(da), "l"(db), "r"(scaleD));
}
__device__ __forceinline__ void wgmma_proj96_init(float (&d)[64], uint64_t da, uint64_t db, int scaleD) {
  asm volatile("{\n.reg .pred p;\nsetp.ne.b32 p, %50, 0;\n"
      "wgmma.mma_async.sync.aligned.m64n96k16.f32.bf16.bf16 "
      "{%0, %1, %2, %3, %4, %5, %6, %7, %8, %9, %10, %11, %12, %13, %14, %15, %16, %17, %18, %19, %20, %21, %22, %23, %24, %25, %26, %27, %28, %29, %30, "
      "%31, %32, %33, %34, %35, %36, %37, %38, %39, %40, %41, %42, %43, %44, %45, %46, %47}, "
      "%48, %49, p, 1, 1, 1, 0;\n}\n"
      : "=f"(d[0]), "=f"(d[1]), "=f"(d[2]), "=f"(d[3]), "=f"(d[4]), "=f"(d[5]), "=f"(d[6]), "=f"(d[7]), "=f"(d[8]), "=f"(d[9]), "=f"(d[10]), "=f"(d[11]),
        "=f"(d[12]), "=f"(d[13]), "=f"(d[14]), "=f"(d[15]), "=f"(d[16]), "=f"(d[17]), "=f"(d[18]), "=f"(d[19]), "=f"(d[20]), "=f"(d[21]), "=f"(d[22]),
        "=f"(d[23]), "=f"(d[24]), "=f"(d[25]), "=f"(d[26]), "=f"(d[27]), "=f"(d[28]), "=f"(d[29]), "=f"(d[30]), "=f"(d[31]), "=f"(d[32]), "=f"(d[33]),
        "=f"(d[34]), "=f"(d[35]), "=f"(d[36]), "=f"(d[37]), "=f"(d[38]), "=f"(d[39]), "=f"(d[40]), "=f"(d[41]), "=f"(d[42]), "=f"(d[43]), "=f"(d[44]),
        "=f"(d[45]), "=f"(d[46]), "=f"(d[47])
      : "l"(da), "l"(db), "r"(scaleD));
}
__device__ __forceinline__ void wgmma_qk_init(float (&d)[32], uint64_t da, uint64_t db, int scaleD) {
  asm volatile("{\n.reg .pred p;\nsetp.ne.b32 p, %34, 0;\n"
      "wgmma.mma_async.sync.aligned.m64n64k16.f32.bf16.bf16 "
      "{%0, %1, %2, %3, %4, %5, %6, %7, %8, %9, %10, %11, %12, %13, %14, %15, %16, %17, %18, %19, %20, %21, %22, %23, %24, %25, %26, %27, %28, %29, %30, "
      "%31}, "
      "%32, %33, p, 1, 1, 0, 0;\n}\n"
      : "=f"(d[0]), "=f"(d[1]), "=f"(d[2]), "=f"(d[3]), "=f"(d[4]), "=f"(d[5]), "=f"(d[6]), "=f"(d[7]), "=f"(d[8]), "=f"(d[9]), "=f"(d[10]), "=f"(d[11]),
        "=f"(d[12]), "=f"(d[13]), "=f"(d[14]), "=f"(d[15]), "=f"(d[16]), "=f"(d[17]), "=f"(d[18]), "=f"(d[19]), "=f"(d[20]), "=f"(d[21]), "=f"(d[22]),
        "=f"(d[23]), "=f"(d[24]), "=f"(d[25]), "=f"(d[26]), "=f"(d[27]), "=f"(d[28]), "=f"(d[29]), "=f"(d[30]), "=f"(d[31])
      : "l"(da), "l"(db), "r"(scaleD));
}
__device__ __forceinline__ void wgmma_qk_rs_init(float (&d)[32], uint32_t a0, uint32_t a1, uint32_t a2, uint32_t a3, uint64_t db, int scaleD) {
  asm volatile("{\n.reg .pred p;\nsetp.ne.b32 p, %37, 0;\n"
      "wgmma.mma_async.sync.aligned.m64n64k16.f32.bf16.bf16 "
      "{%0, %1, %2, %3, %4, %5, %6, %7, %8, %9, %10, %11, %12, %13, %14, %15, %16, %17, %18, %19, %20, %21, %22, %23, %24, %25, %26, %27, %28, %29, %30, "
      "%31}, "
      "{%32, %33, %34, %35}, %36, p, 1, 1, 0;\n}\n"
      : "=f"(d[0]), "=f"(d[1]), "=f"(d[2]), "=f"(d[3]), "=f"(d[4]), "=f"(d[5]), "=f"(d[6]), "=f"(d[7]), "=f"(d[8]), "=f"(d[9]), "=f"(d[10]), "=f"(d[11]),
        "=f"(d[12]), "=f"(d[13]), "=f"(d[14]), "=f"(d[15]), "=f"(d[16]), "=f"(d[17]), "=f"(d[18]), "=f"(d[19]), "=f"(d[20]), "=f"(d[21]), "=f"(d[22]),
        "=f"(d[23]), "=f"(d[24]), "=f"(d[25]), "=f"(d[26]), "=f"(d[27]), "=f"(d[28]), "=f"(d[29]), "=f"(d[30]), "=f"(d[31])
      : "r"(a0), "r"(a1), "r"(a2), "r"(a3), "l"(db), "r"(scaleD));
}
__device__ __forceinline__ void wgmma_pv_init(float (&d)[64], uint32_t a0, uint32_t a1, uint32_t a2, uint32_t a3, uint64_t db, int scaleD) {
  asm volatile("{\n.reg .pred p;\nsetp.ne.b32 p, %69, 0;\n"
      "wgmma.mma_async.sync.aligned.m64n128k16.f32.bf16.bf16 "
      "{%0, %1, %2, %3, %4, %5, %6, %7, %8, %9, %10, %11, %12, %13, %14, %15, %16, %17, %18, %19, %20, %21, %22, %23, %24, %25, %26, %27, %28, %29, %30, "
      "%31, %32, %33, %34, %35, %36, %37, %38, %39, %40, %41, %42, %43, %44, %45, %46, %47, %48, %49, %50, %51, %52, %53, %54, %55, %56, %57, %58, %59, %60, "
      "%61, %62, %63}, "
      "{%64, %65, %66, %67}, %68, p, 1, 1, 1;\n}\n"
      : "=f"(d[0]), "=f"(d[1]), "=f"(d[2]), "=f"(d[3]), "=f"(d[4]), "=f"(d[5]), "=f"(d[6]), "=f"(d[7]), "=f"(d[8]), "=f"(d[9]), "=f"(d[10]), "=f"(d[11]),
        "=f"(d[12]), "=f"(d[13]), "=f"(d[14]), "=f"(d[15]), "=f"(d[16]), "=f"(d[17]), "=f"(d[18]), "=f"(d[19]), "=f"(d[20]), "=f"(d[21]), "=f"(d[22]),
        "=f"(d[23]), "=f"(d[24]), "=f"(d[25]), "=f"(d[26]), "=f"(d[27]), "=f"(d[28]), "=f"(d[29]), "=f"(d[30]), "=f"(d[31]), "=f"(d[32]), "=f"(d[33]),
        "=f"(d[34]), "=f"(d[35]), "=f"(d[36]), "=f"(d[37]), "=f"(d[38]), "=f"(d[39]), "=f"(d[40]), "=f"(d[41]), "=f"(d[42]), "=f"(d[43]), "=f"(d[44]),
        "=f"(d[45]), "=f"(d[46]), "=f"(d[47]), "=f"(d[48]), "=f"(d[49]), "=f"(d[50]), "=f"(d[51]), "=f"(d[52]), "=f"(d[53]), "=f"(d[54]), "=f"(d[55]),
        "=f"(d[56]), "=f"(d[57]), "=f"(d[58]), "=f"(d[59]), "=f"(d[60]), "=f"(d[61]), "=f"(d[62]), "=f"(d[63])
      : "r"(a0), "r"(a1), "r"(a2), "r"(a3), "l"(db), "r"(scaleD));
}
__device__ __forceinline__ void wgmma_qk_sp_init(float (&d)[32], uint32_t a0, uint32_t a1, uint32_t a2, uint32_t a3, uint64_t db, int scaleD, uint32_t meta) {
  asm volatile("{\n.reg .pred p;\nsetp.ne.b32 p, %37, 0;\n"
      "wgmma.mma_async.sp.sync.aligned.m64n64k32.f32.bf16.bf16 "
      "{%0, %1, %2, %3, %4, %5, %6, %7, %8, %9, %10, %11, %12, %13, %14, %15, %16, %17, %18, %19, %20, %21, %22, %23, %24, %25, %26, %27, %28, %29, %30, "
      "%31}, "
      "{%32, %33, %34, %35}, %36, %38, 0, p, 1, 1, 0;\n}\n"
      : "=f"(d[0]), "=f"(d[1]), "=f"(d[2]), "=f"(d[3]), "=f"(d[4]), "=f"(d[5]), "=f"(d[6]), "=f"(d[7]), "=f"(d[8]), "=f"(d[9]), "=f"(d[10]), "=f"(d[11]),
        "=f"(d[12]), "=f"(d[13]), "=f"(d[14]), "=f"(d[15]), "=f"(d[16]), "=f"(d[17]), "=f"(d[18]), "=f"(d[19]), "=f"(d[20]), "=f"(d[21]), "=f"(d[22]),
        "=f"(d[23]), "=f"(d[24]), "=f"(d[25]), "=f"(d[26]), "=f"(d[27]), "=f"(d[28]), "=f"(d[29]), "=f"(d[30]), "=f"(d[31])
      : "r"(a0), "r"(a1), "r"(a2), "r"(a3), "l"(db), "r"(scaleD), "r"(meta));
}
__device__ __forceinline__ void wgmma_pv_sp_init(float (&d)[64], uint32_t a0, uint32_t a1, uint32_t a2, uint32_t a3, uint64_t db, int scaleD, uint32_t meta) {
  asm volatile("{\n.reg .pred p;\nsetp.ne.b32 p, %69, 0;\n"
      "wgmma.mma_async.sp.sync.aligned.m64n128k32.f32.bf16.bf16 "
      "{%0, %1, %2, %3, %4, %5, %6, %7, %8, %9, %10, %11, %12, %13, %14, %15, %16, %17, %18, %19, %20, %21, %22, %23, %24, %25, %26, %27, %28, %29, %30, "
      "%31, %32, %33, %34, %35, %36, %37, %38, %39, %40, %41, %42, %43, %44, %45, %46, %47, %48, %49, %50, %51, %52, %53, %54, %55, %56, %57, %58, %59, %60, "
      "%61, %62, %63}, "
      "{%64, %65, %66, %67}, %68, %70, 0, p, 1, 1, 1;\n}\n"
      : "=f"(d[0]), "=f"(d[1]), "=f"(d[2]), "=f"(d[3]), "=f"(d[4]), "=f"(d[5]), "=f"(d[6]), "=f"(d[7]), "=f"(d[8]), "=f"(d[9]), "=f"(d[10]), "=f"(d[11]),
        "=f"(d[12]), "=f"(d[13]), "=f"(d[14]), "=f"(d[15]), "=f"(d[16]), "=f"(d[17]), "=f"(d[18]), "=f"(d[19]), "=f"(d[20]), "=f"(d[21]), "=f"(d[22]),
        "=f"(d[23]), "=f"(d[24]), "=f"(d[25]), "=f"(d[26]), "=f"(d[27]), "=f"(d[28]), "=f"(d[29]), "=f"(d[30]), "=f"(d[31]), "=f"(d[32]), "=f"(d[33]),
        "=f"(d[34]), "=f"(d[35]), "=f"(d[36]), "=f"(d[37]), "=f"(d[38]), "=f"(d[39]), "=f"(d[40]), "=f"(d[41]), "=f"(d[42]), "=f"(d[43]), "=f"(d[44]),
        "=f"(d[45]), "=f"(d[46]), "=f"(d[47]), "=f"(d[48]), "=f"(d[49]), "=f"(d[50]), "=f"(d[51]), "=f"(d[52]), "=f"(d[53]), "=f"(d[54]), "=f"(d[55]),
        "=f"(d[56]), "=f"(d[57]), "=f"(d[58]), "=f"(d[59]), "=f"(d[60]), "=f"(d[61]), "=f"(d[62]), "=f"(d[63])
      : "r"(a0), "r"(a1), "r"(a2), "r"(a3), "l"(db), "r"(scaleD), "r"(meta));
}

constexpr int NB = 16, SQ = 224, DM = 640, NH = 32, SK = 1024, DH = 128;
constexpr int HD = NH * DH;
constexpr int NBETA = 2 * NB;
constexpr int NCTA = 132;
constexpr uint32_t SB0 = 1024;
constexpr int NS = 10;
constexpr int SLOT = 16384;
constexpr int QBUF_OFF = NS * SLOT;
constexpr int NSX = NS + 4;
constexpr int BAR_OFF = NSX * SLOT;
constexpr int BAR_FULL = BAR_OFF;
constexpr int BAR_EMPTY = BAR_OFF + 8 * NSX;
constexpr int BAR_STG = BAR_OFF + 16 * NSX;
constexpr int BAR_OUT = BAR_STG + 32;
constexpr int BAR_DESC = BAR_OUT + 8;
constexpr int BAR_GO = BAR_DESC + 8;
constexpr int BAR_MAIL = BAR_GO + 8;
constexpr int BAR_RDY = BAR_MAIL + 8;
constexpr int DESC_OFF = BAR_RDY + 8 * NSX;
constexpr int EPOCH_OFF = DESC_OFF + 16;
constexpr int TRACE_OFF = EPOCH_OFF + 16;
constexpr int SMEM_BYTES = TRACE_OFF;
constexpr float SM_C = 0.08838834764831845f * 1.4426950408889634f;
constexpr float SUM_HI = 1099511627776.f, SUM_LO = 1.f / 1099511627776.f;
constexpr uint32_t META_QK = 0xEEEE4444u;
constexpr uint32_t META_PV = 0x44EEEE44u;

#define QK_EARLY_MASK 3
#define ST_ORDER 0x2310
#define LAG_BAR 2
#define ST_NOW 8
#define PF_STEP 3
#define KV_WIN_D 4
#define SF 0xefbf
#define O_STEPS 4
#define KV_WIN_RAMP 4
#define PDEPTH 0
#define KV_WIN_TILES -2
#define REG_C 232
#define REG_P 24
#define GO_P 6
#define P_POS 208
#define OR 6
#define OR0 0
#define B_LATE 22
#define H_LATE 24
#define RM0 1
#define RM1 0xb3
#define RM2 0
#define PAIRB 1
#define LATE0 1
#define LATE1 2
#define GO_J 13
#define LATE_G 32
#define KG 5
#define PK 44
#define EARLY_MASK 0xffffu
#define PIECE_TABLE 0x501e8815,0x689d883d,0x5036b019,0x80000000,0x50345012,0x80000000,0x50244013,0x6b13403a,0x501c3811,0x695a3833,0x50321018,0x80000000,0x502b481a,0x6d4a4832,0x50128016,0x67e08035,0x50210814,0x6ccc0838,0x5012c010,0x695ac03f,0x64ec7836,0x80000000,0x64ecb830,0x80000000,0x5024c81f,0x80000000,0x5024601e,0x80000000,0x5021901d,0x80000000,0x501e7017,0x80000000,0x549b201c,0x80000000,0x67623031,0x80000000,0x67e06837,0x80000000,0x5016a81b,0x6dc8a839,0x689d0034,0x80000000,0x6999985b,0x80000000,0x695a583e,0x80000000,0x5011281c,0x80000000,0x55cea01b,0x80000000,0x6b91185c,0x80000000

struct Params {
  CUtensorMap x[2][2], wq[2], kv[2][2], wo[2];
  CUtensorMap o_ld[2], o_st[2], out_st[2];
  const __nv_bfloat16* kp[2];
  const __nv_bfloat16* vp[2];
};

constexpr int NPART = 32 * 5, O_BLOCKS = NBETA * 64 + 2 * NPART;
__device__ __align__(128) __nv_bfloat16 g_o[(size_t)O_BLOCKS * SQ * 64];
__device__ unsigned g_cnt[NBETA][8];
__device__ unsigned g_rd[NBETA][8];
__device__ unsigned g_epoch, g_next;
__device__ unsigned g_flag[NPART];

__device__ __forceinline__ uint32_t smem_u32(const void* p) { return (uint32_t)__cvta_generic_to_shared(p); }
__device__ __forceinline__ void mbar_arrive(uint32_t bar) {
  asm volatile("mbarrier.arrive.shared::cta.b64 _, [%0];" ::"r"(bar) : "memory");
}
__device__ __forceinline__ void mbar_arrive_warp(uint32_t bar) {
  asm volatile("{\n.reg .pred p;\nelect.sync _|p, 0xffffffff;\n@p mbarrier.arrive.shared::cta.b64 _, [%0];\n}" ::"r"(bar) : "memory");
}
__device__ __forceinline__ int lane_now() { int l; asm volatile("mov.u32 %0, %%laneid;" : "=r"(l)); return l; }
__device__ __forceinline__ bool mbar_try(uint32_t bar, uint32_t parity) {
  uint32_t ok;
  asm volatile("{\n.reg .pred p;\nmbarrier.try_wait.parity.shared::cta.b64 p, [%1], %2;\nselp.u32 %0, 1, 0, p;\n}"
               : "=r"(ok) : "r"(bar), "r"(parity) : "memory");
  return ok;
}
__device__ __forceinline__ bool mbar_test(uint32_t bar, uint32_t parity) {
  uint32_t ok;
  asm volatile("{\n.reg .pred p;\nmbarrier.test_wait.parity.shared::cta.b64 p, [%1], %2;\nselp.u32 %0, 1, 0, p;\n}"
               : "=r"(ok) : "r"(bar), "r"(parity) : "memory");
  return ok;
}
__device__ __forceinline__ void mbar_wait_w(uint32_t bar, uint32_t parity) {
  uint32_t n = 0;
  while (!__all_sync(0xffffffffu, mbar_try(bar, parity))) {
    if (++n > (1u << 22)) __trap();
  }
}
#define ELECT "{\n.reg .pred p;\nelect.sync _|p, 0xffffffff;\n@p "
__device__ __forceinline__ void tma_st3_w(const CUtensorMap* m, uint32_t src, int c1, int c2) {
  asm volatile(ELECT "cp.async.bulk.tensor.3d.global.shared::cta.bulk_group [%0, {0, %2, %3}], [%1];\n}"
               ::"l"(m), "r"(src), "r"(c1), "r"(c2) : "memory");
}
#define EXPECT(bar, bytes) "mbarrier.arrive.expect_tx.shared::cta.b64 _, [" bar "], " bytes ";\n@p "
__device__ __forceinline__ void tma_ld2_w(uint32_t dst, const CUtensorMap* m, int c0, int c1, uint32_t bar, uint32_t bytes) {
  asm volatile(ELECT EXPECT("%2", "%5") "cp.async.bulk.tensor.2d.shared::cluster.global.mbarrier::complete_tx::bytes [%0], [%1, {%3, %4}], [%2];\n}"
               ::"r"(dst), "l"(m), "r"(bar), "r"(c0), "r"(c1), "r"(bytes) : "memory");
}
__device__ __forceinline__ void tma_ld2_hint_w(uint32_t dst, const CUtensorMap* m, int c0, int c1, uint32_t bar, uint32_t bytes, uint64_t pol) {
  asm volatile(ELECT EXPECT("%2", "%6") "cp.async.bulk.tensor.2d.shared::cluster.global.mbarrier::complete_tx::bytes.L2::cache_hint"
               " [%0], [%1, {%3, %4}], [%2], %5;\n}"
               ::"r"(dst), "l"(m), "r"(bar), "r"(c0), "r"(c1), "l"(pol), "r"(bytes) : "memory");
}
__device__ __forceinline__ void tma_ld3_w(uint32_t dst, const CUtensorMap* m, int c0, int c1, int c2, uint32_t bar, uint32_t bytes) {
  asm volatile(ELECT EXPECT("%2", "%6") "cp.async.bulk.tensor.3d.shared::cluster.global.mbarrier::complete_tx::bytes [%0], [%1, {%3, %4, %5}], [%2];\n}"
               ::"r"(dst), "l"(m), "r"(bar), "r"(c0), "r"(c1), "r"(c2), "r"(bytes) : "memory");
}
__device__ __forceinline__ void tma_ld_kv_w(uint32_t dst, const CUtensorMap* m, int grp, uint32_t bar, uint64_t pol) {
  asm volatile(ELECT EXPECT("%2", "16384") "cp.async.bulk.tensor.4d.shared::cluster.global.mbarrier::complete_tx::bytes.L2::cache_hint"
               " [%0], [%1, {0, 0, 0, %3}], [%2], %4;\n}"
               ::"r"(dst), "l"(m), "r"(bar), "r"(grp), "l"(pol) : "memory");
}
__device__ __forceinline__ void tma_ld_wo_w(uint32_t dst, const CUtensorMap* m, int col, int grp, uint32_t bar) {
  asm volatile(ELECT EXPECT("%2", "16384") "cp.async.bulk.tensor.5d.shared::cluster.global.mbarrier::complete_tx::bytes [%0], [%1, {%3, 0, 0, 0, %4}], [%2];\n"
               "@p cp.async.bulk.tensor.5d.shared::cluster.global.mbarrier::complete_tx::bytes [%5], [%1, {%6, 0, 0, 0, %4}], [%2];\n}"
               ::"r"(dst), "l"(m), "r"(bar), "r"(col), "r"(grp), "r"(dst + 8192), "r"(col + 64) : "memory");
}
__device__ __forceinline__ void mbar_arrive8_w(uint32_t bar) {
  asm volatile(ELECT "mbarrier.arrive.shared::cta.b64 _, [%0], 8;\n}" ::"r"(bar) : "memory");
}
__device__ __forceinline__ uint32_t peer(uint32_t a) { uint32_t r; asm("mapa.shared::cluster.u32 %0, %1, %2;" : "=r"(r) : "r"(a), "r"(~blockIdx.x & 1)); return r; }
__device__ __forceinline__ void tma_ld2_both_w(uint32_t dst, const CUtensorMap* m, int c0, int c1, uint32_t bar, uint32_t bytes) {
  asm volatile(ELECT EXPECT("%2", "%5") "cp.async.bulk.tensor.2d.shared::cluster.global.mbarrier::complete_tx::bytes.multicast::cluster"
               " [%0], [%1, {%3, %4}], [%2], %6;\n}"
               ::"r"(dst), "l"(m), "r"(bar), "r"(c0), "r"(c1), "r"(bytes), "h"((uint16_t)3) : "memory");
}
__device__ __forceinline__ void tma_ld2_both_hint_w(uint32_t dst, const CUtensorMap* m, int c0, int c1, uint32_t bar, uint32_t bytes, uint64_t pol) {
  asm volatile(ELECT EXPECT("%2", "%6") "cp.async.bulk.tensor.2d.shared::cluster.global.mbarrier::complete_tx::bytes.multicast::cluster.L2::cache_hint"
               " [%0], [%1, {%3, %4}], [%2], %7, %5;\n}"
               ::"r"(dst), "l"(m), "r"(bar), "r"(c0), "r"(c1), "l"(pol), "r"(bytes), "h"((uint16_t)3) : "memory");
}
__device__ __forceinline__ void bulk_commit() { asm volatile("cp.async.bulk.commit_group;" ::: "memory"); }
template <int N> __device__ __forceinline__ void bulk_wait_read() { asm volatile("cp.async.bulk.wait_group.read %0;" ::"n"(N) : "memory"); }
__device__ __forceinline__ void wg_fence() { asm volatile("wgmma.fence.sync.aligned;" ::: "memory"); }
__device__ __forceinline__ void wg_commit() { asm volatile("wgmma.commit_group.sync.aligned;" ::: "memory"); }
template <int N> __device__ __forceinline__ void wg_wait() { asm volatile("wgmma.wait_group.sync.aligned %0;" ::"n"(N) : "memory"); }
__device__ __forceinline__ void fence_async_smem() { asm volatile("fence.proxy.async.shared::cta;" ::: "memory"); }
__device__ __forceinline__ void bar_sync(int id, int n) { asm volatile("bar.sync %0, %1;" ::"r"(id), "r"(n) : "memory"); }
__device__ __forceinline__ void touch(float& a) { asm volatile("neg.f32 %0, %0;" : "+f"(a)); }
__device__ __forceinline__ void touch(uint32_t& a) { asm volatile("not.b32 %0, %0;" : "+r"(a)); }
template <typename T, int N> __device__ __forceinline__ void touch(T (&a)[N]) {
#pragma unroll
  for (int i = 0; i < N; i++) touch(a[i]);
}
template <int ID, typename... A> __device__ __forceinline__ void sched_fence(uint32_t x, A&... a) {
  if (!((SF >> ID) & 1)) return;
  asm volatile("" : "+r"(x)::"memory");
#pragma unroll 1
  for (; __builtin_expect(x >= 100 + ID, 0); x >>= 1) { (touch(a), ...); __nanosleep(x); }
}
template <int N> __device__ __forceinline__ void reg_fence(float (&a)[N]) {
#pragma unroll
  for (int i = 0; i < N; i++) asm volatile("" : "+f"(a[i])::"memory");
}
template <int N> __device__ __forceinline__ void reg_fence(uint32_t (&a)[N]) {
#pragma unroll
  for (int i = 0; i < N; i++) asm volatile("" : "+r"(a[i])::"memory");
}
__device__ __forceinline__ float ex2(float x) { float y; asm("ex2.approx.ftz.f32 %0, %1;" : "=f"(y) : "f"(x)); return y; }
__device__ __forceinline__ uint32_t pack_bf16(float lo, float hi) {
  uint32_t r; asm("cvt.rn.bf16x2.f32 %0, %1, %2;" : "=r"(r) : "f"(hi), "f"(lo)); return r;
}
__device__ __forceinline__ void stsm4(uint32_t a, uint32_t r0, uint32_t r1, uint32_t r2, uint32_t r3) {
  asm volatile("stmatrix.sync.aligned.m8n8.x4.shared.b16 [%0], {%1, %2, %3, %4};" ::"r"(a), "r"(r0), "r"(r1), "r"(r2), "r"(r3) : "memory");
}
__device__ __forceinline__ void stsm4t(uint32_t a, uint32_t r0, uint32_t r1, uint32_t r2, uint32_t r3) {
  asm volatile("stmatrix.sync.aligned.m8n8.x4.trans.shared.b16 [%0], {%1, %2, %3, %4};" ::"r"(a), "r"(r0), "r"(r1), "r"(r2), "r"(r3) : "memory");
}
__device__ __forceinline__ void ldsm4(uint32_t a, uint32_t& r0, uint32_t& r1, uint32_t& r2, uint32_t& r3) {
  asm volatile("ldmatrix.sync.aligned.m8n8.x4.shared.b16 {%0, %1, %2, %3}, [%4];" : "=r"(r0), "=r"(r1), "=r"(r2), "=r"(r3) : "r"(a) : "memory");
}
__device__ __forceinline__ void sts16(uint32_t a, uint32_t v) { asm volatile("st.shared.u16 [%0], %1;" ::"r"(a), "h"((uint16_t)v) : "memory"); }
__device__ __forceinline__ void mma16816(float& c0, float& c1, float& c2, float& c3, uint32_t a0, uint32_t a1, uint32_t a2, uint32_t a3,
                                         uint32_t b0, uint32_t b1) {
  asm volatile("mma.sync.aligned.m16n8k16.row.col.f32.bf16.bf16.f32 {%0, %1, %2, %3}, {%4, %5, %6, %7}, {%8, %9}, {%0, %1, %2, %3};"
               : "+f"(c0), "+f"(c1), "+f"(c2), "+f"(c3) : "r"(a0), "r"(a1), "r"(a2), "r"(a3), "r"(b0), "r"(b1));
}
__device__ __forceinline__ uint32_t sdesc(uint32_t addr, uint32_t lbo) { return (addr >> 4) + ((lbo >> 4) << 16); }
__device__ __forceinline__ uint64_t desc64(uint32_t lo, uint32_t hi) { uint64_t d; asm("mov.b64 %0, {%1, %2};" : "=l"(d) : "r"(lo), "r"(hi)); return d; }
__device__ __forceinline__ void dadd(uint64_t& d, uint32_t inc) {
  asm("{\n.reg .b32 l, h;\nmov.b64 {l, h}, %0;\nadd.u32 l, l, %1;\nmov.b64 %0, {l, h};\n}" : "+l"(d) : "r"(inc));
}

struct Ring {
  uint32_t slot, phase, xp;
  __device__ __forceinline__ void uniform() {
    slot = __shfl_sync(0xffffffffu, slot, 0); phase = __shfl_sync(0xffffffffu, phase, 0); xp = __shfl_sync(0xffffffffu, xp, 0);
  }
  __device__ __forceinline__ void next() { if (++slot == NS) { slot = 0; phase ^= 1; } }
  __device__ __forceinline__ void next_if(bool p) { slot += p; if (slot == NS) { slot = 0; phase ^= 1; } }
};
__device__ __forceinline__ uint32_t borrow(int ks, int n) {
  const int k = ks + 1;
  return k >= 4 && !(k & 2) && k < n ? k & 1 : 2;
}

constexpr uint32_t Q_RANGES = NBETA * NH + __builtin_popcount(EARLY_MASK) * 5, Q_ALL = NBETA * (NH + 5);
constexpr int NRANGE = NCTA / 5;
struct Work { int kind, mode, k0, nsteps, range, beta, sub; };
struct Sched { uint16_t queue[Q_ALL]; uint32_t piece[NRANGE + 1][4]; };
constexpr Sched make_sched() {
  Sched s{};
  int q = 0, a = 0;
  for (int t = 0, e = 0; a < NBETA * NH; t++) {
    for (; e < NBETA && 8 * (e & ~PAIRB) + PK <= t && a >= P_POS; e++)
      for (int col = 0; col < 5 && (EARLY_MASK >> e & 1); col++) s.queue[q++] = 0x8000 | (e & 1 ? 4 - col : col) << 8 | e;
    for (int b = 0; b < NBETA; b++)
      for (int h = 0; h < NH; h++)
        if ((b >= B_LATE && h >= H_LATE ? 300 + b + LATE_G * (h >> 2) : 8 * (b & ~PAIRB) + KG * (h >> 2)) == t) { s.queue[q++] = b << 5 | h; a++; }
  }
  for (int b = 0; b < NBETA; b++)
    for (int col = 0; col < 5 && !(EARLY_MASK >> b & 1); col++) s.queue[q++] = 0x8000 | col << 8 | b;
  constexpr uint32_t T[NRANGE * 2] = {PIECE_TABLE};
  for (int g = 0; g <= NRANGE; g++)
    for (int n = 0; n < 4; n++) s.piece[g][n] = g < NRANGE && n < 2 ? T[2 * g + n] : 2u << 30;
  return s;
}
__constant__ Sched c_sched = make_sched();
constexpr int N_EARLY = __builtin_popcount(EARLY_MASK);
constexpr bool reuse_ok() {
  const Sched s = make_sched();
  int first[NBETA + OR] = {};
  for (int q = Q_RANGES - 1; q >= 0; q--) if (!(s.queue[q] & 0x8000)) first[s.queue[q] >> 5] = q;
  for (int q = 0; q < Q_RANGES; q++) if ((s.queue[q] & 0x8000) && (s.queue[q] & 31) >= OR0 && q - first[(s.queue[q] & 31) + OR] > NCTA - 32) return false;
  return first[OR0 + OR] >= NCTA && P_POS >= NCTA;
}
static_assert(reuse_ok());
template <bool SIMPLE> __device__ __forceinline__ bool o_reuse(uint32_t b) { return !SIMPLE && b - (OR0 + OR) < N_EARLY - OR0; }
template <bool SIMPLE> __device__ __forceinline__ uint32_t o_slot(uint32_t b) { return o_reuse<SIMPLE>(b) ? OR0 + (b - OR0) % OR : b; }
__device__ __forceinline__ Work decode(uint32_t d) {
  Work w;
  w.kind = d >> 30; if (w.kind == 3) w.kind = 1;
  w.mode = (d >> 28) & 3; w.k0 = (d >> 22) & 63;
  if (w.kind == 0) { w.beta = (d >> 5) & 31; w.sub = d & 31; w.nsteps = DM / 64; }
  else { w.beta = d & 31; w.sub = (d >> 8) & 7; w.nsteps = ((d >> 16) & 63) + 1; }
  w.range = ((d >> 11) & 31) * 5 + w.sub;
  return w;
}

__device__ __forceinline__ bool reached(const unsigned* cnt, unsigned target) {
  unsigned v;
  asm volatile("ld.acquire.gpu.global.u32 %0, [%1];" : "=r"(v) : "l"(cnt) : "memory");
  return (int)(v - target) >= 0;
}
__device__ __forceinline__ void wait_count(const unsigned* cnt, unsigned target) {
  unsigned n = 0;
  while (!__all_sync(0xffffffffu, reached(cnt, target))) { if (++n > (1u << 24)) __trap(); }
}
__device__ __forceinline__ uint32_t lds(uint32_t a) { uint32_t v; asm volatile("ld.volatile.shared.u32 %0, [%1];" : "=r"(v) : "r"(a) : "memory"); return v; }

#define TRACE(u, e)
#define T3(u, e)
#define T2C(u, e)
#define T2P(u, r, e)
#define TTAIL(k)
#define TCLK(k)
#define TO -1
#define TRACE_O(k) if (TO == k) TRACE(i, 5)
#define TRACE_P(u, e)
#define TRACE_IN(u, e)

struct Ctx {
  uint32_t sb;
  int wg, warp;
  uint32_t mqk, mpv;
  bool lead;
  int lane0, lane;
  int src;
};
template <int N> __device__ __forceinline__ uint32_t dhi(uint32_t lo) { return 0x40000040u + (lo >> (26 + N)); }
__device__ __forceinline__ void release(const Ctx& c, uint32_t slot) {
  if (c.lead) mbar_arrive(c.sb + BAR_EMPTY + slot * 8);
}
__device__ __forceinline__ uint32_t acquire(const Ctx& c, Ring& r, bool have = false) {
  const uint32_t s = r.slot;
  if (!have) mbar_wait_w(c.sb + BAR_FULL + s * 8, r.phase);
  r.next();
  return s;
}
__device__ __forceinline__ void mbar_wait2_w(uint32_t b0, uint32_t p0, uint32_t b1, uint32_t p1) {
  uint32_t n = 0;
  while (!__all_sync(0xffffffffu, mbar_try(b0, p0) & mbar_try(b1, p1))) {
    if (++n > (1u << 22)) __trap();
  }
}
__device__ __forceinline__ void mbar_wait3_w(uint32_t b0, uint32_t p0, uint32_t b1, uint32_t p1, uint32_t b2, uint32_t p2) {
  uint32_t n = 0;
  while (!__all_sync(0xffffffffu, mbar_try(b0, p0) & mbar_try(b1, p1) & mbar_try(b2, p2))) {
    if (++n > (1u << 22)) __trap();
  }
}
__device__ __forceinline__ void acquire2(const Ctx& c, Ring& r, uint32_t& s0, uint32_t& s1, bool have = false) {
  const uint32_t p0 = r.phase;
  s0 = r.slot; r.next(); s1 = r.slot;
  if (!have) mbar_wait2_w(c.sb + BAR_FULL + s0 * 8, p0, c.sb + BAR_FULL + s1 * 8, r.phase);
  r.next();
}
template <int N>
__device__ __forceinline__ bool peek(const Ctx& c, Ring r) {
  bool ok = true;
#pragma unroll
  for (int k = 0; k < N; k++) { ok &= mbar_test(c.sb + BAR_FULL + r.slot * 8, r.phase); r.next(); }
  return ok;
}
__device__ __forceinline__ void staged(const Ctx& c, int part) {
  fence_async_smem();
  __syncwarp();
  mbar_arrive_warp(c.sb + BAR_STG + c.wg * 16 + part * 8);
}

template <int WG, bool FIRST, int H>
__device__ __forceinline__ void proj_half(const Ctx& c, float (&acc)[64], uint32_t w, uint32_t x, uint32_t sw) {
  uint64_t dx = desc64((SB0 + x * SLOT + (WG ? 0 : H * 8192)) >> 4, dhi<0>(x) + sw);
  uint64_t dw = desc64(WG ? (SB0 + w * SLOT + H * 8192) >> 4 : sdesc(SB0 + w * SLOT, 8192), dhi<1>(x));
  wg_fence();
  if (WG) { if (FIRST) wgmma_proj96_init(acc, dw, dx, 0); else wgmma_proj96(acc, dw, dx, 1); }
  else { if (FIRST) wgmma_proj_init(acc, dx, dw, 0); else wgmma_proj(acc, dx, dw, 1); }
#pragma unroll
  for (int k = 1; k < 4; k++) {
    dadd(dx, k == 2 ? 2 + (sw >> 30) * 28 : 2); dadd(dw, 128);
    if (WG) wgmma_proj96(acc, dw, dx, 1); else wgmma_proj(acc, dx, dw, 1);
  }
  wg_commit();
}

__device__ __forceinline__ void proj_store16(uint32_t a, const float* f, float sc) {
  stsm4t(a, pack_bf16(f[0] * sc, f[1] * sc), pack_bf16(f[2] * sc, f[3] * sc), pack_bf16(f[4] * sc, f[5] * sc), pack_bf16(f[6] * sc, f[7] * sc));
}

__device__ __forceinline__ uint32_t stage_off(const Ctx& c) {
  const int lane = c.lane, mi = lane >> 3, r8 = lane & 7;
  return ((mi >> 1) * 8 + r8) * 128 + (((2 * c.warp + (mi & 1)) ^ r8) << 4);
}
__device__ __forceinline__ uint32_t q3_swz(uint32_t r8) { return ((r8 & 3) << 1) | (r8 >> 2); }
template <int H>
__device__ __forceinline__ void stage_t2(const Ctx& c, const float (&a)[64], float sc) {
  const uint32_t base = c.sb + QBUF_OFF + 2 * 16384 + H * 8192 + stage_off(c);
#pragma unroll
  for (int jj = 0; jj < 4; jj++) proj_store16(base + jj * 2048, &a[jj * 8], sc);
}
template <int H, bool IS_Q>
__device__ __forceinline__ void stage_t3(const Ctx& c, const float (&a)[64], float sc) {
  const uint32_t off = stage_off(c), r8 = (off >> 7) & 7;
  const uint32_t t3 = c.sb + QBUF_OFF + 3 * 16384 + H * 4096 + (IS_Q ? off ^ ((r8 ^ q3_swz(r8)) << 4) : off);
  proj_store16(t3, &a[32], sc);
  proj_store16(t3 + 2048, &a[40], sc);
}

template <int WG, int h, int NW = 4>
__device__ __forceinline__ void load_part(const Ctx& c, Ring r, uint32_t (&q)[32]) {
  uint32_t n = 0;
  while (NW && !__all_sync(0xffffffffu, peek<NW>(c, r))) {
    if (++n > (1u << 26)) __trap();
  }
  const int lane = c.lane, mi = lane >> 3, r8 = lane & 7;
  if (WG) { r.next(); r.next(); }
  const uint32_t off = c.sb + (WG ? stage_off(c) : (16 * c.warp + (mi & 1) * 8 + r8) * 128), t0 = off + r.slot * SLOT;
  r.next();
  const uint32_t t1 = off + r.slot * SLOT;
#pragma unroll
    for (int jj = 0; jj < (WG ? 6 : 8); jj++) {
      uint32_t* p = &q[4 * jj];
      if (WG) asm volatile("ldmatrix.sync.aligned.m8n8.x4.trans.shared.b16 {%0, %1, %2, %3}, [%4];" : "=r"(p[0]), "=r"(p[1]), "=r"(p[2]), "=r"(p[3])
                           : "r"((jj < 4 ? t0 + h * 8192 : t1 + h * 4096) + (jj & 3) * 2048) : "memory");
      else ldsm4((h ? t1 : t0) + (jj >> 2) * 8192 + (((((2 * jj) & 7) + (mi >> 1)) ^ r8) << 4), p[0], p[1], p[2], p[3]);
    }
}
template <int WG>
__device__ __forceinline__ void add_part(const Ctx& c, const uint32_t (&q)[32], float (&a)[64]) {
  const uint32_t one = (c.lane >> 3) == (c.lane & 3) ? 0x3f80u << (c.lane & 4) * 4 : 0;
#pragma unroll
  for (int i = 0; i < (WG ? 12 : 16); i++)
    asm("mma.sync.aligned.m16n8k8.row.col.f32.bf16.bf16.f32 {%0, %1, %2, %3}, {%4, %5}, {%6}, {%0, %1, %2, %3};"
        : "+f"(a[4 * i]), "+f"(a[4 * i + 1]), "+f"(a[4 * i + 2]), "+f"(a[4 * i + 3]) : "r"(q[2 * i]), "r"(q[2 * i + 1]), "r"(one));
}

__device__ __forceinline__ void trace_dump(const Ctx& c) {
}
struct RowSum { float l0, l1; };
__device__ __forceinline__ const char* o_addr(uint32_t item, int row, int lane) {
  return reinterpret_cast<const char*>(g_o) + (((item >> 10) * (2 * SQ) + row) * 128 + (lane ^ (lane >> 3)) * 16);
}
__device__ __forceinline__ void o_stg(const char* p, int i, const uint32_t* q) {
  asm volatile("st.global.v4.b32 [%0], {%1, %2, %3, %4};"
               ::"l"(p + (i >> 1) * (SQ * 128) + (i & 1) * 512), "r"(q[0]), "r"(q[1]), "r"(q[2]), "r"(q[3]) : "memory");
}
template <int MODE, int I0 = 0, int NI = 4>
__device__ __forceinline__ void o_emit(const char* p, const float (&o)[64], float inv) {
#pragma unroll
  for (int i = I0; i < I0 + NI; i++) {
    uint32_t q[4];
#pragma unroll
    for (int j = 0; j < 4; j++) q[j] = pack_bf16(o[16 * i + 4 * j + 2 * MODE] * inv, o[16 * i + 4 * j + 2 * MODE + 1] * inv);
    o_stg(p, i, q);
  }
}
__device__ __forceinline__ void o_done(const Ctx& c) {
  __syncwarp();
  mbar_arrive_warp(c.sb + BAR_OUT);
  __syncwarp();
}
template <int WG>
__device__ __forceinline__ void o_first(const Ctx& c, uint32_t item, float (&o)[64], const RowSum& inv, uint32_t (&q)[32]) {
  const char* p = o_addr(item, WG ? 192 + 8 * c.warp : 64 + 16 * c.warp, c.lane);
  reg_fence(o);
#pragma unroll
  for (int j = 0; j < 16; j++) {
    if (WG) q[j] = pack_bf16((o[4 * j] + o[4 * j + 2]) * inv.l0, (o[4 * j + 1] + o[4 * j + 3]) * inv.l0);
    else q[j] = pack_bf16(o[4 * j] * inv.l0, o[4 * j + 1] * inv.l0);
    if (!WG && (j & 3) == 3 && (j >> 2) < 8 - LATE0) o_stg(p, j >> 2, q + j - 3);
  }
#pragma unroll
  for (int j = 0; j < 16; j++) {
    if (!WG) q[16 + j] = pack_bf16(o[4 * j + 2] * inv.l1, o[4 * j + 3] * inv.l1);
    if ((j & 3) == 3 && (j >> 2) < 4 - (WG ? LATE1 : LATE0)) o_stg(WG ? p : p + 1024, j >> 2, q + (WG ? 0 : 16) + j - 3);
  }
}
template <int WG>
__device__ __forceinline__ void o_rest(const Ctx& c, uint32_t item, uint32_t (&q)[32]) {
  const char* p = o_addr(item, WG ? 192 + 8 * c.warp : 64 + 16 * c.warp, c.lane);
#pragma unroll
  for (int i = WG ? 4 - LATE1 : 8 - LATE0; i < (WG ? 4 : 8); i++) o_stg(p + (i >> 2) * 1024, i & 3, q + 4 * i);
}
template <int K0, int K1>
__device__ __forceinline__ void o_piece(const Ctx& c, const char* p, int k, const float (&o)[64], const RowSum& inv) {
  constexpr int NI = 8 / O_STEPS, M = K0 * NI / 4;
  if constexpr (K1 - K0 == 1) {
    o_emit<M, K0 * NI % 4, NI>(p + M * 1024, o, M ? inv.l1 : inv.l0);
    if (K1 == O_STEPS) o_done(c);
  } else {
    if (k <= (K0 + K1) / 2) o_piece<K0, (K0 + K1) / 2>(c, p, k, o, inv); else o_piece<(K0 + K1) / 2, K1>(c, p, k, o, inv);
  }
}
template <int WG>
__device__ __forceinline__ void o_second(const Ctx& c, uint32_t item, int k, float (&o)[64], const RowSum& inv) {
  reg_fence(o);
  o_piece<0, O_STEPS>(c, o_addr(item, 128 * WG + 16 * c.warp, c.lane0 + (k >> 8)), k, o, inv);
}
template <int WG>
__device__ __forceinline__ void release_q(const Ctx& c) {
#pragma unroll
  for (int t = 0; t < 2; t++)
    if (c.lead) asm volatile("mbarrier.arrive.shared::cta.b64 _, [%0], 2;" ::"r"(c.sb + BAR_EMPTY + (NS + 2 * WG + t) * 8) : "memory");
  __syncwarp();
}
struct Slots { uint32_t w, x, o, po; };
template <int WG>
__device__ __forceinline__ void acc_fence(float (&a)[64]) {
#pragma unroll
  for (int i = 0; i < (WG ? 48 : 64); i++) asm volatile("" : "+f"(a[i])::"memory");
}
template <int WG>
__device__ __forceinline__ void begin_acquire(const Ctx& c, Ring& r, Slots& h, bool wait) {
  const uint32_t s0 = r.slot, p0 = r.phase, f = c.sb + BAR_FULL;
  r.next();
  const uint32_t p1 = r.phase;
  h.w = r.slot; r.next();
  h.x = WG ? r.slot : s0; h.o = WG ? s0 : r.slot; h.po = r.phase;
  if (wait) { if (WG) mbar_wait3_w(f + s0 * 8, p0, f + h.w * 8, p1, f + h.x * 8, r.phase); else mbar_wait2_w(f + s0 * 8, p0, f + h.w * 8, p1); }
  r.next();
}
template <int WG>
__device__ __forceinline__ void proj_begin(const Ctx& c, Ring& r, float (&a0)[64], Slots& h, bool wait, uint32_t sw) {
  begin_acquire<WG>(c, r, h, wait);
  proj_half<WG, true, 0>(c, a0, h.w, h.x, sw);
  if (WG) release(c, h.o);
}
template <int WG>
__device__ __forceinline__ void proj_main(Ctx& c, Ring& r, float (&a0)[64], float (&a1)[64], Slots& h, int n, uint32_t sw, int unit,
                                          uint32_t item, int nq, float (&o1)[64], const RowSum& inv) {
  constexpr bool DEEP = (PDEPTH >> WG) & 1;
  T2C(unit, 3);
  int ks = 1;
#pragma unroll 1
  do {
    const Slots p = h;
    const uint32_t b = borrow(ks, n), tile = NS + (WG ? 3 - b : b), f = c.sb + BAR_FULL;
    const uint32_t s0 = b != 2 ? tile : r.slot, p0 = b != 2 ? (r.xp >> b) & 1 : r.phase;
    r.next_if(b == 2);
    const uint32_t p1 = r.phase;
    h.w = r.slot; r.next();
    const uint32_t s2 = b != 2 ? tile : r.slot;
    h.po = b != 2 ? p0 : r.phase;
    r.next_if(b == 2);
    r.xp ^= 1 << b;
    h.x = WG ? s2 : s0; h.o = WG ? s0 : s2;
    mbar_wait3_w(f + s0 * 8, p0, f + h.w * 8, p1, f + (WG ? s2 : p.o) * 8, WG ? h.po : p.po);
    if (ks < 10) T2C(unit, ks * 4);
    if (DEEP) {
      proj_half<WG, false, 0>(c, a0, h.w, h.x, sw);
      release(c, WG ? h.o : p.o);
      if (ks < 10) T2C(unit, ks * 4 + 1);
      wg_wait<1>();
      if (ks < 10) T2C(unit, ks * 4 + 2);
      release(c, p.x); release(c, p.w);
    } else {
      release(c, WG ? h.o : p.o);
      wg_wait<0>();
      release(c, p.x); release(c, p.w);
      if (ks < 10) T2C(unit, ks * 4 + 1);
      proj_half<WG, false, 0>(c, a0, h.w, h.x, sw);
      if (ks < 10) T2C(unit, ks * 4 + 2);
    }
    proj_half<WG, false, 1>(c, a1, h.w, h.x, sw);
    if (ks < 10) T2C(unit, ks * 4 + 3);
    if (ks <= nq) o_second<WG>(c, item, ks, o1, inv);
  } while (++ks != n);
  {
    const uint32_t e0 = c.sb + BAR_EMPTY + (NS + 3 * WG) * 8, e1 = c.sb + BAR_EMPTY + (NS + 1 + WG) * 8;
    const uint32_t p0 = (r.xp ^ unit ^ 1) & 1, p1 = ((r.xp >> 1) ^ unit ^ 1) & 1;
    const uint32_t k0 = sw ? e0 : c.sb + BAR_FULL + r.slot * 8, pk = sw ? p0 : r.phase;
    uint32_t cnt = 0;
    while (!__all_sync(0xffffffffu, mbar_try(e0, p0) & mbar_try(e1, p1) & mbar_try(k0, pk) & (WG || mbar_try(c.sb + BAR_FULL + h.o * 8, h.po)))) {
      if (++cnt > (1u << 22)) __trap();
    }
  }
  c.lane = c.lane0 + (h.w >> 5);
  if (!WG) release(c, h.o);
}
template <int WG>
__device__ __forceinline__ void proj_end(const Ctx& c, float (&a1)[64], const Slots& h) {
  wg_wait<0>();
  acc_fence<WG>(a1);
  release(c, h.x); release(c, h.w);
}
__device__ __forceinline__ uint32_t get_desc(const Ctx& c, int i) {
  uint32_t d;
  mbar_wait_w(c.sb + BAR_DESC, (i - 1) & 1);
  asm volatile("ld.volatile.shared.u32 %0, [%1];" : "=r"(d) : "r"(c.sb + DESC_OFF + (i & 3) * 4) : "memory");
  return __shfl_sync(0xffffffffu, d, 0);
}

__device__ __forceinline__ float quad_max(float x) {
  x = fmaxf(x, __shfl_xor_sync(0xffffffffu, x, 1));
  return fmaxf(x, __shfl_xor_sync(0xffffffffu, x, 2));
}
__device__ __forceinline__ float quad_sum(float x) {
  x += __shfl_xor_sync(0xffffffffu, x, 1);
  return x + __shfl_xor_sync(0xffffffffu, x, 2);
}
template <bool SP, bool FIRST>
__device__ __forceinline__ void exps(const Ctx& c, const float (&s)[32], uint32_t (&p)[SP ? 8 : 16], RowSum& st) {
  if constexpr (SP) {
    uint32_t q[8];
    float t;
#pragma unroll
    for (int j = 0; j < 8; j++) {
      const float e0 = ex2(s[4 * j] + s[4 * j + 2]), e1 = ex2(s[4 * j + 1] + s[4 * j + 3]);
      if (j == 0) t = e0 + e1; else t += e0 + e1;
      q[j] = pack_bf16(e0, e1);
    }
    const bool odd = c.src & 2;
#pragma unroll
    for (int g = 0; g < 4; g++) {
      p[2 * g] = __shfl_sync(0xffffffffu, odd ? q[2 * g + 1] : q[2 * g], c.src);
      p[2 * g + 1] = __shfl_sync(0xffffffffu, odd ? q[2 * g] : q[2 * g + 1], c.src ^ 1);
    }
    st.l0 = FIRST ? t : st.l0 + t;
  } else {
    float t0, t1;
#pragma unroll
    for (int j = 0; j < 8; j++) {
      const float e0 = ex2(s[4 * j]), e1 = ex2(s[4 * j + 1]), e2 = ex2(s[4 * j + 2]), e3 = ex2(s[4 * j + 3]);
      if (j == 0) { t0 = e0 + e1; t1 = e2 + e3; } else { t0 += e0 + e1; t1 += e2 + e3; }
      p[2 * j] = pack_bf16(e0, e1);
      p[2 * j + 1] = pack_bf16(e2, e3);
    }
    st.l0 = FIRST ? t0 : st.l0 + t0;
    st.l1 = FIRST ? t1 : st.l1 + t1;
  }
}
template <bool SP>
__device__ __forceinline__ bool finish_sums(RowSum& st) {
  const float a = quad_sum(st.l0), b = SP ? a : quad_sum(st.l1);
  st.l0 = __fdividef(1.f, a); st.l1 = __fdividef(1.f, b);
  return !(a >= SUM_LO && a <= SUM_HI && b >= SUM_LO && b <= SUM_HI);
}
template <bool SP, bool INIT, int SITE, bool COMMIT = true, int RM = 0>
__device__ __forceinline__ void issue_qk(const Ctx& c, float (&s)[32], const uint32_t (&qs)[32], uint32_t dq, uint32_t dk) {
  uint64_t a = desc64(dq, dhi<SITE & 1>(dk)), b = desc64(dk, dhi<1 - (SITE & 1)>(dk) + 64);
  if (SP) {
    if (INIT) wgmma_qk_sp_init(s, qs[0], qs[1], qs[2], qs[3], b, 0, c.mqk); else wgmma_qk_sp(s, qs[0], qs[1], qs[2], qs[3], b, 0, c.mqk);
#pragma unroll
    for (int k = 1; k < 4; k++) { dadd(b, k == 2 ? 60 : 4); wgmma_qk_sp(s, qs[4 * k], qs[4 * k + 1], qs[4 * k + 2], qs[4 * k + 3], b, 1, c.mqk); }
  } else {
    if (RM & 1) wgmma_qk_rs(s, qs[0], qs[1], qs[2], qs[3], b, 0); else if (INIT) wgmma_qk_init(s, a, b, 0); else wgmma_qk(s, a, b, 0);
#pragma unroll
    for (int k = 1; k < 8; k++) {
      dadd(a, k == 4 ? 506 : 2); dadd(b, k == 4 ? 58 : 2);
      if (RM >> k & 1) wgmma_qk_rs(s, qs[4 * k], qs[4 * k + 1], qs[4 * k + 2], qs[4 * k + 3], b, 1); else wgmma_qk(s, a, b, 1);
    }
  }
  if (COMMIT) wg_commit();
}
template <bool SP, bool ACC, int SITE, bool SPLIT = false>
__device__ __forceinline__ void issue_pv(const Ctx& c, float (&o)[64], const uint32_t (&p)[SP ? 8 : 16], uint32_t dv) {
  uint64_t b = desc64(dv, dhi<SITE & 1>(dv) + 64);
  if constexpr (SP) {
    if (ACC) wgmma_pv_sp(o, p[0], p[1], p[2], p[3], b, 1, c.mpv); else wgmma_pv_sp_init(o, p[0], p[1], p[2], p[3], b, 0, c.mpv);
    if (SPLIT) wg_commit();
    dadd(b, 512);
    wgmma_pv_sp(o, p[4], p[5], p[6], p[7], b, 1, c.mpv);
  } else {
    if (ACC) wgmma_pv(o, p[0], p[1], p[2], p[3], b, 1); else wgmma_pv_init(o, p[0], p[1], p[2], p[3], b, 0);
#pragma unroll
    for (int k = 1; k < 4; k++) { dadd(b, 256); wgmma_pv(o, p[4 * k], p[4 * k + 1], p[4 * k + 2], p[4 * k + 3], b, 1); }
  }
  wg_commit();
}
__device__ __forceinline__ void pack_rows(const float (&o)[64], float sc, uint32_t (&q)[32]) {
#pragma unroll
  for (int j = 0; j < 32; j++) q[j] = pack_bf16(o[2 * j] * sc, o[2 * j + 1] * sc);
}
template <int MASK = 255>
__device__ __forceinline__ void stage_rows(const Ctx& c, uint32_t tile_addr, const uint32_t (&q)[32]) {
  const int lane = c.lane, mi = lane >> 3, r8 = lane & 7;
  const uint32_t row_addr = tile_addr + (16 * c.warp + (mi & 1) * 8 + r8) * 128;
#pragma unroll
  for (int jj = 0; jj < 8; jj++)
    if (MASK >> jj & 1) stsm4(row_addr + (jj >> 2) * 8192 + (((((2 * jj) & 7) + (mi >> 1)) ^ r8) << 4), q[4 * jj], q[4 * jj + 1], q[4 * jj + 2], q[4 * jj + 3]);
}
__device__ __forceinline__ void stage_rows(const Ctx& c, uint32_t tile_addr, const float (&o)[64], float sc) {
  uint32_t q[32];
  pack_rows(o, sc, q);
  stage_rows(c, tile_addr, q);
}
template <int WG, int H>
__device__ __forceinline__ void stage_out(const Ctx& c, const float (&a)[64]) {
  if (WG) { stage_t3<H, false>(c, a, 1.f); if (H) staged(c, 0); stage_t2<H>(c, a, 1.f); }
  else stage_rows(c, c.sb + QBUF_OFF + H * 16384, a, 1.f);
  if (H || !WG) staged(c, H);
}
template <int SITE>
__device__ __forceinline__ void issue_qk_rs(float (&s)[32], uint32_t (&q)[32], uint32_t dk) {
  uint64_t b = desc64(dk, dhi<SITE>(dk) + 64);
  reg_fence(q);
  wg_fence();
  wgmma_qk_rs_init(s, q[0], q[1], q[2], q[3], b, 0);
#pragma unroll
  for (int k = 1; k < 8; k++) { dadd(b, k == 4 ? 58 : 2); wgmma_qk_rs(s, q[4 * k], q[4 * k + 1], q[4 * k + 2], q[4 * k + 3], b, 1); }
  wg_commit();
}

__device__ __forceinline__ void redo_tile(const Ctx& c, uint32_t q_addr, uint32_t half, const __nv_bfloat16* kp, const __nv_bfloat16* vp,
                                          uint32_t item, int row) {
  float o[64];
  const int lane = lane_now(), g = lane >> 2, cc = lane & 3, mi = lane >> 3, r8 = lane & 7;
  const uint32_t qa = q_addr + (half == 4096 ? 8 * c.warp + r8 : 16 * c.warp + (mi & 1) * 8 + r8) * 128, swz = half == 4096 ? q3_swz(r8) : r8;
  const uint32_t* kq = reinterpret_cast<const uint32_t*>(kp + g * DH) + cc;
  const unsigned short* vq = reinterpret_cast<const unsigned short*>(vp + 2 * cc * DH) + g;
  float m0 = -INFINITY, m1 = -INFINITY, l0 = 0.f, l1 = 0.f;
#pragma unroll
  for (int i = 0; i < 64; i++) o[i] = 0.f;
#pragma unroll 1
  for (int kb = 0; kb < SK / 16; kb++) {
    float z[8] = {0.f, 0.f, 0.f, 0.f, 0.f, 0.f, 0.f, 0.f};
#pragma unroll 2
    for (int kk = 0; kk < 8; kk++) {
      uint32_t a0, a1, a2, a3;
      ldsm4(qa + (kk >> 2) * half + ((((kk & 3) * 2 + (mi >> 1)) ^ swz) << 4), a0, a1, a2, a3);
      const uint32_t* kr = kq + kb * (16 * DH / 2) + kk * 8;
      mma16816(z[0], z[1], z[2], z[3], a0, a1, a2, a3, __ldg(kr), __ldg(kr + 4));
      mma16816(z[4], z[5], z[6], z[7], a0, a1, a2, a3, __ldg(kr + 8 * DH / 2), __ldg(kr + 8 * DH / 2 + 4));
    }
    const float n0 = fmaxf(m0, quad_max(fmaxf(fmaxf(z[0], z[1]), fmaxf(z[4], z[5]))));
    const float n1 = fmaxf(m1, quad_max(fmaxf(fmaxf(z[2], z[3]), fmaxf(z[6], z[7]))));
    const float al0 = ex2(m0 - n0), al1 = ex2(m1 - n1);
    m0 = n0; m1 = n1;
#pragma unroll
    for (int i = 0; i < 8; i++) z[i] = ex2(z[i] - ((i & 2) ? n1 : n0));
    l0 = l0 * al0 + (z[0] + z[1]) + (z[4] + z[5]);
    l1 = l1 * al1 + (z[2] + z[3]) + (z[6] + z[7]);
    const uint32_t a0 = pack_bf16(z[0], z[1]), a1 = pack_bf16(z[2], z[3]), a2 = pack_bf16(z[4], z[5]), a3 = pack_bf16(z[6], z[7]);
    const unsigned short* vr = vq + kb * (16 * DH);
#pragma unroll
    for (int nb = 0; nb < 16; nb++) {
      o[4 * nb] *= al0; o[4 * nb + 1] *= al0; o[4 * nb + 2] *= al1; o[4 * nb + 3] *= al1;
      const uint32_t b0 = __ldg(vr + nb * 8) | ((uint32_t)__ldg(vr + nb * 8 + DH) << 16);
      const uint32_t b1 = __ldg(vr + nb * 8 + 8 * DH) | ((uint32_t)__ldg(vr + nb * 8 + 9 * DH) << 16);
      mma16816(o[4 * nb], o[4 * nb + 1], o[4 * nb + 2], o[4 * nb + 3], a0, a1, a2, a3, b0, b1);
    }
  }
  const char* p = o_addr(item, row, lane);
  o_emit<0>(p, o, __fdividef(1.f, quad_sum(l0)));
  o_emit<1>(half == 4096 ? p : p + 1024, o, __fdividef(1.f, quad_sum(l1)));
}

template <bool SPA, bool SPB, int SITE, int ID>
__device__ __forceinline__ void batch(const Ctx& c, float (&s)[32], const uint32_t (&qs)[32], uint32_t dq, uint32_t dk, float (&ob)[64],
                                      uint32_t (&pb)[SPB ? 8 : 16], uint32_t dv) {
  if constexpr (SPA) {
    reg_fence(pb);
    wg_fence();
    issue_pv<SPB, true, ID>(c, ob, pb, dv);
    issue_qk<SPA, false, ID>(c, s, qs, dq, dk);
  } else {
    constexpr bool EARLY = ((QK_EARLY_MASK >> (SITE + (SPB ? 2 : 0))) & 1) != 0;
    if (!EARLY) reg_fence(pb);
    wg_fence();
    issue_qk<SPA, false, ID, !SPB, SITE ? RM0 : SPB ? RM2 : RM1>(c, s, qs, dq, dk);
    if (EARLY) { reg_fence(pb); wg_fence(); }
    issue_pv<SPB, true, ID, SPB>(c, ob, pb, dv);
  }
}

template <bool SP0>
__device__ __forceinline__ bool attention(Ctx& c, Ring& r, int unit, uint32_t& d, const float (&a0)[64], float (&o0)[64], float (&o1)[64],
                                          RowSum& st0, RowSum& st1, const Slots& h, uint32_t (&q1)[32]) {
  constexpr bool SP1 = false;
  if (SP0) { c.mqk = META_QK + (d >> 28); c.mpv = META_PV + (d >> 28); asm volatile("" : "+r"(c.mqk), "+r"(c.mpv)); }
  if (SP0) c.src = (c.lane & 28) | ((c.lane & 1) << 1) | ((c.lane >> 1) & 1);
  float s[32];
  uint32_t p0[SP0 ? 8 : 16], p1[16];
  const uint32_t q0a = c.sb + QBUF_OFF + (SP0 ? 3 : 0) * 16384, q1a = c.sb + QBUF_OFF + (SP0 ? 2 : 1) * 16384;
  const uint32_t dq0 = sdesc(SB0 + QBUF_OFF, 0), dq1 = sdesc(SB0 + QBUF_OFF + (SP0 ? 2 : 1) * 16384, 0);
  uint32_t sk = acquire(c, r, true), sv, sn;
  uint32_t qs[32];
  float s1[32];
  if (SP0) {
    stage_t3<0, true>(c, a0, SM_C);
    stage_t2<0>(c, a0, SM_C);
    proj_end<1>(c, o0, h);
    stage_t3<1, true>(c, o0, SM_C);
    stage_t2<1>(c, o0, SM_C);
    bar_sync(5, 128);
    const int g = c.lane >> 2, cc = c.lane & 3;
    const uint32_t qa = q0a + (8 * c.warp + g) * 128 + (cc & 1) * 8;
#pragma unroll
    for (int k = 0; k < 8; k++)
      asm volatile("ld.shared.v2.u32 {%0, %1}, [%2];" : "=r"(qs[2 * k]), "=r"(qs[2 * k + 1])
                   : "r"(qa + (k >> 2) * 4096 + ((((k & 3) * 2 + (cc >> 1)) ^ q3_swz(g)) << 4)) : "memory");
    fence_async_smem();
    bar_sync(1, 256);
    TRACE(unit, 2);
    wg_fence();
    issue_qk<SP1, true, 1>(c, s1, qs, dq1, sdesc(SB0 + sk * SLOT, 0));
#pragma unroll
    for (int k = 0; k < 8; k++)
      if (RM2 >> k & 1) ldsm4(q1a + (k >> 2) * 8192 + (16 * c.warp + (c.lane & 15)) * 128 + (((2 * (k & 3) + (c.lane >> 4)) ^ (c.lane & 7)) << 4),
                              q1[4 * k], q1[4 * k + 1], q1[4 * k + 2], q1[4 * k + 3]);
#pragma unroll
    for (int k = 0; k < 16; k++) asm volatile("" : "+r"(qs[k])::"memory");
    wg_fence();
    issue_qk<SP0, true, 0>(c, s, qs, dq0, sdesc(SB0 + sk * SLOT, 0));
    const bool have = peek<2>(c, r);
    wg_wait<1>();
    reg_fence(s1);
    exps<SP1, true>(c, s1, p1, st1);
    sched_fence<11>(sk, p1);
    acquire2(c, r, sv, sn, __all_sync(0xffffffffu, have));
    wg_wait<0>();
    wg_fence();
    issue_pv<SP1, false, 1>(c, o1, p1, sdesc(SB0 + sv * SLOT, 1024));
    if (LAG_BAR & 1) asm volatile("bar.arrive 4, 256;" ::: "memory");
    sched_fence<12>(sk, s);
    release(c, sk);
    sk = sn;
    exps<SP0, true>(c, s, p0, st0);
    reg_fence(p0);
    wg_fence();
    issue_pv<SP0, false, 0>(c, o0, p0, sdesc(SB0 + sv * SLOT, 1024));
    issue_qk<SP0, true, 2>(c, s, qs, dq0, sdesc(SB0 + sk * SLOT, 0));
    sn = acquire(c, r);
    wg_wait<0>();
    reg_fence(s);
  } else {
    pack_rows(a0, SM_C, qs);
    stage_rows(c, q0a, qs);
    proj_end<0>(c, o1, h);
    TRACE(unit, 2);
    float sc = SM_C;
    issue_qk_rs<0>(s, qs, sdesc(SB0 + sk * SLOT, 0));
    sched_fence<0>(sk, sc);
    pack_rows(o1, sc, q1);
    stage_rows<~RM1>(c, q1a, q1);
    issue_qk_rs<1>(s1, q1, sdesc(SB0 + sk * SLOT, 0));
    asm volatile("bar.arrive 1, 256;" ::: "memory");
    bool have = peek<2>(c, r);
    wg_wait<1>();
    reg_fence(s);
    exps<SP0, true>(c, s, p0, st0);
    sched_fence<1>(sk, p0);
    acquire2(c, r, sv, sn, __all_sync(0xffffffffu, have));
    wg_wait<0>();
    reg_fence(s1);
    fence_async_smem();
    __syncwarp();
    wg_fence();
    issue_qk<SP0, false, 2, true, RM0>(c, s, qs, dq0, sdesc(SB0 + sn * SLOT, 0));
    issue_pv<SP0, false, 0>(c, o0, p0, sdesc(SB0 + sv * SLOT, 1024));
    sched_fence<2>(sk, s1);
    release(c, sk);
    have = peek<1>(c, r);
    sk = sn;
    exps<SP1, true>(c, s1, p1, st1);
    reg_fence(p1);
    wg_fence();
    issue_pv<SP1, false, 1>(c, o1, p1, sdesc(SB0 + sv * SLOT, 1024));
    sn = acquire(c, r, __all_sync(0xffffffffu, have));
    if (LAG_BAR & 1) bar_sync(4, 256);
    wg_wait<1>();
    reg_fence(s);
  }
  TRACE_IN(unit, 4);
  T2C(unit, 51);
#pragma unroll 1
  for (int j = 1; j < 15; j++) {
    const uint32_t sv_prev = sv, sk_prev = sk;
    sv = sn;
    const uint32_t dv = sdesc(SB0 + sv * SLOT, 1024);
    reg_fence(p0);
    exps<SP0, false>(c, s, p0, st0);
    batch<SP1, SP0, 0, 3>(c, s, q1, dq1, sdesc(SB0 + sk * SLOT, 0), o0, p0, dv);
    sk = acquire(c, r);
    wg_wait<1>();
    reg_fence(s); reg_fence(p1);
    release(c, sv_prev); release(c, sk_prev);
    exps<SP1, false>(c, s, p1, st1);
    batch<SP0, SP1, 1, 4>(c, s, qs, dq0, sdesc(SB0 + sk * SLOT, 0), o1, p1, dv);
    sn = acquire(c, r);
    if (SP0) wg_wait<0>(); else wg_wait<1>();
    reg_fence(s);
  }
  TRACE_IN(unit, 5);
  T2C(unit + 1, 52);
  const uint32_t sv_prev = sv;
  sv = sn;
  const uint32_t dv = sdesc(SB0 + sv * SLOT, 1024);
  reg_fence(p0);
  exps<SP0, false>(c, s, p0, st0);
  batch<SP1, SP0, 0, 5>(c, s, q1, dq1, sdesc(SB0 + sk * SLOT, 0), o0, p0, dv);
  asm volatile("ld.volatile.shared.u32 %0, [%1];" : "=r"(d) : "r"(c.sb + DESC_OFF + ((unit + 1) & 3) * 4) : "memory");
  const bool have = peek<2 + SP0>(c, r);
  wg_wait<1>();
  reg_fence(s); reg_fence(p1);
  release(c, sv_prev); release(c, sk);
  exps<SP1, false>(c, s, p1, st1);
  reg_fence(p1);
  wg_fence();
  issue_pv<SP1, true, 2>(c, o1, p1, dv);
  if (SP0) sched_fence<6>(sk, st0.l0, st1.l0, st1.l1); else sched_fence<5>(sk, st0.l0, st0.l1, st1.l0, st1.l1);
  c.lane = c.lane0 + (sk >> 5);
  const bool bad = finish_sums<SP0>(st0) | finish_sums<SP1>(st1);
  uint32_t any;
  asm volatile("{\n.reg .pred p, q;\nsetp.ne.u32 p, %1, 0;\nbar.red.or.pred q, %2, 128, p;\nselp.u32 %0, 1, 0, q;\n}"
               : "=r"(any) : "r"((uint32_t)bad), "n"(2 + SP0) : "memory");
  any = __any_sync(0xffffffffu, any);
  d = __shfl_sync(0xffffffffu, d, 0);
  if (d < (2u << 30) && !__all_sync(0xffffffffu, have)) { Ring t = r; Slots u; begin_acquire<SP0>(c, t, u, true); }
  wg_wait<0>();
  reg_fence(o0); reg_fence(o1);
  release(c, sv);
  return any;
}

template <int WG>
__device__ __forceinline__ void consumer(Ctx c, const __nv_bfloat16* const* kv) {
  asm volatile("setmaxnreg.inc.sync.aligned.u32 %0;" ::"n"(WG ? REG_C : 504 - REG_C - REG_P));
  c.wg = WG;
  Ring r{0, 0, 0};
  float a0[64], a1[64], o1[64];
  Slots h;
  RowSum inv0, inv1;
  uint32_t oq[32];
  uint32_t d = c_sched.queue[blockIdx.x] * 1025, dc = 0, sw;
  int i = 0, nq;
begin:
  sw = d & (1u << 30);
  proj_begin<WG>(c, r, a0, h, true, sw);
  proj_half<WG, true, 1>(c, a1, h.w, h.x, sw);
  nq = 0;
#pragma unroll
  for (int k = 0; k < 64; k++) asm volatile("" : "=f"(o1[k]));
  asm volatile("" : "=f"(inv1.l0), "=f"(inv1.l1));
  while (true) {
    TRACE(i, 0); TRACE(i, 6);
    proj_main<WG>(c, r, a0, a1, h, d >> 30 ? ((d >> 16) & 63) + 1 : DM / 64, sw, i, dc, nq, o1, inv1);
    dc = d;
    TRACE(i, 1);
    if (d >> 30) goto out_tile;
    wg_wait<1>();
    acc_fence<WG>(a0);
    if (WG ? attention<WG>(c, r, i, d, a0, a1, o1, inv0, inv1, h, oq) : attention<WG>(c, r, i, d, a0, o1, a1, inv1, inv0, h, oq)) goto redo;
    if (d >= (2u << 30)) break;
    sw = d & (1u << 30);
    proj_begin<WG>(c, r, a0, h, false, sw);
    release_q<WG>(c);
    if (WG) sched_fence<8>(h.w, inv0.l0); else sched_fence<7>(h.w, inv0.l0, inv0.l1);
    o_first<WG>(c, dc, a1, inv0, oq);
    sched_fence<9>(h.w, inv1.l0);
    proj_half<WG, true, 1>(c, a1, h.w, h.x, sw);
    o_rest<WG>(c, dc, oq);
    nq = O_STEPS;
    TRACE(i, 3); TRACE(i, 7);
    i++;
  }
  release_q<WG>(c);
  o_first<WG>(c, dc, a1, inv0, oq);
  o_rest<WG>(c, dc, oq);
#pragma unroll
  for (int k = 1; k <= O_STEPS; k++) o_second<WG>(c, dc, k, o1, inv1);
next:
  TRACE(i, 3); TRACE(i, 7);
  if ((d >> 30) != 2) {
    i++;
    r.uniform();
    goto begin;
  }
  trace_dump(c);
  return;
out_tile:
  if (d & 96) goto finish;
  d = get_desc(c, i + 1);
  wg_wait<1>();
  acc_fence<WG>(a0);
  TRACE_O(0);
  stage_out<WG, 0>(c, a0);
  TRACE_O(1);
  proj_end<WG>(c, a1, h);
  TRACE_O(2);
  stage_out<WG, 1>(c, a1);
  TRACE(i, 2);
  goto next;
finish:
  {
    uint32_t q[32];
#pragma unroll 1
    for (int k = (d >> 5) & 3; k > 1; k--) {
      wg_wait<0>();
      acc_fence<WG>(a0); acc_fence<WG>(a1);
      if (k == ((d >> 5) & 3)) { release(c, h.x); release(c, h.w); }
      load_part<WG, 0>(c, r, q); add_part<WG>(c, q, a0);
      load_part<WG, 1, 0>(c, r, q); add_part<WG>(c, q, a1);
#pragma unroll
      for (int t = 0; t < 4; t++) { release(c, r.slot); r.next(); }
    }
    load_part<WG, 0, WG ? 4 : 1>(c, r, q);
    wg_wait<1>();
    acc_fence<WG>(a0);
    TRACE_O(0);
    add_part<WG>(c, q, a0);
    stage_out<WG, 0>(c, a0);
    TRACE_O(1);
    load_part<WG, 1, WG ? 0 : 2>(c, r, q);
    wg_wait<0>();
    acc_fence<WG>(a1);
    TRACE_O(2);
    add_part<WG>(c, q, a1);
    stage_out<WG, 1>(c, a1);
    TRACE(i, 2); TRACE(i, 3); TRACE(i, 7);
    trace_dump(c);
    return;
  }
redo:
  {
    if (!WG) { stage_rows<RM1>(c, c.sb + QBUF_OFF + 16384, oq); __syncwarp(); }
    const size_t hoff = (size_t)(dc & 511) * (SK * DH);
    const int br = (dc >> 9) & 1;
#pragma unroll 1
    for (int part = 0; part < 2; part++) {
      const int t = WG ? 3 - part : part;
      redo_tile(c, c.sb + QBUF_OFF + t * 16384, t == 3 ? 4096 : 8192, kv[br] + hoff, kv[2 + br] + hoff, dc,
                t * 64 + (t == 3 ? 8 : 16) * c.warp);
    }
    o_done(c);
    release_q<WG>(c);
  }
  goto next;
}

template <bool SIMPLE>
__global__ void __launch_bounds__(384, 1) mha_fused_kernel(const __grid_constant__ Params P) {
  extern __shared__ __align__(1024) uint8_t smem_raw[];
  const uint32_t sbase = smem_u32(smem_raw);
  const int tid = threadIdx.x;
  const int wg = __shfl_sync(0xffffffffu, tid >> 7, 0);
  const int warp = __shfl_sync(0xffffffffu, (tid >> 5) & 3, 0);
  const int lane = tid & 31;
  const int cta = blockIdx.x;
  constexpr bool PAIR = !SIMPLE;

  if (tid == 0) T3(15, 0);
  if (tid == 0) TTAIL(7);
  uint16_t q0;
  asm volatile("ld.const.u16 %0, [%1];" : "=h"(q0) : "l"(__cvta_generic_to_constant(&c_sched.queue[cta + (lane & 1)])));
  const int wi = wg * 4 + warp;
  asm volatile(ELECT "prefetch.tensormap [%0];\n}" ::"l"(&P.x[0][0] + wi) : "memory");
  if ((sbase & 0xffffff) != SB0) __trap();
  if (wg < 2) {
#pragma unroll 1
    for (int b = BAR_OFF + wi * 8; b < DESC_OFF; b += 64)
      asm volatile(ELECT "mbarrier.init.shared::cta.b64 [%0], %1;\n}"
                   ::"r"(sbase + b), "r"(b < BAR_EMPTY || b >= BAR_DESC ? 1 : b >= BAR_STG && b < BAR_OUT ? 4 : 8) : "memory");
    asm volatile("fence.mbarrier_init.release.cluster;" ::: "memory");
    if (wi < 6) asm volatile(ELECT "prefetch.tensormap [%0];\n}" ::"l"(&P.x[0][0] + 12 + wi) : "memory");
  }
  if (PAIR) asm volatile("barrier.cluster.arrive.relaxed.aligned;" ::: "memory"); else __syncthreads();
#define INIT_DONE() if (PAIR) asm volatile("barrier.cluster.wait.aligned;" ::: "memory")

  if (wg == 2) {
    asm volatile("setmaxnreg.dec.sync.aligned.u32 %0;" ::"n"(REG_P));
    if (warp == 1) {
      const uint32_t qb = sbase + QBUF_OFF;
      const uint32_t ep = __shfl_sync(0xffffffffu, *(volatile unsigned*)&g_epoch + 1, 0);
      asm volatile("st.volatile.shared.u32 [%0], %1;" ::"r"(sbase + EPOCH_OFF), "r"(ep) : "memory");
      INIT_DONE();
      uint32_t dc = __shfl_sync(0xffffffffu, (uint32_t)q0, 0), qi = 0, piece = 0, na = 0;
      TTAIL(0);
      for (int i = 0; (dc >> 30) != 2; i++) {
        if (!(dc >> 30) && o_reuse<SIMPLE>((dc >> 5) & 31)) {
          const unsigned* rd = &g_rd[0][0] + ((dc & 1023) >> 2) - OR * 8;
          for (uint32_t n = 0; !__all_sync(0xffffffffu, reached(rd, ep * 5)); __nanosleep(300)) if (++n > (1u << 22)) __trap();
        }
        mbar_wait_w(sbase + BAR_GO, i & 1);
        if (piece == 0) {
          if (PAIR && (cta & 1)) {
            asm volatile(ELECT EXPECT("%0", "4") "mbarrier.arrive.shared::cluster.b64 _, [%1];\n}" ::"r"(sbase + BAR_MAIL), "r"(peer(sbase + BAR_MAIL)) : "memory");
            mbar_wait_w(sbase + BAR_MAIL, i & 1);
            qi = lds(sbase + EPOCH_OFF + 8);
          } else if (lane == 0) {
            qi = atomicAdd(&g_next, PAIR ? 2 : 1);
            if (qi == (SIMPLE ? Q_ALL : Q_RANGES) - (PAIR ? 2 : 1)) { g_next = 0; g_epoch = ep; }
          }
          qi = __shfl_sync(0xffffffffu, qi, 0);
          if (PAIR && !(cta & 1)) {
            mbar_wait_w(sbase + BAR_MAIL, i & 1);
            asm volatile(ELECT "st.async.shared::cluster.mbarrier::complete_tx::bytes.u32 [%0], %1, [%2];\n}"
                         ::"r"(peer(sbase + EPOCH_OFF + 8)), "r"(qi + 1), "r"(peer(sbase + BAR_MAIL)) : "memory");
          }
          qi += SIMPLE ? gridDim.x : NCTA;
        }
        uint32_t d;
        if (qi < (SIMPLE ? Q_ALL : Q_RANGES)) { d = c_sched.queue[qi]; if (d & 0x8000) d ^= (1u << 30) | (63u << 16) | 0x8000; else d |= o_slot<SIMPLE>(d >> 5) << 15 | (d & 31) << 10; }
        else if (SIMPLE) d = 2u << 30;
        else { const uint32_t e = qi - Q_RANGES, g = e / 5; d = c_sched.piece[g][piece++] | (g & 1 ? g * 5 + 4 - e : e - g * 5) << 8; }
        if ((d >> 30) == 1) {
          const uint32_t k0 = (d >> 22) & 63;
          const uint32_t run = __ffs(__ballot_sync(0xffffffffu, !reached(&g_cnt[d & 31][lane & 7], ep * 4)) & (0xffu << (k0 >> 3))) - 1;
          if (run <= (k0 + ((d >> 16) & 63)) >> 3) d |= run <= (k0 + O_STEPS) >> 3 ? (2u << 30) | 128 : 128;
        }
        asm volatile("st.volatile.shared.u32 [%0], %1;" ::"r"(sbase + DESC_OFF + ((i + 1) & 3) * 4), "r"(d) : "memory");
        __syncwarp();
        mbar_arrive_warp(sbase + BAR_DESC);
        const Work w = decode(dc);
        dc = d;
        if (w.kind == 0) {
          mbar_wait_w(sbase + BAR_OUT, na++ & 1);
          TTAIL(1);
          T3(i, 0); T3(i, 1);
          asm volatile(ELECT "red.release.gpu.global.add.u32 [%0], 1;\n}" ::"l"(&g_cnt[w.beta][w.sub >> 2]) : "memory");
          T3(i, 2);
          TTAIL(2);
          continue;
        }
        const bool fin = w.mode != 1;
        const CUtensorMap* m = fin ? P.out_st : P.o_st;
        const int c1 = fin ? (w.beta & 15) * SQ : 0;
        const int c2 = fin ? (w.beta >> 4) * (DM / 64) + w.sub * 2 : NBETA * 64 + w.range * 2;
        uint32_t pend = 0;
#pragma unroll 1
        for (int e = 0; e < 4; e++) {
          const int t = (ST_ORDER >> (4 * e)) & 3;
          mbar_wait_w(sbase + BAR_STG + (t ^ (t >> 1)) * 8, (i - na) & 1);
          tma_st3_w(m + (t == 3), qb + t * 16384, c1 + t * 64, c2);
          bulk_commit();
          T2P(i + 1, 5, 2 * e);
          if (e == 3 && w.mode == 1 && (d >> 30) == 2) {
            asm volatile("cp.async.bulk.wait_group 2;" ::: "memory");
            asm volatile(ELECT "st.release.gpu.global.u32 [%0], %1;\n}" ::"l"(&g_flag[w.range]), "r"(2 * ep - 1) : "memory");
          }
          if (pend && (d >> 30) != 2) {
            bulk_wait_read<1>();
            mbar_arrive8_w(pend);
            T2P(i + 1, 5, 2 * e - 1);
          }
          pend = sbase + BAR_EMPTY + (NS + t) * 8;
          if ((ST_NOW >> e) & 1) {
            bulk_wait_read<0>();
            mbar_arrive8_w(pend);
            pend = 0;
            T2P(i + 1, 5, 2 * e + 1);
          }
        }
        if (w.beta < N_EARLY) asm volatile(ELECT "red.relaxed.gpu.global.add.u32 [%0], 1;\n}" ::"l"(&g_rd[w.beta][7]) : "memory");
        T3(i, 0);
        if (piece >= 2) TTAIL(piece * 2 - 1);
        asm volatile("cp.async.bulk.wait_group 0;" ::: "memory");
        T3(i, 1);
        if (w.mode == 1) asm volatile(ELECT "st.release.gpu.global.u32 [%0], %1;\n}" ::"l"(&g_flag[w.range]), "r"(2 * ep) : "memory");
        T3(i, 2);
        if (piece >= 2) TTAIL(piece * 2);
      }
      T3(15, 1);
    } else
    if (warp == 0) {
      Ring r{0, 1, 3};
      uint32_t d = __shfl_sync(0xffffffffu, (uint32_t)q0, 0);
      for (int i = 0;; i++) {
        const Work w = decode(d);
        if (w.kind == 2) break;
        const CUtensorMap* m = w.kind == 0 ? &P.wq[w.beta >> 4] : &P.wo[w.beta >> 4];
        if (i == 0) INIT_DONE();
        for (int ks = 0; ks < w.nsteps; ks++) {
          const uint32_t b = borrow(ks, w.nsteps);
          r.next_if(b == 2);
          const uint32_t bar = sbase + BAR_FULL + r.slot * 8;
          mbar_wait_w(bar + (BAR_EMPTY - BAR_FULL), r.phase);
          if (w.kind == 0) tma_ld3_w(sbase + r.slot * SLOT, m, 0, ks * 64, w.sub * 2, bar, 16384);
          else tma_ld_wo_w(sbase + r.slot * SLOT, m, w.sub * 128, (w.k0 + ks) * 2, bar);
          if (w.kind != 0 && w.beta < N_EARLY && (ks & 7) == 5 && ks > 5)
            asm volatile(ELECT "red.relaxed.gpu.global.add.u32 [%0], 1;\n}" ::"l"(&g_rd[w.beta][(ks >> 3) - 1]) : "memory");
          if (ks < 10) T2P(i, 2, ks);
          if (w.kind != 0 && ks == max(w.nsteps - GO_P, 4)) mbar_arrive_warp(sbase + BAR_GO);
          r.next(); r.next_if(b == 2);
        }
        if (w.kind == 0) {
          r.phase ^= 1; r.next(); r.next();
        } else if (w.mode == 2) {
          for (int k = 1; k <= ((d >> 5) & 3); k++) {
            if (k == 1) TTAIL(9);
            bool all = false;
#pragma unroll 1
            for (int t = 0; t < 4; t++) {
              if (!(t & 1) && !all) {
                const uint32_t ep2 = 2 * lds(sbase + EPOCH_OFF);
                uint32_t v, n = 0;
                do {
                  asm volatile("ld.acquire.gpu.global.u32 %0, [%1];" : "=r"(v) : "l"(&g_flag[w.range + 5 * k]) : "memory");
                  v = __shfl_sync(0xffffffffu, v - ep2, 0);
                  if (++n > (1u << 24)) __trap();
                } while ((int)v < (t >> 1) - 1);
                all = v == 0;
                TTAIL(10);
                asm volatile("fence.proxy.async.global;" ::: "memory");
              }
              mbar_wait_w(sbase + BAR_EMPTY + r.slot * 8, r.phase);
              tma_ld3_w(sbase + r.slot * SLOT, &P.o_st[t == 3], 0, t * 64, NBETA * 64 + (w.range + 5 * k) * 2, sbase + BAR_FULL + r.slot * 8,
                        t == 3 ? 8192 : 16384);
              r.next();
            }
          }
        }
        mbar_wait_w(sbase + BAR_DESC, i & 1);
        d = __shfl_sync(0xffffffffu, lds(sbase + DESC_OFF + ((i + 1) & 3) * 4), 0);
      }
    } else {
      const int hi = warp - 2;
      uint64_t pol_stream;
      uint32_t rdy = 0;
      asm volatile("createpolicy.fractional.L2::evict_first.b64 %0, 1.0;" : "=l"(pol_stream));
      Ring r{0, 1, 3};
      uint32_t d = __shfl_sync(0xffffffffu, (uint32_t)q0, 0);
      for (int i = 0;; i++) {
        const Work w = decode(d);
        if (w.kind == 2) break;
        const CUtensorMap* m = w.kind == 0 ? &P.x[hi][w.beta >> 4] : &P.o_ld[hi];
        int c1 = (w.kind == 0 ? (w.beta & 15) : o_slot<SIMPLE>(w.beta) * 64 + w.k0) * SQ + hi * 128;
        int k_wait = -1;
        const bool both = PAIR && (w.kind == 0 || w.sub != 4), mine = !both || hi == (cta & 1);
        if (w.kind != 0 && mine) {
          if (d & 128) k_wait = d >= (3u << 30) ? 0 : 8 - (w.k0 & 7);
          asm volatile("fence.proxy.async.global;" ::: "memory");
        }
        if (i == 0) INIT_DONE();
        for (int ks = 0; ks < w.nsteps; ks++) {
          if (ks == k_wait) {
            wait_count(&g_cnt[d & 31][(w.k0 + ks) >> 3], lds(sbase + EPOCH_OFF) * 4);
            asm volatile("fence.proxy.async.global;" ::: "memory");
            k_wait = ((w.k0 + ks) | 7) + 1 - w.k0;
          }
          const uint32_t b = borrow(ks, w.nsteps);
          const bool bo = b != 2;
          r.next_if(hi && !bo); r.next_if(hi && !bo);
          const uint32_t sl = bo ? NS + (b ^ (3 * hi)) : r.slot, bar = sbase + BAR_FULL + sl * 8;
          mbar_wait_w(bar + (BAR_EMPTY - BAR_FULL), bo ? (r.xp >> b) & 1 : r.phase);
          const uint32_t bytes = hi ? 96 * 128 : 128 * 128;
          const bool used = i > 0 || ks > 4;
          if (!mine) {
            asm volatile(ELECT "mbarrier.arrive.expect_tx.shared::cta.b64 _, [%0], %1;\n}" ::"r"(bar), "r"(bytes) : "memory");
            if (used) asm volatile(ELECT "mbarrier.arrive.shared::cluster.b64 _, [%0];\n}" ::"r"(peer(bar + (BAR_RDY - BAR_FULL))) : "memory");
          } else if (both) {
            if (used) {
              mbar_wait_w(bar + (BAR_RDY - BAR_FULL), (rdy >> sl) & 1);
              rdy ^= 1 << sl;
            }
            if (w.kind == 0) tma_ld2_both_w(sbase + sl * SLOT, m, ks * 64, c1, bar, bytes);
            else tma_ld2_both_hint_w(sbase + sl * SLOT, m, 0, c1, bar, bytes, pol_stream);
          } else if (!PAIR && w.kind == 0) tma_ld2_w(sbase + sl * SLOT, m, ks * 64, c1, bar, bytes);
          else tma_ld2_hint_w(sbase + sl * SLOT, m, 0, c1, bar, bytes, pol_stream);
          if (i == 0 && ks == 0 && mine) TTAIL(8);
          if (w.kind != 0) c1 += SQ;
          if (i == 0 && ks == PF_STEP)
            asm volatile(ELECT "cp.async.bulk.prefetch.tensor.4d.L2.global.L2::cache_hint [%0, {0, 0, 0, %1}], %2;\n}"
                         ::"l"(&P.kv[hi][0]), "r"(d * (SK / 8)), "l"(pol_stream) : "memory");
          if (ks < 10) T2P(i, 3 + hi, ks);
          if (!hi && w.kind != 0 && !(ks & 3)) TCLK(i * 16 + (ks >> 2));
          r.next(); r.next_if(!hi && !bo); r.next_if(!hi && !bo);
          r.xp ^= 1 << b;
        }
        r.xp ^= 3;
        if (w.kind == 0) {
          m = &P.kv[hi][w.beta >> 4];
          c1 = (d & 511) * (SK / 8);
          for (int j = 0; j < 16; j++) {
            if (hi) r.next();
            const uint32_t bar = sbase + BAR_FULL + r.slot * 8;
            const bool tight = i == 0 && j < KV_WIN_TILES + ((KV_WIN_RAMP * cta) >> 5);
            {
              const int s2 = (int)r.slot - (tight ? 2 : KV_WIN_D);
              mbar_wait_w(sbase + BAR_FULL + (s2 < 0 ? s2 + NS : s2) * 8, s2 < 0 ? r.phase : r.phase ^ 1);
            }
            if (j == 15 && hi) mbar_wait_w(sbase + BAR_DESC, i & 1);
            mbar_wait_w(sbase + BAR_EMPTY + r.slot * 8, r.phase);
            tma_ld_kv_w(sbase + r.slot * SLOT, m, c1, bar, pol_stream);
            T2P(i, 3 + hi, 16 + j);
            if (!hi) TCLK(i * 16 + j);
            if (j == GO_J && !hi) mbar_arrive_warp(sbase + BAR_GO);
            c1 += 8;
            r.next();
            if (!hi) r.next();
          }
        }
        mbar_wait_w(sbase + BAR_DESC, i & 1);
        d = __shfl_sync(0xffffffffu, lds(sbase + DESC_OFF + ((i + 1) & 3) * 4), 0);
      }
    }
  } else {
    Ctx c;
    c.sb = sbase; c.wg = wg; c.warp = warp; c.src = 0; c.mqk = 0; c.mpv = 0; c.lead = lane == 0; c.lane0 = c.lane = lane;
    INIT_DONE();
    if (wg == 0) consumer<0>(c, P.kp); else consumer<1>(c, P.kp);
  }
}

typedef CUresult (*EncodeFn)(CUtensorMap*, CUtensorMapDataType, cuuint32_t, void*, const cuuint64_t*, const cuuint64_t*,
                             const cuuint32_t*, const cuuint32_t*, CUtensorMapInterleave, CUtensorMapSwizzle,
                             CUtensorMapL2promotion, CUtensorMapFloatOOBfill);

void make_map(EncodeFn enc, CUtensorMap* m, const void* ptr, int rank, const cuuint64_t* dims, const cuuint64_t* strides,
              const cuuint32_t* box, CUtensorMapSwizzle swz = CU_TENSOR_MAP_SWIZZLE_128B) {
  cuuint32_t es[5] = {1, 1, 1, 1, 1};
  enc(m, CU_TENSOR_MAP_DATA_TYPE_BFLOAT16, rank, const_cast<void*>(ptr), dims, strides, box, es,
      CU_TENSOR_MAP_INTERLEAVE_NONE, swz, CU_TENSOR_MAP_L2_PROMOTION_NONE,
      CU_TENSOR_MAP_FLOAT_OOB_FILL_NONE);
}

}

extern "C" void kernel_launch(void* const* d_in, const int* in_sizes, int n_in, void* d_out, int out_size) {
  (void)in_sizes; (void)n_in; (void)out_size;
  static EncodeFn enc = nullptr;
  static void* o_ptr = nullptr;
  static int n_sm = 0;
  cudaLaunchAttribute at;
  at.id = cudaLaunchAttributeClusterDimension;
  at.val.clusterDim.x = 2; at.val.clusterDim.y = 1; at.val.clusterDim.z = 1;
  cudaLaunchConfig_t cfg = {};
  cfg.gridDim = dim3(NCTA); cfg.blockDim = dim3(384); cfg.dynamicSmemBytes = SMEM_BYTES; cfg.attrs = &at; cfg.numAttrs = 1;
  if (!enc) {
    void* fn = nullptr;
    cudaDriverEntryPointQueryResult qr;
    cudaGetDriverEntryPoint("cuTensorMapEncodeTiled", &fn, cudaEnableDefault, &qr);
    enc = (EncodeFn)fn;
    cudaGetSymbolAddress(&o_ptr, g_o);
    cudaFuncSetAttribute(mha_fused_kernel<false>, cudaFuncAttributeMaxDynamicSharedMemorySize, SMEM_BYTES);
    cudaFuncSetAttribute(mha_fused_kernel<true>, cudaFuncAttributeMaxDynamicSharedMemorySize, SMEM_BYTES);
    int dev = 0;
    cudaGetDevice(&dev);
    cudaDeviceGetAttribute(&n_sm, cudaDevAttrMultiProcessorCount, dev);
    int n_cl = 0;
    cudaOccupancyMaxActiveClusters(&n_cl, mha_fused_kernel<false>, &cfg);
    if (n_cl * 2 < NCTA && n_sm >= NCTA) n_sm = NCTA - 1;
  }
  Params P;
  for (int br = 0; br < 2; br++) {
    const void* x = d_in[br * 5 + 0]; const void* kc = d_in[br * 5 + 1]; const void* vc = d_in[br * 5 + 2];
    const void* wq = d_in[br * 5 + 3]; const void* wo = d_in[br * 5 + 4];
    { cuuint64_t d[2] = {DM, (cuuint64_t)NB * SQ}, s[1] = {DM * 2}; cuuint32_t b[2] = {64, 128}, b2[2] = {64, 96};
      make_map(enc, &P.x[0][br], x, 2, d, s, b); make_map(enc, &P.x[1][br], x, 2, d, s, b2); }
    { cuuint64_t d[3] = {64, DM, HD / 64}, s[2] = {HD * 2, 128}; cuuint32_t b[3] = {64, 64, 2}; make_map(enc, &P.wq[br], wq, 3, d, s, b); }
    { cuuint64_t d[5] = {DM, 2, 4, 4, HD / 32}, s[4] = {DM * 2, 8 * DM * 2, 2 * DM * 2, 32 * DM * 2}; cuuint32_t b[5] = {64, 2, 4, 4, 2};
      make_map(enc, &P.wo[br], wo, 5, d, s, b); }
    { cuuint64_t d[4] = {64, 8, 2, (cuuint64_t)NB * NH * SK / 8}, s[3] = {DH * 2, 128, DH * 16}; cuuint32_t b[4] = {64, 8, 2, 8};
      make_map(enc, &P.kv[0][br], kc, 4, d, s, b); make_map(enc, &P.kv[1][br], vc, 4, d, s, b); }
    P.kp[br] = (const __nv_bfloat16*)kc; P.vp[br] = (const __nv_bfloat16*)vc;

  }
  { cuuint64_t d[2] = {64, (cuuint64_t)NBETA * 64 * SQ}, s[1] = {128}; cuuint32_t b[2] = {64, 128}, b2[2] = {64, 96};
    make_map(enc, &P.o_ld[0], o_ptr, 2, d, s, b, CU_TENSOR_MAP_SWIZZLE_NONE); make_map(enc, &P.o_ld[1], o_ptr, 2, d, s, b2, CU_TENSOR_MAP_SWIZZLE_NONE); }
  { cuuint64_t d[3] = {64, SQ, O_BLOCKS}, s[2] = {128, SQ * 128}; cuuint32_t b[3] = {64, 64, 2}, b2[3] = {64, 32, 2};
    make_map(enc, &P.o_st[0], o_ptr, 3, d, s, b); make_map(enc, &P.o_st[1], o_ptr, 3, d, s, b2); }
  { cuuint64_t d[3] = {64, (cuuint64_t)NB * SQ, 2 * DM / 64}, s[2] = {2 * DM * 2, 128}; cuuint32_t b[3] = {64, 64, 2}, b2[3] = {64, 32, 2};
    make_map(enc, &P.out_st[0], d_out, 3, d, s, b); make_map(enc, &P.out_st[1], d_out, 3, d, s, b2); }
  if (n_sm >= NCTA) cudaLaunchKernelEx(&cfg, mha_fused_kernel<false>, P);
  else mha_fused_kernel<true><<<n_sm, 384, SMEM_BYTES>>>(P);
}
```

```cpp
#include <cuda_runtime.h>
#include <cuda_bf16.h>
#include <cuda.h>
#include <stdint.h>
#include <stdlib.h>

namespace {

__device__ __forceinline__ void wgmma_proj(float (&d)[64], uint64_t da, uint64_t db, int scaleD) {
  asm volatile("{\n.reg .pred p;\nsetp.ne.b32 p, %66, 0;\n"
      "wgmma.mma_async.sync.aligned.m64n128k16.f32.bf16.bf16 "
      "{%0, %1, %2, %3, %4, %5, %6, %7, %8, %9, %10, %11, %12, %13, %14, %15, %16, %17, %18, %19, %20, %21, %22, %23, %24, %25, %26, %27, %28, %29, %30, "
      "%31, %32, %33, %34, %35, %36, %37, %38, %39, %40, %41, %42, %43, %44, %45, %46, %47, %48, %49, %50, %51, %52, %53, %54, %55, %56, %57, %58, %59, %60, "
      "%61, %62, %63}, "
      "%64, %65, p, 1, 1, 0, 1;\n}\n"
      : "+f"(d[0]), "+f"(d[1]), "+f"(d[2]), "+f"(d[3]), "+f"(d[4]), "+f"(d[5]), "+f"(d[6]), "+f"(d[7]), "+f"(d[8]), "+f"(d[9]), "+f"(d[10]), "+f"(d[11]),
        "+f"(d[12]), "+f"(d[13]), "+f"(d[14]), "+f"(d[15]), "+f"(d[16]), "+f"(d[17]), "+f"(d[18]), "+f"(d[19]), "+f"(d[20]), "+f"(d[21]), "+f"(d[22]),
        "+f"(d[23]), "+f"(d[24]), "+f"(d[25]), "+f"(d[26]), "+f"(d[27]), "+f"(d[28]), "+f"(d[29]), "+f"(d[30]), "+f"(d[31]), "+f"(d[32]), "+f"(d[33]),
        "+f"(d[34]), "+f"(d[35]), "+f"(d[36]), "+f"(d[37]), "+f"(d[38]), "+f"(d[39]), "+f"(d[40]), "+f"(d[41]), "+f"(d[42]), "+f"(d[43]), "+f"(d[44]),
        "+f"(d[45]), "+f"(d[46]), "+f"(d[47]), "+f"(d[48]), "+f"(d[49]), "+f"(d[50]), "+f"(d[51]), "+f"(d[52]), "+f"(d[53]), "+f"(d[54]), "+f"(d[55]),
        "+f"(d[56]), "+f"(d[57]), "+f"(d[58]), "+f"(d[59]), "+f"(d[60]), "+f"(d[61]), "+f"(d[62]), "+f"(d[63])
      : "l"(da), "l"(db), "r"(scaleD));
}
__device__ __forceinline__ void wgmma_proj96(float (&d)[64], uint64_t da, uint64_t db, int scaleD) {
  asm volatile("{\n.reg .pred p;\nsetp.ne.b32 p, %50, 0;\n"
      "wgmma.mma_async.sync.aligned.m64n96k16.f32.bf16.bf16 "
      "{%0, %1, %2, %3, %4, %5, %6, %7, %8, %9, %10, %11, %12, %13, %14, %15, %16, %17, %18, %19, %20, %21, %22, %23, %24, %25, %26, %27, %28, %29, %30, "
      "%31, %32, %33, %34, %35, %36, %37, %38, %39, %40, %41, %42, %43, %44, %45, %46, %47}, "
      "%48, %49, p, 1, 1, 1, 0;\n}\n"
      : "+f"(d[0]), "+f"(d[1]), "+f"(d[2]), "+f"(d[3]), "+f"(d[4]), "+f"(d[5]), "+f"(d[6]), "+f"(d[7]), "+f"(d[8]), "+f"(d[9]), "+f"(d[10]), "+f"(d[11]),
        "+f"(d[12]), "+f"(d[13]), "+f"(d[14]), "+f"(d[15]), "+f"(d[16]), "+f"(d[17]), "+f"(d[18]), "+f"(d[19]), "+f"(d[20]), "+f"(d[21]), "+f"(d[22]),
        "+f"(d[23]), "+f"(d[24]), "+f"(d[25]), "+f"(d[26]), "+f"(d[27]), "+f"(d[28]), "+f"(d[29]), "+f"(d[30]), "+f"(d[31]), "+f"(d[32]), "+f"(d[33]),
        "+f"(d[34]), "+f"(d[35]), "+f"(d[36]), "+f"(d[37]), "+f"(d[38]), "+f"(d[39]), "+f"(d[40]), "+f"(d[41]), "+f"(d[42]), "+f"(d[43]), "+f"(d[44]),
        "+f"(d[45]), "+f"(d[46]), "+f"(d[47])
      : "l"(da), "l"(db), "r"(scaleD));
}
__device__ __forceinline__ void wgmma_qk(float (&d)[32], uint64_t da, uint64_t db, int scaleD) {
  asm volatile("{\n.reg .pred p;\nsetp.ne.b32 p, %34, 0;\n"
      "wgmma.mma_async.sync.aligned.m64n64k16.f32.bf16.bf16 "
      "{%0, %1, %2, %3, %4, %5, %6, %7, %8, %9, %10, %11, %12, %13, %14, %15, %16, %17, %18, %19, %20, %21, %22, %23, %24, %25, %26, %27, %28, %29, %30, "
      "%31}, "
      "%32, %33, p, 1, 1, 0, 0;\n}\n"
      : "+f"(d[0]), "+f"(d[1]), "+f"(d[2]), "+f"(d[3]), "+f"(d[4]), "+f"(d[5]), "+f"(d[6]), "+f"(d[7]), "+f"(d[8]), "+f"(d[9]), "+f"(d[10]), "+f"(d[11]),
        "+f"(d[12]), "+f"(d[13]), "+f"(d[14]), "+f"(d[15]), "+f"(d[16]), "+f"(d[17]), "+f"(d[18]), "+f"(d[19]), "+f"(d[20]), "+f"(d[21]), "+f"(d[22]),
        "+f"(d[23]), "+f"(d[24]), "+f"(d[25]), "+f"(d[26]), "+f"(d[27]), "+f"(d[28]), "+f"(d[29]), "+f"(d[30]), "+f"(d[31])
      : "l"(da), "l"(db), "r"(scaleD));
}
__device__ __forceinline__ void wgmma_qk_rs(float (&d)[32], uint32_t a0, uint32_t a1, uint32_t a2, uint32_t a3, uint64_t db, int scaleD) {
  asm volatile("{\n.reg .pred p;\nsetp.ne.b32 p, %37, 0;\n"
      "wgmma.mma_async.sync.aligned.m64n64k16.f32.bf16.bf16 "
      "{%0, %1, %2, %3, %4, %5, %6, %7, %8, %9, %10, %11, %12, %13, %14, %15, %16, %17, %18, %19, %20, %21, %22, %23, %24, %25, %26, %27, %28, %29, %30, "
      "%31}, "
      "{%32, %33, %34, %35}, %36, p, 1, 1, 0;\n}\n"
      : "+f"(d[0]), "+f"(d[1]), "+f"(d[2]), "+f"(d[3]), "+f"(d[4]), "+f"(d[5]), "+f"(d[6]), "+f"(d[7]), "+f"(d[8]), "+f"(d[9]), "+f"(d[10]), "+f"(d[11]),
        "+f"(d[12]), "+f"(d[13]), "+f"(d[14]), "+f"(d[15]), "+f"(d[16]), "+f"(d[17]), "+f"(d[18]), "+f"(d[19]), "+f"(d[20]), "+f"(d[21]), "+f"(d[22]),
        "+f"(d[23]), "+f"(d[24]), "+f"(d[25]), "+f"(d[26]), "+f"(d[27]), "+f"(d[28]), "+f"(d[29]), "+f"(d[30]), "+f"(d[31])
      : "r"(a0), "r"(a1), "r"(a2), "r"(a3), "l"(db), "r"(scaleD));
}
__device__ __forceinline__ void wgmma_pv(float (&d)[64], uint32_t a0, uint32_t a1, uint32_t a2, uint32_t a3, uint64_t db, int scaleD) {
  asm volatile("{\n.reg .pred p;\nsetp.ne.b32 p, %69, 0;\n"
      "wgmma.mma_async.sync.aligned.m64n128k16.f32.bf16.bf16 "
      "{%0, %1, %2, %3, %4, %5, %6, %7, %8, %9, %10, %11, %12, %13, %14, %15, %16, %17, %18, %19, %20, %21, %22, %23, %24, %25, %26, %27, %28, %29, %30, "
      "%31, %32, %33, %34, %35, %36, %37, %38, %39, %40, %41, %42, %43, %44, %45, %46, %47, %48, %49, %50, %51, %52, %53, %54, %55, %56, %57, %58, %59, %60, "
      "%61, %62, %63}, "
      "{%64, %65, %66, %67}, %68, p, 1, 1, 1;\n}\n"
      : "+f"(d[0]), "+f"(d[1]), "+f"(d[2]), "+f"(d[3]), "+f"(d[4]), "+f"(d[5]), "+f"(d[6]), "+f"(d[7]), "+f"(d[8]), "+f"(d[9]), "+f"(d[10]), "+f"(d[11]),
        "+f"(d[12]), "+f"(d[13]), "+f"(d[14]), "+f"(d[15]), "+f"(d[16]), "+f"(d[17]), "+f"(d[18]), "+f"(d[19]), "+f"(d[20]), "+f"(d[21]), "+f"(d[22]),
        "+f"(d[23]), "+f"(d[24]), "+f"(d[25]), "+f"(d[26]), "+f"(d[27]), "+f"(d[28]), "+f"(d[29]), "+f"(d[30]), "+f"(d[31]), "+f"(d[32]), "+f"(d[33]),
        "+f"(d[34]), "+f"(d[35]), "+f"(d[36]), "+f"(d[37]), "+f"(d[38]), "+f"(d[39]), "+f"(d[40]), "+f"(d[41]), "+f"(d[42]), "+f"(d[43]), "+f"(d[44]),
        "+f"(d[45]), "+f"(d[46]), "+f"(d[47]), "+f"(d[48]), "+f"(d[49]), "+f"(d[50]), "+f"(d[51]), "+f"(d[52]), "+f"(d[53]), "+f"(d[54]), "+f"(d[55]),
        "+f"(d[56]), "+f"(d[57]), "+f"(d[58]), "+f"(d[59]), "+f"(d[60]), "+f"(d[61]), "+f"(d[62]), "+f"(d[63])
      : "r"(a0), "r"(a1), "r"(a2), "r"(a3), "l"(db), "r"(scaleD));
}
__device__ __forceinline__ void wgmma_qk_sp(float (&d)[32], uint32_t a0, uint32_t a1, uint32_t a2, uint32_t a3, uint64_t db, int scaleD, uint32_t meta) {
  asm volatile("{\n.reg .pred p;\nsetp.ne.b32 p, %37, 0;\n"
      "wgmma.mma_async.sp.sync.aligned.m64n64k32.f32.bf16.bf16 "
      "{%0, %1, %2, %3, %4, %5, %6, %7, %8, %9, %10, %11, %12, %13, %14, %15, %16, %17, %18, %19, %20, %21, %22, %23, %24, %25, %26, %27, %28, %29, %30, "
      "%31}, "
      "{%32, %33, %34, %35}, %36, %38, 0, p, 1, 1, 0;\n}\n"
      : "+f"(d[0]), "+f"(d[1]), "+f"(d[2]), "+f"(d[3]), "+f"(d[4]), "+f"(d[5]), "+f"(d[6]), "+f"(d[7]), "+f"(d[8]), "+f"(d[9]), "+f"(d[10]), "+f"(d[11]),
        "+f"(d[12]), "+f"(d[13]), "+f"(d[14]), "+f"(d[15]), "+f"(d[16]), "+f"(d[17]), "+f"(d[18]), "+f"(d[19]), "+f"(d[20]), "+f"(d[21]), "+f"(d[22]),
        "+f"(d[23]), "+f"(d[24]), "+f"(d[25]), "+f"(d[26]), "+f"(d[27]), "+f"(d[28]), "+f"(d[29]), "+f"(d[30]), "+f"(d[31])
      : "r"(a0), "r"(a1), "r"(a2), "r"(a3), "l"(db), "r"(scaleD), "r"(meta));
}
__device__ __forceinline__ void wgmma_pv_sp(float (&d)[64], uint32_t a0, uint32_t a1, uint32_t a2, uint32_t a3, uint64_t db, int scaleD, uint32_t meta) {
  asm volatile("{\n.reg .pred p;\nsetp.ne.b32 p, %69, 0;\n"
      "wgmma.mma_async.sp.sync.aligned.m64n128k32.f32.bf16.bf16 "
      "{%0, %1, %2, %3, %4, %5, %6, %7, %8, %9, %10, %11, %12, %13, %14, %15, %16, %17, %18, %19, %20, %21, %22, %23, %24, %25, %26, %27, %28, %29, %30, "
      "%31, %32, %33, %34, %35, %36, %37, %38, %39, %40, %41, %42, %43, %44, %45, %46, %47, %48, %49, %50, %51, %52, %53, %54, %55, %56, %57, %58, %59, %60, "
      "%61, %62, %63}, "
      "{%64, %65, %66, %67}, %68, %70, 0, p, 1, 1, 1;\n}\n"
      : "+f"(d[0]), "+f"(d[1]), "+f"(d[2]), "+f"(d[3]), "+f"(d[4]), "+f"(d[5]), "+f"(d[6]), "+f"(d[7]), "+f"(d[8]), "+f"(d[9]), "+f"(d[10]), "+f"(d[11]),
        "+f"(d[12]), "+f"(d[13]), "+f"(d[14]), "+f"(d[15]), "+f"(d[16]), "+f"(d[17]), "+f"(d[18]), "+f"(d[19]), "+f"(d[20]), "+f"(d[21]), "+f"(d[22]),
        "+f"(d[23]), "+f"(d[24]), "+f"(d[25]), "+f"(d[26]), "+f"(d[27]), "+f"(d[28]), "+f"(d[29]), "+f"(d[30]), "+f"(d[31]), "+f"(d[32]), "+f"(d[33]),
        "+f"(d[34]), "+f"(d[35]), "+f"(d[36]), "+f"(d[37]), "+f"(d[38]), "+f"(d[39]), "+f"(d[40]), "+f"(d[41]), "+f"(d[42]), "+f"(d[43]), "+f"(d[44]),
        "+f"(d[45]), "+f"(d[46]), "+f"(d[47]), "+f"(d[48]), "+f"(d[49]), "+f"(d[50]), "+f"(d[51]), "+f"(d[52]), "+f"(d[53]), "+f"(d[54]), "+f"(d[55]),
        "+f"(d[56]), "+f"(d[57]), "+f"(d[58]), "+f"(d[59]), "+f"(d[60]), "+f"(d[61]), "+f"(d[62]), "+f"(d[63])
      : "r"(a0), "r"(a1), "r"(a2), "r"(a3), "l"(db), "r"(scaleD), "r"(meta));
}
__device__ __forceinline__ void wgmma_proj_init(float (&d)[64], uint64_t da, uint64_t db, int scaleD) {
  asm volatile("{\n.reg .pred p;\nsetp.ne.b32 p, %66, 0;\n"
      "wgmma.mma_async.sync.aligned.m64n128k16.f32.bf16.bf16 "
      "{%0, %1, %2, %3, %4, %5, %6, %7, %8, %9, %10, %11, %12, %13, %14, %15, %16, %17, %18, %19, %20, %21, %22, %23, %24, %25, %26, %27, %28, %29, %30, "
      "%31, %32, %33, %34, %35, %36, %37, %38, %39, %40, %41, %42, %43, %44, %45, %46, %47, %48, %49, %50, %51, %52, %53, %54, %55, %56, %57, %58, %59, %60, "
      "%61, %62, %63}, "
      "%64, %65, p, 1, 1, 0, 1;\n}\n"
      : "=f"(d[0]), "=f"(d[1]), "=f"(d[2]), "=f"(d[3]), "=f"(d[4]), "=f"(d[5]), "=f"(d[6]), "=f"(d[7]), "=f"(d[8]), "=f"(d[9]), "=f"(d[10]), "=f"(d[11]),
        "=f"(d[12]), "=f"(d[13]), "=f"(d[14]), "=f"(d[15]), "=f"(d[16]), "=f"(d[17]), "=f"(d[18]), "=f"(d[19]), "=f"(d[20]), "=f"(d[21]), "=f"(d[22]),
        "=f"(d[23]), "=f"(d[24]), "=f"(d[25]), "=f"(d[26]), "=f"(d[27]), "=f"(d[28]), "=f"(d[29]), "=f"(d[30]), "=f"(d[31]), "=f"(d[32]), "=f"(d[33]),
        "=f"(d[34]), "=f"(d[35]), "=f"(d[36]), "=f"(d[37]), "=f"(d[38]), "=f"(d[39]), "=f"(d[40]), "=f"(d[41]), "=f"(d[42]), "=f"(d[43]), "=f"(d[44]),
        "=f"(d[45]), "=f"(d[46]), "=f"(d[47]), "=f"(d[48]), "=f"(d[49]), "=f"(d[50]), "=f"(d[51]), "=f"(d[52]), "=f"(d[53]), "=f"(d[54]), "=f"(d[55]),
        "=f"(d[56]), "=f"(d[57]), "=f"(d[58]), "=f"(d[59]), "=f"(d[60]), "=f"(d[61]), "=f"(d[62]), "=f"(d[63])
      : "l"(da), "l"(db), "r"(scaleD));
}
__device__ __forceinline__ void wgmma_proj96_init(float (&d)[64], uint64_t da, uint64_t db, int scaleD) {
  asm volatile("{\n.reg .pred p;\nsetp.ne.b32 p, %50, 0;\n"
      "wgmma.mma_async.sync.aligned.m64n96k16.f32.bf16.bf16 "
      "{%0, %1, %2, %3, %4, %5, %6, %7, %8, %9, %10, %11, %12, %13, %14, %15, %16, %17, %18, %19, %20, %21, %22, %23, %24, %25, %26, %27, %28, %29, %30, "
      "%31, %32, %33, %34, %35, %36, %37, %38, %39, %40, %41, %42, %43, %44, %45, %46, %47}, "
      "%48, %49, p, 1, 1, 1, 0;\n}\n"
      : "=f"(d[0]), "=f"(d[1]), "=f"(d[2]), "=f"(d[3]), "=f"(d[4]), "=f"(d[5]), "=f"(d[6]), "=f"(d[7]), "=f"(d[8]), "=f"(d[9]), "=f"(d[10]), "=f"(d[11]),
        "=f"(d[12]), "=f"(d[13]), "=f"(d[14]), "=f"(d[15]), "=f"(d[16]), "=f"(d[17]), "=f"(d[18]), "=f"(d[19]), "=f"(d[20]), "=f"(d[21]), "=f"(d[22]),
        "=f"(d[23]), "=f"(d[24]), "=f"(d[25]), "=f"(d[26]), "=f"(d[27]), "=f"(d[28]), "=f"(d[29]), "=f"(d[30]), "=f"(d[31]), "=f"(d[32]), "=f"(d[33]),
        "=f"(d[34]), "=f"(d[35]), "=f"(d[36]), "=f"(d[37]), "=f"(d[38]), "=f"(d[39]), "=f"(d[40]), "=f"(d[41]), "=f"(d[42]), "=f"(d[43]), "=f"(d[44]),
        "=f"(d[45]), "=f"(d[46]), "=f"(d[47])
      : "l"(da), "l"(db), "r"(scaleD));
}
__device__ __forceinline__ void wgmma_qk_init(float (&d)[32], uint64_t da, uint64_t db, int scaleD) {
  asm volatile("{\n.reg .pred p;\nsetp.ne.b32 p, %34, 0;\n"
      "wgmma.mma_async.sync.aligned.m64n64k16.f32.bf16.bf16 "
      "{%0, %1, %2, %3, %4, %5, %6, %7, %8, %9, %10, %11, %12, %13, %14, %15, %16, %17, %18, %19, %20, %21, %22, %23, %24, %25, %26, %27, %28, %29, %30, "
      "%31}, "
      "%32, %33, p, 1, 1, 0, 0;\n}\n"
      : "=f"(d[0]), "=f"(d[1]), "=f"(d[2]), "=f"(d[3]), "=f"(d[4]), "=f"(d[5]), "=f"(d[6]), "=f"(d[7]), "=f"(d[8]), "=f"(d[9]), "=f"(d[10]), "=f"(d[11]),
        "=f"(d[12]), "=f"(d[13]), "=f"(d[14]), "=f"(d[15]), "=f"(d[16]), "=f"(d[17]), "=f"(d[18]), "=f"(d[19]), "=f"(d[20]), "=f"(d[21]), "=f"(d[22]),
        "=f"(d[23]), "=f"(d[24]), "=f"(d[25]), "=f"(d[26]), "=f"(d[27]), "=f"(d[28]), "=f"(d[29]), "=f"(d[30]), "=f"(d[31])
      : "l"(da), "l"(db), "r"(scaleD));
}
__device__ __forceinline__ void wgmma_qk_rs_init(float (&d)[32], uint32_t a0, uint32_t a1, uint32_t a2, uint32_t a3, uint64_t db, int scaleD) {
  asm volatile("{\n.reg .pred p;\nsetp.ne.b32 p, %37, 0;\n"
      "wgmma.mma_async.sync.aligned.m64n64k16.f32.bf16.bf16 "
      "{%0, %1, %2, %3, %4, %5, %6, %7, %8, %9, %10, %11, %12, %13, %14, %15, %16, %17, %18, %19, %20, %21, %22, %23, %24, %25, %26, %27, %28, %29, %30, "
      "%31}, "
      "{%32, %33, %34, %35}, %36, p, 1, 1, 0;\n}\n"
      : "=f"(d[0]), "=f"(d[1]), "=f"(d[2]), "=f"(d[3]), "=f"(d[4]), "=f"(d[5]), "=f"(d[6]), "=f"(d[7]), "=f"(d[8]), "=f"(d[9]), "=f"(d[10]), "=f"(d[11]),
        "=f"(d[12]), "=f"(d[13]), "=f"(d[14]), "=f"(d[15]), "=f"(d[16]), "=f"(d[17]), "=f"(d[18]), "=f"(d[19]), "=f"(d[20]), "=f"(d[21]), "=f"(d[22]),
        "=f"(d[23]), "=f"(d[24]), "=f"(d[25]), "=f"(d[26]), "=f"(d[27]), "=f"(d[28]), "=f"(d[29]), "=f"(d[30]), "=f"(d[31])
      : "r"(a0), "r"(a1), "r"(a2), "r"(a3), "l"(db), "r"(scaleD));
}
__device__ __forceinline__ void wgmma_pv_init(float (&d)[64], uint32_t a0, uint32_t a1, uint32_t a2, uint32_t a3, uint64_t db, int scaleD) {
  asm volatile("{\n.reg .pred p;\nsetp.ne.b32 p, %69, 0;\n"
      "wgmma.mma_async.sync.aligned.m64n128k16.f32.bf16.bf16 "
      "{%0, %1, %2, %3, %4, %5, %6, %7, %8, %9, %10, %11, %12, %13, %14, %15, %16, %17, %18, %19, %20, %21, %22, %23, %24, %25, %26, %27, %28, %29, %30, "
      "%31, %32, %33, %34, %35, %36, %37, %38, %39, %40, %41, %42, %43, %44, %45, %46, %47, %48, %49, %50, %51, %52, %53, %54, %55, %56, %57, %58, %59, %60, "
      "%61, %62, %63}, "
      "{%64, %65, %66, %67}, %68, p, 1, 1, 1;\n}\n"
      : "=f"(d[0]), "=f"(d[1]), "=f"(d[2]), "=f"(d[3]), "=f"(d[4]), "=f"(d[5]), "=f"(d[6]), "=f"(d[7]), "=f"(d[8]), "=f"(d[9]), "=f"(d[10]), "=f"(d[11]),
        "=f"(d[12]), "=f"(d[13]), "=f"(d[14]), "=f"(d[15]), "=f"(d[16]), "=f"(d[17]), "=f"(d[18]), "=f"(d[19]), "=f"(d[20]), "=f"(d[21]), "=f"(d[22]),
        "=f"(d[23]), "=f"(d[24]), "=f"(d[25]), "=f"(d[26]), "=f"(d[27]), "=f"(d[28]), "=f"(d[29]), "=f"(d[30]), "=f"(d[31]), "=f"(d[32]), "=f"(d[33]),
        "=f"(d[34]), "=f"(d[35]), "=f"(d[36]), "=f"(d[37]), "=f"(d[38]), "=f"(d[39]), "=f"(d[40]), "=f"(d[41]), "=f"(d[42]), "=f"(d[43]), "=f"(d[44]),
        "=f"(d[45]), "=f"(d[46]), "=f"(d[47]), "=f"(d[48]), "=f"(d[49]), "=f"(d[50]), "=f"(d[51]), "=f"(d[52]), "=f"(d[53]), "=f"(d[54]), "=f"(d[55]),
        "=f"(d[56]), "=f"(d[57]), "=f"(d[58]), "=f"(d[59]), "=f"(d[60]), "=f"(d[61]), "=f"(d[62]), "=f"(d[63])
      : "r"(a0), "r"(a1), "r"(a2), "r"(a3), "l"(db), "r"(scaleD));
}
__device__ __forceinline__ void wgmma_qk_sp_init(float (&d)[32], uint32_t a0, uint32_t a1, uint32_t a2, uint32_t a3, uint64_t db, int scaleD, uint32_t meta) {
  asm volatile("{\n.reg .pred p;\nsetp.ne.b32 p, %37, 0;\n"
      "wgmma.mma_async.sp.sync.aligned.m64n64k32.f32.bf16.bf16 "
      "{%0, %1, %2, %3, %4, %5, %6, %7, %8, %9, %10, %11, %12, %13, %14, %15, %16, %17, %18, %19, %20, %21, %22, %23, %24, %25, %26, %27, %28, %29, %30, "
      "%31}, "
      "{%32, %33, %34, %35}, %36, %38, 0, p, 1, 1, 0;\n}\n"
      : "=f"(d[0]), "=f"(d[1]), "=f"(d[2]), "=f"(d[3]), "=f"(d[4]), "=f"(d[5]), "=f"(d[6]), "=f"(d[7]), "=f"(d[8]), "=f"(d[9]), "=f"(d[10]), "=f"(d[11]),
        "=f"(d[12]), "=f"(d[13]), "=f"(d[14]), "=f"(d[15]), "=f"(d[16]), "=f"(d[17]), "=f"(d[18]), "=f"(d[19]), "=f"(d[20]), "=f"(d[21]), "=f"(d[22]),
        "=f"(d[23]), "=f"(d[24]), "=f"(d[25]), "=f"(d[26]), "=f"(d[27]), "=f"(d[28]), "=f"(d[29]), "=f"(d[30]), "=f"(d[31])
      : "r"(a0), "r"(a1), "r"(a2), "r"(a3), "l"(db), "r"(scaleD), "r"(meta));
}
__device__ __forceinline__ void wgmma_pv_sp_init(float (&d)[64], uint32_t a0, uint32_t a1, uint32_t a2, uint32_t a3, uint64_t db, int scaleD, uint32_t meta) {
  asm volatile("{\n.reg .pred p;\nsetp.ne.b32 p, %69, 0;\n"
      "wgmma.mma_async.sp.sync.aligned.m64n128k32.f32.bf16.bf16 "
      "{%0, %1, %2, %3, %4, %5, %6, %7, %8, %9, %10, %11, %12, %13, %14, %15, %16, %17, %18, %19, %20, %21, %22, %23, %24, %25, %26, %27, %28, %29, %30, "
      "%31, %32, %33, %34, %35, %36, %37, %38, %39, %40, %41, %42, %43, %44, %45, %46, %47, %48, %49, %50, %51, %52, %53, %54, %55, %56, %57, %58, %59, %60, "
      "%61, %62, %63}, "
      "{%64, %65, %66, %67}, %68, %70, 0, p, 1, 1, 1;\n}\n"
      : "=f"(d[0]), "=f"(d[1]), "=f"(d[2]), "=f"(d[3]), "=f"(d[4]), "=f"(d[5]), "=f"(d[6]), "=f"(d[7]), "=f"(d[8]), "=f"(d[9]), "=f"(d[10]), "=f"(d[11]),
        "=f"(d[12]), "=f"(d[13]), "=f"(d[14]), "=f"(d[15]), "=f"(d[16]), "=f"(d[17]), "=f"(d[18]), "=f"(d[19]), "=f"(d[20]), "=f"(d[21]), "=f"(d[22]),
        "=f"(d[23]), "=f"(d[24]), "=f"(d[25]), "=f"(d[26]), "=f"(d[27]), "=f"(d[28]), "=f"(d[29]), "=f"(d[30]), "=f"(d[31]), "=f"(d[32]), "=f"(d[33]),
        "=f"(d[34]), "=f"(d[35]), "=f"(d[36]), "=f"(d[37]), "=f"(d[38]), "=f"(d[39]), "=f"(d[40]), "=f"(d[41]), "=f"(d[42]), "=f"(d[43]), "=f"(d[44]),
        "=f"(d[45]), "=f"(d[46]), "=f"(d[47]), "=f"(d[48]), "=f"(d[49]), "=f"(d[50]), "=f"(d[51]), "=f"(d[52]), "=f"(d[53]), "=f"(d[54]), "=f"(d[55]),
        "=f"(d[56]), "=f"(d[57]), "=f"(d[58]), "=f"(d[59]), "=f"(d[60]), "=f"(d[61]), "=f"(d[62]), "=f"(d[63])
      : "r"(a0), "r"(a1), "r"(a2), "r"(a3), "l"(db), "r"(scaleD), "r"(meta));
}

constexpr int NB = 16, SQ = 224, DM = 640, NH = 32, SK = 1024, DH = 128;
constexpr int HD = NH * DH;
constexpr int NBETA = 2 * NB;
constexpr int NCTA = 132;
constexpr uint32_t SB0 = 1024;
constexpr int NS = 10;
constexpr int SLOT = 16384;
constexpr int QBUF_OFF = NS * SLOT;
constexpr int NSX = NS + 4;
constexpr int BAR_OFF = NSX * SLOT;
constexpr int BAR_FULL = BAR_OFF;
constexpr int BAR_EMPTY = BAR_OFF + 8 * NSX;
constexpr int BAR_STG = BAR_OFF + 16 * NSX;
constexpr int BAR_OUT = BAR_STG + 32;
constexpr int BAR_DESC = BAR_OUT + 8;
constexpr int BAR_GO = BAR_DESC + 8;
constexpr int BAR_MAIL = BAR_GO + 8;
constexpr int BAR_RDY = BAR_MAIL + 8;
constexpr int DESC_OFF = BAR_RDY + 8 * NSX;
constexpr int EPOCH_OFF = DESC_OFF + 16;
constexpr int TRACE_OFF = EPOCH_OFF + 16;
constexpr int SMEM_BYTES = TRACE_OFF;
constexpr float SM_C = 0.08838834764831845f * 1.4426950408889634f;
constexpr float SUM_HI = 1099511627776.f, SUM_LO = 1.f / 1099511627776.f;
constexpr uint32_t META_QK = 0xEEEE4444u;
constexpr uint32_t META_PV = 0x44EEEE44u;

#define QK_EARLY_MASK 3
#define ST_ORDER 0x2310
#define LAG_BAR 2
#define ST_NOW 8
#define PF_STEP 2
#define KV_WIN_D 4
#define SF 0xefbf
#define O_STEPS 4
#define KV_WIN_RAMP 4
#define PDEPTH 0
#define KV_WIN_TILES -2
#define REG_C 232
#define REG_P 24
#define GO_P 6
#define P_POS 208
#define OR 6
#define OR0 0
#define B_LATE 22
#define H_LATE 24
#define RM0 1
#define RM1 0xb3
#define RM2 0
#define PAIRB 1
#define LATE0 1
#define LATE1 2
#define GO_J 13
#define LATE_G 32
#define W_FAST 2
#define X_FAST 2
#define KG 5
#define PK 44
#define EARLY_MASK 0xffffu
#define PIECE_TABLE 0x501e8815,0x689d883d,0x5036b019,0x80000000,0x50345012,0x80000000,0x50244013,0x6b13403a,0x501c3811,0x695a3833,0x50321018,0x80000000,0x502b481a,0x6d4a4832,0x50128016,0x67e08035,0x50210814,0x6ccc0838,0x5012c010,0x695ac03f,0x64ec7836,0x80000000,0x64ecb830,0x80000000,0x5024c81f,0x80000000,0x5024601e,0x80000000,0x5021901d,0x80000000,0x501e7017,0x80000000,0x549b201c,0x80000000,0x67623031,0x80000000,0x67e06837,0x80000000,0x5016a81b,0x6dc8a839,0x689d0034,0x80000000,0x6999985b,0x80000000,0x695a583e,0x80000000,0x5011281c,0x80000000,0x55cea01b,0x80000000,0x6b91185c,0x80000000

struct Params {
  CUtensorMap x[2][2], wq[2], kv[2][2], wo[2];
  CUtensorMap o_ld[2], o_st[2], out_st[2];
  const __nv_bfloat16* kp[2];
  const __nv_bfloat16* vp[2];
};

constexpr int NPART = 32 * 5, O_BLOCKS = NBETA * 64 + 2 * NPART;
__device__ __align__(128) __nv_bfloat16 g_o[(size_t)O_BLOCKS * SQ * 64];
__device__ unsigned g_cnt[NBETA][8];
__device__ unsigned g_rd[NBETA][8];
__device__ unsigned g_epoch, g_next;
__device__ unsigned g_flag[NPART];

__device__ __forceinline__ uint32_t smem_u32(const void* p) { return (uint32_t)__cvta_generic_to_shared(p); }
__device__ __forceinline__ void mbar_arrive(uint32_t bar) {
  asm volatile("mbarrier.arrive.shared::cta.b64 _, [%0];" ::"r"(bar) : "memory");
}
__device__ __forceinline__ void mbar_arrive_warp(uint32_t bar) {
  asm volatile("{\n.reg .pred p;\nelect.sync _|p, 0xffffffff;\n@p mbarrier.arrive.shared::cta.b64 _, [%0];\n}" ::"r"(bar) : "memory");
}
__device__ __forceinline__ int lane_now() { int l; asm volatile("mov.u32 %0, %%laneid;" : "=r"(l)); return l; }
__device__ __forceinline__ bool mbar_try(uint32_t bar, uint32_t parity) {
  uint32_t ok;
  asm volatile("{\n.reg .pred p;\nmbarrier.try_wait.parity.shared::cta.b64 p, [%1], %2;\nselp.u32 %0, 1, 0, p;\n}"
               : "=r"(ok) : "r"(bar), "r"(parity) : "memory");
  return ok;
}
__device__ __forceinline__ bool mbar_test(uint32_t bar, uint32_t parity) {
  uint32_t ok;
  asm volatile("{\n.reg .pred p;\nmbarrier.test_wait.parity.shared::cta.b64 p, [%1], %2;\nselp.u32 %0, 1, 0, p;\n}"
               : "=r"(ok) : "r"(bar), "r"(parity) : "memory");
  return ok;
}
__device__ __forceinline__ void mbar_wait_w(uint32_t bar, uint32_t parity) {
  uint32_t n = 0;
  while (!__all_sync(0xffffffffu, mbar_try(bar, parity))) {
    if (++n > (1u << 22)) __trap();
  }
}
#define ELECT "{\n.reg .pred p;\nelect.sync _|p, 0xffffffff;\n@p "
__device__ __forceinline__ void tma_st3_w(const CUtensorMap* m, uint32_t src, int c1, int c2) {
  asm volatile(ELECT "cp.async.bulk.tensor.3d.global.shared::cta.bulk_group [%0, {0, %2, %3}], [%1];\n}"
               ::"l"(m), "r"(src), "r"(c1), "r"(c2) : "memory");
}
#define EXPECT(bar, bytes) "mbarrier.arrive.expect_tx.shared::cta.b64 _, [" bar "], " bytes ";\n@p "
__device__ __forceinline__ void tma_ld2_w(uint32_t dst, const CUtensorMap* m, int c0, int c1, uint32_t bar, uint32_t bytes) {
  asm volatile(ELECT EXPECT("%2", "%5") "cp.async.bulk.tensor.2d.shared::cluster.global.mbarrier::complete_tx::bytes [%0], [%1, {%3, %4}], [%2];\n}"
               ::"r"(dst), "l"(m), "r"(bar), "r"(c0), "r"(c1), "r"(bytes) : "memory");
}
__device__ __forceinline__ void tma_ld2_hint_w(uint32_t dst, const CUtensorMap* m, int c0, int c1, uint32_t bar, uint32_t bytes, uint64_t pol) {
  asm volatile(ELECT EXPECT("%2", "%6") "cp.async.bulk.tensor.2d.shared::cluster.global.mbarrier::complete_tx::bytes.L2::cache_hint"
               " [%0], [%1, {%3, %4}], [%2], %5;\n}"
               ::"r"(dst), "l"(m), "r"(bar), "r"(c0), "r"(c1), "l"(pol), "r"(bytes) : "memory");
}
__device__ __forceinline__ void tma_ld3_w(uint32_t dst, const CUtensorMap* m, int c0, int c1, int c2, uint32_t bar, uint32_t bytes) {
  asm volatile(ELECT EXPECT("%2", "%6") "cp.async.bulk.tensor.3d.shared::cluster.global.mbarrier::complete_tx::bytes [%0], [%1, {%3, %4, %5}], [%2];\n}"
               ::"r"(dst), "l"(m), "r"(bar), "r"(c0), "r"(c1), "r"(c2), "r"(bytes) : "memory");
}
__device__ __forceinline__ void tma_ld_kv_w(uint32_t dst, const CUtensorMap* m, int grp, uint32_t bar, uint64_t pol) {
  asm volatile(ELECT EXPECT("%2", "16384") "cp.async.bulk.tensor.4d.shared::cluster.global.mbarrier::complete_tx::bytes.L2::cache_hint"
               " [%0], [%1, {0, 0, 0, %3}], [%2], %4;\n}"
               ::"r"(dst), "l"(m), "r"(bar), "r"(grp), "l"(pol) : "memory");
}
__device__ __forceinline__ void tma_ld_wo_w(uint32_t dst, const CUtensorMap* m, int col, int grp, uint32_t bar) {
  asm volatile(ELECT EXPECT("%2", "16384") "cp.async.bulk.tensor.5d.shared::cluster.global.mbarrier::complete_tx::bytes [%0], [%1, {%3, 0, 0, 0, %4}], [%2];\n"
               "@p cp.async.bulk.tensor.5d.shared::cluster.global.mbarrier::complete_tx::bytes [%5], [%1, {%6, 0, 0, 0, %4}], [%2];\n}"
               ::"r"(dst), "l"(m), "r"(bar), "r"(col), "r"(grp), "r"(dst + 8192), "r"(col + 64) : "memory");
}
__device__ __forceinline__ void mbar_arrive8_w(uint32_t bar) {
  asm volatile(ELECT "mbarrier.arrive.shared::cta.b64 _, [%0], 8;\n}" ::"r"(bar) : "memory");
}
__device__ __forceinline__ uint32_t peer(uint32_t a) { uint32_t r; asm("mapa.shared::cluster.u32 %0, %1, %2;" : "=r"(r) : "r"(a), "r"(~blockIdx.x & 1)); return r; }
__device__ __forceinline__ void tma_ld2_both_w(uint32_t dst, const CUtensorMap* m, int c0, int c1, uint32_t bar, uint32_t bytes) {
  asm volatile(ELECT EXPECT("%2", "%5") "cp.async.bulk.tensor.2d.shared::cluster.global.mbarrier::complete_tx::bytes.multicast::cluster"
               " [%0], [%1, {%3, %4}], [%2], %6;\n}"
               ::"r"(dst), "l"(m), "r"(bar), "r"(c0), "r"(c1), "r"(bytes), "h"((uint16_t)3) : "memory");
}
__device__ __forceinline__ void tma_ld2_both_hint_w(uint32_t dst, const CUtensorMap* m, int c0, int c1, uint32_t bar, uint32_t bytes, uint64_t pol) {
  asm volatile(ELECT EXPECT("%2", "%6") "cp.async.bulk.tensor.2d.shared::cluster.global.mbarrier::complete_tx::bytes.multicast::cluster.L2::cache_hint"
               " [%0], [%1, {%3, %4}], [%2], %7, %5;\n}"
               ::"r"(dst), "l"(m), "r"(bar), "r"(c0), "r"(c1), "l"(pol), "r"(bytes), "h"((uint16_t)3) : "memory");
}
__device__ __forceinline__ void bulk_commit() { asm volatile("cp.async.bulk.commit_group;" ::: "memory"); }
template <int N> __device__ __forceinline__ void bulk_wait_read() { asm volatile("cp.async.bulk.wait_group.read %0;" ::"n"(N) : "memory"); }
__device__ __forceinline__ void wg_fence() { asm volatile("wgmma.fence.sync.aligned;" ::: "memory"); }
__device__ __forceinline__ void wg_commit() { asm volatile("wgmma.commit_group.sync.aligned;" ::: "memory"); }
template <int N> __device__ __forceinline__ void wg_wait() { asm volatile("wgmma.wait_group.sync.aligned %0;" ::"n"(N) : "memory"); }
__device__ __forceinline__ void fence_async_smem() { asm volatile("fence.proxy.async.shared::cta;" ::: "memory"); }
__device__ __forceinline__ void bar_sync(int id, int n) { asm volatile("bar.sync %0, %1;" ::"r"(id), "r"(n) : "memory"); }
__device__ __forceinline__ void touch(float& a) { asm volatile("neg.f32 %0, %0;" : "+f"(a)); }
__device__ __forceinline__ void touch(uint32_t& a) { asm volatile("not.b32 %0, %0;" : "+r"(a)); }
template <typename T, int N> __device__ __forceinline__ void touch(T (&a)[N]) {
#pragma unroll
  for (int i = 0; i < N; i++) touch(a[i]);
}
template <int ID, typename... A> __device__ __forceinline__ void sched_fence(uint32_t x, A&... a) {
  if (!((SF >> ID) & 1)) return;
  asm volatile("" : "+r"(x)::"memory");
#pragma unroll 1
  for (; __builtin_expect(x >= 100 + ID, 0); x >>= 1) { (touch(a), ...); __nanosleep(x); }
}
template <int N> __device__ __forceinline__ void reg_fence(float (&a)[N]) {
#pragma unroll
  for (int i = 0; i < N; i++) asm volatile("" : "+f"(a[i])::"memory");
}
template <int N> __device__ __forceinline__ void reg_fence(uint32_t (&a)[N]) {
#pragma unroll
  for (int i = 0; i < N; i++) asm volatile("" : "+r"(a[i])::"memory");
}
__device__ __forceinline__ float ex2(float x) { float y; asm("ex2.approx.ftz.f32 %0, %1;" : "=f"(y) : "f"(x)); return y; }
__device__ __forceinline__ uint32_t pack_bf16(float lo, float hi) {
  uint32_t r; asm("cvt.rn.bf16x2.f32 %0, %1, %2;" : "=r"(r) : "f"(hi), "f"(lo)); return r;
}
__device__ __forceinline__ void stsm4(uint32_t a, uint32_t r0, uint32_t r1, uint32_t r2, uint32_t r3) {
  asm volatile("stmatrix.sync.aligned.m8n8.x4.shared.b16 [%0], {%1, %2, %3, %4};" ::"r"(a), "r"(r0), "r"(r1), "r"(r2), "r"(r3) : "memory");
}
__device__ __forceinline__ void stsm4t(uint32_t a, uint32_t r0, uint32_t r1, uint32_t r2, uint32_t r3) {
  asm volatile("stmatrix.sync.aligned.m8n8.x4.trans.shared.b16 [%0], {%1, %2, %3, %4};" ::"r"(a), "r"(r0), "r"(r1), "r"(r2), "r"(r3) : "memory");
}
__device__ __forceinline__ void ldsm4(uint32_t a, uint32_t& r0, uint32_t& r1, uint32_t& r2, uint32_t& r3) {
  asm volatile("ldmatrix.sync.aligned.m8n8.x4.shared.b16 {%0, %1, %2, %3}, [%4];" : "=r"(r0), "=r"(r1), "=r"(r2), "=r"(r3) : "r"(a) : "memory");
}
__device__ __forceinline__ void sts16(uint32_t a, uint32_t v) { asm volatile("st.shared.u16 [%0], %1;" ::"r"(a), "h"((uint16_t)v) : "memory"); }
__device__ __forceinline__ void mma16816(float& c0, float& c1, float& c2, float& c3, uint32_t a0, uint32_t a1, uint32_t a2, uint32_t a3,
                                         uint32_t b0, uint32_t b1) {
  asm volatile("mma.sync.aligned.m16n8k16.row.col.f32.bf16.bf16.f32 {%0, %1, %2, %3}, {%4, %5, %6, %7}, {%8, %9}, {%0, %1, %2, %3};"
               : "+f"(c0), "+f"(c1), "+f"(c2), "+f"(c3) : "r"(a0), "r"(a1), "r"(a2), "r"(a3), "r"(b0), "r"(b1));
}
__device__ __forceinline__ uint32_t sdesc(uint32_t addr, uint32_t lbo) { return (addr >> 4) + ((lbo >> 4) << 16); }
__device__ __forceinline__ uint64_t desc64(uint32_t lo, uint32_t hi) { uint64_t d; asm("mov.b64 %0, {%1, %2};" : "=l"(d) : "r"(lo), "r"(hi)); return d; }
__device__ __forceinline__ void dadd(uint64_t& d, uint32_t inc) {
  asm("{\n.reg .b32 l, h;\nmov.b64 {l, h}, %0;\nadd.u32 l, l, %1;\nmov.b64 %0, {l, h};\n}" : "+l"(d) : "r"(inc));
}

struct Ring {
  uint32_t slot, phase, xp;
  __device__ __forceinline__ void uniform() {
    slot = __shfl_sync(0xffffffffu, slot, 0); phase = __shfl_sync(0xffffffffu, phase, 0); xp = __shfl_sync(0xffffffffu, xp, 0);
  }
  __device__ __forceinline__ void next() { if (++slot == NS) { slot = 0; phase ^= 1; } }
  __device__ __forceinline__ void next_if(bool p) { slot += p; if (slot == NS) { slot = 0; phase ^= 1; } }
};
__device__ __forceinline__ uint32_t borrow(int ks, int n) {
  const int k = ks + 1;
  return k >= 4 && !(k & 2) && k < n ? k & 1 : 2;
}

constexpr uint32_t Q_RANGES = NBETA * NH + __builtin_popcount(EARLY_MASK) * 5, Q_ALL = NBETA * (NH + 5);
constexpr int NRANGE = NCTA / 5;
struct Work { int kind, mode, k0, nsteps, range, beta, sub; };
struct Sched { uint16_t queue[Q_ALL]; uint32_t piece[NRANGE + 1][4]; };
constexpr Sched make_sched() {
  Sched s{};
  int q = 0, a = 0;
  for (int t = 0, e = 0; a < NBETA * NH; t++) {
    for (; e < NBETA && 8 * (e & ~PAIRB) + PK <= t && a >= P_POS; e++)
      for (int col = 0; col < 5 && (EARLY_MASK >> e & 1); col++) s.queue[q++] = 0x8000 | (e & 1 ? 4 - col : col) << 8 | e;
    for (int b = 0; b < NBETA; b++)
      for (int h = 0; h < NH; h++)
        if ((b >= B_LATE && h >= H_LATE ? 300 + b + LATE_G * (h >> 2) : 8 * (b & ~PAIRB) + KG * (h >> 2)) == t) { s.queue[q++] = b << 5 | h; a++; }
  }
  for (int b = 0; b < NBETA; b++)
    for (int col = 0; col < 5 && !(EARLY_MASK >> b & 1); col++) s.queue[q++] = 0x8000 | col << 8 | b;
  constexpr uint32_t T[NRANGE * 2] = {PIECE_TABLE};
  for (int g = 0; g <= NRANGE; g++)
    for (int n = 0; n < 4; n++) s.piece[g][n] = g < NRANGE && n < 2 ? T[2 * g + n] : 2u << 30;
  return s;
}
__constant__ Sched c_sched = make_sched();
constexpr uint64_t first_bits(int k0) {
  const Sched s = make_sched();
  uint64_t v = 0;
  for (int k = 0; k < 10; k++) v |= (uint64_t)(s.queue[(k0 + k) * 8] >> 2) << (6 * k);
  return v;
}
__host__ __device__ constexpr uint32_t first_entry(uint32_t q, uint64_t lo, uint64_t hi) {
  return (uint32_t)((q < 80 ? lo >> (q >> 3) * 6 : hi >> ((q >> 3) - 10) * 6) & 63) * 4 + (q & 4) * 8 + (q & 3);
}
constexpr uint64_t FIRST_LO = first_bits(0), FIRST_HI = first_bits(10);
constexpr bool first_ok() {
  const Sched s = make_sched();
  for (int q = 0; q < NCTA; q++) if (first_entry(q, FIRST_LO, FIRST_HI) != s.queue[q]) return false;
  return true;
}
static_assert(first_ok());
constexpr int N_EARLY = __builtin_popcount(EARLY_MASK);
constexpr bool reuse_ok() {
  const Sched s = make_sched();
  int first[NBETA + OR] = {};
  for (int q = Q_RANGES - 1; q >= 0; q--) if (!(s.queue[q] & 0x8000)) first[s.queue[q] >> 5] = q;
  for (int q = 0; q < Q_RANGES; q++) if ((s.queue[q] & 0x8000) && (s.queue[q] & 31) >= OR0 && q - first[(s.queue[q] & 31) + OR] > NCTA - 32) return false;
  return first[OR0 + OR] >= NCTA && P_POS >= NCTA;
}
static_assert(reuse_ok());
template <bool SIMPLE> __device__ __forceinline__ bool o_reuse(uint32_t b) { return !SIMPLE && b - (OR0 + OR) < N_EARLY - OR0; }
template <bool SIMPLE> __device__ __forceinline__ uint32_t o_slot(uint32_t b) { return o_reuse<SIMPLE>(b) ? OR0 + (b - OR0) % OR : b; }
__device__ __forceinline__ Work decode(uint32_t d) {
  Work w;
  w.kind = d >> 30; if (w.kind == 3) w.kind = 1;
  w.mode = (d >> 28) & 3; w.k0 = (d >> 22) & 63;
  if (w.kind == 0) { w.beta = (d >> 5) & 31; w.sub = d & 31; w.nsteps = DM / 64; }
  else { w.beta = d & 31; w.sub = (d >> 8) & 7; w.nsteps = ((d >> 16) & 63) + 1; }
  w.range = ((d >> 11) & 31) * 5 + w.sub;
  return w;
}

__device__ __forceinline__ bool reached(const unsigned* cnt, unsigned target) {
  unsigned v;
  asm volatile("ld.acquire.gpu.global.u32 %0, [%1];" : "=r"(v) : "l"(cnt) : "memory");
  return (int)(v - target) >= 0;
}
__device__ __forceinline__ void wait_count(const unsigned* cnt, unsigned target) {
  unsigned n = 0;
  while (!__all_sync(0xffffffffu, reached(cnt, target))) { if (++n > (1u << 24)) __trap(); }
}
__device__ __forceinline__ uint32_t lds(uint32_t a) { uint32_t v; asm volatile("ld.volatile.shared.u32 %0, [%1];" : "=r"(v) : "r"(a) : "memory"); return v; }

#define TRACE(u, e)
#define T3(u, e)
#define T2C(u, e)
#define T2P(u, r, e)
#define TTAIL(k)
#define TCLK(k)
#define TO -1
#define TRACE_O(k) if (TO == k) TRACE(i, 5)
#define TRACE_P(u, e)
#define TRACE_IN(u, e)

struct Ctx {
  uint32_t sb;
  int wg, warp;
  uint32_t mqk, mpv;
  bool lead;
  int lane0, lane;
  int src;
};
template <int N> __device__ __forceinline__ uint32_t dhi(uint32_t lo) { return 0x40000040u + (lo >> (26 + N)); }
__device__ __forceinline__ void release(const Ctx& c, uint32_t slot) {
  if (c.lead) mbar_arrive(c.sb + BAR_EMPTY + slot * 8);
}
__device__ __forceinline__ uint32_t acquire(const Ctx& c, Ring& r, bool have = false) {
  const uint32_t s = r.slot;
  if (!have) mbar_wait_w(c.sb + BAR_FULL + s * 8, r.phase);
  r.next();
  return s;
}
__device__ __forceinline__ void mbar_wait2_w(uint32_t b0, uint32_t p0, uint32_t b1, uint32_t p1) {
  uint32_t n = 0;
  while (!__all_sync(0xffffffffu, mbar_try(b0, p0) & mbar_try(b1, p1))) {
    if (++n > (1u << 22)) __trap();
  }
}
__device__ __forceinline__ void mbar_wait3_w(uint32_t b0, uint32_t p0, uint32_t b1, uint32_t p1, uint32_t b2, uint32_t p2) {
  uint32_t n = 0;
  while (!__all_sync(0xffffffffu, mbar_try(b0, p0) & mbar_try(b1, p1) & mbar_try(b2, p2))) {
    if (++n > (1u << 22)) __trap();
  }
}
__device__ __forceinline__ void acquire2(const Ctx& c, Ring& r, uint32_t& s0, uint32_t& s1, bool have = false) {
  const uint32_t p0 = r.phase;
  s0 = r.slot; r.next(); s1 = r.slot;
  if (!have) mbar_wait2_w(c.sb + BAR_FULL + s0 * 8, p0, c.sb + BAR_FULL + s1 * 8, r.phase);
  r.next();
}
template <int N>
__device__ __forceinline__ bool peek(const Ctx& c, Ring r) {
  bool ok = true;
#pragma unroll
  for (int k = 0; k < N; k++) { ok &= mbar_test(c.sb + BAR_FULL + r.slot * 8, r.phase); r.next(); }
  return ok;
}
__device__ __forceinline__ void staged(const Ctx& c, int part) {
  fence_async_smem();
  __syncwarp();
  mbar_arrive_warp(c.sb + BAR_STG + c.wg * 16 + part * 8);
}

template <int WG, bool FIRST, int H>
__device__ __forceinline__ void proj_half(const Ctx& c, float (&acc)[64], uint32_t w, uint32_t x, uint32_t sw) {
  uint64_t dx = desc64((SB0 + x * SLOT + (WG ? 0 : H * 8192)) >> 4, dhi<0>(x) + sw);
  uint64_t dw = desc64(WG ? (SB0 + w * SLOT + H * 8192) >> 4 : sdesc(SB0 + w * SLOT, 8192), dhi<1>(x));
  wg_fence();
  if (WG) { if (FIRST) wgmma_proj96_init(acc, dw, dx, 0); else wgmma_proj96(acc, dw, dx, 1); }
  else { if (FIRST) wgmma_proj_init(acc, dx, dw, 0); else wgmma_proj(acc, dx, dw, 1); }
#pragma unroll
  for (int k = 1; k < 4; k++) {
    dadd(dx, k == 2 ? 2 + (sw >> 30) * 28 : 2); dadd(dw, 128);
    if (WG) wgmma_proj96(acc, dw, dx, 1); else wgmma_proj(acc, dx, dw, 1);
  }
  wg_commit();
}

__device__ __forceinline__ void proj_store16(uint32_t a, const float* f, float sc) {
  stsm4t(a, pack_bf16(f[0] * sc, f[1] * sc), pack_bf16(f[2] * sc, f[3] * sc), pack_bf16(f[4] * sc, f[5] * sc), pack_bf16(f[6] * sc, f[7] * sc));
}

__device__ __forceinline__ uint32_t stage_off(const Ctx& c) {
  const int lane = c.lane, mi = lane >> 3, r8 = lane & 7;
  return ((mi >> 1) * 8 + r8) * 128 + (((2 * c.warp + (mi & 1)) ^ r8) << 4);
}
__device__ __forceinline__ uint32_t q3_swz(uint32_t r8) { return ((r8 & 3) << 1) | (r8 >> 2); }
template <int H>
__device__ __forceinline__ void stage_t2(const Ctx& c, const float (&a)[64], float sc) {
  const uint32_t base = c.sb + QBUF_OFF + 2 * 16384 + H * 8192 + stage_off(c);
#pragma unroll
  for (int jj = 0; jj < 4; jj++) proj_store16(base + jj * 2048, &a[jj * 8], sc);
}
template <int H, bool IS_Q>
__device__ __forceinline__ void stage_t3(const Ctx& c, const float (&a)[64], float sc) {
  const uint32_t off = stage_off(c), r8 = (off >> 7) & 7;
  const uint32_t t3 = c.sb + QBUF_OFF + 3 * 16384 + H * 4096 + (IS_Q ? off ^ ((r8 ^ q3_swz(r8)) << 4) : off);
  proj_store16(t3, &a[32], sc);
  proj_store16(t3 + 2048, &a[40], sc);
}

template <int WG, int h, int NW = 4>
__device__ __forceinline__ void load_part(const Ctx& c, Ring r, uint32_t (&q)[32]) {
  uint32_t n = 0;
  while (NW && !__all_sync(0xffffffffu, peek<NW>(c, r))) {
    if (++n > (1u << 26)) __trap();
  }
  const int lane = c.lane, mi = lane >> 3, r8 = lane & 7;
  if (WG) { r.next(); r.next(); }
  const uint32_t off = c.sb + (WG ? stage_off(c) : (16 * c.warp + (mi & 1) * 8 + r8) * 128), t0 = off + r.slot * SLOT;
  r.next();
  const uint32_t t1 = off + r.slot * SLOT;
#pragma unroll
    for (int jj = 0; jj < (WG ? 6 : 8); jj++) {
      uint32_t* p = &q[4 * jj];
      if (WG) asm volatile("ldmatrix.sync.aligned.m8n8.x4.trans.shared.b16 {%0, %1, %2, %3}, [%4];" : "=r"(p[0]), "=r"(p[1]), "=r"(p[2]), "=r"(p[3])
                           : "r"((jj < 4 ? t0 + h * 8192 : t1 + h * 4096) + (jj & 3) * 2048) : "memory");
      else ldsm4((h ? t1 : t0) + (jj >> 2) * 8192 + (((((2 * jj) & 7) + (mi >> 1)) ^ r8) << 4), p[0], p[1], p[2], p[3]);
    }
}
template <int WG>
__device__ __forceinline__ void add_part(const Ctx& c, const uint32_t (&q)[32], float (&a)[64]) {
  const uint32_t one = (c.lane >> 3) == (c.lane & 3) ? 0x3f80u << (c.lane & 4) * 4 : 0;
#pragma unroll
  for (int i = 0; i < (WG ? 12 : 16); i++)
    asm("mma.sync.aligned.m16n8k8.row.col.f32.bf16.bf16.f32 {%0, %1, %2, %3}, {%4, %5}, {%6}, {%0, %1, %2, %3};"
        : "+f"(a[4 * i]), "+f"(a[4 * i + 1]), "+f"(a[4 * i + 2]), "+f"(a[4 * i + 3]) : "r"(q[2 * i]), "r"(q[2 * i + 1]), "r"(one));
}

__device__ __forceinline__ void trace_dump(const Ctx& c) {
}
struct RowSum { float l0, l1; };
__device__ __forceinline__ const char* o_addr(uint32_t item, int row, int lane) {
  return reinterpret_cast<const char*>(g_o) + (((item >> 10) * (2 * SQ) + row) * 128 + (lane ^ (lane >> 3)) * 16);
}
__device__ __forceinline__ void o_stg(const char* p, int i, const uint32_t* q) {
  asm volatile("st.global.v4.b32 [%0], {%1, %2, %3, %4};"
               ::"l"(p + (i >> 1) * (SQ * 128) + (i & 1) * 512), "r"(q[0]), "r"(q[1]), "r"(q[2]), "r"(q[3]) : "memory");
}
template <int MODE, int I0 = 0, int NI = 4>
__device__ __forceinline__ void o_emit(const char* p, const float (&o)[64], float inv) {
#pragma unroll
  for (int i = I0; i < I0 + NI; i++) {
    uint32_t q[4];
#pragma unroll
    for (int j = 0; j < 4; j++) q[j] = pack_bf16(o[16 * i + 4 * j + 2 * MODE] * inv, o[16 * i + 4 * j + 2 * MODE + 1] * inv);
    o_stg(p, i, q);
  }
}
__device__ __forceinline__ void o_done(const Ctx& c) {
  __syncwarp();
  mbar_arrive_warp(c.sb + BAR_OUT);
  __syncwarp();
}
template <int WG>
__device__ __forceinline__ void o_first(const Ctx& c, uint32_t item, float (&o)[64], const RowSum& inv, uint32_t (&q)[32]) {
  const char* p = o_addr(item, WG ? 192 + 8 * c.warp : 64 + 16 * c.warp, c.lane);
  reg_fence(o);
#pragma unroll
  for (int j = 0; j < 16; j++) {
    if (WG) q[j] = pack_bf16((o[4 * j] + o[4 * j + 2]) * inv.l0, (o[4 * j + 1] + o[4 * j + 3]) * inv.l0);
    else q[j] = pack_bf16(o[4 * j] * inv.l0, o[4 * j + 1] * inv.l0);
    if (!WG && (j & 3) == 3 && (j >> 2) < 8 - LATE0) o_stg(p, j >> 2, q + j - 3);
  }
#pragma unroll
  for (int j = 0; j < 16; j++) {
    if (!WG) q[16 + j] = pack_bf16(o[4 * j + 2] * inv.l1, o[4 * j + 3] * inv.l1);
    if ((j & 3) == 3 && (j >> 2) < 4 - (WG ? LATE1 : LATE0)) o_stg(WG ? p : p + 1024, j >> 2, q + (WG ? 0 : 16) + j - 3);
  }
}
template <int WG>
__device__ __forceinline__ void o_rest(const Ctx& c, uint32_t item, uint32_t (&q)[32]) {
  const char* p = o_addr(item, WG ? 192 + 8 * c.warp : 64 + 16 * c.warp, c.lane);
#pragma unroll
  for (int i = WG ? 4 - LATE1 : 8 - LATE0; i < (WG ? 4 : 8); i++) o_stg(p + (i >> 2) * 1024, i & 3, q + 4 * i);
}
template <int K0, int K1>
__device__ __forceinline__ void o_piece(const Ctx& c, const char* p, int k, const float (&o)[64], const RowSum& inv) {
  constexpr int NI = 8 / O_STEPS, M = K0 * NI / 4;
  if constexpr (K1 - K0 == 1) {
    o_emit<M, K0 * NI % 4, NI>(p + M * 1024, o, M ? inv.l1 : inv.l0);
    if (K1 == O_STEPS) o_done(c);
  } else {
    if (k <= (K0 + K1) / 2) o_piece<K0, (K0 + K1) / 2>(c, p, k, o, inv); else o_piece<(K0 + K1) / 2, K1>(c, p, k, o, inv);
  }
}
template <int WG>
__device__ __forceinline__ void o_second(const Ctx& c, uint32_t item, int k, float (&o)[64], const RowSum& inv) {
  reg_fence(o);
  o_piece<0, O_STEPS>(c, o_addr(item, 128 * WG + 16 * c.warp, c.lane0 + (k >> 8)), k, o, inv);
}
template <int WG>
__device__ __forceinline__ void release_q(const Ctx& c) {
#pragma unroll
  for (int t = 0; t < 2; t++)
    if (c.lead) asm volatile("mbarrier.arrive.shared::cta.b64 _, [%0], 2;" ::"r"(c.sb + BAR_EMPTY + (NS + 2 * WG + t) * 8) : "memory");
  __syncwarp();
}
struct Slots { uint32_t w, x, o, po; };
template <int WG>
__device__ __forceinline__ void acc_fence(float (&a)[64]) {
#pragma unroll
  for (int i = 0; i < (WG ? 48 : 64); i++) asm volatile("" : "+f"(a[i])::"memory");
}
template <int WG>
__device__ __forceinline__ void begin_acquire(const Ctx& c, Ring& r, Slots& h, bool wait) {
  const uint32_t s0 = r.slot, p0 = r.phase, f = c.sb + BAR_FULL;
  r.next();
  const uint32_t p1 = r.phase;
  h.w = r.slot; r.next();
  h.x = WG ? r.slot : s0; h.o = WG ? s0 : r.slot; h.po = r.phase;
  if (wait) { if (WG) mbar_wait3_w(f + s0 * 8, p0, f + h.w * 8, p1, f + h.x * 8, r.phase); else mbar_wait2_w(f + s0 * 8, p0, f + h.w * 8, p1); }
  r.next();
}
template <int WG>
__device__ __forceinline__ void proj_begin(const Ctx& c, Ring& r, float (&a0)[64], Slots& h, bool wait, uint32_t sw) {
  begin_acquire<WG>(c, r, h, wait);
  proj_half<WG, true, 0>(c, a0, h.w, h.x, sw);
  if (WG) release(c, h.o);
}
template <int WG>
__device__ __forceinline__ void proj_main(Ctx& c, Ring& r, float (&a0)[64], float (&a1)[64], Slots& h, int n, uint32_t sw, int unit,
                                          uint32_t item, int nq, float (&o1)[64], const RowSum& inv) {
  constexpr bool DEEP = (PDEPTH >> WG) & 1;
  T2C(unit, 3);
  int ks = 1;
#pragma unroll 1
  do {
    const Slots p = h;
    const uint32_t b = borrow(ks, n), tile = NS + (WG ? 3 - b : b), f = c.sb + BAR_FULL;
    const uint32_t s0 = b != 2 ? tile : r.slot, p0 = b != 2 ? (r.xp >> b) & 1 : r.phase;
    r.next_if(b == 2);
    const uint32_t p1 = r.phase;
    h.w = r.slot; r.next();
    const uint32_t s2 = b != 2 ? tile : r.slot;
    h.po = b != 2 ? p0 : r.phase;
    r.next_if(b == 2);
    r.xp ^= 1 << b;
    h.x = WG ? s2 : s0; h.o = WG ? s0 : s2;
    mbar_wait3_w(f + s0 * 8, p0, f + h.w * 8, p1, f + (WG ? s2 : p.o) * 8, WG ? h.po : p.po);
    if (ks < 10) T2C(unit, ks * 4);
    if (DEEP) {
      proj_half<WG, false, 0>(c, a0, h.w, h.x, sw);
      release(c, WG ? h.o : p.o);
      if (ks < 10) T2C(unit, ks * 4 + 1);
      wg_wait<1>();
      if (ks < 10) T2C(unit, ks * 4 + 2);
      release(c, p.x); release(c, p.w);
    } else {
      release(c, WG ? h.o : p.o);
      wg_wait<0>();
      release(c, p.x); release(c, p.w);
      if (ks < 10) T2C(unit, ks * 4 + 1);
      proj_half<WG, false, 0>(c, a0, h.w, h.x, sw);
      if (ks < 10) T2C(unit, ks * 4 + 2);
    }
    proj_half<WG, false, 1>(c, a1, h.w, h.x, sw);
    if (ks < 10) T2C(unit, ks * 4 + 3);
    if (ks <= nq) o_second<WG>(c, item, ks, o1, inv);
  } while (++ks != n);
  {
    const uint32_t e0 = c.sb + BAR_EMPTY + (NS + 3 * WG) * 8, e1 = c.sb + BAR_EMPTY + (NS + 1 + WG) * 8;
    const uint32_t p0 = (r.xp ^ unit ^ 1) & 1, p1 = ((r.xp >> 1) ^ unit ^ 1) & 1;
    const uint32_t k0 = sw ? e0 : c.sb + BAR_FULL + r.slot * 8, pk = sw ? p0 : r.phase;
    uint32_t cnt = 0;
    while (!__all_sync(0xffffffffu, mbar_try(e0, p0) & mbar_try(e1, p1) & mbar_try(k0, pk) & (WG || mbar_try(c.sb + BAR_FULL + h.o * 8, h.po)))) {
      if (++cnt > (1u << 22)) __trap();
    }
  }
  c.lane = c.lane0 + (h.w >> 5);
  if (!WG) release(c, h.o);
}
template <int WG>
__device__ __forceinline__ void proj_end(const Ctx& c, float (&a1)[64], const Slots& h) {
  wg_wait<0>();
  acc_fence<WG>(a1);
  release(c, h.x); release(c, h.w);
}
__device__ __forceinline__ uint32_t get_desc(const Ctx& c, int i) {
  uint32_t d;
  mbar_wait_w(c.sb + BAR_DESC, (i - 1) & 1);
  asm volatile("ld.volatile.shared.u32 %0, [%1];" : "=r"(d) : "r"(c.sb + DESC_OFF + (i & 3) * 4) : "memory");
  return __shfl_sync(0xffffffffu, d, 0);
}

__device__ __forceinline__ float quad_max(float x) {
  x = fmaxf(x, __shfl_xor_sync(0xffffffffu, x, 1));
  return fmaxf(x, __shfl_xor_sync(0xffffffffu, x, 2));
}
__device__ __forceinline__ float quad_sum(float x) {
  x += __shfl_xor_sync(0xffffffffu, x, 1);
  return x + __shfl_xor_sync(0xffffffffu, x, 2);
}
template <bool SP, bool FIRST>
__device__ __forceinline__ void exps(const Ctx& c, const float (&s)[32], uint32_t (&p)[SP ? 8 : 16], RowSum& st) {
  if constexpr (SP) {
    uint32_t q[8];
    float t;
#pragma unroll
    for (int j = 0; j < 8; j++) {
      const float e0 = ex2(s[4 * j] + s[4 * j + 2]), e1 = ex2(s[4 * j + 1] + s[4 * j + 3]);
      if (j == 0) t = e0 + e1; else t += e0 + e1;
      q[j] = pack_bf16(e0, e1);
    }
    const bool odd = c.src & 2;
#pragma unroll
    for (int g = 0; g < 4; g++) {
      p[2 * g] = __shfl_sync(0xffffffffu, odd ? q[2 * g + 1] : q[2 * g], c.src);
      p[2 * g + 1] = __shfl_sync(0xffffffffu, odd ? q[2 * g] : q[2 * g + 1], c.src ^ 1);
    }
    st.l0 = FIRST ? t : st.l0 + t;
  } else {
    float t0, t1;
#pragma unroll
    for (int j = 0; j < 8; j++) {
      const float e0 = ex2(s[4 * j]), e1 = ex2(s[4 * j + 1]), e2 = ex2(s[4 * j + 2]), e3 = ex2(s[4 * j + 3]);
      if (j == 0) { t0 = e0 + e1; t1 = e2 + e3; } else { t0 += e0 + e1; t1 += e2 + e3; }
      p[2 * j] = pack_bf16(e0, e1);
      p[2 * j + 1] = pack_bf16(e2, e3);
    }
    st.l0 = FIRST ? t0 : st.l0 + t0;
    st.l1 = FIRST ? t1 : st.l1 + t1;
  }
}
template <bool SP>
__device__ __forceinline__ bool finish_sums(RowSum& st) {
  const float a = quad_sum(st.l0), b = SP ? a : quad_sum(st.l1);
  st.l0 = __fdividef(1.f, a); st.l1 = __fdividef(1.f, b);
  return !(a >= SUM_LO && a <= SUM_HI && b >= SUM_LO && b <= SUM_HI);
}
template <bool SP, bool INIT, int SITE, bool COMMIT = true, int RM = 0>
__device__ __forceinline__ void issue_qk(const Ctx& c, float (&s)[32], const uint32_t (&qs)[32], uint32_t dq, uint32_t dk) {
  uint64_t a = desc64(dq, dhi<SITE & 1>(dk)), b = desc64(dk, dhi<1 - (SITE & 1)>(dk) + 64);
  if (SP) {
    if (INIT) wgmma_qk_sp_init(s, qs[0], qs[1], qs[2], qs[3], b, 0, c.mqk); else wgmma_qk_sp(s, qs[0], qs[1], qs[2], qs[3], b, 0, c.mqk);
#pragma unroll
    for (int k = 1; k < 4; k++) { dadd(b, k == 2 ? 60 : 4); wgmma_qk_sp(s, qs[4 * k], qs[4 * k + 1], qs[4 * k + 2], qs[4 * k + 3], b, 1, c.mqk); }
  } else {
    if (RM & 1) wgmma_qk_rs(s, qs[0], qs[1], qs[2], qs[3], b, 0); else if (INIT) wgmma_qk_init(s, a, b, 0); else wgmma_qk(s, a, b, 0);
#pragma unroll
    for (int k = 1; k < 8; k++) {
      dadd(a, k == 4 ? 506 : 2); dadd(b, k == 4 ? 58 : 2);
      if (RM >> k & 1) wgmma_qk_rs(s, qs[4 * k], qs[4 * k + 1], qs[4 * k + 2], qs[4 * k + 3], b, 1); else wgmma_qk(s, a, b, 1);
    }
  }
  if (COMMIT) wg_commit();
}
template <bool SP, bool ACC, int SITE, bool SPLIT = false>
__device__ __forceinline__ void issue_pv(const Ctx& c, float (&o)[64], const uint32_t (&p)[SP ? 8 : 16], uint32_t dv) {
  uint64_t b = desc64(dv, dhi<SITE & 1>(dv) + 64);
  if constexpr (SP) {
    if (ACC) wgmma_pv_sp(o, p[0], p[1], p[2], p[3], b, 1, c.mpv); else wgmma_pv_sp_init(o, p[0], p[1], p[2], p[3], b, 0, c.mpv);
    if (SPLIT) wg_commit();
    dadd(b, 512);
    wgmma_pv_sp(o, p[4], p[5], p[6], p[7], b, 1, c.mpv);
  } else {
    if (ACC) wgmma_pv(o, p[0], p[1], p[2], p[3], b, 1); else wgmma_pv_init(o, p[0], p[1], p[2], p[3], b, 0);
#pragma unroll
    for (int k = 1; k < 4; k++) { dadd(b, 256); wgmma_pv(o, p[4 * k], p[4 * k + 1], p[4 * k + 2], p[4 * k + 3], b, 1); }
  }
  wg_commit();
}
__device__ __forceinline__ void pack_rows(const float (&o)[64], float sc, uint32_t (&q)[32]) {
#pragma unroll
  for (int j = 0; j < 32; j++) q[j] = pack_bf16(o[2 * j] * sc, o[2 * j + 1] * sc);
}
template <int MASK = 255>
__device__ __forceinline__ void stage_rows(const Ctx& c, uint32_t tile_addr, const uint32_t (&q)[32]) {
  const int lane = c.lane, mi = lane >> 3, r8 = lane & 7;
  const uint32_t row_addr = tile_addr + (16 * c.warp + (mi & 1) * 8 + r8) * 128;
#pragma unroll
  for (int jj = 0; jj < 8; jj++)
    if (MASK >> jj & 1) stsm4(row_addr + (jj >> 2) * 8192 + (((((2 * jj) & 7) + (mi >> 1)) ^ r8) << 4), q[4 * jj], q[4 * jj + 1], q[4 * jj + 2], q[4 * jj + 3]);
}
__device__ __forceinline__ void stage_rows(const Ctx& c, uint32_t tile_addr, const float (&o)[64], float sc) {
  uint32_t q[32];
  pack_rows(o, sc, q);
  stage_rows(c, tile_addr, q);
}
template <int WG, int H>
__device__ __forceinline__ void stage_out(const Ctx& c, const float (&a)[64]) {
  if (WG) { stage_t3<H, false>(c, a, 1.f); if (H) staged(c, 0); stage_t2<H>(c, a, 1.f); }
  else stage_rows(c, c.sb + QBUF_OFF + H * 16384, a, 1.f);
  if (H || !WG) staged(c, H);
}
template <int SITE>
__device__ __forceinline__ void issue_qk_rs(float (&s)[32], uint32_t (&q)[32], uint32_t dk) {
  uint64_t b = desc64(dk, dhi<SITE>(dk) + 64);
  reg_fence(q);
  wg_fence();
  wgmma_qk_rs_init(s, q[0], q[1], q[2], q[3], b, 0);
#pragma unroll
  for (int k = 1; k < 8; k++) { dadd(b, k == 4 ? 58 : 2); wgmma_qk_rs(s, q[4 * k], q[4 * k + 1], q[4 * k + 2], q[4 * k + 3], b, 1); }
  wg_commit();
}

__device__ __forceinline__ void redo_tile(const Ctx& c, uint32_t q_addr, uint32_t half, const __nv_bfloat16* kp, const __nv_bfloat16* vp,
                                          uint32_t item, int row) {
  float o[64];
  const int lane = lane_now(), g = lane >> 2, cc = lane & 3, mi = lane >> 3, r8 = lane & 7;
  const uint32_t qa = q_addr + (half == 4096 ? 8 * c.warp + r8 : 16 * c.warp + (mi & 1) * 8 + r8) * 128, swz = half == 4096 ? q3_swz(r8) : r8;
  const uint32_t* kq = reinterpret_cast<const uint32_t*>(kp + g * DH) + cc;
  const unsigned short* vq = reinterpret_cast<const unsigned short*>(vp + 2 * cc * DH) + g;
  float m0 = -INFINITY, m1 = -INFINITY, l0 = 0.f, l1 = 0.f;
#pragma unroll
  for (int i = 0; i < 64; i++) o[i] = 0.f;
#pragma unroll 1
  for (int kb = 0; kb < SK / 16; kb++) {
    float z[8] = {0.f, 0.f, 0.f, 0.f, 0.f, 0.f, 0.f, 0.f};
#pragma unroll 2
    for (int kk = 0; kk < 8; kk++) {
      uint32_t a0, a1, a2, a3;
      ldsm4(qa + (kk >> 2) * half + ((((kk & 3) * 2 + (mi >> 1)) ^ swz) << 4), a0, a1, a2, a3);
      const uint32_t* kr = kq + kb * (16 * DH / 2) + kk * 8;
      mma16816(z[0], z[1], z[2], z[3], a0, a1, a2, a3, __ldg(kr), __ldg(kr + 4));
      mma16816(z[4], z[5], z[6], z[7], a0, a1, a2, a3, __ldg(kr + 8 * DH / 2), __ldg(kr + 8 * DH / 2 + 4));
    }
    const float n0 = fmaxf(m0, quad_max(fmaxf(fmaxf(z[0], z[1]), fmaxf(z[4], z[5]))));
    const float n1 = fmaxf(m1, quad_max(fmaxf(fmaxf(z[2], z[3]), fmaxf(z[6], z[7]))));
    const float al0 = ex2(m0 - n0), al1 = ex2(m1 - n1);
    m0 = n0; m1 = n1;
#pragma unroll
    for (int i = 0; i < 8; i++) z[i] = ex2(z[i] - ((i & 2) ? n1 : n0));
    l0 = l0 * al0 + (z[0] + z[1]) + (z[4] + z[5]);
    l1 = l1 * al1 + (z[2] + z[3]) + (z[6] + z[7]);
    const uint32_t a0 = pack_bf16(z[0], z[1]), a1 = pack_bf16(z[2], z[3]), a2 = pack_bf16(z[4], z[5]), a3 = pack_bf16(z[6], z[7]);
    const unsigned short* vr = vq + kb * (16 * DH);
#pragma unroll
    for (int nb = 0; nb < 16; nb++) {
      o[4 * nb] *= al0; o[4 * nb + 1] *= al0; o[4 * nb + 2] *= al1; o[4 * nb + 3] *= al1;
      const uint32_t b0 = __ldg(vr + nb * 8) | ((uint32_t)__ldg(vr + nb * 8 + DH) << 16);
      const uint32_t b1 = __ldg(vr + nb * 8 + 8 * DH) | ((uint32_t)__ldg(vr + nb * 8 + 9 * DH) << 16);
      mma16816(o[4 * nb], o[4 * nb + 1], o[4 * nb + 2], o[4 * nb + 3], a0, a1, a2, a3, b0, b1);
    }
  }
  const char* p = o_addr(item, row, lane);
  o_emit<0>(p, o, __fdividef(1.f, quad_sum(l0)));
  o_emit<1>(half == 4096 ? p : p + 1024, o, __fdividef(1.f, quad_sum(l1)));
}

template <bool SPA, bool SPB, int SITE, int ID>
__device__ __forceinline__ void batch(const Ctx& c, float (&s)[32], const uint32_t (&qs)[32], uint32_t dq, uint32_t dk, float (&ob)[64],
                                      uint32_t (&pb)[SPB ? 8 : 16], uint32_t dv) {
  if constexpr (SPA) {
    reg_fence(pb);
    wg_fence();
    issue_pv<SPB, true, ID>(c, ob, pb, dv);
    issue_qk<SPA, false, ID>(c, s, qs, dq, dk);
  } else {
    constexpr bool EARLY = ((QK_EARLY_MASK >> (SITE + (SPB ? 2 : 0))) & 1) != 0;
    if (!EARLY) reg_fence(pb);
    wg_fence();
    issue_qk<SPA, false, ID, !SPB, SITE ? RM0 : SPB ? RM2 : RM1>(c, s, qs, dq, dk);
    if (EARLY) { reg_fence(pb); wg_fence(); }
    issue_pv<SPB, true, ID, SPB>(c, ob, pb, dv);
  }
}

template <bool SP0>
__device__ __forceinline__ bool attention(Ctx& c, Ring& r, int unit, uint32_t& d, const float (&a0)[64], float (&o0)[64], float (&o1)[64],
                                          RowSum& st0, RowSum& st1, const Slots& h, uint32_t (&q1)[32]) {
  constexpr bool SP1 = false;
  if (SP0) { c.mqk = META_QK + (d >> 28); c.mpv = META_PV + (d >> 28); asm volatile("" : "+r"(c.mqk), "+r"(c.mpv)); }
  if (SP0) c.src = (c.lane & 28) | ((c.lane & 1) << 1) | ((c.lane >> 1) & 1);
  float s[32];
  uint32_t p0[SP0 ? 8 : 16], p1[16];
  const uint32_t q0a = c.sb + QBUF_OFF + (SP0 ? 3 : 0) * 16384, q1a = c.sb + QBUF_OFF + (SP0 ? 2 : 1) * 16384;
  const uint32_t dq0 = sdesc(SB0 + QBUF_OFF, 0), dq1 = sdesc(SB0 + QBUF_OFF + (SP0 ? 2 : 1) * 16384, 0);
  uint32_t sk = acquire(c, r, true), sv, sn;
  uint32_t qs[32];
  float s1[32];
  if (SP0) {
    stage_t3<0, true>(c, a0, SM_C);
    stage_t2<0>(c, a0, SM_C);
    proj_end<1>(c, o0, h);
    stage_t3<1, true>(c, o0, SM_C);
    stage_t2<1>(c, o0, SM_C);
    bar_sync(5, 128);
    const int g = c.lane >> 2, cc = c.lane & 3;
    const uint32_t qa = q0a + (8 * c.warp + g) * 128 + (cc & 1) * 8;
#pragma unroll
    for (int k = 0; k < 8; k++)
      asm volatile("ld.shared.v2.u32 {%0, %1}, [%2];" : "=r"(qs[2 * k]), "=r"(qs[2 * k + 1])
                   : "r"(qa + (k >> 2) * 4096 + ((((k & 3) * 2 + (cc >> 1)) ^ q3_swz(g)) << 4)) : "memory");
    fence_async_smem();
    bar_sync(1, 256);
    TRACE(unit, 2);
    wg_fence();
    issue_qk<SP1, true, 1>(c, s1, qs, dq1, sdesc(SB0 + sk * SLOT, 0));
#pragma unroll
    for (int k = 0; k < 8; k++)
      if (RM2 >> k & 1) ldsm4(q1a + (k >> 2) * 8192 + (16 * c.warp + (c.lane & 15)) * 128 + (((2 * (k & 3) + (c.lane >> 4)) ^ (c.lane & 7)) << 4),
                              q1[4 * k], q1[4 * k + 1], q1[4 * k + 2], q1[4 * k + 3]);
#pragma unroll
    for (int k = 0; k < 16; k++) asm volatile("" : "+r"(qs[k])::"memory");
    wg_fence();
    issue_qk<SP0, true, 0>(c, s, qs, dq0, sdesc(SB0 + sk * SLOT, 0));
    const bool have = peek<2>(c, r);
    wg_wait<1>();
    reg_fence(s1);
    exps<SP1, true>(c, s1, p1, st1);
    sched_fence<11>(sk, p1);
    acquire2(c, r, sv, sn, __all_sync(0xffffffffu, have));
    wg_wait<0>();
    wg_fence();
    issue_pv<SP1, false, 1>(c, o1, p1, sdesc(SB0 + sv * SLOT, 1024));
    if (LAG_BAR & 1) asm volatile("bar.arrive 4, 256;" ::: "memory");
    sched_fence<12>(sk, s);
    release(c, sk);
    sk = sn;
    exps<SP0, true>(c, s, p0, st0);
    reg_fence(p0);
    wg_fence();
    issue_pv<SP0, false, 0>(c, o0, p0, sdesc(SB0 + sv * SLOT, 1024));
    issue_qk<SP0, true, 2>(c, s, qs, dq0, sdesc(SB0 + sk * SLOT, 0));
    sn = acquire(c, r);
    wg_wait<0>();
    reg_fence(s);
  } else {
    pack_rows(a0, SM_C, qs);
    stage_rows(c, q0a, qs);
    proj_end<0>(c, o1, h);
    TRACE(unit, 2);
    float sc = SM_C;
    issue_qk_rs<0>(s, qs, sdesc(SB0 + sk * SLOT, 0));
    sched_fence<0>(sk, sc);
    pack_rows(o1, sc, q1);
    stage_rows<~RM1>(c, q1a, q1);
    issue_qk_rs<1>(s1, q1, sdesc(SB0 + sk * SLOT, 0));
    asm volatile("bar.arrive 1, 256;" ::: "memory");
    bool have = peek<2>(c, r);
    wg_wait<1>();
    reg_fence(s);
    exps<SP0, true>(c, s, p0, st0);
    sched_fence<1>(sk, p0);
    acquire2(c, r, sv, sn, __all_sync(0xffffffffu, have));
    wg_wait<0>();
    reg_fence(s1);
    fence_async_smem();
    __syncwarp();
    wg_fence();
    issue_qk<SP0, false, 2, true, RM0>(c, s, qs, dq0, sdesc(SB0 + sn * SLOT, 0));
    issue_pv<SP0, false, 0>(c, o0, p0, sdesc(SB0 + sv * SLOT, 1024));
    sched_fence<2>(sk, s1);
    release(c, sk);
    have = peek<1>(c, r);
    sk = sn;
    exps<SP1, true>(c, s1, p1, st1);
    reg_fence(p1);
    wg_fence();
    issue_pv<SP1, false, 1>(c, o1, p1, sdesc(SB0 + sv * SLOT, 1024));
    sn = acquire(c, r, __all_sync(0xffffffffu, have));
    if (LAG_BAR & 1) bar_sync(4, 256);
    wg_wait<1>();
    reg_fence(s);
  }
  TRACE_IN(unit, 4);
  T2C(unit, 51);
#pragma unroll 1
  for (int j = 1; j < 15; j++) {
    const uint32_t sv_prev = sv, sk_prev = sk;
    sv = sn;
    const uint32_t dv = sdesc(SB0 + sv * SLOT, 1024);
    reg_fence(p0);
    exps<SP0, false>(c, s, p0, st0);
    batch<SP1, SP0, 0, 3>(c, s, q1, dq1, sdesc(SB0 + sk * SLOT, 0), o0, p0, dv);
    sk = acquire(c, r);
    wg_wait<1>();
    reg_fence(s); reg_fence(p1);
    release(c, sv_prev); release(c, sk_prev);
    exps<SP1, false>(c, s, p1, st1);
    batch<SP0, SP1, 1, 4>(c, s, qs, dq0, sdesc(SB0 + sk * SLOT, 0), o1, p1, dv);
    sn = acquire(c, r);
    if (SP0) wg_wait<0>(); else wg_wait<1>();
    reg_fence(s);
  }
  TRACE_IN(unit, 5);
  T2C(unit + 1, 52);
  const uint32_t sv_prev = sv;
  sv = sn;
  const uint32_t dv = sdesc(SB0 + sv * SLOT, 1024);
  reg_fence(p0);
  exps<SP0, false>(c, s, p0, st0);
  batch<SP1, SP0, 0, 5>(c, s, q1, dq1, sdesc(SB0 + sk * SLOT, 0), o0, p0, dv);
  asm volatile("ld.volatile.shared.u32 %0, [%1];" : "=r"(d) : "r"(c.sb + DESC_OFF + ((unit + 1) & 3) * 4) : "memory");
  const bool have = peek<2 + SP0>(c, r);
  wg_wait<1>();
  reg_fence(s); reg_fence(p1);
  release(c, sv_prev); release(c, sk);
  exps<SP1, false>(c, s, p1, st1);
  reg_fence(p1);
  wg_fence();
  issue_pv<SP1, true, 2>(c, o1, p1, dv);
  if (SP0) sched_fence<6>(sk, st0.l0, st1.l0, st1.l1); else sched_fence<5>(sk, st0.l0, st0.l1, st1.l0, st1.l1);
  c.lane = c.lane0 + (sk >> 5);
  const bool bad = finish_sums<SP0>(st0) | finish_sums<SP1>(st1);
  uint32_t any;
  asm volatile("{\n.reg .pred p, q;\nsetp.ne.u32 p, %1, 0;\nbar.red.or.pred q, %2, 128, p;\nselp.u32 %0, 1, 0, q;\n}"
               : "=r"(any) : "r"((uint32_t)bad), "n"(2 + SP0) : "memory");
  any = __any_sync(0xffffffffu, any);
  d = __shfl_sync(0xffffffffu, d, 0);
  if (d < (2u << 30) && !__all_sync(0xffffffffu, have)) { Ring t = r; Slots u; begin_acquire<SP0>(c, t, u, true); }
  wg_wait<0>();
  reg_fence(o0); reg_fence(o1);
  release(c, sv);
  return any;
}

template <int WG>
__device__ __forceinline__ void consumer(Ctx c, const __nv_bfloat16* const* kv) {
  asm volatile("setmaxnreg.inc.sync.aligned.u32 %0;" ::"n"(WG ? REG_C : 504 - REG_C - REG_P));
  c.wg = WG;
  Ring r{0, 0, 0};
  float a0[64], a1[64], o1[64];
  Slots h;
  RowSum inv0, inv1;
  uint32_t oq[32];
  uint32_t d = first_entry(blockIdx.x, FIRST_LO, FIRST_HI) * 1025, dc = 0, sw;
  int i = 0, nq;
begin:
  sw = d & (1u << 30);
  proj_begin<WG>(c, r, a0, h, true, sw);
  proj_half<WG, true, 1>(c, a1, h.w, h.x, sw);
  nq = 0;
#pragma unroll
  for (int k = 0; k < 64; k++) asm volatile("" : "=f"(o1[k]));
  asm volatile("" : "=f"(inv1.l0), "=f"(inv1.l1));
  while (true) {
    TRACE(i, 0); TRACE(i, 6);
    proj_main<WG>(c, r, a0, a1, h, d >> 30 ? ((d >> 16) & 63) + 1 : DM / 64, sw, i, dc, nq, o1, inv1);
    dc = d;
    TRACE(i, 1);
    if (d >> 30) goto out_tile;
    wg_wait<1>();
    acc_fence<WG>(a0);
    if (WG ? attention<WG>(c, r, i, d, a0, a1, o1, inv0, inv1, h, oq) : attention<WG>(c, r, i, d, a0, o1, a1, inv1, inv0, h, oq)) goto redo;
    if (d >= (2u << 30)) break;
    sw = d & (1u << 30);
    proj_begin<WG>(c, r, a0, h, false, sw);
    release_q<WG>(c);
    if (WG) sched_fence<8>(h.w, inv0.l0); else sched_fence<7>(h.w, inv0.l0, inv0.l1);
    o_first<WG>(c, dc, a1, inv0, oq);
    sched_fence<9>(h.w, inv1.l0);
    proj_half<WG, true, 1>(c, a1, h.w, h.x, sw);
    o_rest<WG>(c, dc, oq);
    nq = O_STEPS;
    TRACE(i, 3); TRACE(i, 7);
    i++;
  }
  release_q<WG>(c);
  o_first<WG>(c, dc, a1, inv0, oq);
  o_rest<WG>(c, dc, oq);
#pragma unroll
  for (int k = 1; k <= O_STEPS; k++) o_second<WG>(c, dc, k, o1, inv1);
next:
  TRACE(i, 3); TRACE(i, 7);
  if ((d >> 30) != 2) {
    i++;
    r.uniform();
    goto begin;
  }
  trace_dump(c);
  return;
out_tile:
  if (d & 96) goto finish;
  d = get_desc(c, i + 1);
  wg_wait<1>();
  acc_fence<WG>(a0);
  TRACE_O(0);
  stage_out<WG, 0>(c, a0);
  TRACE_O(1);
  proj_end<WG>(c, a1, h);
  TRACE_O(2);
  stage_out<WG, 1>(c, a1);
  TRACE(i, 2);
  goto next;
finish:
  {
    uint32_t q[32];
#pragma unroll 1
    for (int k = (d >> 5) & 3; k > 1; k--) {
      wg_wait<0>();
      acc_fence<WG>(a0); acc_fence<WG>(a1);
      if (k == ((d >> 5) & 3)) { release(c, h.x); release(c, h.w); }
      load_part<WG, 0>(c, r, q); add_part<WG>(c, q, a0);
      load_part<WG, 1, 0>(c, r, q); add_part<WG>(c, q, a1);
#pragma unroll
      for (int t = 0; t < 4; t++) { release(c, r.slot); r.next(); }
    }
    load_part<WG, 0, WG ? 4 : 1>(c, r, q);
    wg_wait<1>();
    acc_fence<WG>(a0);
    TRACE_O(0);
    add_part<WG>(c, q, a0);
    stage_out<WG, 0>(c, a0);
    TRACE_O(1);
    load_part<WG, 1, WG ? 0 : 2>(c, r, q);
    wg_wait<0>();
    acc_fence<WG>(a1);
    TRACE_O(2);
    add_part<WG>(c, q, a1);
    stage_out<WG, 1>(c, a1);
    TRACE(i, 2); TRACE(i, 3); TRACE(i, 7);
    trace_dump(c);
    return;
  }
redo:
  {
    if (!WG) { stage_rows<RM1>(c, c.sb + QBUF_OFF + 16384, oq); __syncwarp(); }
    const size_t hoff = (size_t)(dc & 511) * (SK * DH);
    const int br = (dc >> 9) & 1;
#pragma unroll 1
    for (int part = 0; part < 2; part++) {
      const int t = WG ? 3 - part : part;
      redo_tile(c, c.sb + QBUF_OFF + t * 16384, t == 3 ? 4096 : 8192, kv[br] + hoff, kv[2 + br] + hoff, dc,
                t * 64 + (t == 3 ? 8 : 16) * c.warp);
    }
    o_done(c);
    release_q<WG>(c);
  }
  goto next;
}

template <bool SIMPLE>
__global__ void __launch_bounds__(384, 1) mha_fused_kernel(const __grid_constant__ Params P) {
  extern __shared__ __align__(1024) uint8_t smem_raw[];
  const uint32_t sbase = smem_u32(smem_raw);
  const int tid = threadIdx.x;
  const int wg = __shfl_sync(0xffffffffu, tid >> 7, 0);
  const int warp = __shfl_sync(0xffffffffu, (tid >> 5) & 3, 0);
  const int lane = tid & 31;
  const int cta = blockIdx.x;
  constexpr bool PAIR = !SIMPLE;

  if (tid == 0) T3(15, 0);
  if (tid == 0) TTAIL(7);
  const uint32_t d0 = first_entry(cta, FIRST_LO, FIRST_HI);
  const int wi = wg * 4 + warp;
  asm volatile(ELECT "prefetch.tensormap [%0];\n}" ::"l"(&P.x[0][0] + wi) : "memory");
  if ((sbase & 0xffffff) != SB0) __trap();
  if (wg < 2) {
    asm volatile(ELECT "mbarrier.init.shared::cta.b64 [%0], 1;\n}" ::"r"(sbase + BAR_FULL + wi * 8) : "memory");
    if (PAIR && (wi == 1 || wi == 4 || (W_FAST == 3 && wi == 7))) {
      fence_async_smem();
      tma_ld3_w(sbase + wi * SLOT, P.wq, 0, (wi / 3) * 64, (d0 & 31) * 2, sbase + BAR_FULL + wi * 8, 16384);
      if (wi == 1) TTAIL(8);
    }
#pragma unroll 1
    for (int b = BAR_OFF + 64 + wi * 8; b < DESC_OFF; b += 64)
      asm volatile(ELECT "mbarrier.init.shared::cta.b64 [%0], %1;\n}"
                   ::"r"(sbase + b), "r"(b < BAR_EMPTY || b >= BAR_DESC ? 1 : b >= BAR_STG && b < BAR_OUT ? 4 : 8) : "memory");
    asm volatile("fence.mbarrier_init.release.cluster;" ::: "memory");
    if (wi < 6) asm volatile(ELECT "prefetch.tensormap [%0];\n}" ::"l"(&P.x[0][0] + 12 + wi) : "memory");
  }
  if (PAIR) asm volatile("barrier.cluster.arrive.relaxed.aligned;" ::: "memory"); else __syncthreads();
#define INIT_DONE() if (PAIR) asm volatile("barrier.cluster.wait.aligned;" ::: "memory")

  if (wg == 2) {
    asm volatile("setmaxnreg.dec.sync.aligned.u32 %0;" ::"n"(REG_P));
    if (warp == 1) {
      const uint32_t qb = sbase + QBUF_OFF;
      const uint32_t ep = __shfl_sync(0xffffffffu, *(volatile unsigned*)&g_epoch + 1, 0);
      asm volatile("st.volatile.shared.u32 [%0], %1;" ::"r"(sbase + EPOCH_OFF), "r"(ep) : "memory");
      INIT_DONE();
      uint32_t dc = d0, qi = 0, piece = 0, na = 0;
      TTAIL(0);
      for (int i = 0; (dc >> 30) != 2; i++) {
        if (!(dc >> 30) && o_reuse<SIMPLE>((dc >> 5) & 31)) {
          const unsigned* rd = &g_rd[0][0] + ((dc & 1023) >> 2) - OR * 8;
          for (uint32_t n = 0; !__all_sync(0xffffffffu, reached(rd, ep * 5)); __nanosleep(300)) if (++n > (1u << 22)) __trap();
        }
        mbar_wait_w(sbase + BAR_GO, i & 1);
        if (piece == 0) {
          if (PAIR && (cta & 1)) {
            asm volatile(ELECT EXPECT("%0", "4") "mbarrier.arrive.shared::cluster.b64 _, [%1];\n}" ::"r"(sbase + BAR_MAIL), "r"(peer(sbase + BAR_MAIL)) : "memory");
            mbar_wait_w(sbase + BAR_MAIL, i & 1);
            qi = lds(sbase + EPOCH_OFF + 8);
          } else if (lane == 0) {
            qi = atomicAdd(&g_next, PAIR ? 2 : 1);
            if (qi == (SIMPLE ? Q_ALL : Q_RANGES) - (PAIR ? 2 : 1)) { g_next = 0; g_epoch = ep; }
          }
          qi = __shfl_sync(0xffffffffu, qi, 0);
          if (PAIR && !(cta & 1)) {
            mbar_wait_w(sbase + BAR_MAIL, i & 1);
            asm volatile(ELECT "st.async.shared::cluster.mbarrier::complete_tx::bytes.u32 [%0], %1, [%2];\n}"
                         ::"r"(peer(sbase + EPOCH_OFF + 8)), "r"(qi + 1), "r"(peer(sbase + BAR_MAIL)) : "memory");
          }
          qi += SIMPLE ? gridDim.x : NCTA;
        }
        uint32_t d;
        if (qi < (SIMPLE ? Q_ALL : Q_RANGES)) { d = c_sched.queue[qi]; if (d & 0x8000) d ^= (1u << 30) | (63u << 16) | 0x8000; else d |= o_slot<SIMPLE>(d >> 5) << 15 | (d & 31) << 10; }
        else if (SIMPLE) d = 2u << 30;
        else { const uint32_t e = qi - Q_RANGES, g = e / 5; d = c_sched.piece[g][piece++] | (g & 1 ? g * 5 + 4 - e : e - g * 5) << 8; }
        if ((d >> 30) == 1) {
          const uint32_t k0 = (d >> 22) & 63;
          const uint32_t run = __ffs(__ballot_sync(0xffffffffu, !reached(&g_cnt[d & 31][lane & 7], ep * 4)) & (0xffu << (k0 >> 3))) - 1;
          if (run <= (k0 + ((d >> 16) & 63)) >> 3) d |= run <= (k0 + O_STEPS) >> 3 ? (2u << 30) | 128 : 128;
        }
        asm volatile("st.volatile.shared.u32 [%0], %1;" ::"r"(sbase + DESC_OFF + ((i + 1) & 3) * 4), "r"(d) : "memory");
        __syncwarp();
        mbar_arrive_warp(sbase + BAR_DESC);
        const Work w = decode(dc);
        dc = d;
        if (w.kind == 0) {
          mbar_wait_w(sbase + BAR_OUT, na++ & 1);
          TTAIL(1);
          T3(i, 0); T3(i, 1);
          asm volatile(ELECT "red.release.gpu.global.add.u32 [%0], 1;\n}" ::"l"(&g_cnt[w.beta][w.sub >> 2]) : "memory");
          T3(i, 2);
          TTAIL(2);
          continue;
        }
        const bool fin = w.mode != 1;
        const CUtensorMap* m = fin ? P.out_st : P.o_st;
        const int c1 = fin ? (w.beta & 15) * SQ : 0;
        const int c2 = fin ? (w.beta >> 4) * (DM / 64) + w.sub * 2 : NBETA * 64 + w.range * 2;
        uint32_t pend = 0;
#pragma unroll 1
        for (int e = 0; e < 4; e++) {
          const int t = (ST_ORDER >> (4 * e)) & 3;
          mbar_wait_w(sbase + BAR_STG + (t ^ (t >> 1)) * 8, (i - na) & 1);
          tma_st3_w(m + (t == 3), qb + t * 16384, c1 + t * 64, c2);
          bulk_commit();
          T2P(i + 1, 5, 2 * e);
          if (e == 3 && w.mode == 1 && (d >> 30) == 2) {
            asm volatile("cp.async.bulk.wait_group 2;" ::: "memory");
            asm volatile(ELECT "st.release.gpu.global.u32 [%0], %1;\n}" ::"l"(&g_flag[w.range]), "r"(2 * ep - 1) : "memory");
          }
          if (pend && (d >> 30) != 2) {
            bulk_wait_read<1>();
            mbar_arrive8_w(pend);
            T2P(i + 1, 5, 2 * e - 1);
          }
          pend = sbase + BAR_EMPTY + (NS + t) * 8;
          if ((ST_NOW >> e) & 1) {
            bulk_wait_read<0>();
            mbar_arrive8_w(pend);
            pend = 0;
            T2P(i + 1, 5, 2 * e + 1);
          }
        }
        if (w.beta < N_EARLY) asm volatile(ELECT "red.relaxed.gpu.global.add.u32 [%0], 1;\n}" ::"l"(&g_rd[w.beta][7]) : "memory");
        T3(i, 0);
        if (piece >= 2) TTAIL(piece * 2 - 1);
        asm volatile("cp.async.bulk.wait_group 0;" ::: "memory");
        T3(i, 1);
        if (w.mode == 1) asm volatile(ELECT "st.release.gpu.global.u32 [%0], %1;\n}" ::"l"(&g_flag[w.range]), "r"(2 * ep) : "memory");
        T3(i, 2);
        if (piece >= 2) TTAIL(piece * 2);
      }
      T3(15, 1);
    } else
    if (warp == 0) {
      Ring r{PAIR ? 3 * W_FAST : 0, 1, 3};
      uint32_t d = d0;
      for (int i = 0;; i++) {
        const Work w = decode(d);
        if (w.kind == 2) break;
        const CUtensorMap* m = w.kind == 0 ? &P.wq[w.beta >> 4] : &P.wo[w.beta >> 4];
        if (i == 0) INIT_DONE();
        for (int ks = PAIR && i == 0 ? W_FAST : 0; ks < w.nsteps; ks++) {
          const uint32_t b = borrow(ks, w.nsteps);
          r.next_if(b == 2);
          const uint32_t bar = sbase + BAR_FULL + r.slot * 8;
          mbar_wait_w(bar + (BAR_EMPTY - BAR_FULL), r.phase);
          if (w.kind == 0) tma_ld3_w(sbase + r.slot * SLOT, m, 0, ks * 64, w.sub * 2, bar, 16384);
          else tma_ld_wo_w(sbase + r.slot * SLOT, m, w.sub * 128, (w.k0 + ks) * 2, bar);
          if (w.kind != 0 && w.beta < N_EARLY && (ks & 7) == 5 && ks > 5)
            asm volatile(ELECT "red.relaxed.gpu.global.add.u32 [%0], 1;\n}" ::"l"(&g_rd[w.beta][(ks >> 3) - 1]) : "memory");
          if (ks < 10) T2P(i, 2, ks);
          if (w.kind != 0 && ks == max(w.nsteps - GO_P, 4)) mbar_arrive_warp(sbase + BAR_GO);
          r.next(); r.next_if(b == 2);
        }
        if (w.kind == 0) {
          r.phase ^= 1; r.next(); r.next();
        } else if (w.mode == 2) {
          for (int k = 1; k <= ((d >> 5) & 3); k++) {
            if (k == 1) TTAIL(9);
            bool all = false;
#pragma unroll 1
            for (int t = 0; t < 4; t++) {
              if (!(t & 1) && !all) {
                const uint32_t ep2 = 2 * lds(sbase + EPOCH_OFF);
                uint32_t v, n = 0;
                do {
                  asm volatile("ld.acquire.gpu.global.u32 %0, [%1];" : "=r"(v) : "l"(&g_flag[w.range + 5 * k]) : "memory");
                  v = __shfl_sync(0xffffffffu, v - ep2, 0);
                  if (++n > (1u << 24)) __trap();
                } while ((int)v < (t >> 1) - 1);
                all = v == 0;
                TTAIL(10);
                asm volatile("fence.proxy.async.global;" ::: "memory");
              }
              mbar_wait_w(sbase + BAR_EMPTY + r.slot * 8, r.phase);
              tma_ld3_w(sbase + r.slot * SLOT, &P.o_st[t == 3], 0, t * 64, NBETA * 64 + (w.range + 5 * k) * 2, sbase + BAR_FULL + r.slot * 8,
                        t == 3 ? 8192 : 16384);
              r.next();
            }
          }
        }
        mbar_wait_w(sbase + BAR_DESC, i & 1);
        d = __shfl_sync(0xffffffffu, lds(sbase + DESC_OFF + ((i + 1) & 3) * 4), 0);
      }
    } else {
      const int hi = warp - 2;
      uint64_t pol_stream;
      uint32_t rdy = 0;
      asm volatile("createpolicy.fractional.L2::evict_first.b64 %0, 1.0;" : "=l"(pol_stream));
      Ring r{PAIR ? 3 * X_FAST : 0, 1, 3};
      uint32_t d = d0;
      for (int i = 0;; i++) {
        const Work w = decode(d);
        if (w.kind == 2) break;
        const CUtensorMap* m = w.kind == 0 ? &P.x[hi][w.beta >> 4] : &P.o_ld[hi];
        int c1 = (w.kind == 0 ? (w.beta & 15) : o_slot<SIMPLE>(w.beta) * 64 + w.k0) * SQ + hi * 128;
        int k_wait = -1;
        const bool both = PAIR && (w.kind == 0 || w.sub != 4), mine = !both || hi == (cta & 1);
        if (w.kind != 0 && mine) {
          if (d & 128) k_wait = d >= (3u << 30) ? 0 : 8 - (w.k0 & 7);
          asm volatile("fence.proxy.async.global;" ::: "memory");
        }
        if (i == 0) INIT_DONE();
        for (int ks = PAIR && i == 0 ? X_FAST : 0; ks < w.nsteps; ks++) {
          if (ks == k_wait) {
            wait_count(&g_cnt[d & 31][(w.k0 + ks) >> 3], lds(sbase + EPOCH_OFF) * 4);
            asm volatile("fence.proxy.async.global;" ::: "memory");
            k_wait = ((w.k0 + ks) | 7) + 1 - w.k0;
          }
          const uint32_t b = borrow(ks, w.nsteps);
          const bool bo = b != 2;
          r.next_if(hi && !bo); r.next_if(hi && !bo);
          const uint32_t sl = bo ? NS + (b ^ (3 * hi)) : r.slot, bar = sbase + BAR_FULL + sl * 8;
          mbar_wait_w(bar + (BAR_EMPTY - BAR_FULL), bo ? (r.xp >> b) & 1 : r.phase);
          const uint32_t bytes = hi ? 96 * 128 : 128 * 128;
          const bool used = i > 0 || ks > 4;
          if (!mine) {
            asm volatile(ELECT "mbarrier.arrive.expect_tx.shared::cta.b64 _, [%0], %1;\n}" ::"r"(bar), "r"(bytes) : "memory");
            if (used) asm volatile(ELECT "mbarrier.arrive.shared::cluster.b64 _, [%0];\n}" ::"r"(peer(bar + (BAR_RDY - BAR_FULL))) : "memory");
          } else if (both) {
            if (used) {
              mbar_wait_w(bar + (BAR_RDY - BAR_FULL), (rdy >> sl) & 1);
              rdy ^= 1 << sl;
            }
            if (w.kind == 0) tma_ld2_both_w(sbase + sl * SLOT, m, ks * 64, c1, bar, bytes);
            else tma_ld2_both_hint_w(sbase + sl * SLOT, m, 0, c1, bar, bytes, pol_stream);
          } else if (!PAIR && w.kind == 0) tma_ld2_w(sbase + sl * SLOT, m, ks * 64, c1, bar, bytes);
          else tma_ld2_hint_w(sbase + sl * SLOT, m, 0, c1, bar, bytes, pol_stream);
          if (w.kind != 0) c1 += SQ;
          if (i == 0 && ks == PF_STEP)
            asm volatile(ELECT "cp.async.bulk.prefetch.tensor.4d.L2.global.L2::cache_hint [%0, {0, 0, 0, %1}], %2;\n}"
                         ::"l"(&P.kv[hi][0]), "r"(d * (SK / 8)), "l"(pol_stream) : "memory");
          if (ks < 10) T2P(i, 3 + hi, ks);
          if (!hi && w.kind != 0 && !(ks & 3)) TCLK(i * 16 + (ks >> 2));
          r.next(); r.next_if(!hi && !bo); r.next_if(!hi && !bo);
          r.xp ^= 1 << b;
        }
        r.xp ^= 3;
        if (w.kind == 0) {
          m = &P.kv[hi][w.beta >> 4];
          c1 = (d & 511) * (SK / 8);
          for (int j = 0; j < 16; j++) {
            if (hi) r.next();
            const uint32_t bar = sbase + BAR_FULL + r.slot * 8;
            const bool tight = i == 0 && j < KV_WIN_TILES + ((KV_WIN_RAMP * cta) >> 5);
            {
              const int s2 = (int)r.slot - (tight ? 2 : KV_WIN_D);
              mbar_wait_w(sbase + BAR_FULL + (s2 < 0 ? s2 + NS : s2) * 8, s2 < 0 ? r.phase : r.phase ^ 1);
            }
            if (j == 15 && hi) mbar_wait_w(sbase + BAR_DESC, i & 1);
            mbar_wait_w(sbase + BAR_EMPTY + r.slot * 8, r.phase);
            tma_ld_kv_w(sbase + r.slot * SLOT, m, c1, bar, pol_stream);
            T2P(i, 3 + hi, 16 + j);
            if (!hi) TCLK(i * 16 + j);
            if (j == GO_J && !hi) mbar_arrive_warp(sbase + BAR_GO);
            c1 += 8;
            r.next();
            if (!hi) r.next();
          }
        }
        mbar_wait_w(sbase + BAR_DESC, i & 1);
        d = __shfl_sync(0xffffffffu, lds(sbase + DESC_OFF + ((i + 1) & 3) * 4), 0);
      }
    }
  } else {
    Ctx c;
    c.sb = sbase; c.wg = wg; c.warp = warp; c.src = 0; c.mqk = 0; c.mpv = 0; c.lead = lane == 0; c.lane0 = c.lane = lane;
    INIT_DONE();
    if (PAIR && wi < 2 * X_FAST) {
      const uint32_t t = wi & 1, sl = (wi >> 1) * 3 + t * 2, bar = sbase + BAR_FULL + sl * 8, bytes = t ? 96 * 128 : 128 * 128;
      if (t == (cta & 1)) tma_ld2_both_w(sbase + sl * SLOT, &P.x[t][0], (wi >> 1) * 64, (d0 >> 5) * SQ + t * 128, bar, bytes);
      else asm volatile(ELECT "mbarrier.arrive.expect_tx.shared::cta.b64 _, [%0], %1;\n}" ::"r"(bar), "r"(bytes) : "memory");
    }
    if (PF_STEP < 0 && wi >= 6) {
      uint64_t pol;
      asm volatile("createpolicy.fractional.L2::evict_first.b64 %0, 1.0;" : "=l"(pol));
      asm volatile(ELECT "cp.async.bulk.prefetch.tensor.4d.L2.global.L2::cache_hint [%0, {0, 0, 0, %1}], %2;\n}"
                   ::"l"(&P.kv[wi & 1][0]), "r"(d0 * (SK / 8)), "l"(pol) : "memory");
    }
    if (wg == 0) consumer<0>(c, P.kp); else consumer<1>(c, P.kp);
  }
}

typedef CUresult (*EncodeFn)(CUtensorMap*, CUtensorMapDataType, cuuint32_t, void*, const cuuint64_t*, const cuuint64_t*,
                             const cuuint32_t*, const cuuint32_t*, CUtensorMapInterleave, CUtensorMapSwizzle,
                             CUtensorMapL2promotion, CUtensorMapFloatOOBfill);

void make_map(EncodeFn enc, CUtensorMap* m, const void* ptr, int rank, const cuuint64_t* dims, const cuuint64_t* strides,
              const cuuint32_t* box, CUtensorMapSwizzle swz = CU_TENSOR_MAP_SWIZZLE_128B) {
  cuuint32_t es[5] = {1, 1, 1, 1, 1};
  enc(m, CU_TENSOR_MAP_DATA_TYPE_BFLOAT16, rank, const_cast<void*>(ptr), dims, strides, box, es,
      CU_TENSOR_MAP_INTERLEAVE_NONE, swz, CU_TENSOR_MAP_L2_PROMOTION_NONE,
      CU_TENSOR_MAP_FLOAT_OOB_FILL_NONE);
}

}

extern "C" void kernel_launch(void* const* d_in, const int* in_sizes, int n_in, void* d_out, int out_size) {
  (void)in_sizes; (void)n_in; (void)out_size;
  static EncodeFn enc = nullptr;
  static void* o_ptr = nullptr;
  static int n_sm = 0;
  cudaLaunchAttribute at;
  at.id = cudaLaunchAttributeClusterDimension;
  at.val.clusterDim.x = 2; at.val.clusterDim.y = 1; at.val.clusterDim.z = 1;
  cudaLaunchConfig_t cfg = {};
  cfg.gridDim = dim3(NCTA); cfg.blockDim = dim3(384); cfg.dynamicSmemBytes = SMEM_BYTES; cfg.attrs = &at; cfg.numAttrs = 1;
  if (!enc) {
    void* fn = nullptr;
    cudaDriverEntryPointQueryResult qr;
    cudaGetDriverEntryPoint("cuTensorMapEncodeTiled", &fn, cudaEnableDefault, &qr);
    enc = (EncodeFn)fn;
    cudaGetSymbolAddress(&o_ptr, g_o);
    cudaFuncSetAttribute(mha_fused_kernel<false>, cudaFuncAttributeMaxDynamicSharedMemorySize, SMEM_BYTES);
    cudaFuncSetAttribute(mha_fused_kernel<true>, cudaFuncAttributeMaxDynamicSharedMemorySize, SMEM_BYTES);
    int dev = 0;
    cudaGetDevice(&dev);
    cudaDeviceGetAttribute(&n_sm, cudaDevAttrMultiProcessorCount, dev);
    int n_cl = 0;
    cudaOccupancyMaxActiveClusters(&n_cl, mha_fused_kernel<false>, &cfg);
    if (n_cl * 2 < NCTA && n_sm >= NCTA) n_sm = NCTA - 1;
  }
  Params P;
  for (int br = 0; br < 2; br++) {
    const void* x = d_in[br * 5 + 0]; const void* kc = d_in[br * 5 + 1]; const void* vc = d_in[br * 5 + 2];
    const void* wq = d_in[br * 5 + 3]; const void* wo = d_in[br * 5 + 4];
    { cuuint64_t d[2] = {DM, (cuuint64_t)NB * SQ}, s[1] = {DM * 2}; cuuint32_t b[2] = {64, 128}, b2[2] = {64, 96};
      make_map(enc, &P.x[0][br], x, 2, d, s, b); make_map(enc, &P.x[1][br], x, 2, d, s, b2); }
    { cuuint64_t d[3] = {64, DM, HD / 64}, s[2] = {HD * 2, 128}; cuuint32_t b[3] = {64, 64, 2}; make_map(enc, &P.wq[br], wq, 3, d, s, b); }
    { cuuint64_t d[5] = {DM, 2, 4, 4, HD / 32}, s[4] = {DM * 2, 8 * DM * 2, 2 * DM * 2, 32 * DM * 2}; cuuint32_t b[5] = {64, 2, 4, 4, 2};
      make_map(enc, &P.wo[br], wo, 5, d, s, b); }
    { cuuint64_t d[4] = {64, 8, 2, (cuuint64_t)NB * NH * SK / 8}, s[3] = {DH * 2, 128, DH * 16}; cuuint32_t b[4] = {64, 8, 2, 8};
      make_map(enc, &P.kv[0][br], kc, 4, d, s, b); make_map(enc, &P.kv[1][br], vc, 4, d, s, b); }
    P.kp[br] = (const __nv_bfloat16*)kc; P.vp[br] = (const __nv_bfloat16*)vc;

  }
  { cuuint64_t d[2] = {64, (cuuint64_t)NBETA * 64 * SQ}, s[1] = {128}; cuuint32_t b[2] = {64, 128}, b2[2] = {64, 96};
    make_map(enc, &P.o_ld[0], o_ptr, 2, d, s, b, CU_TENSOR_MAP_SWIZZLE_NONE); make_map(enc, &P.o_ld[1], o_ptr, 2, d, s, b2, CU_TENSOR_MAP_SWIZZLE_NONE); }
  { cuuint64_t d[3] = {64, SQ, O_BLOCKS}, s[2] = {128, SQ * 128}; cuuint32_t b[3] = {64, 64, 2}, b2[3] = {64, 32, 2};
    make_map(enc, &P.o_st[0], o_ptr, 3, d, s, b); make_map(enc, &P.o_st[1], o_ptr, 3, d, s, b2); }
  { cuuint64_t d[3] = {64, (cuuint64_t)NB * SQ, 2 * DM / 64}, s[2] = {2 * DM * 2, 128}; cuuint32_t b[3] = {64, 64, 2}, b2[3] = {64, 32, 2};
    make_map(enc, &P.out_st[0], d_out, 3, d, s, b); make_map(enc, &P.out_st[1], d_out, 3, d, s, b2); }
  if (n_sm >= NCTA) cudaLaunchKernelEx(&cfg, mha_fused_kernel<false>, P);
  else mha_fused_kernel<true><<<n_sm, 384, SMEM_BYTES>>>(P);
}
```

```cpp
#include <cuda_runtime.h>
#include <cuda_bf16.h>
#include <cuda.h>
#include <stdint.h>
#include <stdlib.h>

namespace {

__device__ __forceinline__ void wgmma_proj(float (&d)[64], uint64_t da, uint64_t db, int scaleD) {
  asm volatile("{\n.reg .pred p;\nsetp.ne.b32 p, %66, 0;\n"
      "wgmma.mma_async.sync.aligned.m64n128k16.f32.bf16.bf16 "
      "{%0, %1, %2, %3, %4, %5, %6, %7, %8, %9, %10, %11, %12, %13, %14, %15, %16, %17, %18, %19, %20, %21, %22, %23, %24, %25, %26, %27, %28, %29, %30, "
      "%31, %32, %33, %34, %35, %36, %37, %38, %39, %40, %41, %42, %43, %44, %45, %46, %47, %48, %49, %50, %51, %52, %53, %54, %55, %56, %57, %58, %59, %60, "
      "%61, %62, %63}, "
      "%64, %65, p, 1, 1, 0, 1;\n}\n"
      : "+f"(d[0]), "+f"(d[1]), "+f"(d[2]), "+f"(d[3]), "+f"(d[4]), "+f"(d[5]), "+f"(d[6]), "+f"(d[7]), "+f"(d[8]), "+f"(d[9]), "+f"(d[10]), "+f"(d[11]),
        "+f"(d[12]), "+f"(d[13]), "+f"(d[14]), "+f"(d[15]), "+f"(d[16]), "+f"(d[17]), "+f"(d[18]), "+f"(d[19]), "+f"(d[20]), "+f"(d[21]), "+f"(d[22]),
        "+f"(d[23]), "+f"(d[24]), "+f"(d[25]), "+f"(d[26]), "+f"(d[27]), "+f"(d[28]), "+f"(d[29]), "+f"(d[30]), "+f"(d[31]), "+f"(d[32]), "+f"(d[33]),
        "+f"(d[34]), "+f"(d[35]), "+f"(d[36]), "+f"(d[37]), "+f"(d[38]), "+f"(d[39]), "+f"(d[40]), "+f"(d[41]), "+f"(d[42]), "+f"(d[43]), "+f"(d[44]),
        "+f"(d[45]), "+f"(d[46]), "+f"(d[47]), "+f"(d[48]), "+f"(d[49]), "+f"(d[50]), "+f"(d[51]), "+f"(d[52]), "+f"(d[53]), "+f"(d[54]), "+f"(d[55]),
        "+f"(d[56]), "+f"(d[57]), "+f"(d[58]), "+f"(d[59]), "+f"(d[60]), "+f"(d[61]), "+f"(d[62]), "+f"(d[63])
      : "l"(da), "l"(db), "r"(scaleD));
}
__device__ __forceinline__ void wgmma_proj96(float (&d)[64], uint64_t da, uint64_t db, int scaleD) {
  asm volatile("{\n.reg .pred p;\nsetp.ne.b32 p, %50, 0;\n"
      "wgmma.mma_async.sync.aligned.m64n96k16.f32.bf16.bf16 "
      "{%0, %1, %2, %3, %4, %5, %6, %7, %8, %9, %10, %11, %12, %13, %14, %15, %16, %17, %18, %19, %20, %21, %22, %23, %24, %25, %26, %27, %28, %29, %30, "
      "%31, %32, %33, %34, %35, %36, %37, %38, %39, %40, %41, %42, %43, %44, %45, %46, %47}, "
      "%48, %49, p, 1, 1, 1, 0;\n}\n"
      : "+f"(d[0]), "+f"(d[1]), "+f"(d[2]), "+f"(d[3]), "+f"(d[4]), "+f"(d[5]), "+f"(d[6]), "+f"(d[7]), "+f"(d[8]), "+f"(d[9]), "+f"(d[10]), "+f"(d[11]),
        "+f"(d[12]), "+f"(d[13]), "+f"(d[14]), "+f"(d[15]), "+f"(d[16]), "+f"(d[17]), "+f"(d[18]), "+f"(d[19]), "+f"(d[20]), "+f"(d[21]), "+f"(d[22]),
        "+f"(d[23]), "+f"(d[24]), "+f"(d[25]), "+f"(d[26]), "+f"(d[27]), "+f"(d[28]), "+f"(d[29]), "+f"(d[30]), "+f"(d[31]), "+f"(d[32]), "+f"(d[33]),
        "+f"(d[34]), "+f"(d[35]), "+f"(d[36]), "+f"(d[37]), "+f"(d[38]), "+f"(d[39]), "+f"(d[40]), "+f"(d[41]), "+f"(d[42]), "+f"(d[43]), "+f"(d[44]),
        "+f"(d[45]), "+f"(d[46]), "+f"(d[47])
      : "l"(da), "l"(db), "r"(scaleD));
}
__device__ __forceinline__ void wgmma_qk(float (&d)[32], uint64_t da, uint64_t db, int scaleD) {
  asm volatile("{\n.reg .pred p;\nsetp.ne.b32 p, %34, 0;\n"
      "wgmma.mma_async.sync.aligned.m64n64k16.f32.bf16.bf16 "
      "{%0, %1, %2, %3, %4, %5, %6, %7, %8, %9, %10, %11, %12, %13, %14, %15, %16, %17, %18, %19, %20, %21, %22, %23, %24, %25, %26, %27, %28, %29, %30, "
      "%31}, "
      "%32, %33, p, 1, 1, 0, 0;\n}\n"
      : "+f"(d[0]), "+f"(d[1]), "+f"(d[2]), "+f"(d[3]), "+f"(d[4]), "+f"(d[5]), "+f"(d[6]), "+f"(d[7]), "+f"(d[8]), "+f"(d[9]), "+f"(d[10]), "+f"(d[11]),
        "+f"(d[12]), "+f"(d[13]), "+f"(d[14]), "+f"(d[15]), "+f"(d[16]), "+f"(d[17]), "+f"(d[18]), "+f"(d[19]), "+f"(d[20]), "+f"(d[21]), "+f"(d[22]),
        "+f"(d[23]), "+f"(d[24]), "+f"(d[25]), "+f"(d[26]), "+f"(d[27]), "+f"(d[28]), "+f"(d[29]), "+f"(d[30]), "+f"(d[31])
      : "l"(da), "l"(db), "r"(scaleD));
}
__device__ __forceinline__ void wgmma_qk_rs(float (&d)[32], uint32_t a0, uint32_t a1, uint32_t a2, uint32_t a3, uint64_t db, int scaleD) {
  asm volatile("{\n.reg .pred p;\nsetp.ne.b32 p, %37, 0;\n"
      "wgmma.mma_async.sync.aligned.m64n64k16.f32.bf16.bf16 "
      "{%0, %1, %2, %3, %4, %5, %6, %7, %8, %9, %10, %11, %12, %13, %14, %15, %16, %17, %18, %19, %20, %21, %22, %23, %24, %25, %26, %27, %28, %29, %30, "
      "%31}, "
      "{%32, %33, %34, %35}, %36, p, 1, 1, 0;\n}\n"
      : "+f"(d[0]), "+f"(d[1]), "+f"(d[2]), "+f"(d[3]), "+f"(d[4]), "+f"(d[5]), "+f"(d[6]), "+f"(d[7]), "+f"(d[8]), "+f"(d[9]), "+f"(d[10]), "+f"(d[11]),
        "+f"(d[12]), "+f"(d[13]), "+f"(d[14]), "+f"(d[15]), "+f"(d[16]), "+f"(d[17]), "+f"(d[18]), "+f"(d[19]), "+f"(d[20]), "+f"(d[21]), "+f"(d[22]),
        "+f"(d[23]), "+f"(d[24]), "+f"(d[25]), "+f"(d[26]), "+f"(d[27]), "+f"(d[28]), "+f"(d[29]), "+f"(d[30]), "+f"(d[31])
      : "r"(a0), "r"(a1), "r"(a2), "r"(a3), "l"(db), "r"(scaleD));
}
__device__ __forceinline__ void wgmma_pv(float (&d)[64], uint32_t a0, uint32_t a1, uint32_t a2, uint32_t a3, uint64_t db, int scaleD) {
  asm volatile("{\n.reg .pred p;\nsetp.ne.b32 p, %69, 0;\n"
      "wgmma.mma_async.sync.aligned.m64n128k16.f32.bf16.bf16 "
      "{%0, %1, %2, %3, %4, %5, %6, %7, %8, %9, %10, %11, %12, %13, %14, %15, %16, %17, %18, %19, %20, %21, %22, %23, %24, %25, %26, %27, %28, %29, %30, "
      "%31, %32, %33, %34, %35, %36, %37, %38, %39, %40, %41, %42, %43, %44, %45, %46, %47, %48, %49, %50, %51, %52, %53, %54, %55, %56, %57, %58, %59, %60, "
      "%61, %62, %63}, "
      "{%64, %65, %66, %67}, %68, p, 1, 1, 1;\n}\n"
      : "+f"(d[0]), "+f"(d[1]), "+f"(d[2]), "+f"(d[3]), "+f"(d[4]), "+f"(d[5]), "+f"(d[6]), "+f"(d[7]), "+f"(d[8]), "+f"(d[9]), "+f"(d[10]), "+f"(d[11]),
        "+f"(d[12]), "+f"(d[13]), "+f"(d[14]), "+f"(d[15]), "+f"(d[16]), "+f"(d[17]), "+f"(d[18]), "+f"(d[19]), "+f"(d[20]), "+f"(d[21]), "+f"(d[22]),
        "+f"(d[23]), "+f"(d[24]), "+f"(d[25]), "+f"(d[26]), "+f"(d[27]), "+f"(d[28]), "+f"(d[29]), "+f"(d[30]), "+f"(d[31]), "+f"(d[32]), "+f"(d[33]),
        "+f"(d[34]), "+f"(d[35]), "+f"(d[36]), "+f"(d[37]), "+f"(d[38]), "+f"(d[39]), "+f"(d[40]), "+f"(d[41]), "+f"(d[42]), "+f"(d[43]), "+f"(d[44]),
        "+f"(d[45]), "+f"(d[46]), "+f"(d[47]), "+f"(d[48]), "+f"(d[49]), "+f"(d[50]), "+f"(d[51]), "+f"(d[52]), "+f"(d[53]), "+f"(d[54]), "+f"(d[55]),
        "+f"(d[56]), "+f"(d[57]), "+f"(d[58]), "+f"(d[59]), "+f"(d[60]), "+f"(d[61]), "+f"(d[62]), "+f"(d[63])
      : "r"(a0), "r"(a1), "r"(a2), "r"(a3), "l"(db), "r"(scaleD));
}
__device__ __forceinline__ void wgmma_qk_sp(float (&d)[32], uint32_t a0, uint32_t a1, uint32_t a2, uint32_t a3, uint64_t db, int scaleD, uint32_t meta) {
  asm volatile("{\n.reg .pred p;\nsetp.ne.b32 p, %37, 0;\n"
      "wgmma.mma_async.sp.sync.aligned.m64n64k32.f32.bf16.bf16 "
      "{%0, %1, %2, %3, %4, %5, %6, %7, %8, %9, %10, %11, %12, %13, %14, %15, %16, %17, %18, %19, %20, %21, %22, %23, %24, %25, %26, %27, %28, %29, %30, "
      "%31}, "
      "{%32, %33, %34, %35}, %36, %38, 0, p, 1, 1, 0;\n}\n"
      : "+f"(d[0]), "+f"(d[1]), "+f"(d[2]), "+f"(d[3]), "+f"(d[4]), "+f"(d[5]), "+f"(d[6]), "+f"(d[7]), "+f"(d[8]), "+f"(d[9]), "+f"(d[10]), "+f"(d[11]),
        "+f"(d[12]), "+f"(d[13]), "+f"(d[14]), "+f"(d[15]), "+f"(d[16]), "+f"(d[17]), "+f"(d[18]), "+f"(d[19]), "+f"(d[20]), "+f"(d[21]), "+f"(d[22]),
        "+f"(d[23]), "+f"(d[24]), "+f"(d[25]), "+f"(d[26]), "+f"(d[27]), "+f"(d[28]), "+f"(d[29]), "+f"(d[30]), "+f"(d[31])
      : "r"(a0), "r"(a1), "r"(a2), "r"(a3), "l"(db), "r"(scaleD), "r"(meta));
}
__device__ __forceinline__ void wgmma_pv_sp(float (&d)[64], uint32_t a0, uint32_t a1, uint32_t a2, uint32_t a3, uint64_t db, int scaleD, uint32_t meta) {
  asm volatile("{\n.reg .pred p;\nsetp.ne.b32 p, %69, 0;\n"
      "wgmma.mma_async.sp.sync.aligned.m64n128k32.f32.bf16.bf16 "
      "{%0, %1, %2, %3, %4, %5, %6, %7, %8, %9, %10, %11, %12, %13, %14, %15, %16, %17, %18, %19, %20, %21, %22, %23, %24, %25, %26, %27, %28, %29, %30, "
      "%31, %32, %33, %34, %35, %36, %37, %38, %39, %40, %41, %42, %43, %44, %45, %46, %47, %48, %49, %50, %51, %52, %53, %54, %55, %56, %57, %58, %59, %60, "
      "%61, %62, %63}, "
      "{%64, %65, %66, %67}, %68, %70, 0, p, 1, 1, 1;\n}\n"
      : "+f"(d[0]), "+f"(d[1]), "+f"(d[2]), "+f"(d[3]), "+f"(d[4]), "+f"(d[5]), "+f"(d[6]), "+f"(d[7]), "+f"(d[8]), "+f"(d[9]), "+f"(d[10]), "+f"(d[11]),
        "+f"(d[12]), "+f"(d[13]), "+f"(d[14]), "+f"(d[15]), "+f"(d[16]), "+f"(d[17]), "+f"(d[18]), "+f"(d[19]), "+f"(d[20]), "+f"(d[21]), "+f"(d[22]),
        "+f"(d[23]), "+f"(d[24]), "+f"(d[25]), "+f"(d[26]), "+f"(d[27]), "+f"(d[28]), "+f"(d[29]), "+f"(d[30]), "+f"(d[31]), "+f"(d[32]), "+f"(d[33]),
        "+f"(d[34]), "+f"(d[35]), "+f"(d[36]), "+f"(d[37]), "+f"(d[38]), "+f"(d[39]), "+f"(d[40]), "+f"(d[41]), "+f"(d[42]), "+f"(d[43]), "+f"(d[44]),
        "+f"(d[45]), "+f"(d[46]), "+f"(d[47]), "+f"(d[48]), "+f"(d[49]), "+f"(d[50]), "+f"(d[51]), "+f"(d[52]), "+f"(d[53]), "+f"(d[54]), "+f"(d[55]),
        "+f"(d[56]), "+f"(d[57]), "+f"(d[58]), "+f"(d[59]), "+f"(d[60]), "+f"(d[61]), "+f"(d[62]), "+f"(d[63])
      : "r"(a0), "r"(a1), "r"(a2), "r"(a3), "l"(db), "r"(scaleD), "r"(meta));
}
__device__ __forceinline__ void wgmma_proj_init(float (&d)[64], uint64_t da, uint64_t db, int scaleD) {
  asm volatile("{\n.reg .pred p;\nsetp.ne.b32 p, %66, 0;\n"
      "wgmma.mma_async.sync.aligned.m64n128k16.f32.bf16.bf16 "
      "{%0, %1, %2, %3, %4, %5, %6, %7, %8, %9, %10, %11, %12, %13, %14, %15, %16, %17, %18, %19, %20, %21, %22, %23, %24, %25, %26, %27, %28, %29, %30, "
      "%31, %32, %33, %34, %35, %36, %37, %38, %39, %40, %41, %42, %43, %44, %45, %46, %47, %48, %49, %50, %51, %52, %53, %54, %55, %56, %57, %58, %59, %60, "
      "%61, %62, %63}, "
      "%64, %65, p, 1, 1, 0, 1;\n}\n"
      : "=f"(d[0]), "=f"(d[1]), "=f"(d[2]), "=f"(d[3]), "=f"(d[4]), "=f"(d[5]), "=f"(d[6]), "=f"(d[7]), "=f"(d[8]), "=f"(d[9]), "=f"(d[10]), "=f"(d[11]),
        "=f"(d[12]), "=f"(d[13]), "=f"(d[14]), "=f"(d[15]), "=f"(d[16]), "=f"(d[17]), "=f"(d[18]), "=f"(d[19]), "=f"(d[20]), "=f"(d[21]), "=f"(d[22]),
        "=f"(d[23]), "=f"(d[24]), "=f"(d[25]), "=f"(d[26]), "=f"(d[27]), "=f"(d[28]), "=f"(d[29]), "=f"(d[30]), "=f"(d[31]), "=f"(d[32]), "=f"(d[33]),
        "=f"(d[34]), "=f"(d[35]), "=f"(d[36]), "=f"(d[37]), "=f"(d[38]), "=f"(d[39]), "=f"(d[40]), "=f"(d[41]), "=f"(d[42]), "=f"(d[43]), "=f"(d[44]),
        "=f"(d[45]), "=f"(d[46]), "=f"(d[47]), "=f"(d[48]), "=f"(d[49]), "=f"(d[50]), "=f"(d[51]), "=f"(d[52]), "=f"(d[53]), "=f"(d[54]), "=f"(d[55]),
        "=f"(d[56]), "=f"(d[57]), "=f"(d[58]), "=f"(d[59]), "=f"(d[60]), "=f"(d[61]), "=f"(d[62]), "=f"(d[63])
      : "l"(da), "l"(db), "r"(scaleD));
}
__device__ __forceinline__ void wgmma_proj96_init(float (&d)[64], uint64_t da, uint64_t db, int scaleD) {
  asm volatile("{\n.reg .pred p;\nsetp.ne.b32 p, %50, 0;\n"
      "wgmma.mma_async.sync.aligned.m64n96k16.f32.bf16.bf16 "
      "{%0, %1, %2, %3, %4, %5, %6, %7, %8, %9, %10, %11, %12, %13, %14, %15, %16, %17, %18, %19, %20, %21, %22, %23, %24, %25, %26, %27, %28, %29, %30, "
      "%31, %32, %33, %34, %35, %36, %37, %38, %39, %40, %41, %42, %43, %44, %45, %46, %47}, "
      "%48, %49, p, 1, 1, 1, 0;\n}\n"
      : "=f"(d[0]), "=f"(d[1]), "=f"(d[2]), "=f"(d[3]), "=f"(d[4]), "=f"(d[5]), "=f"(d[6]), "=f"(d[7]), "=f"(d[8]), "=f"(d[9]), "=f"(d[10]), "=f"(d[11]),
        "=f"(d[12]), "=f"(d[13]), "=f"(d[14]), "=f"(d[15]), "=f"(d[16]), "=f"(d[17]), "=f"(d[18]), "=f"(d[19]), "=f"(d[20]), "=f"(d[21]), "=f"(d[22]),
        "=f"(d[23]), "=f"(d[24]), "=f"(d[25]), "=f"(d[26]), "=f"(d[27]), "=f"(d[28]), "=f"(d[29]), "=f"(d[30]), "=f"(d[31]), "=f"(d[32]), "=f"(d[33]),
        "=f"(d[34]), "=f"(d[35]), "=f"(d[36]), "=f"(d[37]), "=f"(d[38]), "=f"(d[39]), "=f"(d[40]), "=f"(d[41]), "=f"(d[42]), "=f"(d[43]), "=f"(d[44]),
        "=f"(d[45]), "=f"(d[46]), "=f"(d[47])
      : "l"(da), "l"(db), "r"(scaleD));
}
__device__ __forceinline__ void wgmma_qk_init(float (&d)[32], uint64_t da, uint64_t db, int scaleD) {
  asm volatile("{\n.reg .pred p;\nsetp.ne.b32 p, %34, 0;\n"
      "wgmma.mma_async.sync.aligned.m64n64k16.f32.bf16.bf16 "
      "{%0, %1, %2, %3, %4, %5, %6, %7, %8, %9, %10, %11, %12, %13, %14, %15, %16, %17, %18, %19, %20, %21, %22, %23, %24, %25, %26, %27, %28, %29, %30, "
      "%31}, "
      "%32, %33, p, 1, 1, 0, 0;\n}\n"
      : "=f"(d[0]), "=f"(d[1]), "=f"(d[2]), "=f"(d[3]), "=f"(d[4]), "=f"(d[5]), "=f"(d[6]), "=f"(d[7]), "=f"(d[8]), "=f"(d[9]), "=f"(d[10]), "=f"(d[11]),
        "=f"(d[12]), "=f"(d[13]), "=f"(d[14]), "=f"(d[15]), "=f"(d[16]), "=f"(d[17]), "=f"(d[18]), "=f"(d[19]), "=f"(d[20]), "=f"(d[21]), "=f"(d[22]),
        "=f"(d[23]), "=f"(d[24]), "=f"(d[25]), "=f"(d[26]), "=f"(d[27]), "=f"(d[28]), "=f"(d[29]), "=f"(d[30]), "=f"(d[31])
      : "l"(da), "l"(db), "r"(scaleD));
}
__device__ __forceinline__ void wgmma_qk_rs_init(float (&d)[32], uint32_t a0, uint32_t a1, uint32_t a2, uint32_t a3, uint64_t db, int scaleD) {
  asm volatile("{\n.reg .pred p;\nsetp.ne.b32 p, %37, 0;\n"
      "wgmma.mma_async.sync.aligned.m64n64k16.f32.bf16.bf16 "
      "{%0, %1, %2, %3, %4, %5, %6, %7, %8, %9, %10, %11, %12, %13, %14, %15, %16, %17, %18, %19, %20, %21, %22, %23, %24, %25, %26, %27, %28, %29, %30, "
      "%31}, "
      "{%32, %33, %34, %35}, %36, p, 1, 1, 0;\n}\n"
      : "=f"(d[0]), "=f"(d[1]), "=f"(d[2]), "=f"(d[3]), "=f"(d[4]), "=f"(d[5]), "=f"(d[6]), "=f"(d[7]), "=f"(d[8]), "=f"(d[9]), "=f"(d[10]), "=f"(d[11]),
        "=f"(d[12]), "=f"(d[13]), "=f"(d[14]), "=f"(d[15]), "=f"(d[16]), "=f"(d[17]), "=f"(d[18]), "=f"(d[19]), "=f"(d[20]), "=f"(d[21]), "=f"(d[22]),
        "=f"(d[23]), "=f"(d[24]), "=f"(d[25]), "=f"(d[26]), "=f"(d[27]), "=f"(d[28]), "=f"(d[29]), "=f"(d[30]), "=f"(d[31])
      : "r"(a0), "r"(a1), "r"(a2), "r"(a3), "l"(db), "r"(scaleD));
}
__device__ __forceinline__ void wgmma_pv_init(float (&d)[64], uint32_t a0, uint32_t a1, uint32_t a2, uint32_t a3, uint64_t db, int scaleD) {
  asm volatile("{\n.reg .pred p;\nsetp.ne.b32 p, %69, 0;\n"
      "wgmma.mma_async.sync.aligned.m64n128k16.f32.bf16.bf16 "
      "{%0, %1, %2, %3, %4, %5, %6, %7, %8, %9, %10, %11, %12, %13, %14, %15, %16, %17, %18, %19, %20, %21, %22, %23, %24, %25, %26, %27, %28, %29, %30, "
      "%31, %32, %33, %34, %35, %36, %37, %38, %39, %40, %41, %42, %43, %44, %45, %46, %47, %48, %49, %50, %51, %52, %53, %54, %55, %56, %57, %58, %59, %60, "
      "%61, %62, %63}, "
      "{%64, %65, %66, %67}, %68, p, 1, 1, 1;\n}\n"
      : "=f"(d[0]), "=f"(d[1]), "=f"(d[2]), "=f"(d[3]), "=f"(d[4]), "=f"(d[5]), "=f"(d[6]), "=f"(d[7]), "=f"(d[8]), "=f"(d[9]), "=f"(d[10]), "=f"(d[11]),
        "=f"(d[12]), "=f"(d[13]), "=f"(d[14]), "=f"(d[15]), "=f"(d[16]), "=f"(d[17]), "=f"(d[18]), "=f"(d[19]), "=f"(d[20]), "=f"(d[21]), "=f"(d[22]),
        "=f"(d[23]), "=f"(d[24]), "=f"(d[25]), "=f"(d[26]), "=f"(d[27]), "=f"(d[28]), "=f"(d[29]), "=f"(d[30]), "=f"(d[31]), "=f"(d[32]), "=f"(d[33]),
        "=f"(d[34]), "=f"(d[35]), "=f"(d[36]), "=f"(d[37]), "=f"(d[38]), "=f"(d[39]), "=f"(d[40]), "=f"(d[41]), "=f"(d[42]), "=f"(d[43]), "=f"(d[44]),
        "=f"(d[45]), "=f"(d[46]), "=f"(d[47]), "=f"(d[48]), "=f"(d[49]), "=f"(d[50]), "=f"(d[51]), "=f"(d[52]), "=f"(d[53]), "=f"(d[54]), "=f"(d[55]),
        "=f"(d[56]), "=f"(d[57]), "=f"(d[58]), "=f"(d[59]), "=f"(d[60]), "=f"(d[61]), "=f"(d[62]), "=f"(d[63])
      : "r"(a0), "r"(a1), "r"(a2), "r"(a3), "l"(db), "r"(scaleD));
}
__device__ __forceinline__ void wgmma_qk_sp_init(float (&d)[32], uint32_t a0, uint32_t a1, uint32_t a2, uint32_t a3, uint64_t db, int scaleD, uint32_t meta) {
  asm volatile("{\n.reg .pred p;\nsetp.ne.b32 p, %37, 0;\n"
      "wgmma.mma_async.sp.sync.aligned.m64n64k32.f32.bf16.bf16 "
      "{%0, %1, %2, %3, %4, %5, %6, %7, %8, %9, %10, %11, %12, %13, %14, %15, %16, %17, %18, %19, %20, %21, %22, %23, %24, %25, %26, %27, %28, %29, %30, "
      "%31}, "
      "{%32, %33, %34, %35}, %36, %38, 0, p, 1, 1, 0;\n}\n"
      : "=f"(d[0]), "=f"(d[1]), "=f"(d[2]), "=f"(d[3]), "=f"(d[4]), "=f"(d[5]), "=f"(d[6]), "=f"(d[7]), "=f"(d[8]), "=f"(d[9]), "=f"(d[10]), "=f"(d[11]),
        "=f"(d[12]), "=f"(d[13]), "=f"(d[14]), "=f"(d[15]), "=f"(d[16]), "=f"(d[17]), "=f"(d[18]), "=f"(d[19]), "=f"(d[20]), "=f"(d[21]), "=f"(d[22]),
        "=f"(d[23]), "=f"(d[24]), "=f"(d[25]), "=f"(d[26]), "=f"(d[27]), "=f"(d[28]), "=f"(d[29]), "=f"(d[30]), "=f"(d[31])
      : "r"(a0), "r"(a1), "r"(a2), "r"(a3), "l"(db), "r"(scaleD), "r"(meta));
}
__device__ __forceinline__ void wgmma_pv_sp_init(float (&d)[64], uint32_t a0, uint32_t a1, uint32_t a2, uint32_t a3, uint64_t db, int scaleD, uint32_t meta) {
  asm volatile("{\n.reg .pred p;\nsetp.ne.b32 p, %69, 0;\n"
      "wgmma.mma_async.sp.sync.aligned.m64n128k32.f32.bf16.bf16 "
      "{%0, %1, %2, %3, %4, %5, %6, %7, %8, %9, %10, %11, %12, %13, %14, %15, %16, %17, %18, %19, %20, %21, %22, %23, %24, %25, %26, %27, %28, %29, %30, "
      "%31, %32, %33, %34, %35, %36, %37, %38, %39, %40, %41, %42, %43, %44, %45, %46, %47, %48, %49, %50, %51, %52, %53, %54, %55, %56, %57, %58, %59, %60, "
      "%61, %62, %63}, "
      "{%64, %65, %66, %67}, %68, %70, 0, p, 1, 1, 1;\n}\n"
      : "=f"(d[0]), "=f"(d[1]), "=f"(d[2]), "=f"(d[3]), "=f"(d[4]), "=f"(d[5]), "=f"(d[6]), "=f"(d[7]), "=f"(d[8]), "=f"(d[9]), "=f"(d[10]), "=f"(d[11]),
        "=f"(d[12]), "=f"(d[13]), "=f"(d[14]), "=f"(d[15]), "=f"(d[16]), "=f"(d[17]), "=f"(d[18]), "=f"(d[19]), "=f"(d[20]), "=f"(d[21]), "=f"(d[22]),
        "=f"(d[23]), "=f"(d[24]), "=f"(d[25]), "=f"(d[26]), "=f"(d[27]), "=f"(d[28]), "=f"(d[29]), "=f"(d[30]), "=f"(d[31]), "=f"(d[32]), "=f"(d[33]),
        "=f"(d[34]), "=f"(d[35]), "=f"(d[36]), "=f"(d[37]), "=f"(d[38]), "=f"(d[39]), "=f"(d[40]), "=f"(d[41]), "=f"(d[42]), "=f"(d[43]), "=f"(d[44]),
        "=f"(d[45]), "=f"(d[46]), "=f"(d[47]), "=f"(d[48]), "=f"(d[49]), "=f"(d[50]), "=f"(d[51]), "=f"(d[52]), "=f"(d[53]), "=f"(d[54]), "=f"(d[55]),
        "=f"(d[56]), "=f"(d[57]), "=f"(d[58]), "=f"(d[59]), "=f"(d[60]), "=f"(d[61]), "=f"(d[62]), "=f"(d[63])
      : "r"(a0), "r"(a1), "r"(a2), "r"(a3), "l"(db), "r"(scaleD), "r"(meta));
}

constexpr int NB = 16, SQ = 224, DM = 640, NH = 32, SK = 1024, DH = 128;
constexpr int HD = NH * DH;
constexpr int NBETA = 2 * NB;
constexpr int NCTA = 132;
constexpr uint32_t SB0 = 1024;
constexpr int NS = 10;
constexpr int SLOT = 16384;
constexpr int QBUF_OFF = NS * SLOT;
constexpr int NSX = NS + 4;
constexpr int BAR_OFF = NSX * SLOT;
constexpr int BAR_FULL = BAR_OFF;
constexpr int BAR_EMPTY = BAR_OFF + 8 * NSX;
constexpr int BAR_STG = BAR_OFF + 16 * NSX;
constexpr int BAR_OUT = BAR_STG + 32;
constexpr int BAR_DESC = BAR_OUT + 8;
constexpr int BAR_GO = BAR_DESC + 8;
constexpr int BAR_MAIL = BAR_GO + 8;
constexpr int BAR_RDY = BAR_MAIL + 8;
constexpr int DESC_OFF = BAR_RDY + 8 * NSX;
constexpr int EPOCH_OFF = DESC_OFF + 16;
constexpr int TRACE_OFF = EPOCH_OFF + 16;
constexpr int SMEM_BYTES = TRACE_OFF;
constexpr float SM_C = 0.08838834764831845f * 1.4426950408889634f;
constexpr float SUM_HI = 1099511627776.f, SUM_LO = 1.f / 1099511627776.f;
constexpr uint32_t META_QK = 0xEEEE4444u;
constexpr uint32_t META_PV = 0x44EEEE44u;

#define QK_EARLY_MASK 3
#define ST_ORDER 0x2310
#define LAG_BAR 2
#define ST_NOW 8
#define PF_STEP 2
#define KV_WIN_D 4
#define SF 0xefbf
#define O_STEPS 4
#define KV_WIN_RAMP 4
#define PDEPTH 0
#define KV_WIN_TILES -2
#define REG_C 232
#define REG_P 24
#define GO_P 6
#define P_POS 208
#define OR 6
#define OR0 0
#define B_LATE 22
#define H_LATE 24
#define RM0 1
#define RM1 0xb3
#define RM2 0
#define PAIRB 1
#define LATE0 1
#define LATE1 2
#define GO_J 13
#define LATE_G 32
constexpr int N_FAST = 2;
#define SUMV 0
#define KG 5
#define PK 44
#define EARLY_MASK 0xffffu
#define PIECE_TABLE 0x501e8815,0x689d883d,0x5036b019,0x80000000,0x50345012,0x80000000,0x50244013,0x6b13403a,0x501c3811,0x695a3833,0x50321018,0x80000000,0x502b481a,0x6d4a4832,0x50128016,0x67e08035,0x50210814,0x6ccc0838,0x5012c010,0x695ac03f,0x64ec7836,0x80000000,0x64ecb830,0x80000000,0x5024c81f,0x80000000,0x5024601e,0x80000000,0x5021901d,0x80000000,0x501e7017,0x80000000,0x549b201c,0x80000000,0x67623031,0x80000000,0x67e06837,0x80000000,0x5016a81b,0x6dc8a839,0x689d0034,0x80000000,0x6999985b,0x80000000,0x695a583e,0x80000000,0x5011281c,0x80000000,0x55cea01b,0x80000000,0x6b91185c,0x80000000

struct Params {
  CUtensorMap x[2][2], wq[2], kv[2][2], wo[2];
  CUtensorMap o_ld[2], o_st[2], out_st[2];
  const __nv_bfloat16* kp[2];
  const __nv_bfloat16* vp[2];
};

constexpr int NPART = 32 * 5, O_BLOCKS = NBETA * 64 + 2 * NPART;
__device__ __align__(128) __nv_bfloat16 g_o[(size_t)O_BLOCKS * SQ * 64];
__device__ unsigned g_cnt[NBETA][8];
__device__ unsigned g_rd[NBETA][8];
__device__ unsigned g_epoch, g_next;
__device__ unsigned g_flag[NPART];

__device__ __forceinline__ uint32_t smem_u32(const void* p) { return (uint32_t)__cvta_generic_to_shared(p); }
__device__ __forceinline__ void mbar_arrive(uint32_t bar) {
  asm volatile("mbarrier.arrive.shared::cta.b64 _, [%0];" ::"r"(bar) : "memory");
}
__device__ __forceinline__ void mbar_arrive_warp(uint32_t bar) {
  asm volatile("{\n.reg .pred p;\nelect.sync _|p, 0xffffffff;\n@p mbarrier.arrive.shared::cta.b64 _, [%0];\n}" ::"r"(bar) : "memory");
}
__device__ __forceinline__ int lane_now() { int l; asm volatile("mov.u32 %0, %%laneid;" : "=r"(l)); return l; }
__device__ __forceinline__ bool mbar_try(uint32_t bar, uint32_t parity) {
  uint32_t ok;
  asm volatile("{\n.reg .pred p;\nmbarrier.try_wait.parity.shared::cta.b64 p, [%1], %2;\nselp.u32 %0, 1, 0, p;\n}"
               : "=r"(ok) : "r"(bar), "r"(parity) : "memory");
  return ok;
}
__device__ __forceinline__ bool mbar_test(uint32_t bar, uint32_t parity) {
  uint32_t ok;
  asm volatile("{\n.reg .pred p;\nmbarrier.test_wait.parity.shared::cta.b64 p, [%1], %2;\nselp.u32 %0, 1, 0, p;\n}"
               : "=r"(ok) : "r"(bar), "r"(parity) : "memory");
  return ok;
}
__device__ __forceinline__ void mbar_wait_w(uint32_t bar, uint32_t parity) {
  uint32_t n = 0;
  while (!__all_sync(0xffffffffu, mbar_try(bar, parity))) {
    if (++n > (1u << 22)) __trap();
  }
}
#define ELECT "{\n.reg .pred p;\nelect.sync _|p, 0xffffffff;\n@p "
__device__ __forceinline__ void tma_st3_w(const CUtensorMap* m, uint32_t src, int c1, int c2) {
  asm volatile(ELECT "cp.async.bulk.tensor.3d.global.shared::cta.bulk_group [%0, {0, %2, %3}], [%1];\n}"
               ::"l"(m), "r"(src), "r"(c1), "r"(c2) : "memory");
}
#define EXPECT(bar, bytes) "mbarrier.arrive.expect_tx.shared::cta.b64 _, [" bar "], " bytes ";\n@p "
__device__ __forceinline__ void tma_ld2_w(uint32_t dst, const CUtensorMap* m, int c0, int c1, uint32_t bar, uint32_t bytes) {
  asm volatile(ELECT EXPECT("%2", "%5") "cp.async.bulk.tensor.2d.shared::cluster.global.mbarrier::complete_tx::bytes [%0], [%1, {%3, %4}], [%2];\n}"
               ::"r"(dst), "l"(m), "r"(bar), "r"(c0), "r"(c1), "r"(bytes) : "memory");
}
__device__ __forceinline__ void tma_ld2_hint_w(uint32_t dst, const CUtensorMap* m, int c0, int c1, uint32_t bar, uint32_t bytes, uint64_t pol) {
  asm volatile(ELECT EXPECT("%2", "%6") "cp.async.bulk.tensor.2d.shared::cluster.global.mbarrier::complete_tx::bytes.L2::cache_hint"
               " [%0], [%1, {%3, %4}], [%2], %5;\n}"
               ::"r"(dst), "l"(m), "r"(bar), "r"(c0), "r"(c1), "l"(pol), "r"(bytes) : "memory");
}
__device__ __forceinline__ void tma_ld3_w(uint32_t dst, const CUtensorMap* m, int c0, int c1, int c2, uint32_t bar, uint32_t bytes) {
  asm volatile(ELECT EXPECT("%2", "%6") "cp.async.bulk.tensor.3d.shared::cluster.global.mbarrier::complete_tx::bytes [%0], [%1, {%3, %4, %5}], [%2];\n}"
               ::"r"(dst), "l"(m), "r"(bar), "r"(c0), "r"(c1), "r"(c2), "r"(bytes) : "memory");
}
__device__ __forceinline__ void tma_ld_kv_w(uint32_t dst, const CUtensorMap* m, int grp, uint32_t bar, uint64_t pol) {
  asm volatile(ELECT EXPECT("%2", "16384") "cp.async.bulk.tensor.4d.shared::cluster.global.mbarrier::complete_tx::bytes.L2::cache_hint"
               " [%0], [%1, {0, 0, 0, %3}], [%2], %4;\n}"
               ::"r"(dst), "l"(m), "r"(bar), "r"(grp), "l"(pol) : "memory");
}
__device__ __forceinline__ void tma_ld_wo_w(uint32_t dst, const CUtensorMap* m, int col, int grp, uint32_t bar) {
  asm volatile(ELECT EXPECT("%2", "16384") "cp.async.bulk.tensor.5d.shared::cluster.global.mbarrier::complete_tx::bytes [%0], [%1, {%3, 0, 0, 0, %4}], [%2];\n"
               "@p cp.async.bulk.tensor.5d.shared::cluster.global.mbarrier::complete_tx::bytes [%5], [%1, {%6, 0, 0, 0, %4}], [%2];\n}"
               ::"r"(dst), "l"(m), "r"(bar), "r"(col), "r"(grp), "r"(dst + 8192), "r"(col + 64) : "memory");
}
__device__ __forceinline__ void mbar_arrive8_w(uint32_t bar) {
  asm volatile(ELECT "mbarrier.arrive.shared::cta.b64 _, [%0], 8;\n}" ::"r"(bar) : "memory");
}
__device__ __forceinline__ uint32_t peer(uint32_t a) { uint32_t r; asm("mapa.shared::cluster.u32 %0, %1, %2;" : "=r"(r) : "r"(a), "r"(~blockIdx.x & 1)); return r; }
__device__ __forceinline__ void tma_ld2_both_w(uint32_t dst, const CUtensorMap* m, int c0, int c1, uint32_t bar, uint32_t bytes) {
  asm volatile(ELECT EXPECT("%2", "%5") "cp.async.bulk.tensor.2d.shared::cluster.global.mbarrier::complete_tx::bytes.multicast::cluster"
               " [%0], [%1, {%3, %4}], [%2], %6;\n}"
               ::"r"(dst), "l"(m), "r"(bar), "r"(c0), "r"(c1), "r"(bytes), "h"((uint16_t)3) : "memory");
}
__device__ __forceinline__ void tma_ld2_both_hint_w(uint32_t dst, const CUtensorMap* m, int c0, int c1, uint32_t bar, uint32_t bytes, uint64_t pol) {
  asm volatile(ELECT EXPECT("%2", "%6") "cp.async.bulk.tensor.2d.shared::cluster.global.mbarrier::complete_tx::bytes.multicast::cluster.L2::cache_hint"
               " [%0], [%1, {%3, %4}], [%2], %7, %5;\n}"
               ::"r"(dst), "l"(m), "r"(bar), "r"(c0), "r"(c1), "l"(pol), "r"(bytes), "h"((uint16_t)3) : "memory");
}
__device__ __forceinline__ void bulk_commit() { asm volatile("cp.async.bulk.commit_group;" ::: "memory"); }
template <int N> __device__ __forceinline__ void bulk_wait_read() { asm volatile("cp.async.bulk.wait_group.read %0;" ::"n"(N) : "memory"); }
__device__ __forceinline__ void wg_fence() { asm volatile("wgmma.fence.sync.aligned;" ::: "memory"); }
__device__ __forceinline__ void wg_commit() { asm volatile("wgmma.commit_group.sync.aligned;" ::: "memory"); }
template <int N> __device__ __forceinline__ void wg_wait() { asm volatile("wgmma.wait_group.sync.aligned %0;" ::"n"(N) : "memory"); }
__device__ __forceinline__ void fence_async_smem() { asm volatile("fence.proxy.async.shared::cta;" ::: "memory"); }
__device__ __forceinline__ void bar_sync(int id, int n) { asm volatile("bar.sync %0, %1;" ::"r"(id), "r"(n) : "memory"); }
__device__ __forceinline__ void touch(float& a) { asm volatile("neg.f32 %0, %0;" : "+f"(a)); }
__device__ __forceinline__ void touch(uint32_t& a) { asm volatile("not.b32 %0, %0;" : "+r"(a)); }
template <typename T, int N> __device__ __forceinline__ void touch(T (&a)[N]) {
#pragma unroll
  for (int i = 0; i < N; i++) touch(a[i]);
}
template <int ID, typename... A> __device__ __forceinline__ void sched_fence(uint32_t x, A&... a) {
  if (!((SF >> ID) & 1)) return;
  asm volatile("" : "+r"(x)::"memory");
#pragma unroll 1
  for (; __builtin_expect(x >= 100 + ID, 0); x >>= 1) { (touch(a), ...); __nanosleep(x); }
}
template <int N> __device__ __forceinline__ void reg_fence(float (&a)[N]) {
#pragma unroll
  for (int i = 0; i < N; i++) asm volatile("" : "+f"(a[i])::"memory");
}
template <int N> __device__ __forceinline__ void reg_fence(uint32_t (&a)[N]) {
#pragma unroll
  for (int i = 0; i < N; i++) asm volatile("" : "+r"(a[i])::"memory");
}
__device__ __forceinline__ float ex2(float x) { float y; asm("ex2.approx.ftz.f32 %0, %1;" : "=f"(y) : "f"(x)); return y; }
__device__ __forceinline__ uint32_t pack_bf16(float lo, float hi) {
  uint32_t r; asm("cvt.rn.bf16x2.f32 %0, %1, %2;" : "=r"(r) : "f"(hi), "f"(lo)); return r;
}
__device__ __forceinline__ void stsm4(uint32_t a, uint32_t r0, uint32_t r1, uint32_t r2, uint32_t r3) {
  asm volatile("stmatrix.sync.aligned.m8n8.x4.shared.b16 [%0], {%1, %2, %3, %4};" ::"r"(a), "r"(r0), "r"(r1), "r"(r2), "r"(r3) : "memory");
}
__device__ __forceinline__ void stsm4t(uint32_t a, uint32_t r0, uint32_t r1, uint32_t r2, uint32_t r3) {
  asm volatile("stmatrix.sync.aligned.m8n8.x4.trans.shared.b16 [%0], {%1, %2, %3, %4};" ::"r"(a), "r"(r0), "r"(r1), "r"(r2), "r"(r3) : "memory");
}
__device__ __forceinline__ void ldsm4(uint32_t a, uint32_t& r0, uint32_t& r1, uint32_t& r2, uint32_t& r3) {
  asm volatile("ldmatrix.sync.aligned.m8n8.x4.shared.b16 {%0, %1, %2, %3}, [%4];" : "=r"(r0), "=r"(r1), "=r"(r2), "=r"(r3) : "r"(a) : "memory");
}
__device__ __forceinline__ void sts16(uint32_t a, uint32_t v) { asm volatile("st.shared.u16 [%0], %1;" ::"r"(a), "h"((uint16_t)v) : "memory"); }
__device__ __forceinline__ void mma16816(float& c0, float& c1, float& c2, float& c3, uint32_t a0, uint32_t a1, uint32_t a2, uint32_t a3,
                                         uint32_t b0, uint32_t b1) {
  asm volatile("mma.sync.aligned.m16n8k16.row.col.f32.bf16.bf16.f32 {%0, %1, %2, %3}, {%4, %5, %6, %7}, {%8, %9}, {%0, %1, %2, %3};"
               : "+f"(c0), "+f"(c1), "+f"(c2), "+f"(c3) : "r"(a0), "r"(a1), "r"(a2), "r"(a3), "r"(b0), "r"(b1));
}
__device__ __forceinline__ uint32_t sdesc(uint32_t addr, uint32_t lbo) { return (addr >> 4) + ((lbo >> 4) << 16); }
__device__ __forceinline__ uint64_t desc64(uint32_t lo, uint32_t hi) { uint64_t d; asm("mov.b64 %0, {%1, %2};" : "=l"(d) : "r"(lo), "r"(hi)); return d; }
__device__ __forceinline__ void dadd(uint64_t& d, uint32_t inc) {
  asm("{\n.reg .b32 l, h;\nmov.b64 {l, h}, %0;\nadd.u32 l, l, %1;\nmov.b64 %0, {l, h};\n}" : "+l"(d) : "r"(inc));
}

struct Ring {
  uint32_t slot, phase, xp;
  __device__ __forceinline__ void uniform() {
    slot = __shfl_sync(0xffffffffu, slot, 0); phase = __shfl_sync(0xffffffffu, phase, 0); xp = __shfl_sync(0xffffffffu, xp, 0);
  }
  __device__ __forceinline__ void next() { if (++slot == NS) { slot = 0; phase ^= 1; } }
  __device__ __forceinline__ void next_if(bool p) { slot += p; if (slot == NS) { slot = 0; phase ^= 1; } }
};
__device__ __forceinline__ uint32_t borrow(int ks, int n) {
  const int k = ks + 1;
  return k >= 4 && !(k & 2) && k < n ? k & 1 : 2;
}

constexpr uint32_t Q_RANGES = NBETA * NH + __builtin_popcount(EARLY_MASK) * 5, Q_ALL = NBETA * (NH + 5);
constexpr int NRANGE = NCTA / 5;
struct Work { int kind, mode, k0, nsteps, range, beta, sub; };
struct Sched { uint16_t queue[Q_ALL]; uint32_t piece[NRANGE + 1][4]; };
constexpr Sched make_sched() {
  Sched s{};
  int q = 0, a = 0;
  for (int t = 0, e = 0; a < NBETA * NH; t++) {
    for (; e < NBETA && 8 * (e & ~PAIRB) + PK <= t && a >= P_POS; e++)
      for (int col = 0; col < 5 && (EARLY_MASK >> e & 1); col++) s.queue[q++] = 0x8000 | (e & 1 ? 4 - col : col) << 8 | e;
    for (int b = 0; b < NBETA; b++)
      for (int h = 0; h < NH; h++)
        if ((b >= B_LATE && h >= H_LATE ? 300 + b + LATE_G * (h >> 2) : 8 * (b & ~PAIRB) + KG * (h >> 2)) == t) { s.queue[q++] = b << 5 | h; a++; }
  }
  for (int b = 0; b < NBETA; b++)
    for (int col = 0; col < 5 && !(EARLY_MASK >> b & 1); col++) s.queue[q++] = 0x8000 | col << 8 | b;
  constexpr uint32_t T[NRANGE * 2] = {PIECE_TABLE};
  for (int g = 0; g <= NRANGE; g++)
    for (int n = 0; n < 4; n++) s.piece[g][n] = g < NRANGE && n < 2 ? T[2 * g + n] : 2u << 30;
  return s;
}
__constant__ Sched c_sched = make_sched();
constexpr uint64_t first_bits(int k0) {
  const Sched s = make_sched();
  uint64_t v = 0;
  for (int k = 0; k < 10; k++) v |= (uint64_t)(s.queue[(k0 + k) * 8] >> 2) << (6 * k);
  return v;
}
__host__ __device__ constexpr uint32_t first_entry(uint32_t q, uint64_t lo, uint64_t hi) {
  return (uint32_t)((q < 80 ? lo >> (q >> 3) * 6 : hi >> ((q >> 3) - 10) * 6) & 63) * 4 + (q & 4) * 8 + (q & 3);
}
constexpr uint64_t FIRST_LO = first_bits(0), FIRST_HI = first_bits(10);
constexpr bool first_ok() {
  const Sched s = make_sched();
  for (int q = 0; q < NCTA; q++) if (first_entry(q, FIRST_LO, FIRST_HI) != s.queue[q]) return false;
  return true;
}
static_assert(first_ok());
constexpr int N_EARLY = __builtin_popcount(EARLY_MASK);
constexpr bool reuse_ok() {
  const Sched s = make_sched();
  int first[NBETA + OR] = {};
  for (int q = Q_RANGES - 1; q >= 0; q--) if (!(s.queue[q] & 0x8000)) first[s.queue[q] >> 5] = q;
  for (int q = 0; q < Q_RANGES; q++) if ((s.queue[q] & 0x8000) && (s.queue[q] & 31) >= OR0 && q - first[(s.queue[q] & 31) + OR] > NCTA - 32) return false;
  return first[OR0 + OR] >= NCTA && P_POS >= NCTA;
}
static_assert(reuse_ok());
template <bool SIMPLE> __device__ __forceinline__ bool o_reuse(uint32_t b) { return !SIMPLE && b - (OR0 + OR) < N_EARLY - OR0; }
template <bool SIMPLE> __device__ __forceinline__ uint32_t o_slot(uint32_t b) { return o_reuse<SIMPLE>(b) ? OR0 + (b - OR0) % OR : b; }
__device__ __forceinline__ Work decode(uint32_t d) {
  Work w;
  w.kind = d >> 30; if (w.kind == 3) w.kind = 1;
  w.mode = (d >> 28) & 3; w.k0 = (d >> 22) & 63;
  if (w.kind == 0) { w.beta = (d >> 5) & 31; w.sub = d & 31; w.nsteps = DM / 64; }
  else { w.beta = d & 31; w.sub = (d >> 8) & 7; w.nsteps = ((d >> 16) & 63) + 1; }
  w.range = ((d >> 11) & 31) * 5 + w.sub;
  return w;
}

__device__ __forceinline__ bool reached(const unsigned* cnt, unsigned target) {
  unsigned v;
  asm volatile("ld.acquire.gpu.global.u32 %0, [%1];" : "=r"(v) : "l"(cnt) : "memory");
  return (int)(v - target) >= 0;
}
__device__ __forceinline__ void wait_count(const unsigned* cnt, unsigned target) {
  unsigned n = 0;
  while (!__all_sync(0xffffffffu, reached(cnt, target))) { if (++n > (1u << 24)) __trap(); }
}
__device__ __forceinline__ uint32_t lds(uint32_t a) { uint32_t v; asm volatile("ld.volatile.shared.u32 %0, [%1];" : "=r"(v) : "r"(a) : "memory"); return v; }

#define TRACE(u, e)
#define T3(u, e)
#define T2C(u, e)
#define T2P(u, r, e)
#define TTAIL(k)
#define TCLK(k)
#define TO -1
#define TRACE_O(k) if (TO == k) TRACE(i, 5)
#define TRACE_P(u, e)
#define TRACE_IN(u, e)

struct Ctx {
  uint32_t sb;
  int wg, warp;
  uint32_t mqk, mpv;
  bool lead;
  int lane0, lane;
  int src;
};
template <int N> __device__ __forceinline__ uint32_t dhi(uint32_t lo) { return 0x40000040u + (lo >> (26 + N)); }
__device__ __forceinline__ void release(const Ctx& c, uint32_t slot) {
  if (c.lead) mbar_arrive(c.sb + BAR_EMPTY + slot * 8);
}
__device__ __forceinline__ uint32_t acquire(const Ctx& c, Ring& r, bool have = false) {
  const uint32_t s = r.slot;
  if (!have) mbar_wait_w(c.sb + BAR_FULL + s * 8, r.phase);
  r.next();
  return s;
}
__device__ __forceinline__ void mbar_wait2_w(uint32_t b0, uint32_t p0, uint32_t b1, uint32_t p1) {
  uint32_t n = 0;
  while (!__all_sync(0xffffffffu, mbar_try(b0, p0) & mbar_try(b1, p1))) {
    if (++n > (1u << 22)) __trap();
  }
}
__device__ __forceinline__ void mbar_wait3_w(uint32_t b0, uint32_t p0, uint32_t b1, uint32_t p1, uint32_t b2, uint32_t p2) {
  uint32_t n = 0;
  while (!__all_sync(0xffffffffu, mbar_try(b0, p0) & mbar_try(b1, p1) & mbar_try(b2, p2))) {
    if (++n > (1u << 22)) __trap();
  }
}
__device__ __forceinline__ void acquire2(const Ctx& c, Ring& r, uint32_t& s0, uint32_t& s1, bool have = false) {
  const uint32_t p0 = r.phase;
  s0 = r.slot; r.next(); s1 = r.slot;
  if (!have) mbar_wait2_w(c.sb + BAR_FULL + s0 * 8, p0, c.sb + BAR_FULL + s1 * 8, r.phase);
  r.next();
}
template <int N>
__device__ __forceinline__ bool peek(const Ctx& c, Ring r) {
  bool ok = true;
#pragma unroll
  for (int k = 0; k < N; k++) { ok &= mbar_test(c.sb + BAR_FULL + r.slot * 8, r.phase); r.next(); }
  return ok;
}
__device__ __forceinline__ void staged(const Ctx& c, int part) {
  fence_async_smem();
  __syncwarp();
  mbar_arrive_warp(c.sb + BAR_STG + c.wg * 16 + part * 8);
}

template <int WG, bool FIRST, int H>
__device__ __forceinline__ void proj_half(const Ctx& c, float (&acc)[64], uint32_t w, uint32_t x, uint32_t sw) {
  uint64_t dx = desc64((SB0 + x * SLOT + (WG ? 0 : H * 8192)) >> 4, dhi<0>(x) + sw);
  uint64_t dw = desc64(WG ? (SB0 + w * SLOT + H * 8192) >> 4 : sdesc(SB0 + w * SLOT, 8192), dhi<1>(x));
  wg_fence();
  if (WG) { if (FIRST) wgmma_proj96_init(acc, dw, dx, 0); else wgmma_proj96(acc, dw, dx, 1); }
  else { if (FIRST) wgmma_proj_init(acc, dx, dw, 0); else wgmma_proj(acc, dx, dw, 1); }
#pragma unroll
  for (int k = 1; k < 4; k++) {
    dadd(dx, k == 2 ? 2 + (sw >> 30) * 28 : 2); dadd(dw, 128);
    if (WG) wgmma_proj96(acc, dw, dx, 1); else wgmma_proj(acc, dx, dw, 1);
  }
  wg_commit();
}

__device__ __forceinline__ void proj_store16(uint32_t a, const float* f, float sc) {
  stsm4t(a, pack_bf16(f[0] * sc, f[1] * sc), pack_bf16(f[2] * sc, f[3] * sc), pack_bf16(f[4] * sc, f[5] * sc), pack_bf16(f[6] * sc, f[7] * sc));
}

__device__ __forceinline__ uint32_t stage_off(const Ctx& c) {
  const int lane = c.lane, mi = lane >> 3, r8 = lane & 7;
  return ((mi >> 1) * 8 + r8) * 128 + (((2 * c.warp + (mi & 1)) ^ r8) << 4);
}
__device__ __forceinline__ uint32_t q3_swz(uint32_t r8) { return ((r8 & 3) << 1) | (r8 >> 2); }
template <int H>
__device__ __forceinline__ void stage_t2(const Ctx& c, const float (&a)[64], float sc) {
  const uint32_t base = c.sb + QBUF_OFF + 2 * 16384 + H * 8192 + stage_off(c);
#pragma unroll
  for (int jj = 0; jj < 4; jj++) proj_store16(base + jj * 2048, &a[jj * 8], sc);
}
template <int H, bool IS_Q>
__device__ __forceinline__ void stage_t3(const Ctx& c, const float (&a)[64], float sc) {
  const uint32_t off = stage_off(c), r8 = (off >> 7) & 7;
  const uint32_t t3 = c.sb + QBUF_OFF + 3 * 16384 + H * 4096 + (IS_Q ? off ^ ((r8 ^ q3_swz(r8)) << 4) : off);
  proj_store16(t3, &a[32], sc);
  proj_store16(t3 + 2048, &a[40], sc);
}

template <int WG, int h, int NW = 4>
__device__ __forceinline__ void load_part(const Ctx& c, Ring r, uint32_t (&q)[32]) {
  uint32_t n = 0;
  while (NW && !__all_sync(0xffffffffu, peek<NW>(c, r))) {
    if (++n > (1u << 26)) __trap();
  }
  const int lane = c.lane, mi = lane >> 3, r8 = lane & 7;
  if (WG) { r.next(); r.next(); }
  const uint32_t off = c.sb + (WG ? stage_off(c) : (16 * c.warp + (mi & 1) * 8 + r8) * 128), t0 = off + r.slot * SLOT;
  r.next();
  const uint32_t t1 = off + r.slot * SLOT;
#pragma unroll
    for (int jj = 0; jj < (WG ? 6 : 8); jj++) {
      uint32_t* p = &q[4 * jj];
      if (WG) asm volatile("ldmatrix.sync.aligned.m8n8.x4.trans.shared.b16 {%0, %1, %2, %3}, [%4];" : "=r"(p[0]), "=r"(p[1]), "=r"(p[2]), "=r"(p[3])
                           : "r"((jj < 4 ? t0 + h * 8192 : t1 + h * 4096) + (jj & 3) * 2048) : "memory");
      else ldsm4((h ? t1 : t0) + (jj >> 2) * 8192 + (((((2 * jj) & 7) + (mi >> 1)) ^ r8) << 4), p[0], p[1], p[2], p[3]);
    }
}
template <int WG>
__device__ __forceinline__ void add_part(const Ctx& c, const uint32_t (&q)[32], float (&a)[64]) {
  const uint32_t one = (c.lane >> 3) == (c.lane & 3) ? 0x3f80u << (c.lane & 4) * 4 : 0;
#pragma unroll
  for (int i = 0; i < (WG ? 12 : 16); i++)
    asm("mma.sync.aligned.m16n8k8.row.col.f32.bf16.bf16.f32 {%0, %1, %2, %3}, {%4, %5}, {%6}, {%0, %1, %2, %3};"
        : "+f"(a[4 * i]), "+f"(a[4 * i + 1]), "+f"(a[4 * i + 2]), "+f"(a[4 * i + 3]) : "r"(q[2 * i]), "r"(q[2 * i + 1]), "r"(one));
}

__device__ __forceinline__ void trace_dump(const Ctx& c) {
}
struct RowSum { float l0, l1; };
__device__ __forceinline__ const char* o_addr(uint32_t item, int row, int lane) {
  return reinterpret_cast<const char*>(g_o) + (((item >> 10) * (2 * SQ) + row) * 128 + (lane ^ (lane >> 3)) * 16);
}
__device__ __forceinline__ void o_stg(const char* p, int i, const uint32_t* q) {
  asm volatile("st.global.v4.b32 [%0], {%1, %2, %3, %4};"
               ::"l"(p + (i >> 1) * (SQ * 128) + (i & 1) * 512), "r"(q[0]), "r"(q[1]), "r"(q[2]), "r"(q[3]) : "memory");
}
template <int MODE, int I0 = 0, int NI = 4>
__device__ __forceinline__ void o_emit(const char* p, const float (&o)[64], float inv) {
#pragma unroll
  for (int i = I0; i < I0 + NI; i++) {
    uint32_t q[4];
#pragma unroll
    for (int j = 0; j < 4; j++) q[j] = pack_bf16(o[16 * i + 4 * j + 2 * MODE] * inv, o[16 * i + 4 * j + 2 * MODE + 1] * inv);
    o_stg(p, i, q);
  }
}
__device__ __forceinline__ void o_done(const Ctx& c) {
  __syncwarp();
  mbar_arrive_warp(c.sb + BAR_OUT);
  __syncwarp();
}
template <int WG>
__device__ __forceinline__ void o_first(const Ctx& c, uint32_t item, float (&o)[64], const RowSum& inv, uint32_t (&q)[32]) {
  const char* p = o_addr(item, WG ? 192 + 8 * c.warp : 64 + 16 * c.warp, c.lane);
  reg_fence(o);
#pragma unroll
  for (int j = 0; j < 16; j++) {
    if (WG) q[j] = pack_bf16((o[4 * j] + o[4 * j + 2]) * inv.l0, (o[4 * j + 1] + o[4 * j + 3]) * inv.l0);
    else q[j] = pack_bf16(o[4 * j] * inv.l0, o[4 * j + 1] * inv.l0);
    if (!WG && (j & 3) == 3 && (j >> 2) < 8 - LATE0) o_stg(p, j >> 2, q + j - 3);
  }
#pragma unroll
  for (int j = 0; j < 16; j++) {
    if (!WG) q[16 + j] = pack_bf16(o[4 * j + 2] * inv.l1, o[4 * j + 3] * inv.l1);
    if ((j & 3) == 3 && (j >> 2) < 4 - (WG ? LATE1 : LATE0)) o_stg(WG ? p : p + 1024, j >> 2, q + (WG ? 0 : 16) + j - 3);
  }
}
template <int WG>
__device__ __forceinline__ void o_rest(const Ctx& c, uint32_t item, uint32_t (&q)[32]) {
  const char* p = o_addr(item, WG ? 192 + 8 * c.warp : 64 + 16 * c.warp, c.lane);
#pragma unroll
  for (int i = WG ? 4 - LATE1 : 8 - LATE0; i < (WG ? 4 : 8); i++) o_stg(p + (i >> 2) * 1024, i & 3, q + 4 * i);
}
template <int K0, int K1>
__device__ __forceinline__ void o_piece(const Ctx& c, const char* p, int k, const float (&o)[64], const RowSum& inv) {
  constexpr int NI = 8 / O_STEPS, M = K0 * NI / 4;
  if constexpr (K1 - K0 == 1) {
    o_emit<M, K0 * NI % 4, NI>(p + M * 1024, o, M ? inv.l1 : inv.l0);
    if (K1 == O_STEPS) o_done(c);
  } else {
    if (k <= (K0 + K1) / 2) o_piece<K0, (K0 + K1) / 2>(c, p, k, o, inv); else o_piece<(K0 + K1) / 2, K1>(c, p, k, o, inv);
  }
}
template <int WG>
__device__ __forceinline__ void o_second(const Ctx& c, uint32_t item, int k, float (&o)[64], const RowSum& inv) {
  reg_fence(o);
  o_piece<0, O_STEPS>(c, o_addr(item, 128 * WG + 16 * c.warp, c.lane0 + (k >> 8)), k, o, inv);
}
template <int WG>
__device__ __forceinline__ void release_q(const Ctx& c) {
#pragma unroll
  for (int t = 0; t < 2; t++)
    if (c.lead) asm volatile("mbarrier.arrive.shared::cta.b64 _, [%0], 2;" ::"r"(c.sb + BAR_EMPTY + (NS + 2 * WG + t) * 8) : "memory");
  __syncwarp();
}
struct Slots { uint32_t w, x, o, po; };
template <int WG>
__device__ __forceinline__ void acc_fence(float (&a)[64]) {
#pragma unroll
  for (int i = 0; i < (WG ? 48 : 64); i++) asm volatile("" : "+f"(a[i])::"memory");
}
template <int WG>
__device__ __forceinline__ void begin_acquire(const Ctx& c, Ring& r, Slots& h, bool wait) {
  const uint32_t s0 = r.slot, p0 = r.phase, f = c.sb + BAR_FULL;
  r.next();
  const uint32_t p1 = r.phase;
  h.w = r.slot; r.next();
  h.x = WG ? r.slot : s0; h.o = WG ? s0 : r.slot; h.po = r.phase;
  if (wait) { if (WG) mbar_wait3_w(f + s0 * 8, p0, f + h.w * 8, p1, f + h.x * 8, r.phase); else mbar_wait2_w(f + s0 * 8, p0, f + h.w * 8, p1); }
  r.next();
}
template <int WG>
__device__ __forceinline__ void proj_begin(const Ctx& c, Ring& r, float (&a0)[64], Slots& h, bool wait, uint32_t sw) {
  begin_acquire<WG>(c, r, h, wait);
  proj_half<WG, true, 0>(c, a0, h.w, h.x, sw);
  if (WG) release(c, h.o);
}
template <int WG>
__device__ __forceinline__ void proj_main(Ctx& c, Ring& r, float (&a0)[64], float (&a1)[64], Slots& h, int n, uint32_t sw, int unit,
                                          uint32_t item, int nq, float (&o1)[64], const RowSum& inv) {
  constexpr bool DEEP = (PDEPTH >> WG) & 1;
  T2C(unit, 3);
  int ks = 1;
#pragma unroll 1
  do {
    const Slots p = h;
    const uint32_t b = borrow(ks, n), tile = NS + (WG ? 3 - b : b), f = c.sb + BAR_FULL;
    const uint32_t s0 = b != 2 ? tile : r.slot, p0 = b != 2 ? (r.xp >> b) & 1 : r.phase;
    r.next_if(b == 2);
    const uint32_t p1 = r.phase;
    h.w = r.slot; r.next();
    const uint32_t s2 = b != 2 ? tile : r.slot;
    h.po = b != 2 ? p0 : r.phase;
    r.next_if(b == 2);
    r.xp ^= 1 << b;
    h.x = WG ? s2 : s0; h.o = WG ? s0 : s2;
    mbar_wait3_w(f + s0 * 8, p0, f + h.w * 8, p1, f + (WG ? s2 : p.o) * 8, WG ? h.po : p.po);
    if (ks < 10) T2C(unit, ks * 4);
    if (DEEP) {
      proj_half<WG, false, 0>(c, a0, h.w, h.x, sw);
      release(c, WG ? h.o : p.o);
      if (ks < 10) T2C(unit, ks * 4 + 1);
      wg_wait<1>();
      if (ks < 10) T2C(unit, ks * 4 + 2);
      release(c, p.x); release(c, p.w);
    } else {
      release(c, WG ? h.o : p.o);
      wg_wait<0>();
      release(c, p.x); release(c, p.w);
      if (ks < 10) T2C(unit, ks * 4 + 1);
      proj_half<WG, false, 0>(c, a0, h.w, h.x, sw);
      if (ks < 10) T2C(unit, ks * 4 + 2);
    }
    proj_half<WG, false, 1>(c, a1, h.w, h.x, sw);
    if (ks < 10) T2C(unit, ks * 4 + 3);
    if (ks <= nq) o_second<WG>(c, item, ks, o1, inv);
  } while (++ks != n);
  {
    const uint32_t e0 = c.sb + BAR_EMPTY + (NS + 3 * WG) * 8, e1 = c.sb + BAR_EMPTY + (NS + 1 + WG) * 8;
    const uint32_t p0 = (r.xp ^ unit ^ 1) & 1, p1 = ((r.xp >> 1) ^ unit ^ 1) & 1;
    const uint32_t k0 = sw ? e0 : c.sb + BAR_FULL + r.slot * 8, pk = sw ? p0 : r.phase;
    uint32_t cnt = 0;
    while (!__all_sync(0xffffffffu, mbar_try(e0, p0) & mbar_try(e1, p1) & mbar_try(k0, pk) & (WG || mbar_try(c.sb + BAR_FULL + h.o * 8, h.po)))) {
      if (++cnt > (1u << 22)) __trap();
    }
  }
  c.lane = c.lane0 + (h.w >> 5);
  if (!WG) release(c, h.o);
}
template <int WG>
__device__ __forceinline__ void proj_end(const Ctx& c, float (&a1)[64], const Slots& h) {
  wg_wait<0>();
  acc_fence<WG>(a1);
  release(c, h.x); release(c, h.w);
}
__device__ __forceinline__ uint32_t get_desc(const Ctx& c, int i) {
  uint32_t d;
  mbar_wait_w(c.sb + BAR_DESC, (i - 1) & 1);
  asm volatile("ld.volatile.shared.u32 %0, [%1];" : "=r"(d) : "r"(c.sb + DESC_OFF + (i & 3) * 4) : "memory");
  return __shfl_sync(0xffffffffu, d, 0);
}

__device__ __forceinline__ float quad_max(float x) {
  x = fmaxf(x, __shfl_xor_sync(0xffffffffu, x, 1));
  return fmaxf(x, __shfl_xor_sync(0xffffffffu, x, 2));
}
__device__ __forceinline__ float quad_sum(float x) {
  x += __shfl_xor_sync(0xffffffffu, x, 1);
  return x + __shfl_xor_sync(0xffffffffu, x, 2);
}
template <bool SP, bool FIRST>
__device__ __forceinline__ void exps(const Ctx& c, const float (&s)[32], uint32_t (&p)[SP ? 8 : 16], RowSum& st) {
  if constexpr (SP) {
    uint32_t q[8];
    float t;
#pragma unroll
    for (int j = 0; j < 8; j++) {
      const float e0 = ex2(s[4 * j] + s[4 * j + 2]), e1 = ex2(s[4 * j + 1] + s[4 * j + 3]);
      if (j == 0) t = e0 + e1; else t += e0 + e1;
      q[j] = pack_bf16(e0, e1);
    }
    const bool odd = c.src & 2;
#pragma unroll
    for (int g = 0; g < 4; g++) {
      p[2 * g] = __shfl_sync(0xffffffffu, odd ? q[2 * g + 1] : q[2 * g], c.src);
      p[2 * g + 1] = __shfl_sync(0xffffffffu, odd ? q[2 * g] : q[2 * g + 1], c.src ^ 1);
    }
    st.l0 = FIRST ? t : st.l0 + t;
  } else {
    float t0, t1, u0, u1;
#pragma unroll
    for (int j = 0; j < 8; j++) {
      const float e0 = ex2(s[4 * j]), e1 = ex2(s[4 * j + 1]), e2 = ex2(s[4 * j + 2]), e3 = ex2(s[4 * j + 3]);
      if (SUMV == 0) { if (j == 0) { t0 = e0 + e1; t1 = e2 + e3; } else { t0 += e0 + e1; t1 += e2 + e3; } }
      else if (SUMV == 1) { if (j == 0) { t0 = e0 + e1; t1 = e2 + e3; } else { t0 = (t0 + e0) + e1; t1 = (t1 + e2) + e3; } }
      else { if (j == 0) { t0 = e0; u0 = e1; t1 = e2; u1 = e3; } else { t0 += e0; u0 += e1; t1 += e2; u1 += e3; } if (j == 7) { t0 += u0; t1 += u1; } }
      p[2 * j] = pack_bf16(e0, e1);
      p[2 * j + 1] = pack_bf16(e2, e3);
    }
    st.l0 = FIRST ? t0 : st.l0 + t0;
    st.l1 = FIRST ? t1 : st.l1 + t1;
  }
}
template <bool SP>
__device__ __forceinline__ bool finish_sums(RowSum& st) {
  const float a = quad_sum(st.l0), b = SP ? a : quad_sum(st.l1);
  st.l0 = __fdividef(1.f, a); st.l1 = __fdividef(1.f, b);
  return !(a >= SUM_LO && a <= SUM_HI && b >= SUM_LO && b <= SUM_HI);
}
template <bool SP, bool INIT, int SITE, bool COMMIT = true, int RM = 0>
__device__ __forceinline__ void issue_qk(const Ctx& c, float (&s)[32], const uint32_t (&qs)[32], uint32_t dq, uint32_t dk) {
  uint64_t a = desc64(dq, dhi<SITE & 1>(dk)), b = desc64(dk, dhi<1 - (SITE & 1)>(dk) + 64);
  if (SP) {
    if (INIT) wgmma_qk_sp_init(s, qs[0], qs[1], qs[2], qs[3], b, 0, c.mqk); else wgmma_qk_sp(s, qs[0], qs[1], qs[2], qs[3], b, 0, c.mqk);
#pragma unroll
    for (int k = 1; k < 4; k++) { dadd(b, k == 2 ? 60 : 4); wgmma_qk_sp(s, qs[4 * k], qs[4 * k + 1], qs[4 * k + 2], qs[4 * k + 3], b, 1, c.mqk); }
  } else {
    if (RM & 1) wgmma_qk_rs(s, qs[0], qs[1], qs[2], qs[3], b, 0); else if (INIT) wgmma_qk_init(s, a, b, 0); else wgmma_qk(s, a, b, 0);
#pragma unroll
    for (int k = 1; k < 8; k++) {
      dadd(a, k == 4 ? 506 : 2); dadd(b, k == 4 ? 58 : 2);
      if (RM >> k & 1) wgmma_qk_rs(s, qs[4 * k], qs[4 * k + 1], qs[4 * k + 2], qs[4 * k + 3], b, 1); else wgmma_qk(s, a, b, 1);
    }
  }
  if (COMMIT) wg_commit();
}
template <bool SP, bool ACC, int SITE, bool SPLIT = false>
__device__ __forceinline__ void issue_pv(const Ctx& c, float (&o)[64], const uint32_t (&p)[SP ? 8 : 16], uint32_t dv) {
  uint64_t b = desc64(dv, dhi<SITE & 1>(dv) + 64);
  if constexpr (SP) {
    if (ACC) wgmma_pv_sp(o, p[0], p[1], p[2], p[3], b, 1, c.mpv); else wgmma_pv_sp_init(o, p[0], p[1], p[2], p[3], b, 0, c.mpv);
    if (SPLIT) wg_commit();
    dadd(b, 512);
    wgmma_pv_sp(o, p[4], p[5], p[6], p[7], b, 1, c.mpv);
  } else {
    if (ACC) wgmma_pv(o, p[0], p[1], p[2], p[3], b, 1); else wgmma_pv_init(o, p[0], p[1], p[2], p[3], b, 0);
#pragma unroll
    for (int k = 1; k < 4; k++) { dadd(b, 256); wgmma_pv(o, p[4 * k], p[4 * k + 1], p[4 * k + 2], p[4 * k + 3], b, 1); }
  }
  wg_commit();
}
__device__ __forceinline__ void pack_rows(const float (&o)[64], float sc, uint32_t (&q)[32]) {
#pragma unroll
  for (int j = 0; j < 32; j++) q[j] = pack_bf16(o[2 * j] * sc, o[2 * j + 1] * sc);
}
template <int MASK = 255>
__device__ __forceinline__ void stage_rows(const Ctx& c, uint32_t tile_addr, const uint32_t (&q)[32]) {
  const int lane = c.lane, mi = lane >> 3, r8 = lane & 7;
  const uint32_t row_addr = tile_addr + (16 * c.warp + (mi & 1) * 8 + r8) * 128;
#pragma unroll
  for (int jj = 0; jj < 8; jj++)
    if (MASK >> jj & 1) stsm4(row_addr + (jj >> 2) * 8192 + (((((2 * jj) & 7) + (mi >> 1)) ^ r8) << 4), q[4 * jj], q[4 * jj + 1], q[4 * jj + 2], q[4 * jj + 3]);
}
__device__ __forceinline__ void stage_rows(const Ctx& c, uint32_t tile_addr, const float (&o)[64], float sc) {
  uint32_t q[32];
  pack_rows(o, sc, q);
  stage_rows(c, tile_addr, q);
}
template <int WG, int H>
__device__ __forceinline__ void stage_out(const Ctx& c, const float (&a)[64]) {
  if (WG) { stage_t3<H, false>(c, a, 1.f); if (H) staged(c, 0); stage_t2<H>(c, a, 1.f); }
  else stage_rows(c, c.sb + QBUF_OFF + H * 16384, a, 1.f);
  if (H || !WG) staged(c, H);
}
template <int SITE>
__device__ __forceinline__ void issue_qk_rs(float (&s)[32], uint32_t (&q)[32], uint32_t dk) {
  uint64_t b = desc64(dk, dhi<SITE>(dk) + 64);
  reg_fence(q);
  wg_fence();
  wgmma_qk_rs_init(s, q[0], q[1], q[2], q[3], b, 0);
#pragma unroll
  for (int k = 1; k < 8; k++) { dadd(b, k == 4 ? 58 : 2); wgmma_qk_rs(s, q[4 * k], q[4 * k + 1], q[4 * k + 2], q[4 * k + 3], b, 1); }
  wg_commit();
}

__device__ __forceinline__ void redo_tile(const Ctx& c, uint32_t q_addr, uint32_t half, const __nv_bfloat16* kp, const __nv_bfloat16* vp,
                                          uint32_t item, int row) {
  float o[64];
  const int lane = lane_now(), g = lane >> 2, cc = lane & 3, mi = lane >> 3, r8 = lane & 7;
  const uint32_t qa = q_addr + (half == 4096 ? 8 * c.warp + r8 : 16 * c.warp + (mi & 1) * 8 + r8) * 128, swz = half == 4096 ? q3_swz(r8) : r8;
  const uint32_t* kq = reinterpret_cast<const uint32_t*>(kp + g * DH) + cc;
  const unsigned short* vq = reinterpret_cast<const unsigned short*>(vp + 2 * cc * DH) + g;
  float m0 = -INFINITY, m1 = -INFINITY, l0 = 0.f, l1 = 0.f;
#pragma unroll
  for (int i = 0; i < 64; i++) o[i] = 0.f;
#pragma unroll 1
  for (int kb = 0; kb < SK / 16; kb++) {
    float z[8] = {0.f, 0.f, 0.f, 0.f, 0.f, 0.f, 0.f, 0.f};
#pragma unroll 2
    for (int kk = 0; kk < 8; kk++) {
      uint32_t a0, a1, a2, a3;
      ldsm4(qa + (kk >> 2) * half + ((((kk & 3) * 2 + (mi >> 1)) ^ swz) << 4), a0, a1, a2, a3);
      const uint32_t* kr = kq + kb * (16 * DH / 2) + kk * 8;
      mma16816(z[0], z[1], z[2], z[3], a0, a1, a2, a3, __ldg(kr), __ldg(kr + 4));
      mma16816(z[4], z[5], z[6], z[7], a0, a1, a2, a3, __ldg(kr + 8 * DH / 2), __ldg(kr + 8 * DH / 2 + 4));
    }
    const float n0 = fmaxf(m0, quad_max(fmaxf(fmaxf(z[0], z[1]), fmaxf(z[4], z[5]))));
    const float n1 = fmaxf(m1, quad_max(fmaxf(fmaxf(z[2], z[3]), fmaxf(z[6], z[7]))));
    const float al0 = ex2(m0 - n0), al1 = ex2(m1 - n1);
    m0 = n0; m1 = n1;
#pragma unroll
    for (int i = 0; i < 8; i++) z[i] = ex2(z[i] - ((i & 2) ? n1 : n0));
    l0 = l0 * al0 + (z[0] + z[1]) + (z[4] + z[5]);
    l1 = l1 * al1 + (z[2] + z[3]) + (z[6] + z[7]);
    const uint32_t a0 = pack_bf16(z[0], z[1]), a1 = pack_bf16(z[2], z[3]), a2 = pack_bf16(z[4], z[5]), a3 = pack_bf16(z[6], z[7]);
    const unsigned short* vr = vq + kb * (16 * DH);
#pragma unroll
    for (int nb = 0; nb < 16; nb++) {
      o[4 * nb] *= al0; o[4 * nb + 1] *= al0; o[4 * nb + 2] *= al1; o[4 * nb + 3] *= al1;
      const uint32_t b0 = __ldg(vr + nb * 8) | ((uint32_t)__ldg(vr + nb * 8 + DH) << 16);
      const uint32_t b1 = __ldg(vr + nb * 8 + 8 * DH) | ((uint32_t)__ldg(vr + nb * 8 + 9 * DH) << 16);
      mma16816(o[4 * nb], o[4 * nb + 1], o[4 * nb + 2], o[4 * nb + 3], a0, a1, a2, a3, b0, b1);
    }
  }
  const char* p = o_addr(item, row, lane);
  o_emit<0>(p, o, __fdividef(1.f, quad_sum(l0)));
  o_emit<1>(half == 4096 ? p : p + 1024, o, __fdividef(1.f, quad_sum(l1)));
}

template <bool SPA, bool SPB, int SITE, int ID>
__device__ __forceinline__ void batch(const Ctx& c, float (&s)[32], const uint32_t (&qs)[32], uint32_t dq, uint32_t dk, float (&ob)[64],
                                      uint32_t (&pb)[SPB ? 8 : 16], uint32_t dv) {
  if constexpr (SPA) {
    reg_fence(pb);
    wg_fence();
    issue_pv<SPB, true, ID>(c, ob, pb, dv);
    issue_qk<SPA, false, ID>(c, s, qs, dq, dk);
  } else {
    constexpr bool EARLY = ((QK_EARLY_MASK >> (SITE + (SPB ? 2 : 0))) & 1) != 0;
    if (!EARLY) reg_fence(pb);
    wg_fence();
    issue_qk<SPA, false, ID, !SPB, SITE ? RM0 : SPB ? RM2 : RM1>(c, s, qs, dq, dk);
    if (EARLY) { reg_fence(pb); wg_fence(); }
    issue_pv<SPB, true, ID, SPB>(c, ob, pb, dv);
  }
}

template <bool SP0>
__device__ __forceinline__ bool attention(Ctx& c, Ring& r, int unit, uint32_t& d, const float (&a0)[64], float (&o0)[64], float (&o1)[64],
                                          RowSum& st0, RowSum& st1, const Slots& h, uint32_t (&q1)[32]) {
  constexpr bool SP1 = false;
  if (SP0) { c.mqk = META_QK + (d >> 28); c.mpv = META_PV + (d >> 28); asm volatile("" : "+r"(c.mqk), "+r"(c.mpv)); }
  if (SP0) c.src = (c.lane & 28) | ((c.lane & 1) << 1) | ((c.lane >> 1) & 1);
  float s[32];
  uint32_t p0[SP0 ? 8 : 16], p1[16];
  const uint32_t q0a = c.sb + QBUF_OFF + (SP0 ? 3 : 0) * 16384, q1a = c.sb + QBUF_OFF + (SP0 ? 2 : 1) * 16384;
  const uint32_t dq0 = sdesc(SB0 + QBUF_OFF, 0), dq1 = sdesc(SB0 + QBUF_OFF + (SP0 ? 2 : 1) * 16384, 0);
  uint32_t sk = acquire(c, r, true), sv, sn;
  uint32_t qs[32];
  float s1[32];
  if (SP0) {
    stage_t3<0, true>(c, a0, SM_C);
    stage_t2<0>(c, a0, SM_C);
    proj_end<1>(c, o0, h);
    stage_t3<1, true>(c, o0, SM_C);
    stage_t2<1>(c, o0, SM_C);
    bar_sync(5, 128);
    const int g = c.lane >> 2, cc = c.lane & 3;
    const uint32_t qa = q0a + (8 * c.warp + g) * 128 + (cc & 1) * 8;
#pragma unroll
    for (int k = 0; k < 8; k++)
      asm volatile("ld.shared.v2.u32 {%0, %1}, [%2];" : "=r"(qs[2 * k]), "=r"(qs[2 * k + 1])
                   : "r"(qa + (k >> 2) * 4096 + ((((k & 3) * 2 + (cc >> 1)) ^ q3_swz(g)) << 4)) : "memory");
    fence_async_smem();
    bar_sync(1, 256);
    TRACE(unit, 2);
    wg_fence();
    issue_qk<SP1, true, 1>(c, s1, qs, dq1, sdesc(SB0 + sk * SLOT, 0));
#pragma unroll
    for (int k = 0; k < 8; k++)
      if (RM2 >> k & 1) ldsm4(q1a + (k >> 2) * 8192 + (16 * c.warp + (c.lane & 15)) * 128 + (((2 * (k & 3) + (c.lane >> 4)) ^ (c.lane & 7)) << 4),
                              q1[4 * k], q1[4 * k + 1], q1[4 * k + 2], q1[4 * k + 3]);
#pragma unroll
    for (int k = 0; k < 16; k++) asm volatile("" : "+r"(qs[k])::"memory");
    wg_fence();
    issue_qk<SP0, true, 0>(c, s, qs, dq0, sdesc(SB0 + sk * SLOT, 0));
    const bool have = peek<2>(c, r);
    wg_wait<1>();
    reg_fence(s1);
    exps<SP1, true>(c, s1, p1, st1);
    sched_fence<11>(sk, p1);
    acquire2(c, r, sv, sn, __all_sync(0xffffffffu, have));
    wg_wait<0>();
    wg_fence();
    issue_pv<SP1, false, 1>(c, o1, p1, sdesc(SB0 + sv * SLOT, 1024));
    if (LAG_BAR & 1) asm volatile("bar.arrive 4, 256;" ::: "memory");
    sched_fence<12>(sk, s);
    release(c, sk);
    sk = sn;
    exps<SP0, true>(c, s, p0, st0);
    reg_fence(p0);
    wg_fence();
    issue_pv<SP0, false, 0>(c, o0, p0, sdesc(SB0 + sv * SLOT, 1024));
    issue_qk<SP0, true, 2>(c, s, qs, dq0, sdesc(SB0 + sk * SLOT, 0));
    sn = acquire(c, r);
    wg_wait<0>();
    reg_fence(s);
  } else {
    pack_rows(a0, SM_C, qs);
    stage_rows(c, q0a, qs);
    proj_end<0>(c, o1, h);
    TRACE(unit, 2);
    float sc = SM_C;
    issue_qk_rs<0>(s, qs, sdesc(SB0 + sk * SLOT, 0));
    sched_fence<0>(sk, sc);
    pack_rows(o1, sc, q1);
    stage_rows<~RM1>(c, q1a, q1);
    issue_qk_rs<1>(s1, q1, sdesc(SB0 + sk * SLOT, 0));
    asm volatile("bar.arrive 1, 256;" ::: "memory");
    bool have = peek<2>(c, r);
    wg_wait<1>();
    reg_fence(s);
    exps<SP0, true>(c, s, p0, st0);
    sched_fence<1>(sk, p0);
    acquire2(c, r, sv, sn, __all_sync(0xffffffffu, have));
    wg_wait<0>();
    reg_fence(s1);
    fence_async_smem();
    __syncwarp();
    wg_fence();
    issue_qk<SP0, false, 2, true, RM0>(c, s, qs, dq0, sdesc(SB0 + sn * SLOT, 0));
    issue_pv<SP0, false, 0>(c, o0, p0, sdesc(SB0 + sv * SLOT, 1024));
    sched_fence<2>(sk, s1);
    release(c, sk);
    have = peek<1>(c, r);
    sk = sn;
    exps<SP1, true>(c, s1, p1, st1);
    reg_fence(p1);
    wg_fence();
    issue_pv<SP1, false, 1>(c, o1, p1, sdesc(SB0 + sv * SLOT, 1024));
    sn = acquire(c, r, __all_sync(0xffffffffu, have));
    if (LAG_BAR & 1) bar_sync(4, 256);
    wg_wait<1>();
    reg_fence(s);
  }
  TRACE_IN(unit, 4);
  T2C(unit, 51);
#pragma unroll 1
  for (int j = 1; j < 15; j++) {
    const uint32_t sv_prev = sv, sk_prev = sk;
    sv = sn;
    const uint32_t dv = sdesc(SB0 + sv * SLOT, 1024);
    reg_fence(p0);
    exps<SP0, false>(c, s, p0, st0);
    batch<SP1, SP0, 0, 3>(c, s, q1, dq1, sdesc(SB0 + sk * SLOT, 0), o0, p0, dv);
    sk = acquire(c, r);
    wg_wait<1>();
    reg_fence(s); reg_fence(p1);
    release(c, sv_prev); release(c, sk_prev);
    exps<SP1, false>(c, s, p1, st1);
    batch<SP0, SP1, 1, 4>(c, s, qs, dq0, sdesc(SB0 + sk * SLOT, 0), o1, p1, dv);
    sn = acquire(c, r);
    if (SP0) wg_wait<0>(); else wg_wait<1>();
    reg_fence(s);
  }
  TRACE_IN(unit, 5);
  T2C(unit + 1, 52);
  const uint32_t sv_prev = sv;
  sv = sn;
  const uint32_t dv = sdesc(SB0 + sv * SLOT, 1024);
  reg_fence(p0);
  exps<SP0, false>(c, s, p0, st0);
  batch<SP1, SP0, 0, 5>(c, s, q1, dq1, sdesc(SB0 + sk * SLOT, 0), o0, p0, dv);
  asm volatile("ld.volatile.shared.u32 %0, [%1];" : "=r"(d) : "r"(c.sb + DESC_OFF + ((unit + 1) & 3) * 4) : "memory");
  const bool have = peek<2 + SP0>(c, r);
  wg_wait<1>();
  reg_fence(s); reg_fence(p1);
  release(c, sv_prev); release(c, sk);
  exps<SP1, false>(c, s, p1, st1);
  reg_fence(p1);
  wg_fence();
  issue_pv<SP1, true, 2>(c, o1, p1, dv);
  if (SP0) sched_fence<6>(sk, st0.l0, st1.l0, st1.l1); else sched_fence<5>(sk, st0.l0, st0.l1, st1.l0, st1.l1);
  c.lane = c.lane0 + (sk >> 5);
  const bool bad = finish_sums<SP0>(st0) | finish_sums<SP1>(st1);
  uint32_t any;
  asm volatile("{\n.reg .pred p, q;\nsetp.ne.u32 p, %1, 0;\nbar.red.or.pred q, %2, 128, p;\nselp.u32 %0, 1, 0, q;\n}"
               : "=r"(any) : "r"((uint32_t)bad), "n"(2 + SP0) : "memory");
  any = __any_sync(0xffffffffu, any);
  d = __shfl_sync(0xffffffffu, d, 0);
  if (d < (2u << 30) && !__all_sync(0xffffffffu, have)) { Ring t = r; Slots u; begin_acquire<SP0>(c, t, u, true); }
  wg_wait<0>();
  reg_fence(o0); reg_fence(o1);
  release(c, sv);
  return any;
}

template <int WG>
__device__ __forceinline__ void consumer(Ctx c, const __nv_bfloat16* const* kv) {
  asm volatile("setmaxnreg.inc.sync.aligned.u32 %0;" ::"n"(WG ? REG_C : 504 - REG_C - REG_P));
  c.wg = WG;
  Ring r{0, 0, 0};
  float a0[64], a1[64], o1[64];
  Slots h;
  RowSum inv0, inv1;
  uint32_t oq[32];
  uint32_t d = first_entry(blockIdx.x, FIRST_LO, FIRST_HI) * 1025, dc = 0, sw;
  int i = 0, nq;
begin:
  sw = d & (1u << 30);
  proj_begin<WG>(c, r, a0, h, true, sw);
  proj_half<WG, true, 1>(c, a1, h.w, h.x, sw);
  nq = 0;
#pragma unroll
  for (int k = 0; k < 64; k++) asm volatile("" : "=f"(o1[k]));
  asm volatile("" : "=f"(inv1.l0), "=f"(inv1.l1));
  while (true) {
    TRACE(i, 0); TRACE(i, 6);
    proj_main<WG>(c, r, a0, a1, h, d >> 30 ? ((d >> 16) & 63) + 1 : DM / 64, sw, i, dc, nq, o1, inv1);
    dc = d;
    TRACE(i, 1);
    if (d >> 30) goto out_tile;
    wg_wait<1>();
    acc_fence<WG>(a0);
    if (WG ? attention<WG>(c, r, i, d, a0, a1, o1, inv0, inv1, h, oq) : attention<WG>(c, r, i, d, a0, o1, a1, inv1, inv0, h, oq)) goto redo;
    if (d >= (2u << 30)) break;
    sw = d & (1u << 30);
    proj_begin<WG>(c, r, a0, h, false, sw);
    release_q<WG>(c);
    if (WG) sched_fence<8>(h.w, inv0.l0); else sched_fence<7>(h.w, inv0.l0, inv0.l1);
    o_first<WG>(c, dc, a1, inv0, oq);
    sched_fence<9>(h.w, inv1.l0);
    proj_half<WG, true, 1>(c, a1, h.w, h.x, sw);
    o_rest<WG>(c, dc, oq);
    nq = O_STEPS;
    TRACE(i, 3); TRACE(i, 7);
    i++;
  }
  release_q<WG>(c);
  o_first<WG>(c, dc, a1, inv0, oq);
  o_rest<WG>(c, dc, oq);
#pragma unroll
  for (int k = 1; k <= O_STEPS; k++) o_second<WG>(c, dc, k, o1, inv1);
next:
  TRACE(i, 3); TRACE(i, 7);
  if ((d >> 30) != 2) {
    i++;
    r.uniform();
    goto begin;
  }
  trace_dump(c);
  return;
out_tile:
  if (d & 96) goto finish;
  d = get_desc(c, i + 1);
  wg_wait<1>();
  acc_fence<WG>(a0);
  TRACE_O(0);
  stage_out<WG, 0>(c, a0);
  TRACE_O(1);
  proj_end<WG>(c, a1, h);
  TRACE_O(2);
  stage_out<WG, 1>(c, a1);
  TRACE(i, 2);
  goto next;
finish:
  {
    uint32_t q[32];
#pragma unroll 1
    for (int k = (d >> 5) & 3; k > 1; k--) {
      wg_wait<0>();
      acc_fence<WG>(a0); acc_fence<WG>(a1);
      if (k == ((d >> 5) & 3)) { release(c, h.x); release(c, h.w); }
      load_part<WG, 0>(c, r, q); add_part<WG>(c, q, a0);
      load_part<WG, 1, 0>(c, r, q); add_part<WG>(c, q, a1);
#pragma unroll
      for (int t = 0; t < 4; t++) { release(c, r.slot); r.next(); }
    }
    load_part<WG, 0, WG ? 4 : 1>(c, r, q);
    wg_wait<1>();
    acc_fence<WG>(a0);
    TRACE_O(0);
    add_part<WG>(c, q, a0);
    stage_out<WG, 0>(c, a0);
    TRACE_O(1);
    load_part<WG, 1, WG ? 0 : 2>(c, r, q);
    wg_wait<0>();
    acc_fence<WG>(a1);
    TRACE_O(2);
    add_part<WG>(c, q, a1);
    stage_out<WG, 1>(c, a1);
    TRACE(i, 2); TRACE(i, 3); TRACE(i, 7);
    trace_dump(c);
    return;
  }
redo:
  {
    if (!WG) { stage_rows<RM1>(c, c.sb + QBUF_OFF + 16384, oq); __syncwarp(); }
    const size_t hoff = (size_t)(dc & 511) * (SK * DH);
    const int br = (dc >> 9) & 1;
#pragma unroll 1
    for (int part = 0; part < 2; part++) {
      const int t = WG ? 3 - part : part;
      redo_tile(c, c.sb + QBUF_OFF + t * 16384, t == 3 ? 4096 : 8192, kv[br] + hoff, kv[2 + br] + hoff, dc,
                t * 64 + (t == 3 ? 8 : 16) * c.warp);
    }
    o_done(c);
    release_q<WG>(c);
  }
  goto next;
}

template <bool SIMPLE>
__global__ void __launch_bounds__(384, 1) mha_fused_kernel(const __grid_constant__ Params P) {
  extern __shared__ __align__(1024) uint8_t smem_raw[];
  const uint32_t sbase = smem_u32(smem_raw);
  const int tid = threadIdx.x;
  const int wg = __shfl_sync(0xffffffffu, tid >> 7, 0);
  const int warp = __shfl_sync(0xffffffffu, (tid >> 5) & 3, 0);
  const int lane = tid & 31;
  const int cta = blockIdx.x;
  constexpr bool PAIR = !SIMPLE;

  if (tid == 0) T3(15, 0);
  if (tid == 0) TTAIL(7);
  const uint32_t d0 = first_entry(cta, FIRST_LO, FIRST_HI);
  const int wi = wg * 4 + warp;
  asm volatile(ELECT "prefetch.tensormap [%0];\n}" ::"l"(&P.x[0][0] + wi) : "memory");
  if ((sbase & 0xffffff) != SB0) __trap();
  if (wg < 2) {
    asm volatile(ELECT "mbarrier.init.shared::cta.b64 [%0], 1;\n}" ::"r"(sbase + BAR_FULL + wi * 8) : "memory");
    if (PAIR && (wi == 1 || wi == 4)) {
      fence_async_smem();
      tma_ld3_w(sbase + wi * SLOT, P.wq, 0, (wi / 3) * 64, (d0 & 31) * 2, sbase + BAR_FULL + wi * 8, 16384);
      if (wi == 1) TTAIL(8);
    }
#pragma unroll 1
    for (int b = BAR_OFF + 64 + wi * 8; b < DESC_OFF; b += 64)
      asm volatile(ELECT "mbarrier.init.shared::cta.b64 [%0], %1;\n}"
                   ::"r"(sbase + b), "r"(b < BAR_EMPTY || b >= BAR_DESC ? 1 : b >= BAR_STG && b < BAR_OUT ? 4 : 8) : "memory");
    asm volatile("fence.mbarrier_init.release.cluster;" ::: "memory");
    if (wi < 6) asm volatile(ELECT "prefetch.tensormap [%0];\n}" ::"l"(&P.x[0][0] + 12 + wi) : "memory");
  }
  if (PAIR) asm volatile("barrier.cluster.arrive.relaxed.aligned;" ::: "memory"); else __syncthreads();
#define INIT_DONE() if (PAIR) asm volatile("barrier.cluster.wait.aligned;" ::: "memory")

  if (wg == 2) {
    asm volatile("setmaxnreg.dec.sync.aligned.u32 %0;" ::"n"(REG_P));
    if (warp == 1) {
      const uint32_t qb = sbase + QBUF_OFF;
      const uint32_t ep = __shfl_sync(0xffffffffu, *(volatile unsigned*)&g_epoch + 1, 0);
      asm volatile("st.volatile.shared.u32 [%0], %1;" ::"r"(sbase + EPOCH_OFF), "r"(ep) : "memory");
      INIT_DONE();
      uint32_t dc = d0, qi = 0, piece = 0, na = 0;
      TTAIL(0);
      for (int i = 0; (dc >> 30) != 2; i++) {
        if (!(dc >> 30) && o_reuse<SIMPLE>((dc >> 5) & 31)) {
          const unsigned* rd = &g_rd[0][0] + ((dc & 1023) >> 2) - OR * 8;
          for (uint32_t n = 0; !__all_sync(0xffffffffu, reached(rd, ep * 5)); __nanosleep(300)) if (++n > (1u << 22)) __trap();
        }
        mbar_wait_w(sbase + BAR_GO, i & 1);
        if (piece == 0) {
          if (PAIR && (cta & 1)) {
            asm volatile(ELECT EXPECT("%0", "4") "mbarrier.arrive.shared::cluster.b64 _, [%1];\n}" ::"r"(sbase + BAR_MAIL), "r"(peer(sbase + BAR_MAIL)) : "memory");
            mbar_wait_w(sbase + BAR_MAIL, i & 1);
            qi = lds(sbase + EPOCH_OFF + 8);
          } else if (lane == 0) {
            qi = atomicAdd(&g_next, PAIR ? 2 : 1);
            if (qi == (SIMPLE ? Q_ALL : Q_RANGES) - (PAIR ? 2 : 1)) { g_next = 0; g_epoch = ep; }
          }
          qi = __shfl_sync(0xffffffffu, qi, 0);
          if (PAIR && !(cta & 1)) {
            mbar_wait_w(sbase + BAR_MAIL, i & 1);
            asm volatile(ELECT "st.async.shared::cluster.mbarrier::complete_tx::bytes.u32 [%0], %1, [%2];\n}"
                         ::"r"(peer(sbase + EPOCH_OFF + 8)), "r"(qi + 1), "r"(peer(sbase + BAR_MAIL)) : "memory");
          }
          qi += SIMPLE ? gridDim.x : NCTA;
        }
        uint32_t d;
        if (qi < (SIMPLE ? Q_ALL : Q_RANGES)) { d = c_sched.queue[qi]; if (d & 0x8000) d ^= (1u << 30) | (63u << 16) | 0x8000; else d |= o_slot<SIMPLE>(d >> 5) << 15 | (d & 31) << 10; }
        else if (SIMPLE) d = 2u << 30;
        else { const uint32_t e = qi - Q_RANGES, g = e / 5; d = c_sched.piece[g][piece++] | (g & 1 ? g * 5 + 4 - e : e - g * 5) << 8; }
        if ((d >> 30) == 1) {
          const uint32_t k0 = (d >> 22) & 63;
          const uint32_t run = __ffs(__ballot_sync(0xffffffffu, !reached(&g_cnt[d & 31][lane & 7], ep * 4)) & (0xffu << (k0 >> 3))) - 1;
          if (run <= (k0 + ((d >> 16) & 63)) >> 3) d |= run <= (k0 + O_STEPS) >> 3 ? (2u << 30) | 128 : 128;
        }
        asm volatile("st.volatile.shared.u32 [%0], %1;" ::"r"(sbase + DESC_OFF + ((i + 1) & 3) * 4), "r"(d) : "memory");
        __syncwarp();
        mbar_arrive_warp(sbase + BAR_DESC);
        const Work w = decode(dc);
        dc = d;
        if (w.kind == 0) {
          mbar_wait_w(sbase + BAR_OUT, na++ & 1);
          TTAIL(1);
          T3(i, 0); T3(i, 1);
          asm volatile(ELECT "red.release.gpu.global.add.u32 [%0], 1;\n}" ::"l"(&g_cnt[w.beta][w.sub >> 2]) : "memory");
          T3(i, 2);
          TTAIL(2);
          continue;
        }
        const bool fin = w.mode != 1;
        const CUtensorMap* m = fin ? P.out_st : P.o_st;
        const int c1 = fin ? (w.beta & 15) * SQ : 0;
        const int c2 = fin ? (w.beta >> 4) * (DM / 64) + w.sub * 2 : NBETA * 64 + w.range * 2;
        uint32_t pend = 0;
#pragma unroll 1
        for (int e = 0; e < 4; e++) {
          const int t = (ST_ORDER >> (4 * e)) & 3;
          mbar_wait_w(sbase + BAR_STG + (t ^ (t >> 1)) * 8, (i - na) & 1);
          tma_st3_w(m + (t == 3), qb + t * 16384, c1 + t * 64, c2);
          bulk_commit();
          T2P(i + 1, 5, 2 * e);
          if (e == 3 && w.mode == 1 && (d >> 30) == 2) {
            asm volatile("cp.async.bulk.wait_group 2;" ::: "memory");
            asm volatile(ELECT "st.release.gpu.global.u32 [%0], %1;\n}" ::"l"(&g_flag[w.range]), "r"(2 * ep - 1) : "memory");
          }
          if (pend && (d >> 30) != 2) {
            bulk_wait_read<1>();
            mbar_arrive8_w(pend);
            T2P(i + 1, 5, 2 * e - 1);
          }
          pend = sbase + BAR_EMPTY + (NS + t) * 8;
          if ((ST_NOW >> e) & 1) {
            bulk_wait_read<0>();
            mbar_arrive8_w(pend);
            pend = 0;
            T2P(i + 1, 5, 2 * e + 1);
          }
        }
        if (w.beta < N_EARLY) asm volatile(ELECT "red.relaxed.gpu.global.add.u32 [%0], 1;\n}" ::"l"(&g_rd[w.beta][7]) : "memory");
        T3(i, 0);
        if (piece >= 2) TTAIL(piece * 2 - 1);
        asm volatile("cp.async.bulk.wait_group 0;" ::: "memory");
        T3(i, 1);
        if (w.mode == 1) asm volatile(ELECT "st.release.gpu.global.u32 [%0], %1;\n}" ::"l"(&g_flag[w.range]), "r"(2 * ep) : "memory");
        T3(i, 2);
        if (piece >= 2) TTAIL(piece * 2);
      }
      T3(15, 1);
    } else
    if (warp == 0) {
      Ring r{PAIR ? 3 * N_FAST : 0, 1, 3};
      uint32_t d = d0;
      for (int i = 0;; i++) {
        const Work w = decode(d);
        if (w.kind == 2) break;
        const CUtensorMap* m = w.kind == 0 ? &P.wq[w.beta >> 4] : &P.wo[w.beta >> 4];
        if (i == 0) INIT_DONE();
        for (int ks = PAIR && i == 0 ? N_FAST : 0; ks < w.nsteps; ks++) {
          const uint32_t b = borrow(ks, w.nsteps);
          r.next_if(b == 2);
          const uint32_t bar = sbase + BAR_FULL + r.slot * 8;
          mbar_wait_w(bar + (BAR_EMPTY - BAR_FULL), r.phase);
          if (w.kind == 0) tma_ld3_w(sbase + r.slot * SLOT, m, 0, ks * 64, w.sub * 2, bar, 16384);
          else tma_ld_wo_w(sbase + r.slot * SLOT, m, w.sub * 128, (w.k0 + ks) * 2, bar);
          if (w.kind != 0 && w.beta < N_EARLY && (ks & 7) == 5 && ks > 5)
            asm volatile(ELECT "red.relaxed.gpu.global.add.u32 [%0], 1;\n}" ::"l"(&g_rd[w.beta][(ks >> 3) - 1]) : "memory");
          if (ks < 10) T2P(i, 2, ks);
          if (w.kind != 0 && ks == max(w.nsteps - GO_P, 4)) mbar_arrive_warp(sbase + BAR_GO);
          r.next(); r.next_if(b == 2);
        }
        if (w.kind == 0) {
          r.phase ^= 1; r.next(); r.next();
        } else if (w.mode == 2) {
          for (int k = 1; k <= ((d >> 5) & 3); k++) {
            if (k == 1) TTAIL(9);
            bool all = false;
#pragma unroll 1
            for (int t = 0; t < 4; t++) {
              if (!(t & 1) && !all) {
                const uint32_t ep2 = 2 * lds(sbase + EPOCH_OFF);
                uint32_t v, n = 0;
                do {
                  asm volatile("ld.acquire.gpu.global.u32 %0, [%1];" : "=r"(v) : "l"(&g_flag[w.range + 5 * k]) : "memory");
                  v = __shfl_sync(0xffffffffu, v - ep2, 0);
                  if (++n > (1u << 24)) __trap();
                } while ((int)v < (t >> 1) - 1);
                all = v == 0;
                TTAIL(10);
                asm volatile("fence.proxy.async.global;" ::: "memory");
              }
              mbar_wait_w(sbase + BAR_EMPTY + r.slot * 8, r.phase);
              tma_ld3_w(sbase + r.slot * SLOT, &P.o_st[t == 3], 0, t * 64, NBETA * 64 + (w.range + 5 * k) * 2, sbase + BAR_FULL + r.slot * 8,
                        t == 3 ? 8192 : 16384);
              r.next();
            }
          }
        }
        mbar_wait_w(sbase + BAR_DESC, i & 1);
        d = __shfl_sync(0xffffffffu, lds(sbase + DESC_OFF + ((i + 1) & 3) * 4), 0);
      }
    } else {
      const int hi = warp - 2;
      uint64_t pol_stream;
      uint32_t rdy = 0;
      asm volatile("createpolicy.fractional.L2::evict_first.b64 %0, 1.0;" : "=l"(pol_stream));
      Ring r{PAIR ? 3 * N_FAST : 0, 1, 3};
      uint32_t d = d0;
      for (int i = 0;; i++) {
        const Work w = decode(d);
        if (w.kind == 2) break;
        const CUtensorMap* m = w.kind == 0 ? &P.x[hi][w.beta >> 4] : &P.o_ld[hi];
        int c1 = (w.kind == 0 ? (w.beta & 15) : o_slot<SIMPLE>(w.beta) * 64 + w.k0) * SQ + hi * 128;
        int k_wait = -1;
        const bool both = PAIR && (w.kind == 0 || w.sub != 4), mine = !both || hi == (cta & 1);
        if (w.kind != 0 && mine) {
          if (d & 128) k_wait = d >= (3u << 30) ? 0 : 8 - (w.k0 & 7);
          asm volatile("fence.proxy.async.global;" ::: "memory");
        }
        if (i == 0) INIT_DONE();
        for (int ks = PAIR && i == 0 ? N_FAST : 0; ks < w.nsteps; ks++) {
          if (ks == k_wait) {
            wait_count(&g_cnt[d & 31][(w.k0 + ks) >> 3], lds(sbase + EPOCH_OFF) * 4);
            asm volatile("fence.proxy.async.global;" ::: "memory");
            k_wait = ((w.k0 + ks) | 7) + 1 - w.k0;
          }
          const uint32_t b = borrow(ks, w.nsteps);
          const bool bo = b != 2;
          r.next_if(hi && !bo); r.next_if(hi && !bo);
          const uint32_t sl = bo ? NS + (b ^ (3 * hi)) : r.slot, bar = sbase + BAR_FULL + sl * 8;
          mbar_wait_w(bar + (BAR_EMPTY - BAR_FULL), bo ? (r.xp >> b) & 1 : r.phase);
          const uint32_t bytes = hi ? 96 * 128 : 128 * 128;
          const bool used = i > 0 || ks > 4;
          if (!mine) {
            asm volatile(ELECT "mbarrier.arrive.expect_tx.shared::cta.b64 _, [%0], %1;\n}" ::"r"(bar), "r"(bytes) : "memory");
            if (used) asm volatile(ELECT "mbarrier.arrive.shared::cluster.b64 _, [%0];\n}" ::"r"(peer(bar + (BAR_RDY - BAR_FULL))) : "memory");
          } else if (both) {
            if (used) {
              mbar_wait_w(bar + (BAR_RDY - BAR_FULL), (rdy >> sl) & 1);
              rdy ^= 1 << sl;
            }
            if (w.kind == 0) tma_ld2_both_w(sbase + sl * SLOT, m, ks * 64, c1, bar, bytes);
            else tma_ld2_both_hint_w(sbase + sl * SLOT, m, 0, c1, bar, bytes, pol_stream);
          } else if (!PAIR && w.kind == 0) tma_ld2_w(sbase + sl * SLOT, m, ks * 64, c1, bar, bytes);
          else tma_ld2_hint_w(sbase + sl * SLOT, m, 0, c1, bar, bytes, pol_stream);
          if (w.kind != 0) c1 += SQ;
          if (i == 0 && ks == PF_STEP)
            asm volatile(ELECT "cp.async.bulk.prefetch.tensor.4d.L2.global.L2::cache_hint [%0, {0, 0, 0, %1}], %2;\n}"
                         ::"l"(&P.kv[hi][0]), "r"(d * (SK / 8)), "l"(pol_stream) : "memory");
          if (ks < 10) T2P(i, 3 + hi, ks);
          if (!hi && w.kind != 0 && !(ks & 3)) TCLK(i * 16 + (ks >> 2));
          r.next(); r.next_if(!hi && !bo); r.next_if(!hi && !bo);
          r.xp ^= 1 << b;
        }
        r.xp ^= 3;
        if (w.kind == 0) {
          m = &P.kv[hi][w.beta >> 4];
          c1 = (d & 511) * (SK / 8);
          for (int j = 0; j < 16; j++) {
            if (hi) r.next();
            const uint32_t bar = sbase + BAR_FULL + r.slot * 8;
            const bool tight = i == 0 && j < KV_WIN_TILES + ((KV_WIN_RAMP * cta) >> 5);
            {
              const int s2 = (int)r.slot - (tight ? 2 : KV_WIN_D);
              mbar_wait_w(sbase + BAR_FULL + (s2 < 0 ? s2 + NS : s2) * 8, s2 < 0 ? r.phase : r.phase ^ 1);
            }
            if (j == 15 && hi) mbar_wait_w(sbase + BAR_DESC, i & 1);
            mbar_wait_w(sbase + BAR_EMPTY + r.slot * 8, r.phase);
            tma_ld_kv_w(sbase + r.slot * SLOT, m, c1, bar, pol_stream);
            T2P(i, 3 + hi, 16 + j);
            if (!hi) TCLK(i * 16 + j);
            if (j == GO_J && !hi) mbar_arrive_warp(sbase + BAR_GO);
            c1 += 8;
            r.next();
            if (!hi) r.next();
          }
        }
        mbar_wait_w(sbase + BAR_DESC, i & 1);
        d = __shfl_sync(0xffffffffu, lds(sbase + DESC_OFF + ((i + 1) & 3) * 4), 0);
      }
    }
  } else {
    Ctx c;
    c.sb = sbase; c.wg = wg; c.warp = warp; c.src = 0; c.mqk = 0; c.mpv = 0; c.lead = lane == 0; c.lane0 = c.lane = lane;
    INIT_DONE();
    if (PAIR && wi < 2 * N_FAST) {
      const uint32_t t = wi & 1, sl = (wi >> 1) * 3 + t * 2, bar = sbase + BAR_FULL + sl * 8, bytes = t ? 96 * 128 : 128 * 128;
      if (t == (cta & 1)) tma_ld2_both_w(sbase + sl * SLOT, &P.x[t][0], (wi >> 1) * 64, (d0 >> 5) * SQ + t * 128, bar, bytes);
      else asm volatile(ELECT "mbarrier.arrive.expect_tx.shared::cta.b64 _, [%0], %1;\n}" ::"r"(bar), "r"(bytes) : "memory");
    }
    if (wg == 0) consumer<0>(c, P.kp); else consumer<1>(c, P.kp);
  }
}

typedef CUresult (*EncodeFn)(CUtensorMap*, CUtensorMapDataType, cuuint32_t, void*, const cuuint64_t*, const cuuint64_t*,
                             const cuuint32_t*, const cuuint32_t*, CUtensorMapInterleave, CUtensorMapSwizzle,
                             CUtensorMapL2promotion, CUtensorMapFloatOOBfill);

void make_map(EncodeFn enc, CUtensorMap* m, const void* ptr, int rank, const cuuint64_t* dims, const cuuint64_t* strides,
              const cuuint32_t* box, CUtensorMapSwizzle swz = CU_TENSOR_MAP_SWIZZLE_128B) {
  cuuint32_t es[5] = {1, 1, 1, 1, 1};
  enc(m, CU_TENSOR_MAP_DATA_TYPE_BFLOAT16, rank, const_cast<void*>(ptr), dims, strides, box, es,
      CU_TENSOR_MAP_INTERLEAVE_NONE, swz, CU_TENSOR_MAP_L2_PROMOTION_NONE,
      CU_TENSOR_MAP_FLOAT_OOB_FILL_NONE);
}

}

extern "C" void kernel_launch(void* const* d_in, const int* in_sizes, int n_in, void* d_out, int out_size) {
  (void)in_sizes; (void)n_in; (void)out_size;
  static EncodeFn enc = nullptr;
  static void* o_ptr = nullptr;
  static int n_sm = 0;
  cudaLaunchAttribute at;
  at.id = cudaLaunchAttributeClusterDimension;
  at.val.clusterDim.x = 2; at.val.clusterDim.y = 1; at.val.clusterDim.z = 1;
  cudaLaunchConfig_t cfg = {};
  cfg.gridDim = dim3(NCTA); cfg.blockDim = dim3(384); cfg.dynamicSmemBytes = SMEM_BYTES; cfg.attrs = &at; cfg.numAttrs = 1;
  if (!enc) {
    void* fn = nullptr;
    cudaDriverEntryPointQueryResult qr;
    cudaGetDriverEntryPoint("cuTensorMapEncodeTiled", &fn, cudaEnableDefault, &qr);
    enc = (EncodeFn)fn;
    cudaGetSymbolAddress(&o_ptr, g_o);
    cudaFuncSetAttribute(mha_fused_kernel<false>, cudaFuncAttributeMaxDynamicSharedMemorySize, SMEM_BYTES);
    cudaFuncSetAttribute(mha_fused_kernel<true>, cudaFuncAttributeMaxDynamicSharedMemorySize, SMEM_BYTES);
    int dev = 0;
    cudaGetDevice(&dev);
    cudaDeviceGetAttribute(&n_sm, cudaDevAttrMultiProcessorCount, dev);
    int n_cl = 0;
    cudaOccupancyMaxActiveClusters(&n_cl, mha_fused_kernel<false>, &cfg);
    if (n_cl * 2 < NCTA && n_sm >= NCTA) n_sm = NCTA - 1;
  }
  Params P;
  for (int br = 0; br < 2; br++) {
    const void* x = d_in[br * 5 + 0]; const void* kc = d_in[br * 5 + 1]; const void* vc = d_in[br * 5 + 2];
    const void* wq = d_in[br * 5 + 3]; const void* wo = d_in[br * 5 + 4];
    { cuuint64_t d[2] = {DM, (cuuint64_t)NB * SQ}, s[1] = {DM * 2}; cuuint32_t b[2] = {64, 128}, b2[2] = {64, 96};
      make_map(enc, &P.x[0][br], x, 2, d, s, b); make_map(enc, &P.x[1][br], x, 2, d, s, b2); }
    { cuuint64_t d[3] = {64, DM, HD / 64}, s[2] = {HD * 2, 128}; cuuint32_t b[3] = {64, 64, 2}; make_map(enc, &P.wq[br], wq, 3, d, s, b); }
    { cuuint64_t d[5] = {DM, 2, 4, 4, HD / 32}, s[4] = {DM * 2, 8 * DM * 2, 2 * DM * 2, 32 * DM * 2}; cuuint32_t b[5] = {64, 2, 4, 4, 2};
      make_map(enc, &P.wo[br], wo, 5, d, s, b); }
    { cuuint64_t d[4] = {64, 8, 2, (cuuint64_t)NB * NH * SK / 8}, s[3] = {DH * 2, 128, DH * 16}; cuuint32_t b[4] = {64, 8, 2, 8};
      make_map(enc, &P.kv[0][br], kc, 4, d, s, b); make_map(enc, &P.kv[1][br], vc, 4, d, s, b); }
    P.kp[br] = (const __nv_bfloat16*)kc; P.vp[br] = (const __nv_bfloat16*)vc;

  }
  { cuuint64_t d[2] = {64, (cuuint64_t)NBETA * 64 * SQ}, s[1] = {128}; cuuint32_t b[2] = {64, 128}, b2[2] = {64, 96};
    make_map(enc, &P.o_ld[0], o_ptr, 2, d, s, b, CU_TENSOR_MAP_SWIZZLE_NONE); make_map(enc, &P.o_ld[1], o_ptr, 2, d, s, b2, CU_TENSOR_MAP_SWIZZLE_NONE); }
  { cuuint64_t d[3] = {64, SQ, O_BLOCKS}, s[2] = {128, SQ * 128}; cuuint32_t b[3] = {64, 64, 2}, b2[3] = {64, 32, 2};
    make_map(enc, &P.o_st[0], o_ptr, 3, d, s, b); make_map(enc, &P.o_st[1], o_ptr, 3, d, s, b2); }
  { cuuint64_t d[3] = {64, (cuuint64_t)NB * SQ, 2 * DM / 64}, s[2] = {2 * DM * 2, 128}; cuuint32_t b[3] = {64, 64, 2}, b2[3] = {64, 32, 2};
    make_map(enc, &P.out_st[0], d_out, 3, d, s, b); make_map(enc, &P.out_st[1], d_out, 3, d, s, b2); }
  if (n_sm >= NCTA) cudaLaunchKernelEx(&cfg, mha_fused_kernel<false>, P);
  else mha_fused_kernel<true><<<n_sm, 384, SMEM_BYTES>>>(P);
}
```

```cpp
#include <cuda_runtime.h>
#include <cuda_bf16.h>
#include <cuda.h>
#include <stdint.h>
#include <stdlib.h>

namespace {

__device__ __forceinline__ void wgmma_proj(float (&d)[64], uint64_t da, uint64_t db, int scaleD) {
  asm volatile("{\n.reg .pred p;\nsetp.ne.b32 p, %66, 0;\n"
      "wgmma.mma_async.sync.aligned.m64n128k16.f32.bf16.bf16 "
      "{%0, %1, %2, %3, %4, %5, %6, %7, %8, %9, %10, %11, %12, %13, %14, %15, %16, %17, %18, %19, %20, %21, %22, %23, %24, %25, %26, %27, %28, %29, %30, "
      "%31, %32, %33, %34, %35, %36, %37, %38, %39, %40, %41, %42, %43, %44, %45, %46, %47, %48, %49, %50, %51, %52, %53, %54, %55, %56, %57, %58, %59, %60, "
      "%61, %62, %63}, "
      "%64, %65, p, 1, 1, 0, 1;\n}\n"
      : "+f"(d[0]), "+f"(d[1]), "+f"(d[2]), "+f"(d[3]), "+f"(d[4]), "+f"(d[5]), "+f"(d[6]), "+f"(d[7]), "+f"(d[8]), "+f"(d[9]), "+f"(d[10]), "+f"(d[11]),
        "+f"(d[12]), "+f"(d[13]), "+f"(d[14]), "+f"(d[15]), "+f"(d[16]), "+f"(d[17]), "+f"(d[18]), "+f"(d[19]), "+f"(d[20]), "+f"(d[21]), "+f"(d[22]),
        "+f"(d[23]), "+f"(d[24]), "+f"(d[25]), "+f"(d[26]), "+f"(d[27]), "+f"(d[28]), "+f"(d[29]), "+f"(d[30]), "+f"(d[31]), "+f"(d[32]), "+f"(d[33]),
        "+f"(d[34]), "+f"(d[35]), "+f"(d[36]), "+f"(d[37]), "+f"(d[38]), "+f"(d[39]), "+f"(d[40]), "+f"(d[41]), "+f"(d[42]), "+f"(d[43]), "+f"(d[44]),
        "+f"(d[45]), "+f"(d[46]), "+f"(d[47]), "+f"(d[48]), "+f"(d[49]), "+f"(d[50]), "+f"(d[51]), "+f"(d[52]), "+f"(d[53]), "+f"(d[54]), "+f"(d[55]),
        "+f"(d[56]), "+f"(d[57]), "+f"(d[58]), "+f"(d[59]), "+f"(d[60]), "+f"(d[61]), "+f"(d[62]), "+f"(d[63])
      : "l"(da), "l"(db), "r"(scaleD));
}
__device__ __forceinline__ void wgmma_proj96(float (&d)[64], uint64_t da, uint64_t db, int scaleD) {
  asm volatile("{\n.reg .pred p;\nsetp.ne.b32 p, %50, 0;\n"
      "wgmma.mma_async.sync.aligned.m64n96k16.f32.bf16.bf16 "
      "{%0, %1, %2, %3, %4, %5, %6, %7, %8, %9, %10, %11, %12, %13, %14, %15, %16, %17, %18, %19, %20, %21, %22, %23, %24, %25, %26, %27, %28, %29, %30, "
      "%31, %32, %33, %34, %35, %36, %37, %38, %39, %40, %41, %42, %43, %44, %45, %46, %47}, "
      "%48, %49, p, 1, 1, 1, 0;\n}\n"
      : "+f"(d[0]), "+f"(d[1]), "+f"(d[2]), "+f"(d[3]), "+f"(d[4]), "+f"(d[5]), "+f"(d[6]), "+f"(d[7]), "+f"(d[8]), "+f"(d[9]), "+f"(d[10]), "+f"(d[11]),
        "+f"(d[12]), "+f"(d[13]), "+f"(d[14]), "+f"(d[15]), "+f"(d[16]), "+f"(d[17]), "+f"(d[18]), "+f"(d[19]), "+f"(d[20]), "+f"(d[21]), "+f"(d[22]),
        "+f"(d[23]), "+f"(d[24]), "+f"(d[25]), "+f"(d[26]), "+f"(d[27]), "+f"(d[28]), "+f"(d[29]), "+f"(d[30]), "+f"(d[31]), "+f"(d[32]), "+f"(d[33]),
        "+f"(d[34]), "+f"(d[35]), "+f"(d[36]), "+f"(d[37]), "+f"(d[38]), "+f"(d[39]), "+f"(d[40]), "+f"(d[41]), "+f"(d[42]), "+f"(d[43]), "+f"(d[44]),
        "+f"(d[45]), "+f"(d[46]), "+f"(d[47])
      : "l"(da), "l"(db), "r"(scaleD));
}
__device__ __forceinline__ void wgmma_qk(float (&d)[32], uint64_t da, uint64_t db, int scaleD) {
  asm volatile("{\n.reg .pred p;\nsetp.ne.b32 p, %34, 0;\n"
      "wgmma.mma_async.sync.aligned.m64n64k16.f32.bf16.bf16 "
      "{%0, %1, %2, %3, %4, %5, %6, %7, %8, %9, %10, %11, %12, %13, %14, %15, %16, %17, %18, %19, %20, %21, %22, %23, %24, %25, %26, %27, %28, %29, %30, "
      "%31}, "
      "%32, %33, p, 1, 1, 0, 0;\n}\n"
      : "+f"(d[0]), "+f"(d[1]), "+f"(d[2]), "+f"(d[3]), "+f"(d[4]), "+f"(d[5]), "+f"(d[6]), "+f"(d[7]), "+f"(d[8]), "+f"(d[9]), "+f"(d[10]), "+f"(d[11]),
        "+f"(d[12]), "+f"(d[13]), "+f"(d[14]), "+f"(d[15]), "+f"(d[16]), "+f"(d[17]), "+f"(d[18]), "+f"(d[19]), "+f"(d[20]), "+f"(d[21]), "+f"(d[22]),
        "+f"(d[23]), "+f"(d[24]), "+f"(d[25]), "+f"(d[26]), "+f"(d[27]), "+f"(d[28]), "+f"(d[29]), "+f"(d[30]), "+f"(d[31])
      : "l"(da), "l"(db), "r"(scaleD));
}
__device__ __forceinline__ void wgmma_qk_rs(float (&d)[32], uint32_t a0, uint32_t a1, uint32_t a2, uint32_t a3, uint64_t db, int scaleD) {
  asm volatile("{\n.reg .pred p;\nsetp.ne.b32 p, %37, 0;\n"
      "wgmma.mma_async.sync.aligned.m64n64k16.f32.bf16.bf16 "
      "{%0, %1, %2, %3, %4, %5, %6, %7, %8, %9, %10, %11, %12, %13, %14, %15, %16, %17, %18, %19, %20, %21, %22, %23, %24, %25, %26, %27, %28, %29, %30, "
      "%31}, "
      "{%32, %33, %34, %35}, %36, p, 1, 1, 0;\n}\n"
      : "+f"(d[0]), "+f"(d[1]), "+f"(d[2]), "+f"(d[3]), "+f"(d[4]), "+f"(d[5]), "+f"(d[6]), "+f"(d[7]), "+f"(d[8]), "+f"(d[9]), "+f"(d[10]), "+f"(d[11]),
        "+f"(d[12]), "+f"(d[13]), "+f"(d[14]), "+f"(d[15]), "+f"(d[16]), "+f"(d[17]), "+f"(d[18]), "+f"(d[19]), "+f"(d[20]), "+f"(d[21]), "+f"(d[22]),
        "+f"(d[23]), "+f"(d[24]), "+f"(d[25]), "+f"(d[26]), "+f"(d[27]), "+f"(d[28]), "+f"(d[29]), "+f"(d[30]), "+f"(d[31])
      : "r"(a0), "r"(a1), "r"(a2), "r"(a3), "l"(db), "r"(scaleD));
}
__device__ __forceinline__ void wgmma_pv(float (&d)[64], uint32_t a0, uint32_t a1, uint32_t a2, uint32_t a3, uint64_t db, int scaleD) {
  asm volatile("{\n.reg .pred p;\nsetp.ne.b32 p, %69, 0;\n"
      "wgmma.mma_async.sync.aligned.m64n128k16.f32.bf16.bf16 "
      "{%0, %1, %2, %3, %4, %5, %6, %7, %8, %9, %10, %11, %12, %13, %14, %15, %16, %17, %18, %19, %20, %21, %22, %23, %24, %25, %26, %27, %28, %29, %30, "
      "%31, %32, %33, %34, %35, %36, %37, %38, %39, %40, %41, %42, %43, %44, %45, %46, %47, %48, %49, %50, %51, %52, %53, %54, %55, %56, %57, %58, %59, %60, "
      "%61, %62, %63}, "
      "{%64, %65, %66, %67}, %68, p, 1, 1, 1;\n}\n"
      : "+f"(d[0]), "+f"(d[1]), "+f"(d[2]), "+f"(d[3]), "+f"(d[4]), "+f"(d[5]), "+f"(d[6]), "+f"(d[7]), "+f"(d[8]), "+f"(d[9]), "+f"(d[10]), "+f"(d[11]),
        "+f"(d[12]), "+f"(d[13]), "+f"(d[14]), "+f"(d[15]), "+f"(d[16]), "+f"(d[17]), "+f"(d[18]), "+f"(d[19]), "+f"(d[20]), "+f"(d[21]), "+f"(d[22]),
        "+f"(d[23]), "+f"(d[24]), "+f"(d[25]), "+f"(d[26]), "+f"(d[27]), "+f"(d[28]), "+f"(d[29]), "+f"(d[30]), "+f"(d[31]), "+f"(d[32]), "+f"(d[33]),
        "+f"(d[34]), "+f"(d[35]), "+f"(d[36]), "+f"(d[37]), "+f"(d[38]), "+f"(d[39]), "+f"(d[40]), "+f"(d[41]), "+f"(d[42]), "+f"(d[43]), "+f"(d[44]),
        "+f"(d[45]), "+f"(d[46]), "+f"(d[47]), "+f"(d[48]), "+f"(d[49]), "+f"(d[50]), "+f"(d[51]), "+f"(d[52]), "+f"(d[53]), "+f"(d[54]), "+f"(d[55]),
        "+f"(d[56]), "+f"(d[57]), "+f"(d[58]), "+f"(d[59]), "+f"(d[60]), "+f"(d[61]), "+f"(d[62]), "+f"(d[63])
      : "r"(a0), "r"(a1), "r"(a2), "r"(a3), "l"(db), "r"(scaleD));
}
__device__ __forceinline__ void wgmma_qk_sp(float (&d)[32], uint32_t a0, uint32_t a1, uint32_t a2, uint32_t a3, uint64_t db, int scaleD, uint32_t meta) {
  asm volatile("{\n.reg .pred p;\nsetp.ne.b32 p, %37, 0;\n"
      "wgmma.mma_async.sp.sync.aligned.m64n64k32.f32.bf16.bf16 "
      "{%0, %1, %2, %3, %4, %5, %6, %7, %8, %9, %10, %11, %12, %13, %14, %15, %16, %17, %18, %19, %20, %21, %22, %23, %24, %25, %26, %27, %28, %29, %30, "
      "%31}, "
      "{%32, %33, %34, %35}, %36, %38, 0, p, 1, 1, 0;\n}\n"
      : "+f"(d[0]), "+f"(d[1]), "+f"(d[2]), "+f"(d[3]), "+f"(d[4]), "+f"(d[5]), "+f"(d[6]), "+f"(d[7]), "+f"(d[8]), "+f"(d[9]), "+f"(d[10]), "+f"(d[11]),
        "+f"(d[12]), "+f"(d[13]), "+f"(d[14]), "+f"(d[15]), "+f"(d[16]), "+f"(d[17]), "+f"(d[18]), "+f"(d[19]), "+f"(d[20]), "+f"(d[21]), "+f"(d[22]),
        "+f"(d[23]), "+f"(d[24]), "+f"(d[25]), "+f"(d[26]), "+f"(d[27]), "+f"(d[28]), "+f"(d[29]), "+f"(d[30]), "+f"(d[31])
      : "r"(a0), "r"(a1), "r"(a2), "r"(a3), "l"(db), "r"(scaleD), "r"(meta));
}
__device__ __forceinline__ void wgmma_pv_sp(float (&d)[64], uint32_t a0, uint32_t a1, uint32_t a2, uint32_t a3, uint64_t db, int scaleD, uint32_t meta) {
  asm volatile("{\n.reg .pred p;\nsetp.ne.b32 p, %69, 0;\n"
      "wgmma.mma_async.sp.sync.aligned.m64n128k32.f32.bf16.bf16 "
      "{%0, %1, %2, %3, %4, %5, %6, %7, %8, %9, %10, %11, %12, %13, %14, %15, %16, %17, %18, %19, %20, %21, %22, %23, %24, %25, %26, %27, %28, %29, %30, "
      "%31, %32, %33, %34, %35, %36, %37, %38, %39, %40, %41, %42, %43, %44, %45, %46, %47, %48, %49, %50, %51, %52, %53, %54, %55, %56, %57, %58, %59, %60, "
      "%61, %62, %63}, "
      "{%64, %65, %66, %67}, %68, %70, 0, p, 1, 1, 1;\n}\n"
      : "+f"(d[0]), "+f"(d[1]), "+f"(d[2]), "+f"(d[3]), "+f"(d[4]), "+f"(d[5]), "+f"(d[6]), "+f"(d[7]), "+f"(d[8]), "+f"(d[9]), "+f"(d[10]), "+f"(d[11]),
        "+f"(d[12]), "+f"(d[13]), "+f"(d[14]), "+f"(d[15]), "+f"(d[16]), "+f"(d[17]), "+f"(d[18]), "+f"(d[19]), "+f"(d[20]), "+f"(d[21]), "+f"(d[22]),
        "+f"(d[23]), "+f"(d[24]), "+f"(d[25]), "+f"(d[26]), "+f"(d[27]), "+f"(d[28]), "+f"(d[29]), "+f"(d[30]), "+f"(d[31]), "+f"(d[32]), "+f"(d[33]),
        "+f"(d[34]), "+f"(d[35]), "+f"(d[36]), "+f"(d[37]), "+f"(d[38]), "+f"(d[39]), "+f"(d[40]), "+f"(d[41]), "+f"(d[42]), "+f"(d[43]), "+f"(d[44]),
        "+f"(d[45]), "+f"(d[46]), "+f"(d[47]), "+f"(d[48]), "+f"(d[49]), "+f"(d[50]), "+f"(d[51]), "+f"(d[52]), "+f"(d[53]), "+f"(d[54]), "+f"(d[55]),
        "+f"(d[56]), "+f"(d[57]), "+f"(d[58]), "+f"(d[59]), "+f"(d[60]), "+f"(d[61]), "+f"(d[62]), "+f"(d[63])
      : "r"(a0), "r"(a1), "r"(a2), "r"(a3), "l"(db), "r"(scaleD), "r"(meta));
}
__device__ __forceinline__ void wgmma_proj_init(float (&d)[64], uint64_t da, uint64_t db, int scaleD) {
  asm volatile("{\n.reg .pred p;\nsetp.ne.b32 p, %66, 0;\n"
      "wgmma.mma_async.sync.aligned.m64n128k16.f32.bf16.bf16 "
      "{%0, %1, %2, %3, %4, %5, %6, %7, %8, %9, %10, %11, %12, %13, %14, %15, %16, %17, %18, %19, %20, %21, %22, %23, %24, %25, %26, %27, %28, %29, %30, "
      "%31, %32, %33, %34, %35, %36, %37, %38, %39, %40, %41, %42, %43, %44, %45, %46, %47, %48, %49, %50, %51, %52, %53, %54, %55, %56, %57, %58, %59, %60, "
      "%61, %62, %63}, "
      "%64, %65, p, 1, 1, 0, 1;\n}\n"
      : "=f"(d[0]), "=f"(d[1]), "=f"(d[2]), "=f"(d[3]), "=f"(d[4]), "=f"(d[5]), "=f"(d[6]), "=f"(d[7]), "=f"(d[8]), "=f"(d[9]), "=f"(d[10]), "=f"(d[11]),
        "=f"(d[12]), "=f"(d[13]), "=f"(d[14]), "=f"(d[15]), "=f"(d[16]), "=f"(d[17]), "=f"(d[18]), "=f"(d[19]), "=f"(d[20]), "=f"(d[21]), "=f"(d[22]),
        "=f"(d[23]), "=f"(d[24]), "=f"(d[25]), "=f"(d[26]), "=f"(d[27]), "=f"(d[28]), "=f"(d[29]), "=f"(d[30]), "=f"(d[31]), "=f"(d[32]), "=f"(d[33]),
        "=f"(d[34]), "=f"(d[35]), "=f"(d[36]), "=f"(d[37]), "=f"(d[38]), "=f"(d[39]), "=f"(d[40]), "=f"(d[41]), "=f"(d[42]), "=f"(d[43]), "=f"(d[44]),
        "=f"(d[45]), "=f"(d[46]), "=f"(d[47]), "=f"(d[48]), "=f"(d[49]), "=f"(d[50]), "=f"(d[51]), "=f"(d[52]), "=f"(d[53]), "=f"(d[54]), "=f"(d[55]),
        "=f"(d[56]), "=f"(d[57]), "=f"(d[58]), "=f"(d[59]), "=f"(d[60]), "=f"(d[61]), "=f"(d[62]), "=f"(d[63])
      : "l"(da), "l"(db), "r"(scaleD));
}
__device__ __forceinline__ void wgmma_proj96_init(float (&d)[64], uint64_t da, uint64_t db, int scaleD) {
  asm volatile("{\n.reg .pred p;\nsetp.ne.b32 p, %50, 0;\n"
      "wgmma.mma_async.sync.aligned.m64n96k16.f32.bf16.bf16 "
      "{%0, %1, %2, %3, %4, %5, %6, %7, %8, %9, %10, %11, %12, %13, %14, %15, %16, %17, %18, %19, %20, %21, %22, %23, %24, %25, %26, %27, %28, %29, %30, "
      "%31, %32, %33, %34, %35, %36, %37, %38, %39, %40, %41, %42, %43, %44, %45, %46, %47}, "
      "%48, %49, p, 1, 1, 1, 0;\n}\n"
      : "=f"(d[0]), "=f"(d[1]), "=f"(d[2]), "=f"(d[3]), "=f"(d[4]), "=f"(d[5]), "=f"(d[6]), "=f"(d[7]), "=f"(d[8]), "=f"(d[9]), "=f"(d[10]), "=f"(d[11]),
        "=f"(d[12]), "=f"(d[13]), "=f"(d[14]), "=f"(d[15]), "=f"(d[16]), "=f"(d[17]), "=f"(d[18]), "=f"(d[19]), "=f"(d[20]), "=f"(d[21]), "=f"(d[22]),
        "=f"(d[23]), "=f"(d[24]), "=f"(d[25]), "=f"(d[26]), "=f"(d[27]), "=f"(d[28]), "=f"(d[29]), "=f"(d[30]), "=f"(d[31]), "=f"(d[32]), "=f"(d[33]),
        "=f"(d[34]), "=f"(d[35]), "=f"(d[36]), "=f"(d[37]), "=f"(d[38]), "=f"(d[39]), "=f"(d[40]), "=f"(d[41]), "=f"(d[42]), "=f"(d[43]), "=f"(d[44]),
        "=f"(d[45]), "=f"(d[46]), "=f"(d[47])
      : "l"(da), "l"(db), "r"(scaleD));
}
__device__ __forceinline__ void wgmma_qk_init(float (&d)[32], uint64_t da, uint64_t db, int scaleD) {
  asm volatile("{\n.reg .pred p;\nsetp.ne.b32 p, %34, 0;\n"
      "wgmma.mma_async.sync.aligned.m64n64k16.f32.bf16.bf16 "
      "{%0, %1, %2, %3, %4, %5, %6, %7, %8, %9, %10, %11, %12, %13, %14, %15, %16, %17, %18, %19, %20, %21, %22, %23, %24, %25, %26, %27, %28, %29, %30, "
      "%31}, "
      "%32, %33, p, 1, 1, 0, 0;\n}\n"
      : "=f"(d[0]), "=f"(d[1]), "=f"(d[2]), "=f"(d[3]), "=f"(d[4]), "=f"(d[5]), "=f"(d[6]), "=f"(d[7]), "=f"(d[8]), "=f"(d[9]), "=f"(d[10]), "=f"(d[11]),
        "=f"(d[12]), "=f"(d[13]), "=f"(d[14]), "=f"(d[15]), "=f"(d[16]), "=f"(d[17]), "=f"(d[18]), "=f"(d[19]), "=f"(d[20]), "=f"(d[21]), "=f"(d[22]),
        "=f"(d[23]), "=f"(d[24]), "=f"(d[25]), "=f"(d[26]), "=f"(d[27]), "=f"(d[28]), "=f"(d[29]), "=f"(d[30]), "=f"(d[31])
      : "l"(da), "l"(db), "r"(scaleD));
}
__device__ __forceinline__ void wgmma_qk_rs_init(float (&d)[32], uint32_t a0, uint32_t a1, uint32_t a2, uint32_t a3, uint64_t db, int scaleD) {
  asm volatile("{\n.reg .pred p;\nsetp.ne.b32 p, %37, 0;\n"
      "wgmma.mma_async.sync.aligned.m64n64k16.f32.bf16.bf16 "
      "{%0, %1, %2, %3, %4, %5, %6, %7, %8, %9, %10, %11, %12, %13, %14, %15, %16, %17, %18, %19, %20, %21, %22, %23, %24, %25, %26, %27, %28, %29, %30, "
      "%31}, "
      "{%32, %33, %34, %35}, %36, p, 1, 1, 0;\n}\n"
      : "=f"(d[0]), "=f"(d[1]), "=f"(d[2]), "=f"(d[3]), "=f"(d[4]), "=f"(d[5]), "=f"(d[6]), "=f"(d[7]), "=f"(d[8]), "=f"(d[9]), "=f"(d[10]), "=f"(d[11]),
        "=f"(d[12]), "=f"(d[13]), "=f"(d[14]), "=f"(d[15]), "=f"(d[16]), "=f"(d[17]), "=f"(d[18]), "=f"(d[19]), "=f"(d[20]), "=f"(d[21]), "=f"(d[22]),
        "=f"(d[23]), "=f"(d[24]), "=f"(d[25]), "=f"(d[26]), "=f"(d[27]), "=f"(d[28]), "=f"(d[29]), "=f"(d[30]), "=f"(d[31])
      : "r"(a0), "r"(a1), "r"(a2), "r"(a3), "l"(db), "r"(scaleD));
}
__device__ __forceinline__ void wgmma_pv_init(float (&d)[64], uint32_t a0, uint32_t a1, uint32_t a2, uint32_t a3, uint64_t db, int scaleD) {
  asm volatile("{\n.reg .pred p;\nsetp.ne.b32 p, %69, 0;\n"
      "wgmma.mma_async.sync.aligned.m64n128k16.f32.bf16.bf16 "
      "{%0, %1, %2, %3, %4, %5, %6, %7, %8, %9, %10, %11, %12, %13, %14, %15, %16, %17, %18, %19, %20, %21, %22, %23, %24, %25, %26, %27, %28, %29, %30, "
      "%31, %32, %33, %34, %35, %36, %37, %38, %39, %40, %41, %42, %43, %44, %45, %46, %47, %48, %49, %50, %51, %52, %53, %54, %55, %56, %57, %58, %59, %60, "
      "%61, %62, %63}, "
      "{%64, %65, %66, %67}, %68, p, 1, 1, 1;\n}\n"
      : "=f"(d[0]), "=f"(d[1]), "=f"(d[2]), "=f"(d[3]), "=f"(d[4]), "=f"(d[5]), "=f"(d[6]), "=f"(d[7]), "=f"(d[8]), "=f"(d[9]), "=f"(d[10]), "=f"(d[11]),
        "=f"(d[12]), "=f"(d[13]), "=f"(d[14]), "=f"(d[15]), "=f"(d[16]), "=f"(d[17]), "=f"(d[18]), "=f"(d[19]), "=f"(d[20]), "=f"(d[21]), "=f"(d[22]),
        "=f"(d[23]), "=f"(d[24]), "=f"(d[25]), "=f"(d[26]), "=f"(d[27]), "=f"(d[28]), "=f"(d[29]), "=f"(d[30]), "=f"(d[31]), "=f"(d[32]), "=f"(d[33]),
        "=f"(d[34]), "=f"(d[35]), "=f"(d[36]), "=f"(d[37]), "=f"(d[38]), "=f"(d[39]), "=f"(d[40]), "=f"(d[41]), "=f"(d[42]), "=f"(d[43]), "=f"(d[44]),
        "=f"(d[45]), "=f"(d[46]), "=f"(d[47]), "=f"(d[48]), "=f"(d[49]), "=f"(d[50]), "=f"(d[51]), "=f"(d[52]), "=f"(d[53]), "=f"(d[54]), "=f"(d[55]),
        "=f"(d[56]), "=f"(d[57]), "=f"(d[58]), "=f"(d[59]), "=f"(d[60]), "=f"(d[61]), "=f"(d[62]), "=f"(d[63])
      : "r"(a0), "r"(a1), "r"(a2), "r"(a3), "l"(db), "r"(scaleD));
}
__device__ __forceinline__ void wgmma_qk_sp_init(float (&d)[32], uint32_t a0, uint32_t a1, uint32_t a2, uint32_t a3, uint64_t db, int scaleD, uint32_t meta) {
  asm volatile("{\n.reg .pred p;\nsetp.ne.b32 p, %37, 0;\n"
      "wgmma.mma_async.sp.sync.aligned.m64n64k32.f32.bf16.bf16 "
      "{%0, %1, %2, %3, %4, %5, %6, %7, %8, %9, %10, %11, %12, %13, %14, %15, %16, %17, %18, %19, %20, %21, %22, %23, %24, %25, %26, %27, %28, %29, %30, "
      "%31}, "
      "{%32, %33, %34, %35}, %36, %38, 0, p, 1, 1, 0;\n}\n"
      : "=f"(d[0]), "=f"(d[1]), "=f"(d[2]), "=f"(d[3]), "=f"(d[4]), "=f"(d[5]), "=f"(d[6]), "=f"(d[7]), "=f"(d[8]), "=f"(d[9]), "=f"(d[10]), "=f"(d[11]),
        "=f"(d[12]), "=f"(d[13]), "=f"(d[14]), "=f"(d[15]), "=f"(d[16]), "=f"(d[17]), "=f"(d[18]), "=f"(d[19]), "=f"(d[20]), "=f"(d[21]), "=f"(d[22]),
        "=f"(d[23]), "=f"(d[24]), "=f"(d[25]), "=f"(d[26]), "=f"(d[27]), "=f"(d[28]), "=f"(d[29]), "=f"(d[30]), "=f"(d[31])
      : "r"(a0), "r"(a1), "r"(a2), "r"(a3), "l"(db), "r"(scaleD), "r"(meta));
}
__device__ __forceinline__ void wgmma_pv_sp_init(float (&d)[64], uint32_t a0, uint32_t a1, uint32_t a2, uint32_t a3, uint64_t db, int scaleD, uint32_t meta) {
  asm volatile("{\n.reg .pred p;\nsetp.ne.b32 p, %69, 0;\n"
      "wgmma.mma_async.sp.sync.aligned.m64n128k32.f32.bf16.bf16 "
      "{%0, %1, %2, %3, %4, %5, %6, %7, %8, %9, %10, %11, %12, %13, %14, %15, %16, %17, %18, %19, %20, %21, %22, %23, %24, %25, %26, %27, %28, %29, %30, "
      "%31, %32, %33, %34, %35, %36, %37, %38, %39, %40, %41, %42, %43, %44, %45, %46, %47, %48, %49, %50, %51, %52, %53, %54, %55, %56, %57, %58, %59, %60, "
      "%61, %62, %63}, "
      "{%64, %65, %66, %67}, %68, %70, 0, p, 1, 1, 1;\n}\n"
      : "=f"(d[0]), "=f"(d[1]), "=f"(d[2]), "=f"(d[3]), "=f"(d[4]), "=f"(d[5]), "=f"(d[6]), "=f"(d[7]), "=f"(d[8]), "=f"(d[9]), "=f"(d[10]), "=f"(d[11]),
        "=f"(d[12]), "=f"(d[13]), "=f"(d[14]), "=f"(d[15]), "=f"(d[16]), "=f"(d[17]), "=f"(d[18]), "=f"(d[19]), "=f"(d[20]), "=f"(d[21]), "=f"(d[22]),
        "=f"(d[23]), "=f"(d[24]), "=f"(d[25]), "=f"(d[26]), "=f"(d[27]), "=f"(d[28]), "=f"(d[29]), "=f"(d[30]), "=f"(d[31]), "=f"(d[32]), "=f"(d[33]),
        "=f"(d[34]), "=f"(d[35]), "=f"(d[36]), "=f"(d[37]), "=f"(d[38]), "=f"(d[39]), "=f"(d[40]), "=f"(d[41]), "=f"(d[42]), "=f"(d[43]), "=f"(d[44]),
        "=f"(d[45]), "=f"(d[46]), "=f"(d[47]), "=f"(d[48]), "=f"(d[49]), "=f"(d[50]), "=f"(d[51]), "=f"(d[52]), "=f"(d[53]), "=f"(d[54]), "=f"(d[55]),
        "=f"(d[56]), "=f"(d[57]), "=f"(d[58]), "=f"(d[59]), "=f"(d[60]), "=f"(d[61]), "=f"(d[62]), "=f"(d[63])
      : "r"(a0), "r"(a1), "r"(a2), "r"(a3), "l"(db), "r"(scaleD), "r"(meta));
}

constexpr int NB = 16, SQ = 224, DM = 640, NH = 32, SK = 1024, DH = 128;
constexpr int HD = NH * DH;
constexpr int NBETA = 2 * NB;
constexpr int NCTA = 132;
constexpr uint32_t SB0 = 1024;
constexpr int NS = 10;
constexpr int SLOT = 16384;
constexpr int QBUF_OFF = NS * SLOT;
constexpr int NSX = NS + 4;
constexpr int BAR_OFF = NSX * SLOT;
constexpr int BAR_FULL = BAR_OFF;
constexpr int BAR_EMPTY = BAR_OFF + 8 * NSX;
constexpr int BAR_STG = BAR_OFF + 16 * NSX;
constexpr int BAR_OUT = BAR_STG + 32;
constexpr int BAR_DESC = BAR_OUT + 8;
constexpr int BAR_GO = BAR_DESC + 8;
constexpr int BAR_MAIL = BAR_GO + 8;
constexpr int BAR_RDY = BAR_MAIL + 8;
constexpr int DESC_OFF = BAR_RDY + 8 * NSX;
constexpr int EPOCH_OFF = DESC_OFF + 16;
constexpr int TRACE_OFF = EPOCH_OFF + 16;
constexpr int SMEM_BYTES = TRACE_OFF;
constexpr float SM_C = 0.08838834764831845f * 1.4426950408889634f;
constexpr float SUM_HI = 1099511627776.f, SUM_LO = 1.f / 1099511627776.f;
constexpr uint32_t META_QK = 0xEEEE4444u;
constexpr uint32_t META_PV = 0x44EEEE44u;

#define QK_EARLY_MASK 3
#define ST_ORDER 0x2310
#define LAG_BAR 2
#define ST_NOW 8
#define PF_MASK 0x3e4
#define PF_CTA 32
#define KV_WIN_D 4
#define SF 0xefbf
#define O_STEPS 4
#define KV_WIN_RAMP 4
#define PDEPTH 0
#define KV_WIN_TILES -2
#define REG_C 232
#define REG_P 24
#define GO_P 6
#define P_POS 208
#define OR 6
#define OR0 0
#define B_LATE 22
#define H_LATE 24
#define RM0 1
#define RM1 0xa7
#define RM2 0
#define PAIRB 1
#define LATE0 1
#define LATE1 2
#define GO_J 13
static_assert(GO_J >= 12);
#define LATE_G 32
constexpr int N_FAST = 2;
#define KG 5
#define PK 44
#define EARLY_MASK 0xffffu
#define PIECE_TABLE 0x501e8815,0x689d883d,0x5036b019,0x80000000,0x50345012,0x80000000,0x50244013,0x6b13403a,0x501c3811,0x695a3833,0x50321018,0x80000000,0x502b481a,0x6d4a4832,0x50128016,0x67e08035,0x50210814,0x6ccc0838,0x5012c010,0x695ac03f,0x64ec7836,0x80000000,0x64ecb830,0x80000000,0x5024c81f,0x80000000,0x5024601e,0x80000000,0x5021901d,0x80000000,0x501e7017,0x80000000,0x549b201c,0x80000000,0x67623031,0x80000000,0x67e06837,0x80000000,0x5016a81b,0x6dc8a839,0x689d0034,0x80000000,0x6999985b,0x80000000,0x695a583e,0x80000000,0x5011281c,0x80000000,0x55cea01b,0x80000000,0x6b91185c,0x80000000

struct Params {
  CUtensorMap x[2][2], wq[2], kv[2][2], wo[2];
  CUtensorMap o_ld[2], o_st[2], out_st[2];
  const __nv_bfloat16* kp[2];
  const __nv_bfloat16* vp[2];
};

constexpr int NPART = 32 * 5, O_BLOCKS = NBETA * 64 + 2 * NPART;
__device__ __align__(128) __nv_bfloat16 g_o[(size_t)O_BLOCKS * SQ * 64];
__device__ unsigned g_cnt[NBETA][8];
__device__ unsigned g_rd[NBETA][8];
__device__ unsigned g_epoch, g_next;
__device__ unsigned g_flag[NPART];

__device__ __forceinline__ uint32_t smem_u32(const void* p) { return (uint32_t)__cvta_generic_to_shared(p); }
__device__ __forceinline__ void mbar_arrive(uint32_t bar) {
  asm volatile("mbarrier.arrive.shared::cta.b64 _, [%0];" ::"r"(bar) : "memory");
}
__device__ __forceinline__ void mbar_arrive_warp(uint32_t bar) {
  asm volatile("{\n.reg .pred p;\nelect.sync _|p, 0xffffffff;\n@p mbarrier.arrive.shared::cta.b64 _, [%0];\n}" ::"r"(bar) : "memory");
}
__device__ __forceinline__ int lane_now() { int l; asm volatile("mov.u32 %0, %%laneid;" : "=r"(l)); return l; }
__device__ __forceinline__ bool mbar_try(uint32_t bar, uint32_t parity) {
  uint32_t ok;
  asm volatile("{\n.reg .pred p;\nmbarrier.try_wait.parity.shared::cta.b64 p, [%1], %2;\nselp.u32 %0, 1, 0, p;\n}"
               : "=r"(ok) : "r"(bar), "r"(parity) : "memory");
  return ok;
}
__device__ __forceinline__ bool mbar_test(uint32_t bar, uint32_t parity) {
  uint32_t ok;
  asm volatile("{\n.reg .pred p;\nmbarrier.test_wait.parity.shared::cta.b64 p, [%1], %2;\nselp.u32 %0, 1, 0, p;\n}"
               : "=r"(ok) : "r"(bar), "r"(parity) : "memory");
  return ok;
}
__device__ __forceinline__ void mbar_wait_w(uint32_t bar, uint32_t parity) {
  uint32_t n = 0;
  while (!__all_sync(0xffffffffu, mbar_try(bar, parity))) {
    if (++n > (1u << 22)) __trap();
  }
}
#define ELECT "{\n.reg .pred p;\nelect.sync _|p, 0xffffffff;\n@p "
__device__ __forceinline__ void tma_st3_w(const CUtensorMap* m, uint32_t src, int c1, int c2) {
  asm volatile(ELECT "cp.async.bulk.tensor.3d.global.shared::cta.bulk_group [%0, {0, %2, %3}], [%1];\n}"
               ::"l"(m), "r"(src), "r"(c1), "r"(c2) : "memory");
}
#define EXPECT(bar, bytes) "mbarrier.arrive.expect_tx.shared::cta.b64 _, [" bar "], " bytes ";\n@p "
__device__ __forceinline__ void tma_ld2_w(uint32_t dst, const CUtensorMap* m, int c0, int c1, uint32_t bar, uint32_t bytes) {
  asm volatile(ELECT EXPECT("%2", "%5") "cp.async.bulk.tensor.2d.shared::cluster.global.mbarrier::complete_tx::bytes [%0], [%1, {%3, %4}], [%2];\n}"
               ::"r"(dst), "l"(m), "r"(bar), "r"(c0), "r"(c1), "r"(bytes) : "memory");
}
__device__ __forceinline__ void tma_ld2_hint_w(uint32_t dst, const CUtensorMap* m, int c0, int c1, uint32_t bar, uint32_t bytes, uint64_t pol) {
  asm volatile(ELECT EXPECT("%2", "%6") "cp.async.bulk.tensor.2d.shared::cluster.global.mbarrier::complete_tx::bytes.L2::cache_hint"
               " [%0], [%1, {%3, %4}], [%2], %5;\n}"
               ::"r"(dst), "l"(m), "r"(bar), "r"(c0), "r"(c1), "l"(pol), "r"(bytes) : "memory");
}
__device__ __forceinline__ void tma_ld3_w(uint32_t dst, const CUtensorMap* m, int c0, int c1, int c2, uint32_t bar, uint32_t bytes) {
  asm volatile(ELECT EXPECT("%2", "%6") "cp.async.bulk.tensor.3d.shared::cluster.global.mbarrier::complete_tx::bytes [%0], [%1, {%3, %4, %5}], [%2];\n}"
               ::"r"(dst), "l"(m), "r"(bar), "r"(c0), "r"(c1), "r"(c2), "r"(bytes) : "memory");
}
__device__ __forceinline__ void tma_ld_kv_w(uint32_t dst, const CUtensorMap* m, int grp, uint32_t bar, uint64_t pol) {
  asm volatile(ELECT EXPECT("%2", "16384") "cp.async.bulk.tensor.4d.shared::cluster.global.mbarrier::complete_tx::bytes.L2::cache_hint"
               " [%0], [%1, {0, 0, 0, %3}], [%2], %4;\n}"
               ::"r"(dst), "l"(m), "r"(bar), "r"(grp), "l"(pol) : "memory");
}
__device__ __forceinline__ void tma_ld_wo_w(uint32_t dst, const CUtensorMap* m, int col, int grp, uint32_t bar) {
  asm volatile(ELECT EXPECT("%2", "16384") "cp.async.bulk.tensor.5d.shared::cluster.global.mbarrier::complete_tx::bytes [%0], [%1, {%3, 0, 0, 0, %4}], [%2];\n"
               "@p cp.async.bulk.tensor.5d.shared::cluster.global.mbarrier::complete_tx::bytes [%5], [%1, {%6, 0, 0, 0, %4}], [%2];\n}"
               ::"r"(dst), "l"(m), "r"(bar), "r"(col), "r"(grp), "r"(dst + 8192), "r"(col + 64) : "memory");
}
__device__ __forceinline__ void mbar_arrive8_w(uint32_t bar) {
  asm volatile(ELECT "mbarrier.arrive.shared::cta.b64 _, [%0], 8;\n}" ::"r"(bar) : "memory");
}
__device__ __forceinline__ uint32_t peer(uint32_t a) { uint32_t r; asm("mapa.shared::cluster.u32 %0, %1, %2;" : "=r"(r) : "r"(a), "r"(~blockIdx.x & 1)); return r; }
__device__ __forceinline__ void tma_ld2_both_w(uint32_t dst, const CUtensorMap* m, int c0, int c1, uint32_t bar, uint32_t bytes) {
  asm volatile(ELECT EXPECT("%2", "%5") "cp.async.bulk.tensor.2d.shared::cluster.global.mbarrier::complete_tx::bytes.multicast::cluster"
               " [%0], [%1, {%3, %4}], [%2], %6;\n}"
               ::"r"(dst), "l"(m), "r"(bar), "r"(c0), "r"(c1), "r"(bytes), "h"((uint16_t)3) : "memory");
}
__device__ __forceinline__ void tma_ld2_both_hint_w(uint32_t dst, const CUtensorMap* m, int c0, int c1, uint32_t bar, uint32_t bytes, uint64_t pol) {
  asm volatile(ELECT EXPECT("%2", "%6") "cp.async.bulk.tensor.2d.shared::cluster.global.mbarrier::complete_tx::bytes.multicast::cluster.L2::cache_hint"
               " [%0], [%1, {%3, %4}], [%2], %7, %5;\n}"
               ::"r"(dst), "l"(m), "r"(bar), "r"(c0), "r"(c1), "l"(pol), "r"(bytes), "h"((uint16_t)3) : "memory");
}
__device__ __forceinline__ void bulk_commit() { asm volatile("cp.async.bulk.commit_group;" ::: "memory"); }
template <int N> __device__ __forceinline__ void bulk_wait_read() { asm volatile("cp.async.bulk.wait_group.read %0;" ::"n"(N) : "memory"); }
__device__ __forceinline__ void wg_fence() { asm volatile("wgmma.fence.sync.aligned;" ::: "memory"); }
__device__ __forceinline__ void wg_commit() { asm volatile("wgmma.commit_group.sync.aligned;" ::: "memory"); }
template <int N> __device__ __forceinline__ void wg_wait() { asm volatile("wgmma.wait_group.sync.aligned %0;" ::"n"(N) : "memory"); }
__device__ __forceinline__ void fence_async_smem() { asm volatile("fence.proxy.async.shared::cta;" ::: "memory"); }
__device__ __forceinline__ void bar_sync(int id, int n) { asm volatile("bar.sync %0, %1;" ::"r"(id), "r"(n) : "memory"); }
__device__ __forceinline__ void touch(float& a) { asm volatile("neg.f32 %0, %0;" : "+f"(a)); }
__device__ __forceinline__ void touch(uint32_t& a) { asm volatile("not.b32 %0, %0;" : "+r"(a)); }
template <typename T, int N> __device__ __forceinline__ void touch(T (&a)[N]) {
#pragma unroll
  for (int i = 0; i < N; i++) touch(a[i]);
}
template <int ID, typename... A> __device__ __forceinline__ void sched_fence(uint32_t x, A&... a) {
  if (!((SF >> ID) & 1)) return;
  asm volatile("" : "+r"(x)::"memory");
#pragma unroll 1
  for (; __builtin_expect(x >= 100 + ID, 0); x >>= 1) { (touch(a), ...); __nanosleep(x); }
}
template <int N> __device__ __forceinline__ void reg_fence(float (&a)[N]) {
#pragma unroll
  for (int i = 0; i < N; i++) asm volatile("" : "+f"(a[i])::"memory");
}
template <int N> __device__ __forceinline__ void reg_fence(uint32_t (&a)[N]) {
#pragma unroll
  for (int i = 0; i < N; i++) asm volatile("" : "+r"(a[i])::"memory");
}
__device__ __forceinline__ float ex2(float x) { float y; asm("ex2.approx.ftz.f32 %0, %1;" : "=f"(y) : "f"(x)); return y; }
__device__ __forceinline__ uint32_t pack_bf16(float lo, float hi) {
  uint32_t r; asm("cvt.rn.bf16x2.f32 %0, %1, %2;" : "=r"(r) : "f"(hi), "f"(lo)); return r;
}
__device__ __forceinline__ void stsm4(uint32_t a, uint32_t r0, uint32_t r1, uint32_t r2, uint32_t r3) {
  asm volatile("stmatrix.sync.aligned.m8n8.x4.shared.b16 [%0], {%1, %2, %3, %4};" ::"r"(a), "r"(r0), "r"(r1), "r"(r2), "r"(r3) : "memory");
}
__device__ __forceinline__ void stsm4t(uint32_t a, uint32_t r0, uint32_t r1, uint32_t r2, uint32_t r3) {
  asm volatile("stmatrix.sync.aligned.m8n8.x4.trans.shared.b16 [%0], {%1, %2, %3, %4};" ::"r"(a), "r"(r0), "r"(r1), "r"(r2), "r"(r3) : "memory");
}
__device__ __forceinline__ void ldsm4(uint32_t a, uint32_t& r0, uint32_t& r1, uint32_t& r2, uint32_t& r3) {
  asm volatile("ldmatrix.sync.aligned.m8n8.x4.shared.b16 {%0, %1, %2, %3}, [%4];" : "=r"(r0), "=r"(r1), "=r"(r2), "=r"(r3) : "r"(a) : "memory");
}
__device__ __forceinline__ void mma16816(float& c0, float& c1, float& c2, float& c3, uint32_t a0, uint32_t a1, uint32_t a2, uint32_t a3,
                                         uint32_t b0, uint32_t b1) {
  asm volatile("mma.sync.aligned.m16n8k16.row.col.f32.bf16.bf16.f32 {%0, %1, %2, %3}, {%4, %5, %6, %7}, {%8, %9}, {%0, %1, %2, %3};"
               : "+f"(c0), "+f"(c1), "+f"(c2), "+f"(c3) : "r"(a0), "r"(a1), "r"(a2), "r"(a3), "r"(b0), "r"(b1));
}
__device__ __forceinline__ uint32_t sdesc(uint32_t addr, uint32_t lbo) { return (addr >> 4) + ((lbo >> 4) << 16); }
__device__ __forceinline__ uint64_t desc64(uint32_t lo, uint32_t hi) { uint64_t d; asm("mov.b64 %0, {%1, %2};" : "=l"(d) : "r"(lo), "r"(hi)); return d; }
__device__ __forceinline__ void dadd(uint64_t& d, uint32_t inc) {
  asm("{\n.reg .b32 l, h;\nmov.b64 {l, h}, %0;\nadd.u32 l, l, %1;\nmov.b64 %0, {l, h};\n}" : "+l"(d) : "r"(inc));
}

struct Ring {
  uint32_t slot, phase, xp;
  __device__ __forceinline__ void uniform() {
    slot = __shfl_sync(0xffffffffu, slot, 0); phase = __shfl_sync(0xffffffffu, phase, 0); xp = __shfl_sync(0xffffffffu, xp, 0);
  }
  __device__ __forceinline__ void next() { if (++slot == NS) { slot = 0; phase ^= 1; } }
  __device__ __forceinline__ void next_if(bool p) { slot += p; if (slot == NS) { slot = 0; phase ^= 1; } }
};
__device__ __forceinline__ uint32_t borrow(int ks, int n) {
  const int k = ks + 1;
  return k >= 4 && !(k & 2) && k < n ? k & 1 : 2;
}

constexpr uint32_t Q_RANGES = NBETA * NH + __builtin_popcount(EARLY_MASK) * 5, Q_ALL = NBETA * (NH + 5);
constexpr int NRANGE = NCTA / 5;
struct Work { int kind, mode, k0, nsteps, range, beta, sub; };
struct Sched { uint16_t queue[Q_ALL]; uint32_t piece[NRANGE + 1][4]; };
constexpr Sched make_sched() {
  Sched s{};
  int q = 0, a = 0;
  for (int t = 0, e = 0; a < NBETA * NH; t++) {
    for (; e < NBETA && 8 * (e & ~PAIRB) + PK <= t && a >= P_POS; e++)
      for (int col = 0; col < 5 && (EARLY_MASK >> e & 1); col++) s.queue[q++] = 0x8000 | (e & 1 ? 4 - col : col) << 8 | e;
    for (int b = 0; b < NBETA; b++)
      for (int h = 0; h < NH; h++)
        if ((b >= B_LATE && h >= H_LATE ? 300 + b + LATE_G * (h >> 2) : 8 * (b & ~PAIRB) + KG * (h >> 2)) == t) { s.queue[q++] = b << 5 | h; a++; }
  }
  for (int b = 0; b < NBETA; b++)
    for (int col = 0; col < 5 && !(EARLY_MASK >> b & 1); col++) s.queue[q++] = 0x8000 | col << 8 | b;
  constexpr uint32_t T[NRANGE * 2] = {PIECE_TABLE};
  for (int g = 0; g <= NRANGE; g++)
    for (int n = 0; n < 4; n++) s.piece[g][n] = g < NRANGE && n < 2 ? T[2 * g + n] : 2u << 30;
  return s;
}
__constant__ Sched c_sched = make_sched();
constexpr uint64_t first_bits(int k0) {
  const Sched s = make_sched();
  uint64_t v = 0;
  for (int k = 0; k < 10; k++) v |= (uint64_t)(s.queue[(k0 + k) * 8] >> 2) << (6 * k);
  return v;
}
__host__ __device__ constexpr uint32_t first_entry(uint32_t q, uint64_t lo, uint64_t hi) {
  return (uint32_t)((q < 80 ? lo >> (q >> 3) * 6 : hi >> ((q >> 3) - 10) * 6) & 63) * 4 + (q & 4) * 8 + (q & 3);
}
constexpr uint64_t FIRST_LO = first_bits(0), FIRST_HI = first_bits(10);
constexpr bool first_ok() {
  const Sched s = make_sched();
  for (int q = 0; q < NCTA; q++) if (first_entry(q, FIRST_LO, FIRST_HI) != s.queue[q]) return false;
  return true;
}
static_assert(first_ok());
constexpr int N_EARLY = __builtin_popcount(EARLY_MASK);
constexpr bool reuse_ok() {
  const Sched s = make_sched();
  int first[NBETA + OR] = {};
  for (int q = Q_RANGES - 1; q >= 0; q--) if (!(s.queue[q] & 0x8000)) first[s.queue[q] >> 5] = q;
  for (int q = 0; q < Q_RANGES; q++) if ((s.queue[q] & 0x8000) && (s.queue[q] & 31) >= OR0 && q - first[(s.queue[q] & 31) + OR] > NCTA - 32) return false;
  return first[OR0 + OR] >= NCTA && P_POS >= NCTA;
}
static_assert(reuse_ok());
template <bool SIMPLE> __device__ __forceinline__ bool o_reuse(uint32_t b) { return !SIMPLE && b - (OR0 + OR) < N_EARLY - OR0; }
template <bool SIMPLE> __device__ __forceinline__ uint32_t o_slot(uint32_t b) { return o_reuse<SIMPLE>(b) ? OR0 + (b - OR0) % OR : b; }
__device__ __forceinline__ Work decode(uint32_t d) {
  Work w;
  w.kind = d >> 30; if (w.kind == 3) w.kind = 1;
  w.mode = (d >> 28) & 3; w.k0 = (d >> 22) & 63;
  if (w.kind == 0) { w.beta = (d >> 5) & 31; w.sub = d & 31; w.nsteps = DM / 64; }
  else { w.beta = d & 31; w.sub = (d >> 8) & 7; w.nsteps = ((d >> 16) & 63) + 1; }
  w.range = ((d >> 11) & 31) * 5 + w.sub;
  return w;
}

__device__ __forceinline__ bool reached(const unsigned* cnt, unsigned target) {
  unsigned v;
  asm volatile("ld.acquire.gpu.global.u32 %0, [%1];" : "=r"(v) : "l"(cnt) : "memory");
  return (int)(v - target) >= 0;
}
__device__ __forceinline__ void wait_count(const unsigned* cnt, unsigned target) {
  unsigned n = 0;
  while (!__all_sync(0xffffffffu, reached(cnt, target))) { if (++n > (1u << 24)) __trap(); }
}
__device__ __forceinline__ uint32_t lds(uint32_t a) { uint32_t v; asm volatile("ld.volatile.shared.u32 %0, [%1];" : "=r"(v) : "r"(a) : "memory"); return v; }

#define TRACE(u, e)
#define T3(u, e)
#define T2C(u, e)
#define T2P(u, r, e)
#define TTAIL(k)
#define TCLK(k)
#define TO -1
#define TRACE_O(k) if (TO == k) TRACE(i, 5)
#define TRACE_P(u, e)
#define TRACE_IN(u, e)

struct Ctx {
  uint32_t sb;
  int wg, warp;
  uint32_t mqk, mpv;
  bool lead;
  int lane0, lane;
  int src;
};
template <int N> __device__ __forceinline__ uint32_t dhi(uint32_t lo) { return 0x40000040u + (lo >> (26 + N)); }
__device__ __forceinline__ void release(const Ctx& c, uint32_t slot) {
  if (c.lead) mbar_arrive(c.sb + BAR_EMPTY + slot * 8);
}
__device__ __forceinline__ uint32_t acquire(const Ctx& c, Ring& r, bool have = false) {
  const uint32_t s = r.slot;
  if (!have) mbar_wait_w(c.sb + BAR_FULL + s * 8, r.phase);
  r.next();
  return s;
}
__device__ __forceinline__ void mbar_wait2_w(uint32_t b0, uint32_t p0, uint32_t b1, uint32_t p1) {
  uint32_t n = 0;
  while (!__all_sync(0xffffffffu, mbar_try(b0, p0) & mbar_try(b1, p1))) {
    if (++n > (1u << 22)) __trap();
  }
}
__device__ __forceinline__ void mbar_wait3_w(uint32_t b0, uint32_t p0, uint32_t b1, uint32_t p1, uint32_t b2, uint32_t p2) {
  uint32_t n = 0;
  while (!__all_sync(0xffffffffu, mbar_try(b0, p0) & mbar_try(b1, p1) & mbar_try(b2, p2))) {
    if (++n > (1u << 22)) __trap();
  }
}
__device__ __forceinline__ void acquire2(const Ctx& c, Ring& r, uint32_t& s0, uint32_t& s1, bool have = false) {
  const uint32_t p0 = r.phase;
  s0 = r.slot; r.next(); s1 = r.slot;
  if (!have) mbar_wait2_w(c.sb + BAR_FULL + s0 * 8, p0, c.sb + BAR_FULL + s1 * 8, r.phase);
  r.next();
}
template <int N>
__device__ __forceinline__ bool peek(const Ctx& c, Ring r) {
  bool ok = true;
#pragma unroll
  for (int k = 0; k < N; k++) { ok &= mbar_test(c.sb + BAR_FULL + r.slot * 8, r.phase); r.next(); }
  return ok;
}
__device__ __forceinline__ void staged(const Ctx& c, int part) {
  fence_async_smem();
  __syncwarp();
  mbar_arrive_warp(c.sb + BAR_STG + c.wg * 16 + part * 8);
}

template <int WG, bool FIRST, int H>
__device__ __forceinline__ void proj_half(const Ctx& c, float (&acc)[64], uint32_t w, uint32_t x, uint32_t sw) {
  uint64_t dx = desc64((SB0 + x * SLOT + (WG ? 0 : H * 8192)) >> 4, dhi<0>(x) + sw);
  uint64_t dw = desc64(WG ? (SB0 + w * SLOT + H * 8192) >> 4 : sdesc(SB0 + w * SLOT, 8192), dhi<1>(x));
  wg_fence();
  if (WG) { if (FIRST) wgmma_proj96_init(acc, dw, dx, 0); else wgmma_proj96(acc, dw, dx, 1); }
  else { if (FIRST) wgmma_proj_init(acc, dx, dw, 0); else wgmma_proj(acc, dx, dw, 1); }
#pragma unroll
  for (int k = 1; k < 4; k++) {
    dadd(dx, k == 2 ? 2 + (sw >> 30) * 28 : 2); dadd(dw, 128);
    if (WG) wgmma_proj96(acc, dw, dx, 1); else wgmma_proj(acc, dx, dw, 1);
  }
  wg_commit();
}

__device__ __forceinline__ void proj_store16(uint32_t a, const float* f, float sc) {
  stsm4t(a, pack_bf16(f[0] * sc, f[1] * sc), pack_bf16(f[2] * sc, f[3] * sc), pack_bf16(f[4] * sc, f[5] * sc), pack_bf16(f[6] * sc, f[7] * sc));
}

__device__ __forceinline__ uint32_t stage_off(const Ctx& c) {
  const int lane = c.lane, mi = lane >> 3, r8 = lane & 7;
  return ((mi >> 1) * 8 + r8) * 128 + (((2 * c.warp + (mi & 1)) ^ r8) << 4);
}
__device__ __forceinline__ uint32_t q3_swz(uint32_t r8) { return ((r8 & 3) << 1) | (r8 >> 2); }
template <int H>
__device__ __forceinline__ void stage_t2(const Ctx& c, const float (&a)[64], float sc) {
  const uint32_t base = c.sb + QBUF_OFF + 2 * 16384 + H * 8192 + stage_off(c);
#pragma unroll
  for (int jj = 0; jj < 4; jj++) proj_store16(base + jj * 2048, &a[jj * 8], sc);
}
template <int H, bool IS_Q>
__device__ __forceinline__ void stage_t3(const Ctx& c, const float (&a)[64], float sc) {
  const uint32_t off = stage_off(c), r8 = (off >> 7) & 7;
  const uint32_t t3 = c.sb + QBUF_OFF + 3 * 16384 + H * 4096 + (IS_Q ? off ^ ((r8 ^ q3_swz(r8)) << 4) : off);
  proj_store16(t3, &a[32], sc);
  proj_store16(t3 + 2048, &a[40], sc);
}

template <int WG, int h, int NW = 4>
__device__ __forceinline__ void load_part(const Ctx& c, Ring r, uint32_t (&q)[32]) {
  uint32_t n = 0;
  while (NW && !__all_sync(0xffffffffu, peek<NW>(c, r))) {
    if (++n > (1u << 26)) __trap();
  }
  const int lane = c.lane, mi = lane >> 3, r8 = lane & 7;
  if (WG) { r.next(); r.next(); }
  const uint32_t off = c.sb + (WG ? stage_off(c) : (16 * c.warp + (mi & 1) * 8 + r8) * 128), t0 = off + r.slot * SLOT;
  r.next();
  const uint32_t t1 = off + r.slot * SLOT;
#pragma unroll
    for (int jj = 0; jj < (WG ? 6 : 8); jj++) {
      uint32_t* p = &q[4 * jj];
      if (WG) asm volatile("ldmatrix.sync.aligned.m8n8.x4.trans.shared.b16 {%0, %1, %2, %3}, [%4];" : "=r"(p[0]), "=r"(p[1]), "=r"(p[2]), "=r"(p[3])
                           : "r"((jj < 4 ? t0 + h * 8192 : t1 + h * 4096) + (jj & 3) * 2048) : "memory");
      else ldsm4((h ? t1 : t0) + (jj >> 2) * 8192 + (((((2 * jj) & 7) + (mi >> 1)) ^ r8) << 4), p[0], p[1], p[2], p[3]);
    }
}
template <int WG>
__device__ __forceinline__ void add_part(const Ctx& c, const uint32_t (&q)[32], float (&a)[64]) {
  const uint32_t one = (c.lane >> 3) == (c.lane & 3) ? 0x3f80u << (c.lane & 4) * 4 : 0;
#pragma unroll
  for (int i = 0; i < (WG ? 12 : 16); i++)
    asm("mma.sync.aligned.m16n8k8.row.col.f32.bf16.bf16.f32 {%0, %1, %2, %3}, {%4, %5}, {%6}, {%0, %1, %2, %3};"
        : "+f"(a[4 * i]), "+f"(a[4 * i + 1]), "+f"(a[4 * i + 2]), "+f"(a[4 * i + 3]) : "r"(q[2 * i]), "r"(q[2 * i + 1]), "r"(one));
}

__device__ __forceinline__ void trace_dump(const Ctx& c) {
}
struct RowSum { float l0, l1; };
__device__ __forceinline__ const char* o_addr(uint32_t item, int row, int lane) {
  return reinterpret_cast<const char*>(g_o) + (((item >> 10) * (2 * SQ) + row) * 128 + (lane ^ (lane >> 3)) * 16);
}
__device__ __forceinline__ void o_stg(const char* p, int i, const uint32_t* q) {
  asm volatile("st.global.v4.b32 [%0], {%1, %2, %3, %4};"
               ::"l"(p + (i >> 1) * (SQ * 128) + (i & 1) * 512), "r"(q[0]), "r"(q[1]), "r"(q[2]), "r"(q[3]) : "memory");
}
template <int MODE, int I0 = 0, int NI = 4>
__device__ __forceinline__ void o_emit(const char* p, const float (&o)[64], float inv) {
#pragma unroll
  for (int i = I0; i < I0 + NI; i++) {
    uint32_t q[4];
#pragma unroll
    for (int j = 0; j < 4; j++) q[j] = pack_bf16(o[16 * i + 4 * j + 2 * MODE] * inv, o[16 * i + 4 * j + 2 * MODE + 1] * inv);
    o_stg(p, i, q);
  }
}
__device__ __forceinline__ void o_done(const Ctx& c) {
  __syncwarp();
  mbar_arrive_warp(c.sb + BAR_OUT);
  __syncwarp();
}
template <int WG>
__device__ __forceinline__ void o_first(const Ctx& c, uint32_t item, float (&o)[64], const RowSum& inv, uint32_t (&q)[32]) {
  const char* p = o_addr(item, WG ? 192 + 8 * c.warp : 64 + 16 * c.warp, c.lane);
  reg_fence(o);
#pragma unroll
  for (int j = 0; j < 16; j++) {
    if (WG) q[j] = pack_bf16((o[4 * j] + o[4 * j + 2]) * inv.l0, (o[4 * j + 1] + o[4 * j + 3]) * inv.l0);
    else q[j] = pack_bf16(o[4 * j] * inv.l0, o[4 * j + 1] * inv.l0);
    if (!WG && (j & 3) == 3 && (j >> 2) < 8 - LATE0) o_stg(p, j >> 2, q + j - 3);
  }
#pragma unroll
  for (int j = 0; j < 16; j++) {
    if (!WG) q[16 + j] = pack_bf16(o[4 * j + 2] * inv.l1, o[4 * j + 3] * inv.l1);
    if ((j & 3) == 3 && (j >> 2) < 4 - (WG ? LATE1 : LATE0)) o_stg(WG ? p : p + 1024, j >> 2, q + (WG ? 0 : 16) + j - 3);
  }
}
template <int WG>
__device__ __forceinline__ void o_rest(const Ctx& c, uint32_t item, uint32_t (&q)[32]) {
  const char* p = o_addr(item, WG ? 192 + 8 * c.warp : 64 + 16 * c.warp, c.lane);
#pragma unroll
  for (int i = WG ? 4 - LATE1 : 8 - LATE0; i < (WG ? 4 : 8); i++) o_stg(p + (i >> 2) * 1024, i & 3, q + 4 * i);
}
template <int K0, int K1>
__device__ __forceinline__ void o_piece(const Ctx& c, const char* p, int k, const float (&o)[64], const RowSum& inv) {
  constexpr int NI = 8 / O_STEPS, M = K0 * NI / 4;
  if constexpr (K1 - K0 == 1) {
    o_emit<M, K0 * NI % 4, NI>(p + M * 1024, o, M ? inv.l1 : inv.l0);
    if (K1 == O_STEPS) o_done(c);
  } else {
    if (k <= (K0 + K1) / 2) o_piece<K0, (K0 + K1) / 2>(c, p, k, o, inv); else o_piece<(K0 + K1) / 2, K1>(c, p, k, o, inv);
  }
}
template <int WG>
__device__ __forceinline__ void o_second(const Ctx& c, uint32_t item, int k, float (&o)[64], const RowSum& inv) {
  reg_fence(o);
  o_piece<0, O_STEPS>(c, o_addr(item, 128 * WG + 16 * c.warp, c.lane0 + (k >> 8)), k, o, inv);
}
template <int WG>
__device__ __forceinline__ void release_q(const Ctx& c) {
#pragma unroll
  for (int t = 0; t < 2; t++)
    if (c.lead) asm volatile("mbarrier.arrive.shared::cta.b64 _, [%0], 2;" ::"r"(c.sb + BAR_EMPTY + (NS + 2 * WG + t) * 8) : "memory");
  __syncwarp();
}
struct Slots { uint32_t w, x, o, po; };
template <int WG>
__device__ __forceinline__ void acc_fence(float (&a)[64]) {
#pragma unroll
  for (int i = 0; i < (WG ? 48 : 64); i++) asm volatile("" : "+f"(a[i])::"memory");
}
template <int WG>
__device__ __forceinline__ void begin_acquire(const Ctx& c, Ring& r, Slots& h, bool wait) {
  const uint32_t s0 = r.slot, p0 = r.phase, f = c.sb + BAR_FULL;
  r.next();
  const uint32_t p1 = r.phase;
  h.w = r.slot; r.next();
  h.x = WG ? r.slot : s0; h.o = WG ? s0 : r.slot; h.po = r.phase;
  if (wait) { if (WG) mbar_wait3_w(f + s0 * 8, p0, f + h.w * 8, p1, f + h.x * 8, r.phase); else mbar_wait2_w(f + s0 * 8, p0, f + h.w * 8, p1); }
  r.next();
}
template <int WG>
__device__ __forceinline__ void proj_begin(const Ctx& c, Ring& r, float (&a0)[64], Slots& h, bool wait, uint32_t sw) {
  begin_acquire<WG>(c, r, h, wait);
  proj_half<WG, true, 0>(c, a0, h.w, h.x, sw);
  if (WG) release(c, h.o);
}
template <int WG>
__device__ __forceinline__ void proj_main(Ctx& c, Ring& r, float (&a0)[64], float (&a1)[64], Slots& h, int n, uint32_t sw, int unit,
                                          uint32_t item, int nq, float (&o1)[64], const RowSum& inv) {
  constexpr bool DEEP = (PDEPTH >> WG) & 1;
  T2C(unit, 3);
  int ks = 1;
#pragma unroll 1
  do {
    const Slots p = h;
    const uint32_t b = borrow(ks, n), tile = NS + (WG ? 3 - b : b), f = c.sb + BAR_FULL;
    const uint32_t s0 = b != 2 ? tile : r.slot, p0 = b != 2 ? (r.xp >> b) & 1 : r.phase;
    r.next_if(b == 2);
    const uint32_t p1 = r.phase;
    h.w = r.slot; r.next();
    const uint32_t s2 = b != 2 ? tile : r.slot;
    h.po = b != 2 ? p0 : r.phase;
    r.next_if(b == 2);
    r.xp ^= 1 << b;
    h.x = WG ? s2 : s0; h.o = WG ? s0 : s2;
    mbar_wait3_w(f + s0 * 8, p0, f + h.w * 8, p1, f + (WG ? s2 : p.o) * 8, WG ? h.po : p.po);
    if (ks < 10) T2C(unit, ks * 4);
    if (DEEP) {
      proj_half<WG, false, 0>(c, a0, h.w, h.x, sw);
      release(c, WG ? h.o : p.o);
      if (ks < 10) T2C(unit, ks * 4 + 1);
      wg_wait<1>();
      if (ks < 10) T2C(unit, ks * 4 + 2);
      release(c, p.x); release(c, p.w);
    } else {
      release(c, WG ? h.o : p.o);
      wg_wait<0>();
      release(c, p.x); release(c, p.w);
      if (ks < 10) T2C(unit, ks * 4 + 1);
      proj_half<WG, false, 0>(c, a0, h.w, h.x, sw);
      if (ks < 10) T2C(unit, ks * 4 + 2);
    }
    proj_half<WG, false, 1>(c, a1, h.w, h.x, sw);
    if (ks < 10) T2C(unit, ks * 4 + 3);
    if (ks <= nq) o_second<WG>(c, item, ks, o1, inv);
  } while (++ks != n);
  {
    const uint32_t e0 = c.sb + BAR_EMPTY + (NS + 3 * WG) * 8, e1 = c.sb + BAR_EMPTY + (NS + 1 + WG) * 8;
    const uint32_t p0 = (r.xp ^ unit ^ 1) & 1, p1 = ((r.xp >> 1) ^ unit ^ 1) & 1;
    const uint32_t k0 = sw ? e0 : c.sb + BAR_FULL + r.slot * 8, pk = sw ? p0 : r.phase;
    uint32_t cnt = 0;
    while (!__all_sync(0xffffffffu, mbar_try(e0, p0) & mbar_try(e1, p1) & mbar_try(k0, pk) & (WG || mbar_try(c.sb + BAR_FULL + h.o * 8, h.po)))) {
      if (++cnt > (1u << 22)) __trap();
    }
  }
  c.lane = c.lane0 + (h.w >> 5);
  if (!WG) release(c, h.o);
}
template <int WG>
__device__ __forceinline__ void proj_end(const Ctx& c, float (&a1)[64], const Slots& h) {
  wg_wait<0>();
  acc_fence<WG>(a1);
  release(c, h.x); release(c, h.w);
}
__device__ __forceinline__ uint32_t get_desc(const Ctx& c, int i) {
  uint32_t d;
  mbar_wait_w(c.sb + BAR_DESC, (i - 1) & 1);
  asm volatile("ld.volatile.shared.u32 %0, [%1];" : "=r"(d) : "r"(c.sb + DESC_OFF + (i & 3) * 4) : "memory");
  return __shfl_sync(0xffffffffu, d, 0);
}

__device__ __forceinline__ float quad_max(float x) {
  x = fmaxf(x, __shfl_xor_sync(0xffffffffu, x, 1));
  return fmaxf(x, __shfl_xor_sync(0xffffffffu, x, 2));
}
__device__ __forceinline__ float quad_sum(float x) {
  x += __shfl_xor_sync(0xffffffffu, x, 1);
  return x + __shfl_xor_sync(0xffffffffu, x, 2);
}
template <bool SP, bool FIRST>
__device__ __forceinline__ void exps(const Ctx& c, const float (&s)[32], uint32_t (&p)[SP ? 8 : 16], RowSum& st) {
  if constexpr (SP) {
    uint32_t q[8];
    float t;
#pragma unroll
    for (int j = 0; j < 8; j++) {
      const float e0 = ex2(s[4 * j] + s[4 * j + 2]), e1 = ex2(s[4 * j + 1] + s[4 * j + 3]);
      if (j == 0) t = e0 + e1; else t += e0 + e1;
      q[j] = pack_bf16(e0, e1);
    }
    const bool odd = c.src & 2;
#pragma unroll
    for (int g = 0; g < 4; g++) {
      p[2 * g] = __shfl_sync(0xffffffffu, odd ? q[2 * g + 1] : q[2 * g], c.src);
      p[2 * g + 1] = __shfl_sync(0xffffffffu, odd ? q[2 * g] : q[2 * g + 1], c.src ^ 1);
    }
    st.l0 = FIRST ? t : st.l0 + t;
  } else {
    float t0, t1;
#pragma unroll
    for (int j = 0; j < 8; j++) {
      const float e0 = ex2(s[4 * j]), e1 = ex2(s[4 * j + 1]), e2 = ex2(s[4 * j + 2]), e3 = ex2(s[4 * j + 3]);
      if (j == 0) { t0 = e0 + e1; t1 = e2 + e3; } else { t0 += e0 + e1; t1 += e2 + e3; }
      p[2 * j] = pack_bf16(e0, e1);
      p[2 * j + 1] = pack_bf16(e2, e3);
    }
    st.l0 = FIRST ? t0 : st.l0 + t0;
    st.l1 = FIRST ? t1 : st.l1 + t1;
  }
}
template <bool SP>
__device__ __forceinline__ bool finish_sums(RowSum& st) {
  const float a = quad_sum(st.l0), b = SP ? a : quad_sum(st.l1);
  st.l0 = __fdividef(1.f, a); st.l1 = __fdividef(1.f, b);
  return !(a >= SUM_LO && a <= SUM_HI && b >= SUM_LO && b <= SUM_HI);
}
template <bool SP, bool INIT, int SITE, bool COMMIT = true, int RM = 0>
__device__ __forceinline__ void issue_qk(const Ctx& c, float (&s)[32], const uint32_t (&qs)[32], uint32_t dq, uint32_t dk) {
  uint64_t a = desc64(dq, dhi<SITE & 1>(dk)), b = desc64(dk, dhi<1 - (SITE & 1)>(dk) + 64);
  if (SP) {
    if (INIT) wgmma_qk_sp_init(s, qs[0], qs[1], qs[2], qs[3], b, 0, c.mqk); else wgmma_qk_sp(s, qs[0], qs[1], qs[2], qs[3], b, 0, c.mqk);
#pragma unroll
    for (int k = 1; k < 4; k++) { dadd(b, k == 2 ? 60 : 4); wgmma_qk_sp(s, qs[4 * k], qs[4 * k + 1], qs[4 * k + 2], qs[4 * k + 3], b, 1, c.mqk); }
  } else {
    if (RM & 1) wgmma_qk_rs(s, qs[0], qs[1], qs[2], qs[3], b, 0); else if (INIT) wgmma_qk_init(s, a, b, 0); else wgmma_qk(s, a, b, 0);
#pragma unroll
    for (int k = 1; k < 8; k++) {
      dadd(a, k == 4 ? 506 : 2); dadd(b, k == 4 ? 58 : 2);
      if (RM >> k & 1) wgmma_qk_rs(s, qs[4 * k], qs[4 * k + 1], qs[4 * k + 2], qs[4 * k + 3], b, 1); else wgmma_qk(s, a, b, 1);
    }
  }
  if (COMMIT) wg_commit();
}
template <bool SP, bool ACC, int SITE, bool SPLIT = false>
__device__ __forceinline__ void issue_pv(const Ctx& c, float (&o)[64], const uint32_t (&p)[SP ? 8 : 16], uint32_t dv) {
  uint64_t b = desc64(dv, dhi<SITE & 1>(dv) + 64);
  if constexpr (SP) {
    if (ACC) wgmma_pv_sp(o, p[0], p[1], p[2], p[3], b, 1, c.mpv); else wgmma_pv_sp_init(o, p[0], p[1], p[2], p[3], b, 0, c.mpv);
    if (SPLIT) wg_commit();
    dadd(b, 512);
    wgmma_pv_sp(o, p[4], p[5], p[6], p[7], b, 1, c.mpv);
  } else {
    if (ACC) wgmma_pv(o, p[0], p[1], p[2], p[3], b, 1); else wgmma_pv_init(o, p[0], p[1], p[2], p[3], b, 0);
#pragma unroll
    for (int k = 1; k < 4; k++) { dadd(b, 256); wgmma_pv(o, p[4 * k], p[4 * k + 1], p[4 * k + 2], p[4 * k + 3], b, 1); }
  }
  wg_commit();
}
__device__ __forceinline__ void pack_rows(const float (&o)[64], float sc, uint32_t (&q)[32]) {
#pragma unroll
  for (int j = 0; j < 32; j++) q[j] = pack_bf16(o[2 * j] * sc, o[2 * j + 1] * sc);
}
template <int MASK = 255>
__device__ __forceinline__ void stage_rows(const Ctx& c, uint32_t tile_addr, const uint32_t (&q)[32]) {
  const int lane = c.lane, mi = lane >> 3, r8 = lane & 7;
  const uint32_t row_addr = tile_addr + (16 * c.warp + (mi & 1) * 8 + r8) * 128;
#pragma unroll
  for (int jj = 0; jj < 8; jj++)
    if (MASK >> jj & 1) stsm4(row_addr + (jj >> 2) * 8192 + (((((2 * jj) & 7) + (mi >> 1)) ^ r8) << 4), q[4 * jj], q[4 * jj + 1], q[4 * jj + 2], q[4 * jj + 3]);
}
__device__ __forceinline__ void stage_rows(const Ctx& c, uint32_t tile_addr, const float (&o)[64], float sc) {
  uint32_t q[32];
  pack_rows(o, sc, q);
  stage_rows(c, tile_addr, q);
}
template <int WG, int H>
__device__ __forceinline__ void stage_out(const Ctx& c, const float (&a)[64]) {
  if (WG) { stage_t3<H, false>(c, a, 1.f); if (H) staged(c, 0); stage_t2<H>(c, a, 1.f); }
  else stage_rows(c, c.sb + QBUF_OFF + H * 16384, a, 1.f);
  if (H || !WG) staged(c, H);
}
template <int SITE>
__device__ __forceinline__ void issue_qk_rs(float (&s)[32], uint32_t (&q)[32], uint32_t dk) {
  uint64_t b = desc64(dk, dhi<SITE>(dk) + 64);
  reg_fence(q);
  wg_fence();
  wgmma_qk_rs_init(s, q[0], q[1], q[2], q[3], b, 0);
#pragma unroll
  for (int k = 1; k < 8; k++) { dadd(b, k == 4 ? 58 : 2); wgmma_qk_rs(s, q[4 * k], q[4 * k + 1], q[4 * k + 2], q[4 * k + 3], b, 1); }
  wg_commit();
}

__device__ __forceinline__ void redo_tile(const Ctx& c, uint32_t q_addr, uint32_t half, const __nv_bfloat16* kp, const __nv_bfloat16* vp,
                                          uint32_t item, int row) {
  float o[64];
  const int lane = lane_now(), g = lane >> 2, cc = lane & 3, mi = lane >> 3, r8 = lane & 7;
  const uint32_t qa = q_addr + (half == 4096 ? 8 * c.warp + r8 : 16 * c.warp + (mi & 1) * 8 + r8) * 128, swz = half == 4096 ? q3_swz(r8) : r8;
  const uint32_t* kq = reinterpret_cast<const uint32_t*>(kp + g * DH) + cc;
  const unsigned short* vq = reinterpret_cast<const unsigned short*>(vp + 2 * cc * DH) + g;
  float m0 = -INFINITY, m1 = -INFINITY, l0 = 0.f, l1 = 0.f;
#pragma unroll
  for (int i = 0; i < 64; i++) o[i] = 0.f;
#pragma unroll 1
  for (int kb = 0; kb < SK / 16; kb++) {
    float z[8] = {0.f, 0.f, 0.f, 0.f, 0.f, 0.f, 0.f, 0.f};
#pragma unroll 2
    for (int kk = 0; kk < 8; kk++) {
      uint32_t a0, a1, a2, a3;
      ldsm4(qa + (kk >> 2) * half + ((((kk & 3) * 2 + (mi >> 1)) ^ swz) << 4), a0, a1, a2, a3);
      const uint32_t* kr = kq + kb * (16 * DH / 2) + kk * 8;
      mma16816(z[0], z[1], z[2], z[3], a0, a1, a2, a3, __ldg(kr), __ldg(kr + 4));
      mma16816(z[4], z[5], z[6], z[7], a0, a1, a2, a3, __ldg(kr + 8 * DH / 2), __ldg(kr + 8 * DH / 2 + 4));
    }
    const float n0 = fmaxf(m0, quad_max(fmaxf(fmaxf(z[0], z[1]), fmaxf(z[4], z[5]))));
    const float n1 = fmaxf(m1, quad_max(fmaxf(fmaxf(z[2], z[3]), fmaxf(z[6], z[7]))));
    const float al0 = ex2(m0 - n0), al1 = ex2(m1 - n1);
    m0 = n0; m1 = n1;
#pragma unroll
    for (int i = 0; i < 8; i++) z[i] = ex2(z[i] - ((i & 2) ? n1 : n0));
    l0 = l0 * al0 + (z[0] + z[1]) + (z[4] + z[5]);
    l1 = l1 * al1 + (z[2] + z[3]) + (z[6] + z[7]);
    const uint32_t a0 = pack_bf16(z[0], z[1]), a1 = pack_bf16(z[2], z[3]), a2 = pack_bf16(z[4], z[5]), a3 = pack_bf16(z[6], z[7]);
    const unsigned short* vr = vq + kb * (16 * DH);
#pragma unroll
    for (int nb = 0; nb < 16; nb++) {
      o[4 * nb] *= al0; o[4 * nb + 1] *= al0; o[4 * nb + 2] *= al1; o[4 * nb + 3] *= al1;
      const uint32_t b0 = __ldg(vr + nb * 8) | ((uint32_t)__ldg(vr + nb * 8 + DH) << 16);
      const uint32_t b1 = __ldg(vr + nb * 8 + 8 * DH) | ((uint32_t)__ldg(vr + nb * 8 + 9 * DH) << 16);
      mma16816(o[4 * nb], o[4 * nb + 1], o[4 * nb + 2], o[4 * nb + 3], a0, a1, a2, a3, b0, b1);
    }
  }
  const char* p = o_addr(item, row, lane);
  o_emit<0>(p, o, __fdividef(1.f, quad_sum(l0)));
  o_emit<1>(half == 4096 ? p : p + 1024, o, __fdividef(1.f, quad_sum(l1)));
}

template <bool SPA, bool SPB, int SITE, int ID>
__device__ __forceinline__ void batch(const Ctx& c, float (&s)[32], const uint32_t (&qs)[32], uint32_t dq, uint32_t dk, float (&ob)[64],
                                      uint32_t (&pb)[SPB ? 8 : 16], uint32_t dv) {
  if constexpr (SPA) {
    reg_fence(pb);
    wg_fence();
    issue_pv<SPB, true, ID>(c, ob, pb, dv);
    issue_qk<SPA, false, ID>(c, s, qs, dq, dk);
  } else {
    constexpr bool EARLY = ((QK_EARLY_MASK >> (SITE + (SPB ? 2 : 0))) & 1) != 0;
    if (!EARLY) reg_fence(pb);
    wg_fence();
    issue_qk<SPA, false, ID, !SPB, SITE ? RM0 : SPB ? RM2 : RM1>(c, s, qs, dq, dk);
    if (EARLY) { reg_fence(pb); wg_fence(); }
    issue_pv<SPB, true, ID, SPB>(c, ob, pb, dv);
  }
}

template <bool SP0>
__device__ __forceinline__ bool attention(Ctx& c, Ring& r, int unit, uint32_t& d, const float (&a0)[64], float (&o0)[64], float (&o1)[64],
                                          RowSum& st0, RowSum& st1, const Slots& h, uint32_t (&q1)[32]) {
  constexpr bool SP1 = false;
  if (SP0) { c.mqk = META_QK + (d >> 28); c.mpv = META_PV + (d >> 28); asm volatile("" : "+r"(c.mqk), "+r"(c.mpv)); }
  if (SP0) c.src = (c.lane & 28) | ((c.lane & 1) << 1) | ((c.lane >> 1) & 1);
  float s[32];
  uint32_t p0[SP0 ? 8 : 16], p1[16];
  const uint32_t q0a = c.sb + QBUF_OFF + (SP0 ? 3 : 0) * 16384, q1a = c.sb + QBUF_OFF + (SP0 ? 2 : 1) * 16384;
  const uint32_t dq0 = sdesc(SB0 + QBUF_OFF, 0), dq1 = sdesc(SB0 + QBUF_OFF + (SP0 ? 2 : 1) * 16384, 0);
  uint32_t sk = acquire(c, r, true), sv, sn;
  uint32_t qs[32];
  float s1[32];
  if (SP0) {
    stage_t3<0, true>(c, a0, SM_C);
    stage_t2<0>(c, a0, SM_C);
    proj_end<1>(c, o0, h);
    stage_t3<1, true>(c, o0, SM_C);
    stage_t2<1>(c, o0, SM_C);
    bar_sync(5, 128);
    const int g = c.lane >> 2, cc = c.lane & 3;
    const uint32_t qa = q0a + (8 * c.warp + g) * 128 + (cc & 1) * 8;
#pragma unroll
    for (int k = 0; k < 8; k++)
      asm volatile("ld.shared.v2.u32 {%0, %1}, [%2];" : "=r"(qs[2 * k]), "=r"(qs[2 * k + 1])
                   : "r"(qa + (k >> 2) * 4096 + ((((k & 3) * 2 + (cc >> 1)) ^ q3_swz(g)) << 4)) : "memory");
    fence_async_smem();
    bar_sync(1, 256);
    TRACE(unit, 2);
    wg_fence();
    issue_qk<SP1, true, 1>(c, s1, qs, dq1, sdesc(SB0 + sk * SLOT, 0));
#pragma unroll
    for (int k = 0; k < 8; k++)
      if (RM2 >> k & 1) ldsm4(q1a + (k >> 2) * 8192 + (16 * c.warp + (c.lane & 15)) * 128 + (((2 * (k & 3) + (c.lane >> 4)) ^ (c.lane & 7)) << 4),
                              q1[4 * k], q1[4 * k + 1], q1[4 * k + 2], q1[4 * k + 3]);
#pragma unroll
    for (int k = 0; k < 16; k++) asm volatile("" : "+r"(qs[k])::"memory");
    wg_fence();
    issue_qk<SP0, true, 0>(c, s, qs, dq0, sdesc(SB0 + sk * SLOT, 0));
    const bool have = peek<2>(c, r);
    wg_wait<1>();
    reg_fence(s1);
    exps<SP1, true>(c, s1, p1, st1);
    sched_fence<11>(sk, p1);
    acquire2(c, r, sv, sn, __all_sync(0xffffffffu, have));
    wg_wait<0>();
    wg_fence();
    issue_pv<SP1, false, 1>(c, o1, p1, sdesc(SB0 + sv * SLOT, 1024));
    if (LAG_BAR & 1) asm volatile("bar.arrive 4, 256;" ::: "memory");
    sched_fence<12>(sk, s);
    release(c, sk);
    sk = sn;
    exps<SP0, true>(c, s, p0, st0);
    reg_fence(p0);
    wg_fence();
    issue_pv<SP0, false, 0>(c, o0, p0, sdesc(SB0 + sv * SLOT, 1024));
    issue_qk<SP0, true, 2>(c, s, qs, dq0, sdesc(SB0 + sk * SLOT, 0));
    sn = acquire(c, r);
    wg_wait<0>();
    reg_fence(s);
  } else {
    pack_rows(a0, SM_C, qs);
    stage_rows(c, q0a, qs);
    proj_end<0>(c, o1, h);
    TRACE(unit, 2);
    float sc = SM_C;
    issue_qk_rs<0>(s, qs, sdesc(SB0 + sk * SLOT, 0));
    sched_fence<0>(sk, sc);
    pack_rows(o1, sc, q1);
    stage_rows<~RM1>(c, q1a, q1);
    issue_qk_rs<1>(s1, q1, sdesc(SB0 + sk * SLOT, 0));
    asm volatile("bar.arrive 1, 256;" ::: "memory");
    bool have = peek<2>(c, r);
    wg_wait<1>();
    reg_fence(s);
    exps<SP0, true>(c, s, p0, st0);
    sched_fence<1>(sk, p0);
    acquire2(c, r, sv, sn, __all_sync(0xffffffffu, have));
    wg_wait<0>();
    reg_fence(s1);
    fence_async_smem();
    __syncwarp();
    wg_fence();
    issue_qk<SP0, false, 2, true, RM0>(c, s, qs, dq0, sdesc(SB0 + sn * SLOT, 0));
    issue_pv<SP0, false, 0>(c, o0, p0, sdesc(SB0 + sv * SLOT, 1024));
    sched_fence<2>(sk, s1);
    release(c, sk);
    have = peek<1>(c, r);
    sk = sn;
    exps<SP1, true>(c, s1, p1, st1);
    reg_fence(p1);
    wg_fence();
    issue_pv<SP1, false, 1>(c, o1, p1, sdesc(SB0 + sv * SLOT, 1024));
    sn = acquire(c, r, __all_sync(0xffffffffu, have));
    if (LAG_BAR & 1) bar_sync(4, 256);
    wg_wait<1>();
    reg_fence(s);
  }
  TRACE_IN(unit, 4);
  T2C(unit, 51);
#pragma unroll 1
  for (int j = 1; j < 15; j++) {
    const uint32_t sv_prev = sv, sk_prev = sk;
    sv = sn;
    const uint32_t dv = sdesc(SB0 + sv * SLOT, 1024);
    reg_fence(p0);
    exps<SP0, false>(c, s, p0, st0);
    batch<SP1, SP0, 0, 3>(c, s, q1, dq1, sdesc(SB0 + sk * SLOT, 0), o0, p0, dv);
    sk = acquire(c, r);
    wg_wait<1>();
    reg_fence(s); reg_fence(p1);
    release(c, sv_prev); release(c, sk_prev);
    exps<SP1, false>(c, s, p1, st1);
    batch<SP0, SP1, 1, 4>(c, s, qs, dq0, sdesc(SB0 + sk * SLOT, 0), o1, p1, dv);
    sn = acquire(c, r);
    if (SP0) wg_wait<0>(); else wg_wait<1>();
    reg_fence(s);
  }
  TRACE_IN(unit, 5);
  T2C(unit + 1, 52);
  const uint32_t sv_prev = sv;
  sv = sn;
  const uint32_t dv = sdesc(SB0 + sv * SLOT, 1024);
  reg_fence(p0);
  exps<SP0, false>(c, s, p0, st0);
  batch<SP1, SP0, 0, 5>(c, s, q1, dq1, sdesc(SB0 + sk * SLOT, 0), o0, p0, dv);
  asm volatile("ld.volatile.shared.u32 %0, [%1];" : "=r"(d) : "r"(c.sb + DESC_OFF + ((unit + 1) & 3) * 4) : "memory");
  const bool have = peek<2 + SP0>(c, r);
  wg_wait<1>();
  reg_fence(s); reg_fence(p1);
  release(c, sv_prev); release(c, sk);
  exps<SP1, false>(c, s, p1, st1);
  reg_fence(p1);
  wg_fence();
  issue_pv<SP1, true, 2>(c, o1, p1, dv);
  if (SP0) sched_fence<6>(sk, st0.l0, st1.l0, st1.l1); else sched_fence<5>(sk, st0.l0, st0.l1, st1.l0, st1.l1);
  c.lane = c.lane0 + (sk >> 5);
  const bool bad = finish_sums<SP0>(st0) | finish_sums<SP1>(st1);
  uint32_t any;
  asm volatile("{\n.reg .pred p, q;\nsetp.ne.u32 p, %1, 0;\nbar.red.or.pred q, %2, 128, p;\nselp.u32 %0, 1, 0, q;\n}"
               : "=r"(any) : "r"((uint32_t)bad), "n"(2 + SP0) : "memory");
  any = __any_sync(0xffffffffu, any);
  d = __shfl_sync(0xffffffffu, d, 0);
  if (d < (2u << 30) && !__all_sync(0xffffffffu, have)) { Ring t = r; Slots u; begin_acquire<SP0>(c, t, u, true); }
  wg_wait<0>();
  reg_fence(o0); reg_fence(o1);
  release(c, sv);
  return any;
}

template <int WG>
__device__ __forceinline__ void consumer(Ctx c, const __nv_bfloat16* const* kv) {
  asm volatile("setmaxnreg.inc.sync.aligned.u32 %0;" ::"n"(WG ? REG_C : 504 - REG_C - REG_P));
  c.wg = WG;
  Ring r{0, 0, 0};
  float a0[64], a1[64], o1[64];
  Slots h;
  RowSum inv0, inv1;
  uint32_t oq[32];
  uint32_t d = first_entry(blockIdx.x, FIRST_LO, FIRST_HI) * 1025, dc = 0, sw;
  int i = 0, nq;
begin:
  sw = d & (1u << 30);
  proj_begin<WG>(c, r, a0, h, true, sw);
  proj_half<WG, true, 1>(c, a1, h.w, h.x, sw);
  nq = 0;
#pragma unroll
  for (int k = 0; k < 64; k++) asm volatile("" : "=f"(o1[k]));
  asm volatile("" : "=f"(inv1.l0), "=f"(inv1.l1));
  while (true) {
    TRACE(i, 0); TRACE(i, 6);
    proj_main<WG>(c, r, a0, a1, h, d >> 30 ? ((d >> 16) & 63) + 1 : DM / 64, sw, i, dc, nq, o1, inv1);
    dc = d;
    TRACE(i, 1);
    if (d >> 30) goto out_tile;
    wg_wait<1>();
    acc_fence<WG>(a0);
    if (WG ? attention<WG>(c, r, i, d, a0, a1, o1, inv0, inv1, h, oq) : attention<WG>(c, r, i, d, a0, o1, a1, inv1, inv0, h, oq)) goto redo;
    if (d >= (2u << 30)) break;
    sw = d & (1u << 30);
    proj_begin<WG>(c, r, a0, h, false, sw);
    release_q<WG>(c);
    if (WG) sched_fence<8>(h.w, inv0.l0); else sched_fence<7>(h.w, inv0.l0, inv0.l1);
    o_first<WG>(c, dc, a1, inv0, oq);
    sched_fence<9>(h.w, inv1.l0);
    proj_half<WG, true, 1>(c, a1, h.w, h.x, sw);
    o_rest<WG>(c, dc, oq);
    nq = O_STEPS;
    TRACE(i, 3); TRACE(i, 7);
    i++;
  }
  release_q<WG>(c);
  o_first<WG>(c, dc, a1, inv0, oq);
  o_rest<WG>(c, dc, oq);
#pragma unroll
  for (int k = 1; k <= O_STEPS; k++) o_second<WG>(c, dc, k, o1, inv1);
next:
  TRACE(i, 3); TRACE(i, 7);
  if ((d >> 30) != 2) {
    i++;
    r.uniform();
    goto begin;
  }
  trace_dump(c);
  return;
out_tile:
  if (d & 96) goto finish;
  d = get_desc(c, i + 1);
  wg_wait<1>();
  acc_fence<WG>(a0);
  TRACE_O(0);
  stage_out<WG, 0>(c, a0);
  TRACE_O(1);
  proj_end<WG>(c, a1, h);
  TRACE_O(2);
  stage_out<WG, 1>(c, a1);
  TRACE(i, 2);
  goto next;
finish:
  {
    uint32_t q[32];
#pragma unroll 1
    for (int k = (d >> 5) & 3; k > 1; k--) {
      wg_wait<0>();
      acc_fence<WG>(a0); acc_fence<WG>(a1);
      if (k == ((d >> 5) & 3)) { release(c, h.x); release(c, h.w); }
      load_part<WG, 0>(c, r, q); add_part<WG>(c, q, a0);
      load_part<WG, 1, 0>(c, r, q); add_part<WG>(c, q, a1);
#pragma unroll
      for (int t = 0; t < 4; t++) { release(c, r.slot); r.next(); }
    }
    load_part<WG, 0, WG ? 4 : 1>(c, r, q);
    wg_wait<1>();
    acc_fence<WG>(a0);
    TRACE_O(0);
    add_part<WG>(c, q, a0);
    stage_out<WG, 0>(c, a0);
    TRACE_O(1);
    load_part<WG, 1, WG ? 0 : 2>(c, r, q);
    wg_wait<0>();
    acc_fence<WG>(a1);
    TRACE_O(2);
    add_part<WG>(c, q, a1);
    stage_out<WG, 1>(c, a1);
    TRACE(i, 2); TRACE(i, 3); TRACE(i, 7);
    trace_dump(c);
    return;
  }
redo:
  {
    if (!WG) { stage_rows<RM1>(c, c.sb + QBUF_OFF + 16384, oq); __syncwarp(); }
    const size_t hoff = (size_t)(dc & 511) * (SK * DH);
    const int br = (dc >> 9) & 1;
#pragma unroll 1
    for (int part = 0; part < 2; part++) {
      const int t = WG ? 3 - part : part;
      redo_tile(c, c.sb + QBUF_OFF + t * 16384, t == 3 ? 4096 : 8192, kv[br] + hoff, kv[2 + br] + hoff, dc,
                t * 64 + (t == 3 ? 8 : 16) * c.warp);
    }
    o_done(c);
    release_q<WG>(c);
  }
  goto next;
}

template <bool SIMPLE>
__global__ void __launch_bounds__(384, 1) mha_fused_kernel(const __grid_constant__ Params P) {
  extern __shared__ __align__(1024) uint8_t smem_raw[];
  const uint32_t sbase = smem_u32(smem_raw);
  const int tid = threadIdx.x;
  const int wg = __shfl_sync(0xffffffffu, tid >> 7, 0);
  const int warp = __shfl_sync(0xffffffffu, (tid >> 5) & 3, 0);
  const int lane = tid & 31;
  const int cta = blockIdx.x;
  constexpr bool PAIR = !SIMPLE;

  if (tid == 0) T3(15, 0);
  if (tid == 0) TTAIL(7);
  const uint32_t d0 = first_entry(cta, FIRST_LO, FIRST_HI);
  const int wi = wg * 4 + warp;
  asm volatile(ELECT "prefetch.tensormap [%0];\n}" ::"l"(&P.x[0][0] + wi) : "memory");
  if ((sbase & 0xffffff) != SB0) __trap();
  if (wg < 2) {
    asm volatile(ELECT "mbarrier.init.shared::cta.b64 [%0], 1;\n}" ::"r"(sbase + BAR_FULL + wi * 8) : "memory");
    if (PAIR && (wi == 1 || wi == 4)) {
      fence_async_smem();
      tma_ld3_w(sbase + wi * SLOT, P.wq, 0, (wi / 3) * 64, (d0 & 31) * 2, sbase + BAR_FULL + wi * 8, 16384);
      if (wi == 1) TTAIL(8);
    }
#pragma unroll 1
    for (int b = BAR_OFF + 64 + wi * 8; b < DESC_OFF; b += 64)
      asm volatile(ELECT "mbarrier.init.shared::cta.b64 [%0], %1;\n}"
                   ::"r"(sbase + b), "r"(b < BAR_EMPTY || b >= BAR_DESC ? 1 : b >= BAR_STG && b < BAR_OUT ? 4 : 8) : "memory");
    asm volatile("fence.mbarrier_init.release.cluster;" ::: "memory");
    if (wi < 6) asm volatile(ELECT "prefetch.tensormap [%0];\n}" ::"l"(&P.x[0][0] + 12 + wi) : "memory");
  }
  if (PAIR) asm volatile("barrier.cluster.arrive.relaxed.aligned;" ::: "memory"); else __syncthreads();
#define INIT_DONE() if (PAIR) asm volatile("barrier.cluster.wait.aligned;" ::: "memory")

  if (wg == 2) {
    asm volatile("setmaxnreg.dec.sync.aligned.u32 %0;" ::"n"(REG_P));
    if (warp == 1) {
      const uint32_t qb = sbase + QBUF_OFF;
      const uint32_t ep = __shfl_sync(0xffffffffu, *(volatile unsigned*)&g_epoch + 1, 0);
      asm volatile("st.volatile.shared.u32 [%0], %1;" ::"r"(sbase + EPOCH_OFF), "r"(ep) : "memory");
      INIT_DONE();
      uint32_t dc = d0, qi = 0, piece = 0, na = 0;
      TTAIL(0);
      for (int i = 0; (dc >> 30) != 2; i++) {
        if (!(dc >> 30) && o_reuse<SIMPLE>((dc >> 5) & 31)) {
          const unsigned* rd = &g_rd[0][0] + ((dc & 1023) >> 2) - OR * 8;
          for (uint32_t n = 0; !__all_sync(0xffffffffu, reached(rd, ep * 5)); __nanosleep(300)) if (++n > (1u << 22)) __trap();
        }
        mbar_wait_w(sbase + BAR_GO, i & 1);
        if (piece == 0) {
          if (PAIR && (cta & 1)) {
            asm volatile(ELECT EXPECT("%0", "4") "mbarrier.arrive.shared::cluster.b64 _, [%1];\n}" ::"r"(sbase + BAR_MAIL), "r"(peer(sbase + BAR_MAIL)) : "memory");
            mbar_wait_w(sbase + BAR_MAIL, i & 1);
            qi = lds(sbase + EPOCH_OFF + 8);
          } else if (lane == 0) {
            qi = atomicAdd(&g_next, PAIR ? 2 : 1);
            if (qi == (SIMPLE ? Q_ALL : Q_RANGES) - (PAIR ? 2 : 1)) { g_next = 0; g_epoch = ep; }
          }
          qi = __shfl_sync(0xffffffffu, qi, 0);
          if (PAIR && !(cta & 1)) {
            mbar_wait_w(sbase + BAR_MAIL, i & 1);
            asm volatile(ELECT "st.async.shared::cluster.mbarrier::complete_tx::bytes.u32 [%0], %1, [%2];\n}"
                         ::"r"(peer(sbase + EPOCH_OFF + 8)), "r"(qi + 1), "r"(peer(sbase + BAR_MAIL)) : "memory");
          }
          qi += SIMPLE ? gridDim.x : NCTA;
        }
        uint32_t d;
        if (qi < (SIMPLE ? Q_ALL : Q_RANGES)) { d = c_sched.queue[qi]; if (d & 0x8000) d ^= (1u << 30) | (63u << 16) | 0x8000; else d |= o_slot<SIMPLE>(d >> 5) << 15 | (d & 31) << 10; }
        else if (SIMPLE) d = 2u << 30;
        else { const uint32_t e = qi - Q_RANGES, g = e / 5; d = c_sched.piece[g][piece++] | (g & 1 ? g * 5 + 4 - e : e - g * 5) << 8; }
        if ((d >> 30) == 1) {
          const uint32_t k0 = (d >> 22) & 63;
          const uint32_t run = __ffs(__ballot_sync(0xffffffffu, !reached(&g_cnt[d & 31][lane & 7], ep * 4)) & (0xffu << (k0 >> 3))) - 1;
          if (run <= (k0 + ((d >> 16) & 63)) >> 3) d |= run <= (k0 + O_STEPS) >> 3 ? (2u << 30) | 128 : 128;
        }
        asm volatile("st.volatile.shared.u32 [%0], %1;" ::"r"(sbase + DESC_OFF + ((i + 1) & 3) * 4), "r"(d) : "memory");
        __syncwarp();
        mbar_arrive_warp(sbase + BAR_DESC);
        const Work w = decode(dc);
        dc = d;
        if (w.kind == 0) {
          mbar_wait_w(sbase + BAR_OUT, na++ & 1);
          TTAIL(1);
          T3(i, 0); T3(i, 1);
          asm volatile(ELECT "red.release.gpu.global.add.u32 [%0], 1;\n}" ::"l"(&g_cnt[w.beta][w.sub >> 2]) : "memory");
          T3(i, 2);
          TTAIL(2);
          continue;
        }
        const bool fin = w.mode != 1;
        const CUtensorMap* m = fin ? P.out_st : P.o_st;
        const int c1 = fin ? (w.beta & 15) * SQ : 0;
        const int c2 = fin ? (w.beta >> 4) * (DM / 64) + w.sub * 2 : NBETA * 64 + w.range * 2;
        uint32_t pend = 0;
#pragma unroll 1
        for (int e = 0; e < 4; e++) {
          const int t = (ST_ORDER >> (4 * e)) & 3;
          mbar_wait_w(sbase + BAR_STG + (t ^ (t >> 1)) * 8, (i - na) & 1);
          tma_st3_w(m + (t == 3), qb + t * 16384, c1 + t * 64, c2);
          bulk_commit();
          T2P(i + 1, 5, 2 * e);
          if (e == 3 && w.mode == 1 && (d >> 30) == 2) {
            asm volatile("cp.async.bulk.wait_group 2;" ::: "memory");
            asm volatile(ELECT "st.release.gpu.global.u32 [%0], %1;\n}" ::"l"(&g_flag[w.range]), "r"(2 * ep - 1) : "memory");
          }
          if (pend && (d >> 30) != 2) {
            bulk_wait_read<1>();
            mbar_arrive8_w(pend);
            T2P(i + 1, 5, 2 * e - 1);
          }
          pend = sbase + BAR_EMPTY + (NS + t) * 8;
          if ((ST_NOW >> e) & 1) {
            bulk_wait_read<0>();
            mbar_arrive8_w(pend);
            pend = 0;
            T2P(i + 1, 5, 2 * e + 1);
          }
        }
        if (w.beta < N_EARLY) asm volatile(ELECT "red.relaxed.gpu.global.add.u32 [%0], 1;\n}" ::"l"(&g_rd[w.beta][7]) : "memory");
        T3(i, 0);
        if (piece >= 2) TTAIL(piece * 2 - 1);
        asm volatile("cp.async.bulk.wait_group 0;" ::: "memory");
        T3(i, 1);
        if (w.mode == 1) asm volatile(ELECT "st.release.gpu.global.u32 [%0], %1;\n}" ::"l"(&g_flag[w.range]), "r"(2 * ep) : "memory");
        T3(i, 2);
        if (piece >= 2) TTAIL(piece * 2);
      }
      T3(15, 1);
    } else
    if (warp == 0) {
      Ring r{PAIR ? 3 * N_FAST : 0, 1, 3};
      uint32_t d = d0;
      for (int i = 0;; i++) {
        const Work w = decode(d);
        if (w.kind == 2) break;
        const CUtensorMap* m = w.kind == 0 ? &P.wq[w.beta >> 4] : &P.wo[w.beta >> 4];
        if (i == 0) INIT_DONE();
        for (int ks = PAIR && i == 0 ? N_FAST : 0; ks < w.nsteps; ks++) {
          const uint32_t b = borrow(ks, w.nsteps);
          r.next_if(b == 2);
          const uint32_t bar = sbase + BAR_FULL + r.slot * 8;
          mbar_wait_w(bar + (BAR_EMPTY - BAR_FULL), r.phase);
          if (w.kind == 0) tma_ld3_w(sbase + r.slot * SLOT, m, 0, ks * 64, w.sub * 2, bar, 16384);
          else tma_ld_wo_w(sbase + r.slot * SLOT, m, w.sub * 128, (w.k0 + ks) * 2, bar);
          if (w.kind != 0 && w.beta < N_EARLY && (ks & 7) == 5 && ks > 5)
            asm volatile(ELECT "red.relaxed.gpu.global.add.u32 [%0], 1;\n}" ::"l"(&g_rd[w.beta][(ks >> 3) - 1]) : "memory");
          if (ks < 10) T2P(i, 2, ks);
          if (w.kind != 0 && ks == max(w.nsteps - GO_P, 4)) mbar_arrive_warp(sbase + BAR_GO);
          r.next(); r.next_if(b == 2);
        }
        if (w.kind == 0) {
          r.phase ^= 1; r.next(); r.next();
        } else if (w.mode == 2) {
          for (int k = 1; k <= ((d >> 5) & 3); k++) {
            if (k == 1) TTAIL(9);
            bool all = false;
#pragma unroll 1
            for (int t = 0; t < 4; t++) {
              if (!(t & 1) && !all) {
                const uint32_t ep2 = 2 * lds(sbase + EPOCH_OFF);
                uint32_t v, n = 0;
                do {
                  asm volatile("ld.acquire.gpu.global.u32 %0, [%1];" : "=r"(v) : "l"(&g_flag[w.range + 5 * k]) : "memory");
                  v = __shfl_sync(0xffffffffu, v - ep2, 0);
                  if (++n > (1u << 24)) __trap();
                } while ((int)v < (t >> 1) - 1);
                all = v == 0;
                TTAIL(10);
                asm volatile("fence.proxy.async.global;" ::: "memory");
              }
              mbar_wait_w(sbase + BAR_EMPTY + r.slot * 8, r.phase);
              tma_ld3_w(sbase + r.slot * SLOT, &P.o_st[t == 3], 0, t * 64, NBETA * 64 + (w.range + 5 * k) * 2, sbase + BAR_FULL + r.slot * 8,
                        t == 3 ? 8192 : 16384);
              r.next();
            }
          }
        }
        mbar_wait_w(sbase + BAR_DESC, i & 1);
        d = __shfl_sync(0xffffffffu, lds(sbase + DESC_OFF + ((i + 1) & 3) * 4), 0);
      }
    } else {
      const int hi = warp - 2;
      uint64_t pol_stream;
      uint32_t rdy = 0;
      asm volatile("createpolicy.fractional.L2::evict_first.b64 %0, 1.0;" : "=l"(pol_stream));
      Ring r{PAIR ? 3 * N_FAST : 0, 1, 3};
      uint32_t d = d0;
      for (int i = 0;; i++) {
        const Work w = decode(d);
        if (w.kind == 2) break;
        const CUtensorMap* m = w.kind == 0 ? &P.x[hi][w.beta >> 4] : &P.o_ld[hi];
        int c1 = (w.kind == 0 ? (w.beta & 15) : o_slot<SIMPLE>(w.beta) * 64 + w.k0) * SQ + hi * 128;
        int k_wait = -1;
        const bool both = PAIR && (w.kind == 0 || w.sub != 4), mine = !both || hi == (cta & 1);
        if (w.kind != 0 && mine) {
          if (d & 128) k_wait = d >= (3u << 30) ? 0 : 8 - (w.k0 & 7);
          asm volatile("fence.proxy.async.global;" ::: "memory");
        }
        if (i == 0) INIT_DONE();
        for (int ks = PAIR && i == 0 ? N_FAST : 0; ks < w.nsteps; ks++) {
          if (ks == k_wait) {
            wait_count(&g_cnt[d & 31][(w.k0 + ks) >> 3], lds(sbase + EPOCH_OFF) * 4);
            asm volatile("fence.proxy.async.global;" ::: "memory");
            k_wait = ((w.k0 + ks) | 7) + 1 - w.k0;
          }
          const uint32_t b = borrow(ks, w.nsteps);
          const bool bo = b != 2;
          r.next_if(hi && !bo); r.next_if(hi && !bo);
          const uint32_t sl = bo ? NS + (b ^ (3 * hi)) : r.slot, bar = sbase + BAR_FULL + sl * 8;
          mbar_wait_w(bar + (BAR_EMPTY - BAR_FULL), bo ? (r.xp >> b) & 1 : r.phase);
          const uint32_t bytes = hi ? 96 * 128 : 128 * 128;
          const bool used = i > 0 || ks > 4;
          if (!mine) {
            asm volatile(ELECT "mbarrier.arrive.expect_tx.shared::cta.b64 _, [%0], %1;\n}" ::"r"(bar), "r"(bytes) : "memory");
            if (used) asm volatile(ELECT "mbarrier.arrive.shared::cluster.b64 _, [%0];\n}" ::"r"(peer(bar + (BAR_RDY - BAR_FULL))) : "memory");
            if ((d & 0xc000001e) == 8 && w.beta < NBETA - 2 && i > 0)
              asm volatile(ELECT "cp.async.bulk.prefetch.tensor.2d.L2.global [%0, {%1, %2}];\n}"
                           ::"l"(&P.x[hi][(w.beta + 2) >> 4]), "r"(ks * 64), "r"(((w.beta + 2) & 15) * SQ + hi * 128) : "memory");
          } else if (both) {
            if (used) {
              mbar_wait_w(bar + (BAR_RDY - BAR_FULL), (rdy >> sl) & 1);
              rdy ^= 1 << sl;
            }
            if (w.kind == 0) tma_ld2_both_w(sbase + sl * SLOT, m, ks * 64, c1, bar, bytes);
            else tma_ld2_both_hint_w(sbase + sl * SLOT, m, 0, c1, bar, bytes, pol_stream);
          } else if (!PAIR && w.kind == 0) tma_ld2_w(sbase + sl * SLOT, m, ks * 64, c1, bar, bytes);
          else tma_ld2_hint_w(sbase + sl * SLOT, m, 0, c1, bar, bytes, pol_stream);
          if (w.kind != 0) c1 += SQ;
          if (i == 0 && (PF_MASK >> ks & 1) && (ks == 2 || cta < PF_CTA))
            asm volatile(ELECT "cp.async.bulk.prefetch.tensor.4d.L2.global.L2::cache_hint [%0, {0, 0, 0, %1}], %2;\n}"
                         ::"l"(&P.kv[hi][0]), "r"(d * (SK / 8) + 8 * __popc(PF_MASK & ((1 << ks) - 1))), "l"(pol_stream) : "memory");
          if (ks < 10) T2P(i, 3 + hi, ks);
          if (!hi && w.kind != 0 && !(ks & 3)) TCLK(i * 16 + (ks >> 2));
          r.next(); r.next_if(!hi && !bo); r.next_if(!hi && !bo);
          r.xp ^= 1 << b;
        }
        r.xp ^= 3;
        if (w.kind == 0) {
          m = &P.kv[hi][w.beta >> 4];
          c1 = (d & 511) * (SK / 8);
          for (int j = 0; j < 16; j++) {
            if (hi) r.next();
            const uint32_t bar = sbase + BAR_FULL + r.slot * 8;
            const bool tight = i == 0 && j < KV_WIN_TILES + ((KV_WIN_RAMP * cta) >> 5);
            {
              const int s2 = (int)r.slot - (tight ? 2 : KV_WIN_D);
              mbar_wait_w(sbase + BAR_FULL + (s2 < 0 ? s2 + NS : s2) * 8, s2 < 0 ? r.phase : r.phase ^ 1);
            }
            if (j == 15 && hi) mbar_wait_w(sbase + BAR_DESC, i & 1);
            mbar_wait_w(sbase + BAR_EMPTY + r.slot * 8, r.phase);
            tma_ld_kv_w(sbase + r.slot * SLOT, m, c1, bar, pol_stream);
            T2P(i, 3 + hi, 16 + j);
            if (!hi) TCLK(i * 16 + j);
            if (j == GO_J && !hi) mbar_arrive_warp(sbase + BAR_GO);
            c1 += 8;
            r.next();
            if (!hi) r.next();
          }
        }
        mbar_wait_w(sbase + BAR_DESC, i & 1);
        d = __shfl_sync(0xffffffffu, lds(sbase + DESC_OFF + ((i + 1) & 3) * 4), 0);
      }
    }
  } else {
    Ctx c;
    c.sb = sbase; c.wg = wg; c.warp = warp; c.src = 0; c.mqk = 0; c.mpv = 0; c.lead = lane == 0; c.lane0 = c.lane = lane;
    INIT_DONE();
    if (PAIR && wi < 2 * N_FAST) {
      const uint32_t t = wi & 1, sl = (wi >> 1) * 3 + t * 2, bar = sbase + BAR_FULL + sl * 8, bytes = t ? 96 * 128 : 128 * 128;
      if (t == (cta & 1)) tma_ld2_both_w(sbase + sl * SLOT, &P.x[t][0], (wi >> 1) * 64, (d0 >> 5) * SQ + t * 128, bar, bytes);
      else asm volatile(ELECT "mbarrier.arrive.expect_tx.shared::cta.b64 _, [%0], %1;\n}" ::"r"(bar), "r"(bytes) : "memory");
    }
    if (wg == 0) consumer<0>(c, P.kp); else consumer<1>(c, P.kp);
  }
}

typedef CUresult (*EncodeFn)(CUtensorMap*, CUtensorMapDataType, cuuint32_t, void*, const cuuint64_t*, const cuuint64_t*,
                             const cuuint32_t*, const cuuint32_t*, CUtensorMapInterleave, CUtensorMapSwizzle,
                             CUtensorMapL2promotion, CUtensorMapFloatOOBfill);

void make_map(EncodeFn enc, CUtensorMap* m, const void* ptr, int rank, const cuuint64_t* dims, const cuuint64_t* strides,
              const cuuint32_t* box, CUtensorMapSwizzle swz = CU_TENSOR_MAP_SWIZZLE_128B) {
  cuuint32_t es[5] = {1, 1, 1, 1, 1};
  enc(m, CU_TENSOR_MAP_DATA_TYPE_BFLOAT16, rank, const_cast<void*>(ptr), dims, strides, box, es,
      CU_TENSOR_MAP_INTERLEAVE_NONE, swz, CU_TENSOR_MAP_L2_PROMOTION_NONE,
      CU_TENSOR_MAP_FLOAT_OOB_FILL_NONE);
}

}

extern "C" void kernel_launch(void* const* d_in, const int* in_sizes, int n_in, void* d_out, int out_size) {
  (void)in_sizes; (void)n_in; (void)out_size;
  static EncodeFn enc = nullptr;
  static void* o_ptr = nullptr;
  static int n_sm = 0;
  cudaLaunchAttribute at;
  at.id = cudaLaunchAttributeClusterDimension;
  at.val.clusterDim.x = 2; at.val.clusterDim.y = 1; at.val.clusterDim.z = 1;
  cudaLaunchConfig_t cfg = {};
  cfg.gridDim = dim3(NCTA); cfg.blockDim = dim3(384); cfg.dynamicSmemBytes = SMEM_BYTES; cfg.attrs = &at; cfg.numAttrs = 1;
  if (!enc) {
    void* fn = nullptr;
    cudaDriverEntryPointQueryResult qr;
    cudaGetDriverEntryPoint("cuTensorMapEncodeTiled", &fn, cudaEnableDefault, &qr);
    enc = (EncodeFn)fn;
    cudaGetSymbolAddress(&o_ptr, g_o);
    cudaFuncSetAttribute(mha_fused_kernel<false>, cudaFuncAttributeMaxDynamicSharedMemorySize, SMEM_BYTES);
    cudaFuncSetAttribute(mha_fused_kernel<true>, cudaFuncAttributeMaxDynamicSharedMemorySize, SMEM_BYTES);
    int dev = 0;
    cudaGetDevice(&dev);
    cudaDeviceGetAttribute(&n_sm, cudaDevAttrMultiProcessorCount, dev);
    int n_cl = 0;
    cudaOccupancyMaxActiveClusters(&n_cl, mha_fused_kernel<false>, &cfg);
    if (n_cl * 2 < NCTA && n_sm >= NCTA) n_sm = NCTA - 1;
  }
  Params P;
  for (int br = 0; br < 2; br++) {
    const void* x = d_in[br * 5 + 0]; const void* kc = d_in[br * 5 + 1]; const void* vc = d_in[br * 5 + 2];
    const void* wq = d_in[br * 5 + 3]; const void* wo = d_in[br * 5 + 4];
    { cuuint64_t d[2] = {DM, (cuuint64_t)NB * SQ}, s[1] = {DM * 2}; cuuint32_t b[2] = {64, 128}, b2[2] = {64, 96};
      make_map(enc, &P.x[0][br], x, 2, d, s, b); make_map(enc, &P.x[1][br], x, 2, d, s, b2); }
    { cuuint64_t d[3] = {64, DM, HD / 64}, s[2] = {HD * 2, 128}; cuuint32_t b[3] = {64, 64, 2}; make_map(enc, &P.wq[br], wq, 3, d, s, b); }
    { cuuint64_t d[5] = {DM, 2, 4, 4, HD / 32}, s[4] = {DM * 2, 8 * DM * 2, 2 * DM * 2, 32 * DM * 2}; cuuint32_t b[5] = {64, 2, 4, 4, 2};
      make_map(enc, &P.wo[br], wo, 5, d, s, b); }
    { cuuint64_t d[4] = {64, 8, 2, (cuuint64_t)NB * NH * SK / 8}, s[3] = {DH * 2, 128, DH * 16}; cuuint32_t b[4] = {64, 8, 2, 8};
      make_map(enc, &P.kv[0][br], kc, 4, d, s, b); make_map(enc, &P.kv[1][br], vc, 4, d, s, b); }
    P.kp[br] = (const __nv_bfloat16*)kc; P.vp[br] = (const __nv_bfloat16*)vc;

  }
  { cuuint64_t d[2] = {64, (cuuint64_t)NBETA * 64 * SQ}, s[1] = {128}; cuuint32_t b[2] = {64, 128}, b2[2] = {64, 96};
    make_map(enc, &P.o_ld[0], o_ptr, 2, d, s, b, CU_TENSOR_MAP_SWIZZLE_NONE); make_map(enc, &P.o_ld[1], o_ptr, 2, d, s, b2, CU_TENSOR_MAP_SWIZZLE_NONE); }
  { cuuint64_t d[3] = {64, SQ, O_BLOCKS}, s[2] = {128, SQ * 128}; cuuint32_t b[3] = {64, 64, 2}, b2[3] = {64, 32, 2};
    make_map(enc, &P.o_st[0], o_ptr, 3, d, s, b); make_map(enc, &P.o_st[1], o_ptr, 3, d, s, b2); }
  { cuuint64_t d[3] = {64, (cuuint64_t)NB * SQ, 2 * DM / 64}, s[2] = {2 * DM * 2, 128}; cuuint32_t b[3] = {64, 64, 2}, b2[3] = {64, 32, 2};
    make_map(enc, &P.out_st[0], d_out, 3, d, s, b); make_map(enc, &P.out_st[1], d_out, 3, d, s, b2); }
  if (n_sm >= NCTA) cudaLaunchKernelEx(&cfg, mha_fused_kernel<false>, P);
  else mha_fused_kernel<true><<<n_sm, 384, SMEM_BYTES>>>(P);
}
```

```cpp
#include <cuda_runtime.h>
#include <cuda_bf16.h>
#include <cuda.h>
#include <stdint.h>
#include <stdlib.h>

namespace {

__device__ __forceinline__ void wgmma_proj(float (&d)[64], uint64_t da, uint64_t db, int scaleD) {
  asm volatile("{\n.reg .pred p;\nsetp.ne.b32 p, %66, 0;\n"
      "wgmma.mma_async.sync.aligned.m64n128k16.f32.bf16.bf16 "
      "{%0, %1, %2, %3, %4, %5, %6, %7, %8, %9, %10, %11, %12, %13, %14, %15, %16, %17, %18, %19, %20, %21, %22, %23, %24, %25, %26, %27, %28, %29, %30, "
      "%31, %32, %33, %34, %35, %36, %37, %38, %39, %40, %41, %42, %43, %44, %45, %46, %47, %48, %49, %50, %51, %52, %53, %54, %55, %56, %57, %58, %59, %60, "
      "%61, %62, %63}, "
      "%64, %65, p, 1, 1, 0, 1;\n}\n"
      : "+f"(d[0]), "+f"(d[1]), "+f"(d[2]), "+f"(d[3]), "+f"(d[4]), "+f"(d[5]), "+f"(d[6]), "+f"(d[7]), "+f"(d[8]), "+f"(d[9]), "+f"(d[10]), "+f"(d[11]),
        "+f"(d[12]), "+f"(d[13]), "+f"(d[14]), "+f"(d[15]), "+f"(d[16]), "+f"(d[17]), "+f"(d[18]), "+f"(d[19]), "+f"(d[20]), "+f"(d[21]), "+f"(d[22]),
        "+f"(d[23]), "+f"(d[24]), "+f"(d[25]), "+f"(d[26]), "+f"(d[27]), "+f"(d[28]), "+f"(d[29]), "+f"(d[30]), "+f"(d[31]), "+f"(d[32]), "+f"(d[33]),
        "+f"(d[34]), "+f"(d[35]), "+f"(d[36]), "+f"(d[37]), "+f"(d[38]), "+f"(d[39]), "+f"(d[40]), "+f"(d[41]), "+f"(d[42]), "+f"(d[43]), "+f"(d[44]),
        "+f"(d[45]), "+f"(d[46]), "+f"(d[47]), "+f"(d[48]), "+f"(d[49]), "+f"(d[50]), "+f"(d[51]), "+f"(d[52]), "+f"(d[53]), "+f"(d[54]), "+f"(d[55]),
        "+f"(d[56]), "+f"(d[57]), "+f"(d[58]), "+f"(d[59]), "+f"(d[60]), "+f"(d[61]), "+f"(d[62]), "+f"(d[63])
      : "l"(da), "l"(db), "r"(scaleD));
}
__device__ __forceinline__ void wgmma_proj96(float (&d)[64], uint64_t da, uint64_t db, int scaleD) {
  asm volatile("{\n.reg .pred p;\nsetp.ne.b32 p, %50, 0;\n"
      "wgmma.mma_async.sync.aligned.m64n96k16.f32.bf16.bf16 "
      "{%0, %1, %2, %3, %4, %5, %6, %7, %8, %9, %10, %11, %12, %13, %14, %15, %16, %17, %18, %19, %20, %21, %22, %23, %24, %25, %26, %27, %28, %29, %30, "
      "%31, %32, %33, %34, %35, %36, %37, %38, %39, %40, %41, %42, %43, %44, %45, %46, %47}, "
      "%48, %49, p, 1, 1, 1, 0;\n}\n"
      : "+f"(d[0]), "+f"(d[1]), "+f"(d[2]), "+f"(d[3]), "+f"(d[4]), "+f"(d[5]), "+f"(d[6]), "+f"(d[7]), "+f"(d[8]), "+f"(d[9]), "+f"(d[10]), "+f"(d[11]),
        "+f"(d[12]), "+f"(d[13]), "+f"(d[14]), "+f"(d[15]), "+f"(d[16]), "+f"(d[17]), "+f"(d[18]), "+f"(d[19]), "+f"(d[20]), "+f"(d[21]), "+f"(d[22]),
        "+f"(d[23]), "+f"(d[24]), "+f"(d[25]), "+f"(d[26]), "+f"(d[27]), "+f"(d[28]), "+f"(d[29]), "+f"(d[30]), "+f"(d[31]), "+f"(d[32]), "+f"(d[33]),
        "+f"(d[34]), "+f"(d[35]), "+f"(d[36]), "+f"(d[37]), "+f"(d[38]), "+f"(d[39]), "+f"(d[40]), "+f"(d[41]), "+f"(d[42]), "+f"(d[43]), "+f"(d[44]),
        "+f"(d[45]), "+f"(d[46]), "+f"(d[47])
      : "l"(da), "l"(db), "r"(scaleD));
}
__device__ __forceinline__ void wgmma_qk(float (&d)[32], uint64_t da, uint64_t db, int scaleD) {
  asm volatile("{\n.reg .pred p;\nsetp.ne.b32 p, %34, 0;\n"
      "wgmma.mma_async.sync.aligned.m64n64k16.f32.bf16.bf16 "
      "{%0, %1, %2, %3, %4, %5, %6, %7, %8, %9, %10, %11, %12, %13, %14, %15, %16, %17, %18, %19, %20, %21, %22, %23, %24, %25, %26, %27, %28, %29, %30, "
      "%31}, "
      "%32, %33, p, 1, 1, 0, 0;\n}\n"
      : "+f"(d[0]), "+f"(d[1]), "+f"(d[2]), "+f"(d[3]), "+f"(d[4]), "+f"(d[5]), "+f"(d[6]), "+f"(d[7]), "+f"(d[8]), "+f"(d[9]), "+f"(d[10]), "+f"(d[11]),
        "+f"(d[12]), "+f"(d[13]), "+f"(d[14]), "+f"(d[15]), "+f"(d[16]), "+f"(d[17]), "+f"(d[18]), "+f"(d[19]), "+f"(d[20]), "+f"(d[21]), "+f"(d[22]),
        "+f"(d[23]), "+f"(d[24]), "+f"(d[25]), "+f"(d[26]), "+f"(d[27]), "+f"(d[28]), "+f"(d[29]), "+f"(d[30]), "+f"(d[31])
      : "l"(da), "l"(db), "r"(scaleD));
}
__device__ __forceinline__ void wgmma_qk_rs(float (&d)[32], uint32_t a0, uint32_t a1, uint32_t a2, uint32_t a3, uint64_t db, int scaleD) {
  asm volatile("{\n.reg .pred p;\nsetp.ne.b32 p, %37, 0;\n"
      "wgmma.mma_async.sync.aligned.m64n64k16.f32.bf16.bf16 "
      "{%0, %1, %2, %3, %4, %5, %6, %7, %8, %9, %10, %11, %12, %13, %14, %15, %16, %17, %18, %19, %20, %21, %22, %23, %24, %25, %26, %27, %28, %29, %30, "
      "%31}, "
      "{%32, %33, %34, %35}, %36, p, 1, 1, 0;\n}\n"
      : "+f"(d[0]), "+f"(d[1]), "+f"(d[2]), "+f"(d[3]), "+f"(d[4]), "+f"(d[5]), "+f"(d[6]), "+f"(d[7]), "+f"(d[8]), "+f"(d[9]), "+f"(d[10]), "+f"(d[11]),
        "+f"(d[12]), "+f"(d[13]), "+f"(d[14]), "+f"(d[15]), "+f"(d[16]), "+f"(d[17]), "+f"(d[18]), "+f"(d[19]), "+f"(d[20]), "+f"(d[21]), "+f"(d[22]),
        "+f"(d[23]), "+f"(d[24]), "+f"(d[25]), "+f"(d[26]), "+f"(d[27]), "+f"(d[28]), "+f"(d[29]), "+f"(d[30]), "+f"(d[31])
      : "r"(a0), "r"(a1), "r"(a2), "r"(a3), "l"(db), "r"(scaleD));
}
__device__ __forceinline__ void wgmma_pv(float (&d)[64], uint32_t a0, uint32_t a1, uint32_t a2, uint32_t a3, uint64_t db, int scaleD) {
  asm volatile("{\n.reg .pred p;\nsetp.ne.b32 p, %69, 0;\n"
      "wgmma.mma_async.sync.aligned.m64n128k16.f32.bf16.bf16 "
      "{%0, %1, %2, %3, %4, %5, %6, %7, %8, %9, %10, %11, %12, %13, %14, %15, %16, %17, %18, %19, %20, %21, %22, %23, %24, %25, %26, %27, %28, %29, %30, "
      "%31, %32, %33, %34, %35, %36, %37, %38, %39, %40, %41, %42, %43, %44, %45, %46, %47, %48, %49, %50, %51, %52, %53, %54, %55, %56, %57, %58, %59, %60, "
      "%61, %62, %63}, "
      "{%64, %65, %66, %67}, %68, p, 1, 1, 1;\n}\n"
      : "+f"(d[0]), "+f"(d[1]), "+f"(d[2]), "+f"(d[3]), "+f"(d[4]), "+f"(d[5]), "+f"(d[6]), "+f"(d[7]), "+f"(d[8]), "+f"(d[9]), "+f"(d[10]), "+f"(d[11]),
        "+f"(d[12]), "+f"(d[13]), "+f"(d[14]), "+f"(d[15]), "+f"(d[16]), "+f"(d[17]), "+f"(d[18]), "+f"(d[19]), "+f"(d[20]), "+f"(d[21]), "+f"(d[22]),
        "+f"(d[23]), "+f"(d[24]), "+f"(d[25]), "+f"(d[26]), "+f"(d[27]), "+f"(d[28]), "+f"(d[29]), "+f"(d[30]), "+f"(d[31]), "+f"(d[32]), "+f"(d[33]),
        "+f"(d[34]), "+f"(d[35]), "+f"(d[36]), "+f"(d[37]), "+f"(d[38]), "+f"(d[39]), "+f"(d[40]), "+f"(d[41]), "+f"(d[42]), "+f"(d[43]), "+f"(d[44]),
        "+f"(d[45]), "+f"(d[46]), "+f"(d[47]), "+f"(d[48]), "+f"(d[49]), "+f"(d[50]), "+f"(d[51]), "+f"(d[52]), "+f"(d[53]), "+f"(d[54]), "+f"(d[55]),
        "+f"(d[56]), "+f"(d[57]), "+f"(d[58]), "+f"(d[59]), "+f"(d[60]), "+f"(d[61]), "+f"(d[62]), "+f"(d[63])
      : "r"(a0), "r"(a1), "r"(a2), "r"(a3), "l"(db), "r"(scaleD));
}
__device__ __forceinline__ void wgmma_qk_sp(float (&d)[32], uint32_t a0, uint32_t a1, uint32_t a2, uint32_t a3, uint64_t db, int scaleD, uint32_t meta) {
  asm volatile("{\n.reg .pred p;\nsetp.ne.b32 p, %37, 0;\n"
      "wgmma.mma_async.sp.sync.aligned.m64n64k32.f32.bf16.bf16 "
      "{%0, %1, %2, %3, %4, %5, %6, %7, %8, %9, %10, %11, %12, %13, %14, %15, %16, %17, %18, %19, %20, %21, %22, %23, %24, %25, %26, %27, %28, %29, %30, "
      "%31}, "
      "{%32, %33, %34, %35}, %36, %38, 0, p, 1, 1, 0;\n}\n"
      : "+f"(d[0]), "+f"(d[1]), "+f"(d[2]), "+f"(d[3]), "+f"(d[4]), "+f"(d[5]), "+f"(d[6]), "+f"(d[7]), "+f"(d[8]), "+f"(d[9]), "+f"(d[10]), "+f"(d[11]),
        "+f"(d[12]), "+f"(d[13]), "+f"(d[14]), "+f"(d[15]), "+f"(d[16]), "+f"(d[17]), "+f"(d[18]), "+f"(d[19]), "+f"(d[20]), "+f"(d[21]), "+f"(d[22]),
        "+f"(d[23]), "+f"(d[24]), "+f"(d[25]), "+f"(d[26]), "+f"(d[27]), "+f"(d[28]), "+f"(d[29]), "+f"(d[30]), "+f"(d[31])
      : "r"(a0), "r"(a1), "r"(a2), "r"(a3), "l"(db), "r"(scaleD), "r"(meta));
}
__device__ __forceinline__ void wgmma_pv_sp(float (&d)[64], uint32_t a0, uint32_t a1, uint32_t a2, uint32_t a3, uint64_t db, int scaleD, uint32_t meta) {
  asm volatile("{\n.reg .pred p;\nsetp.ne.b32 p, %69, 0;\n"
      "wgmma.mma_async.sp.sync.aligned.m64n128k32.f32.bf16.bf16 "
      "{%0, %1, %2, %3, %4, %5, %6, %7, %8, %9, %10, %11, %12, %13, %14, %15, %16, %17, %18, %19, %20, %21, %22, %23, %24, %25, %26, %27, %28, %29, %30, "
      "%31, %32, %33, %34, %35, %36, %37, %38, %39, %40, %41, %42, %43, %44, %45, %46, %47, %48, %49, %50, %51, %52, %53, %54, %55, %56, %57, %58, %59, %60, "
      "%61, %62, %63}, "
      "{%64, %65, %66, %67}, %68, %70, 0, p, 1, 1, 1;\n}\n"
      : "+f"(d[0]), "+f"(d[1]), "+f"(d[2]), "+f"(d[3]), "+f"(d[4]), "+f"(d[5]), "+f"(d[6]), "+f"(d[7]), "+f"(d[8]), "+f"(d[9]), "+f"(d[10]), "+f"(d[11]),
        "+f"(d[12]), "+f"(d[13]), "+f"(d[14]), "+f"(d[15]), "+f"(d[16]), "+f"(d[17]), "+f"(d[18]), "+f"(d[19]), "+f"(d[20]), "+f"(d[21]), "+f"(d[22]),
        "+f"(d[23]), "+f"(d[24]), "+f"(d[25]), "+f"(d[26]), "+f"(d[27]), "+f"(d[28]), "+f"(d[29]), "+f"(d[30]), "+f"(d[31]), "+f"(d[32]), "+f"(d[33]),
        "+f"(d[34]), "+f"(d[35]), "+f"(d[36]), "+f"(d[37]), "+f"(d[38]), "+f"(d[39]), "+f"(d[40]), "+f"(d[41]), "+f"(d[42]), "+f"(d[43]), "+f"(d[44]),
        "+f"(d[45]), "+f"(d[46]), "+f"(d[47]), "+f"(d[48]), "+f"(d[49]), "+f"(d[50]), "+f"(d[51]), "+f"(d[52]), "+f"(d[53]), "+f"(d[54]), "+f"(d[55]),
        "+f"(d[56]), "+f"(d[57]), "+f"(d[58]), "+f"(d[59]), "+f"(d[60]), "+f"(d[61]), "+f"(d[62]), "+f"(d[63])
      : "r"(a0), "r"(a1), "r"(a2), "r"(a3), "l"(db), "r"(scaleD), "r"(meta));
}
__device__ __forceinline__ void wgmma_proj_init(float (&d)[64], uint64_t da, uint64_t db, int scaleD) {
  asm volatile("{\n.reg .pred p;\nsetp.ne.b32 p, %66, 0;\n"
      "wgmma.mma_async.sync.aligned.m64n128k16.f32.bf16.bf16 "
      "{%0, %1, %2, %3, %4, %5, %6, %7, %8, %9, %10, %11, %12, %13, %14, %15, %16, %17, %18, %19, %20, %21, %22, %23, %24, %25, %26, %27, %28, %29, %30, "
      "%31, %32, %33, %34, %35, %36, %37, %38, %39, %40, %41, %42, %43, %44, %45, %46, %47, %48, %49, %50, %51, %52, %53, %54, %55, %56, %57, %58, %59, %60, "
      "%61, %62, %63}, "
      "%64, %65, p, 1, 1, 0, 1;\n}\n"
      : "=f"(d[0]), "=f"(d[1]), "=f"(d[2]), "=f"(d[3]), "=f"(d[4]), "=f"(d[5]), "=f"(d[6]), "=f"(d[7]), "=f"(d[8]), "=f"(d[9]), "=f"(d[10]), "=f"(d[11]),
        "=f"(d[12]), "=f"(d[13]), "=f"(d[14]), "=f"(d[15]), "=f"(d[16]), "=f"(d[17]), "=f"(d[18]), "=f"(d[19]), "=f"(d[20]), "=f"(d[21]), "=f"(d[22]),
        "=f"(d[23]), "=f"(d[24]), "=f"(d[25]), "=f"(d[26]), "=f"(d[27]), "=f"(d[28]), "=f"(d[29]), "=f"(d[30]), "=f"(d[31]), "=f"(d[32]), "=f"(d[33]),
        "=f"(d[34]), "=f"(d[35]), "=f"(d[36]), "=f"(d[37]), "=f"(d[38]), "=f"(d[39]), "=f"(d[40]), "=f"(d[41]), "=f"(d[42]), "=f"(d[43]), "=f"(d[44]),
        "=f"(d[45]), "=f"(d[46]), "=f"(d[47]), "=f"(d[48]), "=f"(d[49]), "=f"(d[50]), "=f"(d[51]), "=f"(d[52]), "=f"(d[53]), "=f"(d[54]), "=f"(d[55]),
        "=f"(d[56]), "=f"(d[57]), "=f"(d[58]), "=f"(d[59]), "=f"(d[60]), "=f"(d[61]), "=f"(d[62]), "=f"(d[63])
      : "l"(da), "l"(db), "r"(scaleD));
}
__device__ __forceinline__ void wgmma_proj96_init(float (&d)[64], uint64_t da, uint64_t db, int scaleD) {
  asm volatile("{\n.reg .pred p;\nsetp.ne.b32 p, %50, 0;\n"
      "wgmma.mma_async.sync.aligned.m64n96k16.f32.bf16.bf16 "
      "{%0, %1, %2, %3, %4, %5, %6, %7, %8, %9, %10, %11, %12, %13, %14, %15, %16, %17, %18, %19, %20, %21, %22, %23, %24, %25, %26, %27, %28, %29, %30, "
      "%31, %32, %33, %34, %35, %36, %37, %38, %39, %40, %41, %42, %43, %44, %45, %46, %47}, "
      "%48, %49, p, 1, 1, 1, 0;\n}\n"
      : "=f"(d[0]), "=f"(d[1]), "=f"(d[2]), "=f"(d[3]), "=f"(d[4]), "=f"(d[5]), "=f"(d[6]), "=f"(d[7]), "=f"(d[8]), "=f"(d[9]), "=f"(d[10]), "=f"(d[11]),
        "=f"(d[12]), "=f"(d[13]), "=f"(d[14]), "=f"(d[15]), "=f"(d[16]), "=f"(d[17]), "=f"(d[18]), "=f"(d[19]), "=f"(d[20]), "=f"(d[21]), "=f"(d[22]),
        "=f"(d[23]), "=f"(d[24]), "=f"(d[25]), "=f"(d[26]), "=f"(d[27]), "=f"(d[28]), "=f"(d[29]), "=f"(d[30]), "=f"(d[31]), "=f"(d[32]), "=f"(d[33]),
        "=f"(d[34]), "=f"(d[35]), "=f"(d[36]), "=f"(d[37]), "=f"(d[38]), "=f"(d[39]), "=f"(d[40]), "=f"(d[41]), "=f"(d[42]), "=f"(d[43]), "=f"(d[44]),
        "=f"(d[45]), "=f"(d[46]), "=f"(d[47])
      : "l"(da), "l"(db), "r"(scaleD));
}
__device__ __forceinline__ void wgmma_qk_init(float (&d)[32], uint64_t da, uint64_t db, int scaleD) {
  asm volatile("{\n.reg .pred p;\nsetp.ne.b32 p, %34, 0;\n"
      "wgmma.mma_async.sync.aligned.m64n64k16.f32.bf16.bf16 "
      "{%0, %1, %2, %3, %4, %5, %6, %7, %8, %9, %10, %11, %12, %13, %14, %15, %16, %17, %18, %19, %20, %21, %22, %23, %24, %25, %26, %27, %28, %29, %30, "
      "%31}, "
      "%32, %33, p, 1, 1, 0, 0;\n}\n"
      : "=f"(d[0]), "=f"(d[1]), "=f"(d[2]), "=f"(d[3]), "=f"(d[4]), "=f"(d[5]), "=f"(d[6]), "=f"(d[7]), "=f"(d[8]), "=f"(d[9]), "=f"(d[10]), "=f"(d[11]),
        "=f"(d[12]), "=f"(d[13]), "=f"(d[14]), "=f"(d[15]), "=f"(d[16]), "=f"(d[17]), "=f"(d[18]), "=f"(d[19]), "=f"(d[20]), "=f"(d[21]), "=f"(d[22]),
        "=f"(d[23]), "=f"(d[24]), "=f"(d[25]), "=f"(d[26]), "=f"(d[27]), "=f"(d[28]), "=f"(d[29]), "=f"(d[30]), "=f"(d[31])
      : "l"(da), "l"(db), "r"(scaleD));
}
__device__ __forceinline__ void wgmma_qk_rs_init(float (&d)[32], uint32_t a0, uint32_t a1, uint32_t a2, uint32_t a3, uint64_t db, int scaleD) {
  asm volatile("{\n.reg .pred p;\nsetp.ne.b32 p, %37, 0;\n"
      "wgmma.mma_async.sync.aligned.m64n64k16.f32.bf16.bf16 "
      "{%0, %1, %2, %3, %4, %5, %6, %7, %8, %9, %10, %11, %12, %13, %14, %15, %16, %17, %18, %19, %20, %21, %22, %23, %24, %25, %26, %27, %28, %29, %30, "
      "%31}, "
      "{%32, %33, %34, %35}, %36, p, 1, 1, 0;\n}\n"
      : "=f"(d[0]), "=f"(d[1]), "=f"(d[2]), "=f"(d[3]), "=f"(d[4]), "=f"(d[5]), "=f"(d[6]), "=f"(d[7]), "=f"(d[8]), "=f"(d[9]), "=f"(d[10]), "=f"(d[11]),
        "=f"(d[12]), "=f"(d[13]), "=f"(d[14]), "=f"(d[15]), "=f"(d[16]), "=f"(d[17]), "=f"(d[18]), "=f"(d[19]), "=f"(d[20]), "=f"(d[21]), "=f"(d[22]),
        "=f"(d[23]), "=f"(d[24]), "=f"(d[25]), "=f"(d[26]), "=f"(d[27]), "=f"(d[28]), "=f"(d[29]), "=f"(d[30]), "=f"(d[31])
      : "r"(a0), "r"(a1), "r"(a2), "r"(a3), "l"(db), "r"(scaleD));
}
__device__ __forceinline__ void wgmma_pv_init(float (&d)[64], uint32_t a0, uint32_t a1, uint32_t a2, uint32_t a3, uint64_t db, int scaleD) {
  asm volatile("{\n.reg .pred p;\nsetp.ne.b32 p, %69, 0;\n"
      "wgmma.mma_async.sync.aligned.m64n128k16.f32.bf16.bf16 "
      "{%0, %1, %2, %3, %4, %5, %6, %7, %8, %9, %10, %11, %12, %13, %14, %15, %16, %17, %18, %19, %20, %21, %22, %23, %24, %25, %26, %27, %28, %29, %30, "
      "%31, %32, %33, %34, %35, %36, %37, %38, %39, %40, %41, %42, %43, %44, %45, %46, %47, %48, %49, %50, %51, %52, %53, %54, %55, %56, %57, %58, %59, %60, "
      "%61, %62, %63}, "
      "{%64, %65, %66, %67}, %68, p, 1, 1, 1;\n}\n"
      : "=f"(d[0]), "=f"(d[1]), "=f"(d[2]), "=f"(d[3]), "=f"(d[4]), "=f"(d[5]), "=f"(d[6]), "=f"(d[7]), "=f"(d[8]), "=f"(d[9]), "=f"(d[10]), "=f"(d[11]),
        "=f"(d[12]), "=f"(d[13]), "=f"(d[14]), "=f"(d[15]), "=f"(d[16]), "=f"(d[17]), "=f"(d[18]), "=f"(d[19]), "=f"(d[20]), "=f"(d[21]), "=f"(d[22]),
        "=f"(d[23]), "=f"(d[24]), "=f"(d[25]), "=f"(d[26]), "=f"(d[27]), "=f"(d[28]), "=f"(d[29]), "=f"(d[30]), "=f"(d[31]), "=f"(d[32]), "=f"(d[33]),
        "=f"(d[34]), "=f"(d[35]), "=f"(d[36]), "=f"(d[37]), "=f"(d[38]), "=f"(d[39]), "=f"(d[40]), "=f"(d[41]), "=f"(d[42]), "=f"(d[43]), "=f"(d[44]),
        "=f"(d[45]), "=f"(d[46]), "=f"(d[47]), "=f"(d[48]), "=f"(d[49]), "=f"(d[50]), "=f"(d[51]), "=f"(d[52]), "=f"(d[53]), "=f"(d[54]), "=f"(d[55]),
        "=f"(d[56]), "=f"(d[57]), "=f"(d[58]), "=f"(d[59]), "=f"(d[60]), "=f"(d[61]), "=f"(d[62]), "=f"(d[63])
      : "r"(a0), "r"(a1), "r"(a2), "r"(a3), "l"(db), "r"(scaleD));
}
__device__ __forceinline__ void wgmma_qk_sp_init(float (&d)[32], uint32_t a0, uint32_t a1, uint32_t a2, uint32_t a3, uint64_t db, int scaleD, uint32_t meta) {
  asm volatile("{\n.reg .pred p;\nsetp.ne.b32 p, %37, 0;\n"
      "wgmma.mma_async.sp.sync.aligned.m64n64k32.f32.bf16.bf16 "
      "{%0, %1, %2, %3, %4, %5, %6, %7, %8, %9, %10, %11, %12, %13, %14, %15, %16, %17, %18, %19, %20, %21, %22, %23, %24, %25, %26, %27, %28, %29, %30, "
      "%31}, "
      "{%32, %33, %34, %35}, %36, %38, 0, p, 1, 1, 0;\n}\n"
      : "=f"(d[0]), "=f"(d[1]), "=f"(d[2]), "=f"(d[3]), "=f"(d[4]), "=f"(d[5]), "=f"(d[6]), "=f"(d[7]), "=f"(d[8]), "=f"(d[9]), "=f"(d[10]), "=f"(d[11]),
        "=f"(d[12]), "=f"(d[13]), "=f"(d[14]), "=f"(d[15]), "=f"(d[16]), "=f"(d[17]), "=f"(d[18]), "=f"(d[19]), "=f"(d[20]), "=f"(d[21]), "=f"(d[22]),
        "=f"(d[23]), "=f"(d[24]), "=f"(d[25]), "=f"(d[26]), "=f"(d[27]), "=f"(d[28]), "=f"(d[29]), "=f"(d[30]), "=f"(d[31])
      : "r"(a0), "r"(a1), "r"(a2), "r"(a3), "l"(db), "r"(scaleD), "r"(meta));
}
__device__ __forceinline__ void wgmma_pv_sp_init(float (&d)[64], uint32_t a0, uint32_t a1, uint32_t a2, uint32_t a3, uint64_t db, int scaleD, uint32_t meta) {
  asm volatile("{\n.reg .pred p;\nsetp.ne.b32 p, %69, 0;\n"
      "wgmma.mma_async.sp.sync.aligned.m64n128k32.f32.bf16.bf16 "
      "{%0, %1, %2, %3, %4, %5, %6, %7, %8, %9, %10, %11, %12, %13, %14, %15, %16, %17, %18, %19, %20, %21, %22, %23, %24, %25, %26, %27, %28, %29, %30, "
      "%31, %32, %33, %34, %35, %36, %37, %38, %39, %40, %41, %42, %43, %44, %45, %46, %47, %48, %49, %50, %51, %52, %53, %54, %55, %56, %57, %58, %59, %60, "
      "%61, %62, %63}, "
      "{%64, %65, %66, %67}, %68, %70, 0, p, 1, 1, 1;\n}\n"
      : "=f"(d[0]), "=f"(d[1]), "=f"(d[2]), "=f"(d[3]), "=f"(d[4]), "=f"(d[5]), "=f"(d[6]), "=f"(d[7]), "=f"(d[8]), "=f"(d[9]), "=f"(d[10]), "=f"(d[11]),
        "=f"(d[12]), "=f"(d[13]), "=f"(d[14]), "=f"(d[15]), "=f"(d[16]), "=f"(d[17]), "=f"(d[18]), "=f"(d[19]), "=f"(d[20]), "=f"(d[21]), "=f"(d[22]),
        "=f"(d[23]), "=f"(d[24]), "=f"(d[25]), "=f"(d[26]), "=f"(d[27]), "=f"(d[28]), "=f"(d[29]), "=f"(d[30]), "=f"(d[31]), "=f"(d[32]), "=f"(d[33]),
        "=f"(d[34]), "=f"(d[35]), "=f"(d[36]), "=f"(d[37]), "=f"(d[38]), "=f"(d[39]), "=f"(d[40]), "=f"(d[41]), "=f"(d[42]), "=f"(d[43]), "=f"(d[44]),
        "=f"(d[45]), "=f"(d[46]), "=f"(d[47]), "=f"(d[48]), "=f"(d[49]), "=f"(d[50]), "=f"(d[51]), "=f"(d[52]), "=f"(d[53]), "=f"(d[54]), "=f"(d[55]),
        "=f"(d[56]), "=f"(d[57]), "=f"(d[58]), "=f"(d[59]), "=f"(d[60]), "=f"(d[61]), "=f"(d[62]), "=f"(d[63])
      : "r"(a0), "r"(a1), "r"(a2), "r"(a3), "l"(db), "r"(scaleD), "r"(meta));
}

constexpr int NB = 16, SQ = 224, DM = 640, NH = 32, SK = 1024, DH = 128;
constexpr int HD = NH * DH;
constexpr int NBETA = 2 * NB;
constexpr int NCTA = 132;
constexpr uint32_t SB0 = 1024;
constexpr int NS = 10;
constexpr int SLOT = 16384;
constexpr int QBUF_OFF = NS * SLOT;
constexpr int NSX = NS + 4;
constexpr int BAR_OFF = NSX * SLOT;
constexpr int BAR_FULL = BAR_OFF;
constexpr int BAR_EMPTY = BAR_OFF + 8 * NSX;
constexpr int BAR_STG = BAR_OFF + 16 * NSX;
constexpr int BAR_OUT = BAR_STG + 32;
constexpr int BAR_DESC = BAR_OUT + 8;
constexpr int BAR_GO = BAR_DESC + 8;
constexpr int BAR_MAIL = BAR_GO + 8;
constexpr int BAR_RDY = BAR_MAIL + 8;
constexpr int DESC_OFF = BAR_RDY + 8 * NSX;
constexpr int EPOCH_OFF = DESC_OFF + 16;
constexpr int TRACE_OFF = EPOCH_OFF + 16;
constexpr int SMEM_BYTES = TRACE_OFF;
constexpr float SM_C = 0.08838834764831845f * 1.4426950408889634f;
constexpr float SUM_HI = 1099511627776.f, SUM_LO = 1.f / 1099511627776.f;
constexpr uint32_t META_QK = 0xEEEE4444u;
constexpr uint32_t META_PV = 0x44EEEE44u;

#define QK_EARLY_MASK 3
#define ST_ORDER 0x2310
#define LAG_BAR 2
#define ST_NOW 8
#define PF_MASK 0x3e4
#define PF_CTA 32
#define KV_WIN_D 4
#define SF 0xefbf
#define O_STEPS 4
#define KV_WIN_RAMP 4
#define PDEPTH 0
#define KV_WIN_TILES -2
#define REG_C 232
#define REG_P 24
#define GO_P 6
#define P_POS 208
#define OR 6
#define OR0 0
#define B_LATE 22
#define H_LATE 24
#define RM0 1
#define RM1 0xa7
#define RM2 0
#define PAIRB 1
#define LATE0 1
#define LATE1 2
#define GO_J 13
static_assert(GO_J >= 12);
#define LATE_G 32
constexpr int N_FAST = 2;
#define KG 5
#define PK 44
#define EARLY_MASK 0xffffu
#define PIECE_TABLE 0x501e8815,0x689d883d,0x5036b019,0x80000000,0x50345012,0x80000000,0x50244013,0x6b13403a,0x501c3811,0x695a3833,0x50321018,0x80000000,0x502b481a,0x6d4a4832,0x50128016,0x67e08035,0x50210814,0x6ccc0838,0x5012c010,0x695ac03f,0x64ec7836,0x80000000,0x64ecb830,0x80000000,0x5024c81f,0x80000000,0x5024601e,0x80000000,0x5021901d,0x80000000,0x501e7017,0x80000000,0x549b201c,0x80000000,0x67623031,0x80000000,0x67e06837,0x80000000,0x5016a81b,0x6dc8a839,0x689d0034,0x80000000,0x6999985b,0x80000000,0x695a583e,0x80000000,0x5011281c,0x80000000,0x55cea01b,0x80000000,0x6b91185c,0x80000000

struct Params {
  CUtensorMap x[2][2], wq[2], kv[2][2], wo[2];
  CUtensorMap o_ld[2], o_st[2], out_st[2];
  const __nv_bfloat16* kp[2];
  const __nv_bfloat16* vp[2];
};

constexpr int NPART = 32 * 5, O_BLOCKS = NBETA * 64 + 2 * NPART;
__device__ __align__(128) __nv_bfloat16 g_o[(size_t)O_BLOCKS * SQ * 64];
__device__ unsigned g_cnt[NBETA][8];
__device__ unsigned g_rd[NBETA][8];
__device__ unsigned g_epoch, g_next;
__device__ unsigned g_flag[NPART];

__device__ __forceinline__ uint32_t smem_u32(const void* p) { return (uint32_t)__cvta_generic_to_shared(p); }
__device__ __forceinline__ void mbar_arrive(uint32_t bar) {
  asm volatile("mbarrier.arrive.shared::cta.b64 _, [%0];" ::"r"(bar) : "memory");
}
__device__ __forceinline__ void mbar_arrive_warp(uint32_t bar) {
  asm volatile("{\n.reg .pred p;\nelect.sync _|p, 0xffffffff;\n@p mbarrier.arrive.shared::cta.b64 _, [%0];\n}" ::"r"(bar) : "memory");
}
__device__ __forceinline__ int lane_now() { int l; asm volatile("mov.u32 %0, %%laneid;" : "=r"(l)); return l; }
__device__ __forceinline__ bool mbar_try(uint32_t bar, uint32_t parity) {
  uint32_t ok;
  asm volatile("{\n.reg .pred p;\nmbarrier.try_wait.parity.shared::cta.b64 p, [%1], %2;\nselp.u32 %0, 1, 0, p;\n}"
               : "=r"(ok) : "r"(bar), "r"(parity) : "memory");
  return ok;
}
__device__ __forceinline__ bool mbar_test(uint32_t bar, uint32_t parity) {
  uint32_t ok;
  asm volatile("{\n.reg .pred p;\nmbarrier.test_wait.parity.shared::cta.b64 p, [%1], %2;\nselp.u32 %0, 1, 0, p;\n}"
               : "=r"(ok) : "r"(bar), "r"(parity) : "memory");
  return ok;
}
__device__ __forceinline__ void mbar_wait_w(uint32_t bar, uint32_t parity) {
  uint32_t n = 0;
  while (!__all_sync(0xffffffffu, mbar_try(bar, parity))) {
    if (++n > (1u << 22)) __trap();
  }
}
#define ELECT "{\n.reg .pred p;\nelect.sync _|p, 0xffffffff;\n@p "
__device__ __forceinline__ void tma_st3_w(const CUtensorMap* m, uint32_t src, int c1, int c2) {
  asm volatile(ELECT "cp.async.bulk.tensor.3d.global.shared::cta.bulk_group [%0, {0, %2, %3}], [%1];\n}"
               ::"l"(m), "r"(src), "r"(c1), "r"(c2) : "memory");
}
#define EXPECT(bar, bytes) "mbarrier.arrive.expect_tx.shared::cta.b64 _, [" bar "], " bytes ";\n@p "
__device__ __forceinline__ void tma_ld2_w(uint32_t dst, const CUtensorMap* m, int c0, int c1, uint32_t bar, uint32_t bytes) {
  asm volatile(ELECT EXPECT("%2", "%5") "cp.async.bulk.tensor.2d.shared::cluster.global.mbarrier::complete_tx::bytes [%0], [%1, {%3, %4}], [%2];\n}"
               ::"r"(dst), "l"(m), "r"(bar), "r"(c0), "r"(c1), "r"(bytes) : "memory");
}
__device__ __forceinline__ void tma_ld2_hint_w(uint32_t dst, const CUtensorMap* m, int c0, int c1, uint32_t bar, uint32_t bytes, uint64_t pol) {
  asm volatile(ELECT EXPECT("%2", "%6") "cp.async.bulk.tensor.2d.shared::cluster.global.mbarrier::complete_tx::bytes.L2::cache_hint"
               " [%0], [%1, {%3, %4}], [%2], %5;\n}"
               ::"r"(dst), "l"(m), "r"(bar), "r"(c0), "r"(c1), "l"(pol), "r"(bytes) : "memory");
}
__device__ __forceinline__ void tma_ld3_w(uint32_t dst, const CUtensorMap* m, int c0, int c1, int c2, uint32_t bar, uint32_t bytes) {
  asm volatile(ELECT EXPECT("%2", "%6") "cp.async.bulk.tensor.3d.shared::cluster.global.mbarrier::complete_tx::bytes [%0], [%1, {%3, %4, %5}], [%2];\n}"
               ::"r"(dst), "l"(m), "r"(bar), "r"(c0), "r"(c1), "r"(c2), "r"(bytes) : "memory");
}
__device__ __forceinline__ void tma_ld_kv_w(uint32_t dst, const CUtensorMap* m, int grp, uint32_t bar, uint64_t pol) {
  asm volatile(ELECT EXPECT("%2", "16384") "cp.async.bulk.tensor.4d.shared::cluster.global.mbarrier::complete_tx::bytes.L2::cache_hint"
               " [%0], [%1, {0, 0, 0, %3}], [%2], %4;\n}"
               ::"r"(dst), "l"(m), "r"(bar), "r"(grp), "l"(pol) : "memory");
}
__device__ __forceinline__ void tma_ld_wo_w(uint32_t dst, const CUtensorMap* m, int col, int grp, uint32_t bar) {
  asm volatile(ELECT EXPECT("%2", "16384") "cp.async.bulk.tensor.5d.shared::cluster.global.mbarrier::complete_tx::bytes [%0], [%1, {%3, 0, 0, 0, %4}], [%2];\n"
               "@p cp.async.bulk.tensor.5d.shared::cluster.global.mbarrier::complete_tx::bytes [%5], [%1, {%6, 0, 0, 0, %4}], [%2];\n}"
               ::"r"(dst), "l"(m), "r"(bar), "r"(col), "r"(grp), "r"(dst + 8192), "r"(col + 64) : "memory");
}
__device__ __forceinline__ void mbar_arrive8_w(uint32_t bar) {
  asm volatile(ELECT "mbarrier.arrive.shared::cta.b64 _, [%0], 8;\n}" ::"r"(bar) : "memory");
}
__device__ __forceinline__ uint32_t peer(uint32_t a) { uint32_t r; asm("mapa.shared::cluster.u32 %0, %1, %2;" : "=r"(r) : "r"(a), "r"(~blockIdx.x & 1)); return r; }
__device__ __forceinline__ void tma_ld2_both_w(uint32_t dst, const CUtensorMap* m, int c0, int c1, uint32_t bar, uint32_t bytes) {
  asm volatile(ELECT EXPECT("%2", "%5") "cp.async.bulk.tensor.2d.shared::cluster.global.mbarrier::complete_tx::bytes.multicast::cluster"
               " [%0], [%1, {%3, %4}], [%2], %6;\n}"
               ::"r"(dst), "l"(m), "r"(bar), "r"(c0), "r"(c1), "r"(bytes), "h"((uint16_t)3) : "memory");
}
__device__ __forceinline__ void tma_ld2_both_hint_w(uint32_t dst, const CUtensorMap* m, int c0, int c1, uint32_t bar, uint32_t bytes, uint64_t pol) {
  asm volatile(ELECT EXPECT("%2", "%6") "cp.async.bulk.tensor.2d.shared::cluster.global.mbarrier::complete_tx::bytes.multicast::cluster.L2::cache_hint"
               " [%0], [%1, {%3, %4}], [%2], %7, %5;\n}"
               ::"r"(dst), "l"(m), "r"(bar), "r"(c0), "r"(c1), "l"(pol), "r"(bytes), "h"((uint16_t)3) : "memory");
}
__device__ __forceinline__ void bulk_commit() { asm volatile("cp.async.bulk.commit_group;" ::: "memory"); }
template <int N> __device__ __forceinline__ void bulk_wait_read() { asm volatile("cp.async.bulk.wait_group.read %0;" ::"n"(N) : "memory"); }
__device__ __forceinline__ void wg_fence() { asm volatile("wgmma.fence.sync.aligned;" ::: "memory"); }
__device__ __forceinline__ void wg_commit() { asm volatile("wgmma.commit_group.sync.aligned;" ::: "memory"); }
template <int N> __device__ __forceinline__ void wg_wait() { asm volatile("wgmma.wait_group.sync.aligned %0;" ::"n"(N) : "memory"); }
__device__ __forceinline__ void fence_async_smem() { asm volatile("fence.proxy.async.shared::cta;" ::: "memory"); }
__device__ __forceinline__ void bar_sync(int id, int n) { asm volatile("bar.sync %0, %1;" ::"r"(id), "r"(n) : "memory"); }
__device__ __forceinline__ void touch(float& a) { asm volatile("neg.f32 %0, %0;" : "+f"(a)); }
__device__ __forceinline__ void touch(uint32_t& a) { asm volatile("not.b32 %0, %0;" : "+r"(a)); }
template <typename T, int N> __device__ __forceinline__ void touch(T (&a)[N]) {
#pragma unroll
  for (int i = 0; i < N; i++) touch(a[i]);
}
template <int ID, typename... A> __device__ __forceinline__ void sched_fence(uint32_t x, A&... a) {
  if (!((SF >> ID) & 1)) return;
  asm volatile("" : "+r"(x)::"memory");
#pragma unroll 1
  for (; __builtin_expect(x >= 100 + ID, 0); x >>= 1) { (touch(a), ...); __nanosleep(x); }
}
template <int N> __device__ __forceinline__ void reg_fence(float (&a)[N]) {
#pragma unroll
  for (int i = 0; i < N; i++) asm volatile("" : "+f"(a[i])::"memory");
}
template <int N> __device__ __forceinline__ void reg_fence(uint32_t (&a)[N]) {
#pragma unroll
  for (int i = 0; i < N; i++) asm volatile("" : "+r"(a[i])::"memory");
}
__device__ __forceinline__ float ex2(float x) { float y; asm("ex2.approx.ftz.f32 %0, %1;" : "=f"(y) : "f"(x)); return y; }
__device__ __forceinline__ uint32_t pack_bf16(float lo, float hi) {
  uint32_t r; asm("cvt.rn.bf16x2.f32 %0, %1, %2;" : "=r"(r) : "f"(hi), "f"(lo)); return r;
}
__device__ __forceinline__ void stsm4(uint32_t a, uint32_t r0, uint32_t r1, uint32_t r2, uint32_t r3) {
  asm volatile("stmatrix.sync.aligned.m8n8.x4.shared.b16 [%0], {%1, %2, %3, %4};" ::"r"(a), "r"(r0), "r"(r1), "r"(r2), "r"(r3) : "memory");
}
__device__ __forceinline__ void stsm4t(uint32_t a, uint32_t r0, uint32_t r1, uint32_t r2, uint32_t r3) {
  asm volatile("stmatrix.sync.aligned.m8n8.x4.trans.shared.b16 [%0], {%1, %2, %3, %4};" ::"r"(a), "r"(r0), "r"(r1), "r"(r2), "r"(r3) : "memory");
}
__device__ __forceinline__ void ldsm4(uint32_t a, uint32_t& r0, uint32_t& r1, uint32_t& r2, uint32_t& r3) {
  asm volatile("ldmatrix.sync.aligned.m8n8.x4.shared.b16 {%0, %1, %2, %3}, [%4];" : "=r"(r0), "=r"(r1), "=r"(r2), "=r"(r3) : "r"(a) : "memory");
}
__device__ __forceinline__ void mma16816(float& c0, float& c1, float& c2, float& c3, uint32_t a0, uint32_t a1, uint32_t a2, uint32_t a3,
                                         uint32_t b0, uint32_t b1) {
  asm volatile("mma.sync.aligned.m16n8k16.row.col.f32.bf16.bf16.f32 {%0, %1, %2, %3}, {%4, %5, %6, %7}, {%8, %9}, {%0, %1, %2, %3};"
               : "+f"(c0), "+f"(c1), "+f"(c2), "+f"(c3) : "r"(a0), "r"(a1), "r"(a2), "r"(a3), "r"(b0), "r"(b1));
}
__device__ __forceinline__ uint32_t sdesc(uint32_t addr, uint32_t lbo) { return (addr >> 4) + ((lbo >> 4) << 16); }
__device__ __forceinline__ uint64_t desc64(uint32_t lo, uint32_t hi) { uint64_t d; asm("mov.b64 %0, {%1, %2};" : "=l"(d) : "r"(lo), "r"(hi)); return d; }
__device__ __forceinline__ void dadd(uint64_t& d, uint32_t inc) {
  asm("{\n.reg .b32 l, h;\nmov.b64 {l, h}, %0;\nadd.u32 l, l, %1;\nmov.b64 %0, {l, h};\n}" : "+l"(d) : "r"(inc));
}

struct Ring {
  uint32_t slot, phase, xp;
  __device__ __forceinline__ void uniform() {
    slot = __shfl_sync(0xffffffffu, slot, 0); phase = __shfl_sync(0xffffffffu, phase, 0); xp = __shfl_sync(0xffffffffu, xp, 0);
  }
  __device__ __forceinline__ void next() { if (++slot == NS) { slot = 0; phase ^= 1; } }
  __device__ __forceinline__ void next_if(bool p) { slot += p; if (slot == NS) { slot = 0; phase ^= 1; } }
};
__device__ __forceinline__ uint32_t borrow(int ks, int n) {
  const int k = ks + 1;
  return k >= 4 && !(k & 2) && k < n ? k & 1 : 2;
}

constexpr uint32_t Q_RANGES = NBETA * NH + __builtin_popcount(EARLY_MASK) * 5, Q_ALL = NBETA * (NH + 5);
constexpr int NRANGE = NCTA / 5;
struct Work { int kind, mode, k0, nsteps, range, beta, sub; };
struct Sched { uint16_t queue[Q_ALL]; uint32_t piece[NRANGE + 1][4]; };
constexpr Sched make_sched() {
  Sched s{};
  int q = 0, a = 0;
  for (int t = 0, e = 0; a < NBETA * NH; t++) {
    for (; e < NBETA && 8 * (e & ~PAIRB) + PK <= t && a >= P_POS; e++)
      for (int col = 0; col < 5 && (EARLY_MASK >> e & 1); col++) s.queue[q++] = 0x8000 | (e & 1 ? 4 - col : col) << 8 | e;
    for (int b = 0; b < NBETA; b++)
      for (int h = 0; h < NH; h++)
        if ((b >= B_LATE && h >= H_LATE ? 300 + b + LATE_G * (h >> 2) : 8 * (b & ~PAIRB) + KG * (h >> 2)) == t) { s.queue[q++] = b << 5 | h; a++; }
  }
  for (int b = 0; b < NBETA; b++)
    for (int col = 0; col < 5 && !(EARLY_MASK >> b & 1); col++) s.queue[q++] = 0x8000 | col << 8 | b;
  constexpr uint32_t T[NRANGE * 2] = {PIECE_TABLE};
  for (int g = 0; g <= NRANGE; g++)
    for (int n = 0; n < 4; n++) s.piece[g][n] = g < NRANGE && n < 2 ? T[2 * g + n] : 2u << 30;
  return s;
}
__constant__ Sched c_sched = make_sched();
constexpr uint64_t first_bits(int k0) {
  const Sched s = make_sched();
  uint64_t v = 0;
  for (int k = 0; k < 10; k++) v |= (uint64_t)(s.queue[(k0 + k) * 8] >> 2) << (6 * k);
  return v;
}
__host__ __device__ constexpr uint32_t first_entry(uint32_t q, uint64_t lo, uint64_t hi) {
  return (uint32_t)((q < 80 ? lo >> (q >> 3) * 6 : hi >> ((q >> 3) - 10) * 6) & 63) * 4 + (q & 4) * 8 + (q & 3);
}
constexpr uint64_t FIRST_LO = first_bits(0), FIRST_HI = first_bits(10);
constexpr bool first_ok() {
  const Sched s = make_sched();
  for (int q = 0; q < NCTA; q++) if (first_entry(q, FIRST_LO, FIRST_HI) != s.queue[q]) return false;
  return true;
}
static_assert(first_ok());
constexpr int N_EARLY = __builtin_popcount(EARLY_MASK);
constexpr bool reuse_ok() {
  const Sched s = make_sched();
  int first[NBETA + OR] = {};
  for (int q = Q_RANGES - 1; q >= 0; q--) if (!(s.queue[q] & 0x8000)) first[s.queue[q] >> 5] = q;
  for (int q = 0; q < Q_RANGES; q++) if ((s.queue[q] & 0x8000) && (s.queue[q] & 31) >= OR0 && q - first[(s.queue[q] & 31) + OR] > NCTA - 32) return false;
  return first[OR0 + OR] >= NCTA && P_POS >= NCTA;
}
static_assert(reuse_ok());
template <bool SIMPLE> __device__ __forceinline__ bool o_reuse(uint32_t b) { return !SIMPLE && b - (OR0 + OR) < N_EARLY - OR0; }
template <bool SIMPLE> __device__ __forceinline__ uint32_t o_slot(uint32_t b) { return o_reuse<SIMPLE>(b) ? OR0 + (b - OR0) % OR : b; }
__device__ __forceinline__ Work decode(uint32_t d) {
  Work w;
  w.kind = d >> 30; if (w.kind == 3) w.kind = 1;
  w.mode = (d >> 28) & 3; w.k0 = (d >> 22) & 63;
  if (w.kind == 0) { w.beta = (d >> 5) & 31; w.sub = d & 31; w.nsteps = DM / 64; }
  else { w.beta = d & 31; w.sub = (d >> 8) & 7; w.nsteps = ((d >> 16) & 63) + 1; }
  w.range = ((d >> 11) & 31) * 5 + w.sub;
  return w;
}

__device__ __forceinline__ bool reached(const unsigned* cnt, unsigned target) {
  unsigned v;
  asm volatile("ld.acquire.gpu.global.u32 %0, [%1];" : "=r"(v) : "l"(cnt) : "memory");
  return (int)(v - target) >= 0;
}
__device__ __forceinline__ void wait_count(const unsigned* cnt, unsigned target) {
  unsigned n = 0;
  while (!__all_sync(0xffffffffu, reached(cnt, target))) { if (++n > (1u << 24)) __trap(); }
}
__device__ __forceinline__ uint32_t lds(uint32_t a) { uint32_t v; asm volatile("ld.volatile.shared.u32 %0, [%1];" : "=r"(v) : "r"(a) : "memory"); return v; }

struct Ctx {
  uint32_t sb;
  int wg, warp;
  uint32_t mqk, mpv;
  bool lead;
  int lane0, lane;
  int src;
};
template <int N> __device__ __forceinline__ uint32_t dhi(uint32_t lo) { return 0x40000040u + (lo >> (26 + N)); }
__device__ __forceinline__ void release(const Ctx& c, uint32_t slot) {
  if (c.lead) mbar_arrive(c.sb + BAR_EMPTY + slot * 8);
}
__device__ __forceinline__ uint32_t acquire(const Ctx& c, Ring& r, bool have = false) {
  const uint32_t s = r.slot;
  if (!have) mbar_wait_w(c.sb + BAR_FULL + s * 8, r.phase);
  r.next();
  return s;
}
__device__ __forceinline__ void mbar_wait2_w(uint32_t b0, uint32_t p0, uint32_t b1, uint32_t p1) {
  uint32_t n = 0;
  while (!__all_sync(0xffffffffu, mbar_try(b0, p0) & mbar_try(b1, p1))) {
    if (++n > (1u << 22)) __trap();
  }
}
__device__ __forceinline__ void mbar_wait3_w(uint32_t b0, uint32_t p0, uint32_t b1, uint32_t p1, uint32_t b2, uint32_t p2) {
  uint32_t n = 0;
  while (!__all_sync(0xffffffffu, mbar_try(b0, p0) & mbar_try(b1, p1) & mbar_try(b2, p2))) {
    if (++n > (1u << 22)) __trap();
  }
}
__device__ __forceinline__ void acquire2(const Ctx& c, Ring& r, uint32_t& s0, uint32_t& s1, bool have = false) {
  const uint32_t p0 = r.phase;
  s0 = r.slot; r.next(); s1 = r.slot;
  if (!have) mbar_wait2_w(c.sb + BAR_FULL + s0 * 8, p0, c.sb + BAR_FULL + s1 * 8, r.phase);
  r.next();
}
template <int N>
__device__ __forceinline__ bool peek(const Ctx& c, Ring r) {
  bool ok = true;
#pragma unroll
  for (int k = 0; k < N; k++) { ok &= mbar_test(c.sb + BAR_FULL + r.slot * 8, r.phase); r.next(); }
  return ok;
}
__device__ __forceinline__ void staged(const Ctx& c, int part) {
  fence_async_smem();
  __syncwarp();
  mbar_arrive_warp(c.sb + BAR_STG + c.wg * 16 + part * 8);
}

template <int WG, bool FIRST, int H>
__device__ __forceinline__ void proj_half(const Ctx& c, float (&acc)[64], uint32_t w, uint32_t x, uint32_t sw) {
  uint64_t dx = desc64((SB0 + x * SLOT + (WG ? 0 : H * 8192)) >> 4, dhi<0>(x) + sw);
  uint64_t dw = desc64(WG ? (SB0 + w * SLOT + H * 8192) >> 4 : sdesc(SB0 + w * SLOT, 8192), dhi<1>(x));
  wg_fence();
  if (WG) { if (FIRST) wgmma_proj96_init(acc, dw, dx, 0); else wgmma_proj96(acc, dw, dx, 1); }
  else { if (FIRST) wgmma_proj_init(acc, dx, dw, 0); else wgmma_proj(acc, dx, dw, 1); }
#pragma unroll
  for (int k = 1; k < 4; k++) {
    dadd(dx, k == 2 ? 2 + (sw >> 30) * 28 : 2); dadd(dw, 128);
    if (WG) wgmma_proj96(acc, dw, dx, 1); else wgmma_proj(acc, dx, dw, 1);
  }
  wg_commit();
}

__device__ __forceinline__ void proj_store16(uint32_t a, const float* f, float sc) {
  stsm4t(a, pack_bf16(f[0] * sc, f[1] * sc), pack_bf16(f[2] * sc, f[3] * sc), pack_bf16(f[4] * sc, f[5] * sc), pack_bf16(f[6] * sc, f[7] * sc));
}

__device__ __forceinline__ uint32_t stage_off(const Ctx& c) {
  const int lane = c.lane, mi = lane >> 3, r8 = lane & 7;
  return ((mi >> 1) * 8 + r8) * 128 + (((2 * c.warp + (mi & 1)) ^ r8) << 4);
}
__device__ __forceinline__ uint32_t q3_swz(uint32_t r8) { return ((r8 & 3) << 1) | (r8 >> 2); }
template <int H>
__device__ __forceinline__ void stage_t2(const Ctx& c, const float (&a)[64], float sc) {
  const uint32_t base = c.sb + QBUF_OFF + 2 * 16384 + H * 8192 + stage_off(c);
#pragma unroll
  for (int jj = 0; jj < 4; jj++) proj_store16(base + jj * 2048, &a[jj * 8], sc);
}
template <int H, bool IS_Q>
__device__ __forceinline__ void stage_t3(const Ctx& c, const float (&a)[64], float sc) {
  const uint32_t off = stage_off(c), r8 = (off >> 7) & 7;
  const uint32_t t3 = c.sb + QBUF_OFF + 3 * 16384 + H * 4096 + (IS_Q ? off ^ ((r8 ^ q3_swz(r8)) << 4) : off);
  proj_store16(t3, &a[32], sc);
  proj_store16(t3 + 2048, &a[40], sc);
}

template <int WG, int h, int NW = 4>
__device__ __forceinline__ void load_part(const Ctx& c, Ring r, uint32_t (&q)[32]) {
  uint32_t n = 0;
  while (NW && !__all_sync(0xffffffffu, peek<NW>(c, r))) {
    if (++n > (1u << 26)) __trap();
  }
  const int lane = c.lane, mi = lane >> 3, r8 = lane & 7;
  if (WG) { r.next(); r.next(); }
  const uint32_t off = c.sb + (WG ? stage_off(c) : (16 * c.warp + (mi & 1) * 8 + r8) * 128), t0 = off + r.slot * SLOT;
  r.next();
  const uint32_t t1 = off + r.slot * SLOT;
#pragma unroll
    for (int jj = 0; jj < (WG ? 6 : 8); jj++) {
      uint32_t* p = &q[4 * jj];
      if (WG) asm volatile("ldmatrix.sync.aligned.m8n8.x4.trans.shared.b16 {%0, %1, %2, %3}, [%4];" : "=r"(p[0]), "=r"(p[1]), "=r"(p[2]), "=r"(p[3])
                           : "r"((jj < 4 ? t0 + h * 8192 : t1 + h * 4096) + (jj & 3) * 2048) : "memory");
      else ldsm4((h ? t1 : t0) + (jj >> 2) * 8192 + (((((2 * jj) & 7) + (mi >> 1)) ^ r8) << 4), p[0], p[1], p[2], p[3]);
    }
}
template <int WG>
__device__ __forceinline__ void add_part(const Ctx& c, const uint32_t (&q)[32], float (&a)[64]) {
  const uint32_t one = (c.lane >> 3) == (c.lane & 3) ? 0x3f80u << (c.lane & 4) * 4 : 0;
#pragma unroll
  for (int i = 0; i < (WG ? 12 : 16); i++)
    asm("mma.sync.aligned.m16n8k8.row.col.f32.bf16.bf16.f32 {%0, %1, %2, %3}, {%4, %5}, {%6}, {%0, %1, %2, %3};"
        : "+f"(a[4 * i]), "+f"(a[4 * i + 1]), "+f"(a[4 * i + 2]), "+f"(a[4 * i + 3]) : "r"(q[2 * i]), "r"(q[2 * i + 1]), "r"(one));
}

struct RowSum { float l0, l1; };
__device__ __forceinline__ const char* o_addr(uint32_t item, int row, int lane) {
  return reinterpret_cast<const char*>(g_o) + (((item >> 10) * (2 * SQ) + row) * 128 + (lane ^ (lane >> 3)) * 16);
}
__device__ __forceinline__ void o_stg(const char* p, int i, const uint32_t* q) {
  asm volatile("st.global.v4.b32 [%0], {%1, %2, %3, %4};"
               ::"l"(p + (i >> 1) * (SQ * 128) + (i & 1) * 512), "r"(q[0]), "r"(q[1]), "r"(q[2]), "r"(q[3]) : "memory");
}
template <int MODE, int I0 = 0, int NI = 4>
__device__ __forceinline__ void o_emit(const char* p, const float (&o)[64], float inv) {
#pragma unroll
  for (int i = I0; i < I0 + NI; i++) {
    uint32_t q[4];
#pragma unroll
    for (int j = 0; j < 4; j++) q[j] = pack_bf16(o[16 * i + 4 * j + 2 * MODE] * inv, o[16 * i + 4 * j + 2 * MODE + 1] * inv);
    o_stg(p, i, q);
  }
}
__device__ __forceinline__ void o_done(const Ctx& c) {
  __syncwarp();
  mbar_arrive_warp(c.sb + BAR_OUT);
  __syncwarp();
}
template <int WG>
__device__ __forceinline__ void o_first(const Ctx& c, uint32_t item, float (&o)[64], const RowSum& inv, uint32_t (&q)[32]) {
  const char* p = o_addr(item, WG ? 192 + 8 * c.warp : 64 + 16 * c.warp, c.lane);
  reg_fence(o);
#pragma unroll
  for (int j = 0; j < 16; j++) {
    if (WG) q[j] = pack_bf16((o[4 * j] + o[4 * j + 2]) * inv.l0, (o[4 * j + 1] + o[4 * j + 3]) * inv.l0);
    else q[j] = pack_bf16(o[4 * j] * inv.l0, o[4 * j + 1] * inv.l0);
    if (!WG && (j & 3) == 3 && (j >> 2) < 8 - LATE0) o_stg(p, j >> 2, q + j - 3);
  }
#pragma unroll
  for (int j = 0; j < 16; j++) {
    if (!WG) q[16 + j] = pack_bf16(o[4 * j + 2] * inv.l1, o[4 * j + 3] * inv.l1);
    if ((j & 3) == 3 && (j >> 2) < 4 - (WG ? LATE1 : LATE0)) o_stg(WG ? p : p + 1024, j >> 2, q + (WG ? 0 : 16) + j - 3);
  }
}
template <int WG>
__device__ __forceinline__ void o_rest(const Ctx& c, uint32_t item, uint32_t (&q)[32]) {
  const char* p = o_addr(item, WG ? 192 + 8 * c.warp : 64 + 16 * c.warp, c.lane);
#pragma unroll
  for (int i = WG ? 4 - LATE1 : 8 - LATE0; i < (WG ? 4 : 8); i++) o_stg(p + (i >> 2) * 1024, i & 3, q + 4 * i);
}
template <int K0, int K1>
__device__ __forceinline__ void o_piece(const Ctx& c, const char* p, int k, const float (&o)[64], const RowSum& inv) {
  constexpr int NI = 8 / O_STEPS, M = K0 * NI / 4;
  if constexpr (K1 - K0 == 1) {
    o_emit<M, K0 * NI % 4, NI>(p + M * 1024, o, M ? inv.l1 : inv.l0);
    if (K1 == O_STEPS) o_done(c);
  } else {
    if (k <= (K0 + K1) / 2) o_piece<K0, (K0 + K1) / 2>(c, p, k, o, inv); else o_piece<(K0 + K1) / 2, K1>(c, p, k, o, inv);
  }
}
template <int WG>
__device__ __forceinline__ void o_second(const Ctx& c, uint32_t item, int k, float (&o)[64], const RowSum& inv) {
  reg_fence(o);
  o_piece<0, O_STEPS>(c, o_addr(item, 128 * WG + 16 * c.warp, c.lane0 + (k >> 8)), k, o, inv);
}
template <int WG>
__device__ __forceinline__ void release_q(const Ctx& c) {
#pragma unroll
  for (int t = 0; t < 2; t++)
    if (c.lead) asm volatile("mbarrier.arrive.shared::cta.b64 _, [%0], 2;" ::"r"(c.sb + BAR_EMPTY + (NS + 2 * WG + t) * 8) : "memory");
  __syncwarp();
}
struct Slots { uint32_t w, x, o, po; };
template <int WG>
__device__ __forceinline__ void acc_fence(float (&a)[64]) {
#pragma unroll
  for (int i = 0; i < (WG ? 48 : 64); i++) asm volatile("" : "+f"(a[i])::"memory");
}
template <int WG>
__device__ __forceinline__ void begin_acquire(const Ctx& c, Ring& r, Slots& h, bool wait) {
  const uint32_t s0 = r.slot, p0 = r.phase, f = c.sb + BAR_FULL;
  r.next();
  const uint32_t p1 = r.phase;
  h.w = r.slot; r.next();
  h.x = WG ? r.slot : s0; h.o = WG ? s0 : r.slot; h.po = r.phase;
  if (wait) { if (WG) mbar_wait3_w(f + s0 * 8, p0, f + h.w * 8, p1, f + h.x * 8, r.phase); else mbar_wait2_w(f + s0 * 8, p0, f + h.w * 8, p1); }
  r.next();
}
template <int WG>
__device__ __forceinline__ void proj_begin(const Ctx& c, Ring& r, float (&a0)[64], Slots& h, bool wait, uint32_t sw) {
  begin_acquire<WG>(c, r, h, wait);
  proj_half<WG, true, 0>(c, a0, h.w, h.x, sw);
  if (WG) release(c, h.o);
}
template <int WG>
__device__ __forceinline__ void proj_main(Ctx& c, Ring& r, float (&a0)[64], float (&a1)[64], Slots& h, int n, uint32_t sw, int unit,
                                          uint32_t item, int nq, float (&o1)[64], const RowSum& inv) {
  constexpr bool DEEP = (PDEPTH >> WG) & 1;
  int ks = 1;
#pragma unroll 1
  do {
    const Slots p = h;
    const uint32_t b = borrow(ks, n), tile = NS + (WG ? 3 - b : b), f = c.sb + BAR_FULL;
    const uint32_t s0 = b != 2 ? tile : r.slot, p0 = b != 2 ? (r.xp >> b) & 1 : r.phase;
    r.next_if(b == 2);
    const uint32_t p1 = r.phase;
    h.w = r.slot; r.next();
    const uint32_t s2 = b != 2 ? tile : r.slot;
    h.po = b != 2 ? p0 : r.phase;
    r.next_if(b == 2);
    r.xp ^= 1 << b;
    h.x = WG ? s2 : s0; h.o = WG ? s0 : s2;
    mbar_wait3_w(f + s0 * 8, p0, f + h.w * 8, p1, f + (WG ? s2 : p.o) * 8, WG ? h.po : p.po);
    if (DEEP) {
      proj_half<WG, false, 0>(c, a0, h.w, h.x, sw);
      release(c, WG ? h.o : p.o);
      wg_wait<1>();
      release(c, p.x); release(c, p.w);
    } else {
      release(c, WG ? h.o : p.o);
      wg_wait<0>();
      release(c, p.x); release(c, p.w);
      proj_half<WG, false, 0>(c, a0, h.w, h.x, sw);
    }
    proj_half<WG, false, 1>(c, a1, h.w, h.x, sw);
    if (ks <= nq) o_second<WG>(c, item, ks, o1, inv);
  } while (++ks != n);
  {
    const uint32_t e0 = c.sb + BAR_EMPTY + (NS + 3 * WG) * 8, e1 = c.sb + BAR_EMPTY + (NS + 1 + WG) * 8;
    const uint32_t p0 = (r.xp ^ unit ^ 1) & 1, p1 = ((r.xp >> 1) ^ unit ^ 1) & 1;
    const uint32_t k0 = sw ? e0 : c.sb + BAR_FULL + r.slot * 8, pk = sw ? p0 : r.phase;
    uint32_t cnt = 0;
    while (!__all_sync(0xffffffffu, mbar_try(e0, p0) & mbar_try(e1, p1) & mbar_try(k0, pk) & (WG || mbar_try(c.sb + BAR_FULL + h.o * 8, h.po)))) {
      if (++cnt > (1u << 22)) __trap();
    }
  }
  c.lane = c.lane0 + (h.w >> 5);
  if (!WG) release(c, h.o);
}
template <int WG>
__device__ __forceinline__ void proj_end(const Ctx& c, float (&a1)[64], const Slots& h) {
  wg_wait<0>();
  acc_fence<WG>(a1);
  release(c, h.x); release(c, h.w);
}
__device__ __forceinline__ uint32_t get_desc(const Ctx& c, int i) {
  uint32_t d;
  mbar_wait_w(c.sb + BAR_DESC, (i - 1) & 1);
  asm volatile("ld.volatile.shared.u32 %0, [%1];" : "=r"(d) : "r"(c.sb + DESC_OFF + (i & 3) * 4) : "memory");
  return __shfl_sync(0xffffffffu, d, 0);
}

__device__ __forceinline__ float quad_max(float x) {
  x = fmaxf(x, __shfl_xor_sync(0xffffffffu, x, 1));
  return fmaxf(x, __shfl_xor_sync(0xffffffffu, x, 2));
}
__device__ __forceinline__ float quad_sum(float x) {
  x += __shfl_xor_sync(0xffffffffu, x, 1);
  return x + __shfl_xor_sync(0xffffffffu, x, 2);
}
template <bool SP, bool FIRST>
__device__ __forceinline__ void exps(const Ctx& c, const float (&s)[32], uint32_t (&p)[SP ? 8 : 16], RowSum& st) {
  if constexpr (SP) {
    uint32_t q[8];
    float t;
#pragma unroll
    for (int j = 0; j < 8; j++) {
      const float e0 = ex2(s[4 * j] + s[4 * j + 2]), e1 = ex2(s[4 * j + 1] + s[4 * j + 3]);
      if (j == 0) t = e0 + e1; else t += e0 + e1;
      q[j] = pack_bf16(e0, e1);
    }
    const bool odd = c.src & 2;
#pragma unroll
    for (int g = 0; g < 4; g++) {
      p[2 * g] = __shfl_sync(0xffffffffu, odd ? q[2 * g + 1] : q[2 * g], c.src);
      p[2 * g + 1] = __shfl_sync(0xffffffffu, odd ? q[2 * g] : q[2 * g + 1], c.src ^ 1);
    }
    st.l0 = FIRST ? t : st.l0 + t;
  } else {
    float t0, t1;
#pragma unroll
    for (int j = 0; j < 8; j++) {
      const float e0 = ex2(s[4 * j]), e1 = ex2(s[4 * j + 1]), e2 = ex2(s[4 * j + 2]), e3 = ex2(s[4 * j + 3]);
      if (j == 0) { t0 = e0 + e1; t1 = e2 + e3; } else { t0 += e0 + e1; t1 += e2 + e3; }
      p[2 * j] = pack_bf16(e0, e1);
      p[2 * j + 1] = pack_bf16(e2, e3);
    }
    st.l0 = FIRST ? t0 : st.l0 + t0;
    st.l1 = FIRST ? t1 : st.l1 + t1;
  }
}
template <bool SP>
__device__ __forceinline__ bool finish_sums(RowSum& st) {
  const float a = quad_sum(st.l0), b = SP ? a : quad_sum(st.l1);
  st.l0 = __fdividef(1.f, a); st.l1 = __fdividef(1.f, b);
  return !(a >= SUM_LO && a <= SUM_HI && b >= SUM_LO && b <= SUM_HI);
}
template <bool SP, bool INIT, int SITE, bool COMMIT = true, int RM = 0>
__device__ __forceinline__ void issue_qk(const Ctx& c, float (&s)[32], const uint32_t (&qs)[32], uint32_t dq, uint32_t dk) {
  uint64_t a = desc64(dq, dhi<SITE & 1>(dk)), b = desc64(dk, dhi<1 - (SITE & 1)>(dk) + 64);
  if (SP) {
    if (INIT) wgmma_qk_sp_init(s, qs[0], qs[1], qs[2], qs[3], b, 0, c.mqk); else wgmma_qk_sp(s, qs[0], qs[1], qs[2], qs[3], b, 0, c.mqk);
#pragma unroll
    for (int k = 1; k < 4; k++) { dadd(b, k == 2 ? 60 : 4); wgmma_qk_sp(s, qs[4 * k], qs[4 * k + 1], qs[4 * k + 2], qs[4 * k + 3], b, 1, c.mqk); }
  } else {
    if (RM & 1) wgmma_qk_rs(s, qs[0], qs[1], qs[2], qs[3], b, 0); else if (INIT) wgmma_qk_init(s, a, b, 0); else wgmma_qk(s, a, b, 0);
#pragma unroll
    for (int k = 1; k < 8; k++) {
      dadd(a, k == 4 ? 506 : 2); dadd(b, k == 4 ? 58 : 2);
      if (RM >> k & 1) wgmma_qk_rs(s, qs[4 * k], qs[4 * k + 1], qs[4 * k + 2], qs[4 * k + 3], b, 1); else wgmma_qk(s, a, b, 1);
    }
  }
  if (COMMIT) wg_commit();
}
template <bool SP, bool ACC, int SITE, bool SPLIT = false>
__device__ __forceinline__ void issue_pv(const Ctx& c, float (&o)[64], const uint32_t (&p)[SP ? 8 : 16], uint32_t dv) {
  uint64_t b = desc64(dv, dhi<SITE & 1>(dv) + 64);
  if constexpr (SP) {
    if (ACC) wgmma_pv_sp(o, p[0], p[1], p[2], p[3], b, 1, c.mpv); else wgmma_pv_sp_init(o, p[0], p[1], p[2], p[3], b, 0, c.mpv);
    if (SPLIT) wg_commit();
    dadd(b, 512);
    wgmma_pv_sp(o, p[4], p[5], p[6], p[7], b, 1, c.mpv);
  } else {
    if (ACC) wgmma_pv(o, p[0], p[1], p[2], p[3], b, 1); else wgmma_pv_init(o, p[0], p[1], p[2], p[3], b, 0);
#pragma unroll
    for (int k = 1; k < 4; k++) { dadd(b, 256); wgmma_pv(o, p[4 * k], p[4 * k + 1], p[4 * k + 2], p[4 * k + 3], b, 1); }
  }
  wg_commit();
}
__device__ __forceinline__ void pack_rows(const float (&o)[64], float sc, uint32_t (&q)[32]) {
#pragma unroll
  for (int j = 0; j < 32; j++) q[j] = pack_bf16(o[2 * j] * sc, o[2 * j + 1] * sc);
}
template <int MASK = 255>
__device__ __forceinline__ void stage_rows(const Ctx& c, uint32_t tile_addr, const uint32_t (&q)[32]) {
  const int lane = c.lane, mi = lane >> 3, r8 = lane & 7;
  const uint32_t row_addr = tile_addr + (16 * c.warp + (mi & 1) * 8 + r8) * 128;
#pragma unroll
  for (int jj = 0; jj < 8; jj++)
    if (MASK >> jj & 1) stsm4(row_addr + (jj >> 2) * 8192 + (((((2 * jj) & 7) + (mi >> 1)) ^ r8) << 4), q[4 * jj], q[4 * jj + 1], q[4 * jj + 2], q[4 * jj + 3]);
}
__device__ __forceinline__ void stage_rows(const Ctx& c, uint32_t tile_addr, const float (&o)[64], float sc) {
  uint32_t q[32];
  pack_rows(o, sc, q);
  stage_rows(c, tile_addr, q);
}
template <int WG, int H>
__device__ __forceinline__ void stage_out(const Ctx& c, const float (&a)[64]) {
  if (WG) { stage_t3<H, false>(c, a, 1.f); if (H) staged(c, 0); stage_t2<H>(c, a, 1.f); }
  else stage_rows(c, c.sb + QBUF_OFF + H * 16384, a, 1.f);
  if (H || !WG) staged(c, H);
}
template <int SITE>
__device__ __forceinline__ void issue_qk_rs(float (&s)[32], uint32_t (&q)[32], uint32_t dk) {
  uint64_t b = desc64(dk, dhi<SITE>(dk) + 64);
  reg_fence(q);
  wg_fence();
  wgmma_qk_rs_init(s, q[0], q[1], q[2], q[3], b, 0);
#pragma unroll
  for (int k = 1; k < 8; k++) { dadd(b, k == 4 ? 58 : 2); wgmma_qk_rs(s, q[4 * k], q[4 * k + 1], q[4 * k + 2], q[4 * k + 3], b, 1); }
  wg_commit();
}

__device__ __forceinline__ void redo_tile(const Ctx& c, uint32_t q_addr, uint32_t half, const __nv_bfloat16* kp, const __nv_bfloat16* vp,
                                          uint32_t item, int row) {
  float o[64];
  const int lane = lane_now(), g = lane >> 2, cc = lane & 3, mi = lane >> 3, r8 = lane & 7;
  const uint32_t qa = q_addr + (half == 4096 ? 8 * c.warp + r8 : 16 * c.warp + (mi & 1) * 8 + r8) * 128, swz = half == 4096 ? q3_swz(r8) : r8;
  const uint32_t* kq = reinterpret_cast<const uint32_t*>(kp + g * DH) + cc;
  const unsigned short* vq = reinterpret_cast<const unsigned short*>(vp + 2 * cc * DH) + g;
  float m0 = -INFINITY, m1 = -INFINITY, l0 = 0.f, l1 = 0.f;
#pragma unroll
  for (int i = 0; i < 64; i++) o[i] = 0.f;
#pragma unroll 1
  for (int kb = 0; kb < SK / 16; kb++) {
    float z[8] = {0.f, 0.f, 0.f, 0.f, 0.f, 0.f, 0.f, 0.f};
#pragma unroll 2
    for (int kk = 0; kk < 8; kk++) {
      uint32_t a0, a1, a2, a3;
      ldsm4(qa + (kk >> 2) * half + ((((kk & 3) * 2 + (mi >> 1)) ^ swz) << 4), a0, a1, a2, a3);
      const uint32_t* kr = kq + kb * (16 * DH / 2) + kk * 8;
      mma16816(z[0], z[1], z[2], z[3], a0, a1, a2, a3, __ldg(kr), __ldg(kr + 4));
      mma16816(z[4], z[5], z[6], z[7], a0, a1, a2, a3, __ldg(kr + 8 * DH / 2), __ldg(kr + 8 * DH / 2 + 4));
    }
    const float n0 = fmaxf(m0, quad_max(fmaxf(fmaxf(z[0], z[1]), fmaxf(z[4], z[5]))));
    const float n1 = fmaxf(m1, quad_max(fmaxf(fmaxf(z[2], z[3]), fmaxf(z[6], z[7]))));
    const float al0 = ex2(m0 - n0), al1 = ex2(m1 - n1);
    m0 = n0; m1 = n1;
#pragma unroll
    for (int i = 0; i < 8; i++) z[i] = ex2(z[i] - ((i & 2) ? n1 : n0));
    l0 = l0 * al0 + (z[0] + z[1]) + (z[4] + z[5]);
    l1 = l1 * al1 + (z[2] + z[3]) + (z[6] + z[7]);
    const uint32_t a0 = pack_bf16(z[0], z[1]), a1 = pack_bf16(z[2], z[3]), a2 = pack_bf16(z[4], z[5]), a3 = pack_bf16(z[6], z[7]);
    const unsigned short* vr = vq + kb * (16 * DH);
#pragma unroll
    for (int nb = 0; nb < 16; nb++) {
      o[4 * nb] *= al0; o[4 * nb + 1] *= al0; o[4 * nb + 2] *= al1; o[4 * nb + 3] *= al1;
      const uint32_t b0 = __ldg(vr + nb * 8) | ((uint32_t)__ldg(vr + nb * 8 + DH) << 16);
      const uint32_t b1 = __ldg(vr + nb * 8 + 8 * DH) | ((uint32_t)__ldg(vr + nb * 8 + 9 * DH) << 16);
      mma16816(o[4 * nb], o[4 * nb + 1], o[4 * nb + 2], o[4 * nb + 3], a0, a1, a2, a3, b0, b1);
    }
  }
  const char* p = o_addr(item, row, lane);
  o_emit<0>(p, o, __fdividef(1.f, quad_sum(l0)));
  o_emit<1>(half == 4096 ? p : p + 1024, o, __fdividef(1.f, quad_sum(l1)));
}

template <bool SPA, bool SPB, int SITE, int ID>
__device__ __forceinline__ void batch(const Ctx& c, float (&s)[32], const uint32_t (&qs)[32], uint32_t dq, uint32_t dk, float (&ob)[64],
                                      uint32_t (&pb)[SPB ? 8 : 16], uint32_t dv) {
  if constexpr (SPA) {
    reg_fence(pb);
    wg_fence();
    issue_pv<SPB, true, ID>(c, ob, pb, dv);
    issue_qk<SPA, false, ID>(c, s, qs, dq, dk);
  } else {
    constexpr bool EARLY = ((QK_EARLY_MASK >> (SITE + (SPB ? 2 : 0))) & 1) != 0;
    if (!EARLY) reg_fence(pb);
    wg_fence();
    issue_qk<SPA, false, ID, !SPB, SITE ? RM0 : SPB ? RM2 : RM1>(c, s, qs, dq, dk);
    if (EARLY) { reg_fence(pb); wg_fence(); }
    issue_pv<SPB, true, ID, SPB>(c, ob, pb, dv);
  }
}

template <bool SP0>
__device__ __forceinline__ bool attention(Ctx& c, Ring& r, int unit, uint32_t& d, const float (&a0)[64], float (&o0)[64], float (&o1)[64],
                                          RowSum& st0, RowSum& st1, const Slots& h, uint32_t (&q1)[32]) {
  constexpr bool SP1 = false;
  if (SP0) { c.mqk = META_QK + (d >> 28); c.mpv = META_PV + (d >> 28); asm volatile("" : "+r"(c.mqk), "+r"(c.mpv)); }
  if (SP0) c.src = (c.lane & 28) | ((c.lane & 1) << 1) | ((c.lane >> 1) & 1);
  float s[32];
  uint32_t p0[SP0 ? 8 : 16], p1[16];
  const uint32_t q0a = c.sb + QBUF_OFF + (SP0 ? 3 : 0) * 16384, q1a = c.sb + QBUF_OFF + (SP0 ? 2 : 1) * 16384;
  const uint32_t dq0 = sdesc(SB0 + QBUF_OFF, 0), dq1 = sdesc(SB0 + QBUF_OFF + (SP0 ? 2 : 1) * 16384, 0);
  uint32_t sk = acquire(c, r, true), sv, sn;
  uint32_t qs[32];
  float s1[32];
  if (SP0) {
    stage_t3<0, true>(c, a0, SM_C);
    stage_t2<0>(c, a0, SM_C);
    proj_end<1>(c, o0, h);
    stage_t3<1, true>(c, o0, SM_C);
    stage_t2<1>(c, o0, SM_C);
    bar_sync(5, 128);
    const int g = c.lane >> 2, cc = c.lane & 3;
    const uint32_t qa = q0a + (8 * c.warp + g) * 128 + (cc & 1) * 8;
#pragma unroll
    for (int k = 0; k < 8; k++)
      asm volatile("ld.shared.v2.u32 {%0, %1}, [%2];" : "=r"(qs[2 * k]), "=r"(qs[2 * k + 1])
                   : "r"(qa + (k >> 2) * 4096 + ((((k & 3) * 2 + (cc >> 1)) ^ q3_swz(g)) << 4)) : "memory");
    fence_async_smem();
    bar_sync(1, 256);
    wg_fence();
    issue_qk<SP1, true, 1>(c, s1, qs, dq1, sdesc(SB0 + sk * SLOT, 0));
#pragma unroll
    for (int k = 0; k < 8; k++)
      if (RM2 >> k & 1) ldsm4(q1a + (k >> 2) * 8192 + (16 * c.warp + (c.lane & 15)) * 128 + (((2 * (k & 3) + (c.lane >> 4)) ^ (c.lane & 7)) << 4),
                              q1[4 * k], q1[4 * k + 1], q1[4 * k + 2], q1[4 * k + 3]);
#pragma unroll
    for (int k = 0; k < 16; k++) asm volatile("" : "+r"(qs[k])::"memory");
    wg_fence();
    issue_qk<SP0, true, 0>(c, s, qs, dq0, sdesc(SB0 + sk * SLOT, 0));
    const bool have = peek<2>(c, r);
    wg_wait<1>();
    reg_fence(s1);
    exps<SP1, true>(c, s1, p1, st1);
    sched_fence<11>(sk, p1);
    acquire2(c, r, sv, sn, __all_sync(0xffffffffu, have));
    wg_wait<0>();
    wg_fence();
    issue_pv<SP1, false, 1>(c, o1, p1, sdesc(SB0 + sv * SLOT, 1024));
    if (LAG_BAR & 1) asm volatile("bar.arrive 4, 256;" ::: "memory");
    sched_fence<12>(sk, s);
    release(c, sk);
    sk = sn;
    exps<SP0, true>(c, s, p0, st0);
    reg_fence(p0);
    wg_fence();
    issue_pv<SP0, false, 0>(c, o0, p0, sdesc(SB0 + sv * SLOT, 1024));
    issue_qk<SP0, true, 2>(c, s, qs, dq0, sdesc(SB0 + sk * SLOT, 0));
    sn = acquire(c, r);
    wg_wait<0>();
    reg_fence(s);
  } else {
    pack_rows(a0, SM_C, qs);
    stage_rows(c, q0a, qs);
    proj_end<0>(c, o1, h);
    float sc = SM_C;
    issue_qk_rs<0>(s, qs, sdesc(SB0 + sk * SLOT, 0));
    sched_fence<0>(sk, sc);
    pack_rows(o1, sc, q1);
    stage_rows<~RM1>(c, q1a, q1);
    issue_qk_rs<1>(s1, q1, sdesc(SB0 + sk * SLOT, 0));
    asm volatile("bar.arrive 1, 256;" ::: "memory");
    bool have = peek<2>(c, r);
    wg_wait<1>();
    reg_fence(s);
    exps<SP0, true>(c, s, p0, st0);
    sched_fence<1>(sk, p0);
    acquire2(c, r, sv, sn, __all_sync(0xffffffffu, have));
    wg_wait<0>();
    reg_fence(s1);
    fence_async_smem();
    __syncwarp();
    wg_fence();
    issue_qk<SP0, false, 2, true, RM0>(c, s, qs, dq0, sdesc(SB0 + sn * SLOT, 0));
    issue_pv<SP0, false, 0>(c, o0, p0, sdesc(SB0 + sv * SLOT, 1024));
    sched_fence<2>(sk, s1);
    release(c, sk);
    have = peek<1>(c, r);
    sk = sn;
    exps<SP1, true>(c, s1, p1, st1);
    reg_fence(p1);
    wg_fence();
    issue_pv<SP1, false, 1>(c, o1, p1, sdesc(SB0 + sv * SLOT, 1024));
    sn = acquire(c, r, __all_sync(0xffffffffu, have));
    if (LAG_BAR & 1) bar_sync(4, 256);
    wg_wait<1>();
    reg_fence(s);
  }
#pragma unroll 1
  for (int j = 1; j < 15; j++) {
    const uint32_t sv_prev = sv, sk_prev = sk;
    sv = sn;
    const uint32_t dv = sdesc(SB0 + sv * SLOT, 1024);
    reg_fence(p0);
    exps<SP0, false>(c, s, p0, st0);
    batch<SP1, SP0, 0, 3>(c, s, q1, dq1, sdesc(SB0 + sk * SLOT, 0), o0, p0, dv);
    sk = acquire(c, r);
    wg_wait<1>();
    reg_fence(s); reg_fence(p1);
    release(c, sv_prev); release(c, sk_prev);
    exps<SP1, false>(c, s, p1, st1);
    batch<SP0, SP1, 1, 4>(c, s, qs, dq0, sdesc(SB0 + sk * SLOT, 0), o1, p1, dv);
    sn = acquire(c, r);
    if (SP0) wg_wait<0>(); else wg_wait<1>();
    reg_fence(s);
  }
  const uint32_t sv_prev = sv;
  sv = sn;
  const uint32_t dv = sdesc(SB0 + sv * SLOT, 1024);
  reg_fence(p0);
  exps<SP0, false>(c, s, p0, st0);
  batch<SP1, SP0, 0, 5>(c, s, q1, dq1, sdesc(SB0 + sk * SLOT, 0), o0, p0, dv);
  asm volatile("ld.volatile.shared.u32 %0, [%1];" : "=r"(d) : "r"(c.sb + DESC_OFF + ((unit + 1) & 3) * 4) : "memory");
  const bool have = peek<2 + SP0>(c, r);
  wg_wait<1>();
  reg_fence(s); reg_fence(p1);
  release(c, sv_prev); release(c, sk);
  exps<SP1, false>(c, s, p1, st1);
  reg_fence(p1);
  wg_fence();
  issue_pv<SP1, true, 2>(c, o1, p1, dv);
  if (SP0) sched_fence<6>(sk, st0.l0, st1.l0, st1.l1); else sched_fence<5>(sk, st0.l0, st0.l1, st1.l0, st1.l1);
  c.lane = c.lane0 + (sk >> 5);
  const bool bad = finish_sums<SP0>(st0) | finish_sums<SP1>(st1);
  uint32_t any;
  asm volatile("{\n.reg .pred p, q;\nsetp.ne.u32 p, %1, 0;\nbar.red.or.pred q, %2, 128, p;\nselp.u32 %0, 1, 0, q;\n}"
               : "=r"(any) : "r"((uint32_t)bad), "n"(2 + SP0) : "memory");
  any = __any_sync(0xffffffffu, any);
  d = __shfl_sync(0xffffffffu, d, 0);
  if (d < (2u << 30) && !__all_sync(0xffffffffu, have)) { Ring t = r; Slots u; begin_acquire<SP0>(c, t, u, true); }
  wg_wait<0>();
  reg_fence(o0); reg_fence(o1);
  release(c, sv);
  return any;
}

template <int WG>
__device__ __forceinline__ void consumer(Ctx c, const __nv_bfloat16* const* kv) {
  asm volatile("setmaxnreg.inc.sync.aligned.u32 %0;" ::"n"(WG ? REG_C : 504 - REG_C - REG_P));
  c.wg = WG;
  Ring r{0, 0, 0};
  float a0[64], a1[64], o1[64];
  Slots h;
  RowSum inv0, inv1;
  uint32_t oq[32];
  uint32_t d = first_entry(blockIdx.x, FIRST_LO, FIRST_HI) * 1025, dc = 0, sw;
  int i = 0, nq;
begin:
  sw = d & (1u << 30);
  proj_begin<WG>(c, r, a0, h, true, sw);
  proj_half<WG, true, 1>(c, a1, h.w, h.x, sw);
  nq = 0;
#pragma unroll
  for (int k = 0; k < 64; k++) asm volatile("" : "=f"(o1[k]));
  asm volatile("" : "=f"(inv1.l0), "=f"(inv1.l1));
  while (true) {
    proj_main<WG>(c, r, a0, a1, h, d >> 30 ? ((d >> 16) & 63) + 1 : DM / 64, sw, i, dc, nq, o1, inv1);
    dc = d;
    if (d >> 30) goto out_tile;
    wg_wait<1>();
    acc_fence<WG>(a0);
    if (WG ? attention<WG>(c, r, i, d, a0, a1, o1, inv0, inv1, h, oq) : attention<WG>(c, r, i, d, a0, o1, a1, inv1, inv0, h, oq)) goto redo;
    if (d >= (2u << 30)) break;
    sw = d & (1u << 30);
    proj_begin<WG>(c, r, a0, h, false, sw);
    release_q<WG>(c);
    if (WG) sched_fence<8>(h.w, inv0.l0); else sched_fence<7>(h.w, inv0.l0, inv0.l1);
    o_first<WG>(c, dc, a1, inv0, oq);
    sched_fence<9>(h.w, inv1.l0);
    proj_half<WG, true, 1>(c, a1, h.w, h.x, sw);
    o_rest<WG>(c, dc, oq);
    nq = O_STEPS;
    i++;
  }
  release_q<WG>(c);
  o_first<WG>(c, dc, a1, inv0, oq);
  o_rest<WG>(c, dc, oq);
#pragma unroll
  for (int k = 1; k <= O_STEPS; k++) o_second<WG>(c, dc, k, o1, inv1);
next:
  if ((d >> 30) != 2) {
    i++;
    r.uniform();
    goto begin;
  }
  return;
out_tile:
  if (d & 96) goto finish;
  d = get_desc(c, i + 1);
  wg_wait<1>();
  acc_fence<WG>(a0);
  stage_out<WG, 0>(c, a0);
  proj_end<WG>(c, a1, h);
  stage_out<WG, 1>(c, a1);
  goto next;
finish:
  {
    uint32_t q[32];
#pragma unroll 1
    for (int k = (d >> 5) & 3; k > 1; k--) {
      wg_wait<0>();
      acc_fence<WG>(a0); acc_fence<WG>(a1);
      if (k == ((d >> 5) & 3)) { release(c, h.x); release(c, h.w); }
      load_part<WG, 0>(c, r, q); add_part<WG>(c, q, a0);
      load_part<WG, 1, 0>(c, r, q); add_part<WG>(c, q, a1);
#pragma unroll
      for (int t = 0; t < 4; t++) { release(c, r.slot); r.next(); }
    }
    load_part<WG, 0, WG ? 4 : 1>(c, r, q);
    wg_wait<1>();
    acc_fence<WG>(a0);
    add_part<WG>(c, q, a0);
    stage_out<WG, 0>(c, a0);
    load_part<WG, 1, WG ? 0 : 2>(c, r, q);
    wg_wait<0>();
    acc_fence<WG>(a1);
    add_part<WG>(c, q, a1);
    stage_out<WG, 1>(c, a1);
    return;
  }
redo:
  {
    if (!WG) { stage_rows<RM1>(c, c.sb + QBUF_OFF + 16384, oq); __syncwarp(); }
    const size_t hoff = (size_t)(dc & 511) * (SK * DH);
    const int br = (dc >> 9) & 1;
#pragma unroll 1
    for (int part = 0; part < 2; part++) {
      const int t = WG ? 3 - part : part;
      redo_tile(c, c.sb + QBUF_OFF + t * 16384, t == 3 ? 4096 : 8192, kv[br] + hoff, kv[2 + br] + hoff, dc,
                t * 64 + (t == 3 ? 8 : 16) * c.warp);
    }
    o_done(c);
    release_q<WG>(c);
  }
  goto next;
}

template <bool SIMPLE>
__global__ void __launch_bounds__(384, 1) mha_fused_kernel(const __grid_constant__ Params P) {
  extern __shared__ __align__(1024) uint8_t smem_raw[];
  const uint32_t sbase = smem_u32(smem_raw);
  const int tid = threadIdx.x;
  const int wg = __shfl_sync(0xffffffffu, tid >> 7, 0);
  const int warp = __shfl_sync(0xffffffffu, (tid >> 5) & 3, 0);
  const int lane = tid & 31;
  const int cta = blockIdx.x;
  constexpr bool PAIR = !SIMPLE;

  const uint32_t d0 = first_entry(cta, FIRST_LO, FIRST_HI);
  const int wi = wg * 4 + warp;
  asm volatile(ELECT "prefetch.tensormap [%0];\n}" ::"l"(&P.x[0][0] + wi) : "memory");
  if ((sbase & 0xffffff) != SB0) __trap();
  if (wg < 2) {
    asm volatile(ELECT "mbarrier.init.shared::cta.b64 [%0], 1;\n}" ::"r"(sbase + BAR_FULL + wi * 8) : "memory");
    if (PAIR && (wi == 1 || wi == 4)) {
      fence_async_smem();
      tma_ld3_w(sbase + wi * SLOT, P.wq, 0, (wi / 3) * 64, (d0 & 31) * 2, sbase + BAR_FULL + wi * 8, 16384);
    }
#pragma unroll 1
    for (int b = BAR_OFF + 64 + wi * 8; b < DESC_OFF; b += 64)
      asm volatile(ELECT "mbarrier.init.shared::cta.b64 [%0], %1;\n}"
                   ::"r"(sbase + b), "r"(b < BAR_EMPTY || b >= BAR_DESC ? 1 : b >= BAR_STG && b < BAR_OUT ? 4 : 8) : "memory");
    asm volatile("fence.mbarrier_init.release.cluster;" ::: "memory");
    if (wi < 6) asm volatile(ELECT "prefetch.tensormap [%0];\n}" ::"l"(&P.x[0][0] + 12 + wi) : "memory");
  }
  if (PAIR) asm volatile("barrier.cluster.arrive.relaxed.aligned;" ::: "memory"); else __syncthreads();
#define INIT_DONE() if (PAIR) asm volatile("barrier.cluster.wait.aligned;" ::: "memory")

  if (wg == 2) {
    asm volatile("setmaxnreg.dec.sync.aligned.u32 %0;" ::"n"(REG_P));
    if (warp == 1) {
      const uint32_t qb = sbase + QBUF_OFF;
      const uint32_t ep = __shfl_sync(0xffffffffu, *(volatile unsigned*)&g_epoch + 1, 0);
      asm volatile("st.volatile.shared.u32 [%0], %1;" ::"r"(sbase + EPOCH_OFF), "r"(ep) : "memory");
      INIT_DONE();
      uint32_t dc = d0, qi = 0, piece = 0, na = 0;
      for (int i = 0; (dc >> 30) != 2; i++) {
        if (!(dc >> 30) && o_reuse<SIMPLE>((dc >> 5) & 31)) {
          const unsigned* rd = &g_rd[0][0] + ((dc & 1023) >> 2) - OR * 8;
          for (uint32_t n = 0; !__all_sync(0xffffffffu, reached(rd, ep * 5)); __nanosleep(300)) if (++n > (1u << 22)) __trap();
        }
        mbar_wait_w(sbase + BAR_GO, i & 1);
        if (piece == 0) {
          if (PAIR && (cta & 1)) {
            asm volatile(ELECT EXPECT("%0", "4") "mbarrier.arrive.shared::cluster.b64 _, [%1];\n}" ::"r"(sbase + BAR_MAIL), "r"(peer(sbase + BAR_MAIL)) : "memory");
            mbar_wait_w(sbase + BAR_MAIL, i & 1);
            qi = lds(sbase + EPOCH_OFF + 8);
          } else if (lane == 0) {
            qi = atomicAdd(&g_next, PAIR ? 2 : 1);
            if (qi == (SIMPLE ? Q_ALL : Q_RANGES) - (PAIR ? 2 : 1)) { g_next = 0; g_epoch = ep; }
          }
          qi = __shfl_sync(0xffffffffu, qi, 0);
          if (PAIR && !(cta & 1)) {
            mbar_wait_w(sbase + BAR_MAIL, i & 1);
            asm volatile(ELECT "st.async.shared::cluster.mbarrier::complete_tx::bytes.u32 [%0], %1, [%2];\n}"
                         ::"r"(peer(sbase + EPOCH_OFF + 8)), "r"(qi + 1), "r"(peer(sbase + BAR_MAIL)) : "memory");
          }
          qi += SIMPLE ? gridDim.x : NCTA;
        }
        uint32_t d;
        if (qi < (SIMPLE ? Q_ALL : Q_RANGES)) { d = c_sched.queue[qi]; if (d & 0x8000) d ^= (1u << 30) | (63u << 16) | 0x8000; else d |= o_slot<SIMPLE>(d >> 5) << 15 | (d & 31) << 10; }
        else if (SIMPLE) d = 2u << 30;
        else { const uint32_t e = qi - Q_RANGES, g = e / 5; d = c_sched.piece[g][piece++] | (g & 1 ? g * 5 + 4 - e : e - g * 5) << 8; }
        if ((d >> 30) == 1) {
          const uint32_t k0 = (d >> 22) & 63;
          const uint32_t run = __ffs(__ballot_sync(0xffffffffu, !reached(&g_cnt[d & 31][lane & 7], ep * 4)) & (0xffu << (k0 >> 3))) - 1;
          if (run <= (k0 + ((d >> 16) & 63)) >> 3) d |= run <= (k0 + O_STEPS) >> 3 ? (2u << 30) | 128 : 128;
        }
        asm volatile("st.volatile.shared.u32 [%0], %1;" ::"r"(sbase + DESC_OFF + ((i + 1) & 3) * 4), "r"(d) : "memory");
        __syncwarp();
        mbar_arrive_warp(sbase + BAR_DESC);
        const Work w = decode(dc);
        dc = d;
        if (w.kind == 0) {
          mbar_wait_w(sbase + BAR_OUT, na++ & 1);
          asm volatile(ELECT "red.release.gpu.global.add.u32 [%0], 1;\n}" ::"l"(&g_cnt[w.beta][w.sub >> 2]) : "memory");
          continue;
        }
        const bool fin = w.mode != 1;
        const CUtensorMap* m = fin ? P.out_st : P.o_st;
        const int c1 = fin ? (w.beta & 15) * SQ : 0;
        const int c2 = fin ? (w.beta >> 4) * (DM / 64) + w.sub * 2 : NBETA * 64 + w.range * 2;
        uint32_t pend = 0;
#pragma unroll 1
        for (int e = 0; e < 4; e++) {
          const int t = (ST_ORDER >> (4 * e)) & 3;
          mbar_wait_w(sbase + BAR_STG + (t ^ (t >> 1)) * 8, (i - na) & 1);
          tma_st3_w(m + (t == 3), qb + t * 16384, c1 + t * 64, c2);
          bulk_commit();
          if (e == 3 && w.mode == 1 && (d >> 30) == 2) {
            asm volatile("cp.async.bulk.wait_group 2;" ::: "memory");
            asm volatile(ELECT "st.release.gpu.global.u32 [%0], %1;\n}" ::"l"(&g_flag[w.range]), "r"(2 * ep - 1) : "memory");
          }
          if (pend && (d >> 30) != 2) {
            bulk_wait_read<1>();
            mbar_arrive8_w(pend);
          }
          pend = sbase + BAR_EMPTY + (NS + t) * 8;
          if ((ST_NOW >> e) & 1) {
            bulk_wait_read<0>();
            mbar_arrive8_w(pend);
            pend = 0;
          }
        }
        if (w.beta < N_EARLY) asm volatile(ELECT "red.relaxed.gpu.global.add.u32 [%0], 1;\n}" ::"l"(&g_rd[w.beta][7]) : "memory");
        asm volatile("cp.async.bulk.wait_group 0;" ::: "memory");
        if (w.mode == 1) asm volatile(ELECT "st.release.gpu.global.u32 [%0], %1;\n}" ::"l"(&g_flag[w.range]), "r"(2 * ep) : "memory");
      }
    } else
    if (warp == 0) {
      Ring r{PAIR ? 3 * N_FAST : 0, 1, 3};
      uint32_t d = d0;
      for (int i = 0;; i++) {
        const Work w = decode(d);
        if (w.kind == 2) break;
        const CUtensorMap* m = w.kind == 0 ? &P.wq[w.beta >> 4] : &P.wo[w.beta >> 4];
        if (i == 0) INIT_DONE();
        for (int ks = PAIR && i == 0 ? N_FAST : 0; ks < w.nsteps; ks++) {
          const uint32_t b = borrow(ks, w.nsteps);
          r.next_if(b == 2);
          const uint32_t bar = sbase + BAR_FULL + r.slot * 8;
          mbar_wait_w(bar + (BAR_EMPTY - BAR_FULL), r.phase);
          if (w.kind == 0) tma_ld3_w(sbase + r.slot * SLOT, m, 0, ks * 64, w.sub * 2, bar, 16384);
          else tma_ld_wo_w(sbase + r.slot * SLOT, m, w.sub * 128, (w.k0 + ks) * 2, bar);
          if (w.kind != 0 && w.beta < N_EARLY && (ks & 7) == 5 && ks > 5)
            asm volatile(ELECT "red.relaxed.gpu.global.add.u32 [%0], 1;\n}" ::"l"(&g_rd[w.beta][(ks >> 3) - 1]) : "memory");
          if (w.kind != 0 && ks == max(w.nsteps - GO_P, 4)) mbar_arrive_warp(sbase + BAR_GO);
          r.next(); r.next_if(b == 2);
        }
        if (w.kind == 0) {
          r.phase ^= 1; r.next(); r.next();
        } else if (w.mode == 2) {
          for (int k = 1; k <= ((d >> 5) & 3); k++) {
            bool all = false;
#pragma unroll 1
            for (int t = 0; t < 4; t++) {
              if (!(t & 1) && !all) {
                const uint32_t ep2 = 2 * lds(sbase + EPOCH_OFF);
                uint32_t v, n = 0;
                do {
                  asm volatile("ld.acquire.gpu.global.u32 %0, [%1];" : "=r"(v) : "l"(&g_flag[w.range + 5 * k]) : "memory");
                  v = __shfl_sync(0xffffffffu, v - ep2, 0);
                  if (++n > (1u << 24)) __trap();
                } while ((int)v < (t >> 1) - 1);
                all = v == 0;
                asm volatile("fence.proxy.async.global;" ::: "memory");
              }
              mbar_wait_w(sbase + BAR_EMPTY + r.slot * 8, r.phase);
              tma_ld3_w(sbase + r.slot * SLOT, &P.o_st[t == 3], 0, t * 64, NBETA * 64 + (w.range + 5 * k) * 2, sbase + BAR_FULL + r.slot * 8,
                        t == 3 ? 8192 : 16384);
              r.next();
            }
          }
        }
        mbar_wait_w(sbase + BAR_DESC, i & 1);
        d = __shfl_sync(0xffffffffu, lds(sbase + DESC_OFF + ((i + 1) & 3) * 4), 0);
      }
    } else {
      const int hi = warp - 2;
      uint64_t pol_stream;
      uint32_t rdy = 0;
      asm volatile("createpolicy.fractional.L2::evict_first.b64 %0, 1.0;" : "=l"(pol_stream));
      Ring r{PAIR ? 3 * N_FAST : 0, 1, 3};
      uint32_t d = d0;
      for (int i = 0;; i++) {
        const Work w = decode(d);
        if (w.kind == 2) break;
        const CUtensorMap* m = w.kind == 0 ? &P.x[hi][w.beta >> 4] : &P.o_ld[hi];
        int c1 = (w.kind == 0 ? (w.beta & 15) : o_slot<SIMPLE>(w.beta) * 64 + w.k0) * SQ + hi * 128;
        int k_wait = -1;
        const bool both = PAIR && (w.kind == 0 || w.sub != 4), mine = !both || hi == (cta & 1);
        if (w.kind != 0 && mine) {
          if (d & 128) k_wait = d >= (3u << 30) ? 0 : 8 - (w.k0 & 7);
          asm volatile("fence.proxy.async.global;" ::: "memory");
        }
        if (i == 0) INIT_DONE();
        for (int ks = PAIR && i == 0 ? N_FAST : 0; ks < w.nsteps; ks++) {
          if (ks == k_wait) {
            wait_count(&g_cnt[d & 31][(w.k0 + ks) >> 3], lds(sbase + EPOCH_OFF) * 4);
            asm volatile("fence.proxy.async.global;" ::: "memory");
            k_wait = ((w.k0 + ks) | 7) + 1 - w.k0;
          }
          const uint32_t b = borrow(ks, w.nsteps);
          const bool bo = b != 2;
          r.next_if(hi && !bo); r.next_if(hi && !bo);
          const uint32_t sl = bo ? NS + (b ^ (3 * hi)) : r.slot, bar = sbase + BAR_FULL + sl * 8;
          mbar_wait_w(bar + (BAR_EMPTY - BAR_FULL), bo ? (r.xp >> b) & 1 : r.phase);
          const uint32_t bytes = hi ? 96 * 128 : 128 * 128;
          const bool used = i > 0 || ks > 4;
          if (!mine) {
            asm volatile(ELECT "mbarrier.arrive.expect_tx.shared::cta.b64 _, [%0], %1;\n}" ::"r"(bar), "r"(bytes) : "memory");
            if (used) asm volatile(ELECT "mbarrier.arrive.shared::cluster.b64 _, [%0];\n}" ::"r"(peer(bar + (BAR_RDY - BAR_FULL))) : "memory");
            if ((d & 0xc000001e) == 8 && w.beta < NBETA - 2 && i > 0)
              asm volatile(ELECT "cp.async.bulk.prefetch.tensor.2d.L2.global [%0, {%1, %2}];\n}"
                           ::"l"(&P.x[hi][(w.beta + 2) >> 4]), "r"(ks * 64), "r"(((w.beta + 2) & 15) * SQ + hi * 128) : "memory");
          } else if (both) {
            if (used) {
              mbar_wait_w(bar + (BAR_RDY - BAR_FULL), (rdy >> sl) & 1);
              rdy ^= 1 << sl;
            }
            if (w.kind == 0) tma_ld2_both_w(sbase + sl * SLOT, m, ks * 64, c1, bar, bytes);
            else tma_ld2_both_hint_w(sbase + sl * SLOT, m, 0, c1, bar, bytes, pol_stream);
          } else if (!PAIR && w.kind == 0) tma_ld2_w(sbase + sl * SLOT, m, ks * 64, c1, bar, bytes);
          else tma_ld2_hint_w(sbase + sl * SLOT, m, 0, c1, bar, bytes, pol_stream);
          if (w.kind != 0) c1 += SQ;
          if (i == 0 && (PF_MASK >> ks & 1) && (ks == 2 || cta < PF_CTA))
            asm volatile(ELECT "cp.async.bulk.prefetch.tensor.4d.L2.global.L2::cache_hint [%0, {0, 0, 0, %1}], %2;\n}"
                         ::"l"(&P.kv[hi][0]), "r"(d * (SK / 8) + 8 * __popc(PF_MASK & ((1 << ks) - 1))), "l"(pol_stream) : "memory");
          r.next(); r.next_if(!hi && !bo); r.next_if(!hi && !bo);
          r.xp ^= 1 << b;
        }
        r.xp ^= 3;
        if (w.kind == 0) {
          m = &P.kv[hi][w.beta >> 4];
          c1 = (d & 511) * (SK / 8);
          for (int j = 0; j < 16; j++) {
            if (hi) r.next();
            const uint32_t bar = sbase + BAR_FULL + r.slot * 8;
            const bool tight = i == 0 && j < KV_WIN_TILES + ((KV_WIN_RAMP * cta) >> 5);
            {
              const int s2 = (int)r.slot - (tight ? 2 : KV_WIN_D);
              mbar_wait_w(sbase + BAR_FULL + (s2 < 0 ? s2 + NS : s2) * 8, s2 < 0 ? r.phase : r.phase ^ 1);
            }
            if (j == 15 && hi) mbar_wait_w(sbase + BAR_DESC, i & 1);
            mbar_wait_w(sbase + BAR_EMPTY + r.slot * 8, r.phase);
            tma_ld_kv_w(sbase + r.slot * SLOT, m, c1, bar, pol_stream);
            if (j == GO_J && !hi) mbar_arrive_warp(sbase + BAR_GO);
            c1 += 8;
            r.next();
            if (!hi) r.next();
          }
        }
        mbar_wait_w(sbase + BAR_DESC, i & 1);
        d = __shfl_sync(0xffffffffu, lds(sbase + DESC_OFF + ((i + 1) & 3) * 4), 0);
      }
    }
  } else {
    Ctx c;
    c.sb = sbase; c.wg = wg; c.warp = warp; c.src = 0; c.mqk = 0; c.mpv = 0; c.lead = lane == 0; c.lane0 = c.lane = lane;
    INIT_DONE();
    if (PAIR && wi < 2 * N_FAST) {
      const uint32_t t = wi & 1, sl = (wi >> 1) * 3 + t * 2, bar = sbase + BAR_FULL + sl * 8, bytes = t ? 96 * 128 : 128 * 128;
      if (t == (cta & 1)) tma_ld2_both_w(sbase + sl * SLOT, &P.x[t][0], (wi >> 1) * 64, (d0 >> 5) * SQ + t * 128, bar, bytes);
      else asm volatile(ELECT "mbarrier.arrive.expect_tx.shared::cta.b64 _, [%0], %1;\n}" ::"r"(bar), "r"(bytes) : "memory");
    }
    if (wg == 0) consumer<0>(c, P.kp); else consumer<1>(c, P.kp);
  }
}

typedef CUresult (*EncodeFn)(CUtensorMap*, CUtensorMapDataType, cuuint32_t, void*, const cuuint64_t*, const cuuint64_t*,
                             const cuuint32_t*, const cuuint32_t*, CUtensorMapInterleave, CUtensorMapSwizzle,
                             CUtensorMapL2promotion, CUtensorMapFloatOOBfill);

void make_map(EncodeFn enc, CUtensorMap* m, const void* ptr, int rank, const cuuint64_t* dims, const cuuint64_t* strides,
              const cuuint32_t* box, CUtensorMapSwizzle swz = CU_TENSOR_MAP_SWIZZLE_128B) {
  cuuint32_t es[5] = {1, 1, 1, 1, 1};
  enc(m, CU_TENSOR_MAP_DATA_TYPE_BFLOAT16, rank, const_cast<void*>(ptr), dims, strides, box, es,
      CU_TENSOR_MAP_INTERLEAVE_NONE, swz, CU_TENSOR_MAP_L2_PROMOTION_NONE,
      CU_TENSOR_MAP_FLOAT_OOB_FILL_NONE);
}

}

extern "C" void kernel_launch(void* const* d_in, const int* in_sizes, int n_in, void* d_out, int out_size) {
  (void)in_sizes; (void)n_in; (void)out_size;
  static EncodeFn enc = nullptr;
  static void* o_ptr = nullptr;
  static int n_sm = 0;
  cudaLaunchAttribute at;
  at.id = cudaLaunchAttributeClusterDimension;
  at.val.clusterDim.x = 2; at.val.clusterDim.y = 1; at.val.clusterDim.z = 1;
  cudaLaunchConfig_t cfg = {};
  cfg.gridDim = dim3(NCTA); cfg.blockDim = dim3(384); cfg.dynamicSmemBytes = SMEM_BYTES; cfg.attrs = &at; cfg.numAttrs = 1;
  if (!enc) {
    void* fn = nullptr;
    cudaDriverEntryPointQueryResult qr;
    cudaGetDriverEntryPoint("cuTensorMapEncodeTiled", &fn, cudaEnableDefault, &qr);
    enc = (EncodeFn)fn;
    cudaGetSymbolAddress(&o_ptr, g_o);
    cudaFuncSetAttribute(mha_fused_kernel<false>, cudaFuncAttributeMaxDynamicSharedMemorySize, SMEM_BYTES);
    cudaFuncSetAttribute(mha_fused_kernel<true>, cudaFuncAttributeMaxDynamicSharedMemorySize, SMEM_BYTES);
    int dev = 0;
    cudaGetDevice(&dev);
    cudaDeviceGetAttribute(&n_sm, cudaDevAttrMultiProcessorCount, dev);
    int n_cl = 0;
    cudaOccupancyMaxActiveClusters(&n_cl, mha_fused_kernel<false>, &cfg);
    if (n_cl * 2 < NCTA && n_sm >= NCTA) n_sm = NCTA - 1;
  }
  Params P;
  for (int br = 0; br < 2; br++) {
    const void* x = d_in[br * 5 + 0]; const void* kc = d_in[br * 5 + 1]; const void* vc = d_in[br * 5 + 2];
    const void* wq = d_in[br * 5 + 3]; const void* wo = d_in[br * 5 + 4];
    { cuuint64_t d[2] = {DM, (cuuint64_t)NB * SQ}, s[1] = {DM * 2}; cuuint32_t b[2] = {64, 128}, b2[2] = {64, 96};
      make_map(enc, &P.x[0][br], x, 2, d, s, b); make_map(enc, &P.x[1][br], x, 2, d, s, b2); }
    { cuuint64_t d[3] = {64, DM, HD / 64}, s[2] = {HD * 2, 128}; cuuint32_t b[3] = {64, 64, 2}; make_map(enc, &P.wq[br], wq, 3, d, s, b); }
    { cuuint64_t d[5] = {DM, 2, 4, 4, HD / 32}, s[4] = {DM * 2, 8 * DM * 2, 2 * DM * 2, 32 * DM * 2}; cuuint32_t b[5] = {64, 2, 4, 4, 2};
      make_map(enc, &P.wo[br], wo, 5, d, s, b); }
    { cuuint64_t d[4] = {64, 8, 2, (cuuint64_t)NB * NH * SK / 8}, s[3] = {DH * 2, 128, DH * 16}; cuuint32_t b[4] = {64, 8, 2, 8};
      make_map(enc, &P.kv[0][br], kc, 4, d, s, b); make_map(enc, &P.kv[1][br], vc, 4, d, s, b); }
    P.kp[br] = (const __nv_bfloat16*)kc; P.vp[br] = (const __nv_bfloat16*)vc;

  }
  { cuuint64_t d[2] = {64, (cuuint64_t)NBETA * 64 * SQ}, s[1] = {128}; cuuint32_t b[2] = {64, 128}, b2[2] = {64, 96};
    make_map(enc, &P.o_ld[0], o_ptr, 2, d, s, b, CU_TENSOR_MAP_SWIZZLE_NONE); make_map(enc, &P.o_ld[1], o_ptr, 2, d, s, b2, CU_TENSOR_MAP_SWIZZLE_NONE); }
  { cuuint64_t d[3] = {64, SQ, O_BLOCKS}, s[2] = {128, SQ * 128}; cuuint32_t b[3] = {64, 64, 2}, b2[3] = {64, 32, 2};
    make_map(enc, &P.o_st[0], o_ptr, 3, d, s, b); make_map(enc, &P.o_st[1], o_ptr, 3, d, s, b2); }
  { cuuint64_t d[3] = {64, (cuuint64_t)NB * SQ, 2 * DM / 64}, s[2] = {2 * DM * 2, 128}; cuuint32_t b[3] = {64, 64, 2}, b2[3] = {64, 32, 2};
    make_map(enc, &P.out_st[0], d_out, 3, d, s, b); make_map(enc, &P.out_st[1], d_out, 3, d, s, b2); }
  if (n_sm >= NCTA) cudaLaunchKernelEx(&cfg, mha_fused_kernel<false>, P);
  else mha_fused_kernel<true><<<n_sm, 384, SMEM_BYTES>>>(P);
}
```
